```python
import torch

def _softmax(x, axis=-1):
    return torch.softmax(x, dim=axis)

def _gelu(x):
    return torch.nn.functional.gelu(x, approximate='tanh')

def _silu(x):
    return torch.nn.functional.silu(x)

def _sigmoid(x):
    return torch.sigmoid(x)

def _layernorm(x, axis=-1, eps=1e-05):
    m = x.mean(dim=axis, keepdim=True)
    v = x.var(dim=axis, keepdim=True, unbiased=False)
    return (x - m) / torch.sqrt(v + eps)

def _scatter_add(tgt, idx, src, axis=0):
    return tgt.clone().index_add_(axis, idx, src)

def _segment_sum(src, seg, n):
    out = torch.zeros((n,) + src.shape[1:], dtype=src.dtype)
    return out.index_add_(0, seg, src)

def _pad(x, pw):
    flat = tuple((v for pair in reversed(pw) for v in pair))
    return torch.nn.functional.pad(x, flat)
kernel_name = 'gated_mix__memory_aug_recurrent_mem_tr__ssm_conv_s4d__prompt'

def setup_inputs():

    _w = lambda a: (lambda t: t.to(torch.bfloat16) if t.is_floating_point() else t)(torch.as_tensor(a))

    def _A_setup():
        B, S, Dm = (1, 2048, 576)
        H, Dh = (32, 128)
        M, seg = (8, 32)
        seg = min(seg, S)
        S = S // seg * seg
        return {'x': _w((lambda *s: torch.randn(*s, dtype=torch.bfloat16) * 0.05)(B, S, Dm)), 'mem0': _w((lambda *s: torch.randn(*s, dtype=torch.bfloat16) * 0.4)(B, M, Dm)), 'Wq': _w((lambda *s: torch.randn(*s, dtype=torch.bfloat16) * 6.4)(Dm, H, Dh) * Dm ** (-0.5)), 'Wk': _w((lambda *s: torch.randn(*s, dtype=torch.bfloat16) * 6.4)(Dm, H, Dh) * Dm ** (-0.5)), 'Wv': _w((lambda *s: torch.randn(*s, dtype=torch.bfloat16) * 0.4)(Dm, H, Dh) * Dm ** (-0.5)), 'Wo': _w((lambda *s: torch.randn(*s, dtype=torch.bfloat16) * 0.4)(H, Dh, Dm) * (H * Dh) ** (-0.5)), 'seg_len': seg}
    _A_in = _A_setup()

    def _B_setup():
        Bsz, L, D, N = (1, 2048, 576, 128)
        return {'u': _w((lambda *s: torch.randn(*s, dtype=torch.bfloat16) * 0.05)(Bsz, L, D)), 'log_A_real': _w((lambda *s: torch.randn(*s, dtype=torch.bfloat16) * 6.4)(D, N) * 0.5), 'A_imag': _w((lambda *s: torch.randn(*s, dtype=torch.bfloat16) * 0.05)(D, N) * 3.14), 'C_real': _w((lambda *s: torch.randn(*s, dtype=torch.bfloat16) * 0.2)(D, N) / N ** 0.5), 'C_imag': _w((lambda *s: torch.randn(*s, dtype=torch.bfloat16) * 0.2)(D, N) / N ** 0.5), 'log_dt': _w((lambda *s: torch.randn(*s, dtype=torch.bfloat16) * 0.05)(D) * 0.5 - 4.0), 'D_skip': _w((lambda *s: torch.randn(*s, dtype=torch.bfloat16) * 0.05)(D))}
    _B_in = _B_setup()
    return {'A_x': _A_in['x'], 'A_mem0': _A_in['mem0'], 'A_Wq': _A_in['Wq'], 'A_Wk': _A_in['Wk'], 'A_Wv': _A_in['Wv'], 'A_Wo': _A_in['Wo'], 'A_seg_len': _A_in['seg_len'], 'B_u': _B_in['u'], 'B_log_A_real': _B_in['log_A_real'], 'B_A_imag': _B_in['A_imag'], 'B_C_real': _B_in['C_real'], 'B_C_imag': _B_in['C_imag'], 'B_log_dt': _B_in['log_dt'], 'B_D_skip': _B_in['D_skip'], 'gate_w': _w((lambda *s: torch.randn(*s, dtype=torch.bfloat16) * 0.05)(576) * 16.0)}

def reference(A_x, A_mem0, A_Wq, A_Wk, A_Wv, A_Wo, A_seg_len, B_u, B_log_A_real, B_A_imag, B_C_real, B_C_imag, B_log_dt, B_D_skip, gate_w):

    def _A_ref(x, mem0, Wq, Wk, Wv, Wo, seg_len):
        B, S, Dm = x.shape
        H, Dh = (Wq.shape[1], Wq.shape[2])
        M = mem0.shape[1]
        scale = Dh ** (-0.5)
        n_seg = S // seg_len
        L = M + seg_len
        idx = torch.arange(L)
        mask = (idx[:, None] < M) | (idx[:, None] >= idx[None, :])
        mem = mem0
        outs = []
        for s in range(n_seg):
            xs = x[:, s * seg_len:(s + 1) * seg_len, :].clone()
            h = torch.concatenate([mem, xs], axis=1)
            q = torch.einsum('btd,dhe->bhte', h, Wq)
            k = torch.einsum('btd,dhe->bhte', h, Wk)
            v = torch.einsum('btd,dhe->bhte', h, Wv)
            scores = torch.einsum('bhqe,bhke->bhqk', q, k) * scale
            scores = torch.where(mask[None, None], scores, -1000000000.0)
            p = _softmax(scores, axis=-1)
            o = torch.einsum('bhqk,bhke->bhqe', p, v)
            o = torch.einsum('bhte,hed->btd', o, Wo)
            mem = o[:, :M, :].clone()
            outs.append(o[:, M:, :])
        return torch.concatenate(outs, axis=1)

    def _B_ref(u, log_A_real, A_imag, C_real, C_imag, log_dt, D_skip):
        L = u.shape[1]
        dt = torch.exp(log_dt)
        A = -torch.exp(log_A_real) + 1j * A_imag
        C = (C_real + 1j * C_imag) * dt[:, None]
        pos = (lambda x, dt: x.to(dt))(torch.arange(L), log_dt.dtype)
        P = torch.exp((A * dt[:, None])[:, :, None] * pos[None, None, :])
        K = 2.0 * torch.einsum('dn,dnl->dl', C, P).real
        L2 = 2 * L
        u_t = (lambda x, *d: x.permute(*d))(u, 0, 2, 1)
        Kf = (lambda x, *a, **k: torch.fft.rfft(x.float(), *a, **k))(K, L2)
        Uf = (lambda x, *a, **k: torch.fft.rfft(x.float(), *a, **k))(u_t, L2)
        y = (lambda x, *a, **k: torch.fft.irfft(x, *a, **k).to(torch.bfloat16))(Uf * Kf[None, :, :], L2)[:, :, :L]
        y = (lambda x, *d: x.permute(*d))(y, 0, 2, 1)
        return y + u * D_skip[None, None, :]
    x = A_x
    g = _sigmoid((x * gate_w).sum(-1, keepdims=True))
    a = _A_ref(x, A_mem0, A_Wq, A_Wk, A_Wv, A_Wo, A_seg_len)
    b = _B_ref(x, B_log_A_real, B_A_imag, B_C_real, B_C_imag, B_log_dt, B_D_skip)
    return g * a + (1 - g) * b
```

```cpp
#include <cuda_runtime.h>
#include <cuda.h>
#include <cuda_bf16.h>
#include <stdint.h>

typedef __nv_bfloat16 bf16;
#define LDV4 "ld.volatile.global.v4.u32 {%0,%1,%2,%3}, [%4];"
#define STV4 "st.volatile.global.v4.u32 [%0], {%1,%2,%3,%4};"
#define STV2 "st.volatile.global.v2.u32 [%0], {%1,%2};"

constexpr int S_LEN = 2048, DM = 576, NH = 32, DH = 128, HD = 4096, MEMT = 8, SEG = 32, NSEG = 64, NST = 128;

__device__ float g_gate[S_LEN];
constexpr int NCTA = NH * 3;
__device__ __align__(1024) unsigned char g_acc[96 * 1024];
__device__ __align__(128) uint2 g_norm[NCTA];
__device__ __align__(128) uint32_t g_rx[NSEG];
__device__ __align__(128) unsigned char g_qkv[NSEG][NH][3][10240];
__device__ __align__(128) bf16 g_ox[S_LEN * HD];
__device__ __align__(128) uint4 g_fp[4][72][7][128];
__device__ unsigned g_flag[NSEG * NH];
__device__ unsigned g_prog[NSEG / 2 * 8];
__device__ unsigned g_gcnt;
__device__ unsigned g_epoch;
__device__ __align__(16) bf16 g_y[DM * S_LEN];

#define TS3(slot) do {} while (0)
#define TS3P(slot) do {} while (0)
#define TSQ(slot) do {} while (0)
#define TS3W(slot) do {} while (0)
#define TSS(row, slot) do {} while (0)
#define TS3C(slot) do {} while (0)
#define TSG(i) do {} while (0)
#define FS(i, dep) do {} while (0)
__device__ __forceinline__ uint32_t smem_u32(const void* p) { return (uint32_t)__cvta_generic_to_shared(p); }
__device__ __forceinline__ float bf16r(float x) { return __bfloat162float(__float2bfloat16_rn(x)); }
__device__ __forceinline__ uint32_t pack_bf16(float lo, float hi) {
    __nv_bfloat162 v = __floats2bfloat162_rn(lo, hi);
    return *reinterpret_cast<uint32_t*>(&v);
}
__device__ __forceinline__ void ldsm_x4(uint32_t (&r)[4], uint32_t addr) {
    asm volatile("ldmatrix.sync.aligned.m8n8.x4.shared.b16 {%0,%1,%2,%3}, [%4];"
                 : "=r"(r[0]), "=r"(r[1]), "=r"(r[2]), "=r"(r[3]) : "r"(addr));
}
__device__ __forceinline__ void ldsm_x4_t(uint32_t (&r)[4], uint32_t addr) {
    asm volatile("ldmatrix.sync.aligned.m8n8.x4.trans.shared.b16 {%0,%1,%2,%3}, [%4];"
                 : "=r"(r[0]), "=r"(r[1]), "=r"(r[2]), "=r"(r[3]) : "r"(addr));
}
__device__ __forceinline__ void mma_bf16(float (&d)[4], const uint32_t (&a)[4], uint32_t b0, uint32_t b1) {
    asm volatile("mma.sync.aligned.m16n8k16.row.col.f32.bf16.bf16.f32 {%0,%1,%2,%3}, {%4,%5,%6,%7}, {%8,%9}, {%0,%1,%2,%3};"
                 : "+f"(d[0]), "+f"(d[1]), "+f"(d[2]), "+f"(d[3])
                 : "r"(a[0]), "r"(a[1]), "r"(a[2]), "r"(a[3]), "r"(b0), "r"(b1));
}
__device__ __forceinline__ uint2 ld_vol_u2(const uint2* p) {
    uint2 v; asm volatile("ld.volatile.global.v2.u32 {%0,%1}, [%2];" : "=r"(v.x), "=r"(v.y) : "l"(p) : "memory"); return v;
}
__device__ __forceinline__ void st_vol_u2(uint2* p, uint2 v) {
    asm volatile(STV2 :: "l"(p), "r"(v.x), "r"(v.y) : "memory");
}
__device__ __forceinline__ unsigned ld_acq(const unsigned* p) {
    unsigned v; asm volatile("ld.acquire.gpu.global.u32 %0, [%1];" : "=r"(v) : "l"(p) : "memory"); return v;
}
#define XK 36
#define RFENCE 0
#define NC1 12
#define NS 6
#define NP 2
#define ST_AT 0
#define XT_AT 0
#define MIMIC 0
#define VX_MODE 3
#define VX_DELAY 100
#define POLL_DELAY 550
constexpr int WO_AFTER = 3;
constexpr int PROMPT = 2;
constexpr unsigned SPIN_LIMIT = 1u << 20;

constexpr int SD_CH = 16;
constexpr int SD_NCTA = DM / SD_CH;
constexpr int SD_USTR = 40 * 72;
constexpr int SD_KLEN = 2048 + 32;
constexpr int SD_TAB = 1024;
constexpr int SD_SMEM = SD_CH * SD_USTR * 2 + 8 * (SD_KLEN * 2 + SD_TAB * 4);

__device__ __forceinline__ uint32_t lds32(uint32_t a) { uint32_t v; asm volatile("ld.shared.u32 %0, [%1];" : "=r"(v) : "r"(a)); return v; }
template <int NT0>
__device__ __forceinline__ void conv_oct(float (&acc)[4][4][4], uint32_t (&Aq)[7][4], uint32_t (&raw)[16], uint32_t kaddr, uint32_t sel, uint32_t uaddr) {
#pragma unroll 1
    for (int k = 8 * NT0; k < 8 * NT0 + 8; k++) {
        uint32_t b[4][2][4];
#pragma unroll
        for (int nt = NT0; nt < 4; nt++) {
            const uint32_t ua = uaddr + (uint32_t)((8 * nt - k) * 144);
            ldsm_x4(b[nt][0], ua);
            ldsm_x4(b[nt][1], ua + 64);
        }
#pragma unroll
        for (int i = 0; i < 3; i++) { Aq[i][0] = Aq[i + 4][0]; Aq[i][1] = Aq[i + 4][1]; Aq[i][2] = Aq[i + 4][2]; Aq[i][3] = Aq[i + 4][3]; }
#pragma unroll
        for (int e = 0; e < 4; e++) {
            const uint32_t a0 = __byte_perm(raw[4 * e], raw[4 * e + 1], sel), a1 = __byte_perm(raw[4 * e + 2], raw[4 * e + 3], sel);
            Aq[3 + e][0] = a0; Aq[3 + e][3] = a0; Aq[3 + e][1] = a1; Aq[3 + e][2] = Aq[2 + e][1];
        }
        if (k + 1 < 32) {
#pragma unroll
            for (int e = 0; e < 4; e++) {
                const uint32_t a = kaddr - 32u * (uint32_t)(4 * (k + 1) + e);
                raw[4 * e] = lds32(a); raw[4 * e + 1] = lds32(a + 4); raw[4 * e + 2] = lds32(a - 16); raw[4 * e + 3] = lds32(a - 12);
            }
        }
#pragma unroll
        for (int nt = NT0; nt < 4; nt++)
#pragma unroll
            for (int kt = 0; kt < 4; kt++)
#pragma unroll
                for (int mt = 0; mt < 4; mt++)
                    mma_bf16(acc[mt][nt], Aq[mt - kt + 3], b[nt][kt >> 1][(kt & 1) * 2], b[nt][kt >> 1][(kt & 1) * 2 + 1]);
    }
}

__device__ __forceinline__ void named_bar(int id, int n) { asm volatile("bar.sync %0, %1;" :: "r"(id), "r"(n) : "memory"); }
__device__ __forceinline__ void cexp_t(float lr, float turns, float& re, float& im) {
    float m;
    asm("ex2.approx.ftz.f32 %0, %1;" : "=f"(m) : "f"(lr));
    const float a = (turns - rintf(turns)) * 6.283185307179586f;
    re = m * __cosf(a); im = m * __sinf(a);
}
__device__ __forceinline__ void csq(float& re, float& im) { const float r = re * re - im * im; im = 2.f * re * im; re = r; }
__device__ __forceinline__ uint32_t tf32r(float v) { return __float_as_uint(v) + 0x1000u; }
__device__ __forceinline__ void kb_mma(float (&d)[4], uint32_t a0, uint32_t a1, uint32_t a2, uint32_t a3, float cr, float ci, float er, float ei) {
    const uint32_t b0 = tf32r(cr * er - ci * ei), b1 = tf32r(-(cr * ei + ci * er));
    asm volatile("mma.sync.aligned.m16n8k8.row.col.f32.tf32.tf32.f32 {%0,%1,%2,%3}, {%4,%5,%6,%7}, {%8,%9}, {%0,%1,%2,%3};"
                 : "+f"(d[0]), "+f"(d[1]), "+f"(d[2]), "+f"(d[3]) : "r"(a0), "r"(a1), "r"(a2), "r"(a3), "r"(b0), "r"(b1));
}
template <int C>
__device__ __forceinline__ void expand_taps(const float* kd, bf16* kr, int l0, int lane) {
    uint32_t w[4];
#pragma unroll
    for (int e = 0; e < 4; e++) {
        float v[2];
#pragma unroll
        for (int k = 0; k < 2; k++) {
            const int l = l0 + 8 * lane + 7 - 2 * e - k;
            const int idx = C == 0 ? l : 128 * C + ((l + (1 << (C > 0 ? C - 1 : 0)) - 1 + ((l >> C) & 1)) >> C);
            v[k] = kd[idx];
        }
        w[e] = pack_bf16(v[0], v[1]);
    }
    *reinterpret_cast<uint4*>(kr + 2040 - l0 - 8 * lane) = make_uint4(w[0], w[1], w[2], w[3]);
}

__device__ __forceinline__ void s4d_phase(unsigned char* smem_raw, const bf16* __restrict__ x, const bf16* __restrict__ logA,
                                          const bf16* __restrict__ Aim, const bf16* __restrict__ Cre, const bf16* __restrict__ Cim,
                                          const bf16* __restrict__ logdt, const bf16* __restrict__ wslice) {
    bf16* u_all = reinterpret_cast<bf16*>(smem_raw);
    bf16* k_all = u_all + SD_CH * SD_USTR;
    float* tab_all = reinterpret_cast<float*>(k_all + 8 * SD_KLEN);
    const int tid = threadIdx.x, warp = tid >> 5, lane = tid & 31;
    const int d0 = blockIdx.x * SD_CH;
    bf16* kr = k_all + warp * SD_KLEN;
    float* tab = tab_all + warp * SD_TAB;
    const int g = lane >> 2, tq = lane & 3;
    for (int i = lane; i < 8 * 72 / 2; i += 32) {
        reinterpret_cast<uint32_t*>(u_all + (2 * warp) * SD_USTR)[i] = 0u;
        reinterpret_cast<uint32_t*>(u_all + (2 * warp + 1) * SD_USTR)[i] = 0u;
    }
    if (lane < 16) reinterpret_cast<uint32_t*>(kr + 2048)[lane] = 0u;
    TS3(20);
#pragma unroll 1
    for (int ch = 0; ch < 2; ch++) {
        const int d = d0 + 2 * warp + ch;
        bf16* us = u_all + (2 * warp + ch) * SD_USTR;
        float k2048 = 0.f;
        {
            const float dt = bf16r(expf(__bfloat162float(logdt[d])));
#pragma unroll
            for (int j = 0; j < 4; j++) {
                const int n = lane + 32 * j;
                const float zl = -bf16r(expf(__bfloat162float(logA[d * NST + n]))) * dt * 1.4426950408889634f;
                const float zt = __bfloat162float(Aim[d * NST + n]) * dt * 0.15915494309189535f;
                const float cr = 2.f * (__bfloat162float(Cre[d * NST + n]) * dt), ci = 2.f * (__bfloat162float(Cim[d * NST + n]) * dt);
                float ar, ai, br, bi, er, ei;
                cexp_t(zl * 8.f, zt * 8.f, ar, ai);
                cexp_t(zl * 128.f, zt * 128.f, br, bi);
                cexp_t(zl * 2048.f, zt * 2048.f, er, ei);
                k2048 += cr * er - ci * ei;
                *reinterpret_cast<float4*>(tab + n * 8) = make_float4(zl, zt, cr, ci);
                *reinterpret_cast<float4*>(tab + n * 8 + 4) = make_float4(ar, ai, br, bi);
            }
#pragma unroll
            for (int o = 16; o; o >>= 1) k2048 += __shfl_xor_sync(0xffffffffu, k2048, o);
        }
        __syncwarp();
        {
            float kc[5][4];
#pragma unroll
            for (int i = 0; i < 5; i++) { kc[i][0] = kc[i][1] = kc[i][2] = kc[i][3] = 0.f; }
            const float gf = (float)g;
#pragma unroll 2
            for (int ks = 0; ks < 32; ks++) {
                const float4 p0 = *reinterpret_cast<const float4*>(tab + (4 * ks + tq) * 8);
                const float4 p1 = *reinterpret_cast<const float4*>(tab + (4 * ks + tq) * 8 + 4);
                float wr[4], wi[4], vr, vi;
                cexp_t(p0.x * gf, p0.y * gf, wr[0], wi[0]);
                vr = wr[0] * p1.x - wi[0] * p1.y; vi = wr[0] * p1.y + wi[0] * p1.x;
#pragma unroll
                for (int c = 1; c < 4; c++) { wr[c] = wr[c - 1]; wi[c] = wi[c - 1]; csq(wr[c], wi[c]); }
                float er = wr[3], ei = wi[3];
                csq(er, ei);
                {
                    const uint32_t a0 = tf32r(wr[0]), a1 = tf32r(vr), a2 = tf32r(wi[0]), a3 = tf32r(vi);
                    kb_mma(kc[0], a0, a1, a2, a3, p0.z, p0.w, er, ei);
                    const float t = er * p1.z - ei * p1.w; ei = er * p1.w + ei * p1.z; er = t;
                    kb_mma(kc[1], a0, a1, a2, a3, p0.z, p0.w, er, ei);
                }
#pragma unroll
                for (int c = 1; c < 4; c++) {
                    csq(vr, vi); csq(er, ei);
                    kb_mma(kc[1 + c], tf32r(wr[c]), tf32r(vr), tf32r(wi[c]), tf32r(vi), p0.z, p0.w, er, ei);
                }
            }
            __syncwarp();
#pragma unroll
            for (int i = 0; i < 5; i++) {
                float* q = tab + 128 * i + 32 * tq + g;
                q[0] = kc[i][0]; q[16] = kc[i][1]; q[8] = kc[i][2]; q[24] = kc[i][3];
            }
            if (lane == 0) tab[640] = k2048;
            __syncwarp();
            expand_taps<0>(tab, kr, 0, lane);
            expand_taps<1>(tab, kr, 256, lane);
            expand_taps<2>(tab, kr, 512, lane);
            expand_taps<2>(tab, kr, 768, lane);
#pragma unroll 1
            for (int i = 0; i < 4; i++) expand_taps<3>(tab, kr, 1024 + 256 * i, lane);
            __syncwarp();
        }
        TS3(21 + 2 * ch);
        if (ch == 0) named_bar(1, 384);
        else {
#pragma unroll
            for (int i = 0; i < 4; i++) asm volatile("prefetch.global.L2 [%0];" :: "l"(wslice + (size_t)((tid & 127) + 128 * i) * DM));
        }
        float acc[4][4][4];
#pragma unroll
        for (int i = 0; i < 4; i++)
#pragma unroll
            for (int j = 0; j < 4; j++) { acc[i][j][0] = acc[i][j][1] = acc[i][j][2] = acc[i][j][3] = 0.f; }
        {
            uint32_t Aq[7][4], raw[16];
#pragma unroll
            for (int i = 0; i < 7; i++) { Aq[i][0] = Aq[i][1] = Aq[i][2] = Aq[i][3] = 0u; }
            const int j0 = 2047 - g + 2 * tq;
            const uint32_t kaddr = smem_u32(kr) + 2u * (uint32_t)(j0 & ~1);
            const uint32_t sel = (j0 & 1) ? 0x5432u : 0x3210u;
            const uint32_t uaddr = smem_u32(us) + (uint32_t)(((lane & 7) + 8) * 144 + (lane >> 3) * 16);
#pragma unroll
            for (int e = 0; e < 4; e++) {
                const uint32_t a = kaddr - 32u * (uint32_t)e;
                raw[4 * e] = lds32(a); raw[4 * e + 1] = lds32(a + 4); raw[4 * e + 2] = lds32(a - 16); raw[4 * e + 3] = lds32(a - 12);
            }
            conv_oct<0>(acc, Aq, raw, kaddr, sel, uaddr);
            conv_oct<1>(acc, Aq, raw, kaddr, sel, uaddr);
            conv_oct<2>(acc, Aq, raw, kaddr, sel, uaddr);
            conv_oct<3>(acc, Aq, raw, kaddr, sel, uaddr);
        }
        __syncwarp();
#pragma unroll
        for (int mt = 0; mt < 4; mt++)
#pragma unroll
            for (int nt = 0; nt < 4; nt++) {
                const int i0 = 8 * nt + 2 * tq, r = 16 * mt + g;
                us[64 * i0 + r] = __float2bfloat16_rn(acc[mt][nt][0]);
                us[64 * (i0 + 1) + r] = __float2bfloat16_rn(acc[mt][nt][1]);
                us[64 * i0 + r + 8] = __float2bfloat16_rn(acc[mt][nt][2]);
                us[64 * (i0 + 1) + r + 8] = __float2bfloat16_rn(acc[mt][nt][3]);
            }
        __syncwarp();
#pragma unroll
        for (int i = 0; i < 8; i++)
            *reinterpret_cast<uint4*>(g_y + (size_t)d * S_LEN + (lane + 32 * i) * 8) = *reinterpret_cast<const uint4*>(us + (lane + 32 * i) * 8);
        TS3(22 + 2 * ch);
    }
}
__device__ __forceinline__ void s4d_stage_u(unsigned char* smem_raw, const bf16* __restrict__ x, int pt) {
    bf16* u_all = reinterpret_cast<bf16*>(smem_raw);
    const int d0 = blockIdx.x * SD_CH;
#pragma unroll 1
    for (int b = 0; b < 4; b++) {
        uint4 v[8];
#pragma unroll
        for (int i = 0; i < 8; i++) {
            int c = pt + 128 * (8 * b + i);
            v[i] = *reinterpret_cast<const uint4*>(x + (size_t)(c >> 1) * DM + d0 + (c & 1) * 8);
        }
#pragma unroll
        for (int i = 0; i < 8; i++) {
            int c = pt + 128 * (8 * b + i), t = c >> 1;
            bf16* dst = u_all + (c & 1) * 8 * SD_USTR + (8 + (t >> 6)) * 72 + (t & 63);
            const bf16* pv = reinterpret_cast<const bf16*>(&v[i]);
#pragma unroll
            for (int ch = 0; ch < 8; ch++) dst[ch * SD_USTR] = pv[ch];
        }
    }
    asm volatile("bar.arrive 1, 384;" ::: "memory");
}

constexpr int WOC = DM / 3;
constexpr int TBUF = 5 * DH * 16;
constexpr int XBUF = SEG * DM * 2;
constexpr float ATT_SCALE = 0.08838834764831845f;
constexpr int SM_BAR = 0;
constexpr int B_SB = 0, B_VM = 16, B_VX = 32, B_XT = 64, B_W0 = 88, B_W1 = 96, B_WO = 104;
constexpr int SM_SC = 256;
constexpr int SM_F = SM_SC + 1280;
constexpr int SM_VM = SM_F + 2048;
constexpr int SM_S = SM_VM + 2048;
constexpr int SM_O = SM_S + 2560;
constexpr int SM_M = SM_O + 2048;
constexpr int SM_WS = 19456;
constexpr int SM_T = SM_WS + 32768;
constexpr int SM_VX = SM_T + 4 * TBUF;
constexpr int SM_X = SM_VX + 2 * 8192;
constexpr int SM_STWO = SM_X + 2 * XBUF;
constexpr int CH_SMEM = SM_STWO + DH * WOC * 2;
static_assert(SM_M + DM * 16 <= SM_WS && SM_WS + DM * DH * 2 <= SM_STWO && CH_SMEM <= 232448 && SM_X % 1024 == 0, "smem");
__device__ __forceinline__ uint32_t clock32() { uint32_t t; asm volatile("mov.u32 %0, %%clock;" : "=r"(t) :: "memory"); return t; }

__device__ __forceinline__ uint32_t mapa(uint32_t a, uint32_t rank) {
    uint32_t r; asm volatile("mapa.shared::cluster.u32 %0, %1, %2;" : "=r"(r) : "r"(a), "r"(rank)); return r;
}
__device__ __forceinline__ void st_async32(uint32_t addr, uint32_t v, uint32_t mbar) {
    asm volatile("st.async.weak.shared::cluster.mbarrier::complete_tx::bytes.b32 [%0], %1, [%2];" :: "r"(addr), "r"(v), "r"(mbar) : "memory");
}
__device__ __forceinline__ void mbar_init(uint32_t bar, uint32_t cnt) {
    asm volatile("mbarrier.init.shared::cta.b64 [%0], %1;" :: "r"(bar), "r"(cnt) : "memory");
}
__device__ __forceinline__ void mbar_expect(uint32_t bar, uint32_t bytes) {
    asm volatile("mbarrier.arrive.expect_tx.shared::cta.b64 _, [%0], %1;" :: "r"(bar), "r"(bytes) : "memory");
}
__device__ __forceinline__ void mbar_wait(uint32_t bar, uint32_t parity) {
    unsigned it = 0;
    while (true) {
        uint32_t ok;
        asm volatile("{\n.reg .pred p;\nmbarrier.try_wait.parity.shared::cta.b64 p, [%1], %2;\nselp.u32 %0, 1, 0, p;\n}"
                     : "=r"(ok) : "r"(bar), "r"(parity) : "memory");
        if (ok || ++it >= SPIN_LIMIT) break;
    }
}
__device__ __forceinline__ void mbar_wait_long(uint32_t bar, uint32_t parity) {
    unsigned it = 0;
    while (true) {
        uint32_t ok;
        asm volatile("{\n.reg .pred p;\nmbarrier.try_wait.parity.shared::cta.b64 p, [%1], %2, %3;\nselp.u32 %0, 1, 0, p;\n}"
                     : "=r"(ok) : "r"(bar), "r"(parity), "r"(20000u) : "memory");
        if (ok || ++it >= SPIN_LIMIT) break;
    }
}
__device__ __forceinline__ uint64_t policy_evict_first() {
    uint64_t pol; asm volatile("createpolicy.fractional.L2::evict_first.b64 %0, 1.0;" : "=l"(pol)); return pol;
}
__device__ __forceinline__ void cluster_sync_all() {
    asm volatile("barrier.cluster.arrive.release.aligned;\nbarrier.cluster.wait.acquire.aligned;" ::: "memory");
}
__device__ __forceinline__ uint4 ld_vol_u4(const uint4* p) {
    uint4 v; asm volatile(LDV4 : "=r"(v.x), "=r"(v.y), "=r"(v.z), "=r"(v.w) : "l"(p) : "memory"); return v;
}
__device__ __forceinline__ void ld_vol_u4_p(uint4& v, const uint4* p, uint32_t pred) {
    asm volatile("{\n.reg .pred p;\nsetp.ne.u32 p, %5, 0;\n@p " LDV4 "\n}"
                 : "+r"(v.x), "+r"(v.y), "+r"(v.z), "+r"(v.w) : "l"(p), "r"(pred) : "memory");
}
__device__ __forceinline__ void st_vol_u4(uint4* p, uint4 v) {
    asm volatile(STV4 :: "l"(p), "r"(v.x), "r"(v.y), "r"(v.z), "r"(v.w) : "memory");
}
__device__ __forceinline__ void mma_bf16_r(float (&d)[4], uint32_t a0, uint32_t a1, uint32_t a2, uint32_t a3, uint32_t b0, uint32_t b1) {
    asm volatile("mma.sync.aligned.m16n8k16.row.col.f32.bf16.bf16.f32 {%0,%1,%2,%3}, {%4,%5,%6,%7}, {%8,%9}, {%0,%1,%2,%3};"
                 : "+f"(d[0]), "+f"(d[1]), "+f"(d[2]), "+f"(d[3])
                 : "r"(a0), "r"(a1), "r"(a2), "r"(a3), "r"(b0), "r"(b1));
}

__device__ __forceinline__ uint64_t smem_desc(uint32_t addr, uint32_t lbo, uint32_t sbo) {
    return (uint64_t)((addr & 0x3FFFF) >> 4) | ((uint64_t)(lbo >> 4) << 16) | ((uint64_t)(sbo >> 4) << 32);
}
__device__ __forceinline__ void wg_fence() { asm volatile("wgmma.fence.sync.aligned;" ::: "memory"); }
__device__ __forceinline__ void wg_commit() { asm volatile("wgmma.commit_group.sync.aligned;" ::: "memory"); }
__device__ __forceinline__ void wg_wait0() { asm volatile("wgmma.wait_group.sync.aligned 0;" ::: "memory"); }
__device__ __forceinline__ void fence_async() { asm volatile("fence.proxy.async.shared::cta;" ::: "memory"); }
__device__ __forceinline__ void wgmma_n32(float (&d)[16], const uint32_t (&a)[4], uint64_t bdesc, int scale_d) {
    asm volatile("{\n.reg .pred p;\nsetp.ne.b32 p, %21, 0;\n"
                 "wgmma.mma_async.sync.aligned.m64n32k16.f32.bf16.bf16 {%0,%1,%2,%3,%4,%5,%6,%7,%8,%9,%10,%11,%12,%13,%14,%15}, {%16,%17,%18,%19}, %20, p, 1, 1, 0;\n}"
                 : "+f"(d[0]), "+f"(d[1]), "+f"(d[2]), "+f"(d[3]), "+f"(d[4]), "+f"(d[5]), "+f"(d[6]), "+f"(d[7]),
                   "+f"(d[8]), "+f"(d[9]), "+f"(d[10]), "+f"(d[11]), "+f"(d[12]), "+f"(d[13]), "+f"(d[14]), "+f"(d[15])
                 : "r"(a[0]), "r"(a[1]), "r"(a[2]), "r"(a[3]), "l"(bdesc), "r"(scale_d));
}

__device__ __forceinline__ void wgmma_n32_ss(float (&d)[16], uint64_t adesc, uint64_t bdesc, int scale_d) {
    asm volatile("{\n.reg .pred p;\nsetp.ne.b32 p, %18, 0;\n"
                 "wgmma.mma_async.sync.aligned.m64n32k16.f32.bf16.bf16 {%0,%1,%2,%3,%4,%5,%6,%7,%8,%9,%10,%11,%12,%13,%14,%15}, %16, %17, p, 1, 1, 1, 0;\n}"
                 : "+f"(d[0]), "+f"(d[1]), "+f"(d[2]), "+f"(d[3]), "+f"(d[4]), "+f"(d[5]), "+f"(d[6]), "+f"(d[7]),
                   "+f"(d[8]), "+f"(d[9]), "+f"(d[10]), "+f"(d[11]), "+f"(d[12]), "+f"(d[13]), "+f"(d[14]), "+f"(d[15])
                 : "l"(adesc), "l"(bdesc), "r"(scale_d));
}

__device__ __forceinline__ void bulk_g2s(uint32_t dst, const void* src, uint32_t bytes, uint32_t mbar) {
    asm volatile("cp.async.bulk.shared::cluster.global.mbarrier::complete_tx::bytes [%0], [%1], %2, [%3];"
                 :: "r"(dst), "l"(src), "r"(bytes), "r"(mbar) : "memory");
}
__device__ __forceinline__ void bulk_g2s_h(uint32_t dst, const void* src, uint32_t bytes, uint32_t mbar, uint64_t pol) {
    asm volatile("cp.async.bulk.shared::cluster.global.mbarrier::complete_tx::bytes.L2::cache_hint [%0], [%1], %2, [%3], %4;"
                 :: "r"(dst), "l"(src), "r"(bytes), "r"(mbar), "l"(pol) : "memory");
}
__device__ __forceinline__ void tma_x(uint32_t dst, const CUtensorMap* tm, int seg, int part, uint32_t mbar) {
    asm volatile("cp.async.bulk.tensor.3d.shared::cluster.global.tile.mbarrier::complete_tx::bytes [%0], [%1, {%2, %3, %4}], [%5];"
                 :: "r"(dst + part * 12288), "l"(tm), "r"(0), "r"(seg * SEG), "r"(part * 3), "r"(mbar) : "memory");
}
__device__ __forceinline__ void tma_x_mc(uint32_t dst, const CUtensorMap* tm, int seg, int part, uint32_t mbar) {
    asm volatile("cp.async.bulk.tensor.3d.shared::cluster.global.tile.mbarrier::complete_tx::bytes.multicast::cluster [%0], [%1, {%2, %3, %4}], [%5], %6;"
                 :: "r"(dst + part * 12288), "l"(tm), "r"(0), "r"(seg * SEG), "r"(part * 3), "r"(mbar), "h"((unsigned short)7) : "memory");
}
__device__ __forceinline__ void bulk_s2s(uint32_t dst, uint32_t src, uint32_t bytes, uint32_t mbar) {
    asm volatile("cp.async.bulk.shared::cluster.shared::cta.mbarrier::complete_tx::bytes [%0], [%1], %2, [%3];"
                 :: "r"(dst), "r"(src), "r"(bytes), "r"(mbar) : "memory");
}
__device__ __forceinline__ void wgmma_n40_ss(float (&d)[20], uint64_t adesc, uint64_t bdesc, int scale_d) {
    asm volatile("{\n.reg .pred p;\nsetp.ne.b32 p, %22, 0;\n"
                 "wgmma.mma_async.sync.aligned.m64n40k16.f32.bf16.bf16 {%0,%1,%2,%3,%4,%5,%6,%7,%8,%9,%10,%11,%12,%13,%14,%15,%16,%17,%18,%19}, %20, %21, p, 1, 1, 1, 1;\n}"
                 : "+f"(d[0]), "+f"(d[1]), "+f"(d[2]), "+f"(d[3]), "+f"(d[4]), "+f"(d[5]), "+f"(d[6]), "+f"(d[7]),
                   "+f"(d[8]), "+f"(d[9]), "+f"(d[10]), "+f"(d[11]), "+f"(d[12]), "+f"(d[13]), "+f"(d[14]), "+f"(d[15]),
                   "+f"(d[16]), "+f"(d[17]), "+f"(d[18]), "+f"(d[19])
                 : "l"(adesc), "l"(bdesc), "r"(scale_d));
}
__device__ __forceinline__ void wgmma_n64_z(float (&d)[32], const uint32_t (&a)[4], uint64_t bdesc) {
    asm volatile("{\n.reg .pred p;\nsetp.ne.b32 p, 0, 0;\n"
                 "wgmma.mma_async.sync.aligned.m64n64k16.f32.bf16.bf16 {%0,%1,%2,%3,%4,%5,%6,%7,%8,%9,%10,%11,%12,%13,%14,%15,%16,%17,%18,%19,%20,%21,%22,%23,%24,%25,%26,%27,%28,%29,%30,%31}, {%32,%33,%34,%35}, %36, p, 1, 1, 0;\n}"
                 : "=f"(d[0]), "=f"(d[1]), "=f"(d[2]), "=f"(d[3]), "=f"(d[4]), "=f"(d[5]), "=f"(d[6]), "=f"(d[7]),
                   "=f"(d[8]), "=f"(d[9]), "=f"(d[10]), "=f"(d[11]), "=f"(d[12]), "=f"(d[13]), "=f"(d[14]), "=f"(d[15]),
                   "=f"(d[16]), "=f"(d[17]), "=f"(d[18]), "=f"(d[19]), "=f"(d[20]), "=f"(d[21]), "=f"(d[22]), "=f"(d[23]),
                   "=f"(d[24]), "=f"(d[25]), "=f"(d[26]), "=f"(d[27]), "=f"(d[28]), "=f"(d[29]), "=f"(d[30]), "=f"(d[31])
                 : "r"(a[0]), "r"(a[1]), "r"(a[2]), "r"(a[3]), "l"(bdesc));
}
__device__ __forceinline__ void wgmma_n64(float (&d)[32], const uint32_t (&a)[4], uint64_t bdesc, int scale_d) {
    asm volatile("{\n.reg .pred p;\nsetp.ne.b32 p, %37, 0;\n"
                 "wgmma.mma_async.sync.aligned.m64n64k16.f32.bf16.bf16 {%0,%1,%2,%3,%4,%5,%6,%7,%8,%9,%10,%11,%12,%13,%14,%15,%16,%17,%18,%19,%20,%21,%22,%23,%24,%25,%26,%27,%28,%29,%30,%31}, {%32,%33,%34,%35}, %36, p, 1, 1, 0;\n}"
                 : "+f"(d[0]), "+f"(d[1]), "+f"(d[2]), "+f"(d[3]), "+f"(d[4]), "+f"(d[5]), "+f"(d[6]), "+f"(d[7]),
                   "+f"(d[8]), "+f"(d[9]), "+f"(d[10]), "+f"(d[11]), "+f"(d[12]), "+f"(d[13]), "+f"(d[14]), "+f"(d[15]),
                   "+f"(d[16]), "+f"(d[17]), "+f"(d[18]), "+f"(d[19]), "+f"(d[20]), "+f"(d[21]), "+f"(d[22]), "+f"(d[23]),
                   "+f"(d[24]), "+f"(d[25]), "+f"(d[26]), "+f"(d[27]), "+f"(d[28]), "+f"(d[29]), "+f"(d[30]), "+f"(d[31])
                 : "r"(a[0]), "r"(a[1]), "r"(a[2]), "r"(a[3]), "l"(bdesc), "r"(scale_d));
}

constexpr int SB_FULL = 0, SB_EMPTY = 64, SB_QKF = 128, SB_VF = 144, SB_QKE = 160, SB_VE = 176, SB_OF = 192, SB_WO = 208;
constexpr int AT_0 = 256, AT_ST = 10240 + 2 * 9216;
constexpr int FS_A = 58368;
constexpr int FS_I = FS_A + 131072;
constexpr int SIDE_SMEM = FS_I + 2 * 18432;
static_assert(SIDE_SMEM <= 232448 && AT_0 + 2 * AT_ST <= FS_A && FS_A + SD_SMEM <= SIDE_SMEM, "smem");

__device__ __forceinline__ void bf16r2(float& a, float& b) {
    uint32_t p = pack_bf16(a, b);
    a = __uint_as_float(p << 16); b = __uint_as_float(p & 0xffff0000u);
}
__device__ __forceinline__ void wg_wait1() { asm volatile("wgmma.wait_group.sync.aligned 1;" ::: "memory"); }
__device__ __forceinline__ void mbar_arrive(uint32_t bar) { asm volatile("mbarrier.arrive.shared::cta.b64 _, [%0];" :: "r"(bar) : "memory"); }
__device__ __forceinline__ void wait_cnt(const unsigned* p, unsigned target) {
    unsigned it = 0;
    while ((int)(ld_acq(p) - target) < 0 && ++it < SPIN_LIMIT) __nanosleep(64);
}
__device__ __forceinline__ void wait_cnt_rlx(const unsigned* p, unsigned target, bool urgent) {
    unsigned it = 0, v;
    while (true) {
        asm volatile("ld.relaxed.gpu.global.u32 %0, [%1];" : "=r"(v) : "l"(p) : "memory");
        if ((int)(v - target) >= 0 || ++it >= SPIN_LIMIT) break;
        if (!urgent) __nanosleep(300);
    }
}

__device__ __forceinline__ void xrow_softmax(float (&sc)[20], uint32_t (&pa)[3][4], int wq, int lane) {
    const int g = lane >> 2, tq = lane & 3;
    float mx0 = -INFINITY;
    const int q0 = MEMT + 8 * wq + g;
#pragma unroll
    for (int j = 0; j < 5; j++) {
        bf16r2(sc[4 * j], sc[4 * j + 1]);
        sc[4 * j] *= ATT_SCALE; sc[4 * j + 1] *= ATT_SCALE;
        bf16r2(sc[4 * j], sc[4 * j + 1]);
#pragma unroll
        for (int c = 0; c < 2; c++) {
            int key = 8 * j + 2 * tq + c;
            if (key > q0) sc[4 * j + c] = -INFINITY;
            mx0 = fmaxf(mx0, sc[4 * j + c]);
        }
    }
    mx0 = fmaxf(mx0, __shfl_xor_sync(0xffffffffu, mx0, 1)); mx0 = fmaxf(mx0, __shfl_xor_sync(0xffffffffu, mx0, 2));
    float sum0 = 0.f;
#pragma unroll
    for (int j = 0; j < 5; j++) {
#pragma unroll
        for (int c = 0; c < 2; c++) {
            float e0 = __expf(sc[4 * j + c] - mx0);
            sc[4 * j + c] = e0;
            sum0 += e0;
        }
    }
    sum0 += __shfl_xor_sync(0xffffffffu, sum0, 1); sum0 += __shfl_xor_sync(0xffffffffu, sum0, 2);
    const float i0 = 1.f / sum0;
#pragma unroll
    for (int ks = 0; ks < 3; ks++) {
        pa[ks][0] = pack_bf16(sc[8 * ks] * i0, sc[8 * ks + 1] * i0);
        pa[ks][1] = 0u;
        pa[ks][2] = ks < 2 ? pack_bf16(sc[8 * ks + 4] * i0, sc[8 * ks + 5] * i0) : 0u;
        pa[ks][3] = 0u;
    }
}

__device__ __forceinline__ void stsm_x4(uint32_t addr, uint32_t r0, uint32_t r1, uint32_t r2, uint32_t r3) {
    asm volatile("stmatrix.sync.aligned.m8n8.x4.shared.b16 [%0], {%1,%2,%3,%4};" :: "r"(addr), "r"(r0), "r"(r1), "r"(r2), "r"(r3) : "memory");
}
__device__ __forceinline__ uint32_t h2_to_bf2(uint32_t h) {
    uint32_t r;
    asm("{\n.reg .f16 l, h;\n.reg .f32 a, b;\nmov.b32 {l, h}, %1;\ncvt.f32.f16 a, l;\ncvt.f32.f16 b, h;\ncvt.rn.bf16x2.f32 %0, b, a;\n}" : "=r"(r) : "r"(h));
    return r;
}
__device__ __forceinline__ uint32_t pack_f16(float lo, float hi) {
    uint32_t r; asm("cvt.rn.f16x2.f32 %0, %1, %2;" : "=r"(r) : "f"(hi), "f"(lo)); return r;
}
__device__ __forceinline__ uint32_t movm(uint32_t v) {
    uint32_t r; asm volatile("movmatrix.sync.aligned.m8n8.trans.b16 %0, %1;" : "=r"(r) : "r"(v)); return r;
}
__device__ __forceinline__ void bar_arrive(int id, int n) { asm volatile("bar.arrive %0, %1;" :: "r"(id), "r"(n) : "memory"); }
__device__ __forceinline__ void lds64(uint32_t& a, uint32_t& b, uint32_t addr) {
    asm volatile("ld.shared.v2.u32 {%0,%1}, [%2];" : "=r"(a), "=r"(b) : "r"(addr) : "memory");
}
__device__ __forceinline__ void lds64f(float& a, float& b, uint32_t addr) {
    asm volatile("ld.shared.v2.f32 {%0,%1}, [%2];" : "=f"(a), "=f"(b) : "r"(addr) : "memory");
}
__device__ __forceinline__ void st_async64(uint32_t addr, uint32_t a, uint32_t b, uint32_t mbar) {
    asm volatile("st.async.weak.shared::cluster.mbarrier::complete_tx::bytes.v2.b32 [%0], {%1,%2}, [%3];" :: "r"(addr), "r"(a), "r"(b), "r"(mbar) : "memory");
}
__device__ __forceinline__ void mma_z(float (&d)[4], const uint32_t (&a)[4], uint32_t b0, uint32_t b1) {
    asm volatile("mma.sync.aligned.m16n8k16.row.col.f32.bf16.bf16.f32 {%0,%1,%2,%3}, {%4,%5,%6,%7}, {%8,%9}, {%10,%10,%10,%10};"
                 : "=f"(d[0]), "=f"(d[1]), "=f"(d[2]), "=f"(d[3])
                 : "r"(a[0]), "r"(a[1]), "r"(a[2]), "r"(a[3]), "r"(b0), "r"(b1), "f"(0.f));
}
__device__ __forceinline__ void mma_k8(float (&d)[4], uint32_t a0, uint32_t a1, uint32_t b) {
    asm volatile("mma.sync.aligned.m16n8k8.row.col.f32.bf16.bf16.f32 {%0,%1,%2,%3}, {%4,%5}, {%6}, {%0,%1,%2,%3};"
                 : "+f"(d[0]), "+f"(d[1]), "+f"(d[2]), "+f"(d[3]) : "r"(a0), "r"(a1), "r"(b));
}
__global__ void __launch_bounds__(512, 1) k_side(const __grid_constant__ CUtensorMap tmo, const bf16* __restrict__ x, const bf16* __restrict__ logA, const bf16* __restrict__ Aim,
                                                 const bf16* __restrict__ Cre, const bf16* __restrict__ Cim, const bf16* __restrict__ logdt,
                                                 const bf16* __restrict__ Wo, const bf16* __restrict__ dskip, const bf16* __restrict__ gw,
                                                 bf16* __restrict__ out) {
    extern __shared__ __align__(1024) unsigned char smem_raw[];
    const uint32_t sbase = smem_u32(smem_raw);
    const int tid = threadIdx.x, warp = __shfl_sync(0xffffffffu, tid >> 5, 0), lane = tid & 31, cta = blockIdx.x;
    const bool sp = cta >= NH;
    if (tid == 0) {
        for (int i = 0; i < 8; i++) { mbar_init(sbase + SB_FULL + 8 * i, 1); mbar_init(sbase + SB_EMPTY + 8 * i, sp ? 4 : 8); }
        for (int i = 0; i < 2; i++) {
            mbar_init(sbase + SB_QKF + 8 * i, 1); mbar_init(sbase + SB_VF + 8 * i, 1); mbar_init(sbase + SB_QKE + 8 * i, 1);
            mbar_init(sbase + SB_VE + 8 * i, 4); mbar_init(sbase + SB_OF + 8 * i, 4);
        }
        mbar_init(sbase + SB_WO, 1);
        asm volatile("fence.mbarrier_init.release.cluster;" ::: "memory");
    }
    TS3(0);
    unsigned ep;
    asm volatile("ld.volatile.global.u32 %0, [%1];" : "=r"(ep) : "l"(&g_epoch) : "memory");
    ep += 1u;
    asm volatile("fence.proxy.async;" ::: "memory");
    __syncthreads();
    if (warp >= 12) {
      asm volatile("setmaxnreg.dec.sync.aligned.u32 40;");
      if (warp == 12 || warp == 15) {
        named_bar(3, 320);
        if (tid == 384) {
            fence_async();
            mbar_expect(sbase + SB_WO, 131072);
#pragma unroll
            for (int i = 0; i < 8; i++)
                asm volatile("cp.async.bulk.tensor.2d.shared::cluster.global.tile.mbarrier::complete_tx::bytes [%0], [%1, {%2, %3}], [%4];"
                             :: "r"(sbase + FS_A + i * 16384), "l"(&tmo), "r"((sp ? 8 : 2 * (cta & 3) + (i >> 2)) * 64),
                                "r"((sp ? 2 * (cta - NH) + (i >> 2) : cta >> 2) * 512 + (i & 3) * 128), "r"(sbase + SB_WO) : "memory");
            TSS(17, 2);
        }
        if (tid == 480) {
            __threadfence();
            asm volatile("red.relaxed.gpu.global.add.u32 [%0], 1;" :: "l"(&g_gcnt) : "memory");
            TSS(17, 3);
        }
        __syncwarp();
        named_bar(7, 320);
        if (lane == 0) {
            const int pi = warp == 12 ? 0 : 1;
            const int kb = sp ? 2 * (cta - NH) + pi : cta >> 2;
            fence_async();
            for (int pr = 0; pr < NSEG / 2; pr++) {
                wait_cnt_rlx(&g_prog[pr * 8 + kb], 8u * ep, pr >= NSEG / 2 - 2);
                if (pr >= 30 && pi == 0) TSS(4 + pr - 30, 0);
                if (pr == 31) TS3P(26);
                if (pr == 30) TS3P(1);
                const int nj = sp ? 4 : 2;
#pragma unroll 1
                for (int j = 0; j < nj; j++) {
                    const int hp = sp ? j : 2 * j + pi, st = sp ? 4 * pi + j : 4 * (pr & 1) + hp;
                    mbar_wait_long(sbase + SB_EMPTY + 8 * st, ((uint32_t)(sp ? pr : pr >> 1) & 1u) ^ 1u);
                    mbar_expect(sbase + SB_FULL + 8 * st, 16384);
                    bulk_g2s(sbase + FS_A + st * 16384, g_ox + ((size_t)(pr * NH + 4 * kb + hp)) * 8192, 16384, sbase + SB_FULL + 8 * st);
                }
            }
        }
        __syncwarp();
      } else if (warp == 13) {
        if (lane == 0 && cta < NH) {
            const uint64_t pol = policy_evict_first();
            for (int seg = 0; seg < NSEG; seg++) {
                const uint32_t st = seg & 1, ph = (uint32_t)(seg >> 1) & 1u, ab = sbase + AT_0 + st * AT_ST;
                wait_cnt_rlx(&g_flag[seg * NH + cta], 3u * ep, seg >= NSEG - 4);
                if (seg >= 60) TSS(seg - 60, 0);
                mbar_wait_long(sbase + SB_QKE + 8 * st, ph ^ 1u);
                if (seg >= 60) TSS(seg - 60, 1);
                mbar_expect(sbase + SB_QKF + 8 * st, 2 * 9216);
                bulk_g2s_h(ab + 10240, &g_qkv[seg][cta][0][1024], 9216, sbase + SB_QKF + 8 * st, pol);
                bulk_g2s_h(ab + 10240 + 9216, &g_qkv[seg][cta][1][1024], 9216, sbase + SB_QKF + 8 * st, pol);
                mbar_wait_long(sbase + SB_VE + 8 * st, ph ^ 1u);
                mbar_expect(sbase + SB_VF + 8 * st, 10240);
                bulk_g2s_h(ab, &g_qkv[seg][cta][2][0], 10240, sbase + SB_VF + 8 * st, pol);
            }
        }
        __syncwarp();
      } else if (warp == 14) {
        if (lane == 0 && cta < NH) {
            for (int seg = 0; seg < NSEG; seg++) {
                const uint32_t st = seg & 1, ab = sbase + AT_0 + st * AT_ST;
                mbar_wait_long(sbase + SB_OF + 8 * st, (uint32_t)(seg >> 1) & 1u);
                if (seg >= 60) TSS(seg - 60, 3);
                unsigned char* dst = reinterpret_cast<unsigned char*>(g_ox) + ((size_t)((seg >> 1) * NH + cta)) * 16384 + (seg & 1) * 4096;
                asm volatile("cp.async.bulk.global.shared::cta.bulk_group [%0], [%1], 4096;" :: "l"(dst), "r"(ab + 12288) : "memory");
                asm volatile("cp.async.bulk.global.shared::cta.bulk_group [%0], [%1], 4096;" :: "l"(dst + 8192), "r"(ab + 16384) : "memory");
                asm volatile("cp.async.bulk.commit_group;" ::: "memory");
                asm volatile("cp.async.bulk.wait_group 0;" ::: "memory");
                asm volatile("red.relaxed.gpu.global.add.u32 [%0], 1;" :: "l"(&g_prog[(seg >> 1) * 8 + (cta >> 2)]) : "memory");
                mbar_arrive(sbase + SB_QKE + 8 * st);
                if (seg >= 60) TSS(seg - 60, 4);
            }
        }
        __syncwarp();
      }
    } else if (warp >= 8) {
        asm volatile("setmaxnreg.dec.sync.aligned.u32 88;");
        s4d_stage_u(smem_raw + FS_A, x, tid - 256);
        {
            uint32_t gwv[9];
#pragma unroll
            for (int i = 0; i < 9; i++) gwv[i] = reinterpret_cast<const uint32_t*>(gw)[lane + 32 * i];
#pragma unroll 3
            for (int i = 0; i < 15; i++) {
                const int tt = 4 * i + warp - 8, t = min(cta * 57 + tt, S_LEN - 1);
                float sm = 0.f;
#pragma unroll
                for (int k = 0; k < 9; k++) {
                    const uint32_t xv = reinterpret_cast<const uint32_t*>(x + t * DM)[lane + 32 * k];
                    float a = __uint_as_float(xv << 16) * __uint_as_float(gwv[k] << 16), b = __uint_as_float(xv & 0xffff0000u) * __uint_as_float(gwv[k] & 0xffff0000u);
                    bf16r2(a, b);
                    sm += a + b;
                }
#pragma unroll
                for (int o = 16; o; o >>= 1) sm += __shfl_xor_sync(0xffffffffu, sm, o);
                if (lane == 0 && tt < 57) g_gate[t] = bf16r(1.f / (1.f + expf(-bf16r(sm))));
            }
#pragma unroll 1
            for (int b4 = 0; b4 < 4; b4++)
#pragma unroll
                for (int i = 0; i < 14; i++) (&g_fp[b4][2 * cta][0][0])[tid - 256 + 128 * i] = make_uint4(0u, 0u, 0u, 0u);
            named_bar(6, 128);
            if (tid == 256) {
                __threadfence();
                asm volatile("red.relaxed.gpu.global.add.u32 [%0], 1;" :: "l"(&g_gcnt) : "memory");
            }
            __syncwarp();
        }
        const int wq = warp - 8;
        for (int seg = 0; seg < (cta < NH ? NSEG : 0); seg++) {
            const uint32_t st = seg & 1, ph = (uint32_t)(seg >> 1) & 1u, ab = sbase + AT_0 + st * AT_ST;
            float sc[20];
            mbar_wait_long(sbase + SB_QKF + 8 * st, ph);
            if (seg >= 60 && tid == 256) TSS(seg - 60, 2);
            {
                const uint64_t da = smem_desc(ab + 10240 + 1024, 128, 1024), db = smem_desc(ab + 10240, 128, 2048);
                wg_fence();
#pragma unroll
                for (int ks = 0; ks < 8; ks++) wgmma_n40_ss(sc, da + (uint64_t)((ks >> 2) * 576 + (ks & 3) * 16), db + (uint64_t)((ks >> 2) * 576 + (ks & 3) * 16), ks > 0);
                wg_commit();
                wg_wait0();
            }
            uint32_t pa[3][4];
            xrow_softmax(sc, pa, wq, lane);
            named_bar(6, 128);
            mbar_wait_long(sbase + SB_VF + 8 * st, ph);
#pragma unroll
            for (int hf = 0; hf < 2; hf++) {
                float o[32];
                const uint64_t dv = smem_desc(ab + hf * 1024, 2048, 128);
                wg_fence();
#pragma unroll
                for (int ks = 0; ks < 3; ks++) { if (ks == 0) wgmma_n64_z(o, pa[0], dv); else wgmma_n64(o, pa[ks], dv + (uint64_t)(ks * 256), 1); }
                wg_commit();
                wg_wait0();
#pragma unroll
                for (int i = 0; i < 2; i++)
                    stsm_x4(ab + 12288 + hf * 4096 + wq * 1024 + i * 512 + lane * 16, pack_bf16(o[16 * i], o[16 * i + 1]), pack_bf16(o[16 * i + 4], o[16 * i + 5]),
                            pack_bf16(o[16 * i + 8], o[16 * i + 9]), pack_bf16(o[16 * i + 12], o[16 * i + 13]));
            }
            if (lane == 0) mbar_arrive(sbase + SB_VE + 8 * st);
            fence_async();
            __syncwarp();
            if (lane == 0) mbar_arrive(sbase + SB_OF + 8 * st);
        }
    } else {
        asm volatile("setmaxnreg.inc.sync.aligned.u32 192;");
        const int wg = warp >> 2, wq = warp & 3;
        const int kb = sp ? 2 * (cta - NH) + wg : cta >> 2, cb = sp ? 8 : 2 * (cta & 3) + wg;
        s4d_phase(smem_raw + FS_A, x, logA, Aim, Cre, Cim, logdt, Wo + (size_t)(kb * 512) * DM + cb * 64);
        TS3(2);
        if (lane == 0) TSS(16, warp);
        named_bar(3, 320);
        if (tid == 0) TSS(17, 0);
        uint32_t wa[32][4];
        mbar_wait_long(sbase + SB_WO, 0);
        if (tid == 0) TSS(17, 1);
        {
            const uint32_t a = sbase + FS_A + wg * 65536 + ((lane >> 4) * 8 + (lane & 7)) * 128 + (((wq * 2 + ((lane >> 3) & 1)) ^ (lane & 7)) << 4);
#pragma unroll
            for (int ks = 0; ks < 32; ks++) ldsm_x4_t(wa[ks], a + ks * 2048);
        }
        named_bar(7, 320);
        TS3(3);
        if (lane == 0) wait_cnt(&g_gcnt, 2 * SD_NCTA * ep);
        __syncwarp();
        if (tid == 0) TSS(17, 4);
        for (int it = 0; it < NSEG / 2 + 2; it++) {
            const int pr = it == NSEG / 2 - 1 ? -1 : (it == NSEG / 2 ? it - 1 : (it > NSEG / 2 ? -1 : it));
            const int pf = it == NSEG / 2 ? -1 : (it > NSEG / 2 ? NSEG / 2 - 1 : it - 1);
            uint32_t t16 = (uint32_t)(wq * 32 + lane) * 16u;
            asm volatile("" : "+r"(t16));
            const int t0 = (pf < 0 ? 0 : pf) * 64 + kb * 8, c0 = cb * 64 + wq * 16;
            const uint32_t xo = (uint32_t)((t0 + ((t16 >> 6) & 7)) * DM + c0) * 2u + ((t16 >> 2) & 12u);
            uint32_t yv[2] = {0u, 0u}, uv[2] = {0u, 0u}, dv[2] = {0u, 0u};
            float gg = 0.f;
            if (pf >= 0) {
                dv[0] = *reinterpret_cast<const uint32_t*>(reinterpret_cast<const unsigned char*>(dskip + c0) + ((t16 >> 2) & 12u));
                dv[1] = *reinterpret_cast<const uint32_t*>(reinterpret_cast<const unsigned char*>(dskip + c0 + 8) + ((t16 >> 2) & 12u));
                const unsigned char* yp = reinterpret_cast<const unsigned char*>(g_y) + ((uint32_t)((c0 + ((t16 >> 6) & 7)) * S_LEN + t0) * 2u + ((t16 >> 2) & 12u));
                yv[0] = __ldcg(reinterpret_cast<const uint32_t*>(yp)); yv[1] = __ldcg(reinterpret_cast<const uint32_t*>(yp + 16 * S_LEN));
                uv[0] = *reinterpret_cast<const uint32_t*>(reinterpret_cast<const unsigned char*>(x) + xo);
                uv[1] = *reinterpret_cast<const uint32_t*>(reinterpret_cast<const unsigned char*>(x) + xo + 16);
                gg = __ldcg(&g_gate[t0 + ((t16 >> 6) & 7)]);
            }
            const unsigned char* src = reinterpret_cast<const unsigned char*>(&g_fp[pf & 3][2 * cta + wg][0][0]) + t16;
            const uint32_t ib = sbase + FS_I + wg * 18432 + t16;
            auto fetch = [&]() {
#pragma unroll
                for (int r = 0; r < 7; r++) asm volatile("cp.async.cg.shared.global [%0], [%1], 16;" :: "r"(ib + r * 2048), "l"(src + r * 2048) : "memory");
            };
            if (pr >= 0) {
                float acc[32];
                const uint32_t st0 = sp ? 4 * wg : 4 * (pr & 1), ph = (uint32_t)(sp ? pr : pr >> 1) & 1u;
                const bool early = pr + 1 < NSEG / 2;
                if (early) {
#pragma unroll
                    for (int j = 0; j < 4; j++) mbar_wait(sbase + SB_FULL + 8 * (st0 + j), ph);
                }
                if (pr + wg > 0) named_bar(4 + wg, 256);
                const uint64_t db = smem_desc(sbase + FS_A + st0 * 16384, 128, 1024);
                TSG(0);
#pragma unroll
                for (int j = 0; j < 4; j++) {
                    if (!early) mbar_wait(sbase + SB_FULL + 8 * (st0 + j), ph);
                    wg_fence();
#pragma unroll
                    for (int ks = 0; ks < 8; ks++) {
                        if ((j | ks) == 0) wgmma_n64_z(acc, wa[0], db);
                        else wgmma_n64(acc, wa[8 * j + ks], db + (uint64_t)(j * 1024 + (ks >> 2) * 512 + (ks & 3) * 16), 1);
                    }
                    wg_commit();
                    if (j == 1 && pf >= 0) fetch();
                    if (j == 3 && pr + wg < NSEG / 2) bar_arrive(4 + (wg ^ 1), 256);
                    if (j > 0) { wg_wait1(); if (lane == 0) mbar_arrive(sbase + SB_EMPTY + 8 * (st0 + j - 1)); }
                }
                wg_wait0();
                if (pr == 31) TS3W(27);
                TSG(3);
                if (lane == 0) mbar_arrive(sbase + SB_EMPTY + 8 * (st0 + 3));
                const uint32_t tag = ((uint32_t)(pr >> 2) & 1u) ^ 1u;
                unsigned char* dst = reinterpret_cast<unsigned char*>(&g_fp[pr & 3][cb < 8 ? cb : 64][kb - 1][0]) + t16;
                const uint32_t dstr = cb < 8 ? 8 * 14336 : 14336;
#pragma unroll
                for (int q = 0; q < 8; q++) {
                    asm volatile("{\n.reg .pred p;\nsetp.ne.s32 p, %5, %6;\n@p st.volatile.global.v4.u32 [%0], {%1,%2,%3,%4};\n@!p st.shared.v4.u32 [%7], {%1,%2,%3,%4};\n}"
                                 :: "l"(dst), "r"((__float_as_uint(acc[4 * q]) & ~1u) | tag), "r"((__float_as_uint(acc[4 * q + 1]) & ~1u) | tag),
                                    "r"((__float_as_uint(acc[4 * q + 2]) & ~1u) | tag), "r"((__float_as_uint(acc[4 * q + 3]) & ~1u) | tag), "r"(q), "r"(kb),
                                    "r"(ib + (7 + (pr & 1)) * 2048) : "memory");
                    dst += q == kb ? dstr + 2048 : dstr;
                }
                if (pr == 31) TS3W(28);
                TSG(4);
            } else if (pf >= 0) fetch();
            if (pf >= 0) {
                const uint32_t tag = ((uint32_t)(pf >> 2) & 1u) ^ 1u;
                uint4 pq[8];
                unsigned n = 0;
                while (true) {
                    asm volatile("cp.async.wait_all;" ::: "memory");
#pragma unroll
                    for (int r = 0; r < 8; r++)
                        asm volatile("ld.shared.v4.u32 {%0,%1,%2,%3}, [%4];" : "=r"(pq[r].x), "=r"(pq[r].y), "=r"(pq[r].z), "=r"(pq[r].w)
                                     : "r"(ib + (r < 7 ? r : 7 + (pf & 1)) * 2048) : "memory");
                    uint32_t any = 0u;
#pragma unroll
                    for (int r = 0; r < 7; r++) {
                        uint32_t c0_, c1_;
                        asm("lop3.b32 %0, %1, %2, %3, 0x7e;" : "=r"(c0_) : "r"(pq[r].x), "r"(pq[r].y), "r"(tag));
                        asm("lop3.b32 %0, %1, %2, %3, 0x7e;" : "=r"(c1_) : "r"(pq[r].z), "r"(pq[r].w), "r"(tag));
                        asm("lop3.b32 %0, %1, %2, %3, 0xfe;" : "=r"(any) : "r"(any), "r"(c0_), "r"(c1_));
                    }
                    if (!__any_sync(0xffffffffu, (any & 1u) != 0u) || ++n >= SPIN_LIMIT) break;
                    if (pf + 1 < NSEG / 2 && n > 1) __nanosleep(100);
                    fetch();
                }
                if (pf == 31) TS3W(29);
                TSG(5);
#define PQS(f) (((__uint_as_float(pq[0].f) + __uint_as_float(pq[1].f)) + (__uint_as_float(pq[2].f) + __uint_as_float(pq[3].f))) + \
                ((__uint_as_float(pq[4].f) + __uint_as_float(pq[5].f)) + (__uint_as_float(pq[6].f) + __uint_as_float(pq[7].f))))
                const uint32_t av[2] = {movm(pack_bf16(PQS(x), PQS(y))), movm(pack_bf16(PQS(z), PQS(w)))};
#undef PQS
                yv[0] = movm(yv[0]); yv[1] = movm(yv[1]);
                const float omg = bf16r(1.f - gg);
#pragma unroll
                for (int j = 0; j < 2; j++) {
                    const float y0 = __uint_as_float(yv[j] << 16), y1 = __uint_as_float(yv[j] & 0xffff0000u);
                    const float u0 = __uint_as_float(uv[j] << 16), u1 = __uint_as_float(uv[j] & 0xffff0000u);
                    const float d0 = __uint_as_float(dv[j] << 16), d1 = __uint_as_float(dv[j] & 0xffff0000u);
                    const float a0 = __uint_as_float(av[j] << 16), a1 = __uint_as_float(av[j] & 0xffff0000u);
                    const float b0 = bf16r(y0 + bf16r(u0 * d0)), b1 = bf16r(y1 + bf16r(u1 * d1));
                    *reinterpret_cast<uint32_t*>(reinterpret_cast<unsigned char*>(out) + xo + 16 * j) =
                        pack_bf16(bf16r(gg * a0) + bf16r(omg * b0), bf16r(gg * a1) + bf16r(omg * b1));
                }
                if (wg == 0 && (pf & 1) == 0) TS3(4 + pf / 2);
                if (pf == 31) TS3W(25);
                TSG(6);
            }
        }
        if (cta == 0 && tid == 0) asm volatile("st.volatile.global.u32 [%0], %1;" :: "l"(&g_epoch), "r"(ep) : "memory");
    }
    asm volatile("griddepcontrol.wait;" ::: "memory");
}

__device__ __forceinline__ uint32_t poll_mem(const uint4* src, uint32_t dst, uint32_t ones) {
    FS(12, 0);
    uint4 v[6];
    uint32_t w[18];
    unsigned it = 0;
#pragma unroll
    for (int j = 0; j < 6; j++) v[j] = ld_vol_u4(src + j * 256);
    while (true) {
#pragma unroll
        for (int j = 0; j < 6; j++) {
            w[3 * j] = h2_to_bf2(v[j].x); w[3 * j + 1] = h2_to_bf2(v[j].y); w[3 * j + 2] = h2_to_bf2(v[j].z);
            if (j == 1) stsm_x4(dst, w[0], w[1], w[2], w[3]);
            if (j == 2) stsm_x4(dst + 512, w[4], w[5], w[6], w[7]);
            if (j == 3) stsm_x4(dst + 1024, w[8], w[9], w[10], w[11]);
            if (j == 4) asm volatile("stmatrix.sync.aligned.m8n8.x2.shared.b16 [%0], {%1,%2};" :: "r"(dst + 1536), "r"(w[12]), "r"(w[13]) : "memory");
            if (j == 5) stsm_x4(dst + 1792, w[14], w[15], w[16], w[17]);
        }
        const uint32_t all = ((v[0].w & v[1].w) & (v[2].w & v[3].w)) & (v[4].w & v[5].w);
        if (!__any_sync(0xffffffffu, (all & 0x5000u) != 0x5000u) || ++it >= SPIN_LIMIT) break;
#pragma unroll
        for (int j = 0; j < 6; j++) ld_vol_u4_p(v[j], src + j * 256, v[j].w ^ 0x5000u);
    }
    FS(13, it);
    bar_arrive(1, 384);
    FS(14, 0);
#pragma unroll
    for (int j = 0; j < 18; j++) asm volatile("" : "+r"(w[j]));
    uint32_t m = 0u;
#pragma unroll
    for (int j = 0; j < 9; j++) m = __vmaxu2(m, __vmaxu2(w[2 * j] & 0x7fff7fffu, w[2 * j + 1] & 0x7fff7fffu));
    return m;
}

__device__ __forceinline__ void score_group(uint32_t qa, const uint32_t (&kf)[2][4], uint32_t d0, uint32_t d1, uint32_t m1, uint32_t d2, uint32_t m2) {
    uint32_t a[2][4];
#pragma unroll
    for (int k2 = 0; k2 < 2; k2++) ldsm_x4_t(a[k2], qa + k2 * 512);
    FS(4, a[1][0]);
    float sc[4][4];
    mma_z(sc[0], a[0], kf[0][0], kf[0][1]);
    mma_z(sc[1], a[0], kf[0][2], kf[0][3]);
    mma_z(sc[2], a[1], kf[1][0], kf[1][1]);
    mma_z(sc[3], a[1], kf[1][2], kf[1][3]);
    const uint32_t v0 = __float_as_uint((sc[0][0] + sc[1][2]) + (sc[2][0] + sc[3][2])), v1 = __float_as_uint((sc[0][1] + sc[1][3]) + (sc[2][1] + sc[3][3]));
    FS(5, v0);
    st_async64(d2, v0, v1, m2);
    st_async64(d1, v0, v1, m1);
    asm volatile("st.shared.v2.u32 [%0], {%1,%2};" :: "r"(d0), "r"(v0), "r"(v1) : "memory");
}
__device__ __forceinline__ void store_tile(int s, int h, int role, uint32_t tile) {
    const uint32_t qoff = role != 2 ? 1024 : 0;
    asm volatile("cp.async.bulk.global.shared::cta.bulk_group.L2::cache_hint [%0], [%1], %2, %3;"
                 :: "l"(&g_qkv[s][h][role][qoff]), "r"(tile + qoff), "r"(10240u - qoff), "l"(policy_evict_first()) : "memory");
    asm volatile("cp.async.bulk.commit_group;" ::: "memory");
}
__device__ __forceinline__ float sumsq8(uint4 v) {
    const uint32_t w[4] = {v.x, v.y, v.z, v.w};
    float t = 0.f;
#pragma unroll
    for (int i = 0; i < 4; i++) {
        const float a = __uint_as_float(w[i] << 16), b = __uint_as_float(w[i] & 0xffff0000u);
        t = fmaf(a, a, t); t = fmaf(b, b, t);
    }
    return t;
}
__device__ __forceinline__ uint32_t w_addr(uint32_t sbase, int warp, int lane) {
    return sbase + SM_WS + (warp >> 2) * 8192 + ((lane & 7) + ((lane >> 4) & 1) * 8) * 128 + ((((warp & 3) * 2 + ((lane >> 3) & 1)) ^ (lane & 7)) << 4);
}
__device__ __forceinline__ void vx_copy(uint32_t sbase, int j, int r) {
    bulk_s2s(mapa(sbase + SM_VX + (j & 1) * 8192, r), sbase + SM_T + (j & 3) * TBUF + DH * 16, 8192, mapa(sbase + B_VX + 8 * (j & 1), r));
}
__device__ __forceinline__ void norms_gather(int lane, float* scs) {
    uint2 v[3];
    uint32_t r[2];
    unsigned it = 0;
    do {
#pragma unroll
        for (int i = 0; i < 3; i++) v[i] = ld_vol_u2(&g_norm[3 * lane + i]);
#pragma unroll
        for (int i = 0; i < 2; i++) asm volatile("ld.volatile.global.u32 %0, [%1];" : "=r"(r[i]) : "l"(&g_rx[lane + 32 * i]) : "memory");
    } while (__any_sync(0xffffffffu, (v[0].x & v[1].x & v[2].x & v[2].y & r[0] & r[1] & 1u) == 0u) && ++it < SPIN_LIMIT);
    float c = sqrtf(__uint_as_float(max(max(v[0].x, v[1].x), v[2].x))) * sqrtf(__uint_as_float(v[2].y));
#pragma unroll
    for (int o = 16; o; o >>= 1) c += __shfl_xor_sync(0xffffffffu, c, o);
    c *= 1.1f;
    scs[16 + lane] = c * sqrtf(__uint_as_float(r[0])); scs[48 + lane] = c * sqrtf(__uint_as_float(r[1]));
    if (lane == 0) scs[1] = c * 24.f;
}

__global__ void __cluster_dims__(3, 1, 1) __launch_bounds__(384, 1)
k_chain(const __grid_constant__ CUtensorMap tmx, const __grid_constant__ CUtensorMap tmq, const __grid_constant__ CUtensorMap tmk,
        const __grid_constant__ CUtensorMap tmv, const __grid_constant__ CUtensorMap tmo, const bf16* __restrict__ mem0, const bf16* __restrict__ xg, const uint32_t ones) {
    extern __shared__ __align__(1024) unsigned char smem_raw[];
    const uint32_t sbase = smem_u32(smem_raw);
    const int cta = blockIdx.x, h = cta / 3, role = cta - 3 * h;
    const int tid = threadIdx.x, warp = __shfl_sync(0xffffffffu, tid >> 5, 0), lane_o = tid & 31;
    TS3C(0);
    asm volatile("griddepcontrol.launch_dependents;" ::: "memory");
    if (tid == 0) {
#pragma unroll
        for (int i = 0; i < 14; i++) mbar_init(sbase + SM_BAR + 8 * i, 1);
        asm volatile("fence.mbarrier_init.release.cluster;" ::: "memory");
        fence_async();
        mbar_expect(sbase + B_W0, DM * DH * 2 / 6 * WO_AFTER);
        mbar_expect(sbase + B_W1, DM * DH * 2 / 6 * (6 - WO_AFTER));
#pragma unroll
        for (int i = 0; i < 18; i++) {
            const CUtensorMap* tw = role == 2 ? &tmv : ((i & 1) ? &tmk : &tmq);
            asm volatile("cp.async.bulk.tensor.2d.shared::cluster.global.tile.mbarrier::complete_tx::bytes [%0], [%1, {%2, %3}], [%4];"
                         :: "r"(sbase + SM_WS + i * 8192), "l"(tw), "r"(h * DH + (role == 2 ? (i & 1) : role) * 64), "r"((i >> 1) * 64),
                            "r"(sbase + (i < 3 * WO_AFTER ? B_W0 : B_W1)) : "memory");
        }
        reinterpret_cast<float*>(smem_raw + SM_SC)[2] = 1.f;
    }
    __syncthreads();
    TS3C(8);
    if (warp < 8) {
        uint32_t wreg[36 - NS][4];
        {
            bf16 mv[18];
            uint4 xv[9];
#pragma unroll
            for (int j = 0; j < 18; j++) mv[j] = mem0[tid + 256 * j];
            if (cta < NSEG) {
#pragma unroll
                for (int k = 0; k < 9; k++) xv[k] = __ldg(reinterpret_cast<const uint4*>(xg + (size_t)(cta * SEG + (tid >> 3)) * DM) + (tid & 7) + 8 * k);
            }
#pragma unroll
            for (int j = 0; j < 18; j++) {
                const int i = tid + 256 * j, tok = i / DM, dcol = i - DM * tok;
                reinterpret_cast<bf16*>(smem_raw + SM_M)[dcol * 8 + tok] = mv[j];
            }
            if (cta < NSEG) {
                float t = 0.f;
#pragma unroll
                for (int k = 0; k < 9; k++) t += sumsq8(xv[k]);
                t += __shfl_xor_sync(0xffffffffu, t, 1); t += __shfl_xor_sync(0xffffffffu, t, 2); t += __shfl_xor_sync(0xffffffffu, t, 4);
                const uint32_t m = __reduce_max_sync(0xffffffffu, __float_as_uint(t));
                if (lane_o == 0) reinterpret_cast<uint32_t*>(smem_raw + SM_SC)[260 + warp] = m;
            }
        }
        {
            const int lane = lane_o;
            const uint32_t a = w_addr(sbase, warp, lane);
            mbar_wait(sbase + B_W0, 0);
            if (tid == 32) {
                mbar_expect(sbase + B_WO, DH * WOC * 2);
#pragma unroll
                for (int i = 0; i < 3; i++)
                    asm volatile("cp.async.bulk.tensor.2d.shared::cluster.global.tile.mbarrier::complete_tx::bytes [%0], [%1, {%2, %3}], [%4];"
                                 :: "r"(sbase + SM_STWO + i * 16384), "l"(&tmo), "r"(role * WOC + i * 64), "r"(h * DH), "r"(sbase + B_WO) : "memory");
            }
            __syncwarp();
            mbar_wait(sbase + B_W1, 0);
            TS3C(2);
#pragma unroll
            for (int ks = NS; ks < 36; ks++) ldsm_x4_t(wreg[ks - NS], a + (ks >> 2) * 16384 + (ks & 3) * 2048);
        }
        named_bar(7, 256);
        asm volatile("barrier.cluster.arrive.relaxed.aligned;" ::: "memory");
        TS3C(3);
        auto xproj1 = [&](float (&acc)[16], int j) {
            const uint32_t dlo = __shfl_sync(0xffffffffu, (uint32_t)smem_desc(sbase + SM_X + (j % 3) * XBUF, 16, 1024), 0);
            wg_fence();
#pragma unroll
            for (int ks = NS; ks < NS + NC1; ks++)
                wgmma_n32(acc, wreg[ks - NS], ((uint64_t)0x40000040u << 32) | (uint64_t)(dlo + (uint32_t)((ks >> 2) * 256 + (ks & 3) * 2)), ks > NS);
            wg_commit();
            wg_wait0();
        };
        auto xproj2 = [&](float (&acc)[16], int j) {
            int lane = lane_o;
            asm volatile("" : "+r"(lane));
            const uint32_t dlo = __shfl_sync(0xffffffffu, (uint32_t)smem_desc(sbase + SM_X + (j % 3) * XBUF, 16, 1024), 0);
            const uint64_t da = smem_desc(sbase + SM_WS + (warp >> 2) * 8192, 1024, 1024) | (1ull << 62);
            wg_fence();
#pragma unroll
            for (int ks = 0; ks < NS; ks++)
                wgmma_n32_ss(acc, da + (uint64_t)((ks >> 2) * 1024 + (ks & 3) * 128), ((uint64_t)0x40000040u << 32) | (uint64_t)(dlo + (uint32_t)((ks >> 2) * 256 + (ks & 3) * 2)), NC1 > 0 || ks > 0);
#pragma unroll
            for (int ks = NS + NC1; ks < XK; ks++)
                wgmma_n32(acc, wreg[ks - NS], ((uint64_t)0x40000040u << 32) | (uint64_t)(dlo + (uint32_t)((ks >> 2) * 256 + (ks & 3) * 2)), 1);
            wg_commit();
            wg_wait0();
            const uint32_t off = sbase + SM_T + (j & 3) * TBUF + (DH + warp * 16 + (lane & 15)) * 16 + (lane >> 4) * (DH * 16);
            stsm_x4(off, pack_bf16(acc[0], acc[1]), pack_bf16(acc[2], acc[3]), pack_bf16(acc[4], acc[5]), pack_bf16(acc[6], acc[7]));
            stsm_x4(off + 2 * DH * 16, pack_bf16(acc[8], acc[9]), pack_bf16(acc[10], acc[11]), pack_bf16(acc[12], acc[13]), pack_bf16(acc[14], acc[15]));
        };
        if (tid == 0) {
            fence_async();
            mbar_expect(sbase + B_XT, XBUF);
            for (int i = 0; i < 3; i++) tma_x(sbase + SM_X, &tmx, 0, i, sbase + B_XT);
            mbar_expect(sbase + B_XT + 8, XBUF);
            for (int i = 0; i < 3; i++) tma_x(sbase + SM_X + XBUF, &tmx, 1, i, sbase + B_XT + 8);
            for (int i = 0; i < 2; i++) {
                mbar_expect(sbase + B_SB + 8 * i, role == 2 ? 2560 : 1280 + 2048);
                if (role != 2) mbar_expect(sbase + B_VX + 8 * i, 8192);
            }
        }
        if (cta < NSEG && warp == 1) {
            const uint32_t mm = __reduce_max_sync(0xffffffffu, reinterpret_cast<uint32_t*>(smem_raw + SM_SC)[260 + (lane_o & 7)]);
            if (lane_o == 0) asm volatile("st.volatile.global.u32 [%0], %1;" :: "l"(&g_rx[cta]), "r"(mm | 1u) : "memory");
        }
        __syncwarp();
        {
            float n[4][4];
#pragma unroll
            for (int i = 0; i < 4; i++) { n[i][0] = n[i][1] = n[i][2] = n[i][3] = 0.f; }
            if (role == 2) {
#pragma unroll
                for (int ks = 0; ks < NS; ks++) {
                    uint32_t w[4];
                    ldsm_x4_t(w, w_addr(sbase, warp, lane_o) + (ks >> 2) * 16384 + (ks & 3) * 2048);
#pragma unroll
                    for (int i = 0; i < 4; i++) mma_k8(n[i], w[i & 2], w[(i & 2) + 1], w[i]);
                }
#pragma unroll
                for (int ks = 0; ks < 36 - NS; ks++)
#pragma unroll
                    for (int i = 0; i < 4; i++) mma_k8(n[i], wreg[ks][i & 2], wreg[ks][(i & 2) + 1], wreg[ks][i]);
            }
            const int g = lane_o >> 2, tq = lane_o & 3;
            float t = (g >> 1) == tq ? ((g & 1) ? (n[0][1] + n[1][3]) + (n[2][1] + n[3][3]) : (n[0][0] + n[1][2]) + (n[2][0] + n[3][2])) : 0.f;
#pragma unroll
            for (int o = 16; o; o >>= 1) t += __shfl_xor_sync(0xffffffffu, t, o);
            if (lane_o == 0) reinterpret_cast<float*>(smem_raw + SM_SC)[8 + warp] = t;
            __syncwarp();
            bar_arrive(8, 384);
        }
        mbar_wait(sbase + B_XT, 0);
        { float acc[16]; xproj1(acc, 0); xproj2(acc, 0); }
        fence_async();
        named_bar(7, 256);
        asm volatile("barrier.cluster.wait.aligned;" ::: "memory");
        asm volatile("barrier.cluster.arrive.relaxed.aligned;" ::: "memory");
        if (tid == 0 && role == 2) {
            bulk_s2s(mapa(sbase + SM_VX, 0), sbase + SM_T + DH * 16, 8192, mapa(sbase + B_VX, 0));
            bulk_s2s(mapa(sbase + SM_VX, 1), sbase + SM_T + DH * 16, 8192, mapa(sbase + B_VX, 1));
        }
        __syncwarp();
        mbar_wait(sbase + B_XT + 8, 0);
        { float acc[16]; xproj1(acc, 1); xproj2(acc, 1); }
        asm volatile("barrier.cluster.wait.aligned;" ::: "memory");
        if (role != 2) bar_arrive(9, 384);
        uint32_t ws[NS][4];
#pragma unroll
        for (int ks = NS - NP; ks < NS; ks++) ldsm_x4_t(ws[ks], w_addr(sbase, warp, lane_o) + (ks >> 2) * 16384 + (ks & 3) * 2048);
        TS3C(4);
        for (int s = 0; s < NSEG; s++) {
            int lane = lane_o;
            asm volatile("" : "+r"(lane));
            uint32_t v0, v1;
            {
#pragma unroll
                for (int ks = 0; ks < NS - NP; ks++) ldsm_x4_t(ws[ks], w_addr(sbase, warp, lane) + (ks >> 2) * 16384 + (ks & 3) * 2048);
                FS(0, ws[0][0]);
                named_bar(1, 384);
                float acc[2][4], minv;
                const uint32_t b_base = sbase + SM_M + lane * 16;
                uint32_t b[3][4];
#pragma unroll
                for (int kk = 0; kk < 3; kk++) ldsm_x4_t(b[kk], b_base + kk * 512);
                FS(1, b[0][0]);
#pragma unroll
                for (int kk = 0; kk < 18; kk++) {
                    if (kk == 0) {
                        mma_z(acc[0], ws[0], b[0][0], b[0][1]);
                        mma_z(acc[1], ws[1], b[0][2], b[0][3]);
                    } else if (2 * kk < NS) {
                        mma_bf16(acc[0], ws[2 * kk < NS ? 2 * kk : 0], b[kk % 3][0], b[kk % 3][1]);
                        mma_bf16(acc[1], ws[2 * kk < NS ? 2 * kk + 1 : 0], b[kk % 3][2], b[kk % 3][3]);
                    } else {
                        mma_bf16(acc[0], wreg[2 * kk >= NS ? 2 * kk - NS : 0], b[kk % 3][0], b[kk % 3][1]);
                        mma_bf16(acc[1], wreg[2 * kk >= NS ? 2 * kk - NS + 1 : 0], b[kk % 3][2], b[kk % 3][3]);
                    }
                    if (kk + 3 < 18) ldsm_x4_t(b[kk % 3], b_base + (kk + 3) * 512);
                    if (kk + 3 == 17) {
                        asm volatile("ld.shared.f32 %0, [%1];" : "=f"(minv) : "r"(sbase + SM_SC + 8) : "memory");
                    }
                }
                v0 = pack_bf16((acc[0][0] + acc[1][0]) * minv, (acc[0][1] + acc[1][1]) * minv);
                v1 = pack_bf16((acc[0][2] + acc[1][2]) * minv, (acc[0][3] + acc[1][3]) * minv);
                FS(2, v0);
            }
            const uint32_t tb = sbase + SM_T + (s & 3) * TBUF;
            if (role == 2 && s + 1 < NSEG) {
                const uint32_t fo = (uint32_t)(warp * 256 + lane * 8);
                const uint32_t rb0 = mapa(sbase, 0), rb1 = mapa(sbase, 1);
                st_async64(rb0 + SM_VM + fo, v0, v1, rb0 + B_SB + 8 * (s & 1));
                st_async64(rb1 + SM_VM + fo, v0, v1, rb1 + B_SB + 8 * (s & 1));
                asm volatile("st.shared.v2.u32 [%0], {%1,%2};" :: "r"(sbase + SM_VM + fo), "r"(v0), "r"(v1) : "memory");
            }
            asm volatile("stmatrix.sync.aligned.m8n8.x2.shared.b16 [%0], {%1,%2};" :: "r"(tb + warp * 256 + (lane & 15) * 16), "r"(v0), "r"(v1) : "memory");
            if (s + 1 < NSEG) {
                if (warp == 7 && role != 2) {
                    const uint32_t d0 = sbase + SM_S + role * 1280 + lane * 8, bo = sbase + B_SB + 8 * (s & 1);
                    const uint32_t d1 = mapa(d0, role ^ 1), m1 = mapa(bo, role ^ 1), d2 = mapa(d0, 2), m2 = mapa(bo, 2);
                    const uint32_t ka = tb + (64 + (lane & 7) + ((lane >> 3) & 1) * 16 + (lane >> 4) * 8) * 16;
                    uint32_t kf[2][4];
                    named_bar(2, 384);
#pragma unroll
                    for (int k2 = 0; k2 < 2; k2++) ldsm_x4_t(kf[k2], ka + k2 * 512);
                    score_group(tb + lane * 16, kf, d0, d1, m1, d2, m2);
                    bar_arrive(6, 160);
                } else bar_arrive(2, 384);
            }
            FS(11, 0);
            __syncwarp();
            if (s + 2 < NSEG) {
                if (warp == 6) mbar_wait(sbase + B_XT + 8 * ((s + 2) % 3), (uint32_t)((s + 2) / 3) & 1u);
                if (role != 2) named_bar(5, 384);
                else {
                    fence_async();
                    named_bar(7, 256);
                }
                float xacc[16];
                if (NC1 > 0) xproj1(xacc, s + 2);
                FS(9, __float_as_uint(xacc[0]));
                if (tid == 0 && role == 2) vx_copy(sbase, s + 1, 0);
                __syncwarp();
                if (role != 2) fence_async();
                FS(14, 0);
                named_bar(4, 384);
                xproj2(xacc, s + 2);
                FS(7, __float_as_uint(xacc[0]));
            }
            if (s >= NSEG - PROMPT) {
                fence_async();
                named_bar(7, 256);
                if (tid == 192) {
                    store_tile(s, h, role, tb);
                    asm volatile("cp.async.bulk.wait_group 0;" ::: "memory");
                    asm volatile("red.relaxed.gpu.global.add.u32 [%0], 1;" :: "l"(&g_flag[s * NH + h]) : "memory");
                }
                __syncwarp();
            }
        }
    } else {
        float* scs = reinterpret_cast<float*>(smem_raw + SM_SC);
        uint32_t wo[3][8][4];
        {
            const int pt = tid - 256, lane = lane_o, wq = warp - 8, g = lane >> 2, tq = lane & 3;
            asm volatile("barrier.cluster.arrive.relaxed.aligned;" ::: "memory");
            if (pt >= 64 && pt < 88) {
                *reinterpret_cast<uint4*>(g_acc + cta * 1024 + (pt - 64) * 16) = make_uint4(0u, 0u, 0u, 0u);
                __threadfence();
            }
            __syncwarp();
            mbar_wait(sbase + B_WO, 0);
            float c0 = 0.f;
#pragma unroll
            for (int t = 0; t < 3; t++) {
                const int T = 3 * wq + t;
                const uint32_t a = sbase + SM_STWO + (T >> 2) * 16384 + ((lane >> 4) * 8 + (lane & 7)) * 128 + ((((T & 3) * 2 + ((lane >> 3) & 1)) ^ (lane & 7)) << 4);
#pragma unroll
                for (int kk = 0; kk < 8; kk++) ldsm_x4_t(wo[t][kk], a + ((2 * wq + kk) & 7) * 2048);
                float n[4][4];
#pragma unroll
                for (int i = 0; i < 4; i++) { n[i][0] = n[i][1] = n[i][2] = n[i][3] = 0.f; }
#pragma unroll
                for (int kk = 0; kk < 8; kk++)
#pragma unroll
                    for (int i = 0; i < 4; i++) mma_k8(n[i], wo[t][kk][i & 2], wo[t][kk][(i & 2) + 1], wo[t][kk][i]);
                if ((g >> 1) == tq) c0 = fmaxf(c0, (g & 1) ? fmaxf(n[0][1] + n[2][1], n[1][3] + n[3][3]) : fmaxf(n[0][0] + n[2][0], n[1][2] + n[3][2]));
            }
            c0 = __uint_as_float(__reduce_max_sync(0xffffffffu, __float_as_uint(c0)));
            if (lane == 0) scs[256 + wq] = c0;
            named_bar(8, 384);
            if (pt == 0) {
                const float a = fmaxf(fmaxf(scs[256], scs[257]), fmaxf(scs[258], scs[259]));
                const float b = ((scs[8] + scs[9]) + (scs[10] + scs[11])) + ((scs[12] + scs[13]) + (scs[14] + scs[15]));
                st_vol_u2(&g_norm[cta], make_uint2(__float_as_uint(a) | 1u, __float_as_uint(b) | 1u));
            }
            if (pt == 32) {
                fence_async();
                mbar_expect(sbase + B_XT + 16, XBUF);
                for (int i = 0; i < 3; i++) tma_x(sbase + SM_X + 2 * XBUF, &tmx, 2, i, sbase + B_XT + 16);
            }
            __syncwarp();
            asm volatile("barrier.cluster.wait.aligned;" ::: "memory");
            asm volatile("barrier.cluster.arrive.relaxed.aligned;" ::: "memory");
            asm volatile("barrier.cluster.wait.aligned;" ::: "memory");
        }
        const int wq = warp - 8, lane = lane_o;
        const uint32_t l8 = __shfl_sync(0xffffffffu, sbase + lane * 8, lane), l16 = __shfl_sync(0xffffffffu, sbase + lane * 16, lane);
        const uint32_t goff = __shfl_sync(0xffffffffu, (lane >> 3) * 1024 + (lane & 7) * 16, lane);
        float minv = 1.f;
        uint32_t mx2 = 0u;
        bar_arrive(1, 384);
#pragma unroll
        for (int j = 0; j < 9; j++) {
            uint32_t w0, w1;
            lds64(w0, w1, l8 + SM_M + wq * 256 + j * 1024);
            mx2 = __vmaxu2(mx2, __vmaxu2(w0 & 0x7fff7fffu, w1 & 0x7fff7fffu));
        }
        if (wq == 1) norms_gather(lane, scs);
        if (role != 2) named_bar(9, 384);
        const uint32_t ka = sbase + SM_T + ((wq + 1) * DH + 64 + (lane & 7) + ((lane >> 3) & 1) * 16 + (lane >> 4) * 8) * 16;
        uint32_t kf[2][4];
#pragma unroll
        for (int k2 = 0; k2 < 2; k2++) ldsm_x4_t(kf[k2], ka + k2 * 512);
        int b3 = 0;
        for (int s = 0; s + 1 < NSEG; s++) {
            const int n3 = b3 == 2 ? 0 : b3 + 1;
            if (lane == 0) {
                if (wq == 1 && s + 3 < NSEG) tma_x_mc(sbase + SM_X + b3 * XBUF, &tmx, s + 3, role, sbase + B_XT + 8 * b3);
                if (wq == 3 && s > 0) {
                    store_tile(s - 1, h, role, sbase + SM_T + ((s - 1) & 3) * TBUF);
                    if (s > 1) {
                        asm volatile("cp.async.bulk.wait_group 1;" ::: "memory");
                        asm volatile("red.relaxed.gpu.global.add.u32 [%0], 1;" :: "l"(&g_flag[(s - 2) * NH + h]) : "memory");
                    }
                }
            }
            __syncwarp();
            if (wq == 2 && s > 1 && lane < 8) {
                *reinterpret_cast<uint4*>(g_acc + n3 * 128 + cta * 1024 + lane * 16) = make_uint4(0u, 0u, 0u, 0u);
            }
            if (s == 1 && tid == 383) {
                st_vol_u2(&g_norm[cta], make_uint2(0u, 0u));
                if (cta < NSEG) asm volatile("st.volatile.global.u32 [%0], %1;" :: "l"(&g_rx[cta]), "r"(0u) : "memory");
            }
            {
                const uint32_t mw = __reduce_max_sync(0xffffffffu, max(mx2 << 16, mx2 & 0xffff0000u));
                if (lane == 0) scs[4 + wq] = __uint_as_float(mw);
            }
            const uint32_t to = SM_T + (s & 3) * TBUF;
            const uint32_t ph = (uint32_t)(s >> 1) & 1u;
            if (role != 2) {
                const uint32_t so = SM_S + role * 1280 + (wq + 1) * 256, bo = sbase + B_SB + 8 * (s & 1);
                const uint32_t d1 = mapa(l8 + so, role ^ 1), m1 = mapa(bo, role ^ 1), d2 = mapa(l8 + so, 2), m2 = mapa(bo, 2);
                mbar_wait(sbase + B_VX + 8 * (s & 1), ph);
                FS(1, 0);
                named_bar(2, 384);
                score_group(l16 + to, kf, l8 + so, d1, m1, d2, m2);
                if (s + 2 < NSEG) bar_arrive(5, 384);
            } else named_bar(2, 384);
            const float4 m4 = *reinterpret_cast<const float4*>(scs + 4);
            const float c24 = scs[1], xb = scs[16 + s];
            unsigned char* dst = (g_acc + b3 * 128 + (role * 32 + wq * 8) * 1024) + goff;
            uint32_t vf[2][2][4], vm[2][2];
            {
                const uint32_t va = sbase + (role == 2 ? to + DH * 16 : SM_VX + (s & 1) * 8192) + (lane >> 4) * 2048 + (32 * wq + (lane & 15)) * 16;
#pragma unroll
                for (int i = 0; i < 4; i++) ldsm_x4(vf[i >> 1][i & 1], va + (i >> 1) * 256 + (i & 1) * 4096);
            }
            float scale;
            {
                const float bound = fmaxf(fmaxf(fmaxf(m4.x, m4.y), fmaxf(m4.z, m4.w)) * minv * c24, xb);
                int e = 141 - (int)((__float_as_uint(bound) >> 23) & 255u);
                e = e > 100 ? 100 : e;
                scale = __uint_as_float((uint32_t)(127 + e) << 23);
                minv = __uint_as_float((uint32_t)(127 - e) << 23);
            }
            FS(7, vf[1][1][0]);
            if (role != 2) named_bar(6, 160);
            if (role == 2) mbar_wait(sbase + B_SB + 8 * (s & 1), ph);
            float sv[5][2];
#pragma unroll
            for (int j = 0; j < 5; j++) lds64f(sv[j][0], sv[j][1], l8 + SM_S + (role & 1) * 1280 + j * 256);
            if (role != 2) mbar_wait(sbase + B_SB + 8 * (s & 1), ph);
            FS(6, 0);
            uint32_t p[5];
            {
                float sr[5][2];
#pragma unroll
                for (int j = 0; j < 5; j++) lds64f(sr[j][0], sr[j][1], l8 + SM_S + ((role & 1) ^ 1) * 1280 + j * 256);
                lds64(vm[0][0], vm[0][1], l8 + SM_VM + wq * 512);
                lds64(vm[1][0], vm[1][1], l8 + SM_VM + wq * 512 + 256);
#pragma unroll
                for (int j = 0; j < 5; j++) {
                    sv[j][0] += sr[j][0]; sv[j][1] += sr[j][1];
                }
                float mx = fmaxf(fmaxf(fmaxf(sv[0][0], sv[0][1]), fmaxf(sv[1][0], sv[1][1])), fmaxf(fmaxf(sv[2][0], sv[2][1]), fmaxf(sv[3][0], sv[3][1])));
                mx = fmaxf(mx, fmaxf(sv[4][0], sv[4][1]));
                mx = fmaxf(mx, __shfl_xor_sync(0xffffffffu, mx, 1));
                mx = fmaxf(mx, __shfl_xor_sync(0xffffffffu, mx, 2));
                constexpr float EC = MIMIC ? 1.4426950408889634f : (float)(1.4426950408889634 * 0.08838834764831845);
#pragma unroll
                for (int jj = 0; jj < 5; jj++) {
                    const int j = (jj + 1) % 5;
                    asm("ex2.approx.ftz.f32 %0, %1;" : "=f"(sv[j][0]) : "f"((sv[j][0] - mx) * EC));
                    asm("ex2.approx.ftz.f32 %0, %1;" : "=f"(sv[j][1]) : "f"((sv[j][1] - mx) * EC));
                    p[j] = pack_bf16(sv[j][0], sv[j][1]);
                }
            }
            FS(0, p[0]);
            uint32_t b[4][4];
            float zs[4];
            {
                float o0[2][4], o1[2][4];
                mma_z(o0[0], vf[0][0], p[1], p[2]);
                mma_z(o0[1], vf[1][0], p[1], p[2]);
                mma_z(o1[0], vf[0][1], p[3], p[4]);
                mma_z(o1[1], vf[1][1], p[3], p[4]);
                mma_k8(o0[0], vm[0][0], vm[0][1], p[0]);
                mma_k8(o0[1], vm[1][0], vm[1][1], p[0]);
                const uint32_t one4[4] = {0x3f803f80u, 0x3f803f80u, 0x3f803f80u, 0x3f803f80u};
                mma_z(zs, one4, p[1], p[2]);
                mma_bf16(zs, one4, p[3], p[4]);
                mma_k8(zs, one4[0], one4[1], p[0]);
                uint32_t ow[4];
#pragma unroll
                for (int m = 0; m < 2; m++) {
                    ow[2 * m] = pack_bf16(o0[m][0] + o1[m][0], o0[m][1] + o1[m][1]);
                    ow[2 * m + 1] = pack_bf16(o0[m][2] + o1[m][2], o0[m][3] + o1[m][3]);
                }
                stsm_x4(l16 + SM_O + wq * 512, ow[0], ow[1], ow[2], ow[3]);
                FS(2, 0);
#pragma unroll
                for (int i = 0; i < 4; i++) b[0][i] = movm(ow[i]);
            }
            float acc[3][2][4];
            named_bar(3, 128);
#pragma unroll
            for (int i = 1; i < 4; i++) ldsm_x4_t(b[i], l16 + SM_O + ((wq + i) & 3) * 512);
#pragma unroll
            for (int t = 0; t < 3; t++) { mma_z(acc[t][0], wo[t][0], b[0][0], b[0][1]); mma_z(acc[t][1], wo[t][1], b[0][2], b[0][3]); }
            float z0, z1;
            asm volatile("rcp.approx.ftz.f32 %0, %1;" : "=f"(z0) : "f"(zs[0]));
            asm volatile("rcp.approx.ftz.f32 %0, %1;" : "=f"(z1) : "f"(zs[1]));
            z0 *= scale; z1 *= scale;
            FS(3, b[1][0]);
#pragma unroll
            for (int i = 1; i < 4; i++)
#pragma unroll
                for (int t = 0; t < 3; t++) { mma_bf16(acc[t][0], wo[t][2 * i], b[i][0], b[i][1]); mma_bf16(acc[t][1], wo[t][2 * i + 1], b[i][2], b[i][3]); }
            {
                uint32_t w[6];
#pragma unroll
                for (int t = 0; t < 3; t++) {
                    w[2 * t] = pack_f16((acc[t][0][0] + acc[t][1][0]) * z0, (acc[t][0][1] + acc[t][1][1]) * z1);
                    w[2 * t + 1] = pack_f16((acc[t][0][2] + acc[t][1][2]) * z0, (acc[t][0][3] + acc[t][1][3]) * z1);
                }
                FS(8, w[5]);
                asm volatile("red.relaxed.gpu.global.add.noftz.v4.f16x2 [%0], {%1,%2,%3,%4};" :: "l"(dst), "r"(w[0]), "r"(w[1]), "r"(w[2]), "r"(0x3c00u) : "memory");
                asm volatile("red.relaxed.gpu.global.add.noftz.v4.f16x2 [%0], {%1,%2,%3,%4};" :: "l"(dst + 4096), "r"(w[3]), "r"(w[4]), "r"(w[5]), "r"(0x3c00u) : "memory");
            }
            FS(9, 0);
            const uint32_t t0 = clock32();
            if (s + 2 < NSEG) bar_arrive(4, 384);
            if (lane == 0) {
                if (wq == 0) scs[2] = minv;
                if (wq == 2 && role == 2 && s + 2 < NSEG) { while (clock32() - t0 < VX_DELAY) {} vx_copy(sbase, s + 1, 1); }
                if (s + 3 < NSEG) {
                    if (wq == 0) mbar_expect(sbase + B_SB + 8 * (s & 1), role == 2 ? 2560 : 1280 + 2048);
                    if (wq == 1) mbar_expect(sbase + B_XT + 8 * b3, XBUF);
                    if (wq == 3 && role != 2) mbar_expect(sbase + B_VX + 8 * (s & 1), 8192);
                }
            }
            __syncwarp();
#pragma unroll
            for (int k2 = 0; k2 < 2; k2++) ldsm_x4_t(kf[k2], ka + ((s + 1) & 3) * TBUF + k2 * 512);
            const uint4* src = reinterpret_cast<const uint4*>((g_acc + b3 * 128 + wq * 24576) + goff);
            while (clock32() - t0 < POLL_DELAY) {}
            mx2 = poll_mem(src, l16 + SM_M + wq * 2304, ones);
            b3 = n3;
        }
        if (ST_AT < 2 && tid == 352) {
            asm volatile("cp.async.bulk.wait_group 0;" ::: "memory");
            asm volatile("red.relaxed.gpu.global.add.u32 [%0], 1;" :: "l"(&g_flag[(NSEG - 3) * NH + h]) : "memory");
        }
    }
    TS3C(1);
    __syncwarp();
    cluster_sync_all();
}

extern "C" void kernel_launch(void* const* d_in, const int* in_sizes, int n_in, void* d_out, int out_size) {
    const bf16* x = (const bf16*)d_in[0];
    const bf16* mem0 = (const bf16*)d_in[1];
    const bf16* Wq = (const bf16*)d_in[2];
    const bf16* Wk = (const bf16*)d_in[3];
    const bf16* Wv = (const bf16*)d_in[4];
    const bf16* Wo = (const bf16*)d_in[5];
    const bf16* logA = (const bf16*)d_in[8];
    const bf16* Aim = (const bf16*)d_in[9];
    const bf16* Cre = (const bf16*)d_in[10];
    const bf16* Cim = (const bf16*)d_in[11];
    const bf16* logdt = (const bf16*)d_in[12];
    const bf16* dskip = (const bf16*)d_in[13];
    const bf16* gw = (const bf16*)d_in[14];
    bf16* out = (bf16*)d_out;
    static bool attr_done = false;
    typedef CUresult (*EncFn)(CUtensorMap*, CUtensorMapDataType, cuuint32_t, void*, const cuuint64_t*, const cuuint64_t*, const cuuint32_t*,
                              const cuuint32_t*, CUtensorMapInterleave, CUtensorMapSwizzle, CUtensorMapL2promotion, CUtensorMapFloatOOBfill);
    static EncFn enc = nullptr;
    if (!attr_done) {
        void* fn = nullptr;
        cudaDriverEntryPointQueryResult qr;
        cudaGetDriverEntryPoint("cuTensorMapEncodeTiled", &fn, cudaEnableDefault, &qr);
        enc = (EncFn)fn;
        cudaFuncSetAttribute(k_chain, cudaFuncAttributeMaxDynamicSharedMemorySize, 232448);
        cudaFuncSetAttribute(k_side, cudaFuncAttributeMaxDynamicSharedMemorySize, SIDE_SMEM);
        attr_done = true;
    }
    CUtensorMap tmx;
    {
        const cuuint64_t dims[3] = {64, (cuuint64_t)S_LEN, 9};
        const cuuint64_t strides[2] = {(cuuint64_t)DM * 2, 128};
        const cuuint32_t box[3] = {64, (cuuint32_t)SEG, 3};
        const cuuint32_t es[3] = {1, 1, 1};
        enc(&tmx, CU_TENSOR_MAP_DATA_TYPE_BFLOAT16, 3, (void*)x, dims, strides, box, es, CU_TENSOR_MAP_INTERLEAVE_NONE,
            CU_TENSOR_MAP_SWIZZLE_128B, CU_TENSOR_MAP_L2_PROMOTION_L2_128B, CU_TENSOR_MAP_FLOAT_OOB_FILL_NONE);
    }
    CUtensorMap tmw[3];
    for (int i = 0; i < 3; i++) {
        const cuuint64_t dims[2] = {(cuuint64_t)HD, (cuuint64_t)DM};
        const cuuint64_t strides[1] = {(cuuint64_t)HD * 2};
        const cuuint32_t box[2] = {64, 64};
        const cuuint32_t es[2] = {1, 1};
        enc(&tmw[i], CU_TENSOR_MAP_DATA_TYPE_BFLOAT16, 2, (void*)(i == 0 ? Wq : (i == 1 ? Wk : Wv)), dims, strides, box, es, CU_TENSOR_MAP_INTERLEAVE_NONE,
            CU_TENSOR_MAP_SWIZZLE_128B, CU_TENSOR_MAP_L2_PROMOTION_L2_256B, CU_TENSOR_MAP_FLOAT_OOB_FILL_NONE);
    }
    CUtensorMap tmo;
    {
        const cuuint64_t dims[2] = {(cuuint64_t)DM, (cuuint64_t)HD};
        const cuuint64_t strides[1] = {(cuuint64_t)DM * 2};
        const cuuint32_t box[2] = {64, 128};
        const cuuint32_t es[2] = {1, 1};
        enc(&tmo, CU_TENSOR_MAP_DATA_TYPE_BFLOAT16, 2, (void*)Wo, dims, strides, box, es, CU_TENSOR_MAP_INTERLEAVE_NONE,
            CU_TENSOR_MAP_SWIZZLE_128B, CU_TENSOR_MAP_L2_PROMOTION_L2_128B, CU_TENSOR_MAP_FLOAT_OOB_FILL_NONE);
    }
    k_chain<<<NCTA, 384, 232448>>>(tmx, tmw[0], tmw[1], tmw[2], tmo, mem0, x, 0xffffffffu);
    {
        cudaLaunchConfig_t cfg = {};
        cfg.gridDim = dim3(SD_NCTA); cfg.blockDim = dim3(512); cfg.dynamicSmemBytes = SIDE_SMEM; cfg.stream = cudaStreamPerThread;
        cudaLaunchAttribute at[1];
        at[0].id = cudaLaunchAttributeProgrammaticStreamSerialization;
        at[0].val.programmaticStreamSerializationAllowed = 1;
        cfg.attrs = at; cfg.numAttrs = 1;
        cudaLaunchKernelEx(&cfg, k_side, tmo, x, logA, Aim, Cre, Cim, logdt, Wo, dskip, gw, out);
    }
}
```

```cpp
#include <cuda_runtime.h>
#include <cuda.h>
#include <cuda_bf16.h>
#include <stdint.h>

typedef __nv_bfloat16 bf16;
#define LDV4 "ld.volatile.global.v4.u32 {%0,%1,%2,%3}, [%4];"
#define STV4 "st.volatile.global.v4.u32 [%0], {%1,%2,%3,%4};"
#define STV2 "st.volatile.global.v2.u32 [%0], {%1,%2};"

constexpr int S_LEN = 2048, DM = 576, NH = 32, DH = 128, HD = 4096, MEMT = 8, SEG = 32, NSEG = 64, NST = 128;

__device__ uint32_t g_gate[S_LEN];
constexpr int NCTA = NH * 3;
__device__ __align__(1024) unsigned char g_acc[96 * 1024];
__device__ __align__(128) uint2 g_norm[NCTA];
__device__ __align__(128) uint32_t g_rx[NSEG];
__device__ __align__(128) unsigned char g_qkv[NSEG][NH][3][10240];
__device__ __align__(128) bf16 g_ox[S_LEN * HD];
__device__ __align__(128) uint4 g_fp[4][72][7][128];
__device__ unsigned g_flag[NSEG * NH];
__device__ unsigned g_prog[NSEG / 2 * 8];
__device__ unsigned g_gcnt;
__device__ unsigned g_epoch;
__device__ __align__(16) bf16 g_y[DM * S_LEN];

#define TS3(slot) do {} while (0)
#define TS3P(slot) do {} while (0)
#define TSQ(slot) do {} while (0)
#define TS3W(slot) do {} while (0)
#define TSS(row, slot) do {} while (0)
#define TS3C(slot) do {} while (0)
#define TSG(i) do {} while (0)
#define FS(i, dep) do {} while (0)
__device__ __forceinline__ uint32_t smem_u32(const void* p) { return (uint32_t)__cvta_generic_to_shared(p); }
__device__ __forceinline__ float bf16r(float x) { return __bfloat162float(__float2bfloat16_rn(x)); }
__device__ __forceinline__ uint32_t pack_bf16(float lo, float hi) {
    __nv_bfloat162 v = __floats2bfloat162_rn(lo, hi);
    return *reinterpret_cast<uint32_t*>(&v);
}
__device__ __forceinline__ void ldsm_x4(uint32_t (&r)[4], uint32_t addr) {
    asm volatile("ldmatrix.sync.aligned.m8n8.x4.shared.b16 {%0,%1,%2,%3}, [%4];"
                 : "=r"(r[0]), "=r"(r[1]), "=r"(r[2]), "=r"(r[3]) : "r"(addr));
}
__device__ __forceinline__ void ldsm_x4_t(uint32_t (&r)[4], uint32_t addr) {
    asm volatile("ldmatrix.sync.aligned.m8n8.x4.trans.shared.b16 {%0,%1,%2,%3}, [%4];"
                 : "=r"(r[0]), "=r"(r[1]), "=r"(r[2]), "=r"(r[3]) : "r"(addr));
}
__device__ __forceinline__ void mma_bf16(float (&d)[4], const uint32_t (&a)[4], uint32_t b0, uint32_t b1) {
    asm volatile("mma.sync.aligned.m16n8k16.row.col.f32.bf16.bf16.f32 {%0,%1,%2,%3}, {%4,%5,%6,%7}, {%8,%9}, {%0,%1,%2,%3};"
                 : "+f"(d[0]), "+f"(d[1]), "+f"(d[2]), "+f"(d[3])
                 : "r"(a[0]), "r"(a[1]), "r"(a[2]), "r"(a[3]), "r"(b0), "r"(b1));
}
__device__ __forceinline__ uint2 ld_vol_u2(const uint2* p) {
    uint2 v; asm volatile("ld.volatile.global.v2.u32 {%0,%1}, [%2];" : "=r"(v.x), "=r"(v.y) : "l"(p) : "memory"); return v;
}
__device__ __forceinline__ void st_vol_u2(uint2* p, uint2 v) {
    asm volatile(STV2 :: "l"(p), "r"(v.x), "r"(v.y) : "memory");
}
__device__ __forceinline__ unsigned ld_acq(const unsigned* p) {
    unsigned v; asm volatile("ld.acquire.gpu.global.u32 %0, [%1];" : "=r"(v) : "l"(p) : "memory"); return v;
}
#define XK 36
#define RFENCE 0
#define NC1 12
#define NS 6
#define NP 2
#define ST_AT 0
#define XT_AT 0
#define MIMIC 0
#define VX_MODE 3
#define VX_DELAY 100
#define POLL_DELAY 550
constexpr int WO_AFTER = 3;
constexpr int PROMPT = 2;
constexpr unsigned SPIN_LIMIT = 1u << 20;

constexpr int SD_CH = 16;
constexpr int SD_NCTA = DM / SD_CH;
constexpr int SD_USTR = 40 * 72;
constexpr int SD_KLEN = 2048 + 32;
constexpr int SD_TAB = 1024;
constexpr int SD_SMEM = SD_CH * SD_USTR * 2 + 8 * (SD_KLEN * 2 + SD_TAB * 4);

__device__ __forceinline__ uint32_t lds32(uint32_t a) { uint32_t v; asm volatile("ld.shared.u32 %0, [%1];" : "=r"(v) : "r"(a)); return v; }
template <int NT0>
__device__ __forceinline__ void conv_oct(float (&acc)[4][4][4], uint32_t (&Aq)[7][4], uint32_t (&raw)[16], uint32_t kaddr, uint32_t sel, uint32_t uaddr) {
#pragma unroll 1
    for (int k = 8 * NT0; k < 8 * NT0 + 8; k++) {
        uint32_t b[4][2][4];
#pragma unroll
        for (int nt = NT0; nt < 4; nt++) {
            const uint32_t ua = uaddr + (uint32_t)((8 * nt - k) * 144);
            ldsm_x4(b[nt][0], ua);
            ldsm_x4(b[nt][1], ua + 64);
        }
#pragma unroll
        for (int i = 0; i < 3; i++) { Aq[i][0] = Aq[i + 4][0]; Aq[i][1] = Aq[i + 4][1]; Aq[i][2] = Aq[i + 4][2]; Aq[i][3] = Aq[i + 4][3]; }
#pragma unroll
        for (int e = 0; e < 4; e++) {
            const uint32_t a0 = __byte_perm(raw[4 * e], raw[4 * e + 1], sel), a1 = __byte_perm(raw[4 * e + 2], raw[4 * e + 3], sel);
            Aq[3 + e][0] = a0; Aq[3 + e][3] = a0; Aq[3 + e][1] = a1; Aq[3 + e][2] = Aq[2 + e][1];
        }
        if (k + 1 < 32) {
#pragma unroll
            for (int e = 0; e < 4; e++) {
                const uint32_t a = kaddr - 32u * (uint32_t)(4 * (k + 1) + e);
                raw[4 * e] = lds32(a); raw[4 * e + 1] = lds32(a + 4); raw[4 * e + 2] = lds32(a - 16); raw[4 * e + 3] = lds32(a - 12);
            }
        }
#pragma unroll
        for (int nt = NT0; nt < 4; nt++)
#pragma unroll
            for (int kt = 0; kt < 4; kt++)
#pragma unroll
                for (int mt = 0; mt < 4; mt++)
                    mma_bf16(acc[mt][nt], Aq[mt - kt + 3], b[nt][kt >> 1][(kt & 1) * 2], b[nt][kt >> 1][(kt & 1) * 2 + 1]);
    }
}

__device__ __forceinline__ void named_bar(int id, int n) { asm volatile("bar.sync %0, %1;" :: "r"(id), "r"(n) : "memory"); }
__device__ __forceinline__ void cexp_t(float lr, float turns, float& re, float& im) {
    float m;
    asm("ex2.approx.ftz.f32 %0, %1;" : "=f"(m) : "f"(lr));
    const float a = (turns - rintf(turns)) * 6.283185307179586f;
    re = m * __cosf(a); im = m * __sinf(a);
}
__device__ __forceinline__ void csq(float& re, float& im) { const float r = re * re - im * im; im = 2.f * re * im; re = r; }
__device__ __forceinline__ uint32_t tf32r(float v) { return __float_as_uint(v) + 0x1000u; }
__device__ __forceinline__ void kb_mma(float (&d)[4], uint32_t a0, uint32_t a1, uint32_t a2, uint32_t a3, float cr, float ci, float er, float ei) {
    const uint32_t b0 = tf32r(cr * er - ci * ei), b1 = tf32r(-(cr * ei + ci * er));
    asm volatile("mma.sync.aligned.m16n8k8.row.col.f32.tf32.tf32.f32 {%0,%1,%2,%3}, {%4,%5,%6,%7}, {%8,%9}, {%0,%1,%2,%3};"
                 : "+f"(d[0]), "+f"(d[1]), "+f"(d[2]), "+f"(d[3]) : "r"(a0), "r"(a1), "r"(a2), "r"(a3), "r"(b0), "r"(b1));
}
template <int C>
__device__ __forceinline__ void expand_taps(const float* kd, bf16* kr, int l0, int lane) {
    uint32_t w[4];
#pragma unroll
    for (int e = 0; e < 4; e++) {
        float v[2];
#pragma unroll
        for (int k = 0; k < 2; k++) {
            const int l = l0 + 8 * lane + 7 - 2 * e - k;
            const int idx = C == 0 ? l : 128 * C + ((l + (1 << (C > 0 ? C - 1 : 0)) - 1 + ((l >> C) & 1)) >> C);
            v[k] = kd[idx];
        }
        w[e] = pack_bf16(v[0], v[1]);
    }
    *reinterpret_cast<uint4*>(kr + 2040 - l0 - 8 * lane) = make_uint4(w[0], w[1], w[2], w[3]);
}

__device__ __forceinline__ void s4d_phase(unsigned char* smem_raw, const bf16* __restrict__ x, const bf16* __restrict__ logA,
                                          const bf16* __restrict__ Aim, const bf16* __restrict__ Cre, const bf16* __restrict__ Cim,
                                          const bf16* __restrict__ logdt, const bf16* __restrict__ wslice) {
    bf16* u_all = reinterpret_cast<bf16*>(smem_raw);
    bf16* k_all = u_all + SD_CH * SD_USTR;
    float* tab_all = reinterpret_cast<float*>(k_all + 8 * SD_KLEN);
    const int tid = threadIdx.x, warp = tid >> 5, lane = tid & 31;
    const int d0 = blockIdx.x * SD_CH;
    bf16* kr = k_all + warp * SD_KLEN;
    float* tab = tab_all + warp * SD_TAB;
    const int g = lane >> 2, tq = lane & 3;
    for (int i = lane; i < 8 * 72 / 2; i += 32) {
        reinterpret_cast<uint32_t*>(u_all + (2 * warp) * SD_USTR)[i] = 0u;
        reinterpret_cast<uint32_t*>(u_all + (2 * warp + 1) * SD_USTR)[i] = 0u;
    }
    if (lane < 16) reinterpret_cast<uint32_t*>(kr + 2048)[lane] = 0u;
    TS3(20);
#pragma unroll 1
    for (int op = 0; op < 4; op++) {
        const bool build = op == 0 || op == (warp < 4 ? 2 : 1);
        const int ch = build ? (op > 0) : (op == 3);
        const int d = d0 + 2 * warp + ch;
        bf16* us = u_all + (2 * warp + ch) * SD_USTR;
        if (build) {
        float k2048 = 0.f;
        {
            const float dt = bf16r(expf(__bfloat162float(logdt[d])));
#pragma unroll
            for (int j = 0; j < 4; j++) {
                const int n = lane + 32 * j;
                const float zl = -bf16r(expf(__bfloat162float(logA[d * NST + n]))) * dt * 1.4426950408889634f;
                const float zt = __bfloat162float(Aim[d * NST + n]) * dt * 0.15915494309189535f;
                const float cr = 2.f * (__bfloat162float(Cre[d * NST + n]) * dt), ci = 2.f * (__bfloat162float(Cim[d * NST + n]) * dt);
                float ar, ai, br, bi, er, ei;
                cexp_t(zl * 8.f, zt * 8.f, ar, ai);
                cexp_t(zl * 128.f, zt * 128.f, br, bi);
                cexp_t(zl * 2048.f, zt * 2048.f, er, ei);
                k2048 += cr * er - ci * ei;
                *reinterpret_cast<float4*>(tab + n * 8) = make_float4(zl, zt, cr, ci);
                *reinterpret_cast<float4*>(tab + n * 8 + 4) = make_float4(ar, ai, br, bi);
            }
#pragma unroll
            for (int o = 16; o; o >>= 1) k2048 += __shfl_xor_sync(0xffffffffu, k2048, o);
        }
        __syncwarp();
        {
            float kc[5][4];
#pragma unroll
            for (int i = 0; i < 5; i++) { kc[i][0] = kc[i][1] = kc[i][2] = kc[i][3] = 0.f; }
            const float gf = (float)g;
#pragma unroll 2
            for (int ks = 0; ks < 32; ks++) {
                const float4 p0 = *reinterpret_cast<const float4*>(tab + (4 * ks + tq) * 8);
                const float4 p1 = *reinterpret_cast<const float4*>(tab + (4 * ks + tq) * 8 + 4);
                float wr[4], wi[4], vr, vi;
                cexp_t(p0.x * gf, p0.y * gf, wr[0], wi[0]);
                vr = wr[0] * p1.x - wi[0] * p1.y; vi = wr[0] * p1.y + wi[0] * p1.x;
#pragma unroll
                for (int c = 1; c < 4; c++) { wr[c] = wr[c - 1]; wi[c] = wi[c - 1]; csq(wr[c], wi[c]); }
                float er = wr[3], ei = wi[3];
                csq(er, ei);
                {
                    const uint32_t a0 = tf32r(wr[0]), a1 = tf32r(vr), a2 = tf32r(wi[0]), a3 = tf32r(vi);
                    kb_mma(kc[0], a0, a1, a2, a3, p0.z, p0.w, er, ei);
                    const float t = er * p1.z - ei * p1.w; ei = er * p1.w + ei * p1.z; er = t;
                    kb_mma(kc[1], a0, a1, a2, a3, p0.z, p0.w, er, ei);
                }
#pragma unroll
                for (int c = 1; c < 4; c++) {
                    csq(vr, vi); csq(er, ei);
                    kb_mma(kc[1 + c], tf32r(wr[c]), tf32r(vr), tf32r(wi[c]), tf32r(vi), p0.z, p0.w, er, ei);
                }
            }
            __syncwarp();
#pragma unroll
            for (int i = 0; i < 5; i++) {
                float* q = tab + 128 * i + 32 * tq + g;
                q[0] = kc[i][0]; q[16] = kc[i][1]; q[8] = kc[i][2]; q[24] = kc[i][3];
            }
            if (lane == 0) tab[640] = k2048;
            __syncwarp();
        }
        } else {
        if (ch == 0) named_bar(warp < 4 ? 1 : 2, 256);
        else {
#pragma unroll
            for (int i = 0; i < 4; i++) asm volatile("prefetch.global.L2 [%0];" :: "l"(wslice + (size_t)((tid & 127) + 128 * i) * DM));
        }
        float acc[4][4][4];
#pragma unroll
        for (int i = 0; i < 4; i++)
#pragma unroll
            for (int j = 0; j < 4; j++) { acc[i][j][0] = acc[i][j][1] = acc[i][j][2] = acc[i][j][3] = 0.f; }
        {
            uint32_t Aq[7][4], raw[16];
#pragma unroll
            for (int i = 0; i < 7; i++) { Aq[i][0] = Aq[i][1] = Aq[i][2] = Aq[i][3] = 0u; }
            const int j0 = 2047 - g + 2 * tq;
            const uint32_t kaddr = smem_u32(kr) + 2u * (uint32_t)(j0 & ~1);
            const uint32_t sel = (j0 & 1) ? 0x5432u : 0x3210u;
            const uint32_t uaddr = smem_u32(us) + (uint32_t)(((lane & 7) + 8) * 144 + (lane >> 3) * 16);
#pragma unroll
            for (int e = 0; e < 4; e++) {
                const uint32_t a = kaddr - 32u * (uint32_t)e;
                raw[4 * e] = lds32(a); raw[4 * e + 1] = lds32(a + 4); raw[4 * e + 2] = lds32(a - 16); raw[4 * e + 3] = lds32(a - 12);
            }
            conv_oct<0>(acc, Aq, raw, kaddr, sel, uaddr);
            conv_oct<1>(acc, Aq, raw, kaddr, sel, uaddr);
            conv_oct<2>(acc, Aq, raw, kaddr, sel, uaddr);
            conv_oct<3>(acc, Aq, raw, kaddr, sel, uaddr);
        }
        __syncwarp();
#pragma unroll
        for (int mt = 0; mt < 4; mt++)
#pragma unroll
            for (int nt = 0; nt < 4; nt++) {
                const int i0 = 8 * nt + 2 * tq, r = 16 * mt + g;
                us[64 * i0 + r] = __float2bfloat16_rn(acc[mt][nt][0]);
                us[64 * (i0 + 1) + r] = __float2bfloat16_rn(acc[mt][nt][1]);
                us[64 * i0 + r + 8] = __float2bfloat16_rn(acc[mt][nt][2]);
                us[64 * (i0 + 1) + r + 8] = __float2bfloat16_rn(acc[mt][nt][3]);
            }
        __syncwarp();
#pragma unroll
        for (int i = 0; i < 8; i++)
            *reinterpret_cast<uint4*>(g_y + (size_t)d * S_LEN + (lane + 32 * i) * 8) = *reinterpret_cast<const uint4*>(us + (lane + 32 * i) * 8);
        }
        if ((op & 1) == 0) {
            expand_taps<0>(tab, kr, 0, lane);
            expand_taps<1>(tab, kr, 256, lane);
            expand_taps<2>(tab, kr, 512, lane);
            expand_taps<2>(tab, kr, 768, lane);
#pragma unroll 1
            for (int i = 0; i < 4; i++) expand_taps<3>(tab, kr, 1024 + 256 * i, lane);
            __syncwarp();
        }
        TS3(21 + op);
    }
}
__device__ __forceinline__ void s4d_stage_u(unsigned char* smem_raw, const bf16* __restrict__ x, int pt) {
    bf16* u_all = reinterpret_cast<bf16*>(smem_raw);
    const int d0 = blockIdx.x * SD_CH;
#pragma unroll 1
    for (int b = 0; b < 4; b++) {
        uint4 v[8];
#pragma unroll
        for (int i = 0; i < 8; i++) {
            int c = pt + 128 * (8 * b + i);
            v[i] = *reinterpret_cast<const uint4*>(x + (size_t)(c >> 1) * DM + d0 + (c & 1) * 8);
        }
#pragma unroll
        for (int i = 0; i < 8; i++) {
            int c = pt + 128 * (8 * b + i), t = c >> 1;
            bf16* dst = u_all + (c & 1) * 8 * SD_USTR + (8 + (t >> 6)) * 72 + (t & 63);
            const bf16* pv = reinterpret_cast<const bf16*>(&v[i]);
#pragma unroll
            for (int ch = 0; ch < 8; ch++) dst[ch * SD_USTR] = pv[ch];
        }
    }
    asm volatile("bar.arrive 1, 256;" ::: "memory");
    asm volatile("bar.arrive 2, 256;" ::: "memory");
}

constexpr int WOC = DM / 3;
constexpr int TBUF = 5 * DH * 16;
constexpr int XBUF = SEG * DM * 2;
constexpr float ATT_SCALE = 0.08838834764831845f;
constexpr int SM_BAR = 0;
constexpr int B_SB = 0, B_VM = 16, B_VX = 32, B_XT = 64, B_W0 = 88, B_W1 = 96, B_WO = 104;
constexpr int SM_SC = 256;
constexpr int SM_F = SM_SC + 1280;
constexpr int SM_VM = SM_F + 2048;
constexpr int SM_S = SM_VM + 2048;
constexpr int SM_O = SM_S + 2560;
constexpr int SM_M = SM_O + 2048;
constexpr int SM_WS = 19456;
constexpr int SM_T = SM_WS + 32768;
constexpr int SM_VX = SM_T + 4 * TBUF;
constexpr int SM_X = SM_VX + 2 * 8192;
constexpr int SM_STWO = SM_X + 2 * XBUF;
constexpr int CH_SMEM = SM_STWO + DH * WOC * 2;
static_assert(SM_M + DM * 16 <= SM_WS && SM_WS + DM * DH * 2 <= SM_STWO && CH_SMEM <= 232448 && SM_X % 1024 == 0, "smem");
__device__ __forceinline__ uint32_t clock32() { uint32_t t; asm volatile("mov.u32 %0, %%clock;" : "=r"(t) :: "memory"); return t; }

__device__ __forceinline__ uint32_t mapa(uint32_t a, uint32_t rank) {
    uint32_t r; asm volatile("mapa.shared::cluster.u32 %0, %1, %2;" : "=r"(r) : "r"(a), "r"(rank)); return r;
}
__device__ __forceinline__ void st_async32(uint32_t addr, uint32_t v, uint32_t mbar) {
    asm volatile("st.async.weak.shared::cluster.mbarrier::complete_tx::bytes.b32 [%0], %1, [%2];" :: "r"(addr), "r"(v), "r"(mbar) : "memory");
}
__device__ __forceinline__ void mbar_init(uint32_t bar, uint32_t cnt) {
    asm volatile("mbarrier.init.shared::cta.b64 [%0], %1;" :: "r"(bar), "r"(cnt) : "memory");
}
__device__ __forceinline__ void mbar_expect(uint32_t bar, uint32_t bytes) {
    asm volatile("mbarrier.arrive.expect_tx.shared::cta.b64 _, [%0], %1;" :: "r"(bar), "r"(bytes) : "memory");
}
__device__ __forceinline__ void mbar_wait(uint32_t bar, uint32_t parity) {
    unsigned it = 0;
    while (true) {
        uint32_t ok;
        asm volatile("{\n.reg .pred p;\nmbarrier.try_wait.parity.shared::cta.b64 p, [%1], %2;\nselp.u32 %0, 1, 0, p;\n}"
                     : "=r"(ok) : "r"(bar), "r"(parity) : "memory");
        if (ok || ++it >= SPIN_LIMIT) break;
    }
}
__device__ __forceinline__ void mbar_wait_long(uint32_t bar, uint32_t parity) {
    unsigned it = 0;
    while (true) {
        uint32_t ok;
        asm volatile("{\n.reg .pred p;\nmbarrier.try_wait.parity.shared::cta.b64 p, [%1], %2, %3;\nselp.u32 %0, 1, 0, p;\n}"
                     : "=r"(ok) : "r"(bar), "r"(parity), "r"(20000u) : "memory");
        if (ok || ++it >= SPIN_LIMIT) break;
    }
}
__device__ __forceinline__ uint64_t policy_evict_first() {
    uint64_t pol; asm volatile("createpolicy.fractional.L2::evict_first.b64 %0, 1.0;" : "=l"(pol)); return pol;
}
__device__ __forceinline__ void cluster_sync_all() {
    asm volatile("barrier.cluster.arrive.release.aligned;\nbarrier.cluster.wait.acquire.aligned;" ::: "memory");
}
__device__ __forceinline__ uint4 ld_vol_u4(const uint4* p) {
    uint4 v; asm volatile(LDV4 : "=r"(v.x), "=r"(v.y), "=r"(v.z), "=r"(v.w) : "l"(p) : "memory"); return v;
}
__device__ __forceinline__ void ld_vol_u4_p(uint4& v, const uint4* p, uint32_t pred) {
    asm volatile("{\n.reg .pred p;\nsetp.ne.u32 p, %5, 0;\n@p " LDV4 "\n}"
                 : "+r"(v.x), "+r"(v.y), "+r"(v.z), "+r"(v.w) : "l"(p), "r"(pred) : "memory");
}
__device__ __forceinline__ void st_vol_u4(uint4* p, uint4 v) {
    asm volatile(STV4 :: "l"(p), "r"(v.x), "r"(v.y), "r"(v.z), "r"(v.w) : "memory");
}
__device__ __forceinline__ void mma_bf16_r(float (&d)[4], uint32_t a0, uint32_t a1, uint32_t a2, uint32_t a3, uint32_t b0, uint32_t b1) {
    asm volatile("mma.sync.aligned.m16n8k16.row.col.f32.bf16.bf16.f32 {%0,%1,%2,%3}, {%4,%5,%6,%7}, {%8,%9}, {%0,%1,%2,%3};"
                 : "+f"(d[0]), "+f"(d[1]), "+f"(d[2]), "+f"(d[3])
                 : "r"(a0), "r"(a1), "r"(a2), "r"(a3), "r"(b0), "r"(b1));
}

__device__ __forceinline__ uint64_t smem_desc(uint32_t addr, uint32_t lbo, uint32_t sbo) {
    return (uint64_t)((addr & 0x3FFFF) >> 4) | ((uint64_t)(lbo >> 4) << 16) | ((uint64_t)(sbo >> 4) << 32);
}
__device__ __forceinline__ void wg_fence() { asm volatile("wgmma.fence.sync.aligned;" ::: "memory"); }
__device__ __forceinline__ void wg_commit() { asm volatile("wgmma.commit_group.sync.aligned;" ::: "memory"); }
__device__ __forceinline__ void wg_wait0() { asm volatile("wgmma.wait_group.sync.aligned 0;" ::: "memory"); }
__device__ __forceinline__ void fence_async() { asm volatile("fence.proxy.async.shared::cta;" ::: "memory"); }
__device__ __forceinline__ void wgmma_n32(float (&d)[16], const uint32_t (&a)[4], uint64_t bdesc, int scale_d) {
    asm volatile("{\n.reg .pred p;\nsetp.ne.b32 p, %21, 0;\n"
                 "wgmma.mma_async.sync.aligned.m64n32k16.f32.bf16.bf16 {%0,%1,%2,%3,%4,%5,%6,%7,%8,%9,%10,%11,%12,%13,%14,%15}, {%16,%17,%18,%19}, %20, p, 1, 1, 0;\n}"
                 : "+f"(d[0]), "+f"(d[1]), "+f"(d[2]), "+f"(d[3]), "+f"(d[4]), "+f"(d[5]), "+f"(d[6]), "+f"(d[7]),
                   "+f"(d[8]), "+f"(d[9]), "+f"(d[10]), "+f"(d[11]), "+f"(d[12]), "+f"(d[13]), "+f"(d[14]), "+f"(d[15])
                 : "r"(a[0]), "r"(a[1]), "r"(a[2]), "r"(a[3]), "l"(bdesc), "r"(scale_d));
}

__device__ __forceinline__ void wgmma_n32_ss(float (&d)[16], uint64_t adesc, uint64_t bdesc, int scale_d) {
    asm volatile("{\n.reg .pred p;\nsetp.ne.b32 p, %18, 0;\n"
                 "wgmma.mma_async.sync.aligned.m64n32k16.f32.bf16.bf16 {%0,%1,%2,%3,%4,%5,%6,%7,%8,%9,%10,%11,%12,%13,%14,%15}, %16, %17, p, 1, 1, 1, 0;\n}"
                 : "+f"(d[0]), "+f"(d[1]), "+f"(d[2]), "+f"(d[3]), "+f"(d[4]), "+f"(d[5]), "+f"(d[6]), "+f"(d[7]),
                   "+f"(d[8]), "+f"(d[9]), "+f"(d[10]), "+f"(d[11]), "+f"(d[12]), "+f"(d[13]), "+f"(d[14]), "+f"(d[15])
                 : "l"(adesc), "l"(bdesc), "r"(scale_d));
}

__device__ __forceinline__ void bulk_g2s(uint32_t dst, const void* src, uint32_t bytes, uint32_t mbar) {
    asm volatile("cp.async.bulk.shared::cluster.global.mbarrier::complete_tx::bytes [%0], [%1], %2, [%3];"
                 :: "r"(dst), "l"(src), "r"(bytes), "r"(mbar) : "memory");
}
__device__ __forceinline__ void bulk_g2s_h(uint32_t dst, const void* src, uint32_t bytes, uint32_t mbar, uint64_t pol) {
    asm volatile("cp.async.bulk.shared::cluster.global.mbarrier::complete_tx::bytes.L2::cache_hint [%0], [%1], %2, [%3], %4;"
                 :: "r"(dst), "l"(src), "r"(bytes), "r"(mbar), "l"(pol) : "memory");
}
__device__ __forceinline__ void tma_x(uint32_t dst, const CUtensorMap* tm, int seg, int part, uint32_t mbar) {
    asm volatile("cp.async.bulk.tensor.3d.shared::cluster.global.tile.mbarrier::complete_tx::bytes [%0], [%1, {%2, %3, %4}], [%5];"
                 :: "r"(dst + part * 12288), "l"(tm), "r"(0), "r"(seg * SEG), "r"(part * 3), "r"(mbar) : "memory");
}
__device__ __forceinline__ void tma_x_mc(uint32_t dst, const CUtensorMap* tm, int seg, int part, uint32_t mbar) {
    asm volatile("cp.async.bulk.tensor.3d.shared::cluster.global.tile.mbarrier::complete_tx::bytes.multicast::cluster [%0], [%1, {%2, %3, %4}], [%5], %6;"
                 :: "r"(dst + part * 12288), "l"(tm), "r"(0), "r"(seg * SEG), "r"(part * 3), "r"(mbar), "h"((unsigned short)7) : "memory");
}
__device__ __forceinline__ void bulk_s2s(uint32_t dst, uint32_t src, uint32_t bytes, uint32_t mbar) {
    asm volatile("cp.async.bulk.shared::cluster.shared::cta.mbarrier::complete_tx::bytes [%0], [%1], %2, [%3];"
                 :: "r"(dst), "r"(src), "r"(bytes), "r"(mbar) : "memory");
}
__device__ __forceinline__ void wgmma_n40_ss(float (&d)[20], uint64_t adesc, uint64_t bdesc, int scale_d) {
    asm volatile("{\n.reg .pred p;\nsetp.ne.b32 p, %22, 0;\n"
                 "wgmma.mma_async.sync.aligned.m64n40k16.f32.bf16.bf16 {%0,%1,%2,%3,%4,%5,%6,%7,%8,%9,%10,%11,%12,%13,%14,%15,%16,%17,%18,%19}, %20, %21, p, 1, 1, 1, 1;\n}"
                 : "+f"(d[0]), "+f"(d[1]), "+f"(d[2]), "+f"(d[3]), "+f"(d[4]), "+f"(d[5]), "+f"(d[6]), "+f"(d[7]),
                   "+f"(d[8]), "+f"(d[9]), "+f"(d[10]), "+f"(d[11]), "+f"(d[12]), "+f"(d[13]), "+f"(d[14]), "+f"(d[15]),
                   "+f"(d[16]), "+f"(d[17]), "+f"(d[18]), "+f"(d[19])
                 : "l"(adesc), "l"(bdesc), "r"(scale_d));
}
__device__ __forceinline__ void wgmma_n64_z(float (&d)[32], const uint32_t (&a)[4], uint64_t bdesc) {
    asm volatile("{\n.reg .pred p;\nsetp.ne.b32 p, 0, 0;\n"
                 "wgmma.mma_async.sync.aligned.m64n64k16.f32.bf16.bf16 {%0,%1,%2,%3,%4,%5,%6,%7,%8,%9,%10,%11,%12,%13,%14,%15,%16,%17,%18,%19,%20,%21,%22,%23,%24,%25,%26,%27,%28,%29,%30,%31}, {%32,%33,%34,%35}, %36, p, 1, 1, 0;\n}"
                 : "=f"(d[0]), "=f"(d[1]), "=f"(d[2]), "=f"(d[3]), "=f"(d[4]), "=f"(d[5]), "=f"(d[6]), "=f"(d[7]),
                   "=f"(d[8]), "=f"(d[9]), "=f"(d[10]), "=f"(d[11]), "=f"(d[12]), "=f"(d[13]), "=f"(d[14]), "=f"(d[15]),
                   "=f"(d[16]), "=f"(d[17]), "=f"(d[18]), "=f"(d[19]), "=f"(d[20]), "=f"(d[21]), "=f"(d[22]), "=f"(d[23]),
                   "=f"(d[24]), "=f"(d[25]), "=f"(d[26]), "=f"(d[27]), "=f"(d[28]), "=f"(d[29]), "=f"(d[30]), "=f"(d[31])
                 : "r"(a[0]), "r"(a[1]), "r"(a[2]), "r"(a[3]), "l"(bdesc));
}
__device__ __forceinline__ void wgmma_n64(float (&d)[32], const uint32_t (&a)[4], uint64_t bdesc, int scale_d) {
    asm volatile("{\n.reg .pred p;\nsetp.ne.b32 p, %37, 0;\n"
                 "wgmma.mma_async.sync.aligned.m64n64k16.f32.bf16.bf16 {%0,%1,%2,%3,%4,%5,%6,%7,%8,%9,%10,%11,%12,%13,%14,%15,%16,%17,%18,%19,%20,%21,%22,%23,%24,%25,%26,%27,%28,%29,%30,%31}, {%32,%33,%34,%35}, %36, p, 1, 1, 0;\n}"
                 : "+f"(d[0]), "+f"(d[1]), "+f"(d[2]), "+f"(d[3]), "+f"(d[4]), "+f"(d[5]), "+f"(d[6]), "+f"(d[7]),
                   "+f"(d[8]), "+f"(d[9]), "+f"(d[10]), "+f"(d[11]), "+f"(d[12]), "+f"(d[13]), "+f"(d[14]), "+f"(d[15]),
                   "+f"(d[16]), "+f"(d[17]), "+f"(d[18]), "+f"(d[19]), "+f"(d[20]), "+f"(d[21]), "+f"(d[22]), "+f"(d[23]),
                   "+f"(d[24]), "+f"(d[25]), "+f"(d[26]), "+f"(d[27]), "+f"(d[28]), "+f"(d[29]), "+f"(d[30]), "+f"(d[31])
                 : "r"(a[0]), "r"(a[1]), "r"(a[2]), "r"(a[3]), "l"(bdesc), "r"(scale_d));
}

constexpr int SB_FULL = 0, SB_EMPTY = 64, SB_QKF = 128, SB_VF = 144, SB_QKE = 160, SB_VE = 176, SB_OF = 192, SB_WO = 208;
constexpr int AT_0 = 256, AT_ST = 10240 + 2 * 9216;
constexpr int FS_A = 58368;
constexpr int FS_I = FS_A + 131072;
constexpr int SIDE_SMEM = FS_I + 2 * 16384;
static_assert(SIDE_SMEM <= 232448 && AT_0 + 2 * AT_ST <= FS_A && FS_A + SD_SMEM <= SIDE_SMEM, "smem");

__device__ __forceinline__ void bf16r2(float& a, float& b) {
    uint32_t p = pack_bf16(a, b);
    a = __uint_as_float(p << 16); b = __uint_as_float(p & 0xffff0000u);
}
__device__ __forceinline__ void wg_wait1() { asm volatile("wgmma.wait_group.sync.aligned 1;" ::: "memory"); }
__device__ __forceinline__ void mbar_arrive(uint32_t bar) { asm volatile("mbarrier.arrive.shared::cta.b64 _, [%0];" :: "r"(bar) : "memory"); }
__device__ __forceinline__ void wait_cnt(const unsigned* p, unsigned target) {
    unsigned it = 0;
    while ((int)(ld_acq(p) - target) < 0 && ++it < SPIN_LIMIT) __nanosleep(64);
}
__device__ __forceinline__ void wait_cnt_rlx(const unsigned* p, unsigned target, bool urgent) {
    unsigned it = 0, v;
    while (true) {
        asm volatile("ld.relaxed.gpu.global.u32 %0, [%1];" : "=r"(v) : "l"(p) : "memory");
        if ((int)(v - target) >= 0 || ++it >= SPIN_LIMIT) break;
        if (!urgent) __nanosleep(300);
    }
}

__device__ __forceinline__ void xrow_softmax(float (&sc)[20], uint32_t (&pa)[3][4], int wq, int lane) {
    const int g = lane >> 2, tq = lane & 3;
    float mx0 = -INFINITY;
    const int q0 = MEMT + 8 * wq + g;
#pragma unroll
    for (int j = 0; j < 5; j++) {
        bf16r2(sc[4 * j], sc[4 * j + 1]);
        sc[4 * j] *= ATT_SCALE; sc[4 * j + 1] *= ATT_SCALE;
        bf16r2(sc[4 * j], sc[4 * j + 1]);
#pragma unroll
        for (int c = 0; c < 2; c++) {
            int key = 8 * j + 2 * tq + c;
            if (key > q0) sc[4 * j + c] = -INFINITY;
            mx0 = fmaxf(mx0, sc[4 * j + c]);
        }
    }
    mx0 = fmaxf(mx0, __shfl_xor_sync(0xffffffffu, mx0, 1)); mx0 = fmaxf(mx0, __shfl_xor_sync(0xffffffffu, mx0, 2));
    float sum0 = 0.f;
#pragma unroll
    for (int j = 0; j < 5; j++) {
#pragma unroll
        for (int c = 0; c < 2; c++) {
            float e0 = __expf(sc[4 * j + c] - mx0);
            sc[4 * j + c] = e0;
            sum0 += e0;
        }
    }
    sum0 += __shfl_xor_sync(0xffffffffu, sum0, 1); sum0 += __shfl_xor_sync(0xffffffffu, sum0, 2);
    const float i0 = 1.f / sum0;
#pragma unroll
    for (int ks = 0; ks < 3; ks++) {
        pa[ks][0] = pack_bf16(sc[8 * ks] * i0, sc[8 * ks + 1] * i0);
        pa[ks][1] = 0u;
        pa[ks][2] = ks < 2 ? pack_bf16(sc[8 * ks + 4] * i0, sc[8 * ks + 5] * i0) : 0u;
        pa[ks][3] = 0u;
    }
}

__device__ __forceinline__ void stsm_x4(uint32_t addr, uint32_t r0, uint32_t r1, uint32_t r2, uint32_t r3) {
    asm volatile("stmatrix.sync.aligned.m8n8.x4.shared.b16 [%0], {%1,%2,%3,%4};" :: "r"(addr), "r"(r0), "r"(r1), "r"(r2), "r"(r3) : "memory");
}
__device__ __forceinline__ uint32_t h2_to_bf2(uint32_t h) {
    uint32_t r;
    asm("{\n.reg .f16 l, h;\n.reg .f32 a, b;\nmov.b32 {l, h}, %1;\ncvt.f32.f16 a, l;\ncvt.f32.f16 b, h;\ncvt.rn.bf16x2.f32 %0, b, a;\n}" : "=r"(r) : "r"(h));
    return r;
}
__device__ __forceinline__ uint32_t pack_f16(float lo, float hi) {
    uint32_t r; asm("cvt.rn.f16x2.f32 %0, %1, %2;" : "=r"(r) : "f"(hi), "f"(lo)); return r;
}
__device__ __forceinline__ uint32_t bf2_mul(uint32_t a, uint32_t b) { uint32_t r; asm("mul.rn.bf16x2 %0, %1, %2;" : "=r"(r) : "r"(a), "r"(b)); return r; }
__device__ __forceinline__ uint32_t bf2_add(uint32_t a, uint32_t b) { uint32_t r; asm("add.rn.bf16x2 %0, %1, %2;" : "=r"(r) : "r"(a), "r"(b)); return r; }
__device__ __forceinline__ uint32_t bf2_sub(uint32_t a, uint32_t b) { uint32_t r; asm("sub.rn.bf16x2 %0, %1, %2;" : "=r"(r) : "r"(a), "r"(b)); return r; }
__device__ __forceinline__ uint32_t movm(uint32_t v) {
    uint32_t r; asm volatile("movmatrix.sync.aligned.m8n8.trans.b16 %0, %1;" : "=r"(r) : "r"(v)); return r;
}
__device__ __forceinline__ void bar_arrive(int id, int n) { asm volatile("bar.arrive %0, %1;" :: "r"(id), "r"(n) : "memory"); }
__device__ __forceinline__ void lds64(uint32_t& a, uint32_t& b, uint32_t addr) {
    asm volatile("ld.shared.v2.u32 {%0,%1}, [%2];" : "=r"(a), "=r"(b) : "r"(addr) : "memory");
}
__device__ __forceinline__ void lds64f(float& a, float& b, uint32_t addr) {
    asm volatile("ld.shared.v2.f32 {%0,%1}, [%2];" : "=f"(a), "=f"(b) : "r"(addr) : "memory");
}
__device__ __forceinline__ void st_async64(uint32_t addr, uint32_t a, uint32_t b, uint32_t mbar) {
    asm volatile("st.async.weak.shared::cluster.mbarrier::complete_tx::bytes.v2.b32 [%0], {%1,%2}, [%3];" :: "r"(addr), "r"(a), "r"(b), "r"(mbar) : "memory");
}
__device__ __forceinline__ void mma_z(float (&d)[4], const uint32_t (&a)[4], uint32_t b0, uint32_t b1) {
    asm volatile("mma.sync.aligned.m16n8k16.row.col.f32.bf16.bf16.f32 {%0,%1,%2,%3}, {%4,%5,%6,%7}, {%8,%9}, {%10,%10,%10,%10};"
                 : "=f"(d[0]), "=f"(d[1]), "=f"(d[2]), "=f"(d[3])
                 : "r"(a[0]), "r"(a[1]), "r"(a[2]), "r"(a[3]), "r"(b0), "r"(b1), "f"(0.f));
}
__device__ __forceinline__ void mma_k8(float (&d)[4], uint32_t a0, uint32_t a1, uint32_t b) {
    asm volatile("mma.sync.aligned.m16n8k8.row.col.f32.bf16.bf16.f32 {%0,%1,%2,%3}, {%4,%5}, {%6}, {%0,%1,%2,%3};"
                 : "+f"(d[0]), "+f"(d[1]), "+f"(d[2]), "+f"(d[3]) : "r"(a0), "r"(a1), "r"(b));
}
__global__ void __launch_bounds__(512, 1) k_side(const __grid_constant__ CUtensorMap tmo, const bf16* __restrict__ x, const bf16* __restrict__ logA, const bf16* __restrict__ Aim,
                                                 const bf16* __restrict__ Cre, const bf16* __restrict__ Cim, const bf16* __restrict__ logdt,
                                                 const bf16* __restrict__ Wo, const bf16* __restrict__ dskip, const bf16* __restrict__ gw,
                                                 bf16* __restrict__ out) {
    extern __shared__ __align__(1024) unsigned char smem_raw[];
    const uint32_t sbase = smem_u32(smem_raw);
    const int tid = threadIdx.x, warp = __shfl_sync(0xffffffffu, tid >> 5, 0), lane = tid & 31, cta = blockIdx.x;
    const bool sp = cta >= NH;
    if (tid == 0) {
        for (int i = 0; i < 4; i++) { mbar_init(sbase + SB_FULL + 8 * i, 1); mbar_init(sbase + SB_EMPTY + 8 * i, sp ? 4 : 8); }
        for (int i = 0; i < 2; i++) {
            mbar_init(sbase + SB_QKF + 8 * i, 1); mbar_init(sbase + SB_VF + 8 * i, 1); mbar_init(sbase + SB_QKE + 8 * i, 1);
            mbar_init(sbase + SB_VE + 8 * i, 4); mbar_init(sbase + SB_OF + 8 * i, 4);
        }
        mbar_init(sbase + SB_WO, 1);
        asm volatile("fence.mbarrier_init.release.cluster;" ::: "memory");
    }
    TS3(0);
    unsigned ep;
    asm volatile("ld.volatile.global.u32 %0, [%1];" : "=r"(ep) : "l"(&g_epoch) : "memory");
    ep += 1u;
    asm volatile("fence.proxy.async;" ::: "memory");
    __syncthreads();
    if (warp >= 12) {
      asm volatile("setmaxnreg.dec.sync.aligned.u32 40;");
      if (warp == 12 || warp == 15) {
        named_bar(3, 320);
        if (tid == 384) {
            fence_async();
            mbar_expect(sbase + SB_WO, 131072);
#pragma unroll
            for (int i = 0; i < 8; i++)
                asm volatile("cp.async.bulk.tensor.2d.shared::cluster.global.tile.mbarrier::complete_tx::bytes [%0], [%1, {%2, %3}], [%4];"
                             :: "r"(sbase + FS_A + i * 16384), "l"(&tmo), "r"((sp ? 8 : 2 * (cta & 3) + (i >> 2)) * 64),
                                "r"((sp ? 2 * (cta - NH) + (i >> 2) : cta >> 2) * 512 + (i & 3) * 128), "r"(sbase + SB_WO) : "memory");
            TSS(17, 2);
        }
        if (tid == 480) {
            __threadfence();
            asm volatile("red.relaxed.gpu.global.add.u32 [%0], 1;" :: "l"(&g_gcnt) : "memory");
            TSS(17, 3);
        }
        __syncwarp();
        named_bar(7, 320);
        if (lane == 0 && (sp || warp == 12)) {
            const int pi = warp == 12 ? 0 : 1;
            const int kb = sp ? 2 * (cta - NH) + pi : cta >> 2;
            fence_async();
            for (int pr = 0; pr < NSEG / 2; pr++) {
                const int gr = sp ? pi : (pr & 1);
                wait_cnt_rlx(&g_prog[pr * 8 + kb], 8u * ep, pr >= NSEG / 2 - 2);
                if (pr >= 30 && pi == 0) TSS(4 + pr - 30, 0);
                if (pr == 31) TS3P(26);
                if (pr == 30) TS3P(1);
                mbar_wait_long(sbase + SB_EMPTY + 8 * gr, ((uint32_t)(sp ? pr : pr >> 1) & 1u) ^ 1u);
#pragma unroll
                for (int j = 0; j < 2; j++) {
                    mbar_expect(sbase + SB_FULL + 16 * gr + 8 * j, 32768);
                    bulk_g2s(sbase + FS_A + gr * 65536 + j * 32768, g_ox + ((size_t)(pr * NH + 4 * kb + 2 * j)) * 8192, 32768, sbase + SB_FULL + 16 * gr + 8 * j);
                }
            }
        }
        __syncwarp();
      } else if (warp == 13) {
        if (lane == 0 && cta < NH) {
            const uint64_t pol = policy_evict_first();
            for (int seg = 0; seg < NSEG; seg++) {
                const uint32_t st = seg & 1, ph = (uint32_t)(seg >> 1) & 1u, ab = sbase + AT_0 + st * AT_ST;
                wait_cnt_rlx(&g_flag[seg * NH + cta], 3u * ep, seg >= NSEG - 4);
                if (seg >= 60) TSS(seg - 60, 0);
                mbar_wait_long(sbase + SB_QKE + 8 * st, ph ^ 1u);
                if (seg >= 60) TSS(seg - 60, 1);
                mbar_expect(sbase + SB_QKF + 8 * st, 2 * 9216);
                bulk_g2s_h(ab + 10240, &g_qkv[seg][cta][0][1024], 9216, sbase + SB_QKF + 8 * st, pol);
                bulk_g2s_h(ab + 10240 + 9216, &g_qkv[seg][cta][1][1024], 9216, sbase + SB_QKF + 8 * st, pol);
                mbar_wait_long(sbase + SB_VE + 8 * st, ph ^ 1u);
                mbar_expect(sbase + SB_VF + 8 * st, 10240);
                bulk_g2s_h(ab, &g_qkv[seg][cta][2][0], 10240, sbase + SB_VF + 8 * st, pol);
            }
        }
        __syncwarp();
      } else if (warp == 14) {
        if (lane == 0 && cta < NH) {
            for (int seg = 0; seg < NSEG; seg++) {
                const uint32_t st = seg & 1, ab = sbase + AT_0 + st * AT_ST;
                mbar_wait_long(sbase + SB_OF + 8 * st, (uint32_t)(seg >> 1) & 1u);
                if (seg >= 60) TSS(seg - 60, 3);
                unsigned char* dst = reinterpret_cast<unsigned char*>(g_ox) + ((size_t)((seg >> 1) * NH + cta)) * 16384 + (seg & 1) * 4096;
                asm volatile("cp.async.bulk.global.shared::cta.bulk_group [%0], [%1], 4096;" :: "l"(dst), "r"(ab + 12288) : "memory");
                asm volatile("cp.async.bulk.global.shared::cta.bulk_group [%0], [%1], 4096;" :: "l"(dst + 8192), "r"(ab + 16384) : "memory");
                asm volatile("cp.async.bulk.commit_group;" ::: "memory");
                asm volatile("cp.async.bulk.wait_group 0;" ::: "memory");
                asm volatile("red.relaxed.gpu.global.add.u32 [%0], 1;" :: "l"(&g_prog[(seg >> 1) * 8 + (cta >> 2)]) : "memory");
                mbar_arrive(sbase + SB_QKE + 8 * st);
                if (seg >= 60) TSS(seg - 60, 4);
            }
        }
        __syncwarp();
      }
    } else if (warp >= 8) {
        asm volatile("setmaxnreg.dec.sync.aligned.u32 88;");
        s4d_stage_u(smem_raw + FS_A, x, tid - 256);
        {
            uint32_t gwv[9];
#pragma unroll
            for (int i = 0; i < 9; i++) gwv[i] = reinterpret_cast<const uint32_t*>(gw)[lane + 32 * i];
#pragma unroll 3
            for (int i = 0; i < 15; i++) {
                const int tt = 4 * i + warp - 8, t = min(cta * 57 + tt, S_LEN - 1);
                float sm = 0.f;
#pragma unroll
                for (int k = 0; k < 9; k++) {
                    const uint32_t xv = reinterpret_cast<const uint32_t*>(x + t * DM)[lane + 32 * k];
                    float a = __uint_as_float(xv << 16) * __uint_as_float(gwv[k] << 16), b = __uint_as_float(xv & 0xffff0000u) * __uint_as_float(gwv[k] & 0xffff0000u);
                    bf16r2(a, b);
                    sm += a + b;
                }
#pragma unroll
                for (int o = 16; o; o >>= 1) sm += __shfl_xor_sync(0xffffffffu, sm, o);
                const float gv = 1.f / (1.f + expf(-bf16r(sm)));
                if (lane == 0 && tt < 57) g_gate[t] = pack_bf16(gv, gv);
            }
#pragma unroll 1
            for (int b4 = 0; b4 < 4; b4++)
#pragma unroll
                for (int i = 0; i < 14; i++) (&g_fp[b4][2 * cta][0][0])[tid - 256 + 128 * i] = make_uint4(0u, 0u, 0u, 0u);
            named_bar(6, 128);
            if (tid == 256) {
                __threadfence();
                asm volatile("red.relaxed.gpu.global.add.u32 [%0], 1;" :: "l"(&g_gcnt) : "memory");
            }
            __syncwarp();
        }
        const int wq = warp - 8;
        for (int seg = 0; seg < (cta < NH ? NSEG : 0); seg++) {
            const uint32_t st = seg & 1, ph = (uint32_t)(seg >> 1) & 1u, ab = sbase + AT_0 + st * AT_ST;
            float sc[20];
            mbar_wait_long(sbase + SB_QKF + 8 * st, ph);
            if (seg >= 60 && tid == 256) TSS(seg - 60, 2);
            {
                const uint64_t da = smem_desc(ab + 10240 + 1024, 128, 1024), db = smem_desc(ab + 10240, 128, 2048);
                wg_fence();
#pragma unroll
                for (int ks = 0; ks < 8; ks++) wgmma_n40_ss(sc, da + (uint64_t)((ks >> 2) * 576 + (ks & 3) * 16), db + (uint64_t)((ks >> 2) * 576 + (ks & 3) * 16), ks > 0);
                wg_commit();
                wg_wait0();
            }
            uint32_t pa[3][4];
            xrow_softmax(sc, pa, wq, lane);
            named_bar(6, 128);
            mbar_wait_long(sbase + SB_VF + 8 * st, ph);
#pragma unroll
            for (int hf = 0; hf < 2; hf++) {
                float o[32];
                const uint64_t dv = smem_desc(ab + hf * 1024, 2048, 128);
                wg_fence();
#pragma unroll
                for (int ks = 0; ks < 3; ks++) { if (ks == 0) wgmma_n64_z(o, pa[0], dv); else wgmma_n64(o, pa[ks], dv + (uint64_t)(ks * 256), 1); }
                wg_commit();
                wg_wait0();
#pragma unroll
                for (int i = 0; i < 2; i++)
                    stsm_x4(ab + 12288 + hf * 4096 + wq * 1024 + i * 512 + lane * 16, pack_bf16(o[16 * i], o[16 * i + 1]), pack_bf16(o[16 * i + 4], o[16 * i + 5]),
                            pack_bf16(o[16 * i + 8], o[16 * i + 9]), pack_bf16(o[16 * i + 12], o[16 * i + 13]));
            }
            if (lane == 0) mbar_arrive(sbase + SB_VE + 8 * st);
            fence_async();
            __syncwarp();
            if (lane == 0) mbar_arrive(sbase + SB_OF + 8 * st);
        }
    } else {
        asm volatile("setmaxnreg.inc.sync.aligned.u32 192;");
        const int wg = warp >> 2, wq = warp & 3;
        const int kb = sp ? 2 * (cta - NH) + wg : cta >> 2, cb = sp ? 8 : 2 * (cta & 3) + wg;
        s4d_phase(smem_raw + FS_A, x, logA, Aim, Cre, Cim, logdt, Wo + (size_t)(kb * 512) * DM + cb * 64);
        TS3(2);
        if (lane == 0) TSS(16, warp);
        named_bar(3, 320);
        if (tid == 0) TSS(17, 0);
        uint32_t wa[32][4];
        mbar_wait_long(sbase + SB_WO, 0);
        if (tid == 0) TSS(17, 1);
        {
            const uint32_t a = sbase + FS_A + wg * 65536 + ((lane >> 4) * 8 + (lane & 7)) * 128 + (((wq * 2 + ((lane >> 3) & 1)) ^ (lane & 7)) << 4);
#pragma unroll
            for (int ks = 0; ks < 32; ks++) ldsm_x4_t(wa[ks], a + ks * 2048);
        }
        named_bar(7, 320);
        TS3(3);
        if (lane == 0) wait_cnt(&g_gcnt, 2 * SD_NCTA * ep);
        __syncwarp();
        if (tid == 0) TSS(17, 4);
        uint32_t dv[2];
        dv[0] = *reinterpret_cast<const uint32_t*>(dskip + cb * 64 + wq * 16 + 2 * (lane & 3));
        dv[1] = *reinterpret_cast<const uint32_t*>(dskip + cb * 64 + wq * 16 + 8 + 2 * (lane & 3));
        for (int it = 0; it < NSEG / 2 + 2; it++) {
            const int pr = it == NSEG / 2 - 1 ? -1 : (it == NSEG / 2 ? it - 1 : (it > NSEG / 2 ? -1 : it));
            const int pf = it == NSEG / 2 ? -1 : (it > NSEG / 2 ? NSEG / 2 - 1 : it - 1);
            uint32_t t16 = (uint32_t)(wq * 32 + lane) * 16u;
            asm volatile("" : "+r"(t16));
            const int t0 = (pf < 0 ? 0 : pf) * 64 + kb * 8, c0 = cb * 64 + wq * 16;
            const uint32_t xo = (uint32_t)((t0 + ((t16 >> 6) & 7)) * DM + c0) * 2u + ((t16 >> 2) & 12u);
            uint32_t yv[2] = {0u, 0u}, uv[2] = {0u, 0u}, gg = 0u;
            if (pf >= 0) {
                const unsigned char* yp = reinterpret_cast<const unsigned char*>(g_y) + ((uint32_t)((c0 + ((t16 >> 6) & 7)) * S_LEN + t0) * 2u + ((t16 >> 2) & 12u));
                yv[0] = __ldcg(reinterpret_cast<const uint32_t*>(yp)); yv[1] = __ldcg(reinterpret_cast<const uint32_t*>(yp + 16 * S_LEN));
                uv[0] = *reinterpret_cast<const uint32_t*>(reinterpret_cast<const unsigned char*>(x) + xo);
                uv[1] = *reinterpret_cast<const uint32_t*>(reinterpret_cast<const unsigned char*>(x) + xo + 16);
                gg = __ldcg(&g_gate[t0 + ((t16 >> 6) & 7)]);
            }
            const uint32_t ib = sbase + FS_I + wg * 16384 + t16;
            auto fetch = [&]() {
                const unsigned char* src = reinterpret_cast<const unsigned char*>(&g_fp[pf & 3][2 * cta + wg][0][0]) + t16;
#pragma unroll
                for (int r = 0; r < 7; r++) asm volatile("cp.async.cg.shared.global [%0], [%1], 16;" :: "r"(ib + r * 2048), "l"(src + r * 2048) : "memory");
                asm volatile("cp.async.commit_group;" ::: "memory");
            };
            auto finalize = [&]() {
                const uint32_t tag = ((uint32_t)(pf >> 2) & 1u) ^ 1u;
                uint32_t zv[2];
#pragma unroll
                for (int j = 0; j < 2; j++) zv[j] = bf2_mul(bf2_sub(0x3f803f80u, gg), bf2_add(movm(yv[j]), bf2_mul(uv[j], dv[j])));
                float sm[4];
                unsigned n = 0;
                while (true) {
                    asm volatile("cp.async.wait_group 0;" ::: "memory");
                    uint32_t any = 0u;
#pragma unroll
                    for (int r = 0; r < 8; r++) {
                        uint4 v;
                        asm volatile("ld.shared.v4.u32 {%0,%1,%2,%3}, [%4];" : "=r"(v.x), "=r"(v.y), "=r"(v.z), "=r"(v.w) : "r"(ib + r * 2048) : "memory");
                        uint32_t c0_, c1_;
                        asm("lop3.b32 %0, %1, %2, %3, 0x7e;" : "=r"(c0_) : "r"(v.x), "r"(v.y), "r"(tag));
                        asm("lop3.b32 %0, %1, %2, %3, 0x7e;" : "=r"(c1_) : "r"(v.z), "r"(v.w), "r"(tag));
                        asm("lop3.b32 %0, %1, %2, %3, 0xfe;" : "=r"(any) : "r"(any), "r"(c0_), "r"(c1_));
                        if (r == 0) { sm[0] = __uint_as_float(v.x); sm[1] = __uint_as_float(v.y); sm[2] = __uint_as_float(v.z); sm[3] = __uint_as_float(v.w); }
                        else asm volatile("add.f32 %0, %0, %4;\nadd.f32 %1, %1, %5;\nadd.f32 %2, %2, %6;\nadd.f32 %3, %3, %7;"
                                          : "+f"(sm[0]), "+f"(sm[1]), "+f"(sm[2]), "+f"(sm[3])
                                          : "f"(__uint_as_float(v.x)), "f"(__uint_as_float(v.y)), "f"(__uint_as_float(v.z)), "f"(__uint_as_float(v.w)));
                    }
                    if (!__any_sync(0xffffffffu, (any & 1u) != 0u) || ++n >= SPIN_LIMIT) break;
                    if (pf + 1 < NSEG / 2 && n > 1) __nanosleep(100);
                    fetch();
                }
                if (pf == 31) TS3W(29);
                TSG(5);
#pragma unroll
                for (int j = 0; j < 2; j++)
                    *reinterpret_cast<uint32_t*>(reinterpret_cast<unsigned char*>(out) + xo + 16 * j) = bf2_add(bf2_mul(gg, movm(pack_bf16(sm[2 * j], sm[2 * j + 1]))), zv[j]);
                if (wg == 0 && (pf & 1) == 0) TS3(4 + pf / 2);
                if (pf == 31) TS3W(25);
                TSG(6);
            };
            if (pr >= 0) {
                float acc[32];
                const uint32_t gr = sp ? wg : (pr & 1), ph = (uint32_t)(sp ? pr : pr >> 1) & 1u;
                mbar_wait(sbase + SB_FULL + 16 * gr, ph);
                if (pr + wg > 0) named_bar(4 + wg, 256);
                const uint64_t db = smem_desc(sbase + FS_A + gr * 65536, 128, 1024);
                TSG(0);
                wg_fence();
#pragma unroll
                for (int ks = 0; ks < 16; ks++) {
                    if (ks == 0) wgmma_n64_z(acc, wa[0], db);
                    else wgmma_n64(acc, wa[ks], db + (uint64_t)((ks >> 2) * 512 + (ks & 3) * 16), 1);
                }
                wg_commit();
                if (pf >= 0) fetch();
                mbar_wait(sbase + SB_FULL + 16 * gr + 8, ph);
                wg_fence();
#pragma unroll
                for (int ks = 16; ks < 32; ks++) wgmma_n64(acc, wa[ks], db + (uint64_t)((ks >> 2) * 512 + (ks & 3) * 16), 1);
                wg_commit();
                if (pr + wg < NSEG / 2) bar_arrive(4 + (wg ^ 1), 256);
                wg_wait0();
                if (pr == 31) TS3W(27);
                TSG(3);
                if (lane == 0) mbar_arrive(sbase + SB_EMPTY + 8 * gr);
                if (pf >= 0) finalize();
                uint32_t tag = ((uint32_t)(pr >> 2) & 1u) ^ 1u;
                tag = __shfl_sync(0xffffffffu, tag, lane);
                unsigned char* dst = reinterpret_cast<unsigned char*>(&g_fp[pr & 3][cb < 8 ? cb : 64][kb - 1][0]) + t16;
                const uint32_t dstr = cb < 8 ? 8 * 14336 : 14336;
#pragma unroll
                for (int q = 0; q < 8; q++) {
                    asm volatile("{\n.reg .pred p;\nsetp.ne.s32 p, %5, %6;\n@p st.volatile.global.v4.u32 [%0], {%1,%2,%3,%4};\n@!p st.shared.v4.u32 [%7], {%1,%2,%3,%4};\n}"
                                 :: "l"(dst), "r"((__float_as_uint(acc[4 * q]) & ~1u) | tag), "r"((__float_as_uint(acc[4 * q + 1]) & ~1u) | tag),
                                    "r"((__float_as_uint(acc[4 * q + 2]) & ~1u) | tag), "r"((__float_as_uint(acc[4 * q + 3]) & ~1u) | tag), "r"(q), "r"(kb),
                                    "r"(ib + 7 * 2048) : "memory");
                    dst += q == kb ? dstr + 2048 : dstr;
                }
                if (pr == 31) TS3W(28);
                TSG(4);
            } else if (pf >= 0) { fetch(); finalize(); }
        }
        if (cta == 0 && tid == 0) asm volatile("st.volatile.global.u32 [%0], %1;" :: "l"(&g_epoch), "r"(ep) : "memory");
    }
    asm volatile("griddepcontrol.wait;" ::: "memory");
}

__device__ __forceinline__ uint32_t poll_mem(const uint4* src, uint32_t dst, uint32_t ones) {
    FS(12, 0);
    uint4 v[6];
    uint32_t w[18];
    unsigned it = 0;
#pragma unroll
    for (int j = 0; j < 6; j++) v[j] = ld_vol_u4(src + j * 256);
    while (true) {
#pragma unroll
        for (int j = 0; j < 6; j++) {
            w[3 * j] = h2_to_bf2(v[j].x); w[3 * j + 1] = h2_to_bf2(v[j].y); w[3 * j + 2] = h2_to_bf2(v[j].z);
            if (j == 1) stsm_x4(dst, w[0], w[1], w[2], w[3]);
            if (j == 2) stsm_x4(dst + 512, w[4], w[5], w[6], w[7]);
            if (j == 3) stsm_x4(dst + 1024, w[8], w[9], w[10], w[11]);
            if (j == 4) asm volatile("stmatrix.sync.aligned.m8n8.x2.shared.b16 [%0], {%1,%2};" :: "r"(dst + 1536), "r"(w[12]), "r"(w[13]) : "memory");
            if (j == 5) stsm_x4(dst + 1792, w[14], w[15], w[16], w[17]);
        }
        const uint32_t all = ((v[0].w & v[1].w) & (v[2].w & v[3].w)) & (v[4].w & v[5].w);
        if (!__any_sync(0xffffffffu, (all & 0x5000u) != 0x5000u) || ++it >= SPIN_LIMIT) break;
#pragma unroll
        for (int j = 0; j < 6; j++) ld_vol_u4_p(v[j], src + j * 256, v[j].w ^ 0x5000u);
    }
    FS(13, it);
    bar_arrive(1, 384);
    FS(14, 0);
#pragma unroll
    for (int j = 0; j < 18; j++) asm volatile("" : "+r"(w[j]));
    uint32_t m = 0u;
#pragma unroll
    for (int j = 0; j < 9; j++) m = __vmaxu2(m, __vmaxu2(w[2 * j] & 0x7fff7fffu, w[2 * j + 1] & 0x7fff7fffu));
    return m;
}

__device__ __forceinline__ void score_group(uint32_t qa, const uint32_t (&kf)[2][4], uint32_t d0, uint32_t d1, uint32_t m1, uint32_t d2, uint32_t m2) {
    uint32_t a[2][4];
#pragma unroll
    for (int k2 = 0; k2 < 2; k2++) ldsm_x4_t(a[k2], qa + k2 * 512);
    FS(4, a[1][0]);
    float sc[4][4];
    mma_z(sc[0], a[0], kf[0][0], kf[0][1]);
    mma_z(sc[1], a[0], kf[0][2], kf[0][3]);
    mma_z(sc[2], a[1], kf[1][0], kf[1][1]);
    mma_z(sc[3], a[1], kf[1][2], kf[1][3]);
    const uint32_t v0 = __float_as_uint((sc[0][0] + sc[1][2]) + (sc[2][0] + sc[3][2])), v1 = __float_as_uint((sc[0][1] + sc[1][3]) + (sc[2][1] + sc[3][3]));
    FS(5, v0);
    st_async64(d2, v0, v1, m2);
    st_async64(d1, v0, v1, m1);
    asm volatile("st.shared.v2.u32 [%0], {%1,%2};" :: "r"(d0), "r"(v0), "r"(v1) : "memory");
}
__device__ __forceinline__ void store_tile(int s, int h, int role, uint32_t tile) {
    const uint32_t qoff = role != 2 ? 1024 : 0;
    asm volatile("cp.async.bulk.global.shared::cta.bulk_group.L2::cache_hint [%0], [%1], %2, %3;"
                 :: "l"(&g_qkv[s][h][role][qoff]), "r"(tile + qoff), "r"(10240u - qoff), "l"(policy_evict_first()) : "memory");
    asm volatile("cp.async.bulk.commit_group;" ::: "memory");
}
__device__ __forceinline__ float sumsq8(uint4 v) {
    const uint32_t w[4] = {v.x, v.y, v.z, v.w};
    float t = 0.f;
#pragma unroll
    for (int i = 0; i < 4; i++) {
        const float a = __uint_as_float(w[i] << 16), b = __uint_as_float(w[i] & 0xffff0000u);
        t = fmaf(a, a, t); t = fmaf(b, b, t);
    }
    return t;
}
__device__ __forceinline__ uint32_t w_addr(uint32_t sbase, int warp, int lane) {
    return sbase + SM_WS + (warp >> 2) * 8192 + ((lane & 7) + ((lane >> 4) & 1) * 8) * 128 + ((((warp & 3) * 2 + ((lane >> 3) & 1)) ^ (lane & 7)) << 4);
}
__device__ __forceinline__ void vx_copy(uint32_t sbase, int j, int r) {
    bulk_s2s(mapa(sbase + SM_VX + (j & 1) * 8192, r), sbase + SM_T + (j & 3) * TBUF + DH * 16, 8192, mapa(sbase + B_VX + 8 * (j & 1), r));
}
__device__ __forceinline__ void norms_gather(int lane, float* scs) {
    uint2 v[3];
    uint32_t r[2];
    unsigned it = 0;
    do {
#pragma unroll
        for (int i = 0; i < 3; i++) v[i] = ld_vol_u2(&g_norm[3 * lane + i]);
#pragma unroll
        for (int i = 0; i < 2; i++) asm volatile("ld.volatile.global.u32 %0, [%1];" : "=r"(r[i]) : "l"(&g_rx[lane + 32 * i]) : "memory");
    } while (__any_sync(0xffffffffu, (v[0].x & v[1].x & v[2].x & v[2].y & r[0] & r[1] & 1u) == 0u) && ++it < SPIN_LIMIT);
    float c = sqrtf(__uint_as_float(max(max(v[0].x, v[1].x), v[2].x))) * sqrtf(__uint_as_float(v[2].y));
#pragma unroll
    for (int o = 16; o; o >>= 1) c += __shfl_xor_sync(0xffffffffu, c, o);
    c *= 1.1f;
    scs[16 + lane] = c * sqrtf(__uint_as_float(r[0])); scs[48 + lane] = c * sqrtf(__uint_as_float(r[1]));
    if (lane == 0) scs[1] = c * 24.f;
}

__global__ void __cluster_dims__(3, 1, 1) __launch_bounds__(384, 1)
k_chain(const __grid_constant__ CUtensorMap tmx, const __grid_constant__ CUtensorMap tmq, const __grid_constant__ CUtensorMap tmk,
        const __grid_constant__ CUtensorMap tmv, const __grid_constant__ CUtensorMap tmo, const bf16* __restrict__ mem0, const bf16* __restrict__ xg, const uint32_t ones) {
    extern __shared__ __align__(1024) unsigned char smem_raw[];
    const uint32_t sbase = smem_u32(smem_raw);
    const int cta = blockIdx.x, h = cta / 3, role = cta - 3 * h;
    const int tid = threadIdx.x, warp = __shfl_sync(0xffffffffu, tid >> 5, 0), lane_o = tid & 31;
    TS3C(0);
    asm volatile("griddepcontrol.launch_dependents;" ::: "memory");
    if (tid == 0) {
#pragma unroll
        for (int i = 0; i < 14; i++) mbar_init(sbase + SM_BAR + 8 * i, 1);
        asm volatile("fence.mbarrier_init.release.cluster;" ::: "memory");
        fence_async();
        mbar_expect(sbase + B_W0, DM * DH * 2 / 6 * WO_AFTER);
        mbar_expect(sbase + B_W1, DM * DH * 2 / 6 * (6 - WO_AFTER));
#pragma unroll
        for (int i = 0; i < 18; i++) {
            const CUtensorMap* tw = role == 2 ? &tmv : ((i & 1) ? &tmk : &tmq);
            asm volatile("cp.async.bulk.tensor.2d.shared::cluster.global.tile.mbarrier::complete_tx::bytes [%0], [%1, {%2, %3}], [%4];"
                         :: "r"(sbase + SM_WS + i * 8192), "l"(tw), "r"(h * DH + (role == 2 ? (i & 1) : role) * 64), "r"((i >> 1) * 64),
                            "r"(sbase + (i < 3 * WO_AFTER ? B_W0 : B_W1)) : "memory");
        }
        reinterpret_cast<float*>(smem_raw + SM_SC)[2] = 1.f;
    }
    __syncthreads();
    TS3C(8);
    if (warp < 8) {
        uint32_t wreg[36 - NS][4];
        {
            bf16 mv[18];
            uint4 xv[9];
#pragma unroll
            for (int j = 0; j < 18; j++) mv[j] = mem0[tid + 256 * j];
            if (cta < NSEG) {
#pragma unroll
                for (int k = 0; k < 9; k++) xv[k] = __ldg(reinterpret_cast<const uint4*>(xg + (size_t)(cta * SEG + (tid >> 3)) * DM) + (tid & 7) + 8 * k);
            }
#pragma unroll
            for (int j = 0; j < 18; j++) {
                const int i = tid + 256 * j, tok = i / DM, dcol = i - DM * tok;
                reinterpret_cast<bf16*>(smem_raw + SM_M)[dcol * 8 + tok] = mv[j];
            }
            if (cta < NSEG) {
                float t = 0.f;
#pragma unroll
                for (int k = 0; k < 9; k++) t += sumsq8(xv[k]);
                t += __shfl_xor_sync(0xffffffffu, t, 1); t += __shfl_xor_sync(0xffffffffu, t, 2); t += __shfl_xor_sync(0xffffffffu, t, 4);
                const uint32_t m = __reduce_max_sync(0xffffffffu, __float_as_uint(t));
                if (lane_o == 0) reinterpret_cast<uint32_t*>(smem_raw + SM_SC)[260 + warp] = m;
            }
        }
        {
            const int lane = lane_o;
            const uint32_t a = w_addr(sbase, warp, lane);
            mbar_wait(sbase + B_W0, 0);
            if (tid == 32) {
                mbar_expect(sbase + B_WO, DH * WOC * 2);
#pragma unroll
                for (int i = 0; i < 3; i++)
                    asm volatile("cp.async.bulk.tensor.2d.shared::cluster.global.tile.mbarrier::complete_tx::bytes [%0], [%1, {%2, %3}], [%4];"
                                 :: "r"(sbase + SM_STWO + i * 16384), "l"(&tmo), "r"(role * WOC + i * 64), "r"(h * DH), "r"(sbase + B_WO) : "memory");
            }
            __syncwarp();
            mbar_wait(sbase + B_W1, 0);
            TS3C(2);
#pragma unroll
            for (int ks = NS; ks < 36; ks++) ldsm_x4_t(wreg[ks - NS], a + (ks >> 2) * 16384 + (ks & 3) * 2048);
        }
        named_bar(7, 256);
        asm volatile("barrier.cluster.arrive.relaxed.aligned;" ::: "memory");
        TS3C(3);
        auto xproj1 = [&](float (&acc)[16], int j) {
            const uint32_t dlo = __shfl_sync(0xffffffffu, (uint32_t)smem_desc(sbase + SM_X + (j % 3) * XBUF, 16, 1024), 0);
            wg_fence();
#pragma unroll
            for (int ks = NS; ks < NS + NC1; ks++)
                wgmma_n32(acc, wreg[ks - NS], ((uint64_t)0x40000040u << 32) | (uint64_t)(dlo + (uint32_t)((ks >> 2) * 256 + (ks & 3) * 2)), ks > NS);
            wg_commit();
            wg_wait0();
        };
        auto xproj2 = [&](float (&acc)[16], int j) {
            int lane = lane_o;
            asm volatile("" : "+r"(lane));
            const uint32_t dlo = __shfl_sync(0xffffffffu, (uint32_t)smem_desc(sbase + SM_X + (j % 3) * XBUF, 16, 1024), 0);
            const uint64_t da = smem_desc(sbase + SM_WS + (warp >> 2) * 8192, 1024, 1024) | (1ull << 62);
            wg_fence();
#pragma unroll
            for (int ks = 0; ks < NS; ks++)
                wgmma_n32_ss(acc, da + (uint64_t)((ks >> 2) * 1024 + (ks & 3) * 128), ((uint64_t)0x40000040u << 32) | (uint64_t)(dlo + (uint32_t)((ks >> 2) * 256 + (ks & 3) * 2)), NC1 > 0 || ks > 0);
#pragma unroll
            for (int ks = NS + NC1; ks < XK; ks++)
                wgmma_n32(acc, wreg[ks - NS], ((uint64_t)0x40000040u << 32) | (uint64_t)(dlo + (uint32_t)((ks >> 2) * 256 + (ks & 3) * 2)), 1);
            wg_commit();
            wg_wait0();
            const uint32_t off = sbase + SM_T + (j & 3) * TBUF + (DH + warp * 16 + (lane & 15)) * 16 + (lane >> 4) * (DH * 16);
            stsm_x4(off, pack_bf16(acc[0], acc[1]), pack_bf16(acc[2], acc[3]), pack_bf16(acc[4], acc[5]), pack_bf16(acc[6], acc[7]));
            stsm_x4(off + 2 * DH * 16, pack_bf16(acc[8], acc[9]), pack_bf16(acc[10], acc[11]), pack_bf16(acc[12], acc[13]), pack_bf16(acc[14], acc[15]));
        };
        if (tid == 0) {
            fence_async();
            mbar_expect(sbase + B_XT, XBUF);
            for (int i = 0; i < 3; i++) tma_x(sbase + SM_X, &tmx, 0, i, sbase + B_XT);
            mbar_expect(sbase + B_XT + 8, XBUF);
            for (int i = 0; i < 3; i++) tma_x(sbase + SM_X + XBUF, &tmx, 1, i, sbase + B_XT + 8);
            for (int i = 0; i < 2; i++) {
                mbar_expect(sbase + B_SB + 8 * i, role == 2 ? 2560 : 1280 + 2048);
                if (role != 2) mbar_expect(sbase + B_VX + 8 * i, 8192);
            }
        }
        if (cta < NSEG && warp == 1) {
            const uint32_t mm = __reduce_max_sync(0xffffffffu, reinterpret_cast<uint32_t*>(smem_raw + SM_SC)[260 + (lane_o & 7)]);
            if (lane_o == 0) asm volatile("st.volatile.global.u32 [%0], %1;" :: "l"(&g_rx[cta]), "r"(mm | 1u) : "memory");
        }
        __syncwarp();
        {
            float n[4][4];
#pragma unroll
            for (int i = 0; i < 4; i++) { n[i][0] = n[i][1] = n[i][2] = n[i][3] = 0.f; }
            if (role == 2) {
#pragma unroll
                for (int ks = 0; ks < NS; ks++) {
                    uint32_t w[4];
                    ldsm_x4_t(w, w_addr(sbase, warp, lane_o) + (ks >> 2) * 16384 + (ks & 3) * 2048);
#pragma unroll
                    for (int i = 0; i < 4; i++) mma_k8(n[i], w[i & 2], w[(i & 2) + 1], w[i]);
                }
#pragma unroll
                for (int ks = 0; ks < 36 - NS; ks++)
#pragma unroll
                    for (int i = 0; i < 4; i++) mma_k8(n[i], wreg[ks][i & 2], wreg[ks][(i & 2) + 1], wreg[ks][i]);
            }
            const int g = lane_o >> 2, tq = lane_o & 3;
            float t = (g >> 1) == tq ? ((g & 1) ? (n[0][1] + n[1][3]) + (n[2][1] + n[3][3]) : (n[0][0] + n[1][2]) + (n[2][0] + n[3][2])) : 0.f;
#pragma unroll
            for (int o = 16; o; o >>= 1) t += __shfl_xor_sync(0xffffffffu, t, o);
            if (lane_o == 0) reinterpret_cast<float*>(smem_raw + SM_SC)[8 + warp] = t;
            __syncwarp();
            bar_arrive(8, 384);
        }
        mbar_wait(sbase + B_XT, 0);
        { float acc[16]; xproj1(acc, 0); xproj2(acc, 0); }
        fence_async();
        named_bar(7, 256);
        asm volatile("barrier.cluster.wait.aligned;" ::: "memory");
        asm volatile("barrier.cluster.arrive.relaxed.aligned;" ::: "memory");
        if (tid == 0 && role == 2) {
            bulk_s2s(mapa(sbase + SM_VX, 0), sbase + SM_T + DH * 16, 8192, mapa(sbase + B_VX, 0));
            bulk_s2s(mapa(sbase + SM_VX, 1), sbase + SM_T + DH * 16, 8192, mapa(sbase + B_VX, 1));
        }
        __syncwarp();
        mbar_wait(sbase + B_XT + 8, 0);
        { float acc[16]; xproj1(acc, 1); xproj2(acc, 1); }
        asm volatile("barrier.cluster.wait.aligned;" ::: "memory");
        if (role != 2) bar_arrive(9, 384);
        uint32_t ws[NS][4];
#pragma unroll
        for (int ks = NS - NP; ks < NS; ks++) ldsm_x4_t(ws[ks], w_addr(sbase, warp, lane_o) + (ks >> 2) * 16384 + (ks & 3) * 2048);
        TS3C(4);
        for (int s = 0; s < NSEG; s++) {
            int lane = lane_o;
            asm volatile("" : "+r"(lane));
            uint32_t v0, v1;
            {
#pragma unroll
                for (int ks = 0; ks < NS - NP; ks++) ldsm_x4_t(ws[ks], w_addr(sbase, warp, lane) + (ks >> 2) * 16384 + (ks & 3) * 2048);
                FS(0, ws[0][0]);
                named_bar(1, 384);
                float acc[2][4], minv;
                const uint32_t b_base = sbase + SM_M + lane * 16;
                uint32_t b[3][4];
#pragma unroll
                for (int kk = 0; kk < 3; kk++) ldsm_x4_t(b[kk], b_base + kk * 512);
                FS(1, b[0][0]);
#pragma unroll
                for (int kk = 0; kk < 18; kk++) {
                    if (kk == 0) {
                        mma_z(acc[0], ws[0], b[0][0], b[0][1]);
                        mma_z(acc[1], ws[1], b[0][2], b[0][3]);
                    } else if (2 * kk < NS) {
                        mma_bf16(acc[0], ws[2 * kk < NS ? 2 * kk : 0], b[kk % 3][0], b[kk % 3][1]);
                        mma_bf16(acc[1], ws[2 * kk < NS ? 2 * kk + 1 : 0], b[kk % 3][2], b[kk % 3][3]);
                    } else {
                        mma_bf16(acc[0], wreg[2 * kk >= NS ? 2 * kk - NS : 0], b[kk % 3][0], b[kk % 3][1]);
                        mma_bf16(acc[1], wreg[2 * kk >= NS ? 2 * kk - NS + 1 : 0], b[kk % 3][2], b[kk % 3][3]);
                    }
                    if (kk + 3 < 18) ldsm_x4_t(b[kk % 3], b_base + (kk + 3) * 512);
                    if (kk + 3 == 17) {
                        asm volatile("ld.shared.f32 %0, [%1];" : "=f"(minv) : "r"(sbase + SM_SC + 8) : "memory");
                    }
                }
                v0 = pack_bf16((acc[0][0] + acc[1][0]) * minv, (acc[0][1] + acc[1][1]) * minv);
                v1 = pack_bf16((acc[0][2] + acc[1][2]) * minv, (acc[0][3] + acc[1][3]) * minv);
                FS(2, v0);
            }
            const uint32_t tb = sbase + SM_T + (s & 3) * TBUF;
            if (role == 2 && s + 1 < NSEG) {
                const uint32_t fo = (uint32_t)(warp * 256 + lane * 8);
                const uint32_t rb0 = mapa(sbase, 0), rb1 = mapa(sbase, 1);
                st_async64(rb0 + SM_VM + fo, v0, v1, rb0 + B_SB + 8 * (s & 1));
                st_async64(rb1 + SM_VM + fo, v0, v1, rb1 + B_SB + 8 * (s & 1));
                asm volatile("st.shared.v2.u32 [%0], {%1,%2};" :: "r"(sbase + SM_VM + fo), "r"(v0), "r"(v1) : "memory");
            }
            asm volatile("stmatrix.sync.aligned.m8n8.x2.shared.b16 [%0], {%1,%2};" :: "r"(tb + warp * 256 + (lane & 15) * 16), "r"(v0), "r"(v1) : "memory");
            if (s + 1 < NSEG) {
                if (warp == 7 && role != 2) {
                    const uint32_t d0 = sbase + SM_S + role * 1280 + lane * 8, bo = sbase + B_SB + 8 * (s & 1);
                    const uint32_t d1 = mapa(d0, role ^ 1), m1 = mapa(bo, role ^ 1), d2 = mapa(d0, 2), m2 = mapa(bo, 2);
                    const uint32_t ka = tb + (64 + (lane & 7) + ((lane >> 3) & 1) * 16 + (lane >> 4) * 8) * 16;
                    uint32_t kf[2][4];
                    named_bar(2, 384);
#pragma unroll
                    for (int k2 = 0; k2 < 2; k2++) ldsm_x4_t(kf[k2], ka + k2 * 512);
                    score_group(tb + lane * 16, kf, d0, d1, m1, d2, m2);
                    bar_arrive(6, 160);
                } else bar_arrive(2, 384);
            }
            FS(11, 0);
            __syncwarp();
            if (s + 2 < NSEG) {
                if (warp == 6) mbar_wait(sbase + B_XT + 8 * ((s + 2) % 3), (uint32_t)((s + 2) / 3) & 1u);
                if (role != 2) named_bar(5, 384);
                else {
                    fence_async();
                    named_bar(7, 256);
                }
                float xacc[16];
                if (NC1 > 0) xproj1(xacc, s + 2);
                FS(9, __float_as_uint(xacc[0]));
                if (tid == 0 && role == 2) vx_copy(sbase, s + 1, 0);
                __syncwarp();
                if (role != 2) fence_async();
                FS(14, 0);
                named_bar(4, 384);
                xproj2(xacc, s + 2);
                FS(7, __float_as_uint(xacc[0]));
            }
            if (s >= NSEG - PROMPT) {
                fence_async();
                named_bar(7, 256);
                if (tid == 192) {
                    store_tile(s, h, role, tb);
                    asm volatile("cp.async.bulk.wait_group 0;" ::: "memory");
                    asm volatile("red.relaxed.gpu.global.add.u32 [%0], 1;" :: "l"(&g_flag[s * NH + h]) : "memory");
                }
                __syncwarp();
            }
        }
    } else {
        float* scs = reinterpret_cast<float*>(smem_raw + SM_SC);
        uint32_t wo[3][8][4];
        {
            const int pt = tid - 256, lane = lane_o, wq = warp - 8, g = lane >> 2, tq = lane & 3;
            asm volatile("barrier.cluster.arrive.relaxed.aligned;" ::: "memory");
            if (pt >= 64 && pt < 88) {
                *reinterpret_cast<uint4*>(g_acc + cta * 1024 + (pt - 64) * 16) = make_uint4(0u, 0u, 0u, 0u);
                __threadfence();
            }
            __syncwarp();
            mbar_wait(sbase + B_WO, 0);
            float c0 = 0.f;
#pragma unroll
            for (int t = 0; t < 3; t++) {
                const int T = 3 * wq + t;
                const uint32_t a = sbase + SM_STWO + (T >> 2) * 16384 + ((lane >> 4) * 8 + (lane & 7)) * 128 + ((((T & 3) * 2 + ((lane >> 3) & 1)) ^ (lane & 7)) << 4);
#pragma unroll
                for (int kk = 0; kk < 8; kk++) ldsm_x4_t(wo[t][kk], a + ((2 * wq + kk) & 7) * 2048);
                float n[4][4];
#pragma unroll
                for (int i = 0; i < 4; i++) { n[i][0] = n[i][1] = n[i][2] = n[i][3] = 0.f; }
#pragma unroll
                for (int kk = 0; kk < 8; kk++)
#pragma unroll
                    for (int i = 0; i < 4; i++) mma_k8(n[i], wo[t][kk][i & 2], wo[t][kk][(i & 2) + 1], wo[t][kk][i]);
                if ((g >> 1) == tq) c0 = fmaxf(c0, (g & 1) ? fmaxf(n[0][1] + n[2][1], n[1][3] + n[3][3]) : fmaxf(n[0][0] + n[2][0], n[1][2] + n[3][2]));
            }
            c0 = __uint_as_float(__reduce_max_sync(0xffffffffu, __float_as_uint(c0)));
            if (lane == 0) scs[256 + wq] = c0;
            named_bar(8, 384);
            if (pt == 0) {
                const float a = fmaxf(fmaxf(scs[256], scs[257]), fmaxf(scs[258], scs[259]));
                const float b = ((scs[8] + scs[9]) + (scs[10] + scs[11])) + ((scs[12] + scs[13]) + (scs[14] + scs[15]));
                st_vol_u2(&g_norm[cta], make_uint2(__float_as_uint(a) | 1u, __float_as_uint(b) | 1u));
            }
            if (pt == 32) {
                fence_async();
                mbar_expect(sbase + B_XT + 16, XBUF);
                for (int i = 0; i < 3; i++) tma_x(sbase + SM_X + 2 * XBUF, &tmx, 2, i, sbase + B_XT + 16);
            }
            __syncwarp();
            asm volatile("barrier.cluster.wait.aligned;" ::: "memory");
            asm volatile("barrier.cluster.arrive.relaxed.aligned;" ::: "memory");
            asm volatile("barrier.cluster.wait.aligned;" ::: "memory");
        }
        const int wq = warp - 8, lane = lane_o;
        const uint32_t l8 = __shfl_sync(0xffffffffu, sbase + lane * 8, lane), l16 = __shfl_sync(0xffffffffu, sbase + lane * 16, lane);
        const uint32_t goff = __shfl_sync(0xffffffffu, (lane >> 3) * 1024 + (lane & 7) * 16, lane);
        float minv = 1.f;
        uint32_t mx2 = 0u;
        bar_arrive(1, 384);
#pragma unroll
        for (int j = 0; j < 9; j++) {
            uint32_t w0, w1;
            lds64(w0, w1, l8 + SM_M + wq * 256 + j * 1024);
            mx2 = __vmaxu2(mx2, __vmaxu2(w0 & 0x7fff7fffu, w1 & 0x7fff7fffu));
        }
        if (wq == 1) norms_gather(lane, scs);
        if (role != 2) named_bar(9, 384);
        const uint32_t ka = sbase + SM_T + ((wq + 1) * DH + 64 + (lane & 7) + ((lane >> 3) & 1) * 16 + (lane >> 4) * 8) * 16;
        uint32_t kf[2][4];
#pragma unroll
        for (int k2 = 0; k2 < 2; k2++) ldsm_x4_t(kf[k2], ka + k2 * 512);
        int b3 = 0;
        for (int s = 0; s + 1 < NSEG; s++) {
            const int n3 = b3 == 2 ? 0 : b3 + 1;
            if (lane == 0) {
                if (wq == 1 && s + 3 < NSEG) tma_x_mc(sbase + SM_X + b3 * XBUF, &tmx, s + 3, role, sbase + B_XT + 8 * b3);
                if (wq == 3 && s > 0) {
                    store_tile(s - 1, h, role, sbase + SM_T + ((s - 1) & 3) * TBUF);
                    if (s > 1) {
                        asm volatile("cp.async.bulk.wait_group 1;" ::: "memory");
                        asm volatile("red.relaxed.gpu.global.add.u32 [%0], 1;" :: "l"(&g_flag[(s - 2) * NH + h]) : "memory");
                    }
                }
            }
            __syncwarp();
            if (wq == 2 && s > 1 && lane < 8) {
                *reinterpret_cast<uint4*>(g_acc + n3 * 128 + cta * 1024 + lane * 16) = make_uint4(0u, 0u, 0u, 0u);
            }
            if (s == 1 && tid == 383) {
                st_vol_u2(&g_norm[cta], make_uint2(0u, 0u));
                if (cta < NSEG) asm volatile("st.volatile.global.u32 [%0], %1;" :: "l"(&g_rx[cta]), "r"(0u) : "memory");
            }
            {
                const uint32_t mw = __reduce_max_sync(0xffffffffu, max(mx2 << 16, mx2 & 0xffff0000u));
                if (lane == 0) scs[4 + wq] = __uint_as_float(mw);
            }
            const uint32_t to = SM_T + (s & 3) * TBUF;
            const uint32_t ph = (uint32_t)(s >> 1) & 1u;
            if (role != 2) {
                const uint32_t so = SM_S + role * 1280 + (wq + 1) * 256, bo = sbase + B_SB + 8 * (s & 1);
                const uint32_t d1 = mapa(l8 + so, role ^ 1), m1 = mapa(bo, role ^ 1), d2 = mapa(l8 + so, 2), m2 = mapa(bo, 2);
                mbar_wait(sbase + B_VX + 8 * (s & 1), ph);
                FS(1, 0);
                named_bar(2, 384);
                score_group(l16 + to, kf, l8 + so, d1, m1, d2, m2);
                if (s + 2 < NSEG) bar_arrive(5, 384);
            } else named_bar(2, 384);
            const float4 m4 = *reinterpret_cast<const float4*>(scs + 4);
            const float c24 = scs[1], xb = scs[16 + s];
            unsigned char* dst = (g_acc + b3 * 128 + (role * 32 + wq * 8) * 1024) + goff;
            uint32_t vf[2][2][4], vm[2][2];
            {
                const uint32_t va = sbase + (role == 2 ? to + DH * 16 : SM_VX + (s & 1) * 8192) + (lane >> 4) * 2048 + (32 * wq + (lane & 15)) * 16;
#pragma unroll
                for (int i = 0; i < 4; i++) ldsm_x4(vf[i >> 1][i & 1], va + (i >> 1) * 256 + (i & 1) * 4096);
            }
            float scale;
            {
                const float bound = fmaxf(fmaxf(fmaxf(m4.x, m4.y), fmaxf(m4.z, m4.w)) * minv * c24, xb);
                int e = 141 - (int)((__float_as_uint(bound) >> 23) & 255u);
                e = e > 100 ? 100 : e;
                scale = __uint_as_float((uint32_t)(127 + e) << 23);
                minv = __uint_as_float((uint32_t)(127 - e) << 23);
            }
            FS(7, vf[1][1][0]);
            if (role != 2) named_bar(6, 160);
            if (role == 2) mbar_wait(sbase + B_SB + 8 * (s & 1), ph);
            float sv[5][2];
#pragma unroll
            for (int j = 0; j < 5; j++) lds64f(sv[j][0], sv[j][1], l8 + SM_S + (role & 1) * 1280 + j * 256);
            if (role != 2) mbar_wait(sbase + B_SB + 8 * (s & 1), ph);
            FS(6, 0);
            uint32_t p[5];
            {
                float sr[5][2];
#pragma unroll
                for (int j = 0; j < 5; j++) lds64f(sr[j][0], sr[j][1], l8 + SM_S + ((role & 1) ^ 1) * 1280 + j * 256);
                lds64(vm[0][0], vm[0][1], l8 + SM_VM + wq * 512);
                lds64(vm[1][0], vm[1][1], l8 + SM_VM + wq * 512 + 256);
#pragma unroll
                for (int j = 0; j < 5; j++) {
                    sv[j][0] += sr[j][0]; sv[j][1] += sr[j][1];
                }
                float mx = fmaxf(fmaxf(fmaxf(sv[0][0], sv[0][1]), fmaxf(sv[1][0], sv[1][1])), fmaxf(fmaxf(sv[2][0], sv[2][1]), fmaxf(sv[3][0], sv[3][1])));
                mx = fmaxf(mx, fmaxf(sv[4][0], sv[4][1]));
                mx = fmaxf(mx, __shfl_xor_sync(0xffffffffu, mx, 1));
                mx = fmaxf(mx, __shfl_xor_sync(0xffffffffu, mx, 2));
                constexpr float EC = MIMIC ? 1.4426950408889634f : (float)(1.4426950408889634 * 0.08838834764831845);
#pragma unroll
                for (int jj = 0; jj < 5; jj++) {
                    const int j = (jj + 1) % 5;
                    asm("ex2.approx.ftz.f32 %0, %1;" : "=f"(sv[j][0]) : "f"((sv[j][0] - mx) * EC));
                    asm("ex2.approx.ftz.f32 %0, %1;" : "=f"(sv[j][1]) : "f"((sv[j][1] - mx) * EC));
                    p[j] = pack_bf16(sv[j][0], sv[j][1]);
                }
            }
            FS(0, p[0]);
            uint32_t b[4][4];
            float zs[4];
            {
                float o0[2][4], o1[2][4];
                mma_z(o0[0], vf[0][0], p[1], p[2]);
                mma_z(o0[1], vf[1][0], p[1], p[2]);
                mma_z(o1[0], vf[0][1], p[3], p[4]);
                mma_z(o1[1], vf[1][1], p[3], p[4]);
                mma_k8(o0[0], vm[0][0], vm[0][1], p[0]);
                mma_k8(o0[1], vm[1][0], vm[1][1], p[0]);
                const uint32_t one4[4] = {0x3f803f80u, 0x3f803f80u, 0x3f803f80u, 0x3f803f80u};
                mma_z(zs, one4, p[1], p[2]);
                mma_bf16(zs, one4, p[3], p[4]);
                mma_k8(zs, one4[0], one4[1], p[0]);
                uint32_t ow[4];
#pragma unroll
                for (int m = 0; m < 2; m++) {
                    ow[2 * m] = pack_bf16(o0[m][0] + o1[m][0], o0[m][1] + o1[m][1]);
                    ow[2 * m + 1] = pack_bf16(o0[m][2] + o1[m][2], o0[m][3] + o1[m][3]);
                }
                stsm_x4(l16 + SM_O + wq * 512, ow[0], ow[1], ow[2], ow[3]);
                FS(2, 0);
#pragma unroll
                for (int i = 0; i < 4; i++) b[0][i] = movm(ow[i]);
            }
            float acc[3][2][4];
            named_bar(3, 128);
#pragma unroll
            for (int i = 1; i < 4; i++) ldsm_x4_t(b[i], l16 + SM_O + ((wq + i) & 3) * 512);
#pragma unroll
            for (int t = 0; t < 3; t++) { mma_z(acc[t][0], wo[t][0], b[0][0], b[0][1]); mma_z(acc[t][1], wo[t][1], b[0][2], b[0][3]); }
            float z0, z1;
            asm volatile("rcp.approx.ftz.f32 %0, %1;" : "=f"(z0) : "f"(zs[0]));
            asm volatile("rcp.approx.ftz.f32 %0, %1;" : "=f"(z1) : "f"(zs[1]));
            z0 *= scale; z1 *= scale;
            FS(3, b[1][0]);
#pragma unroll
            for (int i = 1; i < 4; i++)
#pragma unroll
                for (int t = 0; t < 3; t++) { mma_bf16(acc[t][0], wo[t][2 * i], b[i][0], b[i][1]); mma_bf16(acc[t][1], wo[t][2 * i + 1], b[i][2], b[i][3]); }
            {
                uint32_t w[6];
#pragma unroll
                for (int t = 0; t < 3; t++) {
                    w[2 * t] = pack_f16((acc[t][0][0] + acc[t][1][0]) * z0, (acc[t][0][1] + acc[t][1][1]) * z1);
                    w[2 * t + 1] = pack_f16((acc[t][0][2] + acc[t][1][2]) * z0, (acc[t][0][3] + acc[t][1][3]) * z1);
                }
                FS(8, w[5]);
                asm volatile("red.relaxed.gpu.global.add.noftz.v4.f16x2 [%0], {%1,%2,%3,%4};" :: "l"(dst), "r"(w[0]), "r"(w[1]), "r"(w[2]), "r"(0x3c00u) : "memory");
                asm volatile("red.relaxed.gpu.global.add.noftz.v4.f16x2 [%0], {%1,%2,%3,%4};" :: "l"(dst + 4096), "r"(w[3]), "r"(w[4]), "r"(w[5]), "r"(0x3c00u) : "memory");
            }
            FS(9, 0);
            const uint32_t t0 = clock32();
            if (s + 2 < NSEG) bar_arrive(4, 384);
            if (lane == 0) {
                if (wq == 0) scs[2] = minv;
                if (wq == 2 && role == 2 && s + 2 < NSEG) { while (clock32() - t0 < VX_DELAY) {} vx_copy(sbase, s + 1, 1); }
                if (s + 3 < NSEG) {
                    if (wq == 0) mbar_expect(sbase + B_SB + 8 * (s & 1), role == 2 ? 2560 : 1280 + 2048);
                    if (wq == 1) mbar_expect(sbase + B_XT + 8 * b3, XBUF);
                    if (wq == 3 && role != 2) mbar_expect(sbase + B_VX + 8 * (s & 1), 8192);
                }
            }
            __syncwarp();
#pragma unroll
            for (int k2 = 0; k2 < 2; k2++) ldsm_x4_t(kf[k2], ka + ((s + 1) & 3) * TBUF + k2 * 512);
            const uint4* src = reinterpret_cast<const uint4*>((g_acc + b3 * 128 + wq * 24576) + goff);
            while (clock32() - t0 < POLL_DELAY) {}
            mx2 = poll_mem(src, l16 + SM_M + wq * 2304, ones);
            b3 = n3;
        }
        if (ST_AT < 2 && tid == 352) {
            asm volatile("cp.async.bulk.wait_group 0;" ::: "memory");
            asm volatile("red.relaxed.gpu.global.add.u32 [%0], 1;" :: "l"(&g_flag[(NSEG - 3) * NH + h]) : "memory");
        }
    }
    TS3C(1);
    __syncwarp();
    cluster_sync_all();
}

extern "C" void kernel_launch(void* const* d_in, const int* in_sizes, int n_in, void* d_out, int out_size) {
    const bf16* x = (const bf16*)d_in[0];
    const bf16* mem0 = (const bf16*)d_in[1];
    const bf16* Wq = (const bf16*)d_in[2];
    const bf16* Wk = (const bf16*)d_in[3];
    const bf16* Wv = (const bf16*)d_in[4];
    const bf16* Wo = (const bf16*)d_in[5];
    const bf16* logA = (const bf16*)d_in[8];
    const bf16* Aim = (const bf16*)d_in[9];
    const bf16* Cre = (const bf16*)d_in[10];
    const bf16* Cim = (const bf16*)d_in[11];
    const bf16* logdt = (const bf16*)d_in[12];
    const bf16* dskip = (const bf16*)d_in[13];
    const bf16* gw = (const bf16*)d_in[14];
    bf16* out = (bf16*)d_out;
    static bool attr_done = false;
    typedef CUresult (*EncFn)(CUtensorMap*, CUtensorMapDataType, cuuint32_t, void*, const cuuint64_t*, const cuuint64_t*, const cuuint32_t*,
                              const cuuint32_t*, CUtensorMapInterleave, CUtensorMapSwizzle, CUtensorMapL2promotion, CUtensorMapFloatOOBfill);
    static EncFn enc = nullptr;
    if (!attr_done) {
        void* fn = nullptr;
        cudaDriverEntryPointQueryResult qr;
        cudaGetDriverEntryPoint("cuTensorMapEncodeTiled", &fn, cudaEnableDefault, &qr);
        enc = (EncFn)fn;
        cudaFuncSetAttribute(k_chain, cudaFuncAttributeMaxDynamicSharedMemorySize, 232448);
        cudaFuncSetAttribute(k_side, cudaFuncAttributeMaxDynamicSharedMemorySize, SIDE_SMEM);
        attr_done = true;
    }
    CUtensorMap tmx;
    {
        const cuuint64_t dims[3] = {64, (cuuint64_t)S_LEN, 9};
        const cuuint64_t strides[2] = {(cuuint64_t)DM * 2, 128};
        const cuuint32_t box[3] = {64, (cuuint32_t)SEG, 3};
        const cuuint32_t es[3] = {1, 1, 1};
        enc(&tmx, CU_TENSOR_MAP_DATA_TYPE_BFLOAT16, 3, (void*)x, dims, strides, box, es, CU_TENSOR_MAP_INTERLEAVE_NONE,
            CU_TENSOR_MAP_SWIZZLE_128B, CU_TENSOR_MAP_L2_PROMOTION_L2_128B, CU_TENSOR_MAP_FLOAT_OOB_FILL_NONE);
    }
    CUtensorMap tmw[3];
    for (int i = 0; i < 3; i++) {
        const cuuint64_t dims[2] = {(cuuint64_t)HD, (cuuint64_t)DM};
        const cuuint64_t strides[1] = {(cuuint64_t)HD * 2};
        const cuuint32_t box[2] = {64, 64};
        const cuuint32_t es[2] = {1, 1};
        enc(&tmw[i], CU_TENSOR_MAP_DATA_TYPE_BFLOAT16, 2, (void*)(i == 0 ? Wq : (i == 1 ? Wk : Wv)), dims, strides, box, es, CU_TENSOR_MAP_INTERLEAVE_NONE,
            CU_TENSOR_MAP_SWIZZLE_128B, CU_TENSOR_MAP_L2_PROMOTION_L2_256B, CU_TENSOR_MAP_FLOAT_OOB_FILL_NONE);
    }
    CUtensorMap tmo;
    {
        const cuuint64_t dims[2] = {(cuuint64_t)DM, (cuuint64_t)HD};
        const cuuint64_t strides[1] = {(cuuint64_t)DM * 2};
        const cuuint32_t box[2] = {64, 128};
        const cuuint32_t es[2] = {1, 1};
        enc(&tmo, CU_TENSOR_MAP_DATA_TYPE_BFLOAT16, 2, (void*)Wo, dims, strides, box, es, CU_TENSOR_MAP_INTERLEAVE_NONE,
            CU_TENSOR_MAP_SWIZZLE_128B, CU_TENSOR_MAP_L2_PROMOTION_L2_128B, CU_TENSOR_MAP_FLOAT_OOB_FILL_NONE);
    }
    k_chain<<<NCTA, 384, 232448>>>(tmx, tmw[0], tmw[1], tmw[2], tmo, mem0, x, 0xffffffffu);
    {
        cudaLaunchConfig_t cfg = {};
        cfg.gridDim = dim3(SD_NCTA); cfg.blockDim = dim3(512); cfg.dynamicSmemBytes = SIDE_SMEM; cfg.stream = cudaStreamPerThread;
        cudaLaunchAttribute at[1];
        at[0].id = cudaLaunchAttributeProgrammaticStreamSerialization;
        at[0].val.programmaticStreamSerializationAllowed = 1;
        cfg.attrs = at; cfg.numAttrs = 1;
        cudaLaunchKernelEx(&cfg, k_side, tmo, x, logA, Aim, Cre, Cim, logdt, Wo, dskip, gw, out);
    }
}
```

```cpp
#include <cuda_runtime.h>
#include <cuda.h>
#include <cuda_bf16.h>
#include <stdint.h>

typedef __nv_bfloat16 bf16;
#define LDV4 "ld.volatile.global.v4.u32 {%0,%1,%2,%3}, [%4];"
#define STV4 "st.volatile.global.v4.u32 [%0], {%1,%2,%3,%4};"
#define STV2 "st.volatile.global.v2.u32 [%0], {%1,%2};"

constexpr int S_LEN = 2048, DM = 576, NH = 32, DH = 128, HD = 4096, MEMT = 8, SEG = 32, NSEG = 64, NST = 128;

__device__ uint32_t g_gate[S_LEN];
constexpr int NCTA = NH * 3;
__device__ __align__(1024) unsigned char g_acc[96 * 1024];
__device__ __align__(128) uint2 g_norm[NCTA];
__device__ __align__(128) uint32_t g_rx[NSEG];
__device__ __align__(128) unsigned char g_qkv[NSEG][NH][3][10240];
__device__ __align__(128) bf16 g_ox[S_LEN * HD];
__device__ __align__(128) uint4 g_fp[4][72][7][128];
__device__ unsigned g_flag[NSEG * NH];
__device__ unsigned g_prog[NSEG / 2 * 8];
__device__ unsigned g_gcnt;
__device__ unsigned g_epoch;
__device__ __align__(16) bf16 g_y[DM * S_LEN];

#define TS3(slot) do {} while (0)
#define TS3P(slot) do {} while (0)
#define TSQ(slot) do {} while (0)
#define TS3W(slot) do {} while (0)
#define TSS(row, slot) do {} while (0)
#define TS3C(slot) do {} while (0)
#define TSG(i) do {} while (0)
#define FS(i, dep) do {} while (0)
__device__ __forceinline__ uint32_t smem_u32(const void* p) { return (uint32_t)__cvta_generic_to_shared(p); }
__device__ __forceinline__ float bf16r(float x) { return __bfloat162float(__float2bfloat16_rn(x)); }
__device__ __forceinline__ uint32_t pack_bf16(float lo, float hi) {
    __nv_bfloat162 v = __floats2bfloat162_rn(lo, hi);
    return *reinterpret_cast<uint32_t*>(&v);
}
__device__ __forceinline__ void ldsm_x4(uint32_t (&r)[4], uint32_t addr) {
    asm volatile("ldmatrix.sync.aligned.m8n8.x4.shared.b16 {%0,%1,%2,%3}, [%4];"
                 : "=r"(r[0]), "=r"(r[1]), "=r"(r[2]), "=r"(r[3]) : "r"(addr));
}
__device__ __forceinline__ void ldsm_x4_t(uint32_t (&r)[4], uint32_t addr) {
    asm volatile("ldmatrix.sync.aligned.m8n8.x4.trans.shared.b16 {%0,%1,%2,%3}, [%4];"
                 : "=r"(r[0]), "=r"(r[1]), "=r"(r[2]), "=r"(r[3]) : "r"(addr));
}
__device__ __forceinline__ void mma_bf16(float (&d)[4], const uint32_t (&a)[4], uint32_t b0, uint32_t b1) {
    asm volatile("mma.sync.aligned.m16n8k16.row.col.f32.bf16.bf16.f32 {%0,%1,%2,%3}, {%4,%5,%6,%7}, {%8,%9}, {%0,%1,%2,%3};"
                 : "+f"(d[0]), "+f"(d[1]), "+f"(d[2]), "+f"(d[3])
                 : "r"(a[0]), "r"(a[1]), "r"(a[2]), "r"(a[3]), "r"(b0), "r"(b1));
}
__device__ __forceinline__ uint2 ld_vol_u2(const uint2* p) {
    uint2 v; asm volatile("ld.volatile.global.v2.u32 {%0,%1}, [%2];" : "=r"(v.x), "=r"(v.y) : "l"(p) : "memory"); return v;
}
__device__ __forceinline__ void st_vol_u2(uint2* p, uint2 v) {
    asm volatile(STV2 :: "l"(p), "r"(v.x), "r"(v.y) : "memory");
}
__device__ __forceinline__ unsigned ld_acq(const unsigned* p) {
    unsigned v; asm volatile("ld.acquire.gpu.global.u32 %0, [%1];" : "=r"(v) : "l"(p) : "memory"); return v;
}
#define XK 36
#define RFENCE 0
#define NC1 12
#define NS 6
#define NP 2
#define ST_AT 0
#define XT_AT 0
#define XT_DELAY 250
#define X_SZ 10240u - qoff
#define ST_DELAY 300
#define PF_DELAY 900
#define MIMIC 0
#define VX_MODE 3
#define VX_DELAY 100
#define POLL_DELAY 550
#define WO_AFTER 4
constexpr int PROMPT = 2;
constexpr unsigned SPIN_LIMIT = 1u << 20;

constexpr int SD_CH = 16;
constexpr int SD_NCTA = DM / SD_CH;
constexpr int SD_USTR = 40 * 72;
constexpr int SD_KLEN = 2048 + 32;
constexpr int SD_TAB = 1024;
constexpr int SD_SMEM = SD_CH * SD_USTR * 2 + 8 * (SD_KLEN * 2 + SD_TAB * 4);

__device__ __forceinline__ uint32_t lds32(uint32_t a) { uint32_t v; asm volatile("ld.shared.u32 %0, [%1];" : "=r"(v) : "r"(a)); return v; }
template <int NT0>
__device__ __forceinline__ void conv_oct(float (&acc)[4][4][4], uint32_t (&Aq)[7][4], uint32_t (&raw)[16], uint32_t kaddr, uint32_t sel, uint32_t uaddr) {
#pragma unroll 1
    for (int k = 8 * NT0; k < 8 * NT0 + 8; k++) {
        uint32_t b[4][2][4];
#pragma unroll
        for (int nt = NT0; nt < 4; nt++) {
            const uint32_t ua = uaddr + (uint32_t)((8 * nt - k) * 144);
            ldsm_x4(b[nt][0], ua);
            ldsm_x4(b[nt][1], ua + 64);
        }
#pragma unroll
        for (int i = 0; i < 3; i++) { Aq[i][0] = Aq[i + 4][0]; Aq[i][1] = Aq[i + 4][1]; Aq[i][2] = Aq[i + 4][2]; Aq[i][3] = Aq[i + 4][3]; }
#pragma unroll
        for (int e = 0; e < 4; e++) {
            const uint32_t a0 = __byte_perm(raw[4 * e], raw[4 * e + 1], sel), a1 = __byte_perm(raw[4 * e + 2], raw[4 * e + 3], sel);
            Aq[3 + e][0] = a0; Aq[3 + e][3] = a0; Aq[3 + e][1] = a1; Aq[3 + e][2] = Aq[2 + e][1];
        }
        if (k + 1 < 32) {
#pragma unroll
            for (int e = 0; e < 4; e++) {
                const uint32_t a = kaddr - 32u * (uint32_t)(4 * (k + 1) + e);
                raw[4 * e] = lds32(a); raw[4 * e + 1] = lds32(a + 4); raw[4 * e + 2] = lds32(a - 16); raw[4 * e + 3] = lds32(a - 12);
            }
        }
#pragma unroll
        for (int nt = NT0; nt < 4; nt++)
#pragma unroll
            for (int kt = 0; kt < 4; kt++)
#pragma unroll
                for (int mt = 0; mt < 4; mt++)
                    mma_bf16(acc[mt][nt], Aq[mt - kt + 3], b[nt][kt >> 1][(kt & 1) * 2], b[nt][kt >> 1][(kt & 1) * 2 + 1]);
    }
}

__device__ __forceinline__ void named_bar(int id, int n) { asm volatile("bar.sync %0, %1;" :: "r"(id), "r"(n) : "memory"); }
__device__ __forceinline__ void cexp_t(float lr, float turns, float& re, float& im) {
    float m;
    asm("ex2.approx.ftz.f32 %0, %1;" : "=f"(m) : "f"(lr));
    const float a = (turns - rintf(turns)) * 6.283185307179586f;
    re = m * __cosf(a); im = m * __sinf(a);
}
__device__ __forceinline__ void csq(float& re, float& im) { const float r = re * re - im * im; im = 2.f * re * im; re = r; }
__device__ __forceinline__ uint32_t tf32r(float v) { return __float_as_uint(v) + 0x1000u; }
__device__ __forceinline__ void kb_mma(float (&d)[4], uint32_t a0, uint32_t a1, uint32_t a2, uint32_t a3, float cr, float ci, float er, float ei) {
    const uint32_t b0 = tf32r(cr * er - ci * ei), b1 = tf32r(-(cr * ei + ci * er));
    asm volatile("mma.sync.aligned.m16n8k8.row.col.f32.tf32.tf32.f32 {%0,%1,%2,%3}, {%4,%5,%6,%7}, {%8,%9}, {%0,%1,%2,%3};"
                 : "+f"(d[0]), "+f"(d[1]), "+f"(d[2]), "+f"(d[3]) : "r"(a0), "r"(a1), "r"(a2), "r"(a3), "r"(b0), "r"(b1));
}
template <int C>
__device__ __forceinline__ void expand_taps(const float* kd, bf16* kr, int l0, int lane) {
    uint32_t w[4];
#pragma unroll
    for (int e = 0; e < 4; e++) {
        float v[2];
#pragma unroll
        for (int k = 0; k < 2; k++) {
            const int l = l0 + 8 * lane + 7 - 2 * e - k;
            const int idx = C == 0 ? l : 128 * C + ((l + (1 << (C > 0 ? C - 1 : 0)) - 1 + ((l >> C) & 1)) >> C);
            v[k] = kd[idx];
        }
        w[e] = pack_bf16(v[0], v[1]);
    }
    *reinterpret_cast<uint4*>(kr + 2040 - l0 - 8 * lane) = make_uint4(w[0], w[1], w[2], w[3]);
}

__device__ __forceinline__ void s4d_phase(unsigned char* smem_raw, const bf16* __restrict__ x, const bf16* __restrict__ logA,
                                          const bf16* __restrict__ Aim, const bf16* __restrict__ Cre, const bf16* __restrict__ Cim,
                                          const bf16* __restrict__ logdt, const bf16* __restrict__ wslice) {
    bf16* u_all = reinterpret_cast<bf16*>(smem_raw);
    bf16* k_all = u_all + SD_CH * SD_USTR;
    float* tab_all = reinterpret_cast<float*>(k_all + 8 * SD_KLEN);
    const int tid = threadIdx.x, warp = tid >> 5, lane = tid & 31;
    const int d0 = blockIdx.x * SD_CH;
    bf16* kr = k_all + warp * SD_KLEN;
    float* tab = tab_all + warp * SD_TAB;
    const int g = lane >> 2, tq = lane & 3;
    for (int i = lane; i < 8 * 72 / 2; i += 32) {
        reinterpret_cast<uint32_t*>(u_all + (2 * warp) * SD_USTR)[i] = 0u;
        reinterpret_cast<uint32_t*>(u_all + (2 * warp + 1) * SD_USTR)[i] = 0u;
    }
    if (lane < 16) reinterpret_cast<uint32_t*>(kr + 2048)[lane] = 0u;
    TS3(20);
#pragma unroll 1
    for (int op = 0; op < 4; op++) {
        const bool build = op == 0 || op == (warp < 4 ? 2 : 1);
        const int ch = build ? (op > 0) : (op == 3);
        const int d = d0 + 2 * warp + ch;
        bf16* us = u_all + (2 * warp + ch) * SD_USTR;
        if (build) {
        float k2048 = 0.f;
        {
            const float dt = bf16r(expf(__bfloat162float(logdt[d])));
#pragma unroll
            for (int j = 0; j < 4; j++) {
                const int n = lane + 32 * j;
                const float zl = -bf16r(expf(__bfloat162float(logA[d * NST + n]))) * dt * 1.4426950408889634f;
                const float zt = __bfloat162float(Aim[d * NST + n]) * dt * 0.15915494309189535f;
                const float cr = 2.f * (__bfloat162float(Cre[d * NST + n]) * dt), ci = 2.f * (__bfloat162float(Cim[d * NST + n]) * dt);
                float ar, ai, br, bi, er, ei;
                cexp_t(zl * 8.f, zt * 8.f, ar, ai);
                cexp_t(zl * 128.f, zt * 128.f, br, bi);
                cexp_t(zl * 2048.f, zt * 2048.f, er, ei);
                k2048 += cr * er - ci * ei;
                *reinterpret_cast<float4*>(tab + n * 8) = make_float4(zl, zt, cr, ci);
                *reinterpret_cast<float4*>(tab + n * 8 + 4) = make_float4(ar, ai, br, bi);
            }
#pragma unroll
            for (int o = 16; o; o >>= 1) k2048 += __shfl_xor_sync(0xffffffffu, k2048, o);
        }
        __syncwarp();
        {
            float kc[5][4];
#pragma unroll
            for (int i = 0; i < 5; i++) { kc[i][0] = kc[i][1] = kc[i][2] = kc[i][3] = 0.f; }
            const float gf = (float)g;
#pragma unroll 2
            for (int ks = 0; ks < 32; ks++) {
                const float4 p0 = *reinterpret_cast<const float4*>(tab + (4 * ks + tq) * 8);
                const float4 p1 = *reinterpret_cast<const float4*>(tab + (4 * ks + tq) * 8 + 4);
                float wr[4], wi[4], vr, vi;
                cexp_t(p0.x * gf, p0.y * gf, wr[0], wi[0]);
                vr = wr[0] * p1.x - wi[0] * p1.y; vi = wr[0] * p1.y + wi[0] * p1.x;
#pragma unroll
                for (int c = 1; c < 4; c++) { wr[c] = wr[c - 1]; wi[c] = wi[c - 1]; csq(wr[c], wi[c]); }
                float er = wr[3], ei = wi[3];
                csq(er, ei);
                {
                    const uint32_t a0 = tf32r(wr[0]), a1 = tf32r(vr), a2 = tf32r(wi[0]), a3 = tf32r(vi);
                    kb_mma(kc[0], a0, a1, a2, a3, p0.z, p0.w, er, ei);
                    const float t = er * p1.z - ei * p1.w; ei = er * p1.w + ei * p1.z; er = t;
                    kb_mma(kc[1], a0, a1, a2, a3, p0.z, p0.w, er, ei);
                }
#pragma unroll
                for (int c = 1; c < 4; c++) {
                    csq(vr, vi); csq(er, ei);
                    kb_mma(kc[1 + c], tf32r(wr[c]), tf32r(vr), tf32r(wi[c]), tf32r(vi), p0.z, p0.w, er, ei);
                }
            }
            __syncwarp();
#pragma unroll
            for (int i = 0; i < 5; i++) {
                float* q = tab + 128 * i + 32 * tq + g;
                q[0] = kc[i][0]; q[16] = kc[i][1]; q[8] = kc[i][2]; q[24] = kc[i][3];
            }
            if (lane == 0) tab[640] = k2048;
            __syncwarp();
        }
        } else {
        if (ch == 0) named_bar(warp < 4 ? 1 : 2, 256);
        else {
#pragma unroll
            for (int i = 0; i < 4; i++) asm volatile("prefetch.global.L2 [%0];" :: "l"(wslice + (size_t)((tid & 127) + 128 * i) * DM));
        }
        float acc[4][4][4];
#pragma unroll
        for (int i = 0; i < 4; i++)
#pragma unroll
            for (int j = 0; j < 4; j++) { acc[i][j][0] = acc[i][j][1] = acc[i][j][2] = acc[i][j][3] = 0.f; }
        {
            uint32_t Aq[7][4], raw[16];
#pragma unroll
            for (int i = 0; i < 7; i++) { Aq[i][0] = Aq[i][1] = Aq[i][2] = Aq[i][3] = 0u; }
            const int j0 = 2047 - g + 2 * tq;
            const uint32_t kaddr = smem_u32(kr) + 2u * (uint32_t)(j0 & ~1);
            const uint32_t sel = (j0 & 1) ? 0x5432u : 0x3210u;
            const uint32_t uaddr = smem_u32(us) + (uint32_t)(((lane & 7) + 8) * 144 + (lane >> 3) * 16);
#pragma unroll
            for (int e = 0; e < 4; e++) {
                const uint32_t a = kaddr - 32u * (uint32_t)e;
                raw[4 * e] = lds32(a); raw[4 * e + 1] = lds32(a + 4); raw[4 * e + 2] = lds32(a - 16); raw[4 * e + 3] = lds32(a - 12);
            }
            conv_oct<0>(acc, Aq, raw, kaddr, sel, uaddr);
            conv_oct<1>(acc, Aq, raw, kaddr, sel, uaddr);
            conv_oct<2>(acc, Aq, raw, kaddr, sel, uaddr);
            conv_oct<3>(acc, Aq, raw, kaddr, sel, uaddr);
        }
        __syncwarp();
#pragma unroll
        for (int mt = 0; mt < 4; mt++)
#pragma unroll
            for (int nt = 0; nt < 4; nt++) {
                const int i0 = 8 * nt + 2 * tq, r = 16 * mt + g;
                us[64 * i0 + r] = __float2bfloat16_rn(acc[mt][nt][0]);
                us[64 * (i0 + 1) + r] = __float2bfloat16_rn(acc[mt][nt][1]);
                us[64 * i0 + r + 8] = __float2bfloat16_rn(acc[mt][nt][2]);
                us[64 * (i0 + 1) + r + 8] = __float2bfloat16_rn(acc[mt][nt][3]);
            }
        __syncwarp();
#pragma unroll
        for (int i = 0; i < 8; i++)
            *reinterpret_cast<uint4*>(g_y + (size_t)d * S_LEN + (lane + 32 * i) * 8) = *reinterpret_cast<const uint4*>(us + (lane + 32 * i) * 8);
        }
        if ((op & 1) == 0) {
            expand_taps<0>(tab, kr, 0, lane);
            expand_taps<1>(tab, kr, 256, lane);
            expand_taps<2>(tab, kr, 512, lane);
            expand_taps<2>(tab, kr, 768, lane);
#pragma unroll 1
            for (int i = 0; i < 4; i++) expand_taps<3>(tab, kr, 1024 + 256 * i, lane);
            __syncwarp();
        }
        TS3(21 + op);
    }
}
__device__ __forceinline__ void s4d_stage_u(unsigned char* smem_raw, const bf16* __restrict__ x, int pt) {
    bf16* u_all = reinterpret_cast<bf16*>(smem_raw);
    const int d0 = blockIdx.x * SD_CH;
#pragma unroll 1
    for (int b = 0; b < 4; b++) {
        uint4 v[8];
#pragma unroll
        for (int i = 0; i < 8; i++) {
            int c = pt + 128 * (8 * b + i);
            v[i] = *reinterpret_cast<const uint4*>(x + (size_t)(c >> 1) * DM + d0 + (c & 1) * 8);
        }
#pragma unroll
        for (int i = 0; i < 8; i++) {
            int c = pt + 128 * (8 * b + i), t = c >> 1;
            bf16* dst = u_all + (c & 1) * 8 * SD_USTR + (8 + (t >> 6)) * 72 + (t & 63);
            const bf16* pv = reinterpret_cast<const bf16*>(&v[i]);
#pragma unroll
            for (int ch = 0; ch < 8; ch++) dst[ch * SD_USTR] = pv[ch];
        }
    }
    asm volatile("bar.arrive 1, 256;" ::: "memory");
    asm volatile("bar.arrive 2, 256;" ::: "memory");
}

constexpr int WOC = DM / 3;
constexpr int TBUF = 5 * DH * 16;
constexpr int XBUF = SEG * DM * 2;
constexpr float ATT_SCALE = 0.08838834764831845f;
constexpr int SM_BAR = 0;
constexpr int B_SB = 0, B_VX = 16, B_XT = 32, B_W = 64, B_E = 136;
constexpr int SM_SC = 256;
constexpr int SM_F = SM_SC + 1280;
constexpr int SM_VM = SM_F + 2048;
constexpr int SM_S = SM_VM + 2048;
constexpr int SM_O = SM_S + 2560;
constexpr int SM_M = SM_O + 2048;
constexpr int SM_WS = 19456;
constexpr int SM_T = SM_WS + 32768;
constexpr int SM_VX = SM_T + 4 * TBUF;
constexpr int SM_X = SM_VX + 2 * 8192;
constexpr int SM_X01 = SM_WS + DM * DH * 2;
__host__ __device__ constexpr int x01_off(int b) { return b == 2 ? 2048 : SM_X01 + (b < 2 ? b + 6 : b - 3) * 8192; }
constexpr int SM_E = SM_WS + 6 * 16384;
constexpr int CH_SMEM = SM_X01 + 8 * 8192;
static_assert(SM_M + DM * 16 <= SM_WS && SM_X + 3 * XBUF <= CH_SMEM && CH_SMEM <= 232448 && SM_X % 1024 == 0 && SM_X01 % 1024 == 0 && SM_M >= 10240 && SM_F <= 2048, "smem");
__device__ __forceinline__ uint32_t clock32() { uint32_t t; asm volatile("mov.u32 %0, %%clock;" : "=r"(t) :: "memory"); return t; }

__device__ __forceinline__ uint32_t mapa(uint32_t a, uint32_t rank) {
    uint32_t r; asm volatile("mapa.shared::cluster.u32 %0, %1, %2;" : "=r"(r) : "r"(a), "r"(rank)); return r;
}
__device__ __forceinline__ void st_async32(uint32_t addr, uint32_t v, uint32_t mbar) {
    asm volatile("st.async.weak.shared::cluster.mbarrier::complete_tx::bytes.b32 [%0], %1, [%2];" :: "r"(addr), "r"(v), "r"(mbar) : "memory");
}
__device__ __forceinline__ void mbar_init(uint32_t bar, uint32_t cnt) {
    asm volatile("mbarrier.init.shared::cta.b64 [%0], %1;" :: "r"(bar), "r"(cnt) : "memory");
}
__device__ __forceinline__ void mbar_expect(uint32_t bar, uint32_t bytes) {
    asm volatile("mbarrier.arrive.expect_tx.shared::cta.b64 _, [%0], %1;" :: "r"(bar), "r"(bytes) : "memory");
}
__device__ __forceinline__ void mbar_wait(uint32_t bar, uint32_t parity) {
    unsigned it = 0;
    while (true) {
        uint32_t ok;
        asm volatile("{\n.reg .pred p;\nmbarrier.try_wait.parity.shared::cta.b64 p, [%1], %2;\nselp.u32 %0, 1, 0, p;\n}"
                     : "=r"(ok) : "r"(bar), "r"(parity) : "memory");
        if (ok || ++it >= SPIN_LIMIT) break;
    }
}
__device__ __forceinline__ void mbar_wait_long(uint32_t bar, uint32_t parity) {
    unsigned it = 0;
    while (true) {
        uint32_t ok;
        asm volatile("{\n.reg .pred p;\nmbarrier.try_wait.parity.shared::cta.b64 p, [%1], %2, %3;\nselp.u32 %0, 1, 0, p;\n}"
                     : "=r"(ok) : "r"(bar), "r"(parity), "r"(20000u) : "memory");
        if (ok || ++it >= SPIN_LIMIT) break;
    }
}
__device__ __forceinline__ uint64_t policy_evict_first() {
    uint64_t pol; asm volatile("createpolicy.fractional.L2::evict_first.b64 %0, 1.0;" : "=l"(pol)); return pol;
}
__device__ __forceinline__ void cluster_sync_all() {
    asm volatile("barrier.cluster.arrive.release.aligned;\nbarrier.cluster.wait.acquire.aligned;" ::: "memory");
}
__device__ __forceinline__ uint4 ld_vol_u4(const uint4* p) {
    uint4 v; asm volatile(LDV4 : "=r"(v.x), "=r"(v.y), "=r"(v.z), "=r"(v.w) : "l"(p) : "memory"); return v;
}
__device__ __forceinline__ void ld_vol_u4_p(uint4& v, const uint4* p, uint32_t pred) {
    asm volatile("{\n.reg .pred p;\nsetp.ne.u32 p, %5, 0;\n@p " LDV4 "\n}"
                 : "+r"(v.x), "+r"(v.y), "+r"(v.z), "+r"(v.w) : "l"(p), "r"(pred) : "memory");
}
__device__ __forceinline__ void st_vol_u4(uint4* p, uint4 v) {
    asm volatile(STV4 :: "l"(p), "r"(v.x), "r"(v.y), "r"(v.z), "r"(v.w) : "memory");
}
__device__ __forceinline__ void mma_bf16_r(float (&d)[4], uint32_t a0, uint32_t a1, uint32_t a2, uint32_t a3, uint32_t b0, uint32_t b1) {
    asm volatile("mma.sync.aligned.m16n8k16.row.col.f32.bf16.bf16.f32 {%0,%1,%2,%3}, {%4,%5,%6,%7}, {%8,%9}, {%0,%1,%2,%3};"
                 : "+f"(d[0]), "+f"(d[1]), "+f"(d[2]), "+f"(d[3])
                 : "r"(a0), "r"(a1), "r"(a2), "r"(a3), "r"(b0), "r"(b1));
}

__device__ __forceinline__ uint64_t smem_desc(uint32_t addr, uint32_t lbo, uint32_t sbo) {
    return (uint64_t)((addr & 0x3FFFF) >> 4) | ((uint64_t)(lbo >> 4) << 16) | ((uint64_t)(sbo >> 4) << 32);
}
__device__ __forceinline__ void wg_fence() { asm volatile("wgmma.fence.sync.aligned;" ::: "memory"); }
__device__ __forceinline__ void wg_commit() { asm volatile("wgmma.commit_group.sync.aligned;" ::: "memory"); }
__device__ __forceinline__ void wg_wait0() { asm volatile("wgmma.wait_group.sync.aligned 0;" ::: "memory"); }
__device__ __forceinline__ void fence_async() { asm volatile("fence.proxy.async.shared::cta;" ::: "memory"); }
__device__ __forceinline__ void wgmma_n32(float (&d)[16], const uint32_t (&a)[4], uint64_t bdesc, int scale_d) {
    asm volatile("{\n.reg .pred p;\nsetp.ne.b32 p, %21, 0;\n"
                 "wgmma.mma_async.sync.aligned.m64n32k16.f32.bf16.bf16 {%0,%1,%2,%3,%4,%5,%6,%7,%8,%9,%10,%11,%12,%13,%14,%15}, {%16,%17,%18,%19}, %20, p, 1, 1, 0;\n}"
                 : "+f"(d[0]), "+f"(d[1]), "+f"(d[2]), "+f"(d[3]), "+f"(d[4]), "+f"(d[5]), "+f"(d[6]), "+f"(d[7]),
                   "+f"(d[8]), "+f"(d[9]), "+f"(d[10]), "+f"(d[11]), "+f"(d[12]), "+f"(d[13]), "+f"(d[14]), "+f"(d[15])
                 : "r"(a[0]), "r"(a[1]), "r"(a[2]), "r"(a[3]), "l"(bdesc), "r"(scale_d));
}

__device__ __forceinline__ void wgmma_n32_ss(float (&d)[16], uint64_t adesc, uint64_t bdesc, int scale_d) {
    asm volatile("{\n.reg .pred p;\nsetp.ne.b32 p, %18, 0;\n"
                 "wgmma.mma_async.sync.aligned.m64n32k16.f32.bf16.bf16 {%0,%1,%2,%3,%4,%5,%6,%7,%8,%9,%10,%11,%12,%13,%14,%15}, %16, %17, p, 1, 1, 1, 0;\n}"
                 : "+f"(d[0]), "+f"(d[1]), "+f"(d[2]), "+f"(d[3]), "+f"(d[4]), "+f"(d[5]), "+f"(d[6]), "+f"(d[7]),
                   "+f"(d[8]), "+f"(d[9]), "+f"(d[10]), "+f"(d[11]), "+f"(d[12]), "+f"(d[13]), "+f"(d[14]), "+f"(d[15])
                 : "l"(adesc), "l"(bdesc), "r"(scale_d));
}

__device__ __forceinline__ void wgmma_n64_ss(float (&d)[32], uint64_t adesc, uint64_t bdesc) {
    asm volatile("{\n.reg .pred p;\nsetp.eq.b32 p, 0, 0;\n"
                 "wgmma.mma_async.sync.aligned.m64n64k16.f32.bf16.bf16 {%0,%1,%2,%3,%4,%5,%6,%7,%8,%9,%10,%11,%12,%13,%14,%15,%16,%17,%18,%19,%20,%21,%22,%23,"
                 "%24,%25,%26,%27,%28,%29,%30,%31}, %32, %33, p, 1, 1, 1, 0;\n}"
                 : "+f"(d[0]), "+f"(d[1]), "+f"(d[2]), "+f"(d[3]), "+f"(d[4]), "+f"(d[5]), "+f"(d[6]), "+f"(d[7]),
                   "+f"(d[8]), "+f"(d[9]), "+f"(d[10]), "+f"(d[11]), "+f"(d[12]), "+f"(d[13]), "+f"(d[14]), "+f"(d[15]),
                   "+f"(d[16]), "+f"(d[17]), "+f"(d[18]), "+f"(d[19]), "+f"(d[20]), "+f"(d[21]), "+f"(d[22]), "+f"(d[23]),
                   "+f"(d[24]), "+f"(d[25]), "+f"(d[26]), "+f"(d[27]), "+f"(d[28]), "+f"(d[29]), "+f"(d[30]), "+f"(d[31])
                 : "l"(adesc), "l"(bdesc));
}
__device__ __forceinline__ void tma_2d(uint32_t dst, const CUtensorMap* tm, int c0, int c1, uint32_t mbar) {
    asm volatile("cp.async.bulk.tensor.2d.shared::cluster.global.tile.mbarrier::complete_tx::bytes [%0], [%1, {%2, %3}], [%4];"
                 :: "r"(dst), "l"(tm), "r"(c0), "r"(c1), "r"(mbar) : "memory");
}

__device__ __forceinline__ void bulk_g2s(uint32_t dst, const void* src, uint32_t bytes, uint32_t mbar) {
    asm volatile("cp.async.bulk.shared::cluster.global.mbarrier::complete_tx::bytes [%0], [%1], %2, [%3];"
                 :: "r"(dst), "l"(src), "r"(bytes), "r"(mbar) : "memory");
}
__device__ __forceinline__ void bulk_g2s_h(uint32_t dst, const void* src, uint32_t bytes, uint32_t mbar, uint64_t pol) {
    asm volatile("cp.async.bulk.shared::cluster.global.mbarrier::complete_tx::bytes.L2::cache_hint [%0], [%1], %2, [%3], %4;"
                 :: "r"(dst), "l"(src), "r"(bytes), "r"(mbar), "l"(pol) : "memory");
}
__device__ __forceinline__ void tma_x(uint32_t dst, const CUtensorMap* tm, int seg, int part, uint32_t mbar) {
    asm volatile("cp.async.bulk.tensor.3d.shared::cluster.global.tile.mbarrier::complete_tx::bytes [%0], [%1, {%2, %3, %4}], [%5];"
                 :: "r"(dst + part * 12288), "l"(tm), "r"(0), "r"(seg * SEG), "r"(part * 3), "r"(mbar) : "memory");
}
__device__ __forceinline__ void tma_x_mc(uint32_t dst, const CUtensorMap* tm, int seg, int part, uint32_t mbar) {
    asm volatile("cp.async.bulk.tensor.3d.shared::cluster.global.tile.mbarrier::complete_tx::bytes.multicast::cluster [%0], [%1, {%2, %3, %4}], [%5], %6;"
                 :: "r"(dst + part * 12288), "l"(tm), "r"(0), "r"(seg * SEG), "r"(part * 3), "r"(mbar), "h"((unsigned short)7) : "memory");
}
__device__ __forceinline__ void bulk_s2s(uint32_t dst, uint32_t src, uint32_t bytes, uint32_t mbar) {
    asm volatile("cp.async.bulk.shared::cluster.shared::cta.mbarrier::complete_tx::bytes [%0], [%1], %2, [%3];"
                 :: "r"(dst), "r"(src), "r"(bytes), "r"(mbar) : "memory");
}
__device__ __forceinline__ void wgmma_n40_ss(float (&d)[20], uint64_t adesc, uint64_t bdesc, int scale_d) {
    asm volatile("{\n.reg .pred p;\nsetp.ne.b32 p, %22, 0;\n"
                 "wgmma.mma_async.sync.aligned.m64n40k16.f32.bf16.bf16 {%0,%1,%2,%3,%4,%5,%6,%7,%8,%9,%10,%11,%12,%13,%14,%15,%16,%17,%18,%19}, %20, %21, p, 1, 1, 1, 1;\n}"
                 : "+f"(d[0]), "+f"(d[1]), "+f"(d[2]), "+f"(d[3]), "+f"(d[4]), "+f"(d[5]), "+f"(d[6]), "+f"(d[7]),
                   "+f"(d[8]), "+f"(d[9]), "+f"(d[10]), "+f"(d[11]), "+f"(d[12]), "+f"(d[13]), "+f"(d[14]), "+f"(d[15]),
                   "+f"(d[16]), "+f"(d[17]), "+f"(d[18]), "+f"(d[19])
                 : "l"(adesc), "l"(bdesc), "r"(scale_d));
}
__device__ __forceinline__ void wgmma_n64_z(float (&d)[32], const uint32_t (&a)[4], uint64_t bdesc) {
    asm volatile("{\n.reg .pred p;\nsetp.ne.b32 p, 0, 0;\n"
                 "wgmma.mma_async.sync.aligned.m64n64k16.f32.bf16.bf16 {%0,%1,%2,%3,%4,%5,%6,%7,%8,%9,%10,%11,%12,%13,%14,%15,%16,%17,%18,%19,%20,%21,%22,%23,%24,%25,%26,%27,%28,%29,%30,%31}, {%32,%33,%34,%35}, %36, p, 1, 1, 0;\n}"
                 : "=f"(d[0]), "=f"(d[1]), "=f"(d[2]), "=f"(d[3]), "=f"(d[4]), "=f"(d[5]), "=f"(d[6]), "=f"(d[7]),
                   "=f"(d[8]), "=f"(d[9]), "=f"(d[10]), "=f"(d[11]), "=f"(d[12]), "=f"(d[13]), "=f"(d[14]), "=f"(d[15]),
                   "=f"(d[16]), "=f"(d[17]), "=f"(d[18]), "=f"(d[19]), "=f"(d[20]), "=f"(d[21]), "=f"(d[22]), "=f"(d[23]),
                   "=f"(d[24]), "=f"(d[25]), "=f"(d[26]), "=f"(d[27]), "=f"(d[28]), "=f"(d[29]), "=f"(d[30]), "=f"(d[31])
                 : "r"(a[0]), "r"(a[1]), "r"(a[2]), "r"(a[3]), "l"(bdesc));
}
__device__ __forceinline__ void wgmma_n64(float (&d)[32], const uint32_t (&a)[4], uint64_t bdesc, int scale_d) {
    asm volatile("{\n.reg .pred p;\nsetp.ne.b32 p, %37, 0;\n"
                 "wgmma.mma_async.sync.aligned.m64n64k16.f32.bf16.bf16 {%0,%1,%2,%3,%4,%5,%6,%7,%8,%9,%10,%11,%12,%13,%14,%15,%16,%17,%18,%19,%20,%21,%22,%23,%24,%25,%26,%27,%28,%29,%30,%31}, {%32,%33,%34,%35}, %36, p, 1, 1, 0;\n}"
                 : "+f"(d[0]), "+f"(d[1]), "+f"(d[2]), "+f"(d[3]), "+f"(d[4]), "+f"(d[5]), "+f"(d[6]), "+f"(d[7]),
                   "+f"(d[8]), "+f"(d[9]), "+f"(d[10]), "+f"(d[11]), "+f"(d[12]), "+f"(d[13]), "+f"(d[14]), "+f"(d[15]),
                   "+f"(d[16]), "+f"(d[17]), "+f"(d[18]), "+f"(d[19]), "+f"(d[20]), "+f"(d[21]), "+f"(d[22]), "+f"(d[23]),
                   "+f"(d[24]), "+f"(d[25]), "+f"(d[26]), "+f"(d[27]), "+f"(d[28]), "+f"(d[29]), "+f"(d[30]), "+f"(d[31])
                 : "r"(a[0]), "r"(a[1]), "r"(a[2]), "r"(a[3]), "l"(bdesc), "r"(scale_d));
}

constexpr int SB_FULL = 0, SB_EMPTY = 64, SB_QKF = 128, SB_VF = 144, SB_QKE = 160, SB_VE = 176, SB_OF = 192, SB_WO = 208;
constexpr int AT_0 = 256, AT_ST = 10240 + 2 * 9216;
constexpr int FS_A = 58368;
constexpr int FS_I = FS_A + 131072;
constexpr int SIDE_SMEM = FS_I + 2 * 16384;
static_assert(SIDE_SMEM <= 232448 && AT_0 + 2 * AT_ST <= FS_A && FS_A + SD_SMEM <= SIDE_SMEM, "smem");

__device__ __forceinline__ void bf16r2(float& a, float& b) {
    uint32_t p = pack_bf16(a, b);
    a = __uint_as_float(p << 16); b = __uint_as_float(p & 0xffff0000u);
}
__device__ __forceinline__ void wg_wait1() { asm volatile("wgmma.wait_group.sync.aligned 1;" ::: "memory"); }
__device__ __forceinline__ void mbar_arrive(uint32_t bar) { asm volatile("mbarrier.arrive.shared::cta.b64 _, [%0];" :: "r"(bar) : "memory"); }
__device__ __forceinline__ void wait_cnt(const unsigned* p, unsigned target) {
    unsigned it = 0;
    while ((int)(ld_acq(p) - target) < 0 && ++it < SPIN_LIMIT) __nanosleep(64);
}
__device__ __forceinline__ void wait_cnt_rlx(const unsigned* p, unsigned target, bool urgent) {
    unsigned it = 0, v;
    while (true) {
        asm volatile("ld.relaxed.gpu.global.u32 %0, [%1];" : "=r"(v) : "l"(p) : "memory");
        if ((int)(v - target) >= 0 || ++it >= SPIN_LIMIT) break;
        if (!urgent) __nanosleep(300);
    }
}

__device__ __forceinline__ void xrow_softmax(float (&sc)[20], uint32_t (&pa)[3][4], int wq, int lane) {
    const int g = lane >> 2, tq = lane & 3;
    float mx0 = -INFINITY;
    const int q0 = MEMT + 8 * wq + g;
#pragma unroll
    for (int j = 0; j < 5; j++) {
        bf16r2(sc[4 * j], sc[4 * j + 1]);
        sc[4 * j] *= ATT_SCALE; sc[4 * j + 1] *= ATT_SCALE;
        bf16r2(sc[4 * j], sc[4 * j + 1]);
#pragma unroll
        for (int c = 0; c < 2; c++) {
            int key = 8 * j + 2 * tq + c;
            if (key > q0) sc[4 * j + c] = -INFINITY;
            mx0 = fmaxf(mx0, sc[4 * j + c]);
        }
    }
    mx0 = fmaxf(mx0, __shfl_xor_sync(0xffffffffu, mx0, 1)); mx0 = fmaxf(mx0, __shfl_xor_sync(0xffffffffu, mx0, 2));
    float sum0 = 0.f;
#pragma unroll
    for (int j = 0; j < 5; j++) {
#pragma unroll
        for (int c = 0; c < 2; c++) {
            float e0 = __expf(sc[4 * j + c] - mx0);
            sc[4 * j + c] = e0;
            sum0 += e0;
        }
    }
    sum0 += __shfl_xor_sync(0xffffffffu, sum0, 1); sum0 += __shfl_xor_sync(0xffffffffu, sum0, 2);
    const float i0 = 1.f / sum0;
#pragma unroll
    for (int ks = 0; ks < 3; ks++) {
        pa[ks][0] = pack_bf16(sc[8 * ks] * i0, sc[8 * ks + 1] * i0);
        pa[ks][1] = 0u;
        pa[ks][2] = ks < 2 ? pack_bf16(sc[8 * ks + 4] * i0, sc[8 * ks + 5] * i0) : 0u;
        pa[ks][3] = 0u;
    }
}

__device__ __forceinline__ void stsm_x4(uint32_t addr, uint32_t r0, uint32_t r1, uint32_t r2, uint32_t r3) {
    asm volatile("stmatrix.sync.aligned.m8n8.x4.shared.b16 [%0], {%1,%2,%3,%4};" :: "r"(addr), "r"(r0), "r"(r1), "r"(r2), "r"(r3) : "memory");
}
__device__ __forceinline__ uint32_t h2_to_bf2(uint32_t h) {
    uint32_t r;
    asm("{\n.reg .f16 l, h;\n.reg .f32 a, b;\nmov.b32 {l, h}, %1;\ncvt.f32.f16 a, l;\ncvt.f32.f16 b, h;\ncvt.rn.bf16x2.f32 %0, b, a;\n}" : "=r"(r) : "r"(h));
    return r;
}
__device__ __forceinline__ uint32_t pack_f16(float lo, float hi) {
    uint32_t r; asm("cvt.rn.f16x2.f32 %0, %1, %2;" : "=r"(r) : "f"(hi), "f"(lo)); return r;
}
__device__ __forceinline__ uint32_t bf2_mul(uint32_t a, uint32_t b) { uint32_t r; asm("mul.rn.bf16x2 %0, %1, %2;" : "=r"(r) : "r"(a), "r"(b)); return r; }
__device__ __forceinline__ uint32_t bf2_add(uint32_t a, uint32_t b) { uint32_t r; asm("add.rn.bf16x2 %0, %1, %2;" : "=r"(r) : "r"(a), "r"(b)); return r; }
__device__ __forceinline__ uint32_t bf2_sub(uint32_t a, uint32_t b) { uint32_t r; asm("sub.rn.bf16x2 %0, %1, %2;" : "=r"(r) : "r"(a), "r"(b)); return r; }
__device__ __forceinline__ uint32_t max_abs2(uint32_t a, uint32_t b) { uint32_t r; asm("max.NaN.xorsign.abs.bf16x2 %0, %1, %2;" : "=r"(r) : "r"(a), "r"(b)); return r; }
__device__ __forceinline__ uint32_t movm(uint32_t v) {
    uint32_t r; asm volatile("movmatrix.sync.aligned.m8n8.trans.b16 %0, %1;" : "=r"(r) : "r"(v)); return r;
}
__device__ __forceinline__ void bar_arrive(int id, int n) { asm volatile("bar.arrive %0, %1;" :: "r"(id), "r"(n) : "memory"); }
__device__ __forceinline__ void lds64(uint32_t& a, uint32_t& b, uint32_t addr) {
    asm volatile("ld.shared.v2.u32 {%0,%1}, [%2];" : "=r"(a), "=r"(b) : "r"(addr) : "memory");
}
__device__ __forceinline__ void lds64f(float& a, float& b, uint32_t addr) {
    asm volatile("ld.shared.v2.f32 {%0,%1}, [%2];" : "=f"(a), "=f"(b) : "r"(addr) : "memory");
}
__device__ __forceinline__ void st_async64(uint32_t addr, uint32_t a, uint32_t b, uint32_t mbar) {
    asm volatile("st.async.weak.shared::cluster.mbarrier::complete_tx::bytes.v2.b32 [%0], {%1,%2}, [%3];" :: "r"(addr), "r"(a), "r"(b), "r"(mbar) : "memory");
}
__device__ __forceinline__ void mma_z(float (&d)[4], const uint32_t (&a)[4], uint32_t b0, uint32_t b1) {
    asm volatile("mma.sync.aligned.m16n8k16.row.col.f32.bf16.bf16.f32 {%0,%1,%2,%3}, {%4,%5,%6,%7}, {%8,%9}, {%10,%10,%10,%10};"
                 : "=f"(d[0]), "=f"(d[1]), "=f"(d[2]), "=f"(d[3])
                 : "r"(a[0]), "r"(a[1]), "r"(a[2]), "r"(a[3]), "r"(b0), "r"(b1), "f"(0.f));
}
__device__ __forceinline__ void mma_k8(float (&d)[4], uint32_t a0, uint32_t a1, uint32_t b) {
    asm volatile("mma.sync.aligned.m16n8k8.row.col.f32.bf16.bf16.f32 {%0,%1,%2,%3}, {%4,%5}, {%6}, {%0,%1,%2,%3};"
                 : "+f"(d[0]), "+f"(d[1]), "+f"(d[2]), "+f"(d[3]) : "r"(a0), "r"(a1), "r"(b));
}
__global__ void __launch_bounds__(512, 1) k_side(const __grid_constant__ CUtensorMap tmo, const bf16* __restrict__ x, const bf16* __restrict__ logA, const bf16* __restrict__ Aim,
                                                 const bf16* __restrict__ Cre, const bf16* __restrict__ Cim, const bf16* __restrict__ logdt,
                                                 const bf16* __restrict__ Wo, const bf16* __restrict__ dskip, const bf16* __restrict__ gw,
                                                 bf16* __restrict__ out) {
    extern __shared__ __align__(1024) unsigned char smem_raw[];
    const uint32_t sbase = smem_u32(smem_raw);
    const int tid = threadIdx.x, warp = __shfl_sync(0xffffffffu, tid >> 5, 0), lane = tid & 31, cta = blockIdx.x;
    const bool sp = cta >= NH;
    if (tid == 0) {
        for (int i = 0; i < 4; i++) { mbar_init(sbase + SB_FULL + 8 * i, 1); mbar_init(sbase + SB_EMPTY + 8 * i, sp ? 4 : 8); }
        for (int i = 0; i < 2; i++) {
            mbar_init(sbase + SB_QKF + 8 * i, 1); mbar_init(sbase + SB_VF + 8 * i, 1); mbar_init(sbase + SB_QKE + 8 * i, 1);
            mbar_init(sbase + SB_VE + 8 * i, 4); mbar_init(sbase + SB_OF + 8 * i, 4);
        }
        mbar_init(sbase + SB_WO, 1);
        asm volatile("fence.mbarrier_init.release.cluster;" ::: "memory");
    }
    TS3(0);
    unsigned ep;
    asm volatile("ld.volatile.global.u32 %0, [%1];" : "=r"(ep) : "l"(&g_epoch) : "memory");
    ep += 1u;
    asm volatile("fence.proxy.async;" ::: "memory");
    __syncthreads();
    if (warp >= 12) {
      asm volatile("setmaxnreg.dec.sync.aligned.u32 40;");
      if (warp == 12 || warp == 15) {
        named_bar(3, 320);
        if (tid == 384) {
            fence_async();
            mbar_expect(sbase + SB_WO, 131072);
#pragma unroll
            for (int i = 0; i < 8; i++)
                asm volatile("cp.async.bulk.tensor.2d.shared::cluster.global.tile.mbarrier::complete_tx::bytes [%0], [%1, {%2, %3}], [%4];"
                             :: "r"(sbase + FS_A + i * 16384), "l"(&tmo), "r"((sp ? 8 : 2 * (cta & 3) + (i >> 2)) * 64),
                                "r"((sp ? 2 * (cta - NH) + (i >> 2) : cta >> 2) * 512 + (i & 3) * 128), "r"(sbase + SB_WO) : "memory");
            TSS(17, 2);
        }
        if (tid == 480) {
            __threadfence();
            asm volatile("red.relaxed.gpu.global.add.u32 [%0], 1;" :: "l"(&g_gcnt) : "memory");
            TSS(17, 3);
        }
        __syncwarp();
        named_bar(7, 320);
        if (lane == 0 && (sp || warp == 12)) {
            const int pi = warp == 12 ? 0 : 1;
            const int kb = sp ? 2 * (cta - NH) + pi : cta >> 2;
            fence_async();
            for (int pr = 0; pr < NSEG / 2; pr++) {
                const int gr = sp ? pi : (pr & 1);
                wait_cnt_rlx(&g_prog[pr * 8 + kb], 8u * ep, pr >= NSEG / 2 - 2);
                if (pr >= 30 && pi == 0) TSS(4 + pr - 30, 0);
                if (pr == 31) TS3P(26);
                if (pr == 30) TS3P(1);
                mbar_wait_long(sbase + SB_EMPTY + 8 * gr, ((uint32_t)(sp ? pr : pr >> 1) & 1u) ^ 1u);
#pragma unroll
                for (int j = 0; j < 2; j++) {
                    mbar_expect(sbase + SB_FULL + 16 * gr + 8 * j, 32768);
                    bulk_g2s(sbase + FS_A + gr * 65536 + j * 32768, g_ox + ((size_t)(pr * NH + 4 * kb + 2 * j)) * 8192, 32768, sbase + SB_FULL + 16 * gr + 8 * j);
                }
            }
        }
        __syncwarp();
      } else if (warp == 13) {
        if (lane == 0 && cta < NH) {
            const uint64_t pol = policy_evict_first();
            for (int seg = 0; seg < NSEG; seg++) {
                const uint32_t st = seg & 1, ph = (uint32_t)(seg >> 1) & 1u, ab = sbase + AT_0 + st * AT_ST;
                wait_cnt_rlx(&g_flag[seg * NH + cta], 3u * ep, seg >= NSEG - 4);
                if (seg >= 60) TSS(seg - 60, 0);
                mbar_wait_long(sbase + SB_QKE + 8 * st, ph ^ 1u);
                if (seg >= 60) TSS(seg - 60, 1);
                mbar_expect(sbase + SB_QKF + 8 * st, 2 * 9216);
                bulk_g2s_h(ab + 10240, &g_qkv[seg][cta][0][1024], 9216, sbase + SB_QKF + 8 * st, pol);
                bulk_g2s_h(ab + 10240 + 9216, &g_qkv[seg][cta][1][1024], 9216, sbase + SB_QKF + 8 * st, pol);
                mbar_wait_long(sbase + SB_VE + 8 * st, ph ^ 1u);
                mbar_expect(sbase + SB_VF + 8 * st, 10240);
                bulk_g2s_h(ab, &g_qkv[seg][cta][2][0], 10240, sbase + SB_VF + 8 * st, pol);
            }
        }
        __syncwarp();
      } else if (warp == 14) {
        if (lane == 0 && cta < NH) {
            for (int seg = 0; seg < NSEG; seg++) {
                const uint32_t st = seg & 1, ab = sbase + AT_0 + st * AT_ST;
                mbar_wait_long(sbase + SB_OF + 8 * st, (uint32_t)(seg >> 1) & 1u);
                if (seg >= 60) TSS(seg - 60, 3);
                unsigned char* dst = reinterpret_cast<unsigned char*>(g_ox) + ((size_t)((seg >> 1) * NH + cta)) * 16384 + (seg & 1) * 4096;
                asm volatile("cp.async.bulk.global.shared::cta.bulk_group [%0], [%1], 4096;" :: "l"(dst), "r"(ab + 12288) : "memory");
                asm volatile("cp.async.bulk.global.shared::cta.bulk_group [%0], [%1], 4096;" :: "l"(dst + 8192), "r"(ab + 16384) : "memory");
                asm volatile("cp.async.bulk.commit_group;" ::: "memory");
                asm volatile("cp.async.bulk.wait_group 0;" ::: "memory");
                asm volatile("red.relaxed.gpu.global.add.u32 [%0], 1;" :: "l"(&g_prog[(seg >> 1) * 8 + (cta >> 2)]) : "memory");
                mbar_arrive(sbase + SB_QKE + 8 * st);
                if (seg >= 60) TSS(seg - 60, 4);
            }
        }
        __syncwarp();
      }
    } else if (warp >= 8) {
        asm volatile("setmaxnreg.dec.sync.aligned.u32 88;");
        s4d_stage_u(smem_raw + FS_A, x, tid - 256);
        {
            uint32_t gwv[9];
#pragma unroll
            for (int i = 0; i < 9; i++) gwv[i] = reinterpret_cast<const uint32_t*>(gw)[lane + 32 * i];
#pragma unroll 3
            for (int i = 0; i < 15; i++) {
                const int tt = 4 * i + warp - 8, t = min(cta * 57 + tt, S_LEN - 1);
                float sm = 0.f;
#pragma unroll
                for (int k = 0; k < 9; k++) {
                    const uint32_t xv = reinterpret_cast<const uint32_t*>(x + t * DM)[lane + 32 * k];
                    float a = __uint_as_float(xv << 16) * __uint_as_float(gwv[k] << 16), b = __uint_as_float(xv & 0xffff0000u) * __uint_as_float(gwv[k] & 0xffff0000u);
                    bf16r2(a, b);
                    sm += a + b;
                }
#pragma unroll
                for (int o = 16; o; o >>= 1) sm += __shfl_xor_sync(0xffffffffu, sm, o);
                const float gv = 1.f / (1.f + expf(-bf16r(sm)));
                if (lane == 0 && tt < 57) g_gate[t] = pack_bf16(gv, gv);
            }
#pragma unroll 1
            for (int b4 = 0; b4 < 4; b4++)
#pragma unroll
                for (int i = 0; i < 14; i++) (&g_fp[b4][2 * cta][0][0])[tid - 256 + 128 * i] = make_uint4(0u, 0u, 0u, 0u);
            named_bar(6, 128);
            if (tid == 256) {
                __threadfence();
                asm volatile("red.relaxed.gpu.global.add.u32 [%0], 1;" :: "l"(&g_gcnt) : "memory");
            }
            __syncwarp();
        }
        const int wq = warp - 8;
        for (int seg = 0; seg < (cta < NH ? NSEG : 0); seg++) {
            const uint32_t st = seg & 1, ph = (uint32_t)(seg >> 1) & 1u, ab = sbase + AT_0 + st * AT_ST;
            float sc[20];
            mbar_wait_long(sbase + SB_QKF + 8 * st, ph);
            if (seg >= 60 && tid == 256) TSS(seg - 60, 2);
            {
                const uint64_t da = smem_desc(ab + 10240 + 1024, 128, 1024), db = smem_desc(ab + 10240, 128, 2048);
                wg_fence();
#pragma unroll
                for (int ks = 0; ks < 8; ks++) wgmma_n40_ss(sc, da + (uint64_t)((ks >> 2) * 576 + (ks & 3) * 16), db + (uint64_t)((ks >> 2) * 576 + (ks & 3) * 16), ks > 0);
                wg_commit();
                wg_wait0();
            }
            uint32_t pa[3][4];
            xrow_softmax(sc, pa, wq, lane);
            named_bar(6, 128);
            mbar_wait_long(sbase + SB_VF + 8 * st, ph);
#pragma unroll
            for (int hf = 0; hf < 2; hf++) {
                float o[32];
                const uint64_t dv = smem_desc(ab + hf * 1024, 2048, 128);
                wg_fence();
#pragma unroll
                for (int ks = 0; ks < 3; ks++) { if (ks == 0) wgmma_n64_z(o, pa[0], dv); else wgmma_n64(o, pa[ks], dv + (uint64_t)(ks * 256), 1); }
                wg_commit();
                wg_wait0();
#pragma unroll
                for (int i = 0; i < 2; i++)
                    stsm_x4(ab + 12288 + hf * 4096 + wq * 1024 + i * 512 + lane * 16, pack_bf16(o[16 * i], o[16 * i + 1]), pack_bf16(o[16 * i + 4], o[16 * i + 5]),
                            pack_bf16(o[16 * i + 8], o[16 * i + 9]), pack_bf16(o[16 * i + 12], o[16 * i + 13]));
            }
            if (lane == 0) mbar_arrive(sbase + SB_VE + 8 * st);
            fence_async();
            __syncwarp();
            if (lane == 0) mbar_arrive(sbase + SB_OF + 8 * st);
        }
    } else {
        asm volatile("setmaxnreg.inc.sync.aligned.u32 192;");
        const int wg = warp >> 2, wq = warp & 3;
        const int kb = sp ? 2 * (cta - NH) + wg : cta >> 2, cb = sp ? 8 : 2 * (cta & 3) + wg;
        s4d_phase(smem_raw + FS_A, x, logA, Aim, Cre, Cim, logdt, Wo + (size_t)(kb * 512) * DM + cb * 64);
        TS3(2);
        if (lane == 0) TSS(16, warp);
        named_bar(3, 320);
        if (tid == 0) TSS(17, 0);
        uint32_t wa[32][4];
        mbar_wait_long(sbase + SB_WO, 0);
        if (tid == 0) TSS(17, 1);
        {
            const uint32_t a = sbase + FS_A + wg * 65536 + ((lane >> 4) * 8 + (lane & 7)) * 128 + (((wq * 2 + ((lane >> 3) & 1)) ^ (lane & 7)) << 4);
#pragma unroll
            for (int ks = 0; ks < 32; ks++) ldsm_x4_t(wa[ks], a + ks * 2048);
        }
        named_bar(7, 320);
        TS3(3);
        if (lane == 0) wait_cnt(&g_gcnt, 2 * SD_NCTA * ep);
        __syncwarp();
        if (tid == 0) TSS(17, 4);
        uint32_t dv[2];
        dv[0] = *reinterpret_cast<const uint32_t*>(dskip + cb * 64 + wq * 16 + 2 * (lane & 3));
        dv[1] = *reinterpret_cast<const uint32_t*>(dskip + cb * 64 + wq * 16 + 8 + 2 * (lane & 3));
        for (int it = 0; it < NSEG / 2 + 2; it++) {
            const int pr = it == NSEG / 2 - 1 ? -1 : (it == NSEG / 2 ? it - 1 : (it > NSEG / 2 ? -1 : it));
            const int pf = it == NSEG / 2 ? -1 : (it > NSEG / 2 ? NSEG / 2 - 1 : it - 1);
            uint32_t t16 = (uint32_t)(wq * 32 + lane) * 16u;
            asm volatile("" : "+r"(t16));
            const int t0 = (pf < 0 ? 0 : pf) * 64 + kb * 8, c0 = cb * 64 + wq * 16;
            const uint32_t xo = (uint32_t)((t0 + ((t16 >> 6) & 7)) * DM + c0) * 2u + ((t16 >> 2) & 12u);
            uint32_t yv[2] = {0u, 0u}, uv[2] = {0u, 0u}, gg = 0u;
            if (pf >= 0) {
                const unsigned char* yp = reinterpret_cast<const unsigned char*>(g_y) + ((uint32_t)((c0 + ((t16 >> 6) & 7)) * S_LEN + t0) * 2u + ((t16 >> 2) & 12u));
                yv[0] = __ldcg(reinterpret_cast<const uint32_t*>(yp)); yv[1] = __ldcg(reinterpret_cast<const uint32_t*>(yp + 16 * S_LEN));
                uv[0] = *reinterpret_cast<const uint32_t*>(reinterpret_cast<const unsigned char*>(x) + xo);
                uv[1] = *reinterpret_cast<const uint32_t*>(reinterpret_cast<const unsigned char*>(x) + xo + 16);
                gg = __ldcg(&g_gate[t0 + ((t16 >> 6) & 7)]);
            }
            const uint32_t ib = sbase + FS_I + wg * 16384 + t16;
            auto fetch = [&]() {
                const unsigned char* src = reinterpret_cast<const unsigned char*>(&g_fp[pf & 3][2 * cta + wg][0][0]) + t16;
#pragma unroll
                for (int r = 0; r < 7; r++) asm volatile("cp.async.cg.shared.global [%0], [%1], 16;" :: "r"(ib + r * 2048), "l"(src + r * 2048) : "memory");
                asm volatile("cp.async.commit_group;" ::: "memory");
            };
            auto finalize = [&]() {
                const uint32_t tag = ((uint32_t)(pf >> 2) & 1u) ^ 1u;
                uint32_t zv[2];
#pragma unroll
                for (int j = 0; j < 2; j++) zv[j] = bf2_mul(bf2_sub(0x3f803f80u, gg), bf2_add(movm(yv[j]), bf2_mul(uv[j], dv[j])));
                float sm[4];
                unsigned n = 0;
                while (true) {
                    asm volatile("cp.async.wait_group 0;" ::: "memory");
                    uint32_t any = 0u;
#pragma unroll
                    for (int r = 0; r < 8; r++) {
                        uint4 v;
                        asm volatile("ld.shared.v4.u32 {%0,%1,%2,%3}, [%4];" : "=r"(v.x), "=r"(v.y), "=r"(v.z), "=r"(v.w) : "r"(ib + r * 2048) : "memory");
                        uint32_t c0_, c1_;
                        asm("lop3.b32 %0, %1, %2, %3, 0x7e;" : "=r"(c0_) : "r"(v.x), "r"(v.y), "r"(tag));
                        asm("lop3.b32 %0, %1, %2, %3, 0x7e;" : "=r"(c1_) : "r"(v.z), "r"(v.w), "r"(tag));
                        asm("lop3.b32 %0, %1, %2, %3, 0xfe;" : "=r"(any) : "r"(any), "r"(c0_), "r"(c1_));
                        if (r == 0) { sm[0] = __uint_as_float(v.x); sm[1] = __uint_as_float(v.y); sm[2] = __uint_as_float(v.z); sm[3] = __uint_as_float(v.w); }
                        else asm volatile("add.f32 %0, %0, %4;\nadd.f32 %1, %1, %5;\nadd.f32 %2, %2, %6;\nadd.f32 %3, %3, %7;"
                                          : "+f"(sm[0]), "+f"(sm[1]), "+f"(sm[2]), "+f"(sm[3])
                                          : "f"(__uint_as_float(v.x)), "f"(__uint_as_float(v.y)), "f"(__uint_as_float(v.z)), "f"(__uint_as_float(v.w)));
                    }
                    if (!__any_sync(0xffffffffu, (any & 1u) != 0u) || ++n >= SPIN_LIMIT) break;
                    if (pf + 1 < NSEG / 2 && n > 1) __nanosleep(100);
                    fetch();
                }
                if (pf == 31) TS3W(29);
                TSG(5);
#pragma unroll
                for (int j = 0; j < 2; j++)
                    *reinterpret_cast<uint32_t*>(reinterpret_cast<unsigned char*>(out) + xo + 16 * j) = bf2_add(bf2_mul(gg, movm(pack_bf16(sm[2 * j], sm[2 * j + 1]))), zv[j]);
                if (wg == 0 && (pf & 1) == 0) TS3(4 + pf / 2);
                if (pf == 31) TS3W(25);
                TSG(6);
            };
            if (pr >= 0) {
                float acc[32];
                const uint32_t gr = sp ? wg : (pr & 1), ph = (uint32_t)(sp ? pr : pr >> 1) & 1u;
                mbar_wait(sbase + SB_FULL + 16 * gr, ph);
                if (pr + wg > 0) named_bar(4 + wg, 256);
                const uint64_t db = smem_desc(sbase + FS_A + gr * 65536, 128, 1024);
                TSG(0);
                wg_fence();
#pragma unroll
                for (int ks = 0; ks < 16; ks++) {
                    if (ks == 0) wgmma_n64_z(acc, wa[0], db);
                    else wgmma_n64(acc, wa[ks], db + (uint64_t)((ks >> 2) * 512 + (ks & 3) * 16), 1);
                }
                wg_commit();
                if (pf >= 0) fetch();
                mbar_wait(sbase + SB_FULL + 16 * gr + 8, ph);
                wg_fence();
#pragma unroll
                for (int ks = 16; ks < 32; ks++) wgmma_n64(acc, wa[ks], db + (uint64_t)((ks >> 2) * 512 + (ks & 3) * 16), 1);
                wg_commit();
                if (pr + wg < NSEG / 2) bar_arrive(4 + (wg ^ 1), 256);
                wg_wait0();
                if (pr == 31) TS3W(27);
                TSG(3);
                if (lane == 0) mbar_arrive(sbase + SB_EMPTY + 8 * gr);
                if (pf >= 0) finalize();
                uint32_t tag = ((uint32_t)(pr >> 2) & 1u) ^ 1u;
                tag = __shfl_sync(0xffffffffu, tag, lane);
                unsigned char* dst = reinterpret_cast<unsigned char*>(&g_fp[pr & 3][cb < 8 ? cb : 64][kb - 1][0]) + t16;
                const uint32_t dstr = cb < 8 ? 8 * 14336 : 14336;
#pragma unroll
                for (int q = 0; q < 8; q++) {
                    asm volatile("{\n.reg .pred p;\nsetp.ne.s32 p, %5, %6;\n@p st.volatile.global.v4.u32 [%0], {%1,%2,%3,%4};\n@!p st.shared.v4.u32 [%7], {%1,%2,%3,%4};\n}"
                                 :: "l"(dst), "r"((__float_as_uint(acc[4 * q]) & ~1u) | tag), "r"((__float_as_uint(acc[4 * q + 1]) & ~1u) | tag),
                                    "r"((__float_as_uint(acc[4 * q + 2]) & ~1u) | tag), "r"((__float_as_uint(acc[4 * q + 3]) & ~1u) | tag), "r"(q), "r"(kb),
                                    "r"(ib + 7 * 2048) : "memory");
                    dst += q == kb ? dstr + 2048 : dstr;
                }
                if (pr == 31) TS3W(28);
                TSG(4);
            } else if (pf >= 0) { fetch(); finalize(); }
        }
        if (cta == 0 && tid == 0) asm volatile("st.volatile.global.u32 [%0], %1;" :: "l"(&g_epoch), "r"(ep) : "memory");
    }
    asm volatile("griddepcontrol.wait;" ::: "memory");
}

__device__ __forceinline__ uint32_t poll_mem(const uint4* src, uint32_t dst, uint32_t t0) {
    uint4 v[6];
    unsigned it = 0;
#pragma unroll
    for (int j = 0; j < 6; j++) v[j] = make_uint4(0u, 0u, 0u, 0u);
    while (clock32() - t0 < POLL_DELAY) {}
    FS(12, 0);
    bool more;
#pragma unroll 1
    do {
        asm volatile("{\n.reg .pred p<6>;\n"
                     "setp.ne.u32 p0, %3, 0x5000;\nsetp.ne.u32 p1, %7, 0x5000;\nsetp.ne.u32 p2, %11, 0x5000;\n"
                     "setp.ne.u32 p3, %15, 0x5000;\nsetp.ne.u32 p4, %19, 0x5000;\nsetp.ne.u32 p5, %23, 0x5000;\n"
                     "@p0 ld.volatile.global.v4.u32 {%0,%1,%2,%3}, [%24];\n@p1 ld.volatile.global.v4.u32 {%4,%5,%6,%7}, [%24+4096];\n"
                     "@p2 ld.volatile.global.v4.u32 {%8,%9,%10,%11}, [%24+8192];\n@p3 ld.volatile.global.v4.u32 {%12,%13,%14,%15}, [%24+12288];\n"
                     "@p4 ld.volatile.global.v4.u32 {%16,%17,%18,%19}, [%24+16384];\n@p5 ld.volatile.global.v4.u32 {%20,%21,%22,%23}, [%24+20480];\n}"
                     : "+r"(v[0].x), "+r"(v[0].y), "+r"(v[0].z), "+r"(v[0].w), "+r"(v[1].x), "+r"(v[1].y), "+r"(v[1].z), "+r"(v[1].w),
                       "+r"(v[2].x), "+r"(v[2].y), "+r"(v[2].z), "+r"(v[2].w), "+r"(v[3].x), "+r"(v[3].y), "+r"(v[3].z), "+r"(v[3].w),
                       "+r"(v[4].x), "+r"(v[4].y), "+r"(v[4].z), "+r"(v[4].w), "+r"(v[5].x), "+r"(v[5].y), "+r"(v[5].z), "+r"(v[5].w)
                     : "l"(src) : "memory");
        stsm_x4(dst, h2_to_bf2(v[0].x), h2_to_bf2(v[0].y), h2_to_bf2(v[0].z), h2_to_bf2(v[1].x));
        stsm_x4(dst + 512, h2_to_bf2(v[1].y), h2_to_bf2(v[1].z), h2_to_bf2(v[2].x), h2_to_bf2(v[2].y));
        stsm_x4(dst + 1024, h2_to_bf2(v[2].z), h2_to_bf2(v[3].x), h2_to_bf2(v[3].y), h2_to_bf2(v[3].z));
        asm volatile("stmatrix.sync.aligned.m8n8.x2.shared.b16 [%0], {%1,%2};" :: "r"(dst + 1536), "r"(h2_to_bf2(v[4].x)), "r"(h2_to_bf2(v[4].y)) : "memory");
        stsm_x4(dst + 1792, h2_to_bf2(v[4].z), h2_to_bf2(v[5].x), h2_to_bf2(v[5].y), h2_to_bf2(v[5].z));
        const uint32_t all = ((v[0].w & v[1].w) & (v[2].w & v[3].w)) & (v[4].w & v[5].w);
        more = __any_sync(0xffffffffu, (all & 0x5000u) != 0x5000u) && ++it < SPIN_LIMIT;
    } while (more);
    FS(13, it);
    bar_arrive(1, 384);
    FS(14, 0);
    uint32_t m = 0u;
#pragma unroll
    for (int j = 0; j < 6; j++) {
        asm volatile("max.NaN.xorsign.abs.f16x2 %0, %0, %1;" : "+r"(m) : "r"(v[j].x));
        asm volatile("max.NaN.xorsign.abs.f16x2 %0, %0, %1;" : "+r"(m) : "r"(v[j].y));
        asm volatile("max.NaN.xorsign.abs.f16x2 %0, %0, %1;" : "+r"(m) : "r"(v[j].z));
    }
    return h2_to_bf2(m) & 0x7fff7fffu;
}

__device__ __forceinline__ void score_group(uint32_t qa, const uint32_t (&kf)[2][4], uint32_t d0, uint32_t d1, uint32_t m1, uint32_t d2, uint32_t m2) {
    uint32_t a[2][4];
#pragma unroll
    for (int k2 = 0; k2 < 2; k2++) ldsm_x4_t(a[k2], qa + k2 * 512);
    FS(4, a[1][0]);
    float sc[4][4];
    mma_z(sc[0], a[0], kf[0][0], kf[0][1]);
    mma_z(sc[1], a[0], kf[0][2], kf[0][3]);
    mma_z(sc[2], a[1], kf[1][0], kf[1][1]);
    mma_z(sc[3], a[1], kf[1][2], kf[1][3]);
    const uint32_t v0 = __float_as_uint((sc[0][0] + sc[1][2]) + (sc[2][0] + sc[3][2])), v1 = __float_as_uint((sc[0][1] + sc[1][3]) + (sc[2][1] + sc[3][3]));
    FS(5, v0);
    st_async64(d2, v0, v1, m2);
    st_async64(d1, v0, v1, m1);
    asm volatile("st.shared.v2.u32 [%0], {%1,%2};" :: "r"(d0), "r"(v0), "r"(v1) : "memory");
}
__device__ __forceinline__ void store_tile(int s, int h, int role, uint32_t tile) {
    const uint32_t qoff = role != 2 ? 1024 : 0;
    asm volatile("cp.async.bulk.global.shared::cta.bulk_group.L2::cache_hint [%0], [%1], %2, %3;"
                 :: "l"(&g_qkv[s][h][role][qoff]), "r"(tile + qoff), "r"(X_SZ), "l"(policy_evict_first()) : "memory");
    asm volatile("cp.async.bulk.commit_group;" ::: "memory");
}
__device__ __forceinline__ uint32_t w_addr(uint32_t sbase, int warp, int lane) {
    return sbase + SM_WS + (warp >> 2) * 8192 + ((lane & 7) + ((lane >> 4) & 1) * 8) * 128 + ((((warp & 3) * 2 + ((lane >> 3) & 1)) ^ (lane & 7)) << 4);
}
__device__ __forceinline__ void vx_copy(uint32_t sbase, int j, int r) {
    bulk_s2s(mapa(sbase + SM_VX + (j & 1) * 8192, r), sbase + SM_T + (j & 3) * TBUF + DH * 16, 8192, mapa(sbase + B_VX + 8 * (j & 1), r));
}
__device__ __forceinline__ void norms_gather(int lane, float* scs) {
    uint2 v[3];
    uint32_t r[2];
    unsigned it = 0;
    do {
#pragma unroll
        for (int i = 0; i < 3; i++) v[i] = ld_vol_u2(&g_norm[3 * lane + i]);
#pragma unroll
        for (int i = 0; i < 2; i++) asm volatile("ld.volatile.global.u32 %0, [%1];" : "=r"(r[i]) : "l"(&g_rx[lane + 32 * i]) : "memory");
    } while (__any_sync(0xffffffffu, (v[0].x & v[1].x & v[2].x & v[2].y & r[0] & r[1] & 1u) == 0u) && ++it < SPIN_LIMIT);
    float c;
    asm("sqrt.approx.f32 %0, %1;" : "=f"(c) : "f"(__uint_as_float(max(max(v[0].x, v[1].x), v[2].x))));
    c *= __uint_as_float(v[2].y) * 272.f;
#pragma unroll
    for (int o = 16; o; o >>= 1) c += __shfl_xor_sync(0xffffffffu, c, o);
    scs[16 + lane] = __uint_as_float(r[0]); scs[48 + lane] = __uint_as_float(r[1]);
    if (lane == 0) scs[1] = c * (1.1f * 24.f);
}

__global__ void __cluster_dims__(3, 1, 1) __launch_bounds__(384, 1)
k_chain(const __grid_constant__ CUtensorMap tmx, const __grid_constant__ CUtensorMap tmq, const __grid_constant__ CUtensorMap tmk,
        const __grid_constant__ CUtensorMap tmv, const __grid_constant__ CUtensorMap tmx2, const __grid_constant__ CUtensorMap tmo, const bf16* __restrict__ mem0, const bf16* __restrict__ xg) {
    extern __shared__ __align__(1024) unsigned char smem_raw[];
    const uint32_t sbase = smem_u32(smem_raw);
    const int cta = blockIdx.x, h = cta / 3, role = cta - 3 * h;
    const int tid = threadIdx.x, warp = __shfl_sync(0xffffffffu, tid >> 5, 0), lane_o = tid & 31;
    TS3C(0);
    asm volatile("griddepcontrol.launch_dependents;" ::: "memory");
    auto stage_w = [&](int i) {
        tma_2d(sbase + SM_WS + i * 16384, role == 2 ? &tmv : &tmq, h * DH + (role == 1 ? 64 : 0), i * 64, sbase + B_W + 8 * i);
        tma_2d(sbase + SM_WS + i * 16384 + 8192, role == 2 ? &tmv : &tmk, h * DH + (role == 0 ? 0 : 64), i * 64, sbase + B_W + 8 * i);
    };
    auto stage_x = [&](int i) { tma_2d(sbase + x01_off(i), &tmx2, i * 64, 0, sbase + B_W + 8 * i); };
    if (tid == 0) {
#pragma unroll
        for (int i = 0; i < 10; i++) mbar_init(sbase + B_W + 8 * i, 1);
        fence_async();
        bulk_g2s(sbase + SM_E + XBUF, mem0, MEMT * DM * 2, sbase + B_E);
#pragma unroll
        for (int i = 0; i < 3; i++) tma_2d(sbase + SM_X01 + i * 16384, &tmo, role * WOC + i * 64, h * DH, sbase + B_E);
        if (cta < NSEG) bulk_g2s(sbase + SM_E, xg + (size_t)cta * SEG * DM, XBUF, sbase + B_E);
#pragma unroll 1
        for (int i = 0; i < 6; i++) { if (i < 3) stage_x(i); stage_w(i); }
        mbar_expect(sbase + B_E, 49152 + MEMT * DM * 2 + (cta < NSEG ? XBUF : 0));
#pragma unroll
        for (int i = 0; i < 9; i++) mbar_expect(sbase + B_W + 8 * i, 24576);
    } else if (tid == 32) {
#pragma unroll
        for (int i = 0; i < 7; i++) mbar_init(sbase + SM_BAR + 8 * i, 1);
        asm volatile("fence.mbarrier_init.release.cluster;" ::: "memory");
        for (int i = 0; i < 2; i++) {
            mbar_expect(sbase + B_SB + 8 * i, role == 2 ? 2560 : 1280 + 2048);
            if (role != 2) mbar_expect(sbase + B_VX + 8 * i, 8192);
            mbar_arrive(sbase + B_XT + 8 * i);
        }
        mbar_expect(sbase + B_XT + 16, XBUF);
        reinterpret_cast<float*>(smem_raw + SM_SC)[2] = 1.f;
    } else if (tid >= 64 && tid < 88) {
        *reinterpret_cast<uint4*>(g_acc + cta * 1024 + (tid - 64) * 16) = make_uint4(0u, 0u, 0u, 0u);
        __threadfence();
    }
    __syncthreads();
    TS3C(8);
    if (warp < 8) {
        uint32_t wreg[36 - NS][4];
        {
            const int lane = lane_o;
            const uint32_t a = w_addr(sbase, warp, lane);
            const uint64_t da = smem_desc(sbase + SM_WS + (warp >> 2) * 8192, 1024, 1024) | (1ull << 62);
            float acc[32];
#pragma unroll
            for (int i = 0; i < 32; i++) acc[i] = 0.f;
#pragma unroll 1
            for (int b = 0; b < 9; b++) {
                if (b == 0) TSQ(0);
                mbar_wait(sbase + B_W + 8 * b, 0);
                TSQ(1 + b);
                if (b == 8) TS3C(2);
                const uint64_t db = smem_desc(sbase + x01_off(b), 16, 1024) | (1ull << 62);
                wg_fence();
#pragma unroll
                for (int k = 0; k < 4; k++) wgmma_n64_ss(acc, da + (uint64_t)(b * 1024 + k * 128), db + (uint64_t)(k * 2));
                wg_commit();
                if (b == 5) {
#pragma unroll
                    for (int ks = NS; ks < 24; ks++) ldsm_x4_t(wreg[ks - NS], a + (ks >> 2) * 16384 + (ks & 3) * 2048);
                }
            }
#pragma unroll
            for (int ks = 24; ks < 32; ks++) ldsm_x4_t(wreg[ks - NS], a + (ks >> 2) * 16384 + (ks & 3) * 2048);
            wg_wait0();
            named_bar(9, 384);
            const uint32_t off = sbase + SM_T + (DH + warp * 16 + (lane & 15)) * 16 + (lane >> 4) * (DH * 16);
#pragma unroll
            for (int i = 0; i < 4; i++)
                stsm_x4(off + (i >> 1) * TBUF + (i & 1) * (2 * DH * 16), pack_bf16(acc[8 * i], acc[8 * i + 1]), pack_bf16(acc[8 * i + 2], acc[8 * i + 3]),
                        pack_bf16(acc[8 * i + 4], acc[8 * i + 5]), pack_bf16(acc[8 * i + 6], acc[8 * i + 7]));
#pragma unroll
            for (int ks = 32; ks < 36; ks++) ldsm_x4_t(wreg[ks - NS], a + (ks >> 2) * 16384 + (ks & 3) * 2048);
            if (role == 2) fence_async();
            bar_arrive(8, 384);
            named_bar(7, 256);
            asm volatile("barrier.cluster.arrive.relaxed.aligned;" ::: "memory");
        }
        TS3C(3);
        auto xproj1 = [&](float (&acc)[16], int j) {
            const uint32_t dlo = __shfl_sync(0xffffffffu, (uint32_t)smem_desc(sbase + SM_X + (j % 3) * XBUF, 16, 1024), 0);
            wg_fence();
#pragma unroll
            for (int ks = NS; ks < NS + NC1; ks++)
                wgmma_n32(acc, wreg[ks - NS], ((uint64_t)0x40000040u << 32) | (uint64_t)(dlo + (uint32_t)((ks >> 2) * 256 + (ks & 3) * 2)), ks > NS);
            wg_commit();
            wg_wait0();
        };
        auto xproj2 = [&](float (&acc)[16], int j) {
            int lane = lane_o;
            asm volatile("" : "+r"(lane));
            const uint32_t dlo = __shfl_sync(0xffffffffu, (uint32_t)smem_desc(sbase + SM_X + (j % 3) * XBUF, 16, 1024), 0);
            const uint64_t da = smem_desc(sbase + SM_WS + (warp >> 2) * 8192, 1024, 1024) | (1ull << 62);
            wg_fence();
#pragma unroll
            for (int ks = 0; ks < NS; ks++)
                wgmma_n32_ss(acc, da + (uint64_t)((ks >> 2) * 1024 + (ks & 3) * 128), ((uint64_t)0x40000040u << 32) | (uint64_t)(dlo + (uint32_t)((ks >> 2) * 256 + (ks & 3) * 2)), NC1 > 0 || ks > 0);
#pragma unroll
            for (int ks = NS + NC1; ks < XK; ks++)
                wgmma_n32(acc, wreg[ks - NS], ((uint64_t)0x40000040u << 32) | (uint64_t)(dlo + (uint32_t)((ks >> 2) * 256 + (ks & 3) * 2)), 1);
            wg_commit();
            wg_wait0();
            const uint32_t off = sbase + SM_T + (j & 3) * TBUF + (DH + warp * 16 + (lane & 15)) * 16 + (lane >> 4) * (DH * 16);
            stsm_x4(off, pack_bf16(acc[0], acc[1]), pack_bf16(acc[2], acc[3]), pack_bf16(acc[4], acc[5]), pack_bf16(acc[6], acc[7]));
            stsm_x4(off + 2 * DH * 16, pack_bf16(acc[8], acc[9]), pack_bf16(acc[10], acc[11]), pack_bf16(acc[12], acc[13]), pack_bf16(acc[14], acc[15]));
        };
        uint32_t ws[NS][4];
#pragma unroll
        for (int ks = NS - NP; ks < NS; ks++) ldsm_x4_t(ws[ks], w_addr(sbase, warp, lane_o) + (ks >> 2) * 16384 + (ks & 3) * 2048);
        asm volatile("barrier.cluster.wait.aligned;" ::: "memory");
        if (lane_o == 0 && warp < 2 && role == 2) vx_copy(sbase, 0, warp);
        __syncwarp();
        TS3C(4);
        for (int s = 0; s < NSEG; s++) {
            int lane = lane_o;
            asm volatile("" : "+r"(lane));
            uint32_t v0, v1;
            {
#pragma unroll
                for (int ks = 0; ks < NS - NP; ks++) ldsm_x4_t(ws[ks], w_addr(sbase, warp, lane) + (ks >> 2) * 16384 + (ks & 3) * 2048);
                FS(0, ws[0][0]);
                named_bar(1, 384);
                float acc[2][4], minv;
                const uint32_t b_base = sbase + SM_M + lane * 16;
                uint32_t b[3][4];
#pragma unroll
                for (int kk = 0; kk < 3; kk++) ldsm_x4_t(b[kk], b_base + kk * 512);
                FS(1, b[0][0]);
#pragma unroll
                for (int kk = 0; kk < 18; kk++) {
                    if (kk == 0) {
                        mma_z(acc[0], ws[0], b[0][0], b[0][1]);
                        mma_z(acc[1], ws[1], b[0][2], b[0][3]);
                    } else if (2 * kk < NS) {
                        mma_bf16(acc[0], ws[2 * kk < NS ? 2 * kk : 0], b[kk % 3][0], b[kk % 3][1]);
                        mma_bf16(acc[1], ws[2 * kk < NS ? 2 * kk + 1 : 0], b[kk % 3][2], b[kk % 3][3]);
                    } else {
                        mma_bf16(acc[0], wreg[2 * kk >= NS ? 2 * kk - NS : 0], b[kk % 3][0], b[kk % 3][1]);
                        mma_bf16(acc[1], wreg[2 * kk >= NS ? 2 * kk - NS + 1 : 0], b[kk % 3][2], b[kk % 3][3]);
                    }
                    if (kk + 3 < 18) ldsm_x4_t(b[kk % 3], b_base + (kk + 3) * 512);
                    if (kk + 3 == 17) {
                        asm volatile("ld.shared.f32 %0, [%1];" : "=f"(minv) : "r"(sbase + SM_SC + 8) : "memory");
                    }
                }
                v0 = pack_bf16((acc[0][0] + acc[1][0]) * minv, (acc[0][1] + acc[1][1]) * minv);
                v1 = pack_bf16((acc[0][2] + acc[1][2]) * minv, (acc[0][3] + acc[1][3]) * minv);
                FS(2, v0);
            }
            const uint32_t tb = sbase + SM_T + (s & 3) * TBUF;
            if (role == 2 && s + 1 < NSEG) {
                const uint32_t fo = (uint32_t)(warp * 256 + lane * 8);
                const uint32_t rb0 = mapa(sbase, 0), rb1 = mapa(sbase, 1);
                st_async64(rb0 + SM_VM + fo, v0, v1, rb0 + B_SB + 8 * (s & 1));
                st_async64(rb1 + SM_VM + fo, v0, v1, rb1 + B_SB + 8 * (s & 1));
                asm volatile("st.shared.v2.u32 [%0], {%1,%2};" :: "r"(sbase + SM_VM + fo), "r"(v0), "r"(v1) : "memory");
            }
            asm volatile("stmatrix.sync.aligned.m8n8.x2.shared.b16 [%0], {%1,%2};" :: "r"(tb + warp * 256 + (lane & 15) * 16), "r"(v0), "r"(v1) : "memory");
            if (s + 1 < NSEG) {
                if (warp == 7 && role != 2) {
                    const uint32_t d0 = sbase + SM_S + role * 1280 + lane * 8, bo = sbase + B_SB + 8 * (s & 1);
                    const uint32_t d1 = mapa(d0, role ^ 1), m1 = mapa(bo, role ^ 1), d2 = mapa(d0, 2), m2 = mapa(bo, 2);
                    const uint32_t ka = tb + (64 + (lane & 7) + ((lane >> 3) & 1) * 16 + (lane >> 4) * 8) * 16;
                    uint32_t kf[2][4];
                    named_bar(2, 384);
#pragma unroll
                    for (int k2 = 0; k2 < 2; k2++) ldsm_x4_t(kf[k2], ka + k2 * 512);
                    score_group(tb + lane * 16, kf, d0, d1, m1, d2, m2);
                    bar_arrive(6, 160);
                } else bar_arrive(2, 384);
            }
            FS(11, 0);
            __syncwarp();
            if (s + 2 < NSEG) {
                if (warp == 6) mbar_wait(sbase + B_XT + 8 * ((s + 2) % 3), (uint32_t)((s + 2) / 3) & 1u);
                if (role != 2) named_bar(5, 384);
                else {
                    fence_async();
                    named_bar(7, 256);
                }
                float xacc[16];
                if (NC1 > 0) xproj1(xacc, s + 2);
                FS(9, __float_as_uint(xacc[0]));
                if (tid == 0 && role == 2) vx_copy(sbase, s + 1, 0);
                __syncwarp();
                if (role != 2) fence_async();
                FS(14, 0);
                named_bar(4, 384);
                xproj2(xacc, s + 2);
                FS(7, __float_as_uint(xacc[0]));
            }
            if (s >= NSEG - PROMPT) {
                fence_async();
                named_bar(7, 256);
                if (tid == 192) {
                    store_tile(s, h, role, tb);
                    asm volatile("cp.async.bulk.wait_group 0;" ::: "memory");
                    asm volatile("red.relaxed.gpu.global.add.u32 [%0], 1;" :: "l"(&g_flag[s * NH + h]) : "memory");
                }
                __syncwarp();
            }
        }
    } else {
        float* scs = reinterpret_cast<float*>(smem_raw + SM_SC);
        uint32_t wo[3][8][4];
        uint32_t mx2 = 0u;
        {
            const int pt = tid - 256, lane = lane_o, wq = warp - 8, g = lane >> 2, tq = lane & 3;
            TSQ(7);
            mbar_wait(sbase + B_E, 0);
            TSQ(8);
#pragma unroll
            for (int t = 0; t < 3; t++) {
                const int T = 3 * wq + t;
                const uint32_t a = sbase + SM_X01 + (T >> 2) * 16384 + ((lane >> 4) * 8 + (lane & 7)) * 128 + ((((T & 3) * 2 + ((lane >> 3) & 1)) ^ (lane & 7)) << 4);
#pragma unroll
                for (int kk = 0; kk < 8; kk++) ldsm_x4_t(wo[t][kk], a + ((2 * wq + kk) & 7) * 2048);
            }
            uint32_t m = 0u;
#pragma unroll 6
            for (int j = 0; j < 18; j++) {
                const uint32_t v = lds32(sbase + SM_E + XBUF + (g * DM + wq * 144 + 8 * j) * 2 + tq * 4);
                asm volatile("stmatrix.sync.aligned.m8n8.x1.trans.shared.b16 [%0], {%1};" :: "r"(sbase + SM_M + (wq * 144 + 8 * j + (lane & 7)) * 16), "r"(v) : "memory");
                mx2 = __vmaxu2(mx2, v & 0x7fff7fffu);
                const uint4 xv = *reinterpret_cast<const uint4*>(smem_raw + SM_E + (pt + 128 * j) * 16);
                m = max_abs2(max_abs2(m, max_abs2(xv.x, xv.y)), max_abs2(xv.z, xv.w));
            }
            m = __reduce_max_sync(0xffffffffu, max((m << 16) & 0x7fff0000u, m & 0x7fff0000u));
            if (lane == 0) reinterpret_cast<uint32_t*>(scs)[260 + wq] = m;
            named_bar(3, 128);
            if (pt == 64) {
                fence_async();
#pragma unroll 1
                for (int i = 3; i < 9; i++) { stage_x(i); if (i >= 6) stage_w(i); }
            }
            if (pt == 96 && cta < NSEG) {
                const uint4 q = *reinterpret_cast<const uint4*>(scs + 260);
                asm volatile("st.volatile.global.u32 [%0], %1;" :: "l"(&g_rx[cta]), "r"(max(max(q.x, q.y), max(q.z, q.w)) | 1u) : "memory");
            }
            __syncwarp();
            bar_arrive(1, 384);
            TSQ(9);
            float c0 = 0.f;
#pragma unroll
            for (int t = 0; t < 3; t++) {
                float n[4][4];
#pragma unroll
                for (int i = 0; i < 4; i++) { n[i][0] = n[i][1] = n[i][2] = n[i][3] = 0.f; }
#pragma unroll
                for (int kk = 0; kk < 8; kk++)
#pragma unroll
                    for (int i = 0; i < 4; i++) mma_k8(n[i], wo[t][kk][i & 2], wo[t][kk][(i & 2) + 1], wo[t][kk][i]);
                if ((g >> 1) == tq) c0 = fmaxf(c0, (g & 1) ? fmaxf(n[0][1] + n[2][1], n[1][3] + n[3][3]) : fmaxf(n[0][0] + n[2][0], n[1][2] + n[3][2]));
            }
            c0 = __uint_as_float(__reduce_max_sync(0xffffffffu, __float_as_uint(c0)));
            m = 0u;
#pragma unroll 1
            for (int b = 0; b < 9; b++) {
                if (role == 2) {
                    mbar_wait(sbase + B_W + 8 * b, 0);
#pragma unroll
                    for (int j = 0; j < 8; j++) {
                        const uint4 xv = *reinterpret_cast<const uint4*>(smem_raw + SM_WS + b * 16384 + (pt + 128 * j) * 16);
                        m = max_abs2(max_abs2(m, max_abs2(xv.x, xv.y)), max_abs2(xv.z, xv.w));
                    }
                }
                if (b == 3) bar_arrive(9, 384);
            }
            asm volatile("barrier.cluster.arrive.relaxed.aligned;" ::: "memory");
            m = __reduce_max_sync(0xffffffffu, max((m << 16) & 0x7fff0000u, m & 0x7fff0000u));
            if (lane == 0) { scs[256 + wq] = c0; reinterpret_cast<uint32_t*>(scs)[8 + wq] = m; }
            TSQ(1);
            named_bar(3, 128);
            if (pt == 0) {
                const float a = fmaxf(fmaxf(scs[256], scs[257]), fmaxf(scs[258], scs[259]));
                const float b = fmaxf(fmaxf(scs[8], scs[9]), fmaxf(scs[10], scs[11]));
                st_vol_u2(&g_norm[cta], make_uint2(__float_as_uint(a) | 1u, __float_as_uint(b) | 1u));
            }
            __syncwarp();
            named_bar(8, 384);
            TSQ(2);
            if (pt == 32) {
                fence_async();
                for (int i = 0; i < 3; i++) tma_x(sbase + SM_X + 2 * XBUF, &tmx, 2, i, sbase + B_XT + 16);
            }
            __syncwarp();
            asm volatile("barrier.cluster.wait.aligned;" ::: "memory");
        }
        const int wq = warp - 8, lane = lane_o;
        const uint32_t l8 = __shfl_sync(0xffffffffu, sbase + lane * 8, lane), l16 = __shfl_sync(0xffffffffu, sbase + lane * 16, lane);
        const uint32_t goff = __shfl_sync(0xffffffffu, (lane >> 3) * 1024 + (lane & 7) * 16, lane);
        float minv = 1.f;
        const uint32_t ka = sbase + SM_T + ((wq + 1) * DH + 64 + (lane & 7) + ((lane >> 3) & 1) * 16 + (lane >> 4) * 8) * 16;
        uint32_t kf[2][4];
#pragma unroll
        for (int k2 = 0; k2 < 2; k2++) ldsm_x4_t(kf[k2], ka + k2 * 512);
        int b3 = 0;
        for (int s = 0; s + 1 < NSEG; s++) {
            const int n3 = b3 == 2 ? 0 : b3 + 1;
            if (lane == 0) {
                if (wq == 1 && s + 3 < NSEG) tma_x_mc(sbase + SM_X + b3 * XBUF, &tmx, s + 3, role, sbase + B_XT + 8 * b3);
                if (wq == 3 && s > 0) {
                    store_tile(s - 1, h, role, sbase + SM_T + ((s - 1) & 3) * TBUF);
                    if (s > 1) {
                        asm volatile("cp.async.bulk.wait_group 1;" ::: "memory");
                        asm volatile("red.relaxed.gpu.global.add.u32 [%0], 1;" :: "l"(&g_flag[(s - 2) * NH + h]) : "memory");
                    }
                }
            }
            __syncwarp();
            if (wq == 2 && s > 1 && lane < 8) {
                *reinterpret_cast<uint4*>(g_acc + n3 * 128 + cta * 1024 + lane * 16) = make_uint4(0u, 0u, 0u, 0u);
            }
            if (s == 1 && tid == 383) {
                st_vol_u2(&g_norm[cta], make_uint2(0u, 0u));
                if (cta < NSEG) asm volatile("st.volatile.global.u32 [%0], %1;" :: "l"(&g_rx[cta]), "r"(0u) : "memory");
            }
            {
                const uint32_t mw = __reduce_max_sync(0xffffffffu, max(mx2 << 16, mx2 & 0xffff0000u));
                if (lane == 0) scs[4 + wq] = __uint_as_float(mw);
            }
            const uint32_t to = SM_T + (s & 3) * TBUF;
            const uint32_t ph = (uint32_t)(s >> 1) & 1u;
            if (role != 2) {
                const uint32_t so = SM_S + role * 1280 + (wq + 1) * 256, bo = sbase + B_SB + 8 * (s & 1);
                const uint32_t d1 = mapa(l8 + so, role ^ 1), m1 = mapa(bo, role ^ 1), d2 = mapa(l8 + so, 2), m2 = mapa(bo, 2);
                mbar_wait(sbase + B_VX + 8 * (s & 1), ph);
                FS(1, 0);
                named_bar(2, 384);
                score_group(l16 + to, kf, l8 + so, d1, m1, d2, m2);
                if (s + 2 < NSEG) bar_arrive(5, 384);
            } else named_bar(2, 384);
            if (s == 0) {
                TSQ(3);
                if (wq == 1) norms_gather(lane, scs);
                named_bar(3, 128);
                TSQ(4);
            }
            const float4 m4 = *reinterpret_cast<const float4*>(scs + 4);
            const float c24 = scs[1], xb = scs[16 + s];
            unsigned char* dst = (g_acc + b3 * 128 + (role * 32 + wq * 8) * 1024) + goff;
            uint32_t vf[2][2][4], vm[2][2];
            {
                const uint32_t va = sbase + (role == 2 ? to + DH * 16 : SM_VX + (s & 1) * 8192) + (lane >> 4) * 2048 + (32 * wq + (lane & 15)) * 16;
#pragma unroll
                for (int i = 0; i < 4; i++) ldsm_x4(vf[i >> 1][i & 1], va + (i >> 1) * 256 + (i & 1) * 4096);
            }
            float scale;
            {
                const float bound = fmaxf(fmaxf(fmaxf(m4.x, m4.y), fmaxf(m4.z, m4.w)) * minv, xb) * c24;
                int e = 141 - (int)((__float_as_uint(bound) >> 23) & 255u);
                e = e > 100 ? 100 : e;
                scale = __uint_as_float((uint32_t)(127 + e) << 23);
                minv = __uint_as_float((uint32_t)(127 - e) << 23);
            }
            FS(7, vf[1][1][0]);
            if (role != 2) named_bar(6, 160);
            if (role == 2) mbar_wait(sbase + B_SB + 8 * (s & 1), ph);
            float sv[5][2];
#pragma unroll
            for (int j = 0; j < 5; j++) lds64f(sv[j][0], sv[j][1], l8 + SM_S + (role & 1) * 1280 + j * 256);
            if (role != 2) mbar_wait(sbase + B_SB + 8 * (s & 1), ph);
            FS(6, 0);
            uint32_t p[5];
            {
                float sr[5][2];
#pragma unroll
                for (int j = 0; j < 5; j++) lds64f(sr[j][0], sr[j][1], l8 + SM_S + ((role & 1) ^ 1) * 1280 + j * 256);
                lds64(vm[0][0], vm[0][1], l8 + SM_VM + wq * 512);
                lds64(vm[1][0], vm[1][1], l8 + SM_VM + wq * 512 + 256);
#pragma unroll
                for (int j = 0; j < 5; j++) {
                    sv[j][0] += sr[j][0]; sv[j][1] += sr[j][1];
                }
                float mx = fmaxf(fmaxf(fmaxf(sv[0][0], sv[0][1]), fmaxf(sv[1][0], sv[1][1])), fmaxf(fmaxf(sv[2][0], sv[2][1]), fmaxf(sv[3][0], sv[3][1])));
                mx = fmaxf(mx, fmaxf(sv[4][0], sv[4][1]));
                {
                    const float m1 = __shfl_xor_sync(0xffffffffu, mx, 1), m2 = __shfl_xor_sync(0xffffffffu, mx, 2), m3 = __shfl_xor_sync(0xffffffffu, mx, 3);
                    mx = fmaxf(fmaxf(mx, m1), fmaxf(m2, m3));
                }
                constexpr float EC = MIMIC ? 1.4426950408889634f : (float)(1.4426950408889634 * 0.08838834764831845);
#pragma unroll
                for (int jj = 0; jj < 5; jj++) {
                    const int j = (jj + 1) % 5;
                    asm("ex2.approx.ftz.f32 %0, %1;" : "=f"(sv[j][0]) : "f"((sv[j][0] - mx) * EC));
                    asm("ex2.approx.ftz.f32 %0, %1;" : "=f"(sv[j][1]) : "f"((sv[j][1] - mx) * EC));
                    p[j] = pack_bf16(sv[j][0], sv[j][1]);
                }
            }
            FS(0, p[0]);
            uint32_t b[4][4];
            float zs[4];
            {
                float o0[2][4], o1[2][4];
                mma_z(o0[0], vf[0][0], p[1], p[2]);
                mma_z(o0[1], vf[1][0], p[1], p[2]);
                mma_z(o1[0], vf[0][1], p[3], p[4]);
                mma_z(o1[1], vf[1][1], p[3], p[4]);
                mma_k8(o0[0], vm[0][0], vm[0][1], p[0]);
                mma_k8(o0[1], vm[1][0], vm[1][1], p[0]);
                const uint32_t one4[4] = {0x3f803f80u, 0x3f803f80u, 0x3f803f80u, 0x3f803f80u};
                mma_z(zs, one4, p[1], p[2]);
                mma_bf16(zs, one4, p[3], p[4]);
                mma_k8(zs, one4[0], one4[1], p[0]);
                uint32_t ow[4];
#pragma unroll
                for (int m = 0; m < 2; m++) {
                    ow[2 * m] = pack_bf16(o0[m][0] + o1[m][0], o0[m][1] + o1[m][1]);
                    ow[2 * m + 1] = pack_bf16(o0[m][2] + o1[m][2], o0[m][3] + o1[m][3]);
                }
                stsm_x4(l16 + SM_O + wq * 512, ow[0], ow[1], ow[2], ow[3]);
                FS(2, 0);
#pragma unroll
                for (int i = 0; i < 4; i++) b[0][i] = movm(ow[i]);
            }
            float acc[3][2][4];
            named_bar(3, 128);
#pragma unroll
            for (int i = 1; i < 4; i++) ldsm_x4_t(b[i], l16 + SM_O + ((wq + i) & 3) * 512);
#pragma unroll
            for (int t = 0; t < 3; t++) { mma_z(acc[t][0], wo[t][0], b[0][0], b[0][1]); mma_z(acc[t][1], wo[t][1], b[0][2], b[0][3]); }
            float z0, z1;
            asm volatile("rcp.approx.ftz.f32 %0, %1;" : "=f"(z0) : "f"(zs[0]));
            asm volatile("rcp.approx.ftz.f32 %0, %1;" : "=f"(z1) : "f"(zs[1]));
            z0 *= scale; z1 *= scale;
            FS(3, b[1][0]);
#pragma unroll
            for (int i = 1; i < 4; i++)
#pragma unroll
                for (int t = 0; t < 3; t++) { mma_bf16(acc[t][0], wo[t][2 * i], b[i][0], b[i][1]); mma_bf16(acc[t][1], wo[t][2 * i + 1], b[i][2], b[i][3]); }
            {
                uint32_t w[6];
#pragma unroll
                for (int t = 0; t < 3; t++) {
                    w[2 * t] = pack_f16((acc[t][0][0] + acc[t][1][0]) * z0, (acc[t][0][1] + acc[t][1][1]) * z1);
                    w[2 * t + 1] = pack_f16((acc[t][0][2] + acc[t][1][2]) * z0, (acc[t][0][3] + acc[t][1][3]) * z1);
                }
                FS(8, w[5]);
                asm volatile("red.relaxed.gpu.global.add.noftz.v4.f16x2 [%0], {%1,%2,%3,%4};" :: "l"(dst), "r"(w[0]), "r"(w[1]), "r"(w[2]), "r"(0x3c00u) : "memory");
                asm volatile("red.relaxed.gpu.global.add.noftz.v4.f16x2 [%0], {%1,%2,%3,%4};" :: "l"(dst + 4096), "r"(w[3]), "r"(w[4]), "r"(w[5]), "r"(0x3c00u) : "memory");
            }
            FS(9, 0);
            if (s == 0) TSQ(5);
            const uint32_t t0 = clock32();
            if (s + 2 < NSEG) bar_arrive(4, 384);
            if (lane == 0) {
                if (wq == 0) scs[2] = minv;
                if (wq == 2 && role == 2 && s + 2 < NSEG) { while (clock32() - t0 < VX_DELAY) {} vx_copy(sbase, s + 1, 1); }
                if (s + 3 < NSEG) {
                    if (wq == 0) mbar_expect(sbase + B_SB + 8 * (s & 1), role == 2 ? 2560 : 1280 + 2048);
                    if (wq == 1) mbar_expect(sbase + B_XT + 8 * b3, XBUF);
                    if (wq == 3 && role != 2) mbar_expect(sbase + B_VX + 8 * (s & 1), 8192);
                }
            }
            __syncwarp();
#pragma unroll
            for (int k2 = 0; k2 < 2; k2++) ldsm_x4_t(kf[k2], ka + ((s + 1) & 3) * TBUF + k2 * 512);
            const uint4* src = reinterpret_cast<const uint4*>((g_acc + b3 * 128 + wq * 24576) + goff);
            mx2 = poll_mem(src, l16 + SM_M + wq * 2304, t0);
            if (s == 0) TSQ(6);
            b3 = n3;
        }
        if (ST_AT < 2 && tid == 352) {
            asm volatile("cp.async.bulk.wait_group 0;" ::: "memory");
            asm volatile("red.relaxed.gpu.global.add.u32 [%0], 1;" :: "l"(&g_flag[(NSEG - 3) * NH + h]) : "memory");
        }
    }
    TS3C(1);
    __syncwarp();
    cluster_sync_all();
}

extern "C" void kernel_launch(void* const* d_in, const int* in_sizes, int n_in, void* d_out, int out_size) {
    const bf16* x = (const bf16*)d_in[0];
    const bf16* mem0 = (const bf16*)d_in[1];
    const bf16* Wq = (const bf16*)d_in[2];
    const bf16* Wk = (const bf16*)d_in[3];
    const bf16* Wv = (const bf16*)d_in[4];
    const bf16* Wo = (const bf16*)d_in[5];
    const bf16* logA = (const bf16*)d_in[8];
    const bf16* Aim = (const bf16*)d_in[9];
    const bf16* Cre = (const bf16*)d_in[10];
    const bf16* Cim = (const bf16*)d_in[11];
    const bf16* logdt = (const bf16*)d_in[12];
    const bf16* dskip = (const bf16*)d_in[13];
    const bf16* gw = (const bf16*)d_in[14];
    bf16* out = (bf16*)d_out;
    static bool attr_done = false;
    typedef CUresult (*EncFn)(CUtensorMap*, CUtensorMapDataType, cuuint32_t, void*, const cuuint64_t*, const cuuint64_t*, const cuuint32_t*,
                              const cuuint32_t*, CUtensorMapInterleave, CUtensorMapSwizzle, CUtensorMapL2promotion, CUtensorMapFloatOOBfill);
    static EncFn enc = nullptr;
    if (!attr_done) {
        void* fn = nullptr;
        cudaDriverEntryPointQueryResult qr;
        cudaGetDriverEntryPoint("cuTensorMapEncodeTiled", &fn, cudaEnableDefault, &qr);
        enc = (EncFn)fn;
        cudaFuncSetAttribute(k_chain, cudaFuncAttributeMaxDynamicSharedMemorySize, 232448);
        cudaFuncSetAttribute(k_side, cudaFuncAttributeMaxDynamicSharedMemorySize, SIDE_SMEM);
        attr_done = true;
    }
    CUtensorMap tmx;
    {
        const cuuint64_t dims[3] = {64, (cuuint64_t)S_LEN, 9};
        const cuuint64_t strides[2] = {(cuuint64_t)DM * 2, 128};
        const cuuint32_t box[3] = {64, (cuuint32_t)SEG, 3};
        const cuuint32_t es[3] = {1, 1, 1};
        enc(&tmx, CU_TENSOR_MAP_DATA_TYPE_BFLOAT16, 3, (void*)x, dims, strides, box, es, CU_TENSOR_MAP_INTERLEAVE_NONE,
            CU_TENSOR_MAP_SWIZZLE_128B, CU_TENSOR_MAP_L2_PROMOTION_L2_128B, CU_TENSOR_MAP_FLOAT_OOB_FILL_NONE);
    }
    CUtensorMap tmw[3];
    for (int i = 0; i < 3; i++) {
        const cuuint64_t dims[2] = {(cuuint64_t)HD, (cuuint64_t)DM};
        const cuuint64_t strides[1] = {(cuuint64_t)HD * 2};
        const cuuint32_t box[2] = {64, 64};
        const cuuint32_t es[2] = {1, 1};
        enc(&tmw[i], CU_TENSOR_MAP_DATA_TYPE_BFLOAT16, 2, (void*)(i == 0 ? Wq : (i == 1 ? Wk : Wv)), dims, strides, box, es, CU_TENSOR_MAP_INTERLEAVE_NONE,
            CU_TENSOR_MAP_SWIZZLE_128B, CU_TENSOR_MAP_L2_PROMOTION_L2_256B, CU_TENSOR_MAP_FLOAT_OOB_FILL_NONE);
    }
    CUtensorMap tmo;
    {
        const cuuint64_t dims[2] = {(cuuint64_t)DM, (cuuint64_t)HD};
        const cuuint64_t strides[1] = {(cuuint64_t)DM * 2};
        const cuuint32_t box[2] = {64, 128};
        const cuuint32_t es[2] = {1, 1};
        enc(&tmo, CU_TENSOR_MAP_DATA_TYPE_BFLOAT16, 2, (void*)Wo, dims, strides, box, es, CU_TENSOR_MAP_INTERLEAVE_NONE,
            CU_TENSOR_MAP_SWIZZLE_128B, CU_TENSOR_MAP_L2_PROMOTION_L2_128B, CU_TENSOR_MAP_FLOAT_OOB_FILL_NONE);
    }
    CUtensorMap tmx2;
    {
        const cuuint64_t dims[2] = {(cuuint64_t)DM, (cuuint64_t)S_LEN};
        const cuuint64_t strides[1] = {(cuuint64_t)DM * 2};
        const cuuint32_t box[2] = {64, 64};
        const cuuint32_t es[2] = {1, 1};
        enc(&tmx2, CU_TENSOR_MAP_DATA_TYPE_BFLOAT16, 2, (void*)x, dims, strides, box, es, CU_TENSOR_MAP_INTERLEAVE_NONE,
            CU_TENSOR_MAP_SWIZZLE_128B, CU_TENSOR_MAP_L2_PROMOTION_L2_128B, CU_TENSOR_MAP_FLOAT_OOB_FILL_NONE);
    }
    k_chain<<<NCTA, 384, 232448>>>(tmx, tmw[0], tmw[1], tmw[2], tmx2, tmo, mem0, x);
    {
        cudaLaunchConfig_t cfg = {};
        cfg.gridDim = dim3(SD_NCTA); cfg.blockDim = dim3(512); cfg.dynamicSmemBytes = SIDE_SMEM; cfg.stream = cudaStreamPerThread;
        cudaLaunchAttribute at[1];
        at[0].id = cudaLaunchAttributeProgrammaticStreamSerialization;
        at[0].val.programmaticStreamSerializationAllowed = 1;
        cfg.attrs = at; cfg.numAttrs = 1;
        cudaLaunchKernelEx(&cfg, k_side, tmo, x, logA, Aim, Cre, Cim, logdt, Wo, dskip, gw, out);
    }
}
```

```cpp
#include <cuda_runtime.h>
#include <cuda.h>
#include <cuda_bf16.h>
#include <stdint.h>

typedef __nv_bfloat16 bf16;
#define LDV4 "ld.volatile.global.v4.u32 {%0,%1,%2,%3}, [%4];"
#define STV4 "st.volatile.global.v4.u32 [%0], {%1,%2,%3,%4};"
#define STV2 "st.volatile.global.v2.u32 [%0], {%1,%2};"

constexpr int S_LEN = 2048, DM = 576, NH = 32, DH = 128, HD = 4096, MEMT = 8, SEG = 32, NSEG = 64, NST = 128;

__device__ __align__(128) bf16 g_gate[S_LEN];
constexpr int NCTA = NH * 3;
__device__ __align__(1024) unsigned char g_acc[96 * 1024];
__device__ __align__(128) uint2 g_norm[NCTA];
__device__ __align__(128) uint32_t g_rx[NSEG];
__device__ __align__(128) unsigned char g_qkv[NSEG][NH][3][10240];
__device__ __align__(128) bf16 g_ox[S_LEN * HD];
__device__ __align__(128) uint4 g_fp[8][36][6][128];
__device__ unsigned g_flag[NSEG * NH];
__device__ unsigned g_prog[NSEG / 2 * 8];
__device__ unsigned g_gcnt[64];
__device__ unsigned g_epoch;
__device__ __align__(128) uint2 g_tick;
__device__ __align__(16) bf16 g_y[DM * S_LEN];

#define TS3(slot) do {} while (0)
#define TS3P(slot) do {} while (0)
#define TSQ(slot) do {} while (0)
#define TS3W(slot) do {} while (0)
#define TSS(row, slot) do {} while (0)
#define TS3C(slot) do {} while (0)
#define TSG(i) do {} while (0)
#define FS(i, dep) do {} while (0)
__device__ __forceinline__ uint32_t smem_u32(const void* p) { return (uint32_t)__cvta_generic_to_shared(p); }
__device__ __forceinline__ float bf16r(float x) { return __bfloat162float(__float2bfloat16_rn(x)); }
__device__ __forceinline__ uint32_t pack_bf16(float lo, float hi) {
    __nv_bfloat162 v = __floats2bfloat162_rn(lo, hi);
    return *reinterpret_cast<uint32_t*>(&v);
}
__device__ __forceinline__ void ldsm_x4(uint32_t (&r)[4], uint32_t addr) {
    asm volatile("ldmatrix.sync.aligned.m8n8.x4.shared.b16 {%0,%1,%2,%3}, [%4];"
                 : "=r"(r[0]), "=r"(r[1]), "=r"(r[2]), "=r"(r[3]) : "r"(addr));
}
__device__ __forceinline__ void ldsm_x4_t(uint32_t (&r)[4], uint32_t addr) {
    asm volatile("ldmatrix.sync.aligned.m8n8.x4.trans.shared.b16 {%0,%1,%2,%3}, [%4];"
                 : "=r"(r[0]), "=r"(r[1]), "=r"(r[2]), "=r"(r[3]) : "r"(addr));
}
__device__ __forceinline__ void mma_bf16(float (&d)[4], const uint32_t (&a)[4], uint32_t b0, uint32_t b1) {
    asm volatile("mma.sync.aligned.m16n8k16.row.col.f32.bf16.bf16.f32 {%0,%1,%2,%3}, {%4,%5,%6,%7}, {%8,%9}, {%0,%1,%2,%3};"
                 : "+f"(d[0]), "+f"(d[1]), "+f"(d[2]), "+f"(d[3])
                 : "r"(a[0]), "r"(a[1]), "r"(a[2]), "r"(a[3]), "r"(b0), "r"(b1));
}
__device__ __forceinline__ uint2 ld_vol_u2(const uint2* p) {
    uint2 v; asm volatile("ld.volatile.global.v2.u32 {%0,%1}, [%2];" : "=r"(v.x), "=r"(v.y) : "l"(p) : "memory"); return v;
}
__device__ __forceinline__ void st_vol_u2(uint2* p, uint2 v) {
    asm volatile(STV2 :: "l"(p), "r"(v.x), "r"(v.y) : "memory");
}
__device__ __forceinline__ unsigned ld_acq(const unsigned* p) {
    unsigned v; asm volatile("ld.acquire.gpu.global.u32 %0, [%1];" : "=r"(v) : "l"(p) : "memory"); return v;
}
#define XK 36
#define RFENCE 0
#define NC1 12
#define NS 6
#define NP 2
#define ST_AT 0
#define XT_AT 0
#define XT_DELAY 250
#define X_SZ 10240u - qoff
#define ST_DELAY 300
#define PF_DELAY 900
#define CLR_AT 0
#define CLR_T0 60000
#define X_OXSZ 16384
#define GATE_A 1300
#define GATE_B 300
#define GATE_P 1950u
#define STAGGER 0
#define GATE_ATT 3
#define RLX_SLEEP 300
#define MIMIC 0
#define VX_MODE 3
#define VX_DELAY 100
#define POLL_DELAY 500
#define WO_AFTER 4
constexpr int PROMPT = 2;
constexpr unsigned SPIN_LIMIT = 1u << 20;

constexpr int SD_CH = 16;
constexpr int SD_NCTA = DM / SD_CH;
constexpr int SD_USTR = 40 * 72;
constexpr int SD_KLEN = 2048 + 32;
constexpr int SD_WSTR = 2 * SD_KLEN * 2;
constexpr int SD_SMEM = SD_CH * SD_USTR * 2 + 8 * SD_WSTR;

__device__ __forceinline__ uint32_t lds32(uint32_t a) { uint32_t v; asm volatile("ld.shared.u32 %0, [%1];" : "=r"(v) : "r"(a)); return v; }
__device__ __forceinline__ void tap_tile(uint32_t (&t)[4], uint32_t a) { t[0] = lds32(a); t[1] = lds32(a - 16); t[2] = lds32(a + 16); t[3] = lds32(a); }
template <int NT0>
__device__ __forceinline__ void conv_step(float (&acc)[4][4][4], const uint32_t (&cur)[4][4], uint32_t (&prev)[4][4], uint32_t (&b)[4][2][4], uint32_t ka, uint32_t ua) {
#pragma unroll
    for (int kt = 3; kt >= 0; kt--) {
#pragma unroll
        for (int nt = NT0; nt < 4; nt++)
#pragma unroll
            for (int mt = 0; mt < 4; mt++) {
                if (mt < kt) mma_bf16(acc[mt][nt], prev[(mt - kt + 4) & 3], b[nt][kt >> 1][(kt & 1) * 2], b[nt][kt >> 1][(kt & 1) * 2 + 1]);
                else mma_bf16(acc[mt][nt], cur[(mt - kt) & 3], b[nt][kt >> 1][(kt & 1) * 2], b[nt][kt >> 1][(kt & 1) * 2 + 1]);
            }
        if (kt == 3) { tap_tile(prev[0], ka); tap_tile(prev[1], ka - 32); }
        if (kt == 2) tap_tile(prev[2], ka - 64);
        if (kt == 1) tap_tile(prev[3], ka - 96);
        if ((kt & 1) == 0) {
#pragma unroll
            for (int nt = NT0; nt < 4; nt++) ldsm_x4(b[nt][kt >> 1], ua + nt * 1152 + kt * 32);
        }
    }
}
template <int NT0>
__device__ __forceinline__ void conv_oct(float (&acc)[4][4][4], uint32_t (&X)[4][4], uint32_t (&Y)[4][4], uint32_t (&b)[4][2][4], uint32_t& ka, uint32_t& ua) {
#pragma unroll 1
    for (int i = 0; i < 4; i++) {
        conv_step<NT0>(acc, X, Y, b, ka - 128, ua - 144);
        conv_step<NT0>(acc, Y, X, b, ka - 256, ua - 288);
        ka -= 256; ua -= 288;
    }
}

__device__ __forceinline__ void named_bar(int id, int n) { asm volatile("bar.sync %0, %1;" :: "r"(id), "r"(n) : "memory"); }
__device__ __forceinline__ uint32_t pack_f16(float lo, float hi) {
    uint32_t r; asm("cvt.rn.f16x2.f32 %0, %1, %2;" : "=r"(r) : "f"(hi), "f"(lo)); return r;
}
__device__ __forceinline__ void cexp_t(float lr, float turns, float& re, float& im) {
    float m;
    asm("ex2.approx.ftz.f32 %0, %1;" : "=f"(m) : "f"(lr));
    const float a = (turns - rintf(turns)) * 6.283185307179586f;
    re = m * __cosf(a); im = m * __sinf(a);
}
__device__ __forceinline__ void csq(float& re, float& im) { const float r = re * re - im * im; im = 2.f * re * im; re = r; }
__device__ __forceinline__ void kb_state(const float* tp, float gf, uint32_t (&a)[4][2], uint32_t (&b)[5]) {
    const float4 p0 = *reinterpret_cast<const float4*>(tp), p1 = *reinterpret_cast<const float4*>(tp + 4);
    float wr, wi;
    cexp_t(p0.x * gf, p0.y * gf, wr, wi);
    float vr = wr * p1.x - wi * p1.y, vi = wr * p1.y + wi * p1.x;
#pragma unroll
    for (int c = 0; c < 4; c++) {
        a[c][0] = pack_f16(wr, wi); a[c][1] = pack_f16(vr, vi);
        csq(wr, wi);
        if (c < 3) csq(vr, vi);
    }
    b[0] = pack_f16(p0.z * wr - p0.w * wi, -p0.z * wi - p0.w * wr);
    float er = wr * p1.z - wi * p1.w, ei = wr * p1.w + wi * p1.z;
#pragma unroll
    for (int c = 0; c < 4; c++) {
        b[1 + c] = pack_f16(p0.z * er - p0.w * ei, -p0.z * ei - p0.w * er);
        if (c < 3) csq(er, ei);
    }
}
template <int C>
__device__ __forceinline__ void expand_taps(const float* kd, bf16* kr, int l0, int lane) {
    uint32_t w[4];
#pragma unroll
    for (int e = 0; e < 4; e++) {
        float v[2];
#pragma unroll
        for (int k = 0; k < 2; k++) {
            const int l = l0 + 8 * lane + 7 - 2 * e - k;
            const int idx = C == 0 ? l : 128 * C + ((l + (1 << (C > 0 ? C - 1 : 0)) - 1 + ((l >> C) & 1)) >> C);
            v[k] = kd[idx];
        }
        w[e] = pack_bf16(v[0], v[1]);
    }
    *reinterpret_cast<uint4*>(kr + 2040 - l0 - 8 * lane) = make_uint4(w[0], w[1], w[2], w[3]);
}

__device__ __forceinline__ uint32_t bf2_mul(uint32_t a, uint32_t b) { uint32_t r; asm("mul.rn.bf16x2 %0, %1, %2;" : "=r"(r) : "r"(a), "r"(b)); return r; }
__device__ __forceinline__ uint32_t bf2_add(uint32_t a, uint32_t b) { uint32_t r; asm("add.rn.bf16x2 %0, %1, %2;" : "=r"(r) : "r"(a), "r"(b)); return r; }
__device__ __forceinline__ uint32_t bf2_sub(uint32_t a, uint32_t b) { uint32_t r; asm("sub.rn.bf16x2 %0, %1, %2;" : "=r"(r) : "r"(a), "r"(b)); return r; }
__device__ __forceinline__ void wait_cnt(const unsigned* p, unsigned target) {
    unsigned it = 0;
    while ((int)(ld_acq(p) - target) < 0 && ++it < SPIN_LIMIT) __nanosleep(64);
}
__device__ __forceinline__ void s4d_phase(unsigned char* smem_raw, const bf16* __restrict__ x, const bf16* __restrict__ logA,
                                          const bf16* __restrict__ Aim, const bf16* __restrict__ Cre, const bf16* __restrict__ Cim,
                                          const bf16* __restrict__ logdt, const bf16* __restrict__ dskip, const bf16* __restrict__ wslice, unsigned ep) {
    bf16* u_all = reinterpret_cast<bf16*>(smem_raw);
    const int tid = threadIdx.x, warp = tid >> 5, lane = tid & 31;
    const int d0 = blockIdx.x * SD_CH;
    bf16* kr = u_all + SD_CH * SD_USTR + warp * (SD_WSTR / 2);
    float* tab = reinterpret_cast<float*>(kr + SD_KLEN);
    const int g = lane >> 2, tq = lane & 3;
    uint2 prm[4];
    float ldt;
    auto load_prm = [&](int d) {
        prm[0] = __ldg(reinterpret_cast<const uint2*>(logA + d * NST) + lane); prm[1] = __ldg(reinterpret_cast<const uint2*>(Aim + d * NST) + lane);
        prm[2] = __ldg(reinterpret_cast<const uint2*>(Cre + d * NST) + lane); prm[3] = __ldg(reinterpret_cast<const uint2*>(Cim + d * NST) + lane);
        ldt = __bfloat162float(logdt[d]);
    };
    load_prm(d0 + 2 * warp);
    for (int i = lane; i < 8 * 72 / 2; i += 32) {
        reinterpret_cast<uint32_t*>(u_all + (2 * warp) * SD_USTR)[i] = 0u;
        reinterpret_cast<uint32_t*>(u_all + (2 * warp + 1) * SD_USTR)[i] = 0u;
    }
    if (lane < 16) reinterpret_cast<uint32_t*>(kr + 2048)[lane] = 0u;
    TS3(20);
#pragma unroll 1
    for (int ch = 0; ch < 2; ch++) {
        const int d = d0 + 2 * warp + ch;
        bf16* us = u_all + (2 * warp + ch) * SD_USTR;
        float k2048 = 0.f, sinv;
        {
            const float dt = bf16r(expf(ldt));
            uint32_t cm = __vmaxu2(__vmaxu2(prm[2].x & 0x7fff7fffu, prm[2].y & 0x7fff7fffu), __vmaxu2(prm[3].x & 0x7fff7fffu, prm[3].y & 0x7fff7fffu));
            cm = __reduce_max_sync(0xffffffffu, max(cm << 16, cm & 0xffff0000u));
            int e = 134 - (int)(__float_as_uint(__uint_as_float(cm) * dt) >> 23);
            e = e > 100 ? 100 : (e < -100 ? -100 : e);
            const float s2 = __uint_as_float((uint32_t)(128 + e) << 23);
            sinv = __uint_as_float((uint32_t)(127 - e) << 23);
#pragma unroll
            for (int j = 0; j < 4; j++) {
                float q[4];
#pragma unroll
                for (int i = 0; i < 4; i++) { const uint32_t w = j < 2 ? prm[i].x : prm[i].y; q[i] = __uint_as_float((j & 1) ? w & 0xffff0000u : w << 16); }
                const float zl = -bf16r(expf(q[0])) * dt * 1.4426950408889634f;
                const float zt = q[1] * dt * 0.15915494309189535f;
                const float cr = s2 * (q[2] * dt), ci = s2 * (q[3] * dt);
                float ar, ai, br, bi, er, ei;
                cexp_t(zl * 8.f, zt * 8.f, ar, ai);
                cexp_t(zl * 128.f, zt * 128.f, br, bi);
                cexp_t(zl * 2048.f, zt * 2048.f, er, ei);
                k2048 += cr * er - ci * ei;
                *reinterpret_cast<float4*>(tab + (lane + 32 * j) * 8) = make_float4(zl, zt, cr, ci);
                *reinterpret_cast<float4*>(tab + (lane + 32 * j) * 8 + 4) = make_float4(ar, ai, br, bi);
            }
            if (ch == 0) load_prm(d + 1);
#pragma unroll
            for (int o = 16; o; o >>= 1) k2048 += __shfl_xor_sync(0xffffffffu, k2048, o);
        }
        __syncwarp();
        {
            float kc[5][4];
#pragma unroll
            for (int i = 0; i < 5; i++) { kc[i][0] = kc[i][1] = kc[i][2] = kc[i][3] = 0.f; }
            const float gf = (float)g;
#pragma unroll 2
            for (int ks = 0; ks < 16; ks++) {
                uint32_t a0[4][2], a1[4][2], b0[5], b1[5];
                kb_state(tab + (8 * ks + tq) * 8, gf, a0, b0);
                kb_state(tab + (8 * ks + 4 + tq) * 8, gf, a1, b1);
#pragma unroll
                for (int i = 0; i < 5; i++) {
                    const int c = i > 0 ? i - 1 : 0;
                    asm volatile("mma.sync.aligned.m16n8k16.row.col.f32.f16.f16.f32 {%0,%1,%2,%3}, {%4,%5,%6,%7}, {%8,%9}, {%0,%1,%2,%3};"
                                 : "+f"(kc[i][0]), "+f"(kc[i][1]), "+f"(kc[i][2]), "+f"(kc[i][3])
                                 : "r"(a0[c][0]), "r"(a0[c][1]), "r"(a1[c][0]), "r"(a1[c][1]), "r"(b0[i]), "r"(b1[i]));
                }
            }
            __syncwarp();
#pragma unroll
            for (int i = 0; i < 5; i++) {
                float* q = tab + 128 * i + 32 * tq + g;
                q[0] = kc[i][0] * sinv; q[16] = kc[i][1] * sinv; q[8] = kc[i][2] * sinv; q[24] = kc[i][3] * sinv;
            }
            if (lane == 0) tab[640] = k2048 * sinv;
            __syncwarp();
            expand_taps<0>(tab, kr, 0, lane);
            expand_taps<1>(tab, kr, 256, lane);
            expand_taps<2>(tab, kr, 512, lane);
            expand_taps<2>(tab, kr, 768, lane);
#pragma unroll
            for (int i = 0; i < 4; i++) expand_taps<3>(tab, kr, 1024 + 256 * i, lane);
            __syncwarp();
#pragma unroll
            for (int i = 0; i < 8; i++) {
                const uint4 v = *reinterpret_cast<const uint4*>(kr + (lane + 32 * i) * 8);
                const uint32_t n = *reinterpret_cast<const uint32_t*>(kr + (lane + 32 * i) * 8 + 8);
                *reinterpret_cast<uint4*>(tab + (lane + 32 * i) * 4) =
                    make_uint4(__byte_perm(v.x, v.y, 0x5432), __byte_perm(v.y, v.z, 0x5432), __byte_perm(v.z, v.w, 0x5432), __byte_perm(v.w, n, 0x5432));
            }
            if (lane < 16) tab[1024 + lane] = 0.f;
            __syncwarp();
        }
        TS3(21 + 2 * ch);
        if (ch == 0) { if (!STAGGER || warp < 4) named_bar(1, 384); }
        else {
#pragma unroll
            for (int i = 0; i < 4; i++) asm volatile("prefetch.global.L2 [%0];" :: "l"(wslice + (size_t)((tid & 127) + 128 * i) * DM));
        }
        float acc[4][4][4];
#pragma unroll
        for (int i = 0; i < 4; i++)
#pragma unroll
            for (int j = 0; j < 4; j++) { acc[i][j][0] = acc[i][j][1] = acc[i][j][2] = acc[i][j][3] = 0.f; }
        {
            uint32_t X[4][4], Y[4][4], b[4][2][4];
            const int j0 = 2047 - g + 2 * tq;
            uint32_t ka = smem_u32(kr) + ((j0 & 1) ? SD_KLEN * 2 : 0) + 2u * (uint32_t)(j0 & ~1);
            uint32_t ua = smem_u32(us) + (uint32_t)(((lane & 7) + 8) * 144 + (lane >> 3) * 16);
#pragma unroll
            for (int i = 0; i < 4; i++) {
                Y[i][0] = Y[i][1] = Y[i][2] = Y[i][3] = 0u;
                tap_tile(X[i], ka - 32 * i);
                ldsm_x4(b[i][0], ua + i * 1152); ldsm_x4(b[i][1], ua + i * 1152 + 64);
            }
            conv_oct<0>(acc, X, Y, b, ka, ua);
            conv_oct<1>(acc, X, Y, b, ka, ua);
            conv_oct<2>(acc, X, Y, b, ka, ua);
            conv_oct<3>(acc, X, Y, b, ka, ua);
        }
        __syncwarp();
        if (ch == 0) { if (lane == 0) wait_cnt(&g_gcnt[0], SD_NCTA * ep); __syncwarp(); }
        uint4 gv[8];
#pragma unroll
        for (int i = 0; i < 8; i++) gv[i] = __ldcg(reinterpret_cast<const uint4*>(g_gate) + lane + 32 * i);
        const uint32_t dd = __byte_perm(*reinterpret_cast<const unsigned short*>(dskip + d), 0u, 0x1010);
#pragma unroll
        for (int nt = 0; nt < 4; nt++)
#pragma unroll
            for (int m2 = 0; m2 < 2; m2++)
                asm volatile("stmatrix.sync.aligned.m8n8.x4.trans.shared.b16 [%0], {%1,%2,%3,%4};"
                             :: "r"(smem_u32(kr) + (uint32_t)((8 * nt + (lane & 7)) * 144 + m2 * 64 + (lane >> 3) * 16)),
                                "r"(pack_bf16(acc[2 * m2][nt][0], acc[2 * m2][nt][1])), "r"(pack_bf16(acc[2 * m2][nt][2], acc[2 * m2][nt][3])),
                                "r"(pack_bf16(acc[2 * m2 + 1][nt][0], acc[2 * m2 + 1][nt][1])), "r"(pack_bf16(acc[2 * m2 + 1][nt][2], acc[2 * m2 + 1][nt][3])) : "memory");
        __syncwarp();
#pragma unroll
        for (int i = 0; i < 8; i++) {
            const uint4 y = *reinterpret_cast<const uint4*>(kr + (4 * i + (lane >> 3)) * 72 + (lane & 7) * 8);
            const uint4 u = *reinterpret_cast<const uint4*>(us + (8 + 4 * i + (lane >> 3)) * 72 + (lane & 7) * 8);
            *reinterpret_cast<uint4*>(g_y + (size_t)d * S_LEN + (lane + 32 * i) * 8) =
                make_uint4(bf2_mul(bf2_sub(0x3f803f80u, gv[i].x), bf2_add(y.x, bf2_mul(u.x, dd))), bf2_mul(bf2_sub(0x3f803f80u, gv[i].y), bf2_add(y.y, bf2_mul(u.y, dd))),
                           bf2_mul(bf2_sub(0x3f803f80u, gv[i].z), bf2_add(y.z, bf2_mul(u.z, dd))), bf2_mul(bf2_sub(0x3f803f80u, gv[i].w), bf2_add(y.w, bf2_mul(u.w, dd))));
        }
        __syncwarp();
        if (lane < 16) reinterpret_cast<uint32_t*>(kr + 2048)[lane] = 0u;
        TS3(22 + 2 * ch);
    }
}
__device__ __forceinline__ void s4d_stage_u(unsigned char* smem_raw, const bf16* __restrict__ x, int pt) {
    bf16* u_all = reinterpret_cast<bf16*>(smem_raw);
    const int d0 = blockIdx.x * SD_CH;
#pragma unroll 1
    for (int b = 0; b < 4; b++) {
        uint4 v[8];
#pragma unroll
        for (int i = 0; i < 8; i++) {
            int c = pt + 128 * (8 * b + i);
            v[i] = *reinterpret_cast<const uint4*>(x + (size_t)(c >> 1) * DM + d0 + (c & 1) * 8);
        }
#pragma unroll
        for (int i = 0; i < 8; i++) {
            int c = pt + 128 * (8 * b + i), t = c >> 1;
            bf16* dst = u_all + (c & 1) * 8 * SD_USTR + (8 + (t >> 6)) * 72 + (t & 63);
            const bf16* pv = reinterpret_cast<const bf16*>(&v[i]);
#pragma unroll
            for (int ch = 0; ch < 8; ch++) dst[ch * SD_USTR] = pv[ch];
        }
    }
    asm volatile("bar.arrive 1, 384;" ::: "memory");
}

constexpr int WOC = DM / 3;
constexpr int TBUF = 5 * DH * 16;
constexpr int XBUF = SEG * DM * 2;
constexpr float ATT_SCALE = 0.08838834764831845f;
constexpr int SM_BAR = 0;
constexpr int B_SB = 0, B_VX = 16, B_XT = 32, B_W = 64, B_E = 136;
constexpr int SM_SC = 256;
constexpr int SM_F = SM_SC + 1280;
constexpr int SM_VM = SM_F + 2048;
constexpr int SM_S = SM_VM + 2048;
constexpr int SM_O = SM_S + 2560;
constexpr int SM_M = SM_O + 2048;
constexpr int SM_WS = 19456;
constexpr int SM_T = SM_WS + 32768;
constexpr int SM_VX = SM_T + 4 * TBUF;
constexpr int SM_X = SM_VX + 2 * 8192;
constexpr int SM_X01 = SM_WS + DM * DH * 2;
__host__ __device__ constexpr int x01_off(int b) { return b == 2 ? 2048 : SM_X01 + (b < 2 ? b + 6 : b - 3) * 8192; }
constexpr int SM_E = SM_WS + 6 * 16384;
constexpr int CH_SMEM = SM_X01 + 8 * 8192;
static_assert(SM_M + DM * 16 <= SM_WS && SM_X + 3 * XBUF <= CH_SMEM && CH_SMEM <= 232448 && SM_X % 1024 == 0 && SM_X01 % 1024 == 0 && SM_M >= 10240 && SM_F <= 2048, "smem");
__device__ __forceinline__ uint32_t clock32() { uint32_t t; asm volatile("mov.u32 %0, %%clock;" : "=r"(t) :: "memory"); return t; }

__device__ __forceinline__ uint32_t mapa(uint32_t a, uint32_t rank) {
    uint32_t r; asm volatile("mapa.shared::cluster.u32 %0, %1, %2;" : "=r"(r) : "r"(a), "r"(rank)); return r;
}
__device__ __forceinline__ void st_async32(uint32_t addr, uint32_t v, uint32_t mbar) {
    asm volatile("st.async.weak.shared::cluster.mbarrier::complete_tx::bytes.b32 [%0], %1, [%2];" :: "r"(addr), "r"(v), "r"(mbar) : "memory");
}
__device__ __forceinline__ void mbar_init(uint32_t bar, uint32_t cnt) {
    asm volatile("mbarrier.init.shared::cta.b64 [%0], %1;" :: "r"(bar), "r"(cnt) : "memory");
}
__device__ __forceinline__ void mbar_expect(uint32_t bar, uint32_t bytes) {
    asm volatile("mbarrier.arrive.expect_tx.shared::cta.b64 _, [%0], %1;" :: "r"(bar), "r"(bytes) : "memory");
}
__device__ __forceinline__ void mbar_wait(uint32_t bar, uint32_t parity) {
    unsigned it = 0;
    while (true) {
        uint32_t ok;
        asm volatile("{\n.reg .pred p;\nmbarrier.try_wait.parity.shared::cta.b64 p, [%1], %2;\nselp.u32 %0, 1, 0, p;\n}"
                     : "=r"(ok) : "r"(bar), "r"(parity) : "memory");
        if (ok || ++it >= SPIN_LIMIT) break;
    }
}
__device__ __forceinline__ void mbar_wait_long(uint32_t bar, uint32_t parity) {
    unsigned it = 0;
    while (true) {
        uint32_t ok;
        asm volatile("{\n.reg .pred p;\nmbarrier.try_wait.parity.shared::cta.b64 p, [%1], %2, %3;\nselp.u32 %0, 1, 0, p;\n}"
                     : "=r"(ok) : "r"(bar), "r"(parity), "r"(20000u) : "memory");
        if (ok || ++it >= SPIN_LIMIT) break;
    }
}
__device__ __forceinline__ uint64_t policy_evict_first() {
    uint64_t pol; asm volatile("createpolicy.fractional.L2::evict_first.b64 %0, 1.0;" : "=l"(pol)); return pol;
}
__device__ __forceinline__ void cluster_sync_all() {
    asm volatile("barrier.cluster.arrive.release.aligned;\nbarrier.cluster.wait.acquire.aligned;" ::: "memory");
}
__device__ __forceinline__ uint4 ld_vol_u4(const uint4* p) {
    uint4 v; asm volatile(LDV4 : "=r"(v.x), "=r"(v.y), "=r"(v.z), "=r"(v.w) : "l"(p) : "memory"); return v;
}
__device__ __forceinline__ void ld_vol_u4_p(uint4& v, const uint4* p, uint32_t pred) {
    asm volatile("{\n.reg .pred p;\nsetp.ne.u32 p, %5, 0;\n@p " LDV4 "\n}"
                 : "+r"(v.x), "+r"(v.y), "+r"(v.z), "+r"(v.w) : "l"(p), "r"(pred) : "memory");
}
__device__ __forceinline__ void st_vol_u4(uint4* p, uint4 v) {
    asm volatile(STV4 :: "l"(p), "r"(v.x), "r"(v.y), "r"(v.z), "r"(v.w) : "memory");
}
__device__ __forceinline__ void mma_bf16_r(float (&d)[4], uint32_t a0, uint32_t a1, uint32_t a2, uint32_t a3, uint32_t b0, uint32_t b1) {
    asm volatile("mma.sync.aligned.m16n8k16.row.col.f32.bf16.bf16.f32 {%0,%1,%2,%3}, {%4,%5,%6,%7}, {%8,%9}, {%0,%1,%2,%3};"
                 : "+f"(d[0]), "+f"(d[1]), "+f"(d[2]), "+f"(d[3])
                 : "r"(a0), "r"(a1), "r"(a2), "r"(a3), "r"(b0), "r"(b1));
}

__device__ __forceinline__ uint64_t smem_desc(uint32_t addr, uint32_t lbo, uint32_t sbo) {
    return (uint64_t)((addr & 0x3FFFF) >> 4) | ((uint64_t)(lbo >> 4) << 16) | ((uint64_t)(sbo >> 4) << 32);
}
__device__ __forceinline__ void wg_fence() { asm volatile("wgmma.fence.sync.aligned;" ::: "memory"); }
__device__ __forceinline__ void wg_commit() { asm volatile("wgmma.commit_group.sync.aligned;" ::: "memory"); }
__device__ __forceinline__ void wg_wait0() { asm volatile("wgmma.wait_group.sync.aligned 0;" ::: "memory"); }
__device__ __forceinline__ void fence_async() { asm volatile("fence.proxy.async.shared::cta;" ::: "memory"); }
__device__ __forceinline__ void wgmma_n32(float (&d)[16], const uint32_t (&a)[4], uint64_t bdesc, int scale_d) {
    asm volatile("{\n.reg .pred p;\nsetp.ne.b32 p, %21, 0;\n"
                 "wgmma.mma_async.sync.aligned.m64n32k16.f32.bf16.bf16 {%0,%1,%2,%3,%4,%5,%6,%7,%8,%9,%10,%11,%12,%13,%14,%15}, {%16,%17,%18,%19}, %20, p, 1, 1, 0;\n}"
                 : "+f"(d[0]), "+f"(d[1]), "+f"(d[2]), "+f"(d[3]), "+f"(d[4]), "+f"(d[5]), "+f"(d[6]), "+f"(d[7]),
                   "+f"(d[8]), "+f"(d[9]), "+f"(d[10]), "+f"(d[11]), "+f"(d[12]), "+f"(d[13]), "+f"(d[14]), "+f"(d[15])
                 : "r"(a[0]), "r"(a[1]), "r"(a[2]), "r"(a[3]), "l"(bdesc), "r"(scale_d));
}

__device__ __forceinline__ void wgmma_n32_ss(float (&d)[16], uint64_t adesc, uint64_t bdesc, int scale_d) {
    asm volatile("{\n.reg .pred p;\nsetp.ne.b32 p, %18, 0;\n"
                 "wgmma.mma_async.sync.aligned.m64n32k16.f32.bf16.bf16 {%0,%1,%2,%3,%4,%5,%6,%7,%8,%9,%10,%11,%12,%13,%14,%15}, %16, %17, p, 1, 1, 1, 0;\n}"
                 : "+f"(d[0]), "+f"(d[1]), "+f"(d[2]), "+f"(d[3]), "+f"(d[4]), "+f"(d[5]), "+f"(d[6]), "+f"(d[7]),
                   "+f"(d[8]), "+f"(d[9]), "+f"(d[10]), "+f"(d[11]), "+f"(d[12]), "+f"(d[13]), "+f"(d[14]), "+f"(d[15])
                 : "l"(adesc), "l"(bdesc), "r"(scale_d));
}

__device__ __forceinline__ void wgmma_n64_ss(float (&d)[32], uint64_t adesc, uint64_t bdesc) {
    asm volatile("{\n.reg .pred p;\nsetp.eq.b32 p, 0, 0;\n"
                 "wgmma.mma_async.sync.aligned.m64n64k16.f32.bf16.bf16 {%0,%1,%2,%3,%4,%5,%6,%7,%8,%9,%10,%11,%12,%13,%14,%15,%16,%17,%18,%19,%20,%21,%22,%23,"
                 "%24,%25,%26,%27,%28,%29,%30,%31}, %32, %33, p, 1, 1, 1, 0;\n}"
                 : "+f"(d[0]), "+f"(d[1]), "+f"(d[2]), "+f"(d[3]), "+f"(d[4]), "+f"(d[5]), "+f"(d[6]), "+f"(d[7]),
                   "+f"(d[8]), "+f"(d[9]), "+f"(d[10]), "+f"(d[11]), "+f"(d[12]), "+f"(d[13]), "+f"(d[14]), "+f"(d[15]),
                   "+f"(d[16]), "+f"(d[17]), "+f"(d[18]), "+f"(d[19]), "+f"(d[20]), "+f"(d[21]), "+f"(d[22]), "+f"(d[23]),
                   "+f"(d[24]), "+f"(d[25]), "+f"(d[26]), "+f"(d[27]), "+f"(d[28]), "+f"(d[29]), "+f"(d[30]), "+f"(d[31])
                 : "l"(adesc), "l"(bdesc));
}
__device__ __forceinline__ void tma_2d(uint32_t dst, const CUtensorMap* tm, int c0, int c1, uint32_t mbar) {
    asm volatile("cp.async.bulk.tensor.2d.shared::cluster.global.tile.mbarrier::complete_tx::bytes [%0], [%1, {%2, %3}], [%4];"
                 :: "r"(dst), "l"(tm), "r"(c0), "r"(c1), "r"(mbar) : "memory");
}

__device__ __forceinline__ void bulk_g2s(uint32_t dst, const void* src, uint32_t bytes, uint32_t mbar) {
    asm volatile("cp.async.bulk.shared::cluster.global.mbarrier::complete_tx::bytes [%0], [%1], %2, [%3];"
                 :: "r"(dst), "l"(src), "r"(bytes), "r"(mbar) : "memory");
}
__device__ __forceinline__ void bulk_g2s_h(uint32_t dst, const void* src, uint32_t bytes, uint32_t mbar, uint64_t pol) {
    asm volatile("cp.async.bulk.shared::cluster.global.mbarrier::complete_tx::bytes.L2::cache_hint [%0], [%1], %2, [%3], %4;"
                 :: "r"(dst), "l"(src), "r"(bytes), "r"(mbar), "l"(pol) : "memory");
}
__device__ __forceinline__ void tma_x(uint32_t dst, const CUtensorMap* tm, int seg, int part, uint32_t mbar) {
    asm volatile("cp.async.bulk.tensor.3d.shared::cluster.global.tile.mbarrier::complete_tx::bytes [%0], [%1, {%2, %3, %4}], [%5];"
                 :: "r"(dst + part * 12288), "l"(tm), "r"(0), "r"(seg * SEG), "r"(part * 3), "r"(mbar) : "memory");
}
__device__ __forceinline__ void tma_x_mc(uint32_t dst, const CUtensorMap* tm, int seg, int part, uint32_t mbar) {
    asm volatile("cp.async.bulk.tensor.3d.shared::cluster.global.tile.mbarrier::complete_tx::bytes.multicast::cluster [%0], [%1, {%2, %3, %4}], [%5], %6;"
                 :: "r"(dst + part * 12288), "l"(tm), "r"(0), "r"(seg * SEG), "r"(part * 3), "r"(mbar), "h"((unsigned short)7) : "memory");
}
__device__ __forceinline__ void bulk_s2s(uint32_t dst, uint32_t src, uint32_t bytes, uint32_t mbar) {
    asm volatile("cp.async.bulk.shared::cluster.shared::cta.mbarrier::complete_tx::bytes [%0], [%1], %2, [%3];"
                 :: "r"(dst), "r"(src), "r"(bytes), "r"(mbar) : "memory");
}
__device__ __forceinline__ void wgmma_n40_ss(float (&d)[20], uint64_t adesc, uint64_t bdesc, int scale_d) {
    asm volatile("{\n.reg .pred p;\nsetp.ne.b32 p, %22, 0;\n"
                 "wgmma.mma_async.sync.aligned.m64n40k16.f32.bf16.bf16 {%0,%1,%2,%3,%4,%5,%6,%7,%8,%9,%10,%11,%12,%13,%14,%15,%16,%17,%18,%19}, %20, %21, p, 1, 1, 1, 1;\n}"
                 : "+f"(d[0]), "+f"(d[1]), "+f"(d[2]), "+f"(d[3]), "+f"(d[4]), "+f"(d[5]), "+f"(d[6]), "+f"(d[7]),
                   "+f"(d[8]), "+f"(d[9]), "+f"(d[10]), "+f"(d[11]), "+f"(d[12]), "+f"(d[13]), "+f"(d[14]), "+f"(d[15]),
                   "+f"(d[16]), "+f"(d[17]), "+f"(d[18]), "+f"(d[19])
                 : "l"(adesc), "l"(bdesc), "r"(scale_d));
}
__device__ __forceinline__ void wgmma_n64_z(float (&d)[32], const uint32_t (&a)[4], uint64_t bdesc) {
    asm volatile("{\n.reg .pred p;\nsetp.ne.b32 p, 0, 0;\n"
                 "wgmma.mma_async.sync.aligned.m64n64k16.f32.bf16.bf16 {%0,%1,%2,%3,%4,%5,%6,%7,%8,%9,%10,%11,%12,%13,%14,%15,%16,%17,%18,%19,%20,%21,%22,%23,%24,%25,%26,%27,%28,%29,%30,%31}, {%32,%33,%34,%35}, %36, p, 1, 1, 0;\n}"
                 : "=f"(d[0]), "=f"(d[1]), "=f"(d[2]), "=f"(d[3]), "=f"(d[4]), "=f"(d[5]), "=f"(d[6]), "=f"(d[7]),
                   "=f"(d[8]), "=f"(d[9]), "=f"(d[10]), "=f"(d[11]), "=f"(d[12]), "=f"(d[13]), "=f"(d[14]), "=f"(d[15]),
                   "=f"(d[16]), "=f"(d[17]), "=f"(d[18]), "=f"(d[19]), "=f"(d[20]), "=f"(d[21]), "=f"(d[22]), "=f"(d[23]),
                   "=f"(d[24]), "=f"(d[25]), "=f"(d[26]), "=f"(d[27]), "=f"(d[28]), "=f"(d[29]), "=f"(d[30]), "=f"(d[31])
                 : "r"(a[0]), "r"(a[1]), "r"(a[2]), "r"(a[3]), "l"(bdesc));
}
__device__ __forceinline__ void wgmma_n64(float (&d)[32], const uint32_t (&a)[4], uint64_t bdesc, int scale_d) {
    asm volatile("{\n.reg .pred p;\nsetp.ne.b32 p, %37, 0;\n"
                 "wgmma.mma_async.sync.aligned.m64n64k16.f32.bf16.bf16 {%0,%1,%2,%3,%4,%5,%6,%7,%8,%9,%10,%11,%12,%13,%14,%15,%16,%17,%18,%19,%20,%21,%22,%23,%24,%25,%26,%27,%28,%29,%30,%31}, {%32,%33,%34,%35}, %36, p, 1, 1, 0;\n}"
                 : "+f"(d[0]), "+f"(d[1]), "+f"(d[2]), "+f"(d[3]), "+f"(d[4]), "+f"(d[5]), "+f"(d[6]), "+f"(d[7]),
                   "+f"(d[8]), "+f"(d[9]), "+f"(d[10]), "+f"(d[11]), "+f"(d[12]), "+f"(d[13]), "+f"(d[14]), "+f"(d[15]),
                   "+f"(d[16]), "+f"(d[17]), "+f"(d[18]), "+f"(d[19]), "+f"(d[20]), "+f"(d[21]), "+f"(d[22]), "+f"(d[23]),
                   "+f"(d[24]), "+f"(d[25]), "+f"(d[26]), "+f"(d[27]), "+f"(d[28]), "+f"(d[29]), "+f"(d[30]), "+f"(d[31])
                 : "r"(a[0]), "r"(a[1]), "r"(a[2]), "r"(a[3]), "l"(bdesc), "r"(scale_d));
}

constexpr int SB_FULL = 0, SB_EMPTY = 64, SB_QKF = 128, SB_VF = 144, SB_QKE = 160, SB_VE = 176, SB_OF = 192, SB_WO = 208, SB_TICK = 216;
constexpr int AT_0 = 256, AT_ST = 10240 + 2 * 9216;
constexpr int FS_A = 58368;
constexpr int FS_P = FS_A + 131072;
constexpr int FS_I = FS_P + 16384;
constexpr int FS_O = FS_I + 12288;
constexpr int FS_Z = FS_O + 12288, FS_G = AT_0 + 2 * AT_ST;
constexpr int SIDE_SMEM = FS_Z + 2048;
static_assert(SIDE_SMEM <= 232448 && FS_G + 128 <= FS_A && FS_A + SD_SMEM <= SIDE_SMEM, "smem");

__device__ __forceinline__ void bf16r2(float& a, float& b) {
    uint32_t p = pack_bf16(a, b);
    a = __uint_as_float(p << 16); b = __uint_as_float(p & 0xffff0000u);
}
__device__ __forceinline__ void wg_wait1() { asm volatile("wgmma.wait_group.sync.aligned 1;" ::: "memory"); }
__device__ __forceinline__ void mbar_arrive(uint32_t bar) { asm volatile("mbarrier.arrive.shared::cta.b64 _, [%0];" :: "r"(bar) : "memory"); }
__device__ __forceinline__ void wait_cnt_rlx(const unsigned* p, unsigned target, bool urgent) {
    unsigned it = 0, v;
    while (true) {
        asm volatile("ld.relaxed.gpu.global.u32 %0, [%1];" : "=r"(v) : "l"(p) : "memory");
        if ((int)(v - target) >= 0 || ++it >= SPIN_LIMIT) break;
        if (!urgent) __nanosleep(RLX_SLEEP);
    }
}

__device__ __forceinline__ uint32_t gtime32() { uint32_t t; asm volatile("mov.u32 %0, %%globaltimer_lo;" : "=r"(t) :: "memory"); return t; }
__device__ __forceinline__ void gate(uint32_t tick_addr) {
    uint32_t t1, p;
    asm volatile("ld.volatile.shared.v2.u32 {%0,%1}, [%2];" : "=r"(t1), "=r"(p) : "r"(tick_addr) : "memory");
    uint32_t d = gtime32() - t1;
    if (d < 4u * p) {
        d -= d >= 2u * p ? 2u * p : 0u;
        d -= d >= p ? p : 0u;
        if (d + GATE_A >= p && d + GATE_B < p) {
            const uint32_t t2 = gtime32() + (p - GATE_B - d);
            while ((int)(gtime32() - t2) < 0) {}
        }
    }
}

__device__ __forceinline__ void read_tick(uint32_t tick_addr, bool on) {
    const uint2 tk = ld_vol_u2(&g_tick);
    uint32_t p = tk.x - tk.y;
    p = p > GATE_P + 100u ? GATE_P + 100u : p;
    asm volatile("st.volatile.shared.v2.u32 [%0], {%1,%2};" :: "r"(tick_addr), "r"(tk.x), "r"(on ? p : 0u) : "memory");
}

__device__ __forceinline__ void xrow_softmax(float (&sc)[20], uint32_t (&pa)[3][4], int wq, int lane) {
    const int g = lane >> 2, tq = lane & 3;
    float mx0 = -INFINITY;
    const int q0 = MEMT + 8 * wq + g;
#pragma unroll
    for (int j = 0; j < 5; j++) {
        bf16r2(sc[4 * j], sc[4 * j + 1]);
        sc[4 * j] *= ATT_SCALE; sc[4 * j + 1] *= ATT_SCALE;
        bf16r2(sc[4 * j], sc[4 * j + 1]);
#pragma unroll
        for (int c = 0; c < 2; c++) {
            int key = 8 * j + 2 * tq + c;
            if (key > q0) sc[4 * j + c] = -INFINITY;
            mx0 = fmaxf(mx0, sc[4 * j + c]);
        }
    }
    mx0 = fmaxf(mx0, __shfl_xor_sync(0xffffffffu, mx0, 1)); mx0 = fmaxf(mx0, __shfl_xor_sync(0xffffffffu, mx0, 2));
    float sum0 = 0.f;
#pragma unroll
    for (int j = 0; j < 5; j++) {
#pragma unroll
        for (int c = 0; c < 2; c++) {
            float e0 = __expf(sc[4 * j + c] - mx0);
            sc[4 * j + c] = e0;
            sum0 += e0;
        }
    }
    sum0 += __shfl_xor_sync(0xffffffffu, sum0, 1); sum0 += __shfl_xor_sync(0xffffffffu, sum0, 2);
    const float i0 = 1.f / sum0;
#pragma unroll
    for (int ks = 0; ks < 3; ks++) {
        pa[ks][0] = pack_bf16(sc[8 * ks] * i0, sc[8 * ks + 1] * i0);
        pa[ks][1] = 0u;
        pa[ks][2] = ks < 2 ? pack_bf16(sc[8 * ks + 4] * i0, sc[8 * ks + 5] * i0) : 0u;
        pa[ks][3] = 0u;
    }
}

__device__ __forceinline__ void stsm_x4(uint32_t addr, uint32_t r0, uint32_t r1, uint32_t r2, uint32_t r3) {
    asm volatile("stmatrix.sync.aligned.m8n8.x4.shared.b16 [%0], {%1,%2,%3,%4};" :: "r"(addr), "r"(r0), "r"(r1), "r"(r2), "r"(r3) : "memory");
}
__device__ __forceinline__ uint32_t h2_to_bf2(uint32_t h) {
    uint32_t r;
    asm("{\n.reg .f16 l, h;\n.reg .f32 a, b;\nmov.b32 {l, h}, %1;\ncvt.f32.f16 a, l;\ncvt.f32.f16 b, h;\ncvt.rn.bf16x2.f32 %0, b, a;\n}" : "=r"(r) : "r"(h));
    return r;
}
__device__ __forceinline__ uint32_t max_abs2(uint32_t a, uint32_t b) { uint32_t r; asm("max.NaN.xorsign.abs.bf16x2 %0, %1, %2;" : "=r"(r) : "r"(a), "r"(b)); return r; }
__device__ __forceinline__ uint32_t movm(uint32_t v) {
    uint32_t r; asm volatile("movmatrix.sync.aligned.m8n8.trans.b16 %0, %1;" : "=r"(r) : "r"(v)); return r;
}
__device__ __forceinline__ void bar_arrive(int id, int n) { asm volatile("bar.arrive %0, %1;" :: "r"(id), "r"(n) : "memory"); }
__device__ __forceinline__ void lds64(uint32_t& a, uint32_t& b, uint32_t addr) {
    asm volatile("ld.shared.v2.u32 {%0,%1}, [%2];" : "=r"(a), "=r"(b) : "r"(addr) : "memory");
}
__device__ __forceinline__ void lds64f(float& a, float& b, uint32_t addr) {
    asm volatile("ld.shared.v2.f32 {%0,%1}, [%2];" : "=f"(a), "=f"(b) : "r"(addr) : "memory");
}
__device__ __forceinline__ void st_async64(uint32_t addr, uint32_t a, uint32_t b, uint32_t mbar) {
    asm volatile("st.async.weak.shared::cluster.mbarrier::complete_tx::bytes.v2.b32 [%0], {%1,%2}, [%3];" :: "r"(addr), "r"(a), "r"(b), "r"(mbar) : "memory");
}
__device__ __forceinline__ void mma_z(float (&d)[4], const uint32_t (&a)[4], uint32_t b0, uint32_t b1) {
    asm volatile("mma.sync.aligned.m16n8k16.row.col.f32.bf16.bf16.f32 {%0,%1,%2,%3}, {%4,%5,%6,%7}, {%8,%9}, {%10,%10,%10,%10};"
                 : "=f"(d[0]), "=f"(d[1]), "=f"(d[2]), "=f"(d[3])
                 : "r"(a[0]), "r"(a[1]), "r"(a[2]), "r"(a[3]), "r"(b0), "r"(b1), "f"(0.f));
}
__device__ __forceinline__ void mma_k8(float (&d)[4], uint32_t a0, uint32_t a1, uint32_t b) {
    asm volatile("mma.sync.aligned.m16n8k8.row.col.f32.bf16.bf16.f32 {%0,%1,%2,%3}, {%4,%5}, {%6}, {%0,%1,%2,%3};"
                 : "+f"(d[0]), "+f"(d[1]), "+f"(d[2]), "+f"(d[3]) : "r"(a0), "r"(a1), "r"(b));
}
__global__ void __launch_bounds__(512, 1) k_side(const __grid_constant__ CUtensorMap tmo, const bf16* __restrict__ x, const bf16* __restrict__ logA, const bf16* __restrict__ Aim,
                                                 const bf16* __restrict__ Cre, const bf16* __restrict__ Cim, const bf16* __restrict__ logdt,
                                                 const bf16* __restrict__ Wo, const bf16* __restrict__ dskip, const bf16* __restrict__ gw,
                                                 bf16* __restrict__ out) {
    extern __shared__ __align__(1024) unsigned char smem_raw[];
    const uint32_t sbase = smem_u32(smem_raw);
    const int tid = threadIdx.x, warp = __shfl_sync(0xffffffffu, tid >> 5, 0), lane = tid & 31, cta = blockIdx.x;
    const int cb = cta >> 2, kq = cta & 3;
    if (tid == 0) {
        for (int i = 0; i < 8; i++) { mbar_init(sbase + SB_FULL + 8 * i, 1); mbar_init(sbase + SB_EMPTY + 8 * i, 4); }
        for (int i = 0; i < 2; i++) {
            mbar_init(sbase + SB_QKF + 8 * i, 1); mbar_init(sbase + SB_VF + 8 * i, 1); mbar_init(sbase + SB_QKE + 8 * i, 1);
            mbar_init(sbase + SB_VE + 8 * i, 4); mbar_init(sbase + SB_OF + 8 * i, 4);
        }
        mbar_init(sbase + SB_WO, 1);
        *reinterpret_cast<uint2*>(smem_raw + SB_TICK) = make_uint2(0u, 0u);
        asm volatile("fence.mbarrier_init.release.cluster;" ::: "memory");
    }
    TS3(0);
    unsigned ep;
    asm volatile("ld.volatile.global.u32 %0, [%1];" : "=r"(ep) : "l"(&g_epoch) : "memory");
    ep += 1u;
    asm volatile("fence.proxy.async;" ::: "memory");
    __syncthreads();
    if (warp >= 12) {
      asm volatile("setmaxnreg.dec.sync.aligned.u32 40;");
      if (warp == 12 || warp == 15) {
        named_bar(3, 320);
        if (tid == 384) {
            fence_async();
            mbar_expect(sbase + SB_WO, 131072);
            if (cta >= NH) read_tick(sbase + SB_TICK, true);
#pragma unroll 1
            for (int i = 0; i < 8; i++) {
                gate(sbase + SB_TICK);
                tma_2d(sbase + FS_A + i * 16384, &tmo, cb * 64, kq * 1024 + i * 128, sbase + SB_WO);
                __nanosleep(150);
            }
            TSS(17, 2);
        }
        if (tid == 480) {
            __threadfence();
            asm volatile("red.relaxed.gpu.global.add.u32 [%0], 1;" :: "l"(&g_gcnt[32]) : "memory");
            TSS(17, 3);
        }
        __syncwarp();
        named_bar(7, 320);
        if (lane == 0) {
            const int pi = warp == 12 ? 0 : 1, kb = 2 * kq + pi;
            fence_async();
            for (int pr = 0; pr < NSEG / 2; pr++) {
                wait_cnt_rlx(&g_prog[pr * 8 + kb], 8u * ep, pr >= NSEG / 2 - 2);
                if (pi == 0 && cta >= NH) read_tick(sbase + SB_TICK, pr < NSEG / 2 - 2);
                if (pr >= 30 && pi == 0) TSS(4 + pr - 30, 0);
                if (pr == 31) TS3P(26);
                if (pr == 30) TS3P(1);
#pragma unroll
                for (int j = 0; j < 4; j++) {
                    const int st = 4 * pi + j;
                    mbar_wait_long(sbase + SB_EMPTY + 8 * st, ((uint32_t)pr & 1u) ^ 1u);
                    mbar_expect(sbase + SB_FULL + 8 * st, X_OXSZ);
                    gate(sbase + SB_TICK);
                    bulk_g2s(sbase + FS_A + st * 16384, g_ox + ((size_t)(pr * NH + 4 * kb + j)) * 8192, X_OXSZ, sbase + SB_FULL + 8 * st);
                }
            }
        }
        __syncwarp();
      } else if (warp == 13) {
        if (lane == 0 && cta < NH) {
            const uint64_t pol = policy_evict_first();
            for (int seg = 0; seg < NSEG; seg++) {
                const uint32_t st = seg & 1, ph = (uint32_t)(seg >> 1) & 1u, ab = sbase + AT_0 + st * AT_ST;
                wait_cnt_rlx(&g_flag[seg * NH + cta], 3u * ep, seg >= NSEG - 4);
                if (seg >= 60) TSS(seg - 60, 0);
                mbar_wait_long(sbase + SB_QKE + 8 * st, ph ^ 1u);
                if (seg >= 60) TSS(seg - 60, 1);
                mbar_expect(sbase + SB_QKF + 8 * st, 2 * 9216);
                gate(sbase + SB_TICK);
                bulk_g2s_h(ab + 10240, &g_qkv[seg][cta][0][1024], 9216, sbase + SB_QKF + 8 * st, pol);
                bulk_g2s_h(ab + 10240 + 9216, &g_qkv[seg][cta][1][1024], 9216, sbase + SB_QKF + 8 * st, pol);
                mbar_wait_long(sbase + SB_VE + 8 * st, ph ^ 1u);
                mbar_expect(sbase + SB_VF + 8 * st, 10240);
                bulk_g2s_h(ab, &g_qkv[seg][cta][2][0], 10240, sbase + SB_VF + 8 * st, pol);
                read_tick(sbase + SB_TICK, seg < NSEG - 6);
            }
        }
        __syncwarp();
      } else if (warp == 14) {
        if (lane == 0 && cta < NH) {
            for (int seg = 0; seg < NSEG; seg++) {
                const uint32_t st = seg & 1, ab = sbase + AT_0 + st * AT_ST;
                mbar_wait_long(sbase + SB_OF + 8 * st, (uint32_t)(seg >> 1) & 1u);
                if (seg >= 60) TSS(seg - 60, 3);
                gate(sbase + SB_TICK);
                unsigned char* dst = reinterpret_cast<unsigned char*>(g_ox) + ((size_t)((seg >> 1) * NH + cta)) * 16384 + (seg & 1) * 4096;
                asm volatile("cp.async.bulk.global.shared::cta.bulk_group [%0], [%1], 4096;" :: "l"(dst), "r"(ab + 12288) : "memory");
                asm volatile("cp.async.bulk.global.shared::cta.bulk_group [%0], [%1], 4096;" :: "l"(dst + 8192), "r"(ab + 16384) : "memory");
                asm volatile("cp.async.bulk.commit_group;" ::: "memory");
                asm volatile("cp.async.bulk.wait_group 0;" ::: "memory");
                asm volatile("red.relaxed.gpu.global.add.u32 [%0], 1;" :: "l"(&g_prog[(seg >> 1) * 8 + (cta >> 2)]) : "memory");
                mbar_arrive(sbase + SB_QKE + 8 * st);
                if (seg >= 60) TSS(seg - 60, 4);
            }
        }
        __syncwarp();
      }
    } else if (warp >= 8) {
        asm volatile("setmaxnreg.dec.sync.aligned.u32 88;");
        s4d_stage_u(smem_raw + FS_A, x, tid - 256);
        {
            uint32_t gwv[9];
#pragma unroll
            for (int i = 0; i < 9; i++) gwv[i] = reinterpret_cast<const uint32_t*>(gw)[lane + 32 * i];
#pragma unroll 3
            for (int i = 0; i < 15; i++) {
                const int tt = 4 * i + warp - 8, t = min(cta * 57 + tt, S_LEN - 1);
                float sm = 0.f;
#pragma unroll
                for (int k = 0; k < 9; k++) {
                    const uint32_t xv = reinterpret_cast<const uint32_t*>(x + t * DM)[lane + 32 * k];
                    float a = __uint_as_float(xv << 16) * __uint_as_float(gwv[k] << 16), b = __uint_as_float(xv & 0xffff0000u) * __uint_as_float(gwv[k] & 0xffff0000u);
                    bf16r2(a, b);
                    sm += a + b;
                }
#pragma unroll
                for (int o = 16; o; o >>= 1) sm += __shfl_xor_sync(0xffffffffu, sm, o);
                const float gv = 1.f / (1.f + expf(-bf16r(sm)));
                if (lane == 0 && tt < 57) g_gate[t] = __float2bfloat16_rn(gv);
            }
#pragma unroll 1
            for (int b8 = 0; b8 < 8; b8++)
#pragma unroll
                for (int i = 0; i < 6; i++) g_fp[b8][cta][i][tid - 256] = make_uint4(0u, 0u, 0u, 0u);
            named_bar(6, 128);
            if (tid == 256) {
                __threadfence();
                asm volatile("red.relaxed.gpu.global.add.u32 [%0], 1;" :: "l"(&g_gcnt[0]) : "memory");
            }
            __syncwarp();
        }
        const int wq = warp - 8;
        for (int seg = 0; seg < (cta < NH ? NSEG : 0); seg++) {
            const uint32_t st = seg & 1, ph = (uint32_t)(seg >> 1) & 1u, ab = sbase + AT_0 + st * AT_ST;
            float sc[20];
            mbar_wait_long(sbase + SB_QKF + 8 * st, ph);
            if (seg >= 60 && tid == 256) TSS(seg - 60, 2);
            {
                const uint64_t da = smem_desc(ab + 10240 + 1024, 128, 1024), db = smem_desc(ab + 10240, 128, 2048);
                wg_fence();
#pragma unroll
                for (int ks = 0; ks < 8; ks++) wgmma_n40_ss(sc, da + (uint64_t)((ks >> 2) * 576 + (ks & 3) * 16), db + (uint64_t)((ks >> 2) * 576 + (ks & 3) * 16), ks > 0);
                wg_commit();
                wg_wait0();
            }
            uint32_t pa[3][4];
            xrow_softmax(sc, pa, wq, lane);
            named_bar(6, 128);
            mbar_wait_long(sbase + SB_VF + 8 * st, ph);
#pragma unroll
            for (int hf = 0; hf < 2; hf++) {
                float o[32];
                const uint64_t dv = smem_desc(ab + hf * 1024, 2048, 128);
                wg_fence();
#pragma unroll
                for (int ks = 0; ks < 3; ks++) { if (ks == 0) wgmma_n64_z(o, pa[0], dv); else wgmma_n64(o, pa[ks], dv + (uint64_t)(ks * 256), 1); }
                wg_commit();
                wg_wait0();
#pragma unroll
                for (int i = 0; i < 2; i++)
                    stsm_x4(ab + 12288 + hf * 4096 + wq * 1024 + i * 512 + lane * 16, pack_bf16(o[16 * i], o[16 * i + 1]), pack_bf16(o[16 * i + 4], o[16 * i + 5]),
                            pack_bf16(o[16 * i + 8], o[16 * i + 9]), pack_bf16(o[16 * i + 12], o[16 * i + 13]));
            }
            if (lane == 0) mbar_arrive(sbase + SB_VE + 8 * st);
            fence_async();
            __syncwarp();
            if (lane == 0) mbar_arrive(sbase + SB_OF + 8 * st);
        }
    } else {
        asm volatile("setmaxnreg.inc.sync.aligned.u32 192;");
        const int wg = warp >> 2, wq = warp & 3;
        s4d_phase(smem_raw + FS_A, x, logA, Aim, Cre, Cim, logdt, dskip, Wo + (size_t)((2 * kq + wg) * 512) * DM + cb * 64, ep);
        TS3(2);
        if (lane == 0) TSS(16, warp);
        named_bar(3, 320);
        if (tid == 0) TSS(17, 0);
        uint32_t wa[32][4];
        mbar_wait_long(sbase + SB_WO, 0);
        if (tid == 0) TSS(17, 1);
        {
            const uint32_t a = sbase + FS_A + wg * 65536 + ((lane >> 4) * 8 + (lane & 7)) * 128 + (((wq * 2 + ((lane >> 3) & 1)) ^ (lane & 7)) << 4);
#pragma unroll
            for (int ks = 0; ks < 32; ks++) ldsm_x4_t(wa[ks], a + ks * 2048);
        }
        named_bar(7, 320);
        TS3(3);
        if (tid == 0) TSS(17, 4);
        auto product = [&](float (&acc)[32], int pr) {
                if (pr + wg > 0) named_bar(4 + wg, 256);
                const uint64_t db = smem_desc(sbase + FS_A + wg * 65536, 128, 1024);
                TSG(0);
#pragma unroll
                for (int j = 0; j < 4; j++) {
                    mbar_wait(sbase + SB_FULL + 8 * (4 * wg + j), (uint32_t)pr & 1u);
                    wg_fence();
#pragma unroll
                    for (int ks = 0; ks < 8; ks++) {
                        if ((j | ks) == 0) wgmma_n64_z(acc, wa[0], db);
                        else wgmma_n64(acc, wa[8 * j + ks], db + (uint64_t)(j * 1024 + (ks >> 2) * 512 + (ks & 3) * 16), 1);
                    }
                    wg_commit();
                    if (j == 3 && pr + wg < NSEG / 2) bar_arrive(4 + (wg ^ 1), 256);
                    if (j > 0) { wg_wait1(); if (lane == 0) mbar_arrive(sbase + SB_EMPTY + 8 * (4 * wg + j - 1)); }
                }
                wg_wait0();
                if (pr == 31) TS3W(27);
                TSG(3);
                if (lane == 0) mbar_arrive(sbase + SB_EMPTY + 8 * (4 * wg + 3));
        };
        if (wg == 1) {
            for (int pr = 0; pr < NSEG / 2; pr++) {
                uint32_t t16 = (uint32_t)(wq * 32 + lane) * 16u;
                asm volatile("" : "+r"(t16));
                float acc[32];
                product(acc, pr);
                    uint32_t tag = ((uint32_t)(pr >> 3) & 1u) ^ 1u;
                    tag = __shfl_sync(0xffffffffu, tag, lane);
                    gate(sbase + SB_TICK);
                    named_bar(8, 256);
                    unsigned char* dst = reinterpret_cast<unsigned char*>(&g_fp[pr & 7][4 * cb][2 * kq - 2][0]) + t16;
                    const uint32_t own = sbase + FS_O + (pr % 3) * 4096 + t16;
#pragma unroll
                    for (int q = 0; q < 8; q++) {
                        float4 p;
                        asm volatile("ld.shared.v4.f32 {%0,%1,%2,%3}, [%4];" : "=f"(p.x), "=f"(p.y), "=f"(p.z), "=f"(p.w) : "r"(sbase + FS_P + t16 + q * 2048) : "memory");
                        acc[4 * q] = __uint_as_float((__float_as_uint(acc[4 * q] + p.x) & ~1u) | tag); acc[4 * q + 1] = __uint_as_float((__float_as_uint(acc[4 * q + 1] + p.y) & ~1u) | tag);
                        acc[4 * q + 2] = __uint_as_float((__float_as_uint(acc[4 * q + 2] + p.z) & ~1u) | tag); acc[4 * q + 3] = __uint_as_float((__float_as_uint(acc[4 * q + 3] + p.w) & ~1u) | tag);
                    }
#pragma unroll
                    for (int q = 0; q < 8; q++) {
                        asm volatile("{\n.reg .pred p;\nsetp.ne.s32 p, %5, %6;\n@p st.volatile.global.v4.f32 [%0], {%1,%2,%3,%4};\n@!p st.shared.v4.f32 [%7], {%1,%2,%3,%4};\n}"
                                     :: "l"(dst + (q & 1) * 2048), "f"(acc[4 * q]), "f"(acc[4 * q + 1]), "f"(acc[4 * q + 2]), "f"(acc[4 * q + 3]), "r"(q >> 1), "r"(kq),
                                        "r"(own + (q & 1) * 2048) : "memory");
                        if (q & 1) dst += (q >> 1) == kq ? 12288 + 4096 : 12288;
                    }
                    bar_arrive(9, 256);
                    if (pr == 31) TS3W(28);
                TSG(4);
            }
        } else {
          for (int it = 0; it < NSEG / 2 + 3; it++) {
            const int pr = it < 31 ? it : (it == 33 ? 31 : -1);
            const int pf = it == 33 ? -1 : (it == 34 ? 31 : it - 2);
            uint32_t t16 = (uint32_t)(wq * 32 + lane) * 16u;
            asm volatile("" : "+r"(t16));
            const int t0 = pf * 64 + kq * 16, c0 = cb * 64 + wq * 16;
            auto fetch = [&]() {
                const unsigned char* src = reinterpret_cast<const unsigned char*>(&g_fp[pf & 7][cta][0][0]) + t16;
#pragma unroll
                for (int r = 0; r < 6; r++) asm volatile("cp.async.cg.shared.global [%0], [%1], 16;" :: "r"(sbase + FS_I + t16 + r * 2048), "l"(src + r * 2048) : "memory");
                asm volatile("cp.async.commit_group;" ::: "memory");
            };
            if (pf >= 0) {
                if (pf == 0) { if (lane == 0) wait_cnt(&g_gcnt[32], SD_NCTA * ep); __syncwarp(); }
                asm volatile("cp.async.cg.shared.global [%0], [%1], 16;" :: "r"(sbase + FS_Z + t16), "l"(g_y + (size_t)(c0 + (lane & 15)) * S_LEN + t0 + (lane >> 4) * 8) : "memory");
                if (lane < 2) asm volatile("cp.async.cg.shared.global [%0], [%1], 16;" :: "r"(sbase + FS_G + wq * 32 + lane * 16), "l"(g_gate + t0 + lane * 8) : "memory");
            }
            if (it == 32 || it == 34) named_bar(9, 256);
            if (pf >= 0) { gate(sbase + SB_TICK); fetch(); }
            if (pr >= 0) {
                float acc[32];
                product(acc, pr);
                    if (pr > 0 && pr < 31) named_bar(9, 256);
#pragma unroll
                    for (int q = 0; q < 8; q++)
                        asm volatile("st.shared.v4.f32 [%0], {%1,%2,%3,%4};" :: "r"(sbase + FS_P + t16 + q * 2048), "f"(acc[4 * q]), "f"(acc[4 * q + 1]), "f"(acc[4 * q + 2]), "f"(acc[4 * q + 3]) : "memory");
                    bar_arrive(8, 256);
                TSG(4);
            }
            if (pf >= 0) {
                const uint32_t tag = ((uint32_t)(pf >> 3) & 1u) ^ 1u;
                uint4 v[8];
                unsigned n = 0;
                while (true) {
                    asm volatile("cp.async.wait_group 0;" ::: "memory");
                    uint32_t any = 0u;
#pragma unroll
                    for (int r = 0; r < 8; r++)
                        asm volatile("ld.shared.v4.u32 {%0,%1,%2,%3}, [%4];" : "=r"(v[r].x), "=r"(v[r].y), "=r"(v[r].z), "=r"(v[r].w)
                                     : "r"(sbase + t16 + (r < 6 ? FS_I + r * 2048 : FS_O + (pf % 3) * 4096 + (r - 6) * 2048)) : "memory");
#pragma unroll
                    for (int r = 0; r < 6; r++) {
                        uint32_t c0_, c1_;
                        asm("lop3.b32 %0, %1, %2, %3, 0x7e;" : "=r"(c0_) : "r"(v[r].x), "r"(v[r].y), "r"(tag));
                        asm("lop3.b32 %0, %1, %2, %3, 0x7e;" : "=r"(c1_) : "r"(v[r].z), "r"(v[r].w), "r"(tag));
                        asm("lop3.b32 %0, %1, %2, %3, 0xfe;" : "=r"(any) : "r"(any), "r"(c0_), "r"(c1_));
                    }
                    if (!__any_sync(0xffffffffu, (any & 1u) != 0u) || ++n >= SPIN_LIMIT) break;
                    if (pf + 1 < NSEG / 2) __nanosleep(200);
                    fetch();
                }
                if (pf == 31) TS3(29);
                TSG(5);
                uint32_t zv[4], gg[2];
                ldsm_x4_t(zv, sbase + FS_Z + t16);
#pragma unroll
                for (int k = 0; k < 2; k++) gg[k] = __byte_perm(*reinterpret_cast<const unsigned short*>(smem_raw + FS_G + wq * 32 + k * 16 + (lane >> 2) * 2), 0u, 0x1010);
                const uint32_t xo = (uint32_t)((t0 + (lane >> 2)) * DM + c0 + 2 * (lane & 3)) * 2u;
#define PQS(k, f) ((__uint_as_float(v[k].f) + __uint_as_float(v[2 + k].f)) + (__uint_as_float(v[4 + k].f) + __uint_as_float(v[6 + k].f)))
#pragma unroll
                for (int k = 0; k < 2; k++) {
                    unsigned char* op = reinterpret_cast<unsigned char*>(out) + xo + k * (16 * DM);
                    *reinterpret_cast<uint32_t*>(op) = bf2_add(bf2_mul(gg[k], movm(pack_bf16(PQS(k, x), PQS(k, y)))), zv[2 * k]);
                    *reinterpret_cast<uint32_t*>(op + 16) = bf2_add(bf2_mul(gg[k], movm(pack_bf16(PQS(k, z), PQS(k, w)))), zv[2 * k + 1]);
                }
#undef PQS
                if ((pf & 1) == 0) TS3(4 + pf / 2);
                if (pf == 31) TS3(25);
                TSG(6);
            }
        }
        }
        if (cta == 0 && tid == 0) asm volatile("red.relaxed.gpu.global.add.u32 [%0], 1;" :: "l"(&g_epoch) : "memory");
    }
    asm volatile("griddepcontrol.wait;" ::: "memory");
}

__device__ __forceinline__ uint32_t poll_mem(const uint4* src, uint32_t dst, uint32_t t0) {
    uint4 v[6];
    unsigned it = 0;
#pragma unroll
    for (int j = 0; j < 6; j++) v[j] = make_uint4(0u, 0u, 0u, 0u);
    while (clock32() - t0 < POLL_DELAY) {}
    FS(12, 0);
    bool more;
#pragma unroll 1
    do {
        asm volatile("{\n.reg .pred p<6>;\n"
                     "setp.ne.u32 p0, %3, 0x5000;\nsetp.ne.u32 p1, %7, 0x5000;\nsetp.ne.u32 p2, %11, 0x5000;\n"
                     "setp.ne.u32 p3, %15, 0x5000;\nsetp.ne.u32 p4, %19, 0x5000;\nsetp.ne.u32 p5, %23, 0x5000;\n"
                     "@p0 ld.volatile.global.v4.u32 {%0,%1,%2,%3}, [%24];\n@p1 ld.volatile.global.v4.u32 {%4,%5,%6,%7}, [%24+4096];\n"
                     "@p2 ld.volatile.global.v4.u32 {%8,%9,%10,%11}, [%24+8192];\n@p3 ld.volatile.global.v4.u32 {%12,%13,%14,%15}, [%24+12288];\n"
                     "@p4 ld.volatile.global.v4.u32 {%16,%17,%18,%19}, [%24+16384];\n@p5 ld.volatile.global.v4.u32 {%20,%21,%22,%23}, [%24+20480];\n}"
                     : "+r"(v[0].x), "+r"(v[0].y), "+r"(v[0].z), "+r"(v[0].w), "+r"(v[1].x), "+r"(v[1].y), "+r"(v[1].z), "+r"(v[1].w),
                       "+r"(v[2].x), "+r"(v[2].y), "+r"(v[2].z), "+r"(v[2].w), "+r"(v[3].x), "+r"(v[3].y), "+r"(v[3].z), "+r"(v[3].w),
                       "+r"(v[4].x), "+r"(v[4].y), "+r"(v[4].z), "+r"(v[4].w), "+r"(v[5].x), "+r"(v[5].y), "+r"(v[5].z), "+r"(v[5].w)
                     : "l"(src) : "memory");
        stsm_x4(dst, h2_to_bf2(v[0].x), h2_to_bf2(v[0].y), h2_to_bf2(v[0].z), h2_to_bf2(v[1].x));
        stsm_x4(dst + 512, h2_to_bf2(v[1].y), h2_to_bf2(v[1].z), h2_to_bf2(v[2].x), h2_to_bf2(v[2].y));
        stsm_x4(dst + 1024, h2_to_bf2(v[2].z), h2_to_bf2(v[3].x), h2_to_bf2(v[3].y), h2_to_bf2(v[3].z));
        asm volatile("stmatrix.sync.aligned.m8n8.x2.shared.b16 [%0], {%1,%2};" :: "r"(dst + 1536), "r"(h2_to_bf2(v[4].x)), "r"(h2_to_bf2(v[4].y)) : "memory");
        stsm_x4(dst + 1792, h2_to_bf2(v[4].z), h2_to_bf2(v[5].x), h2_to_bf2(v[5].y), h2_to_bf2(v[5].z));
        const uint32_t all = ((v[0].w & v[1].w) & (v[2].w & v[3].w)) & (v[4].w & v[5].w);
        more = __any_sync(0xffffffffu, (all & 0x5000u) != 0x5000u) && ++it < SPIN_LIMIT;
    } while (more);
    FS(13, it);
    bar_arrive(1, 384);
    FS(14, 0);
    uint32_t m = 0u;
#pragma unroll
    for (int j = 0; j < 6; j++) {
        asm volatile("max.NaN.xorsign.abs.f16x2 %0, %0, %1;" : "+r"(m) : "r"(v[j].x));
        asm volatile("max.NaN.xorsign.abs.f16x2 %0, %0, %1;" : "+r"(m) : "r"(v[j].y));
        asm volatile("max.NaN.xorsign.abs.f16x2 %0, %0, %1;" : "+r"(m) : "r"(v[j].z));
    }
    return h2_to_bf2(m) & 0x7fff7fffu;
}

__device__ __forceinline__ void score_group(uint32_t qa, const uint32_t (&kf)[2][4], uint32_t d0, uint32_t d1, uint32_t m1, uint32_t d2, uint32_t m2) {
    uint32_t a[2][4];
#pragma unroll
    for (int k2 = 0; k2 < 2; k2++) ldsm_x4_t(a[k2], qa + k2 * 512);
    FS(4, a[1][0]);
    float sc[4][4];
    mma_z(sc[0], a[0], kf[0][0], kf[0][1]);
    mma_z(sc[1], a[0], kf[0][2], kf[0][3]);
    mma_z(sc[2], a[1], kf[1][0], kf[1][1]);
    mma_z(sc[3], a[1], kf[1][2], kf[1][3]);
    const uint32_t v0 = __float_as_uint((sc[0][0] + sc[1][2]) + (sc[2][0] + sc[3][2])), v1 = __float_as_uint((sc[0][1] + sc[1][3]) + (sc[2][1] + sc[3][3]));
    FS(5, v0);
    st_async64(d2, v0, v1, m2);
    st_async64(d1, v0, v1, m1);
    asm volatile("st.shared.v2.u32 [%0], {%1,%2};" :: "r"(d0), "r"(v0), "r"(v1) : "memory");
}
__device__ __forceinline__ void store_tile(int s, int h, int role, uint32_t tile) {
    const uint32_t qoff = role != 2 ? 1024 : 0;
    asm volatile("cp.async.bulk.global.shared::cta.bulk_group.L2::cache_hint [%0], [%1], %2, %3;"
                 :: "l"(&g_qkv[s][h][role][qoff]), "r"(tile + qoff), "r"(X_SZ), "l"(policy_evict_first()) : "memory");
    asm volatile("cp.async.bulk.commit_group;" ::: "memory");
}
__device__ __forceinline__ uint32_t w_addr(uint32_t sbase, int warp, int lane) {
    return sbase + SM_WS + (warp >> 2) * 8192 + ((lane & 7) + ((lane >> 4) & 1) * 8) * 128 + ((((warp & 3) * 2 + ((lane >> 3) & 1)) ^ (lane & 7)) << 4);
}
__device__ __forceinline__ void vx_copy(uint32_t sbase, int j, int r) {
    bulk_s2s(mapa(sbase + SM_VX + (j & 1) * 8192, r), sbase + SM_T + (j & 3) * TBUF + DH * 16, 8192, mapa(sbase + B_VX + 8 * (j & 1), r));
}
__device__ __forceinline__ void norms_gather(int lane, float* scs) {
    uint2 v[3];
    uint32_t r[2];
    unsigned it = 0;
    do {
#pragma unroll
        for (int i = 0; i < 3; i++) v[i] = ld_vol_u2(&g_norm[3 * lane + i]);
#pragma unroll
        for (int i = 0; i < 2; i++) asm volatile("ld.volatile.global.u32 %0, [%1];" : "=r"(r[i]) : "l"(&g_rx[lane + 32 * i]) : "memory");
    } while (__any_sync(0xffffffffu, (v[0].x & v[1].x & v[2].x & v[2].y & r[0] & r[1] & 1u) == 0u) && ++it < SPIN_LIMIT);
    float c;
    asm("sqrt.approx.f32 %0, %1;" : "=f"(c) : "f"(__uint_as_float(max(max(v[0].x, v[1].x), v[2].x))));
    c *= __uint_as_float(v[2].y) * 272.f;
#pragma unroll
    for (int o = 16; o; o >>= 1) c += __shfl_xor_sync(0xffffffffu, c, o);
    scs[16 + lane] = __uint_as_float(r[0]); scs[48 + lane] = __uint_as_float(r[1]);
    if (lane == 0) scs[1] = c * (1.1f * 24.f);
}

__global__ void __cluster_dims__(3, 1, 1) __launch_bounds__(384, 1)
k_chain(const __grid_constant__ CUtensorMap tmx, const __grid_constant__ CUtensorMap tmq, const __grid_constant__ CUtensorMap tmk,
        const __grid_constant__ CUtensorMap tmv, const __grid_constant__ CUtensorMap tmx2, const __grid_constant__ CUtensorMap tmo, const bf16* __restrict__ mem0, const bf16* __restrict__ xg) {
    extern __shared__ __align__(1024) unsigned char smem_raw[];
    const uint32_t sbase = smem_u32(smem_raw);
    const int cta = blockIdx.x, h = cta / 3, role = cta - 3 * h;
    const int tid = threadIdx.x, warp = __shfl_sync(0xffffffffu, tid >> 5, 0), lane_o = tid & 31;
    TS3C(0);
    asm volatile("griddepcontrol.launch_dependents;" ::: "memory");
    auto stage_w = [&](int i) {
        tma_2d(sbase + SM_WS + i * 16384, role == 2 ? &tmv : &tmq, h * DH + (role == 1 ? 64 : 0), i * 64, sbase + B_W + 8 * i);
        tma_2d(sbase + SM_WS + i * 16384 + 8192, role == 2 ? &tmv : &tmk, h * DH + (role == 0 ? 0 : 64), i * 64, sbase + B_W + 8 * i);
    };
    auto stage_x = [&](int i) { tma_2d(sbase + x01_off(i), &tmx2, i * 64, 0, sbase + B_W + 8 * i); };
    if (tid == 0) {
#pragma unroll
        for (int i = 0; i < 10; i++) mbar_init(sbase + B_W + 8 * i, 1);
        fence_async();
        bulk_g2s(sbase + SM_E + XBUF, mem0, MEMT * DM * 2, sbase + B_E);
#pragma unroll
        for (int i = 0; i < 3; i++) tma_2d(sbase + SM_X01 + i * 16384, &tmo, role * WOC + i * 64, h * DH, sbase + B_E);
        if (cta < NSEG) bulk_g2s(sbase + SM_E, xg + (size_t)cta * SEG * DM, XBUF, sbase + B_E);
#pragma unroll 1
        for (int i = 0; i < 6; i++) { if (i < 3) stage_x(i); stage_w(i); }
        mbar_expect(sbase + B_E, 49152 + MEMT * DM * 2 + (cta < NSEG ? XBUF : 0));
#pragma unroll
        for (int i = 0; i < 9; i++) mbar_expect(sbase + B_W + 8 * i, 24576);
    } else if (tid == 32) {
#pragma unroll
        for (int i = 0; i < 7; i++) mbar_init(sbase + SM_BAR + 8 * i, 1);
        asm volatile("fence.mbarrier_init.release.cluster;" ::: "memory");
        for (int i = 0; i < 2; i++) {
            mbar_expect(sbase + B_SB + 8 * i, role == 2 ? 2560 : 1280 + 2048);
            if (role != 2) mbar_expect(sbase + B_VX + 8 * i, 8192);
            mbar_arrive(sbase + B_XT + 8 * i);
        }
        mbar_expect(sbase + B_XT + 16, XBUF);
        reinterpret_cast<float*>(smem_raw + SM_SC)[2] = 1.f;
    } else if (tid >= 64 && tid < 88) {
        *reinterpret_cast<uint4*>(g_acc + cta * 1024 + (tid - 64) * 16) = make_uint4(0u, 0u, 0u, 0u);
        __threadfence();
    }
    __syncthreads();
    TS3C(8);
    if (warp < 8) {
        uint32_t wreg[36 - NS][4];
        {
            const int lane = lane_o;
            const uint32_t a = w_addr(sbase, warp, lane);
            const uint64_t da = smem_desc(sbase + SM_WS + (warp >> 2) * 8192, 1024, 1024) | (1ull << 62);
            float acc[32];
#pragma unroll
            for (int i = 0; i < 32; i++) acc[i] = 0.f;
#pragma unroll 1
            for (int b = 0; b < 9; b++) {
                if (b == 0) TSQ(0);
                mbar_wait(sbase + B_W + 8 * b, 0);
                TSQ(1 + b);
                if (b == 8) TS3C(2);
                const uint64_t db = smem_desc(sbase + x01_off(b), 16, 1024) | (1ull << 62);
                wg_fence();
#pragma unroll
                for (int k = 0; k < 4; k++) wgmma_n64_ss(acc, da + (uint64_t)(b * 1024 + k * 128), db + (uint64_t)(k * 2));
                wg_commit();
                if (b == 5) {
#pragma unroll
                    for (int ks = NS; ks < 24; ks++) ldsm_x4_t(wreg[ks - NS], a + (ks >> 2) * 16384 + (ks & 3) * 2048);
                }
            }
#pragma unroll
            for (int ks = 24; ks < 32; ks++) ldsm_x4_t(wreg[ks - NS], a + (ks >> 2) * 16384 + (ks & 3) * 2048);
            wg_wait0();
            named_bar(9, 384);
            const uint32_t off = sbase + SM_T + (DH + warp * 16 + (lane & 15)) * 16 + (lane >> 4) * (DH * 16);
#pragma unroll
            for (int i = 0; i < 4; i++)
                stsm_x4(off + (i >> 1) * TBUF + (i & 1) * (2 * DH * 16), pack_bf16(acc[8 * i], acc[8 * i + 1]), pack_bf16(acc[8 * i + 2], acc[8 * i + 3]),
                        pack_bf16(acc[8 * i + 4], acc[8 * i + 5]), pack_bf16(acc[8 * i + 6], acc[8 * i + 7]));
#pragma unroll
            for (int ks = 32; ks < 36; ks++) ldsm_x4_t(wreg[ks - NS], a + (ks >> 2) * 16384 + (ks & 3) * 2048);
            if (role == 2) fence_async();
            bar_arrive(8, 384);
            named_bar(7, 256);
            asm volatile("barrier.cluster.arrive.relaxed.aligned;" ::: "memory");
        }
        TS3C(3);
        auto xproj1 = [&](float (&acc)[16], int j) {
            const uint32_t dlo = __shfl_sync(0xffffffffu, (uint32_t)smem_desc(sbase + SM_X + (j % 3) * XBUF, 16, 1024), 0);
            wg_fence();
#pragma unroll
            for (int ks = NS; ks < NS + NC1; ks++)
                wgmma_n32(acc, wreg[ks - NS], ((uint64_t)0x40000040u << 32) | (uint64_t)(dlo + (uint32_t)((ks >> 2) * 256 + (ks & 3) * 2)), ks > NS);
            wg_commit();
            wg_wait0();
        };
        auto xproj2 = [&](float (&acc)[16], int j) {
            int lane = lane_o;
            asm volatile("" : "+r"(lane));
            const uint32_t dlo = __shfl_sync(0xffffffffu, (uint32_t)smem_desc(sbase + SM_X + (j % 3) * XBUF, 16, 1024), 0);
            const uint64_t da = smem_desc(sbase + SM_WS + (warp >> 2) * 8192, 1024, 1024) | (1ull << 62);
            wg_fence();
#pragma unroll
            for (int ks = 0; ks < NS; ks++)
                wgmma_n32_ss(acc, da + (uint64_t)((ks >> 2) * 1024 + (ks & 3) * 128), ((uint64_t)0x40000040u << 32) | (uint64_t)(dlo + (uint32_t)((ks >> 2) * 256 + (ks & 3) * 2)), NC1 > 0 || ks > 0);
#pragma unroll
            for (int ks = NS + NC1; ks < XK; ks++)
                wgmma_n32(acc, wreg[ks - NS], ((uint64_t)0x40000040u << 32) | (uint64_t)(dlo + (uint32_t)((ks >> 2) * 256 + (ks & 3) * 2)), 1);
            wg_commit();
            wg_wait0();
            const uint32_t off = sbase + SM_T + (j & 3) * TBUF + (DH + warp * 16 + (lane & 15)) * 16 + (lane >> 4) * (DH * 16);
            stsm_x4(off, pack_bf16(acc[0], acc[1]), pack_bf16(acc[2], acc[3]), pack_bf16(acc[4], acc[5]), pack_bf16(acc[6], acc[7]));
            stsm_x4(off + 2 * DH * 16, pack_bf16(acc[8], acc[9]), pack_bf16(acc[10], acc[11]), pack_bf16(acc[12], acc[13]), pack_bf16(acc[14], acc[15]));
        };
        uint32_t ws[NS][4];
#pragma unroll
        for (int ks = NS - NP; ks < NS; ks++) ldsm_x4_t(ws[ks], w_addr(sbase, warp, lane_o) + (ks >> 2) * 16384 + (ks & 3) * 2048);
        asm volatile("barrier.cluster.wait.aligned;" ::: "memory");
        if (lane_o == 0 && warp < 2 && role == 2) vx_copy(sbase, 0, warp);
        __syncwarp();
        TS3C(4);
        for (int s = 0; s < NSEG; s++) {
            int lane = lane_o;
            asm volatile("" : "+r"(lane));
            uint32_t v0, v1;
            {
#pragma unroll
                for (int ks = 0; ks < NS - NP; ks++) ldsm_x4_t(ws[ks], w_addr(sbase, warp, lane) + (ks >> 2) * 16384 + (ks & 3) * 2048);
                FS(0, ws[0][0]);
                named_bar(1, 384);
                float acc[2][4], minv;
                const uint32_t b_base = sbase + SM_M + lane * 16;
                uint32_t b[3][4];
#pragma unroll
                for (int kk = 0; kk < 3; kk++) ldsm_x4_t(b[kk], b_base + kk * 512);
                FS(1, b[0][0]);
#pragma unroll
                for (int kk = 0; kk < 18; kk++) {
                    if (kk == 0) {
                        mma_z(acc[0], ws[0], b[0][0], b[0][1]);
                        mma_z(acc[1], ws[1], b[0][2], b[0][3]);
                    } else if (2 * kk < NS) {
                        mma_bf16(acc[0], ws[2 * kk < NS ? 2 * kk : 0], b[kk % 3][0], b[kk % 3][1]);
                        mma_bf16(acc[1], ws[2 * kk < NS ? 2 * kk + 1 : 0], b[kk % 3][2], b[kk % 3][3]);
                    } else {
                        mma_bf16(acc[0], wreg[2 * kk >= NS ? 2 * kk - NS : 0], b[kk % 3][0], b[kk % 3][1]);
                        mma_bf16(acc[1], wreg[2 * kk >= NS ? 2 * kk - NS + 1 : 0], b[kk % 3][2], b[kk % 3][3]);
                    }
                    if (kk + 3 < 18) ldsm_x4_t(b[kk % 3], b_base + (kk + 3) * 512);
                    if (kk + 3 == 17) {
                        asm volatile("ld.shared.f32 %0, [%1];" : "=f"(minv) : "r"(sbase + SM_SC + 8) : "memory");
                    }
                }
                v0 = pack_bf16((acc[0][0] + acc[1][0]) * minv, (acc[0][1] + acc[1][1]) * minv);
                v1 = pack_bf16((acc[0][2] + acc[1][2]) * minv, (acc[0][3] + acc[1][3]) * minv);
                FS(2, v0);
            }
            const uint32_t tb = sbase + SM_T + (s & 3) * TBUF;
            if (role == 2 && s + 1 < NSEG) {
                const uint32_t fo = (uint32_t)(warp * 256 + lane * 8);
                const uint32_t rb0 = mapa(sbase, 0), rb1 = mapa(sbase, 1);
                st_async64(rb0 + SM_VM + fo, v0, v1, rb0 + B_SB + 8 * (s & 1));
                st_async64(rb1 + SM_VM + fo, v0, v1, rb1 + B_SB + 8 * (s & 1));
                asm volatile("st.shared.v2.u32 [%0], {%1,%2};" :: "r"(sbase + SM_VM + fo), "r"(v0), "r"(v1) : "memory");
            }
            asm volatile("stmatrix.sync.aligned.m8n8.x2.shared.b16 [%0], {%1,%2};" :: "r"(tb + warp * 256 + (lane & 15) * 16), "r"(v0), "r"(v1) : "memory");
            if (s + 1 < NSEG) {
                if (warp == 7 && role != 2) {
                    const uint32_t d0 = sbase + SM_S + role * 1280 + lane * 8, bo = sbase + B_SB + 8 * (s & 1);
                    const uint32_t d1 = mapa(d0, role ^ 1), m1 = mapa(bo, role ^ 1), d2 = mapa(d0, 2), m2 = mapa(bo, 2);
                    const uint32_t ka = tb + (64 + (lane & 7) + ((lane >> 3) & 1) * 16 + (lane >> 4) * 8) * 16;
                    uint32_t kf[2][4];
                    named_bar(2, 384);
#pragma unroll
                    for (int k2 = 0; k2 < 2; k2++) ldsm_x4_t(kf[k2], ka + k2 * 512);
                    score_group(tb + lane * 16, kf, d0, d1, m1, d2, m2);
                    bar_arrive(6, 160);
                } else bar_arrive(2, 384);
            }
            FS(11, 0);
            __syncwarp();
            if (s + 2 < NSEG) {
                if (warp == 6) mbar_wait(sbase + B_XT + 8 * ((s + 2) % 3), (uint32_t)((s + 2) / 3) & 1u);
                if (role != 2) named_bar(5, 384);
                else {
                    fence_async();
                    named_bar(7, 256);
                }
                float xacc[16];
                if (NC1 > 0) xproj1(xacc, s + 2);
                FS(9, __float_as_uint(xacc[0]));
                if (tid == 0 && role == 2) vx_copy(sbase, s + 1, 0);
                __syncwarp();
                if (role != 2) fence_async();
                FS(14, 0);
                named_bar(4, 384);
                xproj2(xacc, s + 2);
                FS(7, __float_as_uint(xacc[0]));
            }
            if (s >= NSEG - PROMPT) {
                fence_async();
                named_bar(7, 256);
                if (tid == 192) {
                    store_tile(s, h, role, tb);
                    asm volatile("cp.async.bulk.wait_group 0;" ::: "memory");
                    asm volatile("red.relaxed.gpu.global.add.u32 [%0], 1;" :: "l"(&g_flag[s * NH + h]) : "memory");
                }
                __syncwarp();
            }
        }
    } else {
        float* scs = reinterpret_cast<float*>(smem_raw + SM_SC);
        uint32_t wo[3][8][4];
        uint32_t mx2 = 0u;
        {
            const int pt = tid - 256, lane = lane_o, wq = warp - 8, g = lane >> 2, tq = lane & 3;
            TSQ(7);
            mbar_wait(sbase + B_E, 0);
            TSQ(8);
#pragma unroll
            for (int t = 0; t < 3; t++) {
                const int T = 3 * wq + t;
                const uint32_t a = sbase + SM_X01 + (T >> 2) * 16384 + ((lane >> 4) * 8 + (lane & 7)) * 128 + ((((T & 3) * 2 + ((lane >> 3) & 1)) ^ (lane & 7)) << 4);
#pragma unroll
                for (int kk = 0; kk < 8; kk++) ldsm_x4_t(wo[t][kk], a + ((2 * wq + kk) & 7) * 2048);
            }
            uint32_t m = 0u;
#pragma unroll 6
            for (int j = 0; j < 18; j++) {
                const uint32_t v = lds32(sbase + SM_E + XBUF + (g * DM + wq * 144 + 8 * j) * 2 + tq * 4);
                asm volatile("stmatrix.sync.aligned.m8n8.x1.trans.shared.b16 [%0], {%1};" :: "r"(sbase + SM_M + (wq * 144 + 8 * j + (lane & 7)) * 16), "r"(v) : "memory");
                mx2 = __vmaxu2(mx2, v & 0x7fff7fffu);
                const uint4 xv = *reinterpret_cast<const uint4*>(smem_raw + SM_E + (pt + 128 * j) * 16);
                m = max_abs2(max_abs2(m, max_abs2(xv.x, xv.y)), max_abs2(xv.z, xv.w));
            }
            m = __reduce_max_sync(0xffffffffu, max((m << 16) & 0x7fff0000u, m & 0x7fff0000u));
            if (lane == 0) reinterpret_cast<uint32_t*>(scs)[260 + wq] = m;
            named_bar(3, 128);
            if (pt == 64) {
                fence_async();
#pragma unroll 1
                for (int i = 3; i < 9; i++) { stage_x(i); if (i >= 6) stage_w(i); }
            }
            if (pt == 96 && cta < NSEG) {
                const uint4 q = *reinterpret_cast<const uint4*>(scs + 260);
                asm volatile("st.volatile.global.u32 [%0], %1;" :: "l"(&g_rx[cta]), "r"(max(max(q.x, q.y), max(q.z, q.w)) | 1u) : "memory");
            }
            __syncwarp();
            bar_arrive(1, 384);
            TSQ(9);
            float c0 = 0.f;
#pragma unroll
            for (int t = 0; t < 3; t++) {
                float n[4][4];
#pragma unroll
                for (int i = 0; i < 4; i++) { n[i][0] = n[i][1] = n[i][2] = n[i][3] = 0.f; }
#pragma unroll
                for (int kk = 0; kk < 8; kk++)
#pragma unroll
                    for (int i = 0; i < 4; i++) mma_k8(n[i], wo[t][kk][i & 2], wo[t][kk][(i & 2) + 1], wo[t][kk][i]);
                if ((g >> 1) == tq) c0 = fmaxf(c0, (g & 1) ? fmaxf(n[0][1] + n[2][1], n[1][3] + n[3][3]) : fmaxf(n[0][0] + n[2][0], n[1][2] + n[3][2]));
            }
            c0 = __uint_as_float(__reduce_max_sync(0xffffffffu, __float_as_uint(c0)));
            m = 0u;
#pragma unroll 1
            for (int b = 0; b < 9; b++) {
                if (role == 2) {
                    mbar_wait(sbase + B_W + 8 * b, 0);
#pragma unroll
                    for (int j = 0; j < 8; j++) {
                        const uint4 xv = *reinterpret_cast<const uint4*>(smem_raw + SM_WS + b * 16384 + (pt + 128 * j) * 16);
                        m = max_abs2(max_abs2(m, max_abs2(xv.x, xv.y)), max_abs2(xv.z, xv.w));
                    }
                }
                if (b == 3) bar_arrive(9, 384);
            }
            asm volatile("barrier.cluster.arrive.relaxed.aligned;" ::: "memory");
            m = __reduce_max_sync(0xffffffffu, max((m << 16) & 0x7fff0000u, m & 0x7fff0000u));
            if (lane == 0) { scs[256 + wq] = c0; reinterpret_cast<uint32_t*>(scs)[8 + wq] = m; }
            TSQ(1);
            named_bar(3, 128);
            if (pt == 0) {
                const float a = fmaxf(fmaxf(scs[256], scs[257]), fmaxf(scs[258], scs[259]));
                const float b = fmaxf(fmaxf(scs[8], scs[9]), fmaxf(scs[10], scs[11]));
                st_vol_u2(&g_norm[cta], make_uint2(__float_as_uint(a) | 1u, __float_as_uint(b) | 1u));
            }
            __syncwarp();
            named_bar(8, 384);
            TSQ(2);
            if (pt == 32) {
                fence_async();
                for (int i = 0; i < 3; i++) tma_x(sbase + SM_X + 2 * XBUF, &tmx, 2, i, sbase + B_XT + 16);
            }
            __syncwarp();
            asm volatile("barrier.cluster.wait.aligned;" ::: "memory");
        }
        const int wq = warp - 8, lane = lane_o;
        const uint32_t l8 = __shfl_sync(0xffffffffu, sbase + lane * 8, lane), l16 = __shfl_sync(0xffffffffu, sbase + lane * 16, lane);
        const uint32_t goff = __shfl_sync(0xffffffffu, (lane >> 3) * 1024 + (lane & 7) * 16, lane);
        float minv = 1.f;
        const uint32_t ka = sbase + SM_T + ((wq + 1) * DH + 64 + (lane & 7) + ((lane >> 3) & 1) * 16 + (lane >> 4) * 8) * 16;
        uint32_t kf[2][4];
#pragma unroll
        for (int k2 = 0; k2 < 2; k2++) ldsm_x4_t(kf[k2], ka + k2 * 512);
        int b3 = 0;
        for (int s = 0; s + 1 < NSEG; s++) {
            const int n3 = b3 == 2 ? 0 : b3 + 1;
            if (cta == 0 && tid == 256) {
                const uint32_t t = gtime32();
                st_vol_u2(&g_tick, make_uint2(t, reinterpret_cast<uint32_t*>(scs)[3]));
                reinterpret_cast<uint32_t*>(scs)[3] = t;
            }
            if (lane == 0) {
                if (wq == 1 && s + 3 < NSEG) tma_x_mc(sbase + SM_X + b3 * XBUF, &tmx, s + 3, role, sbase + B_XT + 8 * b3);
                if (wq == 3 && s > 0) {
                    store_tile(s - 1, h, role, sbase + SM_T + ((s - 1) & 3) * TBUF);
                    if (s > 1) {
                        asm volatile("cp.async.bulk.wait_group 1;" ::: "memory");
                        asm volatile("red.relaxed.gpu.global.add.u32 [%0], 1;" :: "l"(&g_flag[(s - 2) * NH + h]) : "memory");
                    }
                }
            }
            __syncwarp();
            if (wq == 2 && s > 1 && lane < 8) {
                *reinterpret_cast<uint4*>(g_acc + n3 * 128 + cta * 1024 + lane * 16) = make_uint4(0u, 0u, 0u, 0u);
            }
            if (s == 1 && tid == 383) {
                st_vol_u2(&g_norm[cta], make_uint2(0u, 0u));
                if (cta < NSEG) asm volatile("st.volatile.global.u32 [%0], %1;" :: "l"(&g_rx[cta]), "r"(0u) : "memory");
            }
            {
                const uint32_t mw = __reduce_max_sync(0xffffffffu, max(mx2 << 16, mx2 & 0xffff0000u));
                if (lane == 0) scs[4 + wq] = __uint_as_float(mw);
            }
            const uint32_t to = SM_T + (s & 3) * TBUF;
            const uint32_t ph = (uint32_t)(s >> 1) & 1u;
            if (role != 2) {
                const uint32_t so = SM_S + role * 1280 + (wq + 1) * 256, bo = sbase + B_SB + 8 * (s & 1);
                const uint32_t d1 = mapa(l8 + so, role ^ 1), m1 = mapa(bo, role ^ 1), d2 = mapa(l8 + so, 2), m2 = mapa(bo, 2);
                mbar_wait(sbase + B_VX + 8 * (s & 1), ph);
                FS(1, 0);
                named_bar(2, 384);
                score_group(l16 + to, kf, l8 + so, d1, m1, d2, m2);
                if (s + 2 < NSEG) bar_arrive(5, 384);
            } else named_bar(2, 384);
            if (s == 0) {
                TSQ(3);
                if (wq == 1) norms_gather(lane, scs);
                named_bar(3, 128);
                TSQ(4);
            }
            const float4 m4 = *reinterpret_cast<const float4*>(scs + 4);
            const float c24 = scs[1], xb = scs[16 + s];
            unsigned char* dst = (g_acc + b3 * 128 + (role * 32 + wq * 8) * 1024) + goff;
            uint32_t vf[2][2][4], vm[2][2];
            {
                const uint32_t va = sbase + (role == 2 ? to + DH * 16 : SM_VX + (s & 1) * 8192) + (lane >> 4) * 2048 + (32 * wq + (lane & 15)) * 16;
#pragma unroll
                for (int i = 0; i < 4; i++) ldsm_x4(vf[i >> 1][i & 1], va + (i >> 1) * 256 + (i & 1) * 4096);
            }
            float scale;
            {
                const float bound = fmaxf(fmaxf(fmaxf(m4.x, m4.y), fmaxf(m4.z, m4.w)) * minv, xb) * c24;
                int e = 141 - (int)((__float_as_uint(bound) >> 23) & 255u);
                e = e > 100 ? 100 : e;
                scale = __uint_as_float((uint32_t)(127 + e) << 23);
                minv = __uint_as_float((uint32_t)(127 - e) << 23);
            }
            FS(7, vf[1][1][0]);
            if (role != 2) named_bar(6, 160);
            if (role == 2) mbar_wait(sbase + B_SB + 8 * (s & 1), ph);
            float sv[5][2];
#pragma unroll
            for (int j = 0; j < 5; j++) lds64f(sv[j][0], sv[j][1], l8 + SM_S + (role & 1) * 1280 + j * 256);
            if (role != 2) mbar_wait(sbase + B_SB + 8 * (s & 1), ph);
            FS(6, 0);
            uint32_t p[5];
            {
                float sr[5][2];
#pragma unroll
                for (int j = 0; j < 5; j++) lds64f(sr[j][0], sr[j][1], l8 + SM_S + ((role & 1) ^ 1) * 1280 + j * 256);
                lds64(vm[0][0], vm[0][1], l8 + SM_VM + wq * 512);
                lds64(vm[1][0], vm[1][1], l8 + SM_VM + wq * 512 + 256);
#pragma unroll
                for (int j = 0; j < 5; j++) {
                    sv[j][0] += sr[j][0]; sv[j][1] += sr[j][1];
                }
                float mx = fmaxf(fmaxf(fmaxf(sv[0][0], sv[0][1]), fmaxf(sv[1][0], sv[1][1])), fmaxf(fmaxf(sv[2][0], sv[2][1]), fmaxf(sv[3][0], sv[3][1])));
                mx = fmaxf(mx, fmaxf(sv[4][0], sv[4][1]));
                {
                    const float m1 = __shfl_xor_sync(0xffffffffu, mx, 1), m2 = __shfl_xor_sync(0xffffffffu, mx, 2), m3 = __shfl_xor_sync(0xffffffffu, mx, 3);
                    mx = fmaxf(fmaxf(mx, m1), fmaxf(m2, m3));
                }
                constexpr float EC = MIMIC ? 1.4426950408889634f : (float)(1.4426950408889634 * 0.08838834764831845);
#pragma unroll
                for (int jj = 0; jj < 5; jj++) {
                    const int j = (jj + 1) % 5;
                    asm("ex2.approx.ftz.f32 %0, %1;" : "=f"(sv[j][0]) : "f"((sv[j][0] - mx) * EC));
                    asm("ex2.approx.ftz.f32 %0, %1;" : "=f"(sv[j][1]) : "f"((sv[j][1] - mx) * EC));
                    p[j] = pack_bf16(sv[j][0], sv[j][1]);
                }
            }
            FS(0, p[0]);
            uint32_t b[4][4];
            float zs[4];
            {
                float o0[2][4], o1[2][4];
                mma_z(o0[0], vf[0][0], p[1], p[2]);
                mma_z(o0[1], vf[1][0], p[1], p[2]);
                mma_z(o1[0], vf[0][1], p[3], p[4]);
                mma_z(o1[1], vf[1][1], p[3], p[4]);
                mma_k8(o0[0], vm[0][0], vm[0][1], p[0]);
                mma_k8(o0[1], vm[1][0], vm[1][1], p[0]);
                const uint32_t one4[4] = {0x3f803f80u, 0x3f803f80u, 0x3f803f80u, 0x3f803f80u};
                mma_z(zs, one4, p[1], p[2]);
                mma_bf16(zs, one4, p[3], p[4]);
                mma_k8(zs, one4[0], one4[1], p[0]);
                uint32_t ow[4];
#pragma unroll
                for (int m = 0; m < 2; m++) {
                    ow[2 * m] = pack_bf16(o0[m][0] + o1[m][0], o0[m][1] + o1[m][1]);
                    ow[2 * m + 1] = pack_bf16(o0[m][2] + o1[m][2], o0[m][3] + o1[m][3]);
                }
                stsm_x4(l16 + SM_O + wq * 512, ow[0], ow[1], ow[2], ow[3]);
                FS(2, 0);
#pragma unroll
                for (int i = 0; i < 4; i++) b[0][i] = movm(ow[i]);
            }
            float acc[3][2][4];
            named_bar(3, 128);
#pragma unroll
            for (int i = 1; i < 4; i++) ldsm_x4_t(b[i], l16 + SM_O + ((wq + i) & 3) * 512);
#pragma unroll
            for (int t = 0; t < 3; t++) { mma_z(acc[t][0], wo[t][0], b[0][0], b[0][1]); mma_z(acc[t][1], wo[t][1], b[0][2], b[0][3]); }
            float z0, z1;
            asm volatile("rcp.approx.ftz.f32 %0, %1;" : "=f"(z0) : "f"(zs[0]));
            asm volatile("rcp.approx.ftz.f32 %0, %1;" : "=f"(z1) : "f"(zs[1]));
            z0 *= scale; z1 *= scale;
            FS(3, b[1][0]);
#pragma unroll
            for (int i = 1; i < 4; i++)
#pragma unroll
                for (int t = 0; t < 3; t++) { mma_bf16(acc[t][0], wo[t][2 * i], b[i][0], b[i][1]); mma_bf16(acc[t][1], wo[t][2 * i + 1], b[i][2], b[i][3]); }
            {
                uint32_t w[6];
#pragma unroll
                for (int t = 0; t < 3; t++) {
                    w[2 * t] = pack_f16((acc[t][0][0] + acc[t][1][0]) * z0, (acc[t][0][1] + acc[t][1][1]) * z1);
                    w[2 * t + 1] = pack_f16((acc[t][0][2] + acc[t][1][2]) * z0, (acc[t][0][3] + acc[t][1][3]) * z1);
                }
                FS(8, w[5]);
                asm volatile("red.relaxed.gpu.global.add.noftz.v4.f16x2 [%0], {%1,%2,%3,%4};" :: "l"(dst), "r"(w[0]), "r"(w[1]), "r"(w[2]), "r"(0x3c00u) : "memory");
                asm volatile("red.relaxed.gpu.global.add.noftz.v4.f16x2 [%0], {%1,%2,%3,%4};" :: "l"(dst + 4096), "r"(w[3]), "r"(w[4]), "r"(w[5]), "r"(0x3c00u) : "memory");
            }
            FS(9, 0);
            if (s == 0) TSQ(5);
            const uint32_t t0 = clock32();
            if (s + 2 < NSEG) bar_arrive(4, 384);
            if (lane == 0) {
                if (wq == 0) scs[2] = minv;
                if (wq == 2 && role == 2 && s + 2 < NSEG) { while (clock32() - t0 < VX_DELAY) {} vx_copy(sbase, s + 1, 1); }
                if (s + 3 < NSEG) {
                    if (wq == 0) mbar_expect(sbase + B_SB + 8 * (s & 1), role == 2 ? 2560 : 1280 + 2048);
                    if (wq == 1) mbar_expect(sbase + B_XT + 8 * b3, XBUF);
                    if (wq == 3 && role != 2) mbar_expect(sbase + B_VX + 8 * (s & 1), 8192);
                }
            }
            __syncwarp();
#pragma unroll
            for (int k2 = 0; k2 < 2; k2++) ldsm_x4_t(kf[k2], ka + ((s + 1) & 3) * TBUF + k2 * 512);
            const uint4* src = reinterpret_cast<const uint4*>((g_acc + b3 * 128 + wq * 24576) + goff);
            mx2 = poll_mem(src, l16 + SM_M + wq * 2304, t0);
            if (s == 0) TSQ(6);
            b3 = n3;
        }
        if (ST_AT < 2 && tid == 352) {
            asm volatile("cp.async.bulk.wait_group 0;" ::: "memory");
            asm volatile("red.relaxed.gpu.global.add.u32 [%0], 1;" :: "l"(&g_flag[(NSEG - 3) * NH + h]) : "memory");
        }
    }
    TS3C(1);
    __syncwarp();
    cluster_sync_all();
}

extern "C" void kernel_launch(void* const* d_in, const int* in_sizes, int n_in, void* d_out, int out_size) {
    const bf16* x = (const bf16*)d_in[0];
    const bf16* mem0 = (const bf16*)d_in[1];
    const bf16* Wq = (const bf16*)d_in[2];
    const bf16* Wk = (const bf16*)d_in[3];
    const bf16* Wv = (const bf16*)d_in[4];
    const bf16* Wo = (const bf16*)d_in[5];
    const bf16* logA = (const bf16*)d_in[8];
    const bf16* Aim = (const bf16*)d_in[9];
    const bf16* Cre = (const bf16*)d_in[10];
    const bf16* Cim = (const bf16*)d_in[11];
    const bf16* logdt = (const bf16*)d_in[12];
    const bf16* dskip = (const bf16*)d_in[13];
    const bf16* gw = (const bf16*)d_in[14];
    bf16* out = (bf16*)d_out;
    static bool attr_done = false;
    typedef CUresult (*EncFn)(CUtensorMap*, CUtensorMapDataType, cuuint32_t, void*, const cuuint64_t*, const cuuint64_t*, const cuuint32_t*,
                              const cuuint32_t*, CUtensorMapInterleave, CUtensorMapSwizzle, CUtensorMapL2promotion, CUtensorMapFloatOOBfill);
    static EncFn enc = nullptr;
    if (!attr_done) {
        void* fn = nullptr;
        cudaDriverEntryPointQueryResult qr;
        cudaGetDriverEntryPoint("cuTensorMapEncodeTiled", &fn, cudaEnableDefault, &qr);
        enc = (EncFn)fn;
        cudaFuncSetAttribute(k_chain, cudaFuncAttributeMaxDynamicSharedMemorySize, 232448);
        cudaFuncSetAttribute(k_side, cudaFuncAttributeMaxDynamicSharedMemorySize, SIDE_SMEM);
        attr_done = true;
    }
    CUtensorMap tmx;
    {
        const cuuint64_t dims[3] = {64, (cuuint64_t)S_LEN, 9};
        const cuuint64_t strides[2] = {(cuuint64_t)DM * 2, 128};
        const cuuint32_t box[3] = {64, (cuuint32_t)SEG, 3};
        const cuuint32_t es[3] = {1, 1, 1};
        enc(&tmx, CU_TENSOR_MAP_DATA_TYPE_BFLOAT16, 3, (void*)x, dims, strides, box, es, CU_TENSOR_MAP_INTERLEAVE_NONE,
            CU_TENSOR_MAP_SWIZZLE_128B, CU_TENSOR_MAP_L2_PROMOTION_L2_128B, CU_TENSOR_MAP_FLOAT_OOB_FILL_NONE);
    }
    CUtensorMap tmw[3];
    for (int i = 0; i < 3; i++) {
        const cuuint64_t dims[2] = {(cuuint64_t)HD, (cuuint64_t)DM};
        const cuuint64_t strides[1] = {(cuuint64_t)HD * 2};
        const cuuint32_t box[2] = {64, 64};
        const cuuint32_t es[2] = {1, 1};
        enc(&tmw[i], CU_TENSOR_MAP_DATA_TYPE_BFLOAT16, 2, (void*)(i == 0 ? Wq : (i == 1 ? Wk : Wv)), dims, strides, box, es, CU_TENSOR_MAP_INTERLEAVE_NONE,
            CU_TENSOR_MAP_SWIZZLE_128B, CU_TENSOR_MAP_L2_PROMOTION_L2_256B, CU_TENSOR_MAP_FLOAT_OOB_FILL_NONE);
    }
    CUtensorMap tmo;
    {
        const cuuint64_t dims[2] = {(cuuint64_t)DM, (cuuint64_t)HD};
        const cuuint64_t strides[1] = {(cuuint64_t)DM * 2};
        const cuuint32_t box[2] = {64, 128};
        const cuuint32_t es[2] = {1, 1};
        enc(&tmo, CU_TENSOR_MAP_DATA_TYPE_BFLOAT16, 2, (void*)Wo, dims, strides, box, es, CU_TENSOR_MAP_INTERLEAVE_NONE,
            CU_TENSOR_MAP_SWIZZLE_128B, CU_TENSOR_MAP_L2_PROMOTION_L2_128B, CU_TENSOR_MAP_FLOAT_OOB_FILL_NONE);
    }
    CUtensorMap tmx2;
    {
        const cuuint64_t dims[2] = {(cuuint64_t)DM, (cuuint64_t)S_LEN};
        const cuuint64_t strides[1] = {(cuuint64_t)DM * 2};
        const cuuint32_t box[2] = {64, 64};
        const cuuint32_t es[2] = {1, 1};
        enc(&tmx2, CU_TENSOR_MAP_DATA_TYPE_BFLOAT16, 2, (void*)x, dims, strides, box, es, CU_TENSOR_MAP_INTERLEAVE_NONE,
            CU_TENSOR_MAP_SWIZZLE_128B, CU_TENSOR_MAP_L2_PROMOTION_L2_128B, CU_TENSOR_MAP_FLOAT_OOB_FILL_NONE);
    }
    k_chain<<<NCTA, 384, 232448>>>(tmx, tmw[0], tmw[1], tmw[2], tmx2, tmo, mem0, x);
    {
        cudaLaunchConfig_t cfg = {};
        cfg.gridDim = dim3(SD_NCTA); cfg.blockDim = dim3(512); cfg.dynamicSmemBytes = SIDE_SMEM; cfg.stream = cudaStreamPerThread;
        cudaLaunchAttribute at[1];
        at[0].id = cudaLaunchAttributeProgrammaticStreamSerialization;
        at[0].val.programmaticStreamSerializationAllowed = 1;
        cfg.attrs = at; cfg.numAttrs = 1;
        cudaLaunchKernelEx(&cfg, k_side, tmo, x, logA, Aim, Cre, Cim, logdt, Wo, dskip, gw, out);
    }
}
```

```cpp
#include <cuda_runtime.h>
#include <cuda.h>
#include <cuda_bf16.h>
#include <stdint.h>

typedef __nv_bfloat16 bf16;
#define LDV4 "ld.volatile.global.v4.u32 {%0,%1,%2,%3}, [%4];"
#define STV4 "st.volatile.global.v4.u32 [%0], {%1,%2,%3,%4};"
#define STV2 "st.volatile.global.v2.u32 [%0], {%1,%2};"

constexpr int S_LEN = 2048, DM = 576, NH = 32, DH = 128, HD = 4096, MEMT = 8, SEG = 32, NSEG = 64, NST = 128;

__device__ __align__(128) bf16 g_gate[S_LEN];
constexpr int NCTA = NH * 3;
__device__ __align__(1024) unsigned char g_acc[96 * 1024];
__device__ __align__(128) uint2 g_norm[NCTA];
__device__ __align__(128) uint32_t g_rx[NSEG];
__device__ __align__(128) unsigned char g_qkv[NSEG][NH][3][10240];
__device__ __align__(128) bf16 g_ox[S_LEN * HD];
__device__ __align__(128) uint4 g_fp[8][36][6][128];
__device__ unsigned g_flag[NSEG * NH];
__device__ unsigned g_prog[NSEG / 2 * 8];
__device__ unsigned g_gcnt[64];
__device__ unsigned g_epoch;
__device__ __align__(128) uint2 g_tick;
__device__ __align__(16) bf16 g_y[DM * S_LEN];

#define TS3(slot) do {} while (0)
#define TS3P(slot) do {} while (0)
#define TSQ(slot) do {} while (0)
#define TS3W(slot) do {} while (0)
#define TSS(row, slot) do {} while (0)
#define TS3C(slot) do {} while (0)
#define TST(slot) do {} while (0)
#define TSG(i) do {} while (0)
#define FS(i, dep) do {} while (0)
__device__ __forceinline__ uint32_t smem_u32(const void* p) { return (uint32_t)__cvta_generic_to_shared(p); }
__device__ __forceinline__ float bf16r(float x) { return __bfloat162float(__float2bfloat16_rn(x)); }
__device__ __forceinline__ uint32_t pack_bf16(float lo, float hi) {
    __nv_bfloat162 v = __floats2bfloat162_rn(lo, hi);
    return *reinterpret_cast<uint32_t*>(&v);
}
__device__ __forceinline__ void ldsm_x4(uint32_t (&r)[4], uint32_t addr) {
    asm volatile("ldmatrix.sync.aligned.m8n8.x4.shared.b16 {%0,%1,%2,%3}, [%4];"
                 : "=r"(r[0]), "=r"(r[1]), "=r"(r[2]), "=r"(r[3]) : "r"(addr));
}
__device__ __forceinline__ void ldsm_x4_t(uint32_t (&r)[4], uint32_t addr) {
    asm volatile("ldmatrix.sync.aligned.m8n8.x4.trans.shared.b16 {%0,%1,%2,%3}, [%4];"
                 : "=r"(r[0]), "=r"(r[1]), "=r"(r[2]), "=r"(r[3]) : "r"(addr));
}
__device__ __forceinline__ void mma_bf16(float (&d)[4], const uint32_t (&a)[4], uint32_t b0, uint32_t b1) {
    asm volatile("mma.sync.aligned.m16n8k16.row.col.f32.bf16.bf16.f32 {%0,%1,%2,%3}, {%4,%5,%6,%7}, {%8,%9}, {%0,%1,%2,%3};"
                 : "+f"(d[0]), "+f"(d[1]), "+f"(d[2]), "+f"(d[3])
                 : "r"(a[0]), "r"(a[1]), "r"(a[2]), "r"(a[3]), "r"(b0), "r"(b1));
}
__device__ __forceinline__ uint2 ld_vol_u2(const uint2* p) {
    uint2 v; asm volatile("ld.volatile.global.v2.u32 {%0,%1}, [%2];" : "=r"(v.x), "=r"(v.y) : "l"(p) : "memory"); return v;
}
__device__ __forceinline__ void st_vol_u2(uint2* p, uint2 v) {
    asm volatile(STV2 :: "l"(p), "r"(v.x), "r"(v.y) : "memory");
}
__device__ __forceinline__ unsigned ld_acq(const unsigned* p) {
    unsigned v; asm volatile("ld.acquire.gpu.global.u32 %0, [%1];" : "=r"(v) : "l"(p) : "memory"); return v;
}
#define XK 36
#define NC1 12
#define NS 6
#define NP 2
#define X_OXSZ 16384
#define GATE_A 1300
#define GATE_B 300
#define GATE_P 1950u
#define STAGGER 0
#define GATE_ATT 3
#define RLX_SLEEP 300
#define MIMIC 0
#define VX_DELAY 100
#define TL_DELAY 600
#define POLL_DELAY 500
#define PROMPT 8
#define UNGATE 12
constexpr unsigned SPIN_LIMIT = 1u << 20;
constexpr int NATT = NSEG - 2;

constexpr int SD_CH = 16;
constexpr int SD_NCTA = DM / SD_CH;
constexpr int SD_USTR = 40 * 72;
constexpr int SD_KLEN = 2048 + 32;
constexpr int SD_WSTR = 2 * SD_KLEN * 2;
constexpr int SD_SMEM = SD_CH * SD_USTR * 2 + 8 * SD_WSTR;

__device__ __forceinline__ uint32_t lds32(uint32_t a) { uint32_t v; asm volatile("ld.shared.u32 %0, [%1];" : "=r"(v) : "r"(a)); return v; }
__device__ __forceinline__ void tap_tile(uint32_t (&t)[4], uint32_t a) { t[0] = lds32(a); t[1] = lds32(a - 16); t[2] = lds32(a + 16); t[3] = lds32(a); }
template <int NT0>
__device__ __forceinline__ void conv_step(float (&acc)[4][4][4], const uint32_t (&cur)[4][4], uint32_t (&prev)[4][4], uint32_t (&b)[4][2][4], uint32_t ka, uint32_t ua) {
#pragma unroll
    for (int kt = 3; kt >= 0; kt--) {
#pragma unroll
        for (int nt = NT0; nt < 4; nt++)
#pragma unroll
            for (int mt = 0; mt < 4; mt++) {
                if (mt < kt) mma_bf16(acc[mt][nt], prev[(mt - kt + 4) & 3], b[nt][kt >> 1][(kt & 1) * 2], b[nt][kt >> 1][(kt & 1) * 2 + 1]);
                else mma_bf16(acc[mt][nt], cur[(mt - kt) & 3], b[nt][kt >> 1][(kt & 1) * 2], b[nt][kt >> 1][(kt & 1) * 2 + 1]);
            }
        if (kt == 3) { tap_tile(prev[0], ka); tap_tile(prev[1], ka - 32); }
        if (kt == 2) tap_tile(prev[2], ka - 64);
        if (kt == 1) tap_tile(prev[3], ka - 96);
        if ((kt & 1) == 0) {
#pragma unroll
            for (int nt = NT0; nt < 4; nt++) ldsm_x4(b[nt][kt >> 1], ua + nt * 1152 + kt * 32);
        }
    }
}
template <int NT0>
__device__ __forceinline__ void conv_oct(float (&acc)[4][4][4], uint32_t (&X)[4][4], uint32_t (&Y)[4][4], uint32_t (&b)[4][2][4], uint32_t& ka, uint32_t& ua) {
#pragma unroll 1
    for (int i = 0; i < 4; i++) {
        conv_step<NT0>(acc, X, Y, b, ka - 128, ua - 144);
        conv_step<NT0>(acc, Y, X, b, ka - 256, ua - 288);
        ka -= 256; ua -= 288;
    }
}

__device__ __forceinline__ void named_bar(int id, int n) { asm volatile("bar.sync %0, %1;" :: "r"(id), "r"(n) : "memory"); }
__device__ __forceinline__ uint32_t pack_f16(float lo, float hi) {
    uint32_t r; asm("cvt.rn.f16x2.f32 %0, %1, %2;" : "=r"(r) : "f"(hi), "f"(lo)); return r;
}
__device__ __forceinline__ void cexp_t(float lr, float turns, float& re, float& im) {
    float m;
    asm("ex2.approx.ftz.f32 %0, %1;" : "=f"(m) : "f"(lr));
    const float a = (turns - rintf(turns)) * 6.283185307179586f;
    re = m * __cosf(a); im = m * __sinf(a);
}
__device__ __forceinline__ void csq(float& re, float& im) { const float r = re * re - im * im; im = 2.f * re * im; re = r; }
__device__ __forceinline__ void kb_state(const float* tp, float gf, uint32_t (&a)[4][2], uint32_t (&b)[5]) {
    const float4 p0 = *reinterpret_cast<const float4*>(tp), p1 = *reinterpret_cast<const float4*>(tp + 4);
    float wr, wi;
    cexp_t(p0.x * gf, p0.y * gf, wr, wi);
    float vr = wr * p1.x - wi * p1.y, vi = wr * p1.y + wi * p1.x;
#pragma unroll
    for (int c = 0; c < 4; c++) {
        a[c][0] = pack_f16(wr, wi); a[c][1] = pack_f16(vr, vi);
        csq(wr, wi);
        if (c < 3) csq(vr, vi);
    }
    b[0] = pack_f16(p0.z * wr - p0.w * wi, -p0.z * wi - p0.w * wr);
    float er = wr * p1.z - wi * p1.w, ei = wr * p1.w + wi * p1.z;
#pragma unroll
    for (int c = 0; c < 4; c++) {
        b[1 + c] = pack_f16(p0.z * er - p0.w * ei, -p0.z * ei - p0.w * er);
        if (c < 3) csq(er, ei);
    }
}
template <int C>
__device__ __forceinline__ void expand_taps(const float* kd, bf16* kr, int l0, int lane) {
    uint32_t w[4];
#pragma unroll
    for (int e = 0; e < 4; e++) {
        float v[2];
#pragma unroll
        for (int k = 0; k < 2; k++) {
            const int l = l0 + 8 * lane + 7 - 2 * e - k;
            const int idx = C == 0 ? l : 128 * C + ((l + (1 << (C > 0 ? C - 1 : 0)) - 1 + ((l >> C) & 1)) >> C);
            v[k] = kd[idx];
        }
        w[e] = pack_bf16(v[0], v[1]);
    }
    *reinterpret_cast<uint4*>(kr + 2040 - l0 - 8 * lane) = make_uint4(w[0], w[1], w[2], w[3]);
}

__device__ __forceinline__ uint32_t bf2_mul(uint32_t a, uint32_t b) { uint32_t r; asm("mul.rn.bf16x2 %0, %1, %2;" : "=r"(r) : "r"(a), "r"(b)); return r; }
__device__ __forceinline__ uint32_t bf2_add(uint32_t a, uint32_t b) { uint32_t r; asm("add.rn.bf16x2 %0, %1, %2;" : "=r"(r) : "r"(a), "r"(b)); return r; }
__device__ __forceinline__ uint32_t bf2_sub(uint32_t a, uint32_t b) { uint32_t r; asm("sub.rn.bf16x2 %0, %1, %2;" : "=r"(r) : "r"(a), "r"(b)); return r; }
__device__ __forceinline__ void wait_cnt(const unsigned* p, unsigned target) {
    unsigned it = 0;
    while ((int)(ld_acq(p) - target) < 0 && ++it < SPIN_LIMIT) __nanosleep(64);
}
__device__ __forceinline__ void s4d_phase(unsigned char* smem_raw, const bf16* __restrict__ x, const bf16* __restrict__ logA,
                                          const bf16* __restrict__ Aim, const bf16* __restrict__ Cre, const bf16* __restrict__ Cim,
                                          const bf16* __restrict__ logdt, const bf16* __restrict__ dskip, const bf16* __restrict__ wslice, unsigned ep) {
    bf16* u_all = reinterpret_cast<bf16*>(smem_raw);
    const int tid = threadIdx.x, warp = tid >> 5, lane = tid & 31;
    const int d0 = blockIdx.x * SD_CH;
    bf16* kr = u_all + SD_CH * SD_USTR + warp * (SD_WSTR / 2);
    float* tab = reinterpret_cast<float*>(kr + SD_KLEN);
    const int g = lane >> 2, tq = lane & 3;
    uint2 prm[4];
    float ldt;
    auto load_prm = [&](int d) {
        prm[0] = __ldg(reinterpret_cast<const uint2*>(logA + d * NST) + lane); prm[1] = __ldg(reinterpret_cast<const uint2*>(Aim + d * NST) + lane);
        prm[2] = __ldg(reinterpret_cast<const uint2*>(Cre + d * NST) + lane); prm[3] = __ldg(reinterpret_cast<const uint2*>(Cim + d * NST) + lane);
        ldt = __bfloat162float(logdt[d]);
    };
    load_prm(d0 + 2 * warp);
    for (int i = lane; i < 8 * 72 / 2; i += 32) {
        reinterpret_cast<uint32_t*>(u_all + (2 * warp) * SD_USTR)[i] = 0u;
        reinterpret_cast<uint32_t*>(u_all + (2 * warp + 1) * SD_USTR)[i] = 0u;
    }
    if (lane < 16) reinterpret_cast<uint32_t*>(kr + 2048)[lane] = 0u;
    TS3(20);
#pragma unroll 1
    for (int ch = 0; ch < 2; ch++) {
        const int d = d0 + 2 * warp + ch;
        bf16* us = u_all + (2 * warp + ch) * SD_USTR;
        float k2048 = 0.f, sinv;
        {
            const float dt = bf16r(expf(ldt));
            uint32_t cm = __vmaxu2(__vmaxu2(prm[2].x & 0x7fff7fffu, prm[2].y & 0x7fff7fffu), __vmaxu2(prm[3].x & 0x7fff7fffu, prm[3].y & 0x7fff7fffu));
            cm = __reduce_max_sync(0xffffffffu, max(cm << 16, cm & 0xffff0000u));
            int e = 134 - (int)(__float_as_uint(__uint_as_float(cm) * dt) >> 23);
            e = e > 100 ? 100 : (e < -100 ? -100 : e);
            const float s2 = __uint_as_float((uint32_t)(128 + e) << 23);
            sinv = __uint_as_float((uint32_t)(127 - e) << 23);
#pragma unroll
            for (int j = 0; j < 4; j++) {
                float q[4];
#pragma unroll
                for (int i = 0; i < 4; i++) { const uint32_t w = j < 2 ? prm[i].x : prm[i].y; q[i] = __uint_as_float((j & 1) ? w & 0xffff0000u : w << 16); }
                const float zl = -bf16r(expf(q[0])) * dt * 1.4426950408889634f;
                const float zt = q[1] * dt * 0.15915494309189535f;
                const float cr = s2 * (q[2] * dt), ci = s2 * (q[3] * dt);
                float ar, ai, br, bi, er, ei;
                cexp_t(zl * 8.f, zt * 8.f, ar, ai);
                cexp_t(zl * 128.f, zt * 128.f, br, bi);
                cexp_t(zl * 2048.f, zt * 2048.f, er, ei);
                k2048 += cr * er - ci * ei;
                *reinterpret_cast<float4*>(tab + (lane + 32 * j) * 8) = make_float4(zl, zt, cr, ci);
                *reinterpret_cast<float4*>(tab + (lane + 32 * j) * 8 + 4) = make_float4(ar, ai, br, bi);
            }
            if (ch == 0) load_prm(d + 1);
#pragma unroll
            for (int o = 16; o; o >>= 1) k2048 += __shfl_xor_sync(0xffffffffu, k2048, o);
        }
        __syncwarp();
        {
            float kc[5][4];
#pragma unroll
            for (int i = 0; i < 5; i++) { kc[i][0] = kc[i][1] = kc[i][2] = kc[i][3] = 0.f; }
            const float gf = (float)g;
#pragma unroll 2
            for (int ks = 0; ks < 16; ks++) {
                uint32_t a0[4][2], a1[4][2], b0[5], b1[5];
                kb_state(tab + (8 * ks + tq) * 8, gf, a0, b0);
                kb_state(tab + (8 * ks + 4 + tq) * 8, gf, a1, b1);
#pragma unroll
                for (int i = 0; i < 5; i++) {
                    const int c = i > 0 ? i - 1 : 0;
                    asm volatile("mma.sync.aligned.m16n8k16.row.col.f32.f16.f16.f32 {%0,%1,%2,%3}, {%4,%5,%6,%7}, {%8,%9}, {%0,%1,%2,%3};"
                                 : "+f"(kc[i][0]), "+f"(kc[i][1]), "+f"(kc[i][2]), "+f"(kc[i][3])
                                 : "r"(a0[c][0]), "r"(a0[c][1]), "r"(a1[c][0]), "r"(a1[c][1]), "r"(b0[i]), "r"(b1[i]));
                }
            }
            __syncwarp();
#pragma unroll
            for (int i = 0; i < 5; i++) {
                float* q = tab + 128 * i + 32 * tq + g;
                q[0] = kc[i][0] * sinv; q[16] = kc[i][1] * sinv; q[8] = kc[i][2] * sinv; q[24] = kc[i][3] * sinv;
            }
            if (lane == 0) tab[640] = k2048 * sinv;
            __syncwarp();
            expand_taps<0>(tab, kr, 0, lane);
            expand_taps<1>(tab, kr, 256, lane);
            expand_taps<2>(tab, kr, 512, lane);
            expand_taps<2>(tab, kr, 768, lane);
#pragma unroll
            for (int i = 0; i < 4; i++) expand_taps<3>(tab, kr, 1024 + 256 * i, lane);
            __syncwarp();
#pragma unroll
            for (int i = 0; i < 8; i++) {
                const uint4 v = *reinterpret_cast<const uint4*>(kr + (lane + 32 * i) * 8);
                const uint32_t n = *reinterpret_cast<const uint32_t*>(kr + (lane + 32 * i) * 8 + 8);
                *reinterpret_cast<uint4*>(tab + (lane + 32 * i) * 4) =
                    make_uint4(__byte_perm(v.x, v.y, 0x5432), __byte_perm(v.y, v.z, 0x5432), __byte_perm(v.z, v.w, 0x5432), __byte_perm(v.w, n, 0x5432));
            }
            if (lane < 16) tab[1024 + lane] = 0.f;
            __syncwarp();
        }
        TS3(21 + 2 * ch);
        if (ch == 0) { if (!STAGGER || warp < 4) named_bar(1, 384); }
        else {
#pragma unroll
            for (int i = 0; i < 4; i++) asm volatile("prefetch.global.L2 [%0];" :: "l"(wslice + (size_t)((tid & 127) + 128 * i) * DM));
        }
        float acc[4][4][4];
#pragma unroll
        for (int i = 0; i < 4; i++)
#pragma unroll
            for (int j = 0; j < 4; j++) { acc[i][j][0] = acc[i][j][1] = acc[i][j][2] = acc[i][j][3] = 0.f; }
        {
            uint32_t X[4][4], Y[4][4], b[4][2][4];
            const int j0 = 2047 - g + 2 * tq;
            uint32_t ka = smem_u32(kr) + ((j0 & 1) ? SD_KLEN * 2 : 0) + 2u * (uint32_t)(j0 & ~1);
            uint32_t ua = smem_u32(us) + (uint32_t)(((lane & 7) + 8) * 144 + (lane >> 3) * 16);
#pragma unroll
            for (int i = 0; i < 4; i++) {
                Y[i][0] = Y[i][1] = Y[i][2] = Y[i][3] = 0u;
                tap_tile(X[i], ka - 32 * i);
                ldsm_x4(b[i][0], ua + i * 1152); ldsm_x4(b[i][1], ua + i * 1152 + 64);
            }
            conv_oct<0>(acc, X, Y, b, ka, ua);
            conv_oct<1>(acc, X, Y, b, ka, ua);
            conv_oct<2>(acc, X, Y, b, ka, ua);
            conv_oct<3>(acc, X, Y, b, ka, ua);
        }
        __syncwarp();
        if (ch == 0) { if (lane == 0) wait_cnt(&g_gcnt[0], SD_NCTA * ep); __syncwarp(); }
        uint4 gv[8];
#pragma unroll
        for (int i = 0; i < 8; i++) gv[i] = __ldcg(reinterpret_cast<const uint4*>(g_gate) + lane + 32 * i);
        const uint32_t dd = __byte_perm(*reinterpret_cast<const unsigned short*>(dskip + d), 0u, 0x1010);
#pragma unroll
        for (int nt = 0; nt < 4; nt++)
#pragma unroll
            for (int m2 = 0; m2 < 2; m2++)
                asm volatile("stmatrix.sync.aligned.m8n8.x4.trans.shared.b16 [%0], {%1,%2,%3,%4};"
                             :: "r"(smem_u32(kr) + (uint32_t)((8 * nt + (lane & 7)) * 144 + m2 * 64 + (lane >> 3) * 16)),
                                "r"(pack_bf16(acc[2 * m2][nt][0], acc[2 * m2][nt][1])), "r"(pack_bf16(acc[2 * m2][nt][2], acc[2 * m2][nt][3])),
                                "r"(pack_bf16(acc[2 * m2 + 1][nt][0], acc[2 * m2 + 1][nt][1])), "r"(pack_bf16(acc[2 * m2 + 1][nt][2], acc[2 * m2 + 1][nt][3])) : "memory");
        __syncwarp();
#pragma unroll
        for (int i = 0; i < 8; i++) {
            const uint4 y = *reinterpret_cast<const uint4*>(kr + (4 * i + (lane >> 3)) * 72 + (lane & 7) * 8);
            const uint4 u = *reinterpret_cast<const uint4*>(us + (8 + 4 * i + (lane >> 3)) * 72 + (lane & 7) * 8);
            *reinterpret_cast<uint4*>(g_y + (size_t)d * S_LEN + (lane + 32 * i) * 8) =
                make_uint4(bf2_mul(bf2_sub(0x3f803f80u, gv[i].x), bf2_add(y.x, bf2_mul(u.x, dd))), bf2_mul(bf2_sub(0x3f803f80u, gv[i].y), bf2_add(y.y, bf2_mul(u.y, dd))),
                           bf2_mul(bf2_sub(0x3f803f80u, gv[i].z), bf2_add(y.z, bf2_mul(u.z, dd))), bf2_mul(bf2_sub(0x3f803f80u, gv[i].w), bf2_add(y.w, bf2_mul(u.w, dd))));
        }
        __syncwarp();
        if (lane < 16) reinterpret_cast<uint32_t*>(kr + 2048)[lane] = 0u;
        TS3(22 + 2 * ch);
    }
}
__device__ __forceinline__ void s4d_stage_u(unsigned char* smem_raw, const bf16* __restrict__ x, int pt) {
    bf16* u_all = reinterpret_cast<bf16*>(smem_raw);
    const int d0 = blockIdx.x * SD_CH;
#pragma unroll 1
    for (int b = 0; b < 4; b++) {
        uint4 v[8];
#pragma unroll
        for (int i = 0; i < 8; i++) {
            int c = pt + 128 * (8 * b + i);
            v[i] = *reinterpret_cast<const uint4*>(x + (size_t)(c >> 1) * DM + d0 + (c & 1) * 8);
        }
#pragma unroll
        for (int i = 0; i < 8; i++) {
            int c = pt + 128 * (8 * b + i), t = c >> 1;
            bf16* dst = u_all + (c & 1) * 8 * SD_USTR + (8 + (t >> 6)) * 72 + (t & 63);
            const bf16* pv = reinterpret_cast<const bf16*>(&v[i]);
#pragma unroll
            for (int ch = 0; ch < 8; ch++) dst[ch * SD_USTR] = pv[ch];
        }
    }
    asm volatile("bar.arrive 1, 384;" ::: "memory");
}

constexpr int WOC = DM / 3;
constexpr int TBUF = 5 * DH * 16;
constexpr int XBUF = SEG * DM * 2;
constexpr float ATT_SCALE = 0.08838834764831845f;
constexpr int SM_BAR = 0;
constexpr int B_SB = 0, B_VX = 16, B_XT = 32, B_W = 64, B_E = 136;
constexpr int SM_SC = 256;
constexpr int SM_F = SM_SC + 1280;
constexpr int SM_VM = SM_F + 2048;
constexpr int SM_S = SM_VM + 2048;
constexpr int SM_O = SM_S + 2560;
constexpr int SM_M = SM_O + 2048;
constexpr int SM_WS = 19456;
constexpr int SM_T = SM_WS + 32768;
constexpr int SM_VX = SM_T + 4 * TBUF;
constexpr int SM_X = SM_VX + 2 * 8192;
constexpr int SM_X01 = SM_WS + DM * DH * 2;
__host__ __device__ constexpr int x01_off(int b) { return b == 2 ? 2048 : SM_X01 + (b < 2 ? b + 6 : b - 3) * 8192; }
constexpr int SM_E = SM_WS + 6 * 16384;
constexpr int CH_SMEM = SM_X01 + 8 * 8192;
static_assert(SM_M + DM * 16 <= SM_WS && SM_X + 3 * XBUF <= CH_SMEM && CH_SMEM <= 232448 && SM_X % 1024 == 0 && SM_X01 % 1024 == 0 && SM_M >= 10240 && SM_F <= 2048, "smem");
__device__ __forceinline__ uint32_t clock32() { uint32_t t; asm volatile("mov.u32 %0, %%clock;" : "=r"(t) :: "memory"); return t; }

__device__ __forceinline__ uint32_t mapa(uint32_t a, uint32_t rank) {
    uint32_t r; asm volatile("mapa.shared::cluster.u32 %0, %1, %2;" : "=r"(r) : "r"(a), "r"(rank)); return r;
}
__device__ __forceinline__ void st_async32(uint32_t addr, uint32_t v, uint32_t mbar) {
    asm volatile("st.async.weak.shared::cluster.mbarrier::complete_tx::bytes.b32 [%0], %1, [%2];" :: "r"(addr), "r"(v), "r"(mbar) : "memory");
}
__device__ __forceinline__ void mbar_init(uint32_t bar, uint32_t cnt) {
    asm volatile("mbarrier.init.shared::cta.b64 [%0], %1;" :: "r"(bar), "r"(cnt) : "memory");
}
__device__ __forceinline__ void mbar_expect(uint32_t bar, uint32_t bytes) {
    asm volatile("mbarrier.arrive.expect_tx.shared::cta.b64 _, [%0], %1;" :: "r"(bar), "r"(bytes) : "memory");
}
__device__ __forceinline__ void mbar_wait(uint32_t bar, uint32_t parity) {
    unsigned it = 0;
    while (true) {
        uint32_t ok;
        asm volatile("{\n.reg .pred p;\nmbarrier.try_wait.parity.shared::cta.b64 p, [%1], %2;\nselp.u32 %0, 1, 0, p;\n}"
                     : "=r"(ok) : "r"(bar), "r"(parity) : "memory");
        if (ok || ++it >= SPIN_LIMIT) break;
    }
}
__device__ __forceinline__ void mbar_wait_long(uint32_t bar, uint32_t parity) {
    unsigned it = 0;
    while (true) {
        uint32_t ok;
        asm volatile("{\n.reg .pred p;\nmbarrier.try_wait.parity.shared::cta.b64 p, [%1], %2, %3;\nselp.u32 %0, 1, 0, p;\n}"
                     : "=r"(ok) : "r"(bar), "r"(parity), "r"(20000u) : "memory");
        if (ok || ++it >= SPIN_LIMIT) break;
    }
}
__device__ __forceinline__ uint64_t policy_evict_first() {
    uint64_t pol; asm volatile("createpolicy.fractional.L2::evict_first.b64 %0, 1.0;" : "=l"(pol)); return pol;
}
__device__ __forceinline__ void cluster_sync_all() {
    asm volatile("barrier.cluster.arrive.release.aligned;\nbarrier.cluster.wait.acquire.aligned;" ::: "memory");
}
__device__ __forceinline__ uint4 ld_vol_u4(const uint4* p) {
    uint4 v; asm volatile(LDV4 : "=r"(v.x), "=r"(v.y), "=r"(v.z), "=r"(v.w) : "l"(p) : "memory"); return v;
}
__device__ __forceinline__ void ld_vol_u4_p(uint4& v, const uint4* p, uint32_t pred) {
    asm volatile("{\n.reg .pred p;\nsetp.ne.u32 p, %5, 0;\n@p " LDV4 "\n}"
                 : "+r"(v.x), "+r"(v.y), "+r"(v.z), "+r"(v.w) : "l"(p), "r"(pred) : "memory");
}
__device__ __forceinline__ void st_vol_u4(uint4* p, uint4 v) {
    asm volatile(STV4 :: "l"(p), "r"(v.x), "r"(v.y), "r"(v.z), "r"(v.w) : "memory");
}
__device__ __forceinline__ void mma_bf16_r(float (&d)[4], uint32_t a0, uint32_t a1, uint32_t a2, uint32_t a3, uint32_t b0, uint32_t b1) {
    asm volatile("mma.sync.aligned.m16n8k16.row.col.f32.bf16.bf16.f32 {%0,%1,%2,%3}, {%4,%5,%6,%7}, {%8,%9}, {%0,%1,%2,%3};"
                 : "+f"(d[0]), "+f"(d[1]), "+f"(d[2]), "+f"(d[3])
                 : "r"(a0), "r"(a1), "r"(a2), "r"(a3), "r"(b0), "r"(b1));
}

__device__ __forceinline__ uint64_t smem_desc(uint32_t addr, uint32_t lbo, uint32_t sbo) {
    return (uint64_t)((addr & 0x3FFFF) >> 4) | ((uint64_t)(lbo >> 4) << 16) | ((uint64_t)(sbo >> 4) << 32);
}
__device__ __forceinline__ void wg_fence() { asm volatile("wgmma.fence.sync.aligned;" ::: "memory"); }
__device__ __forceinline__ void wg_commit() { asm volatile("wgmma.commit_group.sync.aligned;" ::: "memory"); }
__device__ __forceinline__ void wg_wait0() { asm volatile("wgmma.wait_group.sync.aligned 0;" ::: "memory"); }
__device__ __forceinline__ void fence_async() { asm volatile("fence.proxy.async.shared::cta;" ::: "memory"); }
__device__ __forceinline__ void wgmma_n32(float (&d)[16], const uint32_t (&a)[4], uint64_t bdesc, int scale_d) {
    asm volatile("{\n.reg .pred p;\nsetp.ne.b32 p, %21, 0;\n"
                 "wgmma.mma_async.sync.aligned.m64n32k16.f32.bf16.bf16 {%0,%1,%2,%3,%4,%5,%6,%7,%8,%9,%10,%11,%12,%13,%14,%15}, {%16,%17,%18,%19}, %20, p, 1, 1, 0;\n}"
                 : "+f"(d[0]), "+f"(d[1]), "+f"(d[2]), "+f"(d[3]), "+f"(d[4]), "+f"(d[5]), "+f"(d[6]), "+f"(d[7]),
                   "+f"(d[8]), "+f"(d[9]), "+f"(d[10]), "+f"(d[11]), "+f"(d[12]), "+f"(d[13]), "+f"(d[14]), "+f"(d[15])
                 : "r"(a[0]), "r"(a[1]), "r"(a[2]), "r"(a[3]), "l"(bdesc), "r"(scale_d));
}

__device__ __forceinline__ void wgmma_n32_ss(float (&d)[16], uint64_t adesc, uint64_t bdesc, int scale_d) {
    asm volatile("{\n.reg .pred p;\nsetp.ne.b32 p, %18, 0;\n"
                 "wgmma.mma_async.sync.aligned.m64n32k16.f32.bf16.bf16 {%0,%1,%2,%3,%4,%5,%6,%7,%8,%9,%10,%11,%12,%13,%14,%15}, %16, %17, p, 1, 1, 1, 0;\n}"
                 : "+f"(d[0]), "+f"(d[1]), "+f"(d[2]), "+f"(d[3]), "+f"(d[4]), "+f"(d[5]), "+f"(d[6]), "+f"(d[7]),
                   "+f"(d[8]), "+f"(d[9]), "+f"(d[10]), "+f"(d[11]), "+f"(d[12]), "+f"(d[13]), "+f"(d[14]), "+f"(d[15])
                 : "l"(adesc), "l"(bdesc), "r"(scale_d));
}

__device__ __forceinline__ void wgmma_n64_ss(float (&d)[32], uint64_t adesc, uint64_t bdesc) {
    asm volatile("{\n.reg .pred p;\nsetp.eq.b32 p, 0, 0;\n"
                 "wgmma.mma_async.sync.aligned.m64n64k16.f32.bf16.bf16 {%0,%1,%2,%3,%4,%5,%6,%7,%8,%9,%10,%11,%12,%13,%14,%15,%16,%17,%18,%19,%20,%21,%22,%23,"
                 "%24,%25,%26,%27,%28,%29,%30,%31}, %32, %33, p, 1, 1, 1, 0;\n}"
                 : "+f"(d[0]), "+f"(d[1]), "+f"(d[2]), "+f"(d[3]), "+f"(d[4]), "+f"(d[5]), "+f"(d[6]), "+f"(d[7]),
                   "+f"(d[8]), "+f"(d[9]), "+f"(d[10]), "+f"(d[11]), "+f"(d[12]), "+f"(d[13]), "+f"(d[14]), "+f"(d[15]),
                   "+f"(d[16]), "+f"(d[17]), "+f"(d[18]), "+f"(d[19]), "+f"(d[20]), "+f"(d[21]), "+f"(d[22]), "+f"(d[23]),
                   "+f"(d[24]), "+f"(d[25]), "+f"(d[26]), "+f"(d[27]), "+f"(d[28]), "+f"(d[29]), "+f"(d[30]), "+f"(d[31])
                 : "l"(adesc), "l"(bdesc));
}
__device__ __forceinline__ void tma_2d(uint32_t dst, const CUtensorMap* tm, int c0, int c1, uint32_t mbar) {
    asm volatile("cp.async.bulk.tensor.2d.shared::cluster.global.tile.mbarrier::complete_tx::bytes [%0], [%1, {%2, %3}], [%4];"
                 :: "r"(dst), "l"(tm), "r"(c0), "r"(c1), "r"(mbar) : "memory");
}

__device__ __forceinline__ void bulk_g2s(uint32_t dst, const void* src, uint32_t bytes, uint32_t mbar) {
    asm volatile("cp.async.bulk.shared::cluster.global.mbarrier::complete_tx::bytes [%0], [%1], %2, [%3];"
                 :: "r"(dst), "l"(src), "r"(bytes), "r"(mbar) : "memory");
}
__device__ __forceinline__ void bulk_g2s_h(uint32_t dst, const void* src, uint32_t bytes, uint32_t mbar, uint64_t pol) {
    asm volatile("cp.async.bulk.shared::cluster.global.mbarrier::complete_tx::bytes.L2::cache_hint [%0], [%1], %2, [%3], %4;"
                 :: "r"(dst), "l"(src), "r"(bytes), "r"(mbar), "l"(pol) : "memory");
}
__device__ __forceinline__ void tma_x(uint32_t dst, const CUtensorMap* tm, int seg, int part, uint32_t mbar) {
    asm volatile("cp.async.bulk.tensor.3d.shared::cluster.global.tile.mbarrier::complete_tx::bytes [%0], [%1, {%2, %3, %4}], [%5];"
                 :: "r"(dst + part * 12288), "l"(tm), "r"(0), "r"(seg * SEG), "r"(part * 3), "r"(mbar) : "memory");
}
__device__ __forceinline__ void tma_x_mc(uint32_t dst, const CUtensorMap* tm, int seg, int part, uint32_t mbar) {
    asm volatile("cp.async.bulk.tensor.3d.shared::cluster.global.tile.mbarrier::complete_tx::bytes.multicast::cluster [%0], [%1, {%2, %3, %4}], [%5], %6;"
                 :: "r"(dst + part * 12288), "l"(tm), "r"(0), "r"(seg * SEG), "r"(part * 3), "r"(mbar), "h"((unsigned short)7) : "memory");
}
__device__ __forceinline__ void bulk_s2s(uint32_t dst, uint32_t src, uint32_t bytes, uint32_t mbar) {
    asm volatile("cp.async.bulk.shared::cluster.shared::cta.mbarrier::complete_tx::bytes [%0], [%1], %2, [%3];"
                 :: "r"(dst), "r"(src), "r"(bytes), "r"(mbar) : "memory");
}
__device__ __forceinline__ void wgmma_n40_ss(float (&d)[20], uint64_t adesc, uint64_t bdesc, int scale_d) {
    asm volatile("{\n.reg .pred p;\nsetp.ne.b32 p, %22, 0;\n"
                 "wgmma.mma_async.sync.aligned.m64n40k16.f32.bf16.bf16 {%0,%1,%2,%3,%4,%5,%6,%7,%8,%9,%10,%11,%12,%13,%14,%15,%16,%17,%18,%19}, %20, %21, p, 1, 1, 1, 1;\n}"
                 : "+f"(d[0]), "+f"(d[1]), "+f"(d[2]), "+f"(d[3]), "+f"(d[4]), "+f"(d[5]), "+f"(d[6]), "+f"(d[7]),
                   "+f"(d[8]), "+f"(d[9]), "+f"(d[10]), "+f"(d[11]), "+f"(d[12]), "+f"(d[13]), "+f"(d[14]), "+f"(d[15]),
                   "+f"(d[16]), "+f"(d[17]), "+f"(d[18]), "+f"(d[19])
                 : "l"(adesc), "l"(bdesc), "r"(scale_d));
}
__device__ __forceinline__ void wgmma_n64_z(float (&d)[32], const uint32_t (&a)[4], uint64_t bdesc) {
    asm volatile("{\n.reg .pred p;\nsetp.ne.b32 p, 0, 0;\n"
                 "wgmma.mma_async.sync.aligned.m64n64k16.f32.bf16.bf16 {%0,%1,%2,%3,%4,%5,%6,%7,%8,%9,%10,%11,%12,%13,%14,%15,%16,%17,%18,%19,%20,%21,%22,%23,%24,%25,%26,%27,%28,%29,%30,%31}, {%32,%33,%34,%35}, %36, p, 1, 1, 0;\n}"
                 : "=f"(d[0]), "=f"(d[1]), "=f"(d[2]), "=f"(d[3]), "=f"(d[4]), "=f"(d[5]), "=f"(d[6]), "=f"(d[7]),
                   "=f"(d[8]), "=f"(d[9]), "=f"(d[10]), "=f"(d[11]), "=f"(d[12]), "=f"(d[13]), "=f"(d[14]), "=f"(d[15]),
                   "=f"(d[16]), "=f"(d[17]), "=f"(d[18]), "=f"(d[19]), "=f"(d[20]), "=f"(d[21]), "=f"(d[22]), "=f"(d[23]),
                   "=f"(d[24]), "=f"(d[25]), "=f"(d[26]), "=f"(d[27]), "=f"(d[28]), "=f"(d[29]), "=f"(d[30]), "=f"(d[31])
                 : "r"(a[0]), "r"(a[1]), "r"(a[2]), "r"(a[3]), "l"(bdesc));
}
__device__ __forceinline__ void wgmma_n64(float (&d)[32], const uint32_t (&a)[4], uint64_t bdesc, int scale_d) {
    asm volatile("{\n.reg .pred p;\nsetp.ne.b32 p, %37, 0;\n"
                 "wgmma.mma_async.sync.aligned.m64n64k16.f32.bf16.bf16 {%0,%1,%2,%3,%4,%5,%6,%7,%8,%9,%10,%11,%12,%13,%14,%15,%16,%17,%18,%19,%20,%21,%22,%23,%24,%25,%26,%27,%28,%29,%30,%31}, {%32,%33,%34,%35}, %36, p, 1, 1, 0;\n}"
                 : "+f"(d[0]), "+f"(d[1]), "+f"(d[2]), "+f"(d[3]), "+f"(d[4]), "+f"(d[5]), "+f"(d[6]), "+f"(d[7]),
                   "+f"(d[8]), "+f"(d[9]), "+f"(d[10]), "+f"(d[11]), "+f"(d[12]), "+f"(d[13]), "+f"(d[14]), "+f"(d[15]),
                   "+f"(d[16]), "+f"(d[17]), "+f"(d[18]), "+f"(d[19]), "+f"(d[20]), "+f"(d[21]), "+f"(d[22]), "+f"(d[23]),
                   "+f"(d[24]), "+f"(d[25]), "+f"(d[26]), "+f"(d[27]), "+f"(d[28]), "+f"(d[29]), "+f"(d[30]), "+f"(d[31])
                 : "r"(a[0]), "r"(a[1]), "r"(a[2]), "r"(a[3]), "l"(bdesc), "r"(scale_d));
}

constexpr int SB_FULL = 0, SB_EMPTY = 64, SB_QKF = 128, SB_VF = 144, SB_QKE = 160, SB_VE = 176, SB_OF = 192, SB_WO = 208, SB_TICK = 216;
constexpr int AT_0 = 256, AT_ST = 10240 + 2 * 9216;
constexpr int FS_A = 58368;
constexpr int FS_P = FS_A + 131072;
constexpr int FS_I = FS_P + 16384;
constexpr int FS_O = FS_I + 12288;
constexpr int FS_Z = FS_O + 12288, FS_G = AT_0 + 2 * AT_ST;
constexpr int SIDE_SMEM = FS_Z + 2048;
static_assert(SIDE_SMEM <= 232448 && FS_G + 128 <= FS_A && FS_A + SD_SMEM <= SIDE_SMEM, "smem");

__device__ __forceinline__ void bf16r2(float& a, float& b) {
    uint32_t p = pack_bf16(a, b);
    a = __uint_as_float(p << 16); b = __uint_as_float(p & 0xffff0000u);
}
__device__ __forceinline__ void wg_wait1() { asm volatile("wgmma.wait_group.sync.aligned 1;" ::: "memory"); }
__device__ __forceinline__ void mbar_arrive(uint32_t bar) { asm volatile("mbarrier.arrive.shared::cta.b64 _, [%0];" :: "r"(bar) : "memory"); }
__device__ __forceinline__ void wait_cnt_rlx(const unsigned* p, unsigned target, bool urgent) {
    unsigned it = 0, v;
    while (true) {
        asm volatile("ld.relaxed.gpu.global.u32 %0, [%1];" : "=r"(v) : "l"(p) : "memory");
        if ((int)(v - target) >= 0 || ++it >= SPIN_LIMIT) break;
        if (!urgent) __nanosleep(RLX_SLEEP);
    }
}

__device__ __forceinline__ uint32_t gtime32() { uint32_t t; asm volatile("mov.u32 %0, %%globaltimer_lo;" : "=r"(t) :: "memory"); return t; }
__device__ __forceinline__ void gate(uint32_t tick_addr) {
    uint32_t t1, p;
    asm volatile("ld.volatile.shared.v2.u32 {%0,%1}, [%2];" : "=r"(t1), "=r"(p) : "r"(tick_addr) : "memory");
    uint32_t d = gtime32() - t1;
    if (d < 4u * p) {
        d -= d >= 2u * p ? 2u * p : 0u;
        d -= d >= p ? p : 0u;
        if (d + GATE_A >= p && d + GATE_B < p) {
            const uint32_t t2 = gtime32() + (p - GATE_B - d);
            while ((int)(gtime32() - t2) < 0) {}
        }
    }
}

__device__ __forceinline__ void read_tick(uint32_t tick_addr, bool on) {
    const uint2 tk = ld_vol_u2(&g_tick);
    uint32_t p = tk.x - tk.y;
    p = p > GATE_P + 100u ? GATE_P + 100u : p;
    asm volatile("st.volatile.shared.v2.u32 [%0], {%1,%2};" :: "r"(tick_addr), "r"(tk.x), "r"(on ? p : 0u) : "memory");
}

__device__ __forceinline__ void xrow_softmax(float (&sc)[20], uint32_t (&pa)[3][4], int wq, int lane) {
    const int g = lane >> 2, tq = lane & 3;
    float mx0 = -INFINITY;
    const int q0 = MEMT + 8 * wq + g;
#pragma unroll
    for (int j = 0; j < 5; j++) {
        bf16r2(sc[4 * j], sc[4 * j + 1]);
        sc[4 * j] *= ATT_SCALE; sc[4 * j + 1] *= ATT_SCALE;
        bf16r2(sc[4 * j], sc[4 * j + 1]);
#pragma unroll
        for (int c = 0; c < 2; c++) {
            int key = 8 * j + 2 * tq + c;
            if (key > q0) sc[4 * j + c] = -INFINITY;
            mx0 = fmaxf(mx0, sc[4 * j + c]);
        }
    }
    mx0 = fmaxf(mx0, __shfl_xor_sync(0xffffffffu, mx0, 1)); mx0 = fmaxf(mx0, __shfl_xor_sync(0xffffffffu, mx0, 2));
    float sum0 = 0.f;
#pragma unroll
    for (int j = 0; j < 5; j++) {
#pragma unroll
        for (int c = 0; c < 2; c++) {
            float e0 = __expf(sc[4 * j + c] - mx0);
            sc[4 * j + c] = e0;
            sum0 += e0;
        }
    }
    sum0 += __shfl_xor_sync(0xffffffffu, sum0, 1); sum0 += __shfl_xor_sync(0xffffffffu, sum0, 2);
    const float i0 = 1.f / sum0;
#pragma unroll
    for (int ks = 0; ks < 3; ks++) {
        pa[ks][0] = pack_bf16(sc[8 * ks] * i0, sc[8 * ks + 1] * i0);
        pa[ks][1] = 0u;
        pa[ks][2] = ks < 2 ? pack_bf16(sc[8 * ks + 4] * i0, sc[8 * ks + 5] * i0) : 0u;
        pa[ks][3] = 0u;
    }
}

__device__ __forceinline__ void stsm_x4(uint32_t addr, uint32_t r0, uint32_t r1, uint32_t r2, uint32_t r3) {
    asm volatile("stmatrix.sync.aligned.m8n8.x4.shared.b16 [%0], {%1,%2,%3,%4};" :: "r"(addr), "r"(r0), "r"(r1), "r"(r2), "r"(r3) : "memory");
}
__device__ __forceinline__ uint32_t h2_to_bf2(uint32_t h) {
    uint32_t r;
    asm("{\n.reg .f16 l, h;\n.reg .f32 a, b;\nmov.b32 {l, h}, %1;\ncvt.f32.f16 a, l;\ncvt.f32.f16 b, h;\ncvt.rn.bf16x2.f32 %0, b, a;\n}" : "=r"(r) : "r"(h));
    return r;
}
__device__ __forceinline__ uint32_t max_abs2(uint32_t a, uint32_t b) { uint32_t r; asm("max.NaN.xorsign.abs.bf16x2 %0, %1, %2;" : "=r"(r) : "r"(a), "r"(b)); return r; }
__device__ __forceinline__ uint32_t movm(uint32_t v) {
    uint32_t r; asm volatile("movmatrix.sync.aligned.m8n8.trans.b16 %0, %1;" : "=r"(r) : "r"(v)); return r;
}
__device__ __forceinline__ void bar_arrive(int id, int n) { asm volatile("bar.arrive %0, %1;" :: "r"(id), "r"(n) : "memory"); }
__device__ __forceinline__ void lds64(uint32_t& a, uint32_t& b, uint32_t addr) {
    asm volatile("ld.shared.v2.u32 {%0,%1}, [%2];" : "=r"(a), "=r"(b) : "r"(addr) : "memory");
}
__device__ __forceinline__ void lds64f(float& a, float& b, uint32_t addr) {
    asm volatile("ld.shared.v2.f32 {%0,%1}, [%2];" : "=f"(a), "=f"(b) : "r"(addr) : "memory");
}
__device__ __forceinline__ void st_async64(uint32_t addr, uint32_t a, uint32_t b, uint32_t mbar) {
    asm volatile("st.async.weak.shared::cluster.mbarrier::complete_tx::bytes.v2.b32 [%0], {%1,%2}, [%3];" :: "r"(addr), "r"(a), "r"(b), "r"(mbar) : "memory");
}
__device__ __forceinline__ void mma_z(float (&d)[4], const uint32_t (&a)[4], uint32_t b0, uint32_t b1) {
    asm volatile("mma.sync.aligned.m16n8k16.row.col.f32.bf16.bf16.f32 {%0,%1,%2,%3}, {%4,%5,%6,%7}, {%8,%9}, {%10,%10,%10,%10};"
                 : "=f"(d[0]), "=f"(d[1]), "=f"(d[2]), "=f"(d[3])
                 : "r"(a[0]), "r"(a[1]), "r"(a[2]), "r"(a[3]), "r"(b0), "r"(b1), "f"(0.f));
}
__device__ __forceinline__ void mma_k8(float (&d)[4], uint32_t a0, uint32_t a1, uint32_t b) {
    asm volatile("mma.sync.aligned.m16n8k8.row.col.f32.bf16.bf16.f32 {%0,%1,%2,%3}, {%4,%5}, {%6}, {%0,%1,%2,%3};"
                 : "+f"(d[0]), "+f"(d[1]), "+f"(d[2]), "+f"(d[3]) : "r"(a0), "r"(a1), "r"(b));
}
__global__ void __launch_bounds__(512, 1) k_side(const __grid_constant__ CUtensorMap tmo, const bf16* __restrict__ x, const bf16* __restrict__ logA, const bf16* __restrict__ Aim,
                                                 const bf16* __restrict__ Cre, const bf16* __restrict__ Cim, const bf16* __restrict__ logdt,
                                                 const bf16* __restrict__ Wo, const bf16* __restrict__ dskip, const bf16* __restrict__ gw,
                                                 bf16* __restrict__ out) {
    extern __shared__ __align__(1024) unsigned char smem_raw[];
    const uint32_t sbase = smem_u32(smem_raw);
    const int tid = threadIdx.x, warp = __shfl_sync(0xffffffffu, tid >> 5, 0), lane = tid & 31, cta = blockIdx.x;
    const int cb = cta >> 2, kq = cta & 3;
    if (tid == 0) {
        for (int i = 0; i < 8; i++) { mbar_init(sbase + SB_FULL + 8 * i, 1); mbar_init(sbase + SB_EMPTY + 8 * i, 4); }
        for (int i = 0; i < 2; i++) {
            mbar_init(sbase + SB_QKF + 8 * i, 1); mbar_init(sbase + SB_VF + 8 * i, 1); mbar_init(sbase + SB_QKE + 8 * i, 1);
            mbar_init(sbase + SB_VE + 8 * i, 4); mbar_init(sbase + SB_OF + 8 * i, 4);
        }
        mbar_init(sbase + SB_WO, 1);
        *reinterpret_cast<uint2*>(smem_raw + SB_TICK) = make_uint2(0u, 0u);
        asm volatile("fence.mbarrier_init.release.cluster;" ::: "memory");
    }
    TS3(0);
    unsigned ep;
    asm volatile("ld.volatile.global.u32 %0, [%1];" : "=r"(ep) : "l"(&g_epoch) : "memory");
    ep += 1u;
    asm volatile("fence.proxy.async;" ::: "memory");
    __syncthreads();
    if (warp >= 12) {
      asm volatile("setmaxnreg.dec.sync.aligned.u32 40;");
      if (warp == 12 || warp == 15) {
        named_bar(3, 320);
        if (tid == 384) {
            fence_async();
            mbar_expect(sbase + SB_WO, 131072);
            if (cta >= NH) read_tick(sbase + SB_TICK, true);
#pragma unroll 1
            for (int i = 0; i < 8; i++) {
                gate(sbase + SB_TICK);
                tma_2d(sbase + FS_A + i * 16384, &tmo, cb * 64, kq * 1024 + i * 128, sbase + SB_WO);
                __nanosleep(150);
            }
            TSS(17, 2);
        }
        if (tid == 480) {
            __threadfence();
            asm volatile("red.relaxed.gpu.global.add.u32 [%0], 1;" :: "l"(&g_gcnt[32]) : "memory");
            TSS(17, 3);
        }
        __syncwarp();
        named_bar(7, 320);
        if (lane == 0) {
            const int pi = warp == 12 ? 0 : 1, kb = 2 * kq + pi;
            fence_async();
            for (int pr = 0; pr < NSEG / 2; pr++) {
                wait_cnt_rlx(&g_prog[pr * 8 + kb], 8u * ep, pr >= NSEG / 2 - 2);
                if (pi == 0 && cta >= NH) read_tick(sbase + SB_TICK, pr < (NSEG - UNGATE) / 2);
                if (pr >= 30 && pi == 0) TSS(4 + pr - 30, 0);
                if (pr == 31) TS3P(26);
                if (pr == 30) TS3P(1);
#pragma unroll
                for (int j = 0; j < 4; j++) {
                    const int st = 4 * pi + j;
                    mbar_wait_long(sbase + SB_EMPTY + 8 * st, ((uint32_t)pr & 1u) ^ 1u);
                    mbar_expect(sbase + SB_FULL + 8 * st, X_OXSZ);
                    gate(sbase + SB_TICK);
                    bulk_g2s(sbase + FS_A + st * 16384, g_ox + ((size_t)(pr * NH + 4 * kb + j)) * 8192, X_OXSZ, sbase + SB_FULL + 8 * st);
                }
            }
        }
        __syncwarp();
      } else if (warp == 13) {
        if (lane == 0 && cta < NH) {
            const uint64_t pol = policy_evict_first();
            for (int seg = 0; seg < NATT; seg++) {
                const uint32_t st = seg & 1, ph = (uint32_t)(seg >> 1) & 1u, ab = sbase + AT_0 + st * AT_ST;
                wait_cnt_rlx(&g_flag[seg * NH + cta], 3u * ep, seg >= NSEG - PROMPT - 1);
                if (seg >= 58) TSS(seg - 58, 0);
                mbar_wait_long(sbase + SB_QKE + 8 * st, ph ^ 1u);
                if (seg >= 58) TSS(seg - 58, 1);
                mbar_expect(sbase + SB_QKF + 8 * st, 2 * 9216);
                gate(sbase + SB_TICK);
                bulk_g2s_h(ab + 10240, &g_qkv[seg][cta][0][1024], 9216, sbase + SB_QKF + 8 * st, pol);
                bulk_g2s_h(ab + 10240 + 9216, &g_qkv[seg][cta][1][1024], 9216, sbase + SB_QKF + 8 * st, pol);
                mbar_wait_long(sbase + SB_VE + 8 * st, ph ^ 1u);
                mbar_expect(sbase + SB_VF + 8 * st, 10240);
                bulk_g2s_h(ab, &g_qkv[seg][cta][2][0], 10240, sbase + SB_VF + 8 * st, pol);
                read_tick(sbase + SB_TICK, seg < NSEG - UNGATE);
            }
        }
        __syncwarp();
      } else if (warp == 14) {
        if (lane == 0 && cta < NH) {
            for (int seg = 0; seg < NATT; seg++) {
                const uint32_t st = seg & 1, ab = sbase + AT_0 + st * AT_ST;
                mbar_wait_long(sbase + SB_OF + 8 * st, (uint32_t)(seg >> 1) & 1u);
                if (seg >= 58) TSS(seg - 58, 3);
                gate(sbase + SB_TICK);
                unsigned char* dst = reinterpret_cast<unsigned char*>(g_ox) + ((size_t)((seg >> 1) * NH + cta)) * 16384 + (seg & 1) * 4096;
                asm volatile("cp.async.bulk.global.shared::cta.bulk_group [%0], [%1], 4096;" :: "l"(dst), "r"(ab + 12288) : "memory");
                asm volatile("cp.async.bulk.global.shared::cta.bulk_group [%0], [%1], 4096;" :: "l"(dst + 8192), "r"(ab + 16384) : "memory");
                asm volatile("cp.async.bulk.commit_group;" ::: "memory");
                asm volatile("cp.async.bulk.wait_group 0;" ::: "memory");
                asm volatile("red.relaxed.gpu.global.add.u32 [%0], 1;" :: "l"(&g_prog[(seg >> 1) * 8 + (cta >> 2)]) : "memory");
                mbar_arrive(sbase + SB_QKE + 8 * st);
                if (seg >= 58) TSS(seg - 58, 4);
            }
        }
        __syncwarp();
      }
    } else if (warp >= 8) {
        asm volatile("setmaxnreg.dec.sync.aligned.u32 88;");
        s4d_stage_u(smem_raw + FS_A, x, tid - 256);
        {
            uint32_t gwv[9];
#pragma unroll
            for (int i = 0; i < 9; i++) gwv[i] = reinterpret_cast<const uint32_t*>(gw)[lane + 32 * i];
#pragma unroll 3
            for (int i = 0; i < 15; i++) {
                const int tt = 4 * i + warp - 8, t = min(cta * 57 + tt, S_LEN - 1);
                float sm = 0.f;
#pragma unroll
                for (int k = 0; k < 9; k++) {
                    const uint32_t xv = reinterpret_cast<const uint32_t*>(x + t * DM)[lane + 32 * k];
                    float a = __uint_as_float(xv << 16) * __uint_as_float(gwv[k] << 16), b = __uint_as_float(xv & 0xffff0000u) * __uint_as_float(gwv[k] & 0xffff0000u);
                    bf16r2(a, b);
                    sm += a + b;
                }
#pragma unroll
                for (int o = 16; o; o >>= 1) sm += __shfl_xor_sync(0xffffffffu, sm, o);
                const float gv = 1.f / (1.f + expf(-bf16r(sm)));
                if (lane == 0 && tt < 57) g_gate[t] = __float2bfloat16_rn(gv);
            }
#pragma unroll 1
            for (int b8 = 0; b8 < 8; b8++)
#pragma unroll
                for (int i = 0; i < 6; i++) g_fp[b8][cta][i][tid - 256] = make_uint4(0u, 0u, 0u, 0u);
            named_bar(6, 128);
            if (tid == 256) {
                __threadfence();
                asm volatile("red.relaxed.gpu.global.add.u32 [%0], 1;" :: "l"(&g_gcnt[0]) : "memory");
            }
            __syncwarp();
        }
        const int wq = warp - 8;
        for (int seg = 0; seg < (cta < NH ? NATT : 0); seg++) {
            const uint32_t st = seg & 1, ph = (uint32_t)(seg >> 1) & 1u, ab = sbase + AT_0 + st * AT_ST;
            float sc[20];
            mbar_wait_long(sbase + SB_QKF + 8 * st, ph);
            if (seg >= 58 && tid == 256) TSS(seg - 58, 2);
            {
                const uint64_t da = smem_desc(ab + 10240 + 1024, 128, 1024), db = smem_desc(ab + 10240, 128, 2048);
                wg_fence();
#pragma unroll
                for (int ks = 0; ks < 8; ks++) wgmma_n40_ss(sc, da + (uint64_t)((ks >> 2) * 576 + (ks & 3) * 16), db + (uint64_t)((ks >> 2) * 576 + (ks & 3) * 16), ks > 0);
                wg_commit();
                wg_wait0();
            }
            uint32_t pa[3][4];
            xrow_softmax(sc, pa, wq, lane);
            named_bar(6, 128);
            mbar_wait_long(sbase + SB_VF + 8 * st, ph);
#pragma unroll
            for (int hf = 0; hf < 2; hf++) {
                float o[32];
                const uint64_t dv = smem_desc(ab + hf * 1024, 2048, 128);
                wg_fence();
#pragma unroll
                for (int ks = 0; ks < 3; ks++) { if (ks == 0) wgmma_n64_z(o, pa[0], dv); else wgmma_n64(o, pa[ks], dv + (uint64_t)(ks * 256), 1); }
                wg_commit();
                wg_wait0();
#pragma unroll
                for (int i = 0; i < 2; i++)
                    stsm_x4(ab + 12288 + hf * 4096 + wq * 1024 + i * 512 + lane * 16, pack_bf16(o[16 * i], o[16 * i + 1]), pack_bf16(o[16 * i + 4], o[16 * i + 5]),
                            pack_bf16(o[16 * i + 8], o[16 * i + 9]), pack_bf16(o[16 * i + 12], o[16 * i + 13]));
            }
            if (lane == 0) mbar_arrive(sbase + SB_VE + 8 * st);
            fence_async();
            __syncwarp();
            if (lane == 0) mbar_arrive(sbase + SB_OF + 8 * st);
        }
    } else {
        asm volatile("setmaxnreg.inc.sync.aligned.u32 192;");
        const int wg = warp >> 2, wq = warp & 3;
        s4d_phase(smem_raw + FS_A, x, logA, Aim, Cre, Cim, logdt, dskip, Wo + (size_t)((2 * kq + wg) * 512) * DM + cb * 64, ep);
        TS3(2);
        if (lane == 0) TSS(16, warp);
        named_bar(3, 320);
        if (tid == 0) TSS(17, 0);
        uint32_t wa[32][4];
        mbar_wait_long(sbase + SB_WO, 0);
        if (tid == 0) TSS(17, 1);
        {
            const uint32_t a = sbase + FS_A + wg * 65536 + ((lane >> 4) * 8 + (lane & 7)) * 128 + (((wq * 2 + ((lane >> 3) & 1)) ^ (lane & 7)) << 4);
#pragma unroll
            for (int ks = 0; ks < 32; ks++) ldsm_x4_t(wa[ks], a + ks * 2048);
        }
        named_bar(7, 320);
        TS3(3);
        if (tid == 0) TSS(17, 4);
        auto product = [&](float (&acc)[32], int pr) {
                if (pr + wg > 0 && pr + wg < NSEG / 2) named_bar(4 + wg, 256);
                const uint64_t db = smem_desc(sbase + FS_A + wg * 65536, 128, 1024);
                TSG(0);
#pragma unroll
                for (int j = 0; j < 4; j++) {
                    mbar_wait(sbase + SB_FULL + 8 * (4 * wg + j), (uint32_t)pr & 1u);
                    wg_fence();
#pragma unroll
                    for (int ks = 0; ks < 8; ks++) {
                        if ((j | ks) == 0) wgmma_n64_z(acc, wa[0], db);
                        else wgmma_n64(acc, wa[8 * j + ks], db + (uint64_t)(j * 1024 + (ks >> 2) * 512 + (ks & 3) * 16), 1);
                    }
                    wg_commit();
                    if (j == 3 && pr + 1 < NSEG / 2) bar_arrive(4 + (wg ^ 1), 256);
                    if (j > 0) { wg_wait1(); if (lane == 0) mbar_arrive(sbase + SB_EMPTY + 8 * (4 * wg + j - 1)); }
                }
                wg_wait0();
                if (pr == 31) TS3W(27);
                TSG(3);
                if (lane == 0) mbar_arrive(sbase + SB_EMPTY + 8 * (4 * wg + 3));
        };
        if (wg == 1) {
            for (int pr = 0; pr < NSEG / 2; pr++) {
                uint32_t t16 = (uint32_t)(wq * 32 + lane) * 16u;
                asm volatile("" : "+r"(t16));
                float acc[32];
                product(acc, pr);
                    uint32_t tag = ((uint32_t)(pr >> 3) & 1u) ^ 1u;
                    tag = __shfl_sync(0xffffffffu, tag, lane);
                    gate(sbase + SB_TICK);
                    named_bar(8, 256);
                    unsigned char* dst = reinterpret_cast<unsigned char*>(&g_fp[pr & 7][4 * cb][2 * kq - 2][0]) + t16;
                    const uint32_t own = sbase + FS_O + (pr % 3) * 4096 + t16;
#pragma unroll
                    for (int q = 0; q < 8; q++) {
                        float4 p;
                        asm volatile("ld.shared.v4.f32 {%0,%1,%2,%3}, [%4];" : "=f"(p.x), "=f"(p.y), "=f"(p.z), "=f"(p.w) : "r"(sbase + FS_P + t16 + q * 2048) : "memory");
                        acc[4 * q] = __uint_as_float((__float_as_uint(acc[4 * q] + p.x) & ~1u) | tag); acc[4 * q + 1] = __uint_as_float((__float_as_uint(acc[4 * q + 1] + p.y) & ~1u) | tag);
                        acc[4 * q + 2] = __uint_as_float((__float_as_uint(acc[4 * q + 2] + p.z) & ~1u) | tag); acc[4 * q + 3] = __uint_as_float((__float_as_uint(acc[4 * q + 3] + p.w) & ~1u) | tag);
                    }
#pragma unroll
                    for (int q = 0; q < 8; q++) {
                        asm volatile("{\n.reg .pred p;\nsetp.ne.s32 p, %5, %6;\n@p st.volatile.global.v4.f32 [%0], {%1,%2,%3,%4};\n@!p st.shared.v4.f32 [%7], {%1,%2,%3,%4};\n}"
                                     :: "l"(dst + (q & 1) * 2048), "f"(acc[4 * q]), "f"(acc[4 * q + 1]), "f"(acc[4 * q + 2]), "f"(acc[4 * q + 3]), "r"(q >> 1), "r"(kq),
                                        "r"(own + (q & 1) * 2048) : "memory");
                        if (q & 1) dst += (q >> 1) == kq ? 12288 + 4096 : 12288;
                    }
                    bar_arrive(9, 256);
                    if (pr == 31) TS3W(28);
                TSG(4);
            }
        } else {
          for (int it = 0; it < NSEG / 2 + 2; it++) {
            const int pr = it < 31 ? it : (it == 32 ? 31 : -1);
            const int pf = it - 2;
            uint32_t t16 = (uint32_t)(wq * 32 + lane) * 16u;
            asm volatile("" : "+r"(t16));
            const int t0 = pf * 64 + kq * 16, c0 = cb * 64 + wq * 16;
            auto fetch = [&]() {
                const unsigned char* src = reinterpret_cast<const unsigned char*>(&g_fp[pf & 7][cta][0][0]) + t16;
#pragma unroll
                for (int r = 0; r < 6; r++) asm volatile("cp.async.cg.shared.global [%0], [%1], 16;" :: "r"(sbase + FS_I + t16 + r * 2048), "l"(src + r * 2048) : "memory");
                asm volatile("cp.async.commit_group;" ::: "memory");
            };
            if (pf >= 0) {
                if (pf == 0) { if (lane == 0) wait_cnt(&g_gcnt[32], SD_NCTA * ep); __syncwarp(); }
                asm volatile("cp.async.cg.shared.global [%0], [%1], 16;" :: "r"(sbase + FS_Z + t16), "l"(g_y + (size_t)(c0 + (lane & 15)) * S_LEN + t0 + (lane >> 4) * 8) : "memory");
                if (lane < 2) asm volatile("cp.async.cg.shared.global [%0], [%1], 16;" :: "r"(sbase + FS_G + wq * 32 + lane * 16), "l"(g_gate + t0 + lane * 8) : "memory");
            }
            if (it == 33) named_bar(9, 256);
            if (pf >= 0) { gate(sbase + SB_TICK); fetch(); }
            if (pr >= 0) {
                float acc[32];
                product(acc, pr);
                    if (pr > 0) named_bar(9, 256);
#pragma unroll
                    for (int q = 0; q < 8; q++)
                        asm volatile("st.shared.v4.f32 [%0], {%1,%2,%3,%4};" :: "r"(sbase + FS_P + t16 + q * 2048), "f"(acc[4 * q]), "f"(acc[4 * q + 1]), "f"(acc[4 * q + 2]), "f"(acc[4 * q + 3]) : "memory");
                    bar_arrive(8, 256);
                TSG(4);
            }
            if (pf >= 0) {
                const uint32_t tag = ((uint32_t)(pf >> 3) & 1u) ^ 1u;
                uint4 v[8];
                unsigned n = 0;
                while (true) {
                    asm volatile("cp.async.wait_group 0;" ::: "memory");
                    uint32_t any = 0u;
#pragma unroll
                    for (int r = 0; r < 8; r++)
                        asm volatile("ld.shared.v4.u32 {%0,%1,%2,%3}, [%4];" : "=r"(v[r].x), "=r"(v[r].y), "=r"(v[r].z), "=r"(v[r].w)
                                     : "r"(sbase + t16 + (r < 6 ? FS_I + r * 2048 : FS_O + (pf % 3) * 4096 + (r - 6) * 2048)) : "memory");
#pragma unroll
                    for (int r = 0; r < 6; r++) {
                        uint32_t c0_, c1_;
                        asm("lop3.b32 %0, %1, %2, %3, 0x7e;" : "=r"(c0_) : "r"(v[r].x), "r"(v[r].y), "r"(tag));
                        asm("lop3.b32 %0, %1, %2, %3, 0x7e;" : "=r"(c1_) : "r"(v[r].z), "r"(v[r].w), "r"(tag));
                        asm("lop3.b32 %0, %1, %2, %3, 0xfe;" : "=r"(any) : "r"(any), "r"(c0_), "r"(c1_));
                    }
                    if (!__any_sync(0xffffffffu, (any & 1u) != 0u) || ++n >= SPIN_LIMIT) break;
                    if (pf + 1 < NSEG / 2) __nanosleep(200);
                    fetch();
                }
                if (pf == 31) TS3(29);
                TSG(5);
                uint32_t zv[4], gg[2];
                ldsm_x4_t(zv, sbase + FS_Z + t16);
#pragma unroll
                for (int k = 0; k < 2; k++) gg[k] = __byte_perm(*reinterpret_cast<const unsigned short*>(smem_raw + FS_G + wq * 32 + k * 16 + (lane >> 2) * 2), 0u, 0x1010);
                const uint32_t xo = (uint32_t)((t0 + (lane >> 2)) * DM + c0 + 2 * (lane & 3)) * 2u;
#define PQS(k, f) ((__uint_as_float(v[k].f) + __uint_as_float(v[2 + k].f)) + (__uint_as_float(v[4 + k].f) + __uint_as_float(v[6 + k].f)))
#pragma unroll
                for (int k = 0; k < 2; k++) {
                    unsigned char* op = reinterpret_cast<unsigned char*>(out) + xo + k * (16 * DM);
                    *reinterpret_cast<uint32_t*>(op) = bf2_add(bf2_mul(gg[k], movm(pack_bf16(PQS(k, x), PQS(k, y)))), zv[2 * k]);
                    *reinterpret_cast<uint32_t*>(op + 16) = bf2_add(bf2_mul(gg[k], movm(pack_bf16(PQS(k, z), PQS(k, w)))), zv[2 * k + 1]);
                }
#undef PQS
                if ((pf & 1) == 0) TS3(4 + pf / 2);
                if (pf == 31) TS3(25);
                TSG(6);
            }
        }
        }
        if (cta == 0 && tid == 0) asm volatile("red.relaxed.gpu.global.add.u32 [%0], 1;" :: "l"(&g_epoch) : "memory");
    }
    asm volatile("griddepcontrol.wait;" ::: "memory");
}

__device__ __forceinline__ uint32_t poll_mem(const uint4* src, uint32_t dst, uint32_t t0) {
    uint4 v[6];
    unsigned it = 0;
#pragma unroll
    for (int j = 0; j < 6; j++) v[j] = make_uint4(0u, 0u, 0u, 0u);
    while (clock32() - t0 < POLL_DELAY) {}
    FS(12, 0);
    bool more;
#pragma unroll 1
    do {
        asm volatile("{\n.reg .pred p<6>;\n"
                     "setp.ne.u32 p0, %3, 0x5000;\nsetp.ne.u32 p1, %7, 0x5000;\nsetp.ne.u32 p2, %11, 0x5000;\n"
                     "setp.ne.u32 p3, %15, 0x5000;\nsetp.ne.u32 p4, %19, 0x5000;\nsetp.ne.u32 p5, %23, 0x5000;\n"
                     "@p0 ld.volatile.global.v4.u32 {%0,%1,%2,%3}, [%24];\n@p1 ld.volatile.global.v4.u32 {%4,%5,%6,%7}, [%24+4096];\n"
                     "@p2 ld.volatile.global.v4.u32 {%8,%9,%10,%11}, [%24+8192];\n@p3 ld.volatile.global.v4.u32 {%12,%13,%14,%15}, [%24+12288];\n"
                     "@p4 ld.volatile.global.v4.u32 {%16,%17,%18,%19}, [%24+16384];\n@p5 ld.volatile.global.v4.u32 {%20,%21,%22,%23}, [%24+20480];\n}"
                     : "+r"(v[0].x), "+r"(v[0].y), "+r"(v[0].z), "+r"(v[0].w), "+r"(v[1].x), "+r"(v[1].y), "+r"(v[1].z), "+r"(v[1].w),
                       "+r"(v[2].x), "+r"(v[2].y), "+r"(v[2].z), "+r"(v[2].w), "+r"(v[3].x), "+r"(v[3].y), "+r"(v[3].z), "+r"(v[3].w),
                       "+r"(v[4].x), "+r"(v[4].y), "+r"(v[4].z), "+r"(v[4].w), "+r"(v[5].x), "+r"(v[5].y), "+r"(v[5].z), "+r"(v[5].w)
                     : "l"(src) : "memory");
        stsm_x4(dst, h2_to_bf2(v[0].x), h2_to_bf2(v[0].y), h2_to_bf2(v[0].z), h2_to_bf2(v[1].x));
        stsm_x4(dst + 512, h2_to_bf2(v[1].y), h2_to_bf2(v[1].z), h2_to_bf2(v[2].x), h2_to_bf2(v[2].y));
        stsm_x4(dst + 1024, h2_to_bf2(v[2].z), h2_to_bf2(v[3].x), h2_to_bf2(v[3].y), h2_to_bf2(v[3].z));
        asm volatile("stmatrix.sync.aligned.m8n8.x2.shared.b16 [%0], {%1,%2};" :: "r"(dst + 1536), "r"(h2_to_bf2(v[4].x)), "r"(h2_to_bf2(v[4].y)) : "memory");
        stsm_x4(dst + 1792, h2_to_bf2(v[4].z), h2_to_bf2(v[5].x), h2_to_bf2(v[5].y), h2_to_bf2(v[5].z));
        const uint32_t all = ((v[0].w & v[1].w) & (v[2].w & v[3].w)) & (v[4].w & v[5].w);
        more = __any_sync(0xffffffffu, (all & 0x5000u) != 0x5000u) && ++it < SPIN_LIMIT;
    } while (more);
    FS(13, it);
    bar_arrive(1, 384);
    FS(14, 0);
    uint32_t m = 0u;
#pragma unroll
    for (int j = 0; j < 6; j++) {
        asm volatile("max.NaN.xorsign.abs.f16x2 %0, %0, %1;" : "+r"(m) : "r"(v[j].x));
        asm volatile("max.NaN.xorsign.abs.f16x2 %0, %0, %1;" : "+r"(m) : "r"(v[j].y));
        asm volatile("max.NaN.xorsign.abs.f16x2 %0, %0, %1;" : "+r"(m) : "r"(v[j].z));
    }
    return h2_to_bf2(m) & 0x7fff7fffu;
}

__device__ __forceinline__ void score_group(uint32_t qa, const uint32_t (&kf)[2][4], uint32_t d0, uint32_t d1, uint32_t m1, uint32_t d2, uint32_t m2) {
    uint32_t a[2][4];
#pragma unroll
    for (int k2 = 0; k2 < 2; k2++) ldsm_x4_t(a[k2], qa + k2 * 512);
    FS(4, a[1][0]);
    float sc[4][4];
    mma_z(sc[0], a[0], kf[0][0], kf[0][1]);
    mma_z(sc[1], a[0], kf[0][2], kf[0][3]);
    mma_z(sc[2], a[1], kf[1][0], kf[1][1]);
    mma_z(sc[3], a[1], kf[1][2], kf[1][3]);
    const uint32_t v0 = __float_as_uint((sc[0][0] + sc[1][2]) + (sc[2][0] + sc[3][2])), v1 = __float_as_uint((sc[0][1] + sc[1][3]) + (sc[2][1] + sc[3][3]));
    FS(5, v0);
    st_async64(d2, v0, v1, m2);
    st_async64(d1, v0, v1, m1);
    asm volatile("st.shared.v2.u32 [%0], {%1,%2};" :: "r"(d0), "r"(v0), "r"(v1) : "memory");
}
__device__ __forceinline__ void store_tile(int s, int h, int role, uint32_t tile) {
    const uint32_t qoff = role != 2 ? 1024 : 0;
    asm volatile("cp.async.bulk.global.shared::cta.bulk_group.L2::cache_hint [%0], [%1], %2, %3;"
                 :: "l"(&g_qkv[s][h][role][qoff]), "r"(tile + qoff), "r"(10240u - qoff), "l"(policy_evict_first()) : "memory");
    asm volatile("cp.async.bulk.commit_group;" ::: "memory");
}
__device__ __forceinline__ uint32_t w_addr(uint32_t sbase, int warp, int lane) {
    return sbase + SM_WS + (warp >> 2) * 8192 + ((lane & 7) + ((lane >> 4) & 1) * 8) * 128 + ((((warp & 3) * 2 + ((lane >> 3) & 1)) ^ (lane & 7)) << 4);
}
__device__ __forceinline__ void vx_copy(uint32_t sbase, int j, int r) {
    bulk_s2s(mapa(sbase + SM_VX + (j & 1) * 8192, r), sbase + SM_T + (j & 3) * TBUF + DH * 16, 8192, mapa(sbase + B_VX + 8 * (j & 1), r));
}
__device__ __forceinline__ void norms_gather(int lane, float* scs) {
    uint2 v[3];
    uint32_t r[2];
    unsigned it = 0;
    do {
#pragma unroll
        for (int i = 0; i < 3; i++) v[i] = ld_vol_u2(&g_norm[3 * lane + i]);
#pragma unroll
        for (int i = 0; i < 2; i++) asm volatile("ld.volatile.global.u32 %0, [%1];" : "=r"(r[i]) : "l"(&g_rx[lane + 32 * i]) : "memory");
    } while (__any_sync(0xffffffffu, (v[0].x & v[1].x & v[2].x & v[2].y & r[0] & r[1] & 1u) == 0u) && ++it < SPIN_LIMIT);
    float c;
    asm("sqrt.approx.f32 %0, %1;" : "=f"(c) : "f"(__uint_as_float(max(max(v[0].x, v[1].x), v[2].x))));
    c *= __uint_as_float(v[2].y) * 272.f;
#pragma unroll
    for (int o = 16; o; o >>= 1) c += __shfl_xor_sync(0xffffffffu, c, o);
    scs[16 + lane] = __uint_as_float(r[0]); scs[48 + lane] = __uint_as_float(r[1]);
    if (lane == 0) scs[1] = c * (1.1f * 24.f);
}

__global__ void __cluster_dims__(3, 1, 1) __launch_bounds__(384, 1)
k_chain(const __grid_constant__ CUtensorMap tmx, const __grid_constant__ CUtensorMap tmq, const __grid_constant__ CUtensorMap tmk,
        const __grid_constant__ CUtensorMap tmv, const __grid_constant__ CUtensorMap tmx2, const __grid_constant__ CUtensorMap tmo, const bf16* __restrict__ mem0, const bf16* __restrict__ xg) {
    extern __shared__ __align__(1024) unsigned char smem_raw[];
    const uint32_t sbase = smem_u32(smem_raw);
    const int cta = blockIdx.x, h = cta / 3, role = cta - 3 * h;
    const int tid = threadIdx.x, warp = __shfl_sync(0xffffffffu, tid >> 5, 0), lane_o = tid & 31;
    TS3C(0);
    asm volatile("griddepcontrol.launch_dependents;" ::: "memory");
    auto stage_w = [&](int i) {
        tma_2d(sbase + SM_WS + i * 16384, role == 2 ? &tmv : &tmq, h * DH + (role == 1 ? 64 : 0), i * 64, sbase + B_W + 8 * i);
        tma_2d(sbase + SM_WS + i * 16384 + 8192, role == 2 ? &tmv : &tmk, h * DH + (role == 0 ? 0 : 64), i * 64, sbase + B_W + 8 * i);
    };
    auto stage_x = [&](int i) { tma_2d(sbase + x01_off(i), &tmx2, i * 64, 0, sbase + B_W + 8 * i); };
    if (tid == 0) {
#pragma unroll
        for (int i = 0; i < 10; i++) mbar_init(sbase + B_W + 8 * i, 1);
        fence_async();
        bulk_g2s(sbase + SM_E + XBUF, mem0, MEMT * DM * 2, sbase + B_E);
#pragma unroll
        for (int i = 0; i < 3; i++) tma_2d(sbase + SM_X01 + i * 16384, &tmo, role * WOC + i * 64, h * DH, sbase + B_E);
        if (cta < NSEG) bulk_g2s(sbase + SM_E, xg + (size_t)cta * SEG * DM, XBUF, sbase + B_E);
#pragma unroll 1
        for (int i = 0; i < 6; i++) { if (i < 3) stage_x(i); stage_w(i); }
        mbar_expect(sbase + B_E, 49152 + MEMT * DM * 2 + (cta < NSEG ? XBUF : 0));
#pragma unroll
        for (int i = 0; i < 9; i++) mbar_expect(sbase + B_W + 8 * i, 24576);
    } else if (tid == 32) {
#pragma unroll
        for (int i = 0; i < 7; i++) mbar_init(sbase + SM_BAR + 8 * i, 1);
        asm volatile("fence.mbarrier_init.release.cluster;" ::: "memory");
        for (int i = 0; i < 2; i++) {
            mbar_expect(sbase + B_SB + 8 * i, role == 2 ? 2560 : 1280 + 2048);
            mbar_expect(sbase + B_VX + 8 * i, role != 2 ? 8192 : 2 * 9216);
            mbar_arrive(sbase + B_XT + 8 * i);
        }
        mbar_expect(sbase + B_XT + 16, XBUF);
        reinterpret_cast<float*>(smem_raw + SM_SC)[2] = 1.f;
    } else if (tid >= 64 && tid < 88) {
        *reinterpret_cast<uint4*>(g_acc + cta * 1024 + (tid - 64) * 16) = make_uint4(0u, 0u, 0u, 0u);
        __threadfence();
    }
    __syncthreads();
    TS3C(8);
    if (warp < 8) {
        uint32_t wreg[36 - NS][4];
        {
            const int lane = lane_o;
            const uint32_t a = w_addr(sbase, warp, lane);
            const uint64_t da = smem_desc(sbase + SM_WS + (warp >> 2) * 8192, 1024, 1024) | (1ull << 62);
            float acc[32];
#pragma unroll
            for (int i = 0; i < 32; i++) acc[i] = 0.f;
#pragma unroll 1
            for (int b = 0; b < 9; b++) {
                if (b == 0) TSQ(0);
                mbar_wait(sbase + B_W + 8 * b, 0);
                TSQ(1 + b);
                if (b == 8) TS3C(2);
                const uint64_t db = smem_desc(sbase + x01_off(b), 16, 1024) | (1ull << 62);
                wg_fence();
#pragma unroll
                for (int k = 0; k < 4; k++) wgmma_n64_ss(acc, da + (uint64_t)(b * 1024 + k * 128), db + (uint64_t)(k * 2));
                wg_commit();
                if (b == 5) {
#pragma unroll
                    for (int ks = NS; ks < 24; ks++) ldsm_x4_t(wreg[ks - NS], a + (ks >> 2) * 16384 + (ks & 3) * 2048);
                }
            }
#pragma unroll
            for (int ks = 24; ks < 32; ks++) ldsm_x4_t(wreg[ks - NS], a + (ks >> 2) * 16384 + (ks & 3) * 2048);
            wg_wait0();
            named_bar(9, 384);
            const uint32_t off = sbase + SM_T + (DH + warp * 16 + (lane & 15)) * 16 + (lane >> 4) * (DH * 16);
#pragma unroll
            for (int i = 0; i < 4; i++)
                stsm_x4(off + (i >> 1) * TBUF + (i & 1) * (2 * DH * 16), pack_bf16(acc[8 * i], acc[8 * i + 1]), pack_bf16(acc[8 * i + 2], acc[8 * i + 3]),
                        pack_bf16(acc[8 * i + 4], acc[8 * i + 5]), pack_bf16(acc[8 * i + 6], acc[8 * i + 7]));
#pragma unroll
            for (int ks = 32; ks < 36; ks++) ldsm_x4_t(wreg[ks - NS], a + (ks >> 2) * 16384 + (ks & 3) * 2048);
            if (role == 2) fence_async();
            bar_arrive(8, 384);
            named_bar(7, 256);
            asm volatile("barrier.cluster.arrive.relaxed.aligned;" ::: "memory");
        }
        TS3C(3);
        auto xproj1 = [&](float (&acc)[16], int j) {
            const uint32_t dlo = __shfl_sync(0xffffffffu, (uint32_t)smem_desc(sbase + SM_X + (j % 3) * XBUF, 16, 1024), 0);
            wg_fence();
#pragma unroll
            for (int ks = NS; ks < NS + NC1; ks++)
                wgmma_n32(acc, wreg[ks - NS], ((uint64_t)0x40000040u << 32) | (uint64_t)(dlo + (uint32_t)((ks >> 2) * 256 + (ks & 3) * 2)), ks > NS);
            wg_commit();
            wg_wait0();
        };
        auto xproj2 = [&](float (&acc)[16], int j) {
            int lane = lane_o;
            asm volatile("" : "+r"(lane));
            const uint32_t dlo = __shfl_sync(0xffffffffu, (uint32_t)smem_desc(sbase + SM_X + (j % 3) * XBUF, 16, 1024), 0);
            const uint64_t da = smem_desc(sbase + SM_WS + (warp >> 2) * 8192, 1024, 1024) | (1ull << 62);
            wg_fence();
#pragma unroll
            for (int ks = 0; ks < NS; ks++)
                wgmma_n32_ss(acc, da + (uint64_t)((ks >> 2) * 1024 + (ks & 3) * 128), ((uint64_t)0x40000040u << 32) | (uint64_t)(dlo + (uint32_t)((ks >> 2) * 256 + (ks & 3) * 2)), NC1 > 0 || ks > 0);
#pragma unroll
            for (int ks = NS + NC1; ks < XK; ks++)
                wgmma_n32(acc, wreg[ks - NS], ((uint64_t)0x40000040u << 32) | (uint64_t)(dlo + (uint32_t)((ks >> 2) * 256 + (ks & 3) * 2)), 1);
            wg_commit();
            wg_wait0();
            const uint32_t off = sbase + SM_T + (j & 3) * TBUF + (DH + warp * 16 + (lane & 15)) * 16 + (lane >> 4) * (DH * 16);
            stsm_x4(off, pack_bf16(acc[0], acc[1]), pack_bf16(acc[2], acc[3]), pack_bf16(acc[4], acc[5]), pack_bf16(acc[6], acc[7]));
            stsm_x4(off + 2 * DH * 16, pack_bf16(acc[8], acc[9]), pack_bf16(acc[10], acc[11]), pack_bf16(acc[12], acc[13]), pack_bf16(acc[14], acc[15]));
        };
        uint32_t ws[NS][4];
#pragma unroll
        for (int ks = NS - NP; ks < NS; ks++) ldsm_x4_t(ws[ks], w_addr(sbase, warp, lane_o) + (ks >> 2) * 16384 + (ks & 3) * 2048);
        asm volatile("barrier.cluster.wait.aligned;" ::: "memory");
        if (lane_o == 0 && warp < 2 && role == 2) vx_copy(sbase, 0, warp);
        __syncwarp();
        TS3C(4);
        for (int s = 0; s < NSEG; s++) {
            int lane = lane_o;
            asm volatile("" : "+r"(lane));
            uint32_t v0, v1;
            {
#pragma unroll
                for (int ks = 0; ks < NS - NP; ks++) ldsm_x4_t(ws[ks], w_addr(sbase, warp, lane) + (ks >> 2) * 16384 + (ks & 3) * 2048);
                FS(0, ws[0][0]);
                named_bar(1, 384);
                float acc[2][4], minv;
                const uint32_t b_base = sbase + SM_M + lane * 16;
                uint32_t b[3][4];
#pragma unroll
                for (int kk = 0; kk < 3; kk++) ldsm_x4_t(b[kk], b_base + kk * 512);
                FS(1, b[0][0]);
#pragma unroll
                for (int kk = 0; kk < 18; kk++) {
                    if (kk == 0) {
                        mma_z(acc[0], ws[0], b[0][0], b[0][1]);
                        mma_z(acc[1], ws[1], b[0][2], b[0][3]);
                    } else if (2 * kk < NS) {
                        mma_bf16(acc[0], ws[2 * kk < NS ? 2 * kk : 0], b[kk % 3][0], b[kk % 3][1]);
                        mma_bf16(acc[1], ws[2 * kk < NS ? 2 * kk + 1 : 0], b[kk % 3][2], b[kk % 3][3]);
                    } else {
                        mma_bf16(acc[0], wreg[2 * kk >= NS ? 2 * kk - NS : 0], b[kk % 3][0], b[kk % 3][1]);
                        mma_bf16(acc[1], wreg[2 * kk >= NS ? 2 * kk - NS + 1 : 0], b[kk % 3][2], b[kk % 3][3]);
                    }
                    if (kk + 3 < 18) ldsm_x4_t(b[kk % 3], b_base + (kk + 3) * 512);
                    if (kk + 3 == 17) {
                        asm volatile("ld.shared.f32 %0, [%1];" : "=f"(minv) : "r"(sbase + SM_SC + 8) : "memory");
                    }
                }
                v0 = pack_bf16((acc[0][0] + acc[1][0]) * minv, (acc[0][1] + acc[1][1]) * minv);
                v1 = pack_bf16((acc[0][2] + acc[1][2]) * minv, (acc[0][3] + acc[1][3]) * minv);
                FS(2, v0);
            }
            const uint32_t tb = sbase + SM_T + (s & 3) * TBUF;
            if (role == 2 && s + 1 < NSEG) {
                const uint32_t fo = (uint32_t)(warp * 256 + lane * 8);
                const uint32_t rb0 = mapa(sbase, 0), rb1 = mapa(sbase, 1);
                st_async64(rb0 + SM_VM + fo, v0, v1, rb0 + B_SB + 8 * (s & 1));
                st_async64(rb1 + SM_VM + fo, v0, v1, rb1 + B_SB + 8 * (s & 1));
                asm volatile("st.shared.v2.u32 [%0], {%1,%2};" :: "r"(sbase + SM_VM + fo), "r"(v0), "r"(v1) : "memory");
            }
            asm volatile("stmatrix.sync.aligned.m8n8.x2.shared.b16 [%0], {%1,%2};" :: "r"(tb + warp * 256 + (lane & 15) * 16), "r"(v0), "r"(v1) : "memory");
            if (s + 1 == NSEG) {
                if (role != 2 && warp >= 4) {
                    const uint32_t dk = mapa(sbase + SM_X + XBUF + (2 + role) * 9216 + (warp - 4) * 256 + lane * 4, 2), mb = mapa(sbase + B_VX + 8, 2);
                    st_async32(dk, v0, mb);
                    st_async32(dk + 128, v1, mb);
                }
            } else {
                if (warp == 7 && role != 2) {
                    const uint32_t d0 = sbase + SM_S + role * 1280 + lane * 8, bo = sbase + B_SB + 8 * (s & 1);
                    const uint32_t d1 = mapa(d0, role ^ 1), m1 = mapa(bo, role ^ 1), d2 = mapa(d0, 2), m2 = mapa(bo, 2);
                    const uint32_t ka = tb + (64 + (lane & 7) + ((lane >> 3) & 1) * 16 + (lane >> 4) * 8) * 16;
                    uint32_t kf[2][4];
                    named_bar(2, 384);
#pragma unroll
                    for (int k2 = 0; k2 < 2; k2++) ldsm_x4_t(kf[k2], ka + k2 * 512);
                    score_group(tb + lane * 16, kf, d0, d1, m1, d2, m2);
                    bar_arrive(6, 160);
                } else bar_arrive(2, 384);
            }
            FS(11, 0);
            const bool prompt = s >= NSEG - PROMPT;
            if (s + 2 < NSEG) {
                if (warp == 6) mbar_wait(sbase + B_XT + 8 * ((s + 2) % 3), (uint32_t)((s + 2) / 3) & 1u);
                if (role == 2 || prompt) fence_async();
                if (role != 2) named_bar(5, 384); else named_bar(7, 256);
                if (prompt) {
                    if (tid == 64) store_tile(s, h, role, tb);
                    __syncwarp();
                }
                float xacc[16];
                xproj1(xacc, s + 2);
                FS(9, __float_as_uint(xacc[0]));
                if (tid == 0 && role == 2) vx_copy(sbase, s + 1, 0);
                if (prompt && tid == 64) {
                    asm volatile("cp.async.bulk.wait_group 0;" ::: "memory");
                    asm volatile("red.relaxed.gpu.global.add.u32 [%0], 1;" :: "l"(&g_flag[s * NH + h]) : "memory");
                }
                __syncwarp();
                if (role != 2) fence_async();
                FS(14, 0);
                named_bar(4, 384);
                xproj2(xacc, s + 2);
                FS(7, __float_as_uint(xacc[0]));
            } else if (role != 2 && s + 2 == NSEG) {
                const uint32_t t0 = clock32();
                const uint32_t dq = mapa(sbase + SM_X + XBUF + role * 9216, 2), mb = mapa(sbase + B_VX, 2);
                fence_async();
                named_bar(7, 256);
                if (tid == 64) { while (clock32() - t0 < TL_DELAY) {} bulk_s2s(dq, tb + 1024, 9216, mb); }
                __syncwarp();
                named_bar(4, 384);
                if (tid == 64) { const uint32_t t1 = clock32(); while (clock32() - t1 < VX_DELAY) {} bulk_s2s(dq + 2 * 9216 + 1024, sbase + SM_T + ((s + 1) & 3) * TBUF + 2048, 8192, mb + 8); }
                __syncwarp();
            }
        }
        if (role == 2) named_bar(7, 256);
    } else {
        float* scs = reinterpret_cast<float*>(smem_raw + SM_SC);
        uint32_t wo[3][8][4];
        uint32_t mx2 = 0u;
        {
            const int pt = tid - 256, lane = lane_o, wq = warp - 8, g = lane >> 2, tq = lane & 3;
            TSQ(7);
            mbar_wait(sbase + B_E, 0);
            TSQ(8);
#pragma unroll
            for (int t = 0; t < 3; t++) {
                const int T = 3 * wq + t;
                const uint32_t a = sbase + SM_X01 + (T >> 2) * 16384 + ((lane >> 4) * 8 + (lane & 7)) * 128 + ((((T & 3) * 2 + ((lane >> 3) & 1)) ^ (lane & 7)) << 4);
#pragma unroll
                for (int kk = 0; kk < 8; kk++) ldsm_x4_t(wo[t][kk], a + ((2 * wq + kk) & 7) * 2048);
            }
            uint32_t m = 0u;
#pragma unroll 6
            for (int j = 0; j < 18; j++) {
                const uint32_t v = lds32(sbase + SM_E + XBUF + (g * DM + wq * 144 + 8 * j) * 2 + tq * 4);
                asm volatile("stmatrix.sync.aligned.m8n8.x1.trans.shared.b16 [%0], {%1};" :: "r"(sbase + SM_M + (wq * 144 + 8 * j + (lane & 7)) * 16), "r"(v) : "memory");
                mx2 = __vmaxu2(mx2, v & 0x7fff7fffu);
                const uint4 xv = *reinterpret_cast<const uint4*>(smem_raw + SM_E + (pt + 128 * j) * 16);
                m = max_abs2(max_abs2(m, max_abs2(xv.x, xv.y)), max_abs2(xv.z, xv.w));
            }
            m = __reduce_max_sync(0xffffffffu, max((m << 16) & 0x7fff0000u, m & 0x7fff0000u));
            if (lane == 0) reinterpret_cast<uint32_t*>(scs)[260 + wq] = m;
            named_bar(3, 128);
            if (pt == 64) {
                fence_async();
#pragma unroll 1
                for (int i = 3; i < 9; i++) { stage_x(i); if (i >= 6) stage_w(i); }
            }
            if (pt == 96 && cta < NSEG) {
                const uint4 q = *reinterpret_cast<const uint4*>(scs + 260);
                asm volatile("st.volatile.global.u32 [%0], %1;" :: "l"(&g_rx[cta]), "r"(max(max(q.x, q.y), max(q.z, q.w)) | 1u) : "memory");
            }
            __syncwarp();
            bar_arrive(1, 384);
            TSQ(9);
            float c0 = 0.f;
#pragma unroll
            for (int t = 0; t < 3; t++) {
                float n[4][4];
#pragma unroll
                for (int i = 0; i < 4; i++) { n[i][0] = n[i][1] = n[i][2] = n[i][3] = 0.f; }
#pragma unroll
                for (int kk = 0; kk < 8; kk++)
#pragma unroll
                    for (int i = 0; i < 4; i++) mma_k8(n[i], wo[t][kk][i & 2], wo[t][kk][(i & 2) + 1], wo[t][kk][i]);
                if ((g >> 1) == tq) c0 = fmaxf(c0, (g & 1) ? fmaxf(n[0][1] + n[2][1], n[1][3] + n[3][3]) : fmaxf(n[0][0] + n[2][0], n[1][2] + n[3][2]));
            }
            c0 = __uint_as_float(__reduce_max_sync(0xffffffffu, __float_as_uint(c0)));
            m = 0u;
#pragma unroll 1
            for (int b = 0; b < 9; b++) {
                if (role == 2) {
                    mbar_wait(sbase + B_W + 8 * b, 0);
#pragma unroll
                    for (int j = 0; j < 8; j++) {
                        const uint4 xv = *reinterpret_cast<const uint4*>(smem_raw + SM_WS + b * 16384 + (pt + 128 * j) * 16);
                        m = max_abs2(max_abs2(m, max_abs2(xv.x, xv.y)), max_abs2(xv.z, xv.w));
                    }
                }
                if (b == 3) bar_arrive(9, 384);
            }
            asm volatile("barrier.cluster.arrive.relaxed.aligned;" ::: "memory");
            m = __reduce_max_sync(0xffffffffu, max((m << 16) & 0x7fff0000u, m & 0x7fff0000u));
            if (lane == 0) { scs[256 + wq] = c0; reinterpret_cast<uint32_t*>(scs)[8 + wq] = m; }
            TSQ(1);
            named_bar(3, 128);
            if (pt == 0) {
                const float a = fmaxf(fmaxf(scs[256], scs[257]), fmaxf(scs[258], scs[259]));
                const float b = fmaxf(fmaxf(scs[8], scs[9]), fmaxf(scs[10], scs[11]));
                st_vol_u2(&g_norm[cta], make_uint2(__float_as_uint(a) | 1u, __float_as_uint(b) | 1u));
            }
            __syncwarp();
            named_bar(8, 384);
            TSQ(2);
            if (pt == 32) {
                fence_async();
                for (int i = 0; i < 3; i++) tma_x(sbase + SM_X + 2 * XBUF, &tmx, 2, i, sbase + B_XT + 16);
            }
            __syncwarp();
            asm volatile("barrier.cluster.wait.aligned;" ::: "memory");
        }
        const int wq = warp - 8, lane = lane_o;
        const uint32_t l8 = __shfl_sync(0xffffffffu, sbase + lane * 8, lane), l16 = __shfl_sync(0xffffffffu, sbase + lane * 16, lane);
        const uint32_t goff = __shfl_sync(0xffffffffu, (lane >> 3) * 1024 + (lane & 7) * 16, lane);
        float minv = 1.f;
        const uint32_t ka = sbase + SM_T + ((wq + 1) * DH + 64 + (lane & 7) + ((lane >> 3) & 1) * 16 + (lane >> 4) * 8) * 16;
        uint32_t kf[2][4];
#pragma unroll
        for (int k2 = 0; k2 < 2; k2++) ldsm_x4_t(kf[k2], ka + k2 * 512);
        int b3 = 0;
        for (int s = 0; s + 1 < NSEG; s++) {
            const int n3 = b3 == 2 ? 0 : b3 + 1;
            if (cta == 0 && tid == 256) {
                const uint32_t t = gtime32();
                st_vol_u2(&g_tick, make_uint2(t, reinterpret_cast<uint32_t*>(scs)[3]));
                reinterpret_cast<uint32_t*>(scs)[3] = t;
            }
            if (lane == 0) {
                if (wq == 1 && s + 3 < NSEG) tma_x_mc(sbase + SM_X + b3 * XBUF, &tmx, s + 3, role, sbase + B_XT + 8 * b3);
                if (wq == 3 && s > 0 && s <= NSEG - PROMPT + 1) {
                    if (s <= NSEG - PROMPT) store_tile(s - 1, h, role, sbase + SM_T + ((s - 1) & 3) * TBUF);
                    else asm volatile("cp.async.bulk.commit_group;" ::: "memory");
                    if (s > 1) {
                        asm volatile("cp.async.bulk.wait_group 1;" ::: "memory");
                        asm volatile("red.relaxed.gpu.global.add.u32 [%0], 1;" :: "l"(&g_flag[(s - 2) * NH + h]) : "memory");
                    }
                }
            }
            __syncwarp();
            if (wq == 2 && s > 1 && lane < 8) {
                *reinterpret_cast<uint4*>(g_acc + n3 * 128 + cta * 1024 + lane * 16) = make_uint4(0u, 0u, 0u, 0u);
            }
            if (s == 1 && tid == 383) {
                st_vol_u2(&g_norm[cta], make_uint2(0u, 0u));
                if (cta < NSEG) asm volatile("st.volatile.global.u32 [%0], %1;" :: "l"(&g_rx[cta]), "r"(0u) : "memory");
            }
            {
                const uint32_t mw = __reduce_max_sync(0xffffffffu, max(mx2 << 16, mx2 & 0xffff0000u));
                if (lane == 0) scs[4 + wq] = __uint_as_float(mw);
            }
            const uint32_t to = SM_T + (s & 3) * TBUF;
            const uint32_t ph = (uint32_t)(s >> 1) & 1u;
            if (role != 2) {
                const uint32_t so = SM_S + role * 1280 + (wq + 1) * 256, bo = sbase + B_SB + 8 * (s & 1);
                const uint32_t d1 = mapa(l8 + so, role ^ 1), m1 = mapa(bo, role ^ 1), d2 = mapa(l8 + so, 2), m2 = mapa(bo, 2);
                mbar_wait(sbase + B_VX + 8 * (s & 1), ph);
                FS(1, 0);
                named_bar(2, 384);
                score_group(l16 + to, kf, l8 + so, d1, m1, d2, m2);
                if (s + 2 < NSEG) bar_arrive(5, 384);
            } else named_bar(2, 384);
            if (s == 0) {
                TSQ(3);
                if (wq == 1) norms_gather(lane, scs);
                named_bar(3, 128);
                TSQ(4);
            }
            const float4 m4 = *reinterpret_cast<const float4*>(scs + 4);
            const float c24 = scs[1], xb = scs[16 + s];
            unsigned char* dst = (g_acc + b3 * 128 + (role * 32 + wq * 8) * 1024) + goff;
            uint32_t vf[2][2][4], vm[2][2];
            {
                const uint32_t va = sbase + (role == 2 ? to + DH * 16 : SM_VX + (s & 1) * 8192) + (lane >> 4) * 2048 + (32 * wq + (lane & 15)) * 16;
#pragma unroll
                for (int i = 0; i < 4; i++) ldsm_x4(vf[i >> 1][i & 1], va + (i >> 1) * 256 + (i & 1) * 4096);
            }
            float scale;
            {
                const float bound = fmaxf(fmaxf(fmaxf(m4.x, m4.y), fmaxf(m4.z, m4.w)) * minv, xb) * c24;
                int e = 141 - (int)((__float_as_uint(bound) >> 23) & 255u);
                e = e > 100 ? 100 : e;
                scale = __uint_as_float((uint32_t)(127 + e) << 23);
                minv = __uint_as_float((uint32_t)(127 - e) << 23);
            }
            FS(7, vf[1][1][0]);
            if (role != 2) named_bar(6, 160);
            if (role == 2) mbar_wait(sbase + B_SB + 8 * (s & 1), ph);
            float sv[5][2];
#pragma unroll
            for (int j = 0; j < 5; j++) lds64f(sv[j][0], sv[j][1], l8 + SM_S + (role & 1) * 1280 + j * 256);
            if (role != 2) mbar_wait(sbase + B_SB + 8 * (s & 1), ph);
            FS(6, 0);
            uint32_t p[5];
            {
                float sr[5][2];
#pragma unroll
                for (int j = 0; j < 5; j++) lds64f(sr[j][0], sr[j][1], l8 + SM_S + ((role & 1) ^ 1) * 1280 + j * 256);
                lds64(vm[0][0], vm[0][1], l8 + SM_VM + wq * 512);
                lds64(vm[1][0], vm[1][1], l8 + SM_VM + wq * 512 + 256);
#pragma unroll
                for (int j = 0; j < 5; j++) {
                    sv[j][0] += sr[j][0]; sv[j][1] += sr[j][1];
                }
                float mx = fmaxf(fmaxf(fmaxf(sv[0][0], sv[0][1]), fmaxf(sv[1][0], sv[1][1])), fmaxf(fmaxf(sv[2][0], sv[2][1]), fmaxf(sv[3][0], sv[3][1])));
                mx = fmaxf(mx, fmaxf(sv[4][0], sv[4][1]));
                {
                    const float m1 = __shfl_xor_sync(0xffffffffu, mx, 1), m2 = __shfl_xor_sync(0xffffffffu, mx, 2), m3 = __shfl_xor_sync(0xffffffffu, mx, 3);
                    mx = fmaxf(fmaxf(mx, m1), fmaxf(m2, m3));
                }
                constexpr float EC = MIMIC ? 1.4426950408889634f : (float)(1.4426950408889634 * 0.08838834764831845);
#pragma unroll
                for (int jj = 0; jj < 5; jj++) {
                    const int j = (jj + 1) % 5;
                    asm("ex2.approx.ftz.f32 %0, %1;" : "=f"(sv[j][0]) : "f"((sv[j][0] - mx) * EC));
                    asm("ex2.approx.ftz.f32 %0, %1;" : "=f"(sv[j][1]) : "f"((sv[j][1] - mx) * EC));
                    p[j] = pack_bf16(sv[j][0], sv[j][1]);
                }
            }
            FS(0, p[0]);
            uint32_t b[4][4];
            float zs[4];
            {
                float o0[2][4], o1[2][4];
                mma_z(o0[0], vf[0][0], p[1], p[2]);
                mma_z(o0[1], vf[1][0], p[1], p[2]);
                mma_z(o1[0], vf[0][1], p[3], p[4]);
                mma_z(o1[1], vf[1][1], p[3], p[4]);
                mma_k8(o0[0], vm[0][0], vm[0][1], p[0]);
                mma_k8(o0[1], vm[1][0], vm[1][1], p[0]);
                const uint32_t one4[4] = {0x3f803f80u, 0x3f803f80u, 0x3f803f80u, 0x3f803f80u};
                mma_z(zs, one4, p[1], p[2]);
                mma_bf16(zs, one4, p[3], p[4]);
                mma_k8(zs, one4[0], one4[1], p[0]);
                uint32_t ow[4];
#pragma unroll
                for (int m = 0; m < 2; m++) {
                    ow[2 * m] = pack_bf16(o0[m][0] + o1[m][0], o0[m][1] + o1[m][1]);
                    ow[2 * m + 1] = pack_bf16(o0[m][2] + o1[m][2], o0[m][3] + o1[m][3]);
                }
                stsm_x4(l16 + SM_O + wq * 512, ow[0], ow[1], ow[2], ow[3]);
                FS(2, 0);
#pragma unroll
                for (int i = 0; i < 4; i++) b[0][i] = movm(ow[i]);
            }
            float acc[3][2][4];
            named_bar(3, 128);
#pragma unroll
            for (int i = 1; i < 4; i++) ldsm_x4_t(b[i], l16 + SM_O + ((wq + i) & 3) * 512);
#pragma unroll
            for (int t = 0; t < 3; t++) { mma_z(acc[t][0], wo[t][0], b[0][0], b[0][1]); mma_z(acc[t][1], wo[t][1], b[0][2], b[0][3]); }
            float z0, z1;
            asm volatile("rcp.approx.ftz.f32 %0, %1;" : "=f"(z0) : "f"(zs[0]));
            asm volatile("rcp.approx.ftz.f32 %0, %1;" : "=f"(z1) : "f"(zs[1]));
            z0 *= scale; z1 *= scale;
            FS(3, b[1][0]);
#pragma unroll
            for (int i = 1; i < 4; i++)
#pragma unroll
                for (int t = 0; t < 3; t++) { mma_bf16(acc[t][0], wo[t][2 * i], b[i][0], b[i][1]); mma_bf16(acc[t][1], wo[t][2 * i + 1], b[i][2], b[i][3]); }
            {
                uint32_t w[6];
#pragma unroll
                for (int t = 0; t < 3; t++) {
                    w[2 * t] = pack_f16((acc[t][0][0] + acc[t][1][0]) * z0, (acc[t][0][1] + acc[t][1][1]) * z1);
                    w[2 * t + 1] = pack_f16((acc[t][0][2] + acc[t][1][2]) * z0, (acc[t][0][3] + acc[t][1][3]) * z1);
                }
                FS(8, w[5]);
                asm volatile("red.relaxed.gpu.global.add.noftz.v4.f16x2 [%0], {%1,%2,%3,%4};" :: "l"(dst), "r"(w[0]), "r"(w[1]), "r"(w[2]), "r"(0x3c00u) : "memory");
                asm volatile("red.relaxed.gpu.global.add.noftz.v4.f16x2 [%0], {%1,%2,%3,%4};" :: "l"(dst + 4096), "r"(w[3]), "r"(w[4]), "r"(w[5]), "r"(0x3c00u) : "memory");
            }
            FS(9, 0);
            if (s == 0) TSQ(5);
            const uint32_t t0 = clock32();
            if (s + 2 < NSEG || role != 2) bar_arrive(4, 384);
            if (lane == 0) {
                if (wq == 0) scs[2] = minv;
                if (wq == 2 && role == 2 && s + 2 < NSEG) { while (clock32() - t0 < VX_DELAY) {} vx_copy(sbase, s + 1, 1); }
                if (s + 3 < NSEG) {
                    if (wq == 0) mbar_expect(sbase + B_SB + 8 * (s & 1), role == 2 ? 2560 : 1280 + 2048);
                    if (wq == 1) mbar_expect(sbase + B_XT + 8 * b3, XBUF);
                    if (wq == 3 && role != 2) mbar_expect(sbase + B_VX + 8 * (s & 1), 8192);
                }
            }
            __syncwarp();
#pragma unroll
            for (int k2 = 0; k2 < 2; k2++) ldsm_x4_t(kf[k2], ka + ((s + 1) & 3) * TBUF + k2 * 512);
            const uint4* src = reinterpret_cast<const uint4*>((g_acc + b3 * 128 + wq * 24576) + goff);
            mx2 = poll_mem(src, l16 + SM_M + wq * 2304, t0);
            if (s == 0) TSQ(6);
            b3 = n3;
        }
    }
    TS3C(1);
    if (role == 2 && warp >= 4) {
        const int sg = warp < 8, wq = warp & 3, lane = lane_o;
        const uint32_t qk = sbase + SM_X + XBUF + sg * (2 * 9216), ob = sbase + SM_X + 2 * XBUF + sg * 8192;
        TST(0);
        mbar_wait(sbase + B_VX + 8 * sg, 0);
        fence_async();
        TST(1);
        float sc[20];
        {
            const uint64_t da = smem_desc(qk + 1024, 128, 1024), db = smem_desc(qk, 128, 2048);
            wg_fence();
#pragma unroll
            for (int ks = 0; ks < 8; ks++) wgmma_n40_ss(sc, da + (uint64_t)((ks >> 2) * 576 + (ks & 3) * 16), db + (uint64_t)((ks >> 2) * 576 + (ks & 3) * 16), ks > 0);
            wg_commit();
            wg_wait0();
        }
        uint32_t pa[3][4];
        xrow_softmax(sc, pa, wq, lane);
        float o[2][32];
        const uint64_t dv = smem_desc(sbase + SM_T + ((NSEG - 2 + sg) & 3) * TBUF, 2048, 128);
        wg_fence();
#pragma unroll
        for (int hf = 0; hf < 2; hf++)
#pragma unroll
            for (int ks = 0; ks < 3; ks++) { if (ks == 0) wgmma_n64_z(o[hf], pa[0], dv + (uint64_t)(hf * 64)); else wgmma_n64(o[hf], pa[ks], dv + (uint64_t)(hf * 64 + ks * 256), 1); }
        wg_commit();
        wg_wait0();
#pragma unroll
        for (int hf = 0; hf < 2; hf++)
#pragma unroll
            for (int i = 0; i < 2; i++)
                stsm_x4(ob + hf * 4096 + wq * 1024 + i * 512 + lane * 16, pack_bf16(o[hf][16 * i], o[hf][16 * i + 1]), pack_bf16(o[hf][16 * i + 4], o[hf][16 * i + 5]),
                        pack_bf16(o[hf][16 * i + 8], o[hf][16 * i + 9]), pack_bf16(o[hf][16 * i + 12], o[hf][16 * i + 13]));
        fence_async();
        named_bar(11 + sg, 128);
        TST(2);
        if ((tid & 127) == 0) {
            unsigned char* dst = reinterpret_cast<unsigned char*>(g_ox) + ((size_t)((NSEG / 2 - 1) * NH + h)) * 16384 + sg * 4096;
            asm volatile("cp.async.bulk.global.shared::cta.bulk_group [%0], [%1], 4096;" :: "l"(dst), "r"(ob) : "memory");
            asm volatile("cp.async.bulk.global.shared::cta.bulk_group [%0], [%1], 4096;" :: "l"(dst + 8192), "r"(ob + 4096) : "memory");
            asm volatile("cp.async.bulk.commit_group;" ::: "memory");
            asm volatile("cp.async.bulk.wait_group 0;" ::: "memory");
            asm volatile("red.relaxed.gpu.global.add.u32 [%0], 1;" :: "l"(&g_prog[(NSEG / 2 - 1) * 8 + (h >> 2)]) : "memory");
        }
        TST(3);
    }
    __syncwarp();
    cluster_sync_all();
}

extern "C" void kernel_launch(void* const* d_in, const int* in_sizes, int n_in, void* d_out, int out_size) {
    const bf16* x = (const bf16*)d_in[0];
    const bf16* mem0 = (const bf16*)d_in[1];
    const bf16* Wq = (const bf16*)d_in[2];
    const bf16* Wk = (const bf16*)d_in[3];
    const bf16* Wv = (const bf16*)d_in[4];
    const bf16* Wo = (const bf16*)d_in[5];
    const bf16* logA = (const bf16*)d_in[8];
    const bf16* Aim = (const bf16*)d_in[9];
    const bf16* Cre = (const bf16*)d_in[10];
    const bf16* Cim = (const bf16*)d_in[11];
    const bf16* logdt = (const bf16*)d_in[12];
    const bf16* dskip = (const bf16*)d_in[13];
    const bf16* gw = (const bf16*)d_in[14];
    bf16* out = (bf16*)d_out;
    static bool attr_done = false;
    typedef CUresult (*EncFn)(CUtensorMap*, CUtensorMapDataType, cuuint32_t, void*, const cuuint64_t*, const cuuint64_t*, const cuuint32_t*,
                              const cuuint32_t*, CUtensorMapInterleave, CUtensorMapSwizzle, CUtensorMapL2promotion, CUtensorMapFloatOOBfill);
    static EncFn enc = nullptr;
    if (!attr_done) {
        void* fn = nullptr;
        cudaDriverEntryPointQueryResult qr;
        cudaGetDriverEntryPoint("cuTensorMapEncodeTiled", &fn, cudaEnableDefault, &qr);
        enc = (EncFn)fn;
        cudaFuncSetAttribute(k_chain, cudaFuncAttributeMaxDynamicSharedMemorySize, 232448);
        cudaFuncSetAttribute(k_side, cudaFuncAttributeMaxDynamicSharedMemorySize, SIDE_SMEM);
        attr_done = true;
    }
    CUtensorMap tmx;
    {
        const cuuint64_t dims[3] = {64, (cuuint64_t)S_LEN, 9};
        const cuuint64_t strides[2] = {(cuuint64_t)DM * 2, 128};
        const cuuint32_t box[3] = {64, (cuuint32_t)SEG, 3};
        const cuuint32_t es[3] = {1, 1, 1};
        enc(&tmx, CU_TENSOR_MAP_DATA_TYPE_BFLOAT16, 3, (void*)x, dims, strides, box, es, CU_TENSOR_MAP_INTERLEAVE_NONE,
            CU_TENSOR_MAP_SWIZZLE_128B, CU_TENSOR_MAP_L2_PROMOTION_L2_128B, CU_TENSOR_MAP_FLOAT_OOB_FILL_NONE);
    }
    CUtensorMap tmw[3];
    for (int i = 0; i < 3; i++) {
        const cuuint64_t dims[2] = {(cuuint64_t)HD, (cuuint64_t)DM};
        const cuuint64_t strides[1] = {(cuuint64_t)HD * 2};
        const cuuint32_t box[2] = {64, 64};
        const cuuint32_t es[2] = {1, 1};
        enc(&tmw[i], CU_TENSOR_MAP_DATA_TYPE_BFLOAT16, 2, (void*)(i == 0 ? Wq : (i == 1 ? Wk : Wv)), dims, strides, box, es, CU_TENSOR_MAP_INTERLEAVE_NONE,
            CU_TENSOR_MAP_SWIZZLE_128B, CU_TENSOR_MAP_L2_PROMOTION_L2_256B, CU_TENSOR_MAP_FLOAT_OOB_FILL_NONE);
    }
    CUtensorMap tmo;
    {
        const cuuint64_t dims[2] = {(cuuint64_t)DM, (cuuint64_t)HD};
        const cuuint64_t strides[1] = {(cuuint64_t)DM * 2};
        const cuuint32_t box[2] = {64, 128};
        const cuuint32_t es[2] = {1, 1};
        enc(&tmo, CU_TENSOR_MAP_DATA_TYPE_BFLOAT16, 2, (void*)Wo, dims, strides, box, es, CU_TENSOR_MAP_INTERLEAVE_NONE,
            CU_TENSOR_MAP_SWIZZLE_128B, CU_TENSOR_MAP_L2_PROMOTION_L2_128B, CU_TENSOR_MAP_FLOAT_OOB_FILL_NONE);
    }
    CUtensorMap tmx2;
    {
        const cuuint64_t dims[2] = {(cuuint64_t)DM, (cuuint64_t)S_LEN};
        const cuuint64_t strides[1] = {(cuuint64_t)DM * 2};
        const cuuint32_t box[2] = {64, 64};
        const cuuint32_t es[2] = {1, 1};
        enc(&tmx2, CU_TENSOR_MAP_DATA_TYPE_BFLOAT16, 2, (void*)x, dims, strides, box, es, CU_TENSOR_MAP_INTERLEAVE_NONE,
            CU_TENSOR_MAP_SWIZZLE_128B, CU_TENSOR_MAP_L2_PROMOTION_L2_128B, CU_TENSOR_MAP_FLOAT_OOB_FILL_NONE);
    }
    k_chain<<<NCTA, 384, 232448>>>(tmx, tmw[0], tmw[1], tmw[2], tmx2, tmo, mem0, x);
    {
        cudaLaunchConfig_t cfg = {};
        cfg.gridDim = dim3(SD_NCTA); cfg.blockDim = dim3(512); cfg.dynamicSmemBytes = SIDE_SMEM; cfg.stream = cudaStreamPerThread;
        cudaLaunchAttribute at[1];
        at[0].id = cudaLaunchAttributeProgrammaticStreamSerialization;
        at[0].val.programmaticStreamSerializationAllowed = 1;
        cfg.attrs = at; cfg.numAttrs = 1;
        cudaLaunchKernelEx(&cfg, k_side, tmo, x, logA, Aim, Cre, Cim, logdt, Wo, dskip, gw, out);
    }
}
```

```cpp
#include <cuda_runtime.h>
#include <cuda.h>
#include <cuda_bf16.h>
#include <stdint.h>

typedef __nv_bfloat16 bf16;
#define LDV4 "ld.volatile.global.v4.u32 {%0,%1,%2,%3}, [%4];"
#define STV4 "st.volatile.global.v4.u32 [%0], {%1,%2,%3,%4};"
#define STV2 "st.volatile.global.v2.u32 [%0], {%1,%2};"

constexpr int S_LEN = 2048, DM = 576, NH = 32, DH = 128, HD = 4096, MEMT = 8, SEG = 32, NSEG = 64, NST = 128;

__device__ __align__(128) bf16 g_gate[S_LEN];
constexpr int NCTA = NH * 3;
__device__ __align__(1024) unsigned char g_acc[96 * 1024];
__device__ __align__(128) uint2 g_norm[NCTA];
__device__ __align__(128) uint32_t g_rx[NSEG];
__device__ __align__(128) unsigned char g_qkv[NSEG][NH][3][10240];
__device__ __align__(128) bf16 g_ox[S_LEN * HD];
__device__ __align__(128) uint4 g_fp[8][36][6][128];
__device__ unsigned g_flag[NSEG * NH];
__device__ unsigned g_prog[NSEG / 2 * 8];
__device__ unsigned g_gcnt[64];
__device__ unsigned g_epoch;
__device__ __align__(128) uint2 g_tick;
__device__ __align__(16) bf16 g_y[DM * S_LEN];

#define TS3(slot) do {} while (0)
#define TS3P(slot) do {} while (0)
#define TSQ(slot) do {} while (0)
#define TS3W(slot) do {} while (0)
#define TSS(row, slot) do {} while (0)
#define TS3C(slot) do {} while (0)
#define TST(slot) do {} while (0)
#define TSG(i) do {} while (0)
#define FS(i, dep) do {} while (0)
__device__ __forceinline__ uint32_t smem_u32(const void* p) { return (uint32_t)__cvta_generic_to_shared(p); }
__device__ __forceinline__ float bf16r(float x) { return __bfloat162float(__float2bfloat16_rn(x)); }
__device__ __forceinline__ uint32_t pack_bf16(float lo, float hi) {
    __nv_bfloat162 v = __floats2bfloat162_rn(lo, hi);
    return *reinterpret_cast<uint32_t*>(&v);
}
__device__ __forceinline__ void ldsm_x4(uint32_t (&r)[4], uint32_t addr) {
    asm volatile("ldmatrix.sync.aligned.m8n8.x4.shared.b16 {%0,%1,%2,%3}, [%4];"
                 : "=r"(r[0]), "=r"(r[1]), "=r"(r[2]), "=r"(r[3]) : "r"(addr));
}
__device__ __forceinline__ void ldsm_x4_t(uint32_t (&r)[4], uint32_t addr) {
    asm volatile("ldmatrix.sync.aligned.m8n8.x4.trans.shared.b16 {%0,%1,%2,%3}, [%4];"
                 : "=r"(r[0]), "=r"(r[1]), "=r"(r[2]), "=r"(r[3]) : "r"(addr));
}
__device__ __forceinline__ void mma_bf16(float (&d)[4], const uint32_t (&a)[4], uint32_t b0, uint32_t b1) {
    asm volatile("mma.sync.aligned.m16n8k16.row.col.f32.bf16.bf16.f32 {%0,%1,%2,%3}, {%4,%5,%6,%7}, {%8,%9}, {%0,%1,%2,%3};"
                 : "+f"(d[0]), "+f"(d[1]), "+f"(d[2]), "+f"(d[3])
                 : "r"(a[0]), "r"(a[1]), "r"(a[2]), "r"(a[3]), "r"(b0), "r"(b1));
}
__device__ __forceinline__ uint2 ld_vol_u2(const uint2* p) {
    uint2 v; asm volatile("ld.volatile.global.v2.u32 {%0,%1}, [%2];" : "=r"(v.x), "=r"(v.y) : "l"(p) : "memory"); return v;
}
__device__ __forceinline__ void st_vol_u2(uint2* p, uint2 v) {
    asm volatile(STV2 :: "l"(p), "r"(v.x), "r"(v.y) : "memory");
}
__device__ __forceinline__ unsigned ld_acq(const unsigned* p) {
    unsigned v; asm volatile("ld.acquire.gpu.global.u32 %0, [%1];" : "=r"(v) : "l"(p) : "memory"); return v;
}
#define XK 36
#define NC1 7
#define NS 6
#define NP 4
#define X_OXSZ 16384
#define GATE_A 1220
#define GATE_B 430
#define GATE_P 1880u
#define STAGGER 0
#define GATE_ATT 3
#define RLX_SLEEP 300
#define VX_DELAY 100
#define EARLY4 0
#define SPEC_M 1
#define SPEC_H 1
#define C1_DELAY 0
#define C2_DELAY 0
#define SS_POS 2
#define TL_DELAY 600
#define POLL_DELAY 500
#define PROMPT 8
#define UNGATE 12
constexpr unsigned SPIN_LIMIT = 1u << 20;
constexpr int NATT = NSEG - 2;

constexpr int SD_CH = 16;
constexpr int SD_NCTA = DM / SD_CH;
constexpr int SD_USTR = 40 * 72;
constexpr int SD_KLEN = 2048 + 32;
constexpr int SD_WSTR = 2 * SD_KLEN * 2;
constexpr int SD_SMEM = SD_CH * SD_USTR * 2 + 8 * SD_WSTR;

__device__ __forceinline__ uint32_t lds32(uint32_t a) { uint32_t v; asm volatile("ld.shared.u32 %0, [%1];" : "=r"(v) : "r"(a)); return v; }
__device__ __forceinline__ void tap_tile(uint32_t (&t)[4], uint32_t a) { t[0] = lds32(a); t[1] = lds32(a - 16); t[2] = lds32(a + 16); t[3] = lds32(a); }
template <int NT0>
__device__ __forceinline__ void conv_step(float (&acc)[4][4][4], const uint32_t (&cur)[4][4], uint32_t (&prev)[4][4], uint32_t (&b)[4][2][4], uint32_t ka, uint32_t ua) {
#pragma unroll
    for (int kt = 3; kt >= 0; kt--) {
#pragma unroll
        for (int nt = NT0; nt < 4; nt++)
#pragma unroll
            for (int mt = 0; mt < 4; mt++) {
                if (mt < kt) mma_bf16(acc[mt][nt], prev[(mt - kt + 4) & 3], b[nt][kt >> 1][(kt & 1) * 2], b[nt][kt >> 1][(kt & 1) * 2 + 1]);
                else mma_bf16(acc[mt][nt], cur[(mt - kt) & 3], b[nt][kt >> 1][(kt & 1) * 2], b[nt][kt >> 1][(kt & 1) * 2 + 1]);
            }
        if (kt == 3) { tap_tile(prev[0], ka); tap_tile(prev[1], ka - 32); }
        if (kt == 2) tap_tile(prev[2], ka - 64);
        if (kt == 1) tap_tile(prev[3], ka - 96);
        if ((kt & 1) == 0) {
#pragma unroll
            for (int nt = NT0; nt < 4; nt++) ldsm_x4(b[nt][kt >> 1], ua + nt * 1152 + kt * 32);
        }
    }
}
template <int NT0>
__device__ __forceinline__ void conv_oct(float (&acc)[4][4][4], uint32_t (&X)[4][4], uint32_t (&Y)[4][4], uint32_t (&b)[4][2][4], uint32_t& ka, uint32_t& ua) {
#pragma unroll 1
    for (int i = 0; i < 4; i++) {
        conv_step<NT0>(acc, X, Y, b, ka - 128, ua - 144);
        conv_step<NT0>(acc, Y, X, b, ka - 256, ua - 288);
        ka -= 256; ua -= 288;
    }
}

__device__ __forceinline__ void named_bar(int id, int n) { asm volatile("bar.sync %0, %1;" :: "r"(id), "r"(n) : "memory"); }
__device__ __forceinline__ uint32_t pack_f16(float lo, float hi) {
    uint32_t r; asm("cvt.rn.f16x2.f32 %0, %1, %2;" : "=r"(r) : "f"(hi), "f"(lo)); return r;
}
__device__ __forceinline__ void cexp_t(float lr, float turns, float& re, float& im) {
    float m;
    asm("ex2.approx.ftz.f32 %0, %1;" : "=f"(m) : "f"(lr));
    const float a = (turns - rintf(turns)) * 6.283185307179586f;
    re = m * __cosf(a); im = m * __sinf(a);
}
__device__ __forceinline__ void csq(float& re, float& im) { const float r = re * re - im * im; im = 2.f * re * im; re = r; }
__device__ __forceinline__ void kb_state(const float* tp, float gf, uint32_t (&a)[4][2], uint32_t (&b)[5]) {
    const float4 p0 = *reinterpret_cast<const float4*>(tp), p1 = *reinterpret_cast<const float4*>(tp + 4);
    float wr, wi;
    cexp_t(p0.x * gf, p0.y * gf, wr, wi);
    float vr = wr * p1.x - wi * p1.y, vi = wr * p1.y + wi * p1.x;
#pragma unroll
    for (int c = 0; c < 4; c++) {
        a[c][0] = pack_f16(wr, wi); a[c][1] = pack_f16(vr, vi);
        csq(wr, wi);
        if (c < 3) csq(vr, vi);
    }
    b[0] = pack_f16(p0.z * wr - p0.w * wi, -p0.z * wi - p0.w * wr);
    float er = wr * p1.z - wi * p1.w, ei = wr * p1.w + wi * p1.z;
#pragma unroll
    for (int c = 0; c < 4; c++) {
        b[1 + c] = pack_f16(p0.z * er - p0.w * ei, -p0.z * ei - p0.w * er);
        if (c < 3) csq(er, ei);
    }
}
template <int C>
__device__ __forceinline__ void expand_taps(const float* kd, bf16* kr, int l0, int lane) {
    uint32_t w[4];
#pragma unroll
    for (int e = 0; e < 4; e++) {
        float v[2];
#pragma unroll
        for (int k = 0; k < 2; k++) {
            const int l = l0 + 8 * lane + 7 - 2 * e - k;
            const int idx = C == 0 ? l : 128 * C + ((l + (1 << (C > 0 ? C - 1 : 0)) - 1 + ((l >> C) & 1)) >> C);
            v[k] = kd[idx];
        }
        w[e] = pack_bf16(v[0], v[1]);
    }
    *reinterpret_cast<uint4*>(kr + 2040 - l0 - 8 * lane) = make_uint4(w[0], w[1], w[2], w[3]);
}

__device__ __forceinline__ uint32_t bf2_mul(uint32_t a, uint32_t b) { uint32_t r; asm("mul.rn.bf16x2 %0, %1, %2;" : "=r"(r) : "r"(a), "r"(b)); return r; }
__device__ __forceinline__ uint32_t bf2_add(uint32_t a, uint32_t b) { uint32_t r; asm("add.rn.bf16x2 %0, %1, %2;" : "=r"(r) : "r"(a), "r"(b)); return r; }
__device__ __forceinline__ uint32_t bf2_sub(uint32_t a, uint32_t b) { uint32_t r; asm("sub.rn.bf16x2 %0, %1, %2;" : "=r"(r) : "r"(a), "r"(b)); return r; }
__device__ __forceinline__ void wait_cnt(const unsigned* p, unsigned target) {
    unsigned it = 0;
    while ((int)(ld_acq(p) - target) < 0 && ++it < SPIN_LIMIT) __nanosleep(64);
}
__device__ __forceinline__ void s4d_phase(unsigned char* smem_raw, const bf16* __restrict__ x, const bf16* __restrict__ logA,
                                          const bf16* __restrict__ Aim, const bf16* __restrict__ Cre, const bf16* __restrict__ Cim,
                                          const bf16* __restrict__ logdt, const bf16* __restrict__ dskip, const bf16* __restrict__ wslice, unsigned ep) {
    bf16* u_all = reinterpret_cast<bf16*>(smem_raw);
    const int tid = threadIdx.x, warp = tid >> 5, lane = tid & 31;
    const int d0 = blockIdx.x * SD_CH;
    bf16* kr = u_all + SD_CH * SD_USTR + warp * (SD_WSTR / 2);
    float* tab = reinterpret_cast<float*>(kr + SD_KLEN);
    const int g = lane >> 2, tq = lane & 3;
    uint2 prm[4];
    float ldt;
    auto load_prm = [&](int d) {
        prm[0] = __ldg(reinterpret_cast<const uint2*>(logA + d * NST) + lane); prm[1] = __ldg(reinterpret_cast<const uint2*>(Aim + d * NST) + lane);
        prm[2] = __ldg(reinterpret_cast<const uint2*>(Cre + d * NST) + lane); prm[3] = __ldg(reinterpret_cast<const uint2*>(Cim + d * NST) + lane);
        ldt = __bfloat162float(logdt[d]);
    };
    load_prm(d0 + 2 * warp);
    for (int i = lane; i < 8 * 72 / 2; i += 32) {
        reinterpret_cast<uint32_t*>(u_all + (2 * warp) * SD_USTR)[i] = 0u;
        reinterpret_cast<uint32_t*>(u_all + (2 * warp + 1) * SD_USTR)[i] = 0u;
    }
    if (lane < 16) reinterpret_cast<uint32_t*>(kr + 2048)[lane] = 0u;
    TS3(20);
#pragma unroll 1
    for (int ch = 0; ch < 2; ch++) {
        const int d = d0 + 2 * warp + ch;
        bf16* us = u_all + (2 * warp + ch) * SD_USTR;
        float k2048 = 0.f, sinv;
        {
            const float dt = bf16r(expf(ldt));
            uint32_t cm = __vmaxu2(__vmaxu2(prm[2].x & 0x7fff7fffu, prm[2].y & 0x7fff7fffu), __vmaxu2(prm[3].x & 0x7fff7fffu, prm[3].y & 0x7fff7fffu));
            cm = __reduce_max_sync(0xffffffffu, max(cm << 16, cm & 0xffff0000u));
            int e = 134 - (int)(__float_as_uint(__uint_as_float(cm) * dt) >> 23);
            e = e > 100 ? 100 : (e < -100 ? -100 : e);
            const float s2 = __uint_as_float((uint32_t)(128 + e) << 23);
            sinv = __uint_as_float((uint32_t)(127 - e) << 23);
#pragma unroll
            for (int j = 0; j < 4; j++) {
                float q[4];
#pragma unroll
                for (int i = 0; i < 4; i++) { const uint32_t w = j < 2 ? prm[i].x : prm[i].y; q[i] = __uint_as_float((j & 1) ? w & 0xffff0000u : w << 16); }
                const float zl = -bf16r(expf(q[0])) * dt * 1.4426950408889634f;
                const float zt = q[1] * dt * 0.15915494309189535f;
                const float cr = s2 * (q[2] * dt), ci = s2 * (q[3] * dt);
                float ar, ai, br, bi, er, ei;
                cexp_t(zl * 8.f, zt * 8.f, ar, ai);
                cexp_t(zl * 128.f, zt * 128.f, br, bi);
                cexp_t(zl * 2048.f, zt * 2048.f, er, ei);
                k2048 += cr * er - ci * ei;
                *reinterpret_cast<float4*>(tab + (lane + 32 * j) * 8) = make_float4(zl, zt, cr, ci);
                *reinterpret_cast<float4*>(tab + (lane + 32 * j) * 8 + 4) = make_float4(ar, ai, br, bi);
            }
            if (ch == 0) load_prm(d + 1);
#pragma unroll
            for (int o = 16; o; o >>= 1) k2048 += __shfl_xor_sync(0xffffffffu, k2048, o);
        }
        __syncwarp();
        {
            float kc[5][4];
#pragma unroll
            for (int i = 0; i < 5; i++) { kc[i][0] = kc[i][1] = kc[i][2] = kc[i][3] = 0.f; }
            const float gf = (float)g;
#pragma unroll 2
            for (int ks = 0; ks < 16; ks++) {
                uint32_t a0[4][2], a1[4][2], b0[5], b1[5];
                kb_state(tab + (8 * ks + tq) * 8, gf, a0, b0);
                kb_state(tab + (8 * ks + 4 + tq) * 8, gf, a1, b1);
#pragma unroll
                for (int i = 0; i < 5; i++) {
                    const int c = i > 0 ? i - 1 : 0;
                    asm volatile("mma.sync.aligned.m16n8k16.row.col.f32.f16.f16.f32 {%0,%1,%2,%3}, {%4,%5,%6,%7}, {%8,%9}, {%0,%1,%2,%3};"
                                 : "+f"(kc[i][0]), "+f"(kc[i][1]), "+f"(kc[i][2]), "+f"(kc[i][3])
                                 : "r"(a0[c][0]), "r"(a0[c][1]), "r"(a1[c][0]), "r"(a1[c][1]), "r"(b0[i]), "r"(b1[i]));
                }
            }
            __syncwarp();
#pragma unroll
            for (int i = 0; i < 5; i++) {
                float* q = tab + 128 * i + 32 * tq + g;
                q[0] = kc[i][0] * sinv; q[16] = kc[i][1] * sinv; q[8] = kc[i][2] * sinv; q[24] = kc[i][3] * sinv;
            }
            if (lane == 0) tab[640] = k2048 * sinv;
            __syncwarp();
            expand_taps<0>(tab, kr, 0, lane);
            expand_taps<1>(tab, kr, 256, lane);
            expand_taps<2>(tab, kr, 512, lane);
            expand_taps<2>(tab, kr, 768, lane);
#pragma unroll
            for (int i = 0; i < 4; i++) expand_taps<3>(tab, kr, 1024 + 256 * i, lane);
            __syncwarp();
#pragma unroll
            for (int i = 0; i < 8; i++) {
                const uint4 v = *reinterpret_cast<const uint4*>(kr + (lane + 32 * i) * 8);
                const uint32_t n = *reinterpret_cast<const uint32_t*>(kr + (lane + 32 * i) * 8 + 8);
                *reinterpret_cast<uint4*>(tab + (lane + 32 * i) * 4) =
                    make_uint4(__byte_perm(v.x, v.y, 0x5432), __byte_perm(v.y, v.z, 0x5432), __byte_perm(v.z, v.w, 0x5432), __byte_perm(v.w, n, 0x5432));
            }
            if (lane < 16) tab[1024 + lane] = 0.f;
            __syncwarp();
        }
        TS3(21 + 2 * ch);
        if (ch == 0) { if (!STAGGER || warp < 4) named_bar(1, 384); }
        else {
#pragma unroll
            for (int i = 0; i < 4; i++) asm volatile("prefetch.global.L2 [%0];" :: "l"(wslice + (size_t)((tid & 127) + 128 * i) * DM));
        }
        float acc[4][4][4];
#pragma unroll
        for (int i = 0; i < 4; i++)
#pragma unroll
            for (int j = 0; j < 4; j++) { acc[i][j][0] = acc[i][j][1] = acc[i][j][2] = acc[i][j][3] = 0.f; }
        {
            uint32_t X[4][4], Y[4][4], b[4][2][4];
            const int j0 = 2047 - g + 2 * tq;
            uint32_t ka = smem_u32(kr) + ((j0 & 1) ? SD_KLEN * 2 : 0) + 2u * (uint32_t)(j0 & ~1);
            uint32_t ua = smem_u32(us) + (uint32_t)(((lane & 7) + 8) * 144 + (lane >> 3) * 16);
#pragma unroll
            for (int i = 0; i < 4; i++) {
                Y[i][0] = Y[i][1] = Y[i][2] = Y[i][3] = 0u;
                tap_tile(X[i], ka - 32 * i);
                ldsm_x4(b[i][0], ua + i * 1152); ldsm_x4(b[i][1], ua + i * 1152 + 64);
            }
            conv_oct<0>(acc, X, Y, b, ka, ua);
            conv_oct<1>(acc, X, Y, b, ka, ua);
            conv_oct<2>(acc, X, Y, b, ka, ua);
            conv_oct<3>(acc, X, Y, b, ka, ua);
        }
        __syncwarp();
        if (ch == 0) { if (lane == 0) wait_cnt(&g_gcnt[0], SD_NCTA * ep); __syncwarp(); }
        uint4 gv[8];
#pragma unroll
        for (int i = 0; i < 8; i++) gv[i] = __ldcg(reinterpret_cast<const uint4*>(g_gate) + lane + 32 * i);
        const uint32_t dd = __byte_perm(*reinterpret_cast<const unsigned short*>(dskip + d), 0u, 0x1010);
#pragma unroll
        for (int nt = 0; nt < 4; nt++)
#pragma unroll
            for (int m2 = 0; m2 < 2; m2++)
                asm volatile("stmatrix.sync.aligned.m8n8.x4.trans.shared.b16 [%0], {%1,%2,%3,%4};"
                             :: "r"(smem_u32(kr) + (uint32_t)((8 * nt + (lane & 7)) * 144 + m2 * 64 + (lane >> 3) * 16)),
                                "r"(pack_bf16(acc[2 * m2][nt][0], acc[2 * m2][nt][1])), "r"(pack_bf16(acc[2 * m2][nt][2], acc[2 * m2][nt][3])),
                                "r"(pack_bf16(acc[2 * m2 + 1][nt][0], acc[2 * m2 + 1][nt][1])), "r"(pack_bf16(acc[2 * m2 + 1][nt][2], acc[2 * m2 + 1][nt][3])) : "memory");
        __syncwarp();
#pragma unroll
        for (int i = 0; i < 8; i++) {
            const uint4 y = *reinterpret_cast<const uint4*>(kr + (4 * i + (lane >> 3)) * 72 + (lane & 7) * 8);
            const uint4 u = *reinterpret_cast<const uint4*>(us + (8 + 4 * i + (lane >> 3)) * 72 + (lane & 7) * 8);
            *reinterpret_cast<uint4*>(g_y + (size_t)d * S_LEN + (lane + 32 * i) * 8) =
                make_uint4(bf2_mul(bf2_sub(0x3f803f80u, gv[i].x), bf2_add(y.x, bf2_mul(u.x, dd))), bf2_mul(bf2_sub(0x3f803f80u, gv[i].y), bf2_add(y.y, bf2_mul(u.y, dd))),
                           bf2_mul(bf2_sub(0x3f803f80u, gv[i].z), bf2_add(y.z, bf2_mul(u.z, dd))), bf2_mul(bf2_sub(0x3f803f80u, gv[i].w), bf2_add(y.w, bf2_mul(u.w, dd))));
        }
        __syncwarp();
        if (lane < 16) reinterpret_cast<uint32_t*>(kr + 2048)[lane] = 0u;
        TS3(22 + 2 * ch);
    }
}
__device__ __forceinline__ void s4d_stage_u(unsigned char* smem_raw, const bf16* __restrict__ x, int pt) {
    bf16* u_all = reinterpret_cast<bf16*>(smem_raw);
    const int d0 = blockIdx.x * SD_CH;
#pragma unroll 1
    for (int b = 0; b < 4; b++) {
        uint4 v[8];
#pragma unroll
        for (int i = 0; i < 8; i++) {
            int c = pt + 128 * (8 * b + i);
            v[i] = *reinterpret_cast<const uint4*>(x + (size_t)(c >> 1) * DM + d0 + (c & 1) * 8);
        }
#pragma unroll
        for (int i = 0; i < 8; i++) {
            int c = pt + 128 * (8 * b + i), t = c >> 1;
            bf16* dst = u_all + (c & 1) * 8 * SD_USTR + (8 + (t >> 6)) * 72 + (t & 63);
            const bf16* pv = reinterpret_cast<const bf16*>(&v[i]);
#pragma unroll
            for (int ch = 0; ch < 8; ch++) dst[ch * SD_USTR] = pv[ch];
        }
    }
    asm volatile("bar.arrive 1, 384;" ::: "memory");
}

constexpr int WOC = DM / 3;
constexpr int TBUF = 5 * DH * 16;
constexpr int XBUF = SEG * DM * 2;
constexpr float ATT_SCALE = 0.08838834764831845f;
constexpr int SM_BAR = 0;
constexpr int B_SB = 0, B_VX = 16, B_XT = 32, B_W = 64, B_E = 136;
constexpr int SM_SC = 256;
constexpr int SM_F = SM_SC + 1280;
constexpr int SM_VM = SM_F + 2048;
constexpr int SM_S = SM_VM + 2048;
constexpr int SM_O = SM_S + 2560;
constexpr int SM_M = SM_O + 2048;
constexpr int SM_WS = 19456;
constexpr int SM_T = SM_WS + 32768;
constexpr int SM_VX = SM_T + 4 * TBUF;
constexpr int SM_X = SM_VX + 2 * 8192;
constexpr int SM_X01 = SM_WS + DM * DH * 2;
__host__ __device__ constexpr int x01_off(int b) { return b == 2 ? 2048 : SM_X01 + (b < 2 ? b + 6 : b - 3) * 8192; }
constexpr int SM_E = SM_WS + 6 * 16384;
constexpr int CH_SMEM = SM_X01 + 8 * 8192;
static_assert(SM_M + DM * 16 <= SM_WS && SM_X + 3 * XBUF <= CH_SMEM && CH_SMEM <= 232448 && SM_X % 1024 == 0 && SM_X01 % 1024 == 0 && SM_M >= 10240 && SM_F <= 2048, "smem");
__device__ __forceinline__ uint32_t clock32() { uint32_t t; asm volatile("mov.u32 %0, %%clock;" : "=r"(t) :: "memory"); return t; }

__device__ __forceinline__ uint32_t mapa(uint32_t a, uint32_t rank) {
    uint32_t r; asm volatile("mapa.shared::cluster.u32 %0, %1, %2;" : "=r"(r) : "r"(a), "r"(rank)); return r;
}
__device__ __forceinline__ void st_async32(uint32_t addr, uint32_t v, uint32_t mbar) {
    asm volatile("st.async.weak.shared::cluster.mbarrier::complete_tx::bytes.b32 [%0], %1, [%2];" :: "r"(addr), "r"(v), "r"(mbar) : "memory");
}
__device__ __forceinline__ void mbar_init(uint32_t bar, uint32_t cnt) {
    asm volatile("mbarrier.init.shared::cta.b64 [%0], %1;" :: "r"(bar), "r"(cnt) : "memory");
}
__device__ __forceinline__ void mbar_expect(uint32_t bar, uint32_t bytes) {
    asm volatile("mbarrier.arrive.expect_tx.shared::cta.b64 _, [%0], %1;" :: "r"(bar), "r"(bytes) : "memory");
}
__device__ __forceinline__ void mbar_wait(uint32_t bar, uint32_t parity) {
    unsigned it = 0;
    while (true) {
        uint32_t ok;
        asm volatile("{\n.reg .pred p;\nmbarrier.try_wait.parity.shared::cta.b64 p, [%1], %2;\nselp.u32 %0, 1, 0, p;\n}"
                     : "=r"(ok) : "r"(bar), "r"(parity) : "memory");
        if (ok || ++it >= SPIN_LIMIT) break;
    }
}
__device__ __forceinline__ void mbar_wait_long(uint32_t bar, uint32_t parity) {
    unsigned it = 0;
    while (true) {
        uint32_t ok;
        asm volatile("{\n.reg .pred p;\nmbarrier.try_wait.parity.shared::cta.b64 p, [%1], %2, %3;\nselp.u32 %0, 1, 0, p;\n}"
                     : "=r"(ok) : "r"(bar), "r"(parity), "r"(20000u) : "memory");
        if (ok || ++it >= SPIN_LIMIT) break;
    }
}
__device__ __forceinline__ uint64_t policy_evict_first() {
    uint64_t pol; asm volatile("createpolicy.fractional.L2::evict_first.b64 %0, 1.0;" : "=l"(pol)); return pol;
}
__device__ __forceinline__ void cluster_sync_all() {
    asm volatile("barrier.cluster.arrive.release.aligned;\nbarrier.cluster.wait.acquire.aligned;" ::: "memory");
}
__device__ __forceinline__ uint4 ld_vol_u4(const uint4* p) {
    uint4 v; asm volatile(LDV4 : "=r"(v.x), "=r"(v.y), "=r"(v.z), "=r"(v.w) : "l"(p) : "memory"); return v;
}
__device__ __forceinline__ void ld_vol_u4_p(uint4& v, const uint4* p, uint32_t pred) {
    asm volatile("{\n.reg .pred p;\nsetp.ne.u32 p, %5, 0;\n@p " LDV4 "\n}"
                 : "+r"(v.x), "+r"(v.y), "+r"(v.z), "+r"(v.w) : "l"(p), "r"(pred) : "memory");
}
__device__ __forceinline__ void st_vol_u4(uint4* p, uint4 v) {
    asm volatile(STV4 :: "l"(p), "r"(v.x), "r"(v.y), "r"(v.z), "r"(v.w) : "memory");
}
__device__ __forceinline__ void mma_bf16_r(float (&d)[4], uint32_t a0, uint32_t a1, uint32_t a2, uint32_t a3, uint32_t b0, uint32_t b1) {
    asm volatile("mma.sync.aligned.m16n8k16.row.col.f32.bf16.bf16.f32 {%0,%1,%2,%3}, {%4,%5,%6,%7}, {%8,%9}, {%0,%1,%2,%3};"
                 : "+f"(d[0]), "+f"(d[1]), "+f"(d[2]), "+f"(d[3])
                 : "r"(a0), "r"(a1), "r"(a2), "r"(a3), "r"(b0), "r"(b1));
}

__device__ __forceinline__ uint64_t smem_desc(uint32_t addr, uint32_t lbo, uint32_t sbo) {
    return (uint64_t)((addr & 0x3FFFF) >> 4) | ((uint64_t)(lbo >> 4) << 16) | ((uint64_t)(sbo >> 4) << 32);
}
__device__ __forceinline__ void wg_fence() { asm volatile("wgmma.fence.sync.aligned;" ::: "memory"); }
__device__ __forceinline__ void wg_commit() { asm volatile("wgmma.commit_group.sync.aligned;" ::: "memory"); }
__device__ __forceinline__ void wg_wait0() { asm volatile("wgmma.wait_group.sync.aligned 0;" ::: "memory"); }
__device__ __forceinline__ void fence_async() { asm volatile("fence.proxy.async.shared::cta;" ::: "memory"); }
__device__ __forceinline__ void wgmma_n32(float (&d)[16], const uint32_t (&a)[4], uint64_t bdesc, int scale_d) {
    asm volatile("{\n.reg .pred p;\nsetp.ne.b32 p, %21, 0;\n"
                 "wgmma.mma_async.sync.aligned.m64n32k16.f32.bf16.bf16 {%0,%1,%2,%3,%4,%5,%6,%7,%8,%9,%10,%11,%12,%13,%14,%15}, {%16,%17,%18,%19}, %20, p, 1, 1, 0;\n}"
                 : "+f"(d[0]), "+f"(d[1]), "+f"(d[2]), "+f"(d[3]), "+f"(d[4]), "+f"(d[5]), "+f"(d[6]), "+f"(d[7]),
                   "+f"(d[8]), "+f"(d[9]), "+f"(d[10]), "+f"(d[11]), "+f"(d[12]), "+f"(d[13]), "+f"(d[14]), "+f"(d[15])
                 : "r"(a[0]), "r"(a[1]), "r"(a[2]), "r"(a[3]), "l"(bdesc), "r"(scale_d));
}

__device__ __forceinline__ void wgmma_n32_ss(float (&d)[16], uint64_t adesc, uint64_t bdesc, int scale_d) {
    asm volatile("{\n.reg .pred p;\nsetp.ne.b32 p, %18, 0;\n"
                 "wgmma.mma_async.sync.aligned.m64n32k16.f32.bf16.bf16 {%0,%1,%2,%3,%4,%5,%6,%7,%8,%9,%10,%11,%12,%13,%14,%15}, %16, %17, p, 1, 1, 1, 0;\n}"
                 : "+f"(d[0]), "+f"(d[1]), "+f"(d[2]), "+f"(d[3]), "+f"(d[4]), "+f"(d[5]), "+f"(d[6]), "+f"(d[7]),
                   "+f"(d[8]), "+f"(d[9]), "+f"(d[10]), "+f"(d[11]), "+f"(d[12]), "+f"(d[13]), "+f"(d[14]), "+f"(d[15])
                 : "l"(adesc), "l"(bdesc), "r"(scale_d));
}

__device__ __forceinline__ void wgmma_n64_ss(float (&d)[32], uint64_t adesc, uint64_t bdesc) {
    asm volatile("{\n.reg .pred p;\nsetp.eq.b32 p, 0, 0;\n"
                 "wgmma.mma_async.sync.aligned.m64n64k16.f32.bf16.bf16 {%0,%1,%2,%3,%4,%5,%6,%7,%8,%9,%10,%11,%12,%13,%14,%15,%16,%17,%18,%19,%20,%21,%22,%23,"
                 "%24,%25,%26,%27,%28,%29,%30,%31}, %32, %33, p, 1, 1, 1, 0;\n}"
                 : "+f"(d[0]), "+f"(d[1]), "+f"(d[2]), "+f"(d[3]), "+f"(d[4]), "+f"(d[5]), "+f"(d[6]), "+f"(d[7]),
                   "+f"(d[8]), "+f"(d[9]), "+f"(d[10]), "+f"(d[11]), "+f"(d[12]), "+f"(d[13]), "+f"(d[14]), "+f"(d[15]),
                   "+f"(d[16]), "+f"(d[17]), "+f"(d[18]), "+f"(d[19]), "+f"(d[20]), "+f"(d[21]), "+f"(d[22]), "+f"(d[23]),
                   "+f"(d[24]), "+f"(d[25]), "+f"(d[26]), "+f"(d[27]), "+f"(d[28]), "+f"(d[29]), "+f"(d[30]), "+f"(d[31])
                 : "l"(adesc), "l"(bdesc));
}
__device__ __forceinline__ void tma_2d(uint32_t dst, const CUtensorMap* tm, int c0, int c1, uint32_t mbar) {
    asm volatile("cp.async.bulk.tensor.2d.shared::cluster.global.tile.mbarrier::complete_tx::bytes [%0], [%1, {%2, %3}], [%4];"
                 :: "r"(dst), "l"(tm), "r"(c0), "r"(c1), "r"(mbar) : "memory");
}

__device__ __forceinline__ void bulk_g2s(uint32_t dst, const void* src, uint32_t bytes, uint32_t mbar) {
    asm volatile("cp.async.bulk.shared::cluster.global.mbarrier::complete_tx::bytes [%0], [%1], %2, [%3];"
                 :: "r"(dst), "l"(src), "r"(bytes), "r"(mbar) : "memory");
}
__device__ __forceinline__ void bulk_g2s_h(uint32_t dst, const void* src, uint32_t bytes, uint32_t mbar, uint64_t pol) {
    asm volatile("cp.async.bulk.shared::cluster.global.mbarrier::complete_tx::bytes.L2::cache_hint [%0], [%1], %2, [%3], %4;"
                 :: "r"(dst), "l"(src), "r"(bytes), "r"(mbar), "l"(pol) : "memory");
}
__device__ __forceinline__ void tma_x(uint32_t dst, const CUtensorMap* tm, int seg, int part, uint32_t mbar) {
    asm volatile("cp.async.bulk.tensor.3d.shared::cluster.global.tile.mbarrier::complete_tx::bytes [%0], [%1, {%2, %3, %4}], [%5];"
                 :: "r"(dst + part * 12288), "l"(tm), "r"(0), "r"(seg * SEG), "r"(part * 3), "r"(mbar) : "memory");
}
__device__ __forceinline__ void tma_x_mc(uint32_t dst, const CUtensorMap* tm, int seg, int part, uint32_t mbar) {
    asm volatile("cp.async.bulk.tensor.3d.shared::cluster.global.tile.mbarrier::complete_tx::bytes.multicast::cluster [%0], [%1, {%2, %3, %4}], [%5], %6;"
                 :: "r"(dst + part * 12288), "l"(tm), "r"(0), "r"(seg * SEG), "r"(part * 3), "r"(mbar), "h"((unsigned short)7) : "memory");
}
__device__ __forceinline__ void bulk_s2s(uint32_t dst, uint32_t src, uint32_t bytes, uint32_t mbar) {
    asm volatile("cp.async.bulk.shared::cluster.shared::cta.mbarrier::complete_tx::bytes [%0], [%1], %2, [%3];"
                 :: "r"(dst), "r"(src), "r"(bytes), "r"(mbar) : "memory");
}
__device__ __forceinline__ void wgmma_n40_ss(float (&d)[20], uint64_t adesc, uint64_t bdesc, int scale_d) {
    asm volatile("{\n.reg .pred p;\nsetp.ne.b32 p, %22, 0;\n"
                 "wgmma.mma_async.sync.aligned.m64n40k16.f32.bf16.bf16 {%0,%1,%2,%3,%4,%5,%6,%7,%8,%9,%10,%11,%12,%13,%14,%15,%16,%17,%18,%19}, %20, %21, p, 1, 1, 1, 1;\n}"
                 : "+f"(d[0]), "+f"(d[1]), "+f"(d[2]), "+f"(d[3]), "+f"(d[4]), "+f"(d[5]), "+f"(d[6]), "+f"(d[7]),
                   "+f"(d[8]), "+f"(d[9]), "+f"(d[10]), "+f"(d[11]), "+f"(d[12]), "+f"(d[13]), "+f"(d[14]), "+f"(d[15]),
                   "+f"(d[16]), "+f"(d[17]), "+f"(d[18]), "+f"(d[19])
                 : "l"(adesc), "l"(bdesc), "r"(scale_d));
}
__device__ __forceinline__ void wgmma_n64_z(float (&d)[32], const uint32_t (&a)[4], uint64_t bdesc) {
    asm volatile("{\n.reg .pred p;\nsetp.ne.b32 p, 0, 0;\n"
                 "wgmma.mma_async.sync.aligned.m64n64k16.f32.bf16.bf16 {%0,%1,%2,%3,%4,%5,%6,%7,%8,%9,%10,%11,%12,%13,%14,%15,%16,%17,%18,%19,%20,%21,%22,%23,%24,%25,%26,%27,%28,%29,%30,%31}, {%32,%33,%34,%35}, %36, p, 1, 1, 0;\n}"
                 : "=f"(d[0]), "=f"(d[1]), "=f"(d[2]), "=f"(d[3]), "=f"(d[4]), "=f"(d[5]), "=f"(d[6]), "=f"(d[7]),
                   "=f"(d[8]), "=f"(d[9]), "=f"(d[10]), "=f"(d[11]), "=f"(d[12]), "=f"(d[13]), "=f"(d[14]), "=f"(d[15]),
                   "=f"(d[16]), "=f"(d[17]), "=f"(d[18]), "=f"(d[19]), "=f"(d[20]), "=f"(d[21]), "=f"(d[22]), "=f"(d[23]),
                   "=f"(d[24]), "=f"(d[25]), "=f"(d[26]), "=f"(d[27]), "=f"(d[28]), "=f"(d[29]), "=f"(d[30]), "=f"(d[31])
                 : "r"(a[0]), "r"(a[1]), "r"(a[2]), "r"(a[3]), "l"(bdesc));
}
__device__ __forceinline__ void wgmma_n64(float (&d)[32], const uint32_t (&a)[4], uint64_t bdesc, int scale_d) {
    asm volatile("{\n.reg .pred p;\nsetp.ne.b32 p, %37, 0;\n"
                 "wgmma.mma_async.sync.aligned.m64n64k16.f32.bf16.bf16 {%0,%1,%2,%3,%4,%5,%6,%7,%8,%9,%10,%11,%12,%13,%14,%15,%16,%17,%18,%19,%20,%21,%22,%23,%24,%25,%26,%27,%28,%29,%30,%31}, {%32,%33,%34,%35}, %36, p, 1, 1, 0;\n}"
                 : "+f"(d[0]), "+f"(d[1]), "+f"(d[2]), "+f"(d[3]), "+f"(d[4]), "+f"(d[5]), "+f"(d[6]), "+f"(d[7]),
                   "+f"(d[8]), "+f"(d[9]), "+f"(d[10]), "+f"(d[11]), "+f"(d[12]), "+f"(d[13]), "+f"(d[14]), "+f"(d[15]),
                   "+f"(d[16]), "+f"(d[17]), "+f"(d[18]), "+f"(d[19]), "+f"(d[20]), "+f"(d[21]), "+f"(d[22]), "+f"(d[23]),
                   "+f"(d[24]), "+f"(d[25]), "+f"(d[26]), "+f"(d[27]), "+f"(d[28]), "+f"(d[29]), "+f"(d[30]), "+f"(d[31])
                 : "r"(a[0]), "r"(a[1]), "r"(a[2]), "r"(a[3]), "l"(bdesc), "r"(scale_d));
}

constexpr int SB_FULL = 0, SB_EMPTY = 64, SB_QKF = 128, SB_VF = 144, SB_QKE = 160, SB_VE = 176, SB_OF = 192, SB_WO = 208, SB_TICK = 216;
constexpr int AT_0 = 256, AT_ST = 10240 + 2 * 9216;
constexpr int FS_A = 58368;
constexpr int FS_P = FS_A + 131072;
constexpr int FS_I = FS_P + 16384;
constexpr int FS_O = FS_I + 12288;
constexpr int FS_Z = FS_O + 12288, FS_G = AT_0 + 2 * AT_ST;
constexpr int SIDE_SMEM = FS_Z + 2048;
static_assert(SIDE_SMEM <= 232448 && FS_G + 128 <= FS_A && FS_A + SD_SMEM <= SIDE_SMEM, "smem");

__device__ __forceinline__ void bf16r2(float& a, float& b) {
    uint32_t p = pack_bf16(a, b);
    a = __uint_as_float(p << 16); b = __uint_as_float(p & 0xffff0000u);
}
__device__ __forceinline__ void wg_wait1() { asm volatile("wgmma.wait_group.sync.aligned 1;" ::: "memory"); }
__device__ __forceinline__ void mbar_arrive(uint32_t bar) { asm volatile("mbarrier.arrive.shared::cta.b64 _, [%0];" :: "r"(bar) : "memory"); }
__device__ __forceinline__ void wait_cnt_rlx(const unsigned* p, unsigned target, bool urgent) {
    unsigned it = 0, v;
    while (true) {
        asm volatile("ld.relaxed.gpu.global.u32 %0, [%1];" : "=r"(v) : "l"(p) : "memory");
        if ((int)(v - target) >= 0 || ++it >= SPIN_LIMIT) break;
        if (!urgent) __nanosleep(RLX_SLEEP);
    }
}

__device__ __forceinline__ uint32_t gtime32() { uint32_t t; asm volatile("mov.u32 %0, %%globaltimer_lo;" : "=r"(t) :: "memory"); return t; }
__device__ __forceinline__ void gate(uint32_t tick_addr) {
    uint32_t t1, p;
    asm volatile("ld.volatile.shared.v2.u32 {%0,%1}, [%2];" : "=r"(t1), "=r"(p) : "r"(tick_addr) : "memory");
    uint32_t d = gtime32() - t1;
    if (d < 4u * p) {
        d -= d >= 2u * p ? 2u * p : 0u;
        d -= d >= p ? p : 0u;
        if (d + GATE_A >= p && d + GATE_B < p) {
            const uint32_t t2 = gtime32() + (p - GATE_B - d);
            while ((int)(gtime32() - t2) < 0) {}
        }
    }
}

__device__ __forceinline__ void read_tick(uint32_t tick_addr, bool on) {
    const uint2 tk = ld_vol_u2(&g_tick);
    uint32_t p = tk.x - tk.y;
    p = p > GATE_P + 100u ? GATE_P + 100u : p;
    asm volatile("st.volatile.shared.v2.u32 [%0], {%1,%2};" :: "r"(tick_addr), "r"(tk.x), "r"(on ? p : 0u) : "memory");
}

__device__ __forceinline__ void xrow_softmax(float (&sc)[20], uint32_t (&pa)[3][4], int wq, int lane) {
    const int g = lane >> 2, tq = lane & 3;
    float mx0 = -INFINITY;
    const int q0 = MEMT + 8 * wq + g;
#pragma unroll
    for (int j = 0; j < 5; j++) {
        bf16r2(sc[4 * j], sc[4 * j + 1]);
        sc[4 * j] *= ATT_SCALE; sc[4 * j + 1] *= ATT_SCALE;
        bf16r2(sc[4 * j], sc[4 * j + 1]);
#pragma unroll
        for (int c = 0; c < 2; c++) {
            int key = 8 * j + 2 * tq + c;
            if (key > q0) sc[4 * j + c] = -INFINITY;
            mx0 = fmaxf(mx0, sc[4 * j + c]);
        }
    }
    mx0 = fmaxf(mx0, __shfl_xor_sync(0xffffffffu, mx0, 1)); mx0 = fmaxf(mx0, __shfl_xor_sync(0xffffffffu, mx0, 2));
    float sum0 = 0.f;
#pragma unroll
    for (int j = 0; j < 5; j++) {
#pragma unroll
        for (int c = 0; c < 2; c++) {
            float e0 = __expf(sc[4 * j + c] - mx0);
            sc[4 * j + c] = e0;
            sum0 += e0;
        }
    }
    sum0 += __shfl_xor_sync(0xffffffffu, sum0, 1); sum0 += __shfl_xor_sync(0xffffffffu, sum0, 2);
    const float i0 = 1.f / sum0;
#pragma unroll
    for (int ks = 0; ks < 3; ks++) {
        pa[ks][0] = pack_bf16(sc[8 * ks] * i0, sc[8 * ks + 1] * i0);
        pa[ks][1] = 0u;
        pa[ks][2] = ks < 2 ? pack_bf16(sc[8 * ks + 4] * i0, sc[8 * ks + 5] * i0) : 0u;
        pa[ks][3] = 0u;
    }
}

__device__ __forceinline__ void stsm_x4(uint32_t addr, uint32_t r0, uint32_t r1, uint32_t r2, uint32_t r3) {
    asm volatile("stmatrix.sync.aligned.m8n8.x4.shared.b16 [%0], {%1,%2,%3,%4};" :: "r"(addr), "r"(r0), "r"(r1), "r"(r2), "r"(r3) : "memory");
}
__device__ __forceinline__ uint32_t h2_to_bf2(uint32_t h) {
    uint32_t r;
    asm("{\n.reg .f16 l, h;\n.reg .f32 a, b;\nmov.b32 {l, h}, %1;\ncvt.f32.f16 a, l;\ncvt.f32.f16 b, h;\ncvt.rn.bf16x2.f32 %0, b, a;\n}" : "=r"(r) : "r"(h));
    return r;
}
__device__ __forceinline__ uint32_t max_abs2(uint32_t a, uint32_t b) { uint32_t r; asm("max.NaN.xorsign.abs.bf16x2 %0, %1, %2;" : "=r"(r) : "r"(a), "r"(b)); return r; }
__device__ __forceinline__ uint32_t movm(uint32_t v) {
    uint32_t r; asm volatile("movmatrix.sync.aligned.m8n8.trans.b16 %0, %1;" : "=r"(r) : "r"(v)); return r;
}
__device__ __forceinline__ void bar_arrive(int id, int n) { asm volatile("bar.arrive %0, %1;" :: "r"(id), "r"(n) : "memory"); }
__device__ __forceinline__ void lds64(uint32_t& a, uint32_t& b, uint32_t addr) {
    asm volatile("ld.shared.v2.u32 {%0,%1}, [%2];" : "=r"(a), "=r"(b) : "r"(addr) : "memory");
}
__device__ __forceinline__ void lds64f(float& a, float& b, uint32_t addr) {
    asm volatile("ld.shared.v2.f32 {%0,%1}, [%2];" : "=f"(a), "=f"(b) : "r"(addr) : "memory");
}
__device__ __forceinline__ void st_async64(uint32_t addr, uint32_t a, uint32_t b, uint32_t mbar) {
    asm volatile("st.async.weak.shared::cluster.mbarrier::complete_tx::bytes.v2.b32 [%0], {%1,%2}, [%3];" :: "r"(addr), "r"(a), "r"(b), "r"(mbar) : "memory");
}
__device__ __forceinline__ void mma_z(float (&d)[4], const uint32_t (&a)[4], uint32_t b0, uint32_t b1) {
    asm volatile("mma.sync.aligned.m16n8k16.row.col.f32.bf16.bf16.f32 {%0,%1,%2,%3}, {%4,%5,%6,%7}, {%8,%9}, {%10,%10,%10,%10};"
                 : "=f"(d[0]), "=f"(d[1]), "=f"(d[2]), "=f"(d[3])
                 : "r"(a[0]), "r"(a[1]), "r"(a[2]), "r"(a[3]), "r"(b0), "r"(b1), "f"(0.f));
}
__device__ __forceinline__ void mma_k8(float (&d)[4], uint32_t a0, uint32_t a1, uint32_t b) {
    asm volatile("mma.sync.aligned.m16n8k8.row.col.f32.bf16.bf16.f32 {%0,%1,%2,%3}, {%4,%5}, {%6}, {%0,%1,%2,%3};"
                 : "+f"(d[0]), "+f"(d[1]), "+f"(d[2]), "+f"(d[3]) : "r"(a0), "r"(a1), "r"(b));
}
__global__ void __launch_bounds__(512, 1) k_side(const __grid_constant__ CUtensorMap tmo, const bf16* __restrict__ x, const bf16* __restrict__ logA, const bf16* __restrict__ Aim,
                                                 const bf16* __restrict__ Cre, const bf16* __restrict__ Cim, const bf16* __restrict__ logdt,
                                                 const bf16* __restrict__ Wo, const bf16* __restrict__ dskip, const bf16* __restrict__ gw,
                                                 bf16* __restrict__ out) {
    extern __shared__ __align__(1024) unsigned char smem_raw[];
    const uint32_t sbase = smem_u32(smem_raw);
    const int tid = threadIdx.x, warp = __shfl_sync(0xffffffffu, tid >> 5, 0), lane = tid & 31, cta = blockIdx.x;
    const int cb = cta >> 2, kq = cta & 3;
    if (tid == 0) {
        for (int i = 0; i < 8; i++) { mbar_init(sbase + SB_FULL + 8 * i, 1); mbar_init(sbase + SB_EMPTY + 8 * i, 4); }
        for (int i = 0; i < 2; i++) {
            mbar_init(sbase + SB_QKF + 8 * i, 1); mbar_init(sbase + SB_VF + 8 * i, 1); mbar_init(sbase + SB_QKE + 8 * i, 1);
            mbar_init(sbase + SB_VE + 8 * i, 4); mbar_init(sbase + SB_OF + 8 * i, 4);
        }
        mbar_init(sbase + SB_WO, 1);
        *reinterpret_cast<uint2*>(smem_raw + SB_TICK) = make_uint2(0u, 0u);
        asm volatile("fence.mbarrier_init.release.cluster;" ::: "memory");
    }
    TS3(0);
    unsigned ep;
    asm volatile("ld.volatile.global.u32 %0, [%1];" : "=r"(ep) : "l"(&g_epoch) : "memory");
    ep += 1u;
    asm volatile("fence.proxy.async;" ::: "memory");
    __syncthreads();
    if (warp >= 12) {
      asm volatile("setmaxnreg.dec.sync.aligned.u32 40;");
      if (warp == 12 || warp == 15) {
        named_bar(3, 320);
        if (tid == 384) {
            fence_async();
            mbar_expect(sbase + SB_WO, 131072);
            if (cta >= NH) read_tick(sbase + SB_TICK, true);
#pragma unroll 1
            for (int i = 0; i < 8; i++) {
                gate(sbase + SB_TICK);
                tma_2d(sbase + FS_A + i * 16384, &tmo, cb * 64, kq * 1024 + i * 128, sbase + SB_WO);
                __nanosleep(150);
            }
            TSS(17, 2);
        }
        if (tid == 480) {
            __threadfence();
            asm volatile("red.relaxed.gpu.global.add.u32 [%0], 1;" :: "l"(&g_gcnt[32]) : "memory");
            TSS(17, 3);
        }
        __syncwarp();
        named_bar(7, 320);
        if (lane == 0) {
            const int pi = warp == 12 ? 0 : 1, kb = 2 * kq + pi;
            fence_async();
            for (int pr = 0; pr < NSEG / 2; pr++) {
                wait_cnt_rlx(&g_prog[pr * 8 + kb], 8u * ep, pr >= NSEG / 2 - 2);
                if (pi == 0 && cta >= NH) read_tick(sbase + SB_TICK, pr < (NSEG - UNGATE) / 2);
                if (pr >= 30 && pi == 0) TSS(4 + pr - 30, 0);
                if (pr == 31) TS3P(26);
                if (pr == 30) TS3P(1);
#pragma unroll
                for (int j = 0; j < 4; j++) {
                    const int st = 4 * pi + j;
                    mbar_wait_long(sbase + SB_EMPTY + 8 * st, ((uint32_t)pr & 1u) ^ 1u);
                    mbar_expect(sbase + SB_FULL + 8 * st, X_OXSZ);
                    gate(sbase + SB_TICK);
                    bulk_g2s(sbase + FS_A + st * 16384, g_ox + ((size_t)(pr * NH + 4 * kb + j)) * 8192, X_OXSZ, sbase + SB_FULL + 8 * st);
                }
            }
        }
        __syncwarp();
      } else if (warp == 13) {
        if (lane == 0 && cta < NH) {
            const uint64_t pol = policy_evict_first();
            for (int seg = 0; seg < NATT; seg++) {
                const uint32_t st = seg & 1, ph = (uint32_t)(seg >> 1) & 1u, ab = sbase + AT_0 + st * AT_ST;
                wait_cnt_rlx(&g_flag[seg * NH + cta], 3u * ep, seg >= NSEG - PROMPT - 1);
                if (seg >= 58) TSS(seg - 58, 0);
                mbar_wait_long(sbase + SB_QKE + 8 * st, ph ^ 1u);
                if (seg >= 58) TSS(seg - 58, 1);
                mbar_expect(sbase + SB_QKF + 8 * st, 2 * 9216);
                gate(sbase + SB_TICK);
                bulk_g2s_h(ab + 10240, &g_qkv[seg][cta][0][1024], 9216, sbase + SB_QKF + 8 * st, pol);
                bulk_g2s_h(ab + 10240 + 9216, &g_qkv[seg][cta][1][1024], 9216, sbase + SB_QKF + 8 * st, pol);
                mbar_wait_long(sbase + SB_VE + 8 * st, ph ^ 1u);
                mbar_expect(sbase + SB_VF + 8 * st, 10240);
                bulk_g2s_h(ab, &g_qkv[seg][cta][2][0], 10240, sbase + SB_VF + 8 * st, pol);
                read_tick(sbase + SB_TICK, seg < NSEG - UNGATE);
            }
        }
        __syncwarp();
      } else if (warp == 14) {
        if (lane == 0 && cta < NH) {
            for (int seg = 0; seg < NATT; seg++) {
                const uint32_t st = seg & 1, ab = sbase + AT_0 + st * AT_ST;
                mbar_wait_long(sbase + SB_OF + 8 * st, (uint32_t)(seg >> 1) & 1u);
                if (seg >= 58) TSS(seg - 58, 3);
                gate(sbase + SB_TICK);
                unsigned char* dst = reinterpret_cast<unsigned char*>(g_ox) + ((size_t)((seg >> 1) * NH + cta)) * 16384 + (seg & 1) * 4096;
                asm volatile("cp.async.bulk.global.shared::cta.bulk_group [%0], [%1], 4096;" :: "l"(dst), "r"(ab + 12288) : "memory");
                asm volatile("cp.async.bulk.global.shared::cta.bulk_group [%0], [%1], 4096;" :: "l"(dst + 8192), "r"(ab + 16384) : "memory");
                asm volatile("cp.async.bulk.commit_group;" ::: "memory");
                asm volatile("cp.async.bulk.wait_group 0;" ::: "memory");
                asm volatile("red.relaxed.gpu.global.add.u32 [%0], 1;" :: "l"(&g_prog[(seg >> 1) * 8 + (cta >> 2)]) : "memory");
                mbar_arrive(sbase + SB_QKE + 8 * st);
                if (seg >= 58) TSS(seg - 58, 4);
            }
        }
        __syncwarp();
      }
    } else if (warp >= 8) {
        asm volatile("setmaxnreg.dec.sync.aligned.u32 88;");
        s4d_stage_u(smem_raw + FS_A, x, tid - 256);
        {
            uint32_t gwv[9];
#pragma unroll
            for (int i = 0; i < 9; i++) gwv[i] = reinterpret_cast<const uint32_t*>(gw)[lane + 32 * i];
#pragma unroll 3
            for (int i = 0; i < 15; i++) {
                const int tt = 4 * i + warp - 8, t = min(cta * 57 + tt, S_LEN - 1);
                float sm = 0.f;
#pragma unroll
                for (int k = 0; k < 9; k++) {
                    const uint32_t xv = reinterpret_cast<const uint32_t*>(x + t * DM)[lane + 32 * k];
                    float a = __uint_as_float(xv << 16) * __uint_as_float(gwv[k] << 16), b = __uint_as_float(xv & 0xffff0000u) * __uint_as_float(gwv[k] & 0xffff0000u);
                    bf16r2(a, b);
                    sm += a + b;
                }
#pragma unroll
                for (int o = 16; o; o >>= 1) sm += __shfl_xor_sync(0xffffffffu, sm, o);
                const float gv = 1.f / (1.f + expf(-bf16r(sm)));
                if (lane == 0 && tt < 57) g_gate[t] = __float2bfloat16_rn(gv);
            }
#pragma unroll 1
            for (int b8 = 0; b8 < 8; b8++)
#pragma unroll
                for (int i = 0; i < 6; i++) g_fp[b8][cta][i][tid - 256] = make_uint4(0u, 0u, 0u, 0u);
            named_bar(6, 128);
            if (tid == 256) {
                __threadfence();
                asm volatile("red.relaxed.gpu.global.add.u32 [%0], 1;" :: "l"(&g_gcnt[0]) : "memory");
            }
            __syncwarp();
        }
        const int wq = warp - 8;
        for (int seg = 0; seg < (cta < NH ? NATT : 0); seg++) {
            const uint32_t st = seg & 1, ph = (uint32_t)(seg >> 1) & 1u, ab = sbase + AT_0 + st * AT_ST;
            float sc[20];
            mbar_wait_long(sbase + SB_QKF + 8 * st, ph);
            if (seg >= 58 && tid == 256) TSS(seg - 58, 2);
            {
                const uint64_t da = smem_desc(ab + 10240 + 1024, 128, 1024), db = smem_desc(ab + 10240, 128, 2048);
                wg_fence();
#pragma unroll
                for (int ks = 0; ks < 8; ks++) wgmma_n40_ss(sc, da + (uint64_t)((ks >> 2) * 576 + (ks & 3) * 16), db + (uint64_t)((ks >> 2) * 576 + (ks & 3) * 16), ks > 0);
                wg_commit();
                wg_wait0();
            }
            uint32_t pa[3][4];
            xrow_softmax(sc, pa, wq, lane);
            named_bar(6, 128);
            mbar_wait_long(sbase + SB_VF + 8 * st, ph);
#pragma unroll
            for (int hf = 0; hf < 2; hf++) {
                float o[32];
                const uint64_t dv = smem_desc(ab + hf * 1024, 2048, 128);
                wg_fence();
#pragma unroll
                for (int ks = 0; ks < 3; ks++) { if (ks == 0) wgmma_n64_z(o, pa[0], dv); else wgmma_n64(o, pa[ks], dv + (uint64_t)(ks * 256), 1); }
                wg_commit();
                wg_wait0();
#pragma unroll
                for (int i = 0; i < 2; i++)
                    stsm_x4(ab + 12288 + hf * 4096 + wq * 1024 + i * 512 + lane * 16, pack_bf16(o[16 * i], o[16 * i + 1]), pack_bf16(o[16 * i + 4], o[16 * i + 5]),
                            pack_bf16(o[16 * i + 8], o[16 * i + 9]), pack_bf16(o[16 * i + 12], o[16 * i + 13]));
            }
            if (lane == 0) mbar_arrive(sbase + SB_VE + 8 * st);
            fence_async();
            __syncwarp();
            if (lane == 0) mbar_arrive(sbase + SB_OF + 8 * st);
        }
    } else {
        asm volatile("setmaxnreg.inc.sync.aligned.u32 192;");
        const int wg = warp >> 2, wq = warp & 3;
        s4d_phase(smem_raw + FS_A, x, logA, Aim, Cre, Cim, logdt, dskip, Wo + (size_t)((2 * kq + wg) * 512) * DM + cb * 64, ep);
        TS3(2);
        if (lane == 0) TSS(16, warp);
        named_bar(3, 320);
        if (tid == 0) TSS(17, 0);
        uint32_t wa[32][4];
        mbar_wait_long(sbase + SB_WO, 0);
        if (tid == 0) TSS(17, 1);
        {
            const uint32_t a = sbase + FS_A + wg * 65536 + ((lane >> 4) * 8 + (lane & 7)) * 128 + (((wq * 2 + ((lane >> 3) & 1)) ^ (lane & 7)) << 4);
#pragma unroll
            for (int ks = 0; ks < 32; ks++) ldsm_x4_t(wa[ks], a + ks * 2048);
        }
        named_bar(7, 320);
        TS3(3);
        if (tid == 0) TSS(17, 4);
        auto product = [&](float (&acc)[32], int pr) {
                if (pr + wg > 0 && pr + wg < NSEG / 2) named_bar(4 + wg, 256);
                const uint64_t db = smem_desc(sbase + FS_A + wg * 65536, 128, 1024);
                TSG(0);
#pragma unroll
                for (int j = 0; j < 4; j++) {
                    mbar_wait(sbase + SB_FULL + 8 * (4 * wg + j), (uint32_t)pr & 1u);
                    wg_fence();
#pragma unroll
                    for (int ks = 0; ks < 8; ks++) {
                        if ((j | ks) == 0) wgmma_n64_z(acc, wa[0], db);
                        else wgmma_n64(acc, wa[8 * j + ks], db + (uint64_t)(j * 1024 + (ks >> 2) * 512 + (ks & 3) * 16), 1);
                    }
                    wg_commit();
                    if (j == 3 && pr + 1 < NSEG / 2) bar_arrive(4 + (wg ^ 1), 256);
                    if (j > 0) { wg_wait1(); if (lane == 0) mbar_arrive(sbase + SB_EMPTY + 8 * (4 * wg + j - 1)); }
                }
                wg_wait0();
                if (pr == 31) TS3W(27);
                TSG(3);
                if (lane == 0) mbar_arrive(sbase + SB_EMPTY + 8 * (4 * wg + 3));
        };
        if (wg == 1) {
            for (int pr = 0; pr < NSEG / 2; pr++) {
                uint32_t t16 = (uint32_t)(wq * 32 + lane) * 16u;
                asm volatile("" : "+r"(t16));
                float acc[32];
                product(acc, pr);
                    uint32_t tag = ((uint32_t)(pr >> 3) & 1u) ^ 1u;
                    tag = __shfl_sync(0xffffffffu, tag, lane);
                    gate(sbase + SB_TICK);
                    named_bar(8, 256);
                    unsigned char* dst = reinterpret_cast<unsigned char*>(&g_fp[pr & 7][4 * cb][2 * kq - 2][0]) + t16;
                    const uint32_t own = sbase + FS_O + (pr % 3) * 4096 + t16;
#pragma unroll
                    for (int q = 0; q < 8; q++) {
                        float4 p;
                        asm volatile("ld.shared.v4.f32 {%0,%1,%2,%3}, [%4];" : "=f"(p.x), "=f"(p.y), "=f"(p.z), "=f"(p.w) : "r"(sbase + FS_P + t16 + q * 2048) : "memory");
                        acc[4 * q] = __uint_as_float((__float_as_uint(acc[4 * q] + p.x) & ~1u) | tag); acc[4 * q + 1] = __uint_as_float((__float_as_uint(acc[4 * q + 1] + p.y) & ~1u) | tag);
                        acc[4 * q + 2] = __uint_as_float((__float_as_uint(acc[4 * q + 2] + p.z) & ~1u) | tag); acc[4 * q + 3] = __uint_as_float((__float_as_uint(acc[4 * q + 3] + p.w) & ~1u) | tag);
                    }
#pragma unroll
                    for (int q = 0; q < 8; q++) {
                        asm volatile("{\n.reg .pred p;\nsetp.ne.s32 p, %5, %6;\n@p st.volatile.global.v4.f32 [%0], {%1,%2,%3,%4};\n@!p st.shared.v4.f32 [%7], {%1,%2,%3,%4};\n}"
                                     :: "l"(dst + (q & 1) * 2048), "f"(acc[4 * q]), "f"(acc[4 * q + 1]), "f"(acc[4 * q + 2]), "f"(acc[4 * q + 3]), "r"(q >> 1), "r"(kq),
                                        "r"(own + (q & 1) * 2048) : "memory");
                        if (q & 1) dst += (q >> 1) == kq ? 12288 + 4096 : 12288;
                    }
                    bar_arrive(9, 256);
                    if (pr == 31) TS3W(28);
                TSG(4);
            }
        } else {
          for (int it = 0; it < NSEG / 2 + 2; it++) {
            const int pr = it < 31 ? it : (it == 32 ? 31 : -1);
            const int pf = it - 2;
            uint32_t t16 = (uint32_t)(wq * 32 + lane) * 16u;
            asm volatile("" : "+r"(t16));
            const int t0 = pf * 64 + kq * 16, c0 = cb * 64 + wq * 16;
            auto fetch = [&]() {
                const unsigned char* src = reinterpret_cast<const unsigned char*>(&g_fp[pf & 7][cta][0][0]) + t16;
#pragma unroll
                for (int r = 0; r < 6; r++) asm volatile("cp.async.cg.shared.global [%0], [%1], 16;" :: "r"(sbase + FS_I + t16 + r * 2048), "l"(src + r * 2048) : "memory");
                asm volatile("cp.async.commit_group;" ::: "memory");
            };
            if (pf >= 0) {
                if (pf == 0) { if (lane == 0) wait_cnt(&g_gcnt[32], SD_NCTA * ep); __syncwarp(); }
                asm volatile("cp.async.cg.shared.global [%0], [%1], 16;" :: "r"(sbase + FS_Z + t16), "l"(g_y + (size_t)(c0 + (lane & 15)) * S_LEN + t0 + (lane >> 4) * 8) : "memory");
                if (lane < 2) asm volatile("cp.async.cg.shared.global [%0], [%1], 16;" :: "r"(sbase + FS_G + wq * 32 + lane * 16), "l"(g_gate + t0 + lane * 8) : "memory");
            }
            if (it == 33) named_bar(9, 256);
            if (pf >= 0) { gate(sbase + SB_TICK); fetch(); }
            if (pr >= 0) {
                float acc[32];
                product(acc, pr);
                    if (pr > 0) named_bar(9, 256);
#pragma unroll
                    for (int q = 0; q < 8; q++)
                        asm volatile("st.shared.v4.f32 [%0], {%1,%2,%3,%4};" :: "r"(sbase + FS_P + t16 + q * 2048), "f"(acc[4 * q]), "f"(acc[4 * q + 1]), "f"(acc[4 * q + 2]), "f"(acc[4 * q + 3]) : "memory");
                    bar_arrive(8, 256);
                TSG(4);
            }
            if (pf >= 0) {
                const uint32_t tag = ((uint32_t)(pf >> 3) & 1u) ^ 1u;
                uint4 v[8];
                unsigned n = 0;
                while (true) {
                    asm volatile("cp.async.wait_group 0;" ::: "memory");
                    uint32_t any = 0u;
#pragma unroll
                    for (int r = 0; r < 8; r++)
                        asm volatile("ld.shared.v4.u32 {%0,%1,%2,%3}, [%4];" : "=r"(v[r].x), "=r"(v[r].y), "=r"(v[r].z), "=r"(v[r].w)
                                     : "r"(sbase + t16 + (r < 6 ? FS_I + r * 2048 : FS_O + (pf % 3) * 4096 + (r - 6) * 2048)) : "memory");
#pragma unroll
                    for (int r = 0; r < 6; r++) {
                        uint32_t c0_, c1_;
                        asm("lop3.b32 %0, %1, %2, %3, 0x7e;" : "=r"(c0_) : "r"(v[r].x), "r"(v[r].y), "r"(tag));
                        asm("lop3.b32 %0, %1, %2, %3, 0x7e;" : "=r"(c1_) : "r"(v[r].z), "r"(v[r].w), "r"(tag));
                        asm("lop3.b32 %0, %1, %2, %3, 0xfe;" : "=r"(any) : "r"(any), "r"(c0_), "r"(c1_));
                    }
                    if (!__any_sync(0xffffffffu, (any & 1u) != 0u) || ++n >= SPIN_LIMIT) break;
                    if (pf + 1 < NSEG / 2) __nanosleep(200);
                    fetch();
                }
                if (pf == 31) TS3(29);
                TSG(5);
                uint32_t zv[4], gg[2];
                ldsm_x4_t(zv, sbase + FS_Z + t16);
#pragma unroll
                for (int k = 0; k < 2; k++) gg[k] = __byte_perm(*reinterpret_cast<const unsigned short*>(smem_raw + FS_G + wq * 32 + k * 16 + (lane >> 2) * 2), 0u, 0x1010);
                const uint32_t xo = (uint32_t)((t0 + (lane >> 2)) * DM + c0 + 2 * (lane & 3)) * 2u;
#define PQS(k, f) ((__uint_as_float(v[k].f) + __uint_as_float(v[2 + k].f)) + (__uint_as_float(v[4 + k].f) + __uint_as_float(v[6 + k].f)))
#pragma unroll
                for (int k = 0; k < 2; k++) {
                    unsigned char* op = reinterpret_cast<unsigned char*>(out) + xo + k * (16 * DM);
                    *reinterpret_cast<uint32_t*>(op) = bf2_add(bf2_mul(gg[k], movm(pack_bf16(PQS(k, x), PQS(k, y)))), zv[2 * k]);
                    *reinterpret_cast<uint32_t*>(op + 16) = bf2_add(bf2_mul(gg[k], movm(pack_bf16(PQS(k, z), PQS(k, w)))), zv[2 * k + 1]);
                }
#undef PQS
                if ((pf & 1) == 0) TS3(4 + pf / 2);
                if (pf == 31) TS3(25);
                TSG(6);
            }
        }
        }
        if (cta == 0 && tid == 0) asm volatile("red.relaxed.gpu.global.add.u32 [%0], 1;" :: "l"(&g_epoch) : "memory");
    }
    asm volatile("griddepcontrol.wait;" ::: "memory");
}

__device__ __forceinline__ uint32_t poll_mem(const uint4* src, uint32_t dst, uint32_t t0) {
    uint4 v[6];
    unsigned it = 0;
#pragma unroll
    for (int j = 0; j < 6; j++) v[j] = make_uint4(0u, 0u, 0u, 0u);
    while (clock32() - t0 < POLL_DELAY) {}
    FS(12, 0);
    bool more;
#pragma unroll 1
    do {
        asm volatile("{\n.reg .pred p<6>;\n"
                     "setp.ne.u32 p0, %3, 0x5000;\nsetp.ne.u32 p1, %7, 0x5000;\nsetp.ne.u32 p2, %11, 0x5000;\n"
                     "setp.ne.u32 p3, %15, 0x5000;\nsetp.ne.u32 p4, %19, 0x5000;\nsetp.ne.u32 p5, %23, 0x5000;\n"
                     "@p0 ld.volatile.global.v4.u32 {%0,%1,%2,%3}, [%24];\n@p1 ld.volatile.global.v4.u32 {%4,%5,%6,%7}, [%24+4096];\n"
                     "@p2 ld.volatile.global.v4.u32 {%8,%9,%10,%11}, [%24+8192];\n@p3 ld.volatile.global.v4.u32 {%12,%13,%14,%15}, [%24+12288];\n"
                     "@p4 ld.volatile.global.v4.u32 {%16,%17,%18,%19}, [%24+16384];\n@p5 ld.volatile.global.v4.u32 {%20,%21,%22,%23}, [%24+20480];\n}"
                     : "+r"(v[0].x), "+r"(v[0].y), "+r"(v[0].z), "+r"(v[0].w), "+r"(v[1].x), "+r"(v[1].y), "+r"(v[1].z), "+r"(v[1].w),
                       "+r"(v[2].x), "+r"(v[2].y), "+r"(v[2].z), "+r"(v[2].w), "+r"(v[3].x), "+r"(v[3].y), "+r"(v[3].z), "+r"(v[3].w),
                       "+r"(v[4].x), "+r"(v[4].y), "+r"(v[4].z), "+r"(v[4].w), "+r"(v[5].x), "+r"(v[5].y), "+r"(v[5].z), "+r"(v[5].w)
                     : "l"(src) : "memory");
        stsm_x4(dst, h2_to_bf2(v[0].x), h2_to_bf2(v[0].y), h2_to_bf2(v[0].z), h2_to_bf2(v[1].x));
        stsm_x4(dst + 512, h2_to_bf2(v[1].y), h2_to_bf2(v[1].z), h2_to_bf2(v[2].x), h2_to_bf2(v[2].y));
        stsm_x4(dst + 1024, h2_to_bf2(v[2].z), h2_to_bf2(v[3].x), h2_to_bf2(v[3].y), h2_to_bf2(v[3].z));
        asm volatile("stmatrix.sync.aligned.m8n8.x2.shared.b16 [%0], {%1,%2};" :: "r"(dst + 1536), "r"(h2_to_bf2(v[4].x)), "r"(h2_to_bf2(v[4].y)) : "memory");
        stsm_x4(dst + 1792, h2_to_bf2(v[4].z), h2_to_bf2(v[5].x), h2_to_bf2(v[5].y), h2_to_bf2(v[5].z));
        const uint32_t all = ((v[0].w & v[1].w) & (v[2].w & v[3].w)) & (v[4].w & v[5].w);
        more = __any_sync(0xffffffffu, (all & 0x5000u) != 0x5000u) && ++it < SPIN_LIMIT;
    } while (more);
    FS(13, it);
    bar_arrive(1, 384);
    FS(14, 0);
    uint32_t m = 0u;
#pragma unroll
    for (int j = 0; j < 6; j++) {
        asm volatile("max.NaN.xorsign.abs.f16x2 %0, %0, %1;" : "+r"(m) : "r"(v[j].x));
        asm volatile("max.NaN.xorsign.abs.f16x2 %0, %0, %1;" : "+r"(m) : "r"(v[j].y));
        asm volatile("max.NaN.xorsign.abs.f16x2 %0, %0, %1;" : "+r"(m) : "r"(v[j].z));
    }
    return h2_to_bf2(m) & 0x7fff7fffu;
}

template <bool V> struct Flag { static constexpr bool value = V; };
struct RFlag { bool value; };
__device__ __forceinline__ void score_group(const uint32_t (&a)[2][4], const uint32_t (&kf)[2][4], uint32_t d0, uint32_t d1, uint32_t m1, uint32_t d2, uint32_t m2) {
    FS(4, a[1][0]);
    float sc[4][4];
    mma_z(sc[0], a[0], kf[0][0], kf[0][1]);
    mma_z(sc[1], a[0], kf[0][2], kf[0][3]);
    mma_z(sc[2], a[1], kf[1][0], kf[1][1]);
    mma_z(sc[3], a[1], kf[1][2], kf[1][3]);
    const uint32_t v0 = __float_as_uint((sc[0][0] + sc[1][2]) + (sc[2][0] + sc[3][2])), v1 = __float_as_uint((sc[0][1] + sc[1][3]) + (sc[2][1] + sc[3][3]));
    FS(5, v0);
    st_async64(d2, v0, v1, m2);
    st_async64(d1, v0, v1, m1);
    asm volatile("st.shared.v2.u32 [%0], {%1,%2};" :: "r"(d0), "r"(v0), "r"(v1) : "memory");
}
__device__ __forceinline__ void store_tile(int s, int h, int role, uint32_t tile) {
    const uint32_t qoff = role != 2 ? 1024 : 0;
    asm volatile("cp.async.bulk.global.shared::cta.bulk_group.L2::cache_hint [%0], [%1], %2, %3;"
                 :: "l"(&g_qkv[s][h][role][qoff]), "r"(tile + qoff), "r"(10240u - qoff), "l"(policy_evict_first()) : "memory");
    asm volatile("cp.async.bulk.commit_group;" ::: "memory");
}
__device__ __forceinline__ uint32_t w_addr(uint32_t sbase, int warp, int lane) {
    return sbase + SM_WS + (warp >> 2) * 8192 + ((lane & 7) + ((lane >> 4) & 1) * 8) * 128 + ((((warp & 3) * 2 + ((lane >> 3) & 1)) ^ (lane & 7)) << 4);
}
__device__ __forceinline__ void vx_copy(uint32_t sbase, int j, int r) {
    bulk_s2s(mapa(sbase + SM_VX + (j & 1) * 8192, r), sbase + SM_T + (j & 3) * TBUF + DH * 16, 8192, mapa(sbase + B_VX + 8 * (j & 1), r));
}
__device__ __forceinline__ void norms_gather(int lane, float* scs) {
    uint2 v[3];
    uint32_t r[2];
    unsigned it = 0;
    do {
#pragma unroll
        for (int i = 0; i < 3; i++) v[i] = ld_vol_u2(&g_norm[3 * lane + i]);
#pragma unroll
        for (int i = 0; i < 2; i++) asm volatile("ld.volatile.global.u32 %0, [%1];" : "=r"(r[i]) : "l"(&g_rx[lane + 32 * i]) : "memory");
    } while (__any_sync(0xffffffffu, (v[0].x & v[1].x & v[2].x & v[2].y & r[0] & r[1] & 1u) == 0u) && ++it < SPIN_LIMIT);
    float c;
    asm("sqrt.approx.f32 %0, %1;" : "=f"(c) : "f"(__uint_as_float(max(max(v[0].x, v[1].x), v[2].x))));
    c *= __uint_as_float(v[2].y) * 272.f;
#pragma unroll
    for (int o = 16; o; o >>= 1) c += __shfl_xor_sync(0xffffffffu, c, o);
    scs[16 + lane] = __uint_as_float(r[0]); scs[48 + lane] = __uint_as_float(r[1]);
    if (lane == 0) scs[1] = c * (1.1f * 24.f);
}

__global__ void __cluster_dims__(3, 1, 1) __launch_bounds__(384, 1)
k_chain(const __grid_constant__ CUtensorMap tmx, const __grid_constant__ CUtensorMap tmq, const __grid_constant__ CUtensorMap tmk,
        const __grid_constant__ CUtensorMap tmv, const __grid_constant__ CUtensorMap tmx2, const __grid_constant__ CUtensorMap tmo, const bf16* __restrict__ mem0, const bf16* __restrict__ xg) {
    extern __shared__ __align__(1024) unsigned char smem_raw[];
    const uint32_t sbase = smem_u32(smem_raw);
    const int cta = blockIdx.x, h = cta / 3, role = cta - 3 * h;
    const int tid = threadIdx.x, warp = __shfl_sync(0xffffffffu, tid >> 5, 0), lane_o = tid & 31;
    TS3C(0);
    asm volatile("griddepcontrol.launch_dependents;" ::: "memory");
    auto stage_w = [&](int i) {
        tma_2d(sbase + SM_WS + i * 16384, role == 2 ? &tmv : &tmq, h * DH + (role == 1 ? 64 : 0), i * 64, sbase + B_W + 8 * i);
        tma_2d(sbase + SM_WS + i * 16384 + 8192, role == 2 ? &tmv : &tmk, h * DH + (role == 0 ? 0 : 64), i * 64, sbase + B_W + 8 * i);
    };
    auto stage_x = [&](int i) { tma_2d(sbase + x01_off(i), &tmx2, i * 64, 0, sbase + B_W + 8 * i); };
    if (tid == 0) {
#pragma unroll
        for (int i = 0; i < 10; i++) mbar_init(sbase + B_W + 8 * i, 1);
        fence_async();
        bulk_g2s(sbase + SM_E + XBUF, mem0, MEMT * DM * 2, sbase + B_E);
#pragma unroll
        for (int i = 0; i < 3; i++) tma_2d(sbase + SM_X01 + i * 16384, &tmo, role * WOC + i * 64, h * DH, sbase + B_E);
        if (cta < NSEG) bulk_g2s(sbase + SM_E, xg + (size_t)cta * SEG * DM, XBUF, sbase + B_E);
#pragma unroll 1
        for (int i = 0; i < 6; i++) { if (i < 3) stage_x(i); stage_w(i); }
        mbar_expect(sbase + B_E, 49152 + MEMT * DM * 2 + (cta < NSEG ? XBUF : 0));
#pragma unroll
        for (int i = 0; i < 9; i++) mbar_expect(sbase + B_W + 8 * i, 24576);
    } else if (tid == 32) {
#pragma unroll
        for (int i = 0; i < 7; i++) mbar_init(sbase + SM_BAR + 8 * i, 1);
        asm volatile("fence.mbarrier_init.release.cluster;" ::: "memory");
        for (int i = 0; i < 2; i++) {
            mbar_expect(sbase + B_SB + 8 * i, role == 2 ? 2560 : 1280 + 2048);
            mbar_expect(sbase + B_VX + 8 * i, role != 2 ? 8192 : 2 * 9216);
            mbar_arrive(sbase + B_XT + 8 * i);
        }
        mbar_expect(sbase + B_XT + 16, XBUF);
        reinterpret_cast<float*>(smem_raw + SM_SC)[2] = 1.f;
    } else if (tid >= 64 && tid < 88) {
        *reinterpret_cast<uint4*>(g_acc + cta * 1024 + (tid - 64) * 16) = make_uint4(0u, 0u, 0u, 0u);
        __threadfence();
    }
    __syncthreads();
    TS3C(8);
    if (warp < 8) {
        uint32_t wreg[36 - NS][4];
        {
            const int lane = lane_o;
            const uint32_t a = w_addr(sbase, warp, lane);
            const uint64_t da = smem_desc(sbase + SM_WS + (warp >> 2) * 8192, 1024, 1024) | (1ull << 62);
            float acc[32];
#pragma unroll
            for (int i = 0; i < 32; i++) acc[i] = 0.f;
#pragma unroll 1
            for (int b = 0; b < 9; b++) {
                if (b == 0) TSQ(0);
                mbar_wait(sbase + B_W + 8 * b, 0);
                TSQ(1 + b);
                if (b == 8) TS3C(2);
                const uint64_t db = smem_desc(sbase + x01_off(b), 16, 1024) | (1ull << 62);
                wg_fence();
#pragma unroll
                for (int k = 0; k < 4; k++) wgmma_n64_ss(acc, da + (uint64_t)(b * 1024 + k * 128), db + (uint64_t)(k * 2));
                wg_commit();
                if (b == 5) {
#pragma unroll
                    for (int ks = NS; ks < 24; ks++) ldsm_x4_t(wreg[ks - NS], a + (ks >> 2) * 16384 + (ks & 3) * 2048);
                }
            }
#pragma unroll
            for (int ks = 24; ks < 32; ks++) ldsm_x4_t(wreg[ks - NS], a + (ks >> 2) * 16384 + (ks & 3) * 2048);
            wg_wait0();
            named_bar(9, 384);
            const uint32_t off = sbase + SM_T + (DH + warp * 16 + (lane & 15)) * 16 + (lane >> 4) * (DH * 16);
#pragma unroll
            for (int i = 0; i < 4; i++)
                stsm_x4(off + (i >> 1) * TBUF + (i & 1) * (2 * DH * 16), pack_bf16(acc[8 * i], acc[8 * i + 1]), pack_bf16(acc[8 * i + 2], acc[8 * i + 3]),
                        pack_bf16(acc[8 * i + 4], acc[8 * i + 5]), pack_bf16(acc[8 * i + 6], acc[8 * i + 7]));
#pragma unroll
            for (int ks = 32; ks < 36; ks++) ldsm_x4_t(wreg[ks - NS], a + (ks >> 2) * 16384 + (ks & 3) * 2048);
            if (role == 2) fence_async();
            bar_arrive(8, 384);
            named_bar(7, 256);
            asm volatile("barrier.cluster.arrive.relaxed.aligned;" ::: "memory");
        }
        TS3C(3);
        auto xproj1 = [&](float (&acc)[16], int j) {
            const uint32_t dlo = __shfl_sync(0xffffffffu, (uint32_t)smem_desc(sbase + SM_X + (j % 3) * XBUF, 16, 1024), 0);
            wg_fence();
#pragma unroll
            for (int ks = NS; ks < NS + NC1; ks++)
                wgmma_n32(acc, wreg[ks - NS], ((uint64_t)0x40000040u << 32) | (uint64_t)(dlo + (uint32_t)((ks >> 2) * 256 + (ks & 3) * 2)), ks > NS);
            wg_commit();
            wg_wait0();
        };
        auto xproj2 = [&](float (&acc)[16], int j) {
            int lane = lane_o;
            asm volatile("" : "+r"(lane));
            const uint32_t dlo = __shfl_sync(0xffffffffu, (uint32_t)smem_desc(sbase + SM_X + (j % 3) * XBUF, 16, 1024), 0);
            const uint64_t da = smem_desc(sbase + SM_WS + (warp >> 2) * 8192, 1024, 1024) | (1ull << 62);
            wg_fence();
#pragma unroll
            for (int ks = NS + NC1; ks < NS + NC1 + SS_POS; ks++)
                wgmma_n32(acc, wreg[ks - NS], ((uint64_t)0x40000040u << 32) | (uint64_t)(dlo + (uint32_t)((ks >> 2) * 256 + (ks & 3) * 2)), 1);
#pragma unroll
            for (int ks = 0; ks < NS; ks++)
                wgmma_n32_ss(acc, da + (uint64_t)((ks >> 2) * 1024 + (ks & 3) * 128), ((uint64_t)0x40000040u << 32) | (uint64_t)(dlo + (uint32_t)((ks >> 2) * 256 + (ks & 3) * 2)), 1);
#pragma unroll
            for (int ks = NS + NC1 + SS_POS; ks < XK; ks++)
                wgmma_n32(acc, wreg[ks - NS], ((uint64_t)0x40000040u << 32) | (uint64_t)(dlo + (uint32_t)((ks >> 2) * 256 + (ks & 3) * 2)), 1);
            wg_commit();
            wg_wait0();
            const uint32_t off = sbase + SM_T + (j & 3) * TBUF + (DH + warp * 16 + (lane & 15)) * 16 + (lane >> 4) * (DH * 16);
            stsm_x4(off, pack_bf16(acc[0], acc[1]), pack_bf16(acc[2], acc[3]), pack_bf16(acc[4], acc[5]), pack_bf16(acc[6], acc[7]));
            stsm_x4(off + 2 * DH * 16, pack_bf16(acc[8], acc[9]), pack_bf16(acc[10], acc[11]), pack_bf16(acc[12], acc[13]), pack_bf16(acc[14], acc[15]));
        };
        uint32_t ws[NS][4];
#pragma unroll
        for (int ks = NS - NP; ks < NS; ks++) ldsm_x4_t(ws[ks], w_addr(sbase, warp, lane_o) + (ks >> 2) * 16384 + (ks & 3) * 2048);
        asm volatile("barrier.cluster.wait.aligned;" ::: "memory");
        if (lane_o == 0 && warp < 2 && role == 2) vx_copy(sbase, 0, warp);
        __syncwarp();
        TS3C(4);
        auto main_loop = [&](auto is_c) {
            const bool C = is_c.value;
            const uint32_t l16 = __shfl_sync(0xffffffffu, sbase + lane_o * 16, lane_o);
            const uint32_t ta = __shfl_sync(0xffffffffu, sbase + SM_T + warp * 256 + (lane_o & 15) * 16, lane_o);
            const uint32_t ka = __shfl_sync(0xffffffffu, sbase + SM_T + (64 + (lane_o & 7) + ((lane_o >> 3) & 1) * 16 + (lane_o >> 4) * 8) * 16, lane_o);
            uint32_t to = 0;
            for (int s = 0; s < NSEG; s++) {
                int lane = lane_o;
                asm volatile("" : "+r"(lane));
                uint32_t v0, v1;
                const uint32_t tb = sbase + SM_T + to;
                {
#pragma unroll
                    for (int ks = 0; ks < NS - NP; ks++) ldsm_x4_t(ws[ks], w_addr(sbase, warp, lane) + (ks >> 2) * 16384 + (ks & 3) * 2048);
                    FS(0, ws[0][0]);
                    named_bar(1, 384);
                    float acc[2][4], minv;
                    uint32_t b[3][4];
#pragma unroll
                    for (int kk = 0; kk < 3; kk++) ldsm_x4_t(b[kk], l16 + SM_M + kk * 512);
                    FS(1, b[0][0]);
#pragma unroll
                    for (int kk = 0; kk < 18; kk++) {
#pragma unroll
                        for (int i = 0; i < 2; i++) {
                            const int ks = 2 * kk + i;
                            if (ks < 2) mma_z(acc[i], ws[ks], b[kk % 3][2 * i], b[kk % 3][2 * i + 1]);
                            else if (ks < NS) mma_bf16(acc[i], ws[ks < NS ? ks : 0], b[kk % 3][2 * i], b[kk % 3][2 * i + 1]);
                            else mma_bf16(acc[i], wreg[ks >= NS ? ks - NS : 0], b[kk % 3][2 * i], b[kk % 3][2 * i + 1]);
                        }
                        if (kk + 3 < 18) ldsm_x4_t(b[kk % 3], l16 + SM_M + (kk + 3) * 512);
                        if (kk + 3 == 17) asm volatile("ld.shared.f32 %0, [%1];" : "=f"(minv) : "r"(sbase + SM_SC + 8) : "memory");
                    }
                    v0 = pack_bf16(fmaf(acc[1][0], minv, acc[0][0] * minv), fmaf(acc[1][1], minv, acc[0][1] * minv));
                    v1 = pack_bf16(fmaf(acc[1][2], minv, acc[0][2] * minv), fmaf(acc[1][3], minv, acc[0][3] * minv));
                    FS(2, v0);
                }
                asm volatile("stmatrix.sync.aligned.m8n8.x2.shared.b16 [%0], {%1,%2};" :: "r"(ta + to), "r"(v0), "r"(v1) : "memory");
                if (C) {
                    if (s + 1 < NSEG) {
                        const uint32_t fo = (uint32_t)(warp * 256 + lane * 8);
                        const uint32_t rb0 = mapa(sbase, 0), rb1 = mapa(sbase, 1);
                        st_async64(rb0 + SM_VM + fo, v0, v1, rb0 + B_SB + 8 * (s & 1));
                        st_async64(rb1 + SM_VM + fo, v0, v1, rb1 + B_SB + 8 * (s & 1));
                        asm volatile("st.shared.v2.u32 [%0], {%1,%2};" :: "r"(sbase + SM_VM + fo), "r"(v0), "r"(v1) : "memory");
                        bar_arrive(2, 384);
                    }
                } else {
                    named_bar(2, 384);
                    if (warp == 7) {
                        uint32_t kf[2][4], qf[2][4];
#pragma unroll
                        for (int k2 = 0; k2 < 2; k2++) { ldsm_x4_t(kf[k2], ka + to + k2 * 512); ldsm_x4_t(qf[k2], l16 + SM_T + to + k2 * 512); }
                        if (s + 1 < NSEG) {
                            const uint32_t d0 = sbase + SM_S + role * 1280 + lane * 8, bo = sbase + B_SB + 8 * (s & 1);
                            const uint32_t d1 = mapa(d0, role ^ 1), m1 = mapa(bo, role ^ 1), d2 = mapa(d0, 2), m2 = mapa(bo, 2);
                            score_group(qf, kf, d0, d1, m1, d2, m2);
                            bar_arrive(6, 160);
                        }
                    }
                    if (s + 1 == NSEG && warp >= 4) {
                        const uint32_t dk = mapa(sbase + SM_X + XBUF + (2 + role) * 9216 + (warp - 4) * 256 + lane * 4, 2), mb = mapa(sbase + B_VX + 8, 2);
                        st_async32(dk, v0, mb);
                        st_async32(dk + 128, v1, mb);
                    }
                }
                to = to == 3 * TBUF ? 0 : to + TBUF;
                FS(11, 0);
                const bool prompt = s >= NSEG - PROMPT;
                if (s + 2 < NSEG) {
                    if (warp == 6) mbar_wait(sbase + B_XT + 8 * ((s + 2) % 3), (uint32_t)((s + 2) / 3) & 1u);
                    if (C || prompt) fence_async();
                    if (!C) named_bar(5, 384); else named_bar(7, 256);
                    if (prompt) {
                        if (tid == 64) store_tile(s, h, role, tb);
                        __syncwarp();
                    }
                    float xacc[16];
                    if (C1_DELAY > 0) { const uint32_t t1 = clock32(); while (clock32() - t1 < C1_DELAY) {} }
                    xproj1(xacc, s + 2);
                    FS(9, __float_as_uint(xacc[0]));
                    if (C && tid == 0) vx_copy(sbase, s + 1, 0);
                    if (prompt && tid == 64) {
                        asm volatile("cp.async.bulk.wait_group 0;" ::: "memory");
                        asm volatile("red.relaxed.gpu.global.add.u32 [%0], 1;" :: "l"(&g_flag[s * NH + h]) : "memory");
                    }
                    __syncwarp();
                    if (!C) fence_async();
                    FS(14, 0);
                    named_bar(4, 384);
                    if (C2_DELAY > 0) { const uint32_t t1 = clock32(); while (clock32() - t1 < C2_DELAY) {} }
                    xproj2(xacc, s + 2);
                    FS(7, __float_as_uint(xacc[0]));
                } else if (s + 2 == NSEG) {
                    const uint32_t t0 = clock32();
                    const uint32_t dq = mapa(sbase + SM_X + XBUF + role * 9216, 2), mb = mapa(sbase + B_VX, 2);
                    if (!C) {
                        fence_async();
                        named_bar(5, 384);
                        if (tid == 64) { while (clock32() - t0 < TL_DELAY) {} bulk_s2s(dq, tb + 1024, 9216, mb); }
                        __syncwarp();
                    }
                    named_bar(4, 384);
                    if (!C && tid == 64) { const uint32_t t1 = clock32(); while (clock32() - t1 < VX_DELAY) {} bulk_s2s(dq + 2 * 9216 + 1024, sbase + SM_T + ((s + 1) & 3) * TBUF + 2048, 8192, mb + 8); }
                    __syncwarp();
                }
            }
            if (C) named_bar(7, 256);
        };
        if (role == 2) main_loop(Flag<true>()); else main_loop(Flag<false>());
    } else {
        float* scs = reinterpret_cast<float*>(smem_raw + SM_SC);
        uint32_t wo[3][8][4];
        uint32_t mx2 = 0u;
        {
            const int pt = tid - 256, lane = lane_o, wq = warp - 8, g = lane >> 2, tq = lane & 3;
            TSQ(7);
            mbar_wait(sbase + B_E, 0);
            TSQ(8);
#pragma unroll
            for (int t = 0; t < 3; t++) {
                const int T = 3 * wq + t;
                const uint32_t a = sbase + SM_X01 + (T >> 2) * 16384 + ((lane >> 4) * 8 + (lane & 7)) * 128 + ((((T & 3) * 2 + ((lane >> 3) & 1)) ^ (lane & 7)) << 4);
#pragma unroll
                for (int kk = 0; kk < 8; kk++) ldsm_x4_t(wo[t][kk], a + ((2 * wq + kk) & 7) * 2048);
            }
            uint32_t m = 0u;
#pragma unroll 6
            for (int j = 0; j < 18; j++) {
                const uint32_t v = lds32(sbase + SM_E + XBUF + (g * DM + wq * 144 + 8 * j) * 2 + tq * 4);
                asm volatile("stmatrix.sync.aligned.m8n8.x1.trans.shared.b16 [%0], {%1};" :: "r"(sbase + SM_M + (wq * 144 + 8 * j + (lane & 7)) * 16), "r"(v) : "memory");
                mx2 = __vmaxu2(mx2, v & 0x7fff7fffu);
                const uint4 xv = *reinterpret_cast<const uint4*>(smem_raw + SM_E + (pt + 128 * j) * 16);
                m = max_abs2(max_abs2(m, max_abs2(xv.x, xv.y)), max_abs2(xv.z, xv.w));
            }
            m = __reduce_max_sync(0xffffffffu, max((m << 16) & 0x7fff0000u, m & 0x7fff0000u));
            if (lane == 0) reinterpret_cast<uint32_t*>(scs)[260 + wq] = m;
            named_bar(3, 128);
            if (pt == 64) {
                fence_async();
#pragma unroll 1
                for (int i = 3; i < 9; i++) { stage_x(i); if (i >= 6) stage_w(i); }
            }
            if (pt == 96 && cta < NSEG) {
                const uint4 q = *reinterpret_cast<const uint4*>(scs + 260);
                asm volatile("st.volatile.global.u32 [%0], %1;" :: "l"(&g_rx[cta]), "r"(max(max(q.x, q.y), max(q.z, q.w)) | 1u) : "memory");
            }
            __syncwarp();
            bar_arrive(1, 384);
            TSQ(9);
            float c0 = 0.f;
#pragma unroll
            for (int t = 0; t < 3; t++) {
                float n[4][4];
#pragma unroll
                for (int i = 0; i < 4; i++) { n[i][0] = n[i][1] = n[i][2] = n[i][3] = 0.f; }
#pragma unroll
                for (int kk = 0; kk < 8; kk++)
#pragma unroll
                    for (int i = 0; i < 4; i++) mma_k8(n[i], wo[t][kk][i & 2], wo[t][kk][(i & 2) + 1], wo[t][kk][i]);
                if ((g >> 1) == tq) c0 = fmaxf(c0, (g & 1) ? fmaxf(n[0][1] + n[2][1], n[1][3] + n[3][3]) : fmaxf(n[0][0] + n[2][0], n[1][2] + n[3][2]));
            }
            c0 = __uint_as_float(__reduce_max_sync(0xffffffffu, __float_as_uint(c0)));
            m = 0u;
#pragma unroll 1
            for (int b = 0; b < 9; b++) {
                if (role == 2) {
                    mbar_wait(sbase + B_W + 8 * b, 0);
#pragma unroll
                    for (int j = 0; j < 8; j++) {
                        const uint4 xv = *reinterpret_cast<const uint4*>(smem_raw + SM_WS + b * 16384 + (pt + 128 * j) * 16);
                        m = max_abs2(max_abs2(m, max_abs2(xv.x, xv.y)), max_abs2(xv.z, xv.w));
                    }
                }
                if (b == 3) bar_arrive(9, 384);
            }
            asm volatile("barrier.cluster.arrive.relaxed.aligned;" ::: "memory");
            m = __reduce_max_sync(0xffffffffu, max((m << 16) & 0x7fff0000u, m & 0x7fff0000u));
            if (lane == 0) { scs[256 + wq] = c0; reinterpret_cast<uint32_t*>(scs)[8 + wq] = m; }
            TSQ(1);
            named_bar(3, 128);
            if (pt == 0) {
                const float a = fmaxf(fmaxf(scs[256], scs[257]), fmaxf(scs[258], scs[259]));
                const float b = fmaxf(fmaxf(scs[8], scs[9]), fmaxf(scs[10], scs[11]));
                st_vol_u2(&g_norm[cta], make_uint2(__float_as_uint(a) | 1u, __float_as_uint(b) | 1u));
            }
            __syncwarp();
            named_bar(8, 384);
            TSQ(2);
            if (pt == 32) {
                fence_async();
                for (int i = 0; i < 3; i++) tma_x(sbase + SM_X + 2 * XBUF, &tmx, 2, i, sbase + B_XT + 16);
            }
            __syncwarp();
            asm volatile("barrier.cluster.wait.aligned;" ::: "memory");
        }
        const int wq = warp - 8;
        auto helper_loop = [&](auto is_c) {
        const bool C = is_c.value;
        const uint32_t l8 = __shfl_sync(0xffffffffu, sbase + lane_o * 8, lane_o), l16 = __shfl_sync(0xffffffffu, sbase + lane_o * 16, lane_o);
        unsigned char* dst = g_acc + (role * 32 + wq * 8 + (lane_o >> 3)) * 1024 + (lane_o & 7) * 16;
        const uint32_t ka = __shfl_sync(0xffffffffu, sbase + SM_T + ((wq + 1) * DH + 64 + (lane_o & 7) + ((lane_o >> 3) & 1) * 16 + (lane_o >> 4) * 8) * 16, lane_o);
        const uint32_t vb = __shfl_sync(0xffffffffu, sbase + (lane_o >> 4) * 2048 + (32 * wq + (lane_o & 15)) * 16, lane_o);
        float minv = 1.f;
        uint32_t kf[2][4];
#pragma unroll
        for (int k2 = 0; k2 < 2; k2++) if (!C) ldsm_x4_t(kf[k2], ka + k2 * 512);
        int b3 = 0;
        for (int s = 0; s + 1 < NSEG; s++) {
            const int n3 = b3 == 2 ? 0 : b3 + 1;
            {
                int lane = lane_o;
                asm volatile("" : "+r"(lane));
                if (lane == 0) {
                    if (wq == 0 && cta == 0) {
                        const uint32_t t = gtime32();
                        st_vol_u2(&g_tick, make_uint2(t, reinterpret_cast<uint32_t*>(scs)[3]));
                        reinterpret_cast<uint32_t*>(scs)[3] = t;
                    }
                    if (wq == 1 && s + 3 < NSEG) tma_x_mc(sbase + SM_X + b3 * XBUF, &tmx, s + 3, role, sbase + B_XT + 8 * b3);
                    if (wq == 3 && s > 0 && s <= NSEG - PROMPT + 1) {
                        if (s <= NSEG - PROMPT) store_tile(s - 1, h, role, sbase + SM_T + ((s - 1) & 3) * TBUF);
                        else asm volatile("cp.async.bulk.commit_group;" ::: "memory");
                        if (s > 1) {
                            asm volatile("cp.async.bulk.wait_group 1;" ::: "memory");
                            asm volatile("red.relaxed.gpu.global.add.u32 [%0], 1;" :: "l"(&g_flag[(s - 2) * NH + h]) : "memory");
                        } else {
                            st_vol_u2(&g_norm[cta], make_uint2(0u, 0u));
                            if (cta < NSEG) asm volatile("st.volatile.global.u32 [%0], %1;" :: "l"(&g_rx[cta]), "r"(0u) : "memory");
                        }
                    }
                }
                __syncwarp();
                if (wq == 2 && s > 1 && lane < 8) {
                    *reinterpret_cast<uint4*>(g_acc + n3 * 128 + cta * 1024 + lane * 16) = make_uint4(0u, 0u, 0u, 0u);
                }
                const uint32_t mw = __reduce_max_sync(0xffffffffu, max(mx2 << 16, mx2 & 0xffff0000u));
                if (lane == 0) scs[4 + wq] = __uint_as_float(mw);
            }
            const uint32_t to = SM_T + (s & 3) * TBUF;
            const uint32_t ph = (uint32_t)(s >> 1) & 1u;
            if (!C) {
                const uint32_t so = SM_S + role * 1280 + (wq + 1) * 256, bo = sbase + B_SB + 8 * (s & 1);
                uint32_t d0 = l8 + so, qa = l16 + to;
                const uint32_t d1 = mapa(d0, role ^ 1), m1 = mapa(bo, role ^ 1), d2 = mapa(d0, 2), m2 = mapa(bo, 2);
                asm volatile("" : "+r"(d0), "+r"(qa));
                mbar_wait(sbase + B_VX + 8 * (s & 1), ph);
                FS(1, 0);
                named_bar(2, 384);
                uint32_t qf[2][4];
#pragma unroll
                for (int k2 = 0; k2 < 2; k2++) ldsm_x4_t(qf[k2], qa + k2 * 512);
                score_group(qf, kf, d0, d1, m1, d2, m2);
                bar_arrive(5, 384);
            } else named_bar(2, 384);
            if (s == 0) {
                TSQ(3);
                int lane = lane_o;
                asm volatile("" : "+r"(lane));
                if (wq == 1) norms_gather(lane, scs);
                named_bar(3, 128);
                TSQ(4);
            }
            const float4 m4 = *reinterpret_cast<const float4*>(scs + 4);
            const float c24 = scs[1], xb = scs[16 + s];
            uint32_t vf[2][2][4], vm[2][2];
            {
                const uint32_t va = vb + (C ? to + DH * 16 : SM_VX + (s & 1) * 8192);
#pragma unroll
                for (int i = 0; i < 4; i++) ldsm_x4(vf[i >> 1][i & 1], va + (i >> 1) * 256 + (i & 1) * 4096);
            }
            float scale;
            {
                const float bound = fmaxf(fmaxf(fmaxf(m4.x, m4.y), fmaxf(m4.z, m4.w)) * minv, xb) * c24;
                int e = 141 - (int)((__float_as_uint(bound) >> 23) & 255u);
                e = e > 100 ? 100 : e;
                scale = __uint_as_float((uint32_t)(127 + e) << 23);
            }
            uint32_t s0 = l8 + (role & 1) * 1280, s1 = l8 + ((role & 1) ^ 1) * 1280, oa = l16 + wq * 512;
            asm volatile("" : "+f"(scale), "+r"(s0), "+r"(s1), "+r"(oa));
            FS(7, vf[1][1][0]);
            constexpr float EC = (float)(1.4426950408889634 * 0.08838834764831845);
            if (!C) named_bar(6, 160);
            if (C) mbar_wait(sbase + B_SB + 8 * (s & 1), ph);
            float sv[5][2];
#pragma unroll
            for (int j = 0; j < 5; j++) lds64f(sv[j][0], sv[j][1], s0 + SM_S + j * 256);
            if (!C) {
#pragma unroll
                for (int j = 0; j < 5; j++) { sv[j][0] *= EC; sv[j][1] *= EC; asm volatile("" : "+f"(sv[j][0]), "+f"(sv[j][1])); }
                mbar_wait(sbase + B_SB + 8 * (s & 1), ph);
            }
            FS(6, 0);
            uint32_t p[5];
            {
                float sr[5][2];
#pragma unroll
                for (int j = 0; j < 5; j++) lds64f(sr[j][0], sr[j][1], s1 + SM_S + j * 256);
                lds64(vm[0][0], vm[0][1], l8 + SM_VM + wq * 512);
                lds64(vm[1][0], vm[1][1], l8 + SM_VM + wq * 512 + 256);
                if (C) {
#pragma unroll
                    for (int j = 0; j < 5; j++) { sv[j][0] *= EC; sv[j][1] *= EC; }
                }
#pragma unroll
                for (int j = 0; j < 5; j++) { sv[j][0] = fmaf(sr[j][0], EC, sv[j][0]); sv[j][1] = fmaf(sr[j][1], EC, sv[j][1]); }
                float mx = fmaxf(fmaxf(fmaxf(sv[0][0], sv[0][1]), fmaxf(sv[1][0], sv[1][1])), fmaxf(fmaxf(sv[2][0], sv[2][1]), fmaxf(sv[3][0], sv[3][1])));
                mx = fmaxf(mx, fmaxf(sv[4][0], sv[4][1]));
                {
                    const float m1 = __shfl_xor_sync(0xffffffffu, mx, 1), m2 = __shfl_xor_sync(0xffffffffu, mx, 2), m3 = __shfl_xor_sync(0xffffffffu, mx, 3);
                    mx = fmaxf(fmaxf(mx, m1), fmaxf(m2, m3));
                }
#pragma unroll
                for (int jj = 0; jj < 5; jj++) {
                    const int j = (jj + 1) % 5;
                    asm("ex2.approx.ftz.f32 %0, %1;" : "=f"(sv[j][0]) : "f"(sv[j][0] - mx));
                    asm("ex2.approx.ftz.f32 %0, %1;" : "=f"(sv[j][1]) : "f"(sv[j][1] - mx));
                    p[j] = pack_bf16(sv[j][0], sv[j][1]);
                }
            }
            FS(0, p[0]);
            uint32_t b[4][4];
            float zs[4];
            {
                float o0[2][4], o1[2][4];
                mma_z(o0[0], vf[0][0], p[1], p[2]);
                mma_z(o0[1], vf[1][0], p[1], p[2]);
                mma_z(o1[0], vf[0][1], p[3], p[4]);
                mma_z(o1[1], vf[1][1], p[3], p[4]);
                mma_k8(o0[0], vm[0][0], vm[0][1], p[0]);
                mma_k8(o0[1], vm[1][0], vm[1][1], p[0]);
                const uint32_t one4[4] = {0x3f803f80u, 0x3f803f80u, 0x3f803f80u, 0x3f803f80u};
                mma_z(zs, one4, p[1], p[2]);
                mma_bf16(zs, one4, p[3], p[4]);
                mma_k8(zs, one4[0], one4[1], p[0]);
                uint32_t ow[4];
#pragma unroll
                for (int m = 0; m < 2; m++) {
                    ow[2 * m] = pack_bf16(o0[m][0] + o1[m][0], o0[m][1] + o1[m][1]);
                    ow[2 * m + 1] = pack_bf16(o0[m][2] + o1[m][2], o0[m][3] + o1[m][3]);
                }
                stsm_x4(oa + SM_O, ow[0], ow[1], ow[2], ow[3]);
                FS(2, 0);
#pragma unroll
                for (int i = 0; i < 4; i++) b[0][i] = movm(ow[i]);
            }
            float acc[3][2][4];
            named_bar(3, 128);
#pragma unroll
            for (int i = 1; i < 4; i++) ldsm_x4_t(b[i], l16 + SM_O + ((wq + i) & 3) * 512);
#pragma unroll
            for (int c = 0; c < 2; c++)
#pragma unroll
                for (int t = 0; t < 3; t++) mma_z(acc[t][c], wo[t][c], b[0][2 * c], b[0][2 * c + 1]);
            float z0, z1;
            asm volatile("rcp.approx.ftz.f32 %0, %1;" : "=f"(z0) : "f"(zs[0]));
            asm volatile("rcp.approx.ftz.f32 %0, %1;" : "=f"(z1) : "f"(zs[1]));
            z0 *= scale; z1 *= scale;
            FS(3, b[1][0]);
#pragma unroll
            for (int i = 1; i < 4; i++)
#pragma unroll
                for (int c = 0; c < 2; c++)
#pragma unroll
                    for (int t = 0; t < 3; t++) mma_bf16(acc[t][c], wo[t][2 * i + c], b[i][2 * c], b[i][2 * c + 1]);
            {
                uint32_t w[6];
#pragma unroll
                for (int t = 0; t < 3; t++) {
                    w[2 * t] = pack_f16(fmaf(acc[t][1][0], z0, acc[t][0][0] * z0), fmaf(acc[t][1][1], z1, acc[t][0][1] * z1));
                    w[2 * t + 1] = pack_f16(fmaf(acc[t][1][2], z0, acc[t][0][2] * z0), fmaf(acc[t][1][3], z1, acc[t][0][3] * z1));
                }
                FS(8, w[5]);
                asm volatile("red.relaxed.gpu.global.add.noftz.v4.f16x2 [%0], {%1,%2,%3,%4};" :: "l"(dst), "r"(w[0]), "r"(w[1]), "r"(w[2]), "r"(0x3c00u) : "memory");
                asm volatile("red.relaxed.gpu.global.add.noftz.v4.f16x2 [%0], {%1,%2,%3,%4};" :: "l"(dst + 4096), "r"(w[3]), "r"(w[4]), "r"(w[5]), "r"(0x3c00u) : "memory");
            }
            FS(9, 0);
            if (s == 0) TSQ(5);
            bar_arrive(4, 384);
            const uint32_t t0 = clock32();
            minv = __uint_as_float(0x7f000000u - __float_as_uint(scale));
            if (lane_o == 0) {
                if (wq == 0) scs[2] = minv;
                if (wq == 2 && C && s + 2 < NSEG) { while (clock32() - t0 < VX_DELAY) {} vx_copy(sbase, s + 1, 1); }
                if (s + 3 < NSEG) {
                    if (wq == 0) mbar_expect(sbase + B_SB + 8 * (s & 1), C ? 2560 : 1280 + 2048);
                    if (wq == 1) mbar_expect(sbase + B_XT + 8 * b3, XBUF);
                    if (wq == 3 && !C) mbar_expect(sbase + B_VX + 8 * (s & 1), 8192);
                }
            }
            __syncwarp();
#pragma unroll
            for (int k2 = 0; k2 < 2; k2++) if (!C) ldsm_x4_t(kf[k2], ka + ((s + 1) & 3) * TBUF + k2 * 512);
            const uint4* src = reinterpret_cast<const uint4*>(dst + (wq * 16 - role * 32) * 1024);
            dst += n3 == 0 ? -256 : 128;
            asm volatile("" : "+l"(dst));
            mx2 = poll_mem(src, l16 + SM_M + wq * 2304, t0);
            if (s == 0) TSQ(6);
            b3 = n3;
        }
        if (!C) bar_arrive(2, 384);
        };
        if (role == 2) helper_loop(Flag<true>()); else helper_loop(Flag<false>());
    }
    TS3C(1);
    if (role == 2 && warp >= 4) {
        const int sg = warp < 8, wq = warp & 3, lane = lane_o;
        const uint32_t qk = sbase + SM_X + XBUF + sg * (2 * 9216), ob = sbase + SM_X + 2 * XBUF + sg * 8192;
        TST(0);
        mbar_wait(sbase + B_VX + 8 * sg, 0);
        fence_async();
        TST(1);
        float sc[20];
        {
            const uint64_t da = smem_desc(qk + 1024, 128, 1024), db = smem_desc(qk, 128, 2048);
            wg_fence();
#pragma unroll
            for (int ks = 0; ks < 8; ks++) wgmma_n40_ss(sc, da + (uint64_t)((ks >> 2) * 576 + (ks & 3) * 16), db + (uint64_t)((ks >> 2) * 576 + (ks & 3) * 16), ks > 0);
            wg_commit();
            wg_wait0();
        }
        uint32_t pa[3][4];
        xrow_softmax(sc, pa, wq, lane);
        float o[2][32];
        const uint64_t dv = smem_desc(sbase + SM_T + ((NSEG - 2 + sg) & 3) * TBUF, 2048, 128);
        wg_fence();
#pragma unroll
        for (int hf = 0; hf < 2; hf++)
#pragma unroll
            for (int ks = 0; ks < 3; ks++) { if (ks == 0) wgmma_n64_z(o[hf], pa[0], dv + (uint64_t)(hf * 64)); else wgmma_n64(o[hf], pa[ks], dv + (uint64_t)(hf * 64 + ks * 256), 1); }
        wg_commit();
        wg_wait0();
#pragma unroll
        for (int hf = 0; hf < 2; hf++)
#pragma unroll
            for (int i = 0; i < 2; i++)
                stsm_x4(ob + hf * 4096 + wq * 1024 + i * 512 + lane * 16, pack_bf16(o[hf][16 * i], o[hf][16 * i + 1]), pack_bf16(o[hf][16 * i + 4], o[hf][16 * i + 5]),
                        pack_bf16(o[hf][16 * i + 8], o[hf][16 * i + 9]), pack_bf16(o[hf][16 * i + 12], o[hf][16 * i + 13]));
        fence_async();
        named_bar(11 + sg, 128);
        TST(2);
        if ((tid & 127) == 0) {
            unsigned char* dst = reinterpret_cast<unsigned char*>(g_ox) + ((size_t)((NSEG / 2 - 1) * NH + h)) * 16384 + sg * 4096;
            asm volatile("cp.async.bulk.global.shared::cta.bulk_group [%0], [%1], 4096;" :: "l"(dst), "r"(ob) : "memory");
            asm volatile("cp.async.bulk.global.shared::cta.bulk_group [%0], [%1], 4096;" :: "l"(dst + 8192), "r"(ob + 4096) : "memory");
            asm volatile("cp.async.bulk.commit_group;" ::: "memory");
            asm volatile("cp.async.bulk.wait_group 0;" ::: "memory");
            asm volatile("red.relaxed.gpu.global.add.u32 [%0], 1;" :: "l"(&g_prog[(NSEG / 2 - 1) * 8 + (h >> 2)]) : "memory");
        }
        TST(3);
    }
    __syncwarp();
    cluster_sync_all();
}

extern "C" void kernel_launch(void* const* d_in, const int* in_sizes, int n_in, void* d_out, int out_size) {
    const bf16* x = (const bf16*)d_in[0];
    const bf16* mem0 = (const bf16*)d_in[1];
    const bf16* Wq = (const bf16*)d_in[2];
    const bf16* Wk = (const bf16*)d_in[3];
    const bf16* Wv = (const bf16*)d_in[4];
    const bf16* Wo = (const bf16*)d_in[5];
    const bf16* logA = (const bf16*)d_in[8];
    const bf16* Aim = (const bf16*)d_in[9];
    const bf16* Cre = (const bf16*)d_in[10];
    const bf16* Cim = (const bf16*)d_in[11];
    const bf16* logdt = (const bf16*)d_in[12];
    const bf16* dskip = (const bf16*)d_in[13];
    const bf16* gw = (const bf16*)d_in[14];
    bf16* out = (bf16*)d_out;
    static bool attr_done = false;
    typedef CUresult (*EncFn)(CUtensorMap*, CUtensorMapDataType, cuuint32_t, void*, const cuuint64_t*, const cuuint64_t*, const cuuint32_t*,
                              const cuuint32_t*, CUtensorMapInterleave, CUtensorMapSwizzle, CUtensorMapL2promotion, CUtensorMapFloatOOBfill);
    static EncFn enc = nullptr;
    if (!attr_done) {
        void* fn = nullptr;
        cudaDriverEntryPointQueryResult qr;
        cudaGetDriverEntryPoint("cuTensorMapEncodeTiled", &fn, cudaEnableDefault, &qr);
        enc = (EncFn)fn;
        cudaFuncSetAttribute(k_chain, cudaFuncAttributeMaxDynamicSharedMemorySize, 232448);
        cudaFuncSetAttribute(k_side, cudaFuncAttributeMaxDynamicSharedMemorySize, SIDE_SMEM);
        attr_done = true;
    }
    CUtensorMap tmx;
    {
        const cuuint64_t dims[3] = {64, (cuuint64_t)S_LEN, 9};
        const cuuint64_t strides[2] = {(cuuint64_t)DM * 2, 128};
        const cuuint32_t box[3] = {64, (cuuint32_t)SEG, 3};
        const cuuint32_t es[3] = {1, 1, 1};
        enc(&tmx, CU_TENSOR_MAP_DATA_TYPE_BFLOAT16, 3, (void*)x, dims, strides, box, es, CU_TENSOR_MAP_INTERLEAVE_NONE,
            CU_TENSOR_MAP_SWIZZLE_128B, CU_TENSOR_MAP_L2_PROMOTION_L2_128B, CU_TENSOR_MAP_FLOAT_OOB_FILL_NONE);
    }
    CUtensorMap tmw[3];
    for (int i = 0; i < 3; i++) {
        const cuuint64_t dims[2] = {(cuuint64_t)HD, (cuuint64_t)DM};
        const cuuint64_t strides[1] = {(cuuint64_t)HD * 2};
        const cuuint32_t box[2] = {64, 64};
        const cuuint32_t es[2] = {1, 1};
        enc(&tmw[i], CU_TENSOR_MAP_DATA_TYPE_BFLOAT16, 2, (void*)(i == 0 ? Wq : (i == 1 ? Wk : Wv)), dims, strides, box, es, CU_TENSOR_MAP_INTERLEAVE_NONE,
            CU_TENSOR_MAP_SWIZZLE_128B, CU_TENSOR_MAP_L2_PROMOTION_L2_256B, CU_TENSOR_MAP_FLOAT_OOB_FILL_NONE);
    }
    CUtensorMap tmo;
    {
        const cuuint64_t dims[2] = {(cuuint64_t)DM, (cuuint64_t)HD};
        const cuuint64_t strides[1] = {(cuuint64_t)DM * 2};
        const cuuint32_t box[2] = {64, 128};
        const cuuint32_t es[2] = {1, 1};
        enc(&tmo, CU_TENSOR_MAP_DATA_TYPE_BFLOAT16, 2, (void*)Wo, dims, strides, box, es, CU_TENSOR_MAP_INTERLEAVE_NONE,
            CU_TENSOR_MAP_SWIZZLE_128B, CU_TENSOR_MAP_L2_PROMOTION_L2_128B, CU_TENSOR_MAP_FLOAT_OOB_FILL_NONE);
    }
    CUtensorMap tmx2;
    {
        const cuuint64_t dims[2] = {(cuuint64_t)DM, (cuuint64_t)S_LEN};
        const cuuint64_t strides[1] = {(cuuint64_t)DM * 2};
        const cuuint32_t box[2] = {64, 64};
        const cuuint32_t es[2] = {1, 1};
        enc(&tmx2, CU_TENSOR_MAP_DATA_TYPE_BFLOAT16, 2, (void*)x, dims, strides, box, es, CU_TENSOR_MAP_INTERLEAVE_NONE,
            CU_TENSOR_MAP_SWIZZLE_128B, CU_TENSOR_MAP_L2_PROMOTION_L2_128B, CU_TENSOR_MAP_FLOAT_OOB_FILL_NONE);
    }
    k_chain<<<NCTA, 384, 232448>>>(tmx, tmw[0], tmw[1], tmw[2], tmx2, tmo, mem0, x);
    {
        cudaLaunchConfig_t cfg = {};
        cfg.gridDim = dim3(SD_NCTA); cfg.blockDim = dim3(512); cfg.dynamicSmemBytes = SIDE_SMEM; cfg.stream = cudaStreamPerThread;
        cudaLaunchAttribute at[1];
        at[0].id = cudaLaunchAttributeProgrammaticStreamSerialization;
        at[0].val.programmaticStreamSerializationAllowed = 1;
        cfg.attrs = at; cfg.numAttrs = 1;
        cudaLaunchKernelEx(&cfg, k_side, tmo, x, logA, Aim, Cre, Cim, logdt, Wo, dskip, gw, out);
    }
}
```

```cpp
#include <cuda_runtime.h>
#include <cuda.h>
#include <cuda_bf16.h>
#include <stdint.h>

typedef __nv_bfloat16 bf16;
#define LDV4 "ld.volatile.global.v4.u32 {%0,%1,%2,%3}, [%4];"
#define STV4 "st.volatile.global.v4.u32 [%0], {%1,%2,%3,%4};"
#define STV2 "st.volatile.global.v2.u32 [%0], {%1,%2};"

constexpr int S_LEN = 2048, DM = 576, NH = 32, DH = 128, HD = 4096, MEMT = 8, SEG = 32, NSEG = 64, NST = 128;

__device__ __align__(128) bf16 g_gate[S_LEN];
constexpr int NCTA = NH * 3;
__device__ __align__(1024) unsigned char g_acc[96 * 1024];
__device__ __align__(128) uint2 g_norm[NCTA];
__device__ __align__(128) uint32_t g_rx[NSEG];
__device__ __align__(128) unsigned char g_qkv[NSEG][NH][3][10240];
__device__ __align__(128) bf16 g_ox[S_LEN * HD];
__device__ __align__(128) uint4 g_fp[8][36][6][128];
__device__ __align__(128) unsigned g_flag[NH * NSEG];
__device__ unsigned g_prog[NSEG / 2 * 8];
__device__ unsigned g_gcnt[64];
__device__ unsigned g_epoch;
__device__ __align__(128) uint2 g_tick;
__device__ __align__(16) bf16 g_y[DM * S_LEN];

#define TS3(slot) do {} while (0)
#define TS3P(slot) do {} while (0)
#define TSQ(slot) do {} while (0)
#define TS3W(slot) do {} while (0)
#define TSS(row, slot) do {} while (0)
#define TS3C(slot) do {} while (0)
#define TST(slot) do {} while (0)
#define TSA(seg, slot) do {} while (0)
#define TSG(i) do {} while (0)
#define FS(i, dep) do {} while (0)
__device__ __forceinline__ uint32_t smem_u32(const void* p) { return (uint32_t)__cvta_generic_to_shared(p); }
__device__ __forceinline__ float bf16r(float x) { return __bfloat162float(__float2bfloat16_rn(x)); }
__device__ __forceinline__ uint32_t pack_bf16(float lo, float hi) {
    __nv_bfloat162 v = __floats2bfloat162_rn(lo, hi);
    return *reinterpret_cast<uint32_t*>(&v);
}
__device__ __forceinline__ void ldsm_x4(uint32_t (&r)[4], uint32_t addr) {
    asm volatile("ldmatrix.sync.aligned.m8n8.x4.shared.b16 {%0,%1,%2,%3}, [%4];"
                 : "=r"(r[0]), "=r"(r[1]), "=r"(r[2]), "=r"(r[3]) : "r"(addr));
}
__device__ __forceinline__ void ldsm_x4_t(uint32_t (&r)[4], uint32_t addr) {
    asm volatile("ldmatrix.sync.aligned.m8n8.x4.trans.shared.b16 {%0,%1,%2,%3}, [%4];"
                 : "=r"(r[0]), "=r"(r[1]), "=r"(r[2]), "=r"(r[3]) : "r"(addr));
}
__device__ __forceinline__ void mma_bf16(float (&d)[4], const uint32_t (&a)[4], uint32_t b0, uint32_t b1) {
    asm volatile("mma.sync.aligned.m16n8k16.row.col.f32.bf16.bf16.f32 {%0,%1,%2,%3}, {%4,%5,%6,%7}, {%8,%9}, {%0,%1,%2,%3};"
                 : "+f"(d[0]), "+f"(d[1]), "+f"(d[2]), "+f"(d[3])
                 : "r"(a[0]), "r"(a[1]), "r"(a[2]), "r"(a[3]), "r"(b0), "r"(b1));
}
__device__ __forceinline__ uint2 ld_vol_u2(const uint2* p) {
    uint2 v; asm volatile("ld.volatile.global.v2.u32 {%0,%1}, [%2];" : "=r"(v.x), "=r"(v.y) : "l"(p) : "memory"); return v;
}
__device__ __forceinline__ void st_vol_u2(uint2* p, uint2 v) {
    asm volatile(STV2 :: "l"(p), "r"(v.x), "r"(v.y) : "memory");
}
__device__ __forceinline__ unsigned ld_acq(const unsigned* p) {
    unsigned v; asm volatile("ld.acquire.gpu.global.u32 %0, [%1];" : "=r"(v) : "l"(p) : "memory"); return v;
}
#define XK 36
#define NC1 7
#define NS 6
#define NP 4
#define X_OXSZ 16384
#define GATE_A 1220
#define GATE_B 430
#define GATE_P 1880u
#define STAGGER 0
#define RLX_SLEEP 300
#define VX_DELAY 100
#define EARLY4 0
#define SPEC_M 1
#define SPEC_H 1
#define C1_DELAY 0
#define C2_DELAY 0
#define SS_POS 2
#define UNGATE_G 3
#define GATE_Y 0
#define GATE_S 1
#define GATE_F 1
#define TL_DELAY 600
#define POLL_DELAY 500
#define UNGATE 6
constexpr unsigned SPIN_LIMIT = 1u << 20;
constexpr int NATT = NSEG - 2;

constexpr int SD_CH = 16;
constexpr int SD_NCTA = DM / SD_CH;
constexpr int SD_ROW = 528;
constexpr int SD_U = 8 * SD_ROW;
constexpr int SD_TAP = 5888;
constexpr int SD_CPY = 1376 * 2;
constexpr int SD_WSTR = SD_TAP + 2 * SD_CPY;
constexpr int SD_SMEM = SD_CH * SD_U + 8 * SD_WSTR;
constexpr int O_U = 79, O_U3 = 911, O_U4 = 1055, O_W79 = 1023, O_W35 = 1151, O_W610 = 1279, O_W511 = 1487;

__device__ __forceinline__ uint32_t lds32(uint32_t a) { uint32_t v; asm volatile("ld.shared.u32 %0, [%1];" : "=r"(v) : "r"(a)); return v; }
__device__ __forceinline__ void tap_tile(uint32_t (&t)[4], uint32_t a) {
    asm volatile("ld.volatile.shared.u32 %0, [%4];\nld.volatile.shared.u32 %1, [%4+-16];\nld.volatile.shared.u32 %2, [%4+16];\nld.volatile.shared.u32 %3, [%4];"
                 : "=r"(t[0]), "=r"(t[1]), "=r"(t[2]), "=r"(t[3]) : "r"(a));
}
constexpr uint32_t sd_pass(int type, int dl, int o, int d0, int d1) { return (uint32_t)(type | dl << 2 | d0 << 8 | d1 << 12 | o << 17); }
__constant__ uint32_t SD_PASS[14] = {sd_pass(0, 0, O_U, 0, 2), sd_pass(0, 1, O_U + 96, 0, 2), sd_pass(0, 2, O_U + 192, 0, 4), sd_pass(0, 3, O_U + 288, 0, 2), sd_pass(1, 0, O_U3, 8, 8),
                                     sd_pass(0, 4, O_U + 384, 0, 2), sd_pass(1, 0, O_U4, 8, 15), sd_pass(0, 5, O_U + 480, 0, 2), sd_pass(0, 6, O_U + 576, 0, 4), sd_pass(0, 7, O_U + 672, 0, 2),
                                     sd_pass(2, 0, O_W35, 2, 8), sd_pass(3, 0, O_W79, 2, 4), sd_pass(2, 1, O_W610, 4, 8), sd_pass(3, 0, O_W511, 8, 15)};
__device__ __forceinline__ uint32_t band2(int x, int lo, int hi) { return (x >= lo && x <= hi ? 0x3f80u : 0u) | (x + 1 >= lo && x + 1 <= hi ? 0x3f800000u : 0u); }
__device__ __forceinline__ void mma_z(float (&d)[4], const uint32_t (&a)[4], uint32_t b0, uint32_t b1);
__device__ __forceinline__ void put_tap(uint32_t a, float v) {
    asm volatile("{\n.reg .b16 h;\ncvt.rn.bf16.f32 h, %1;\nst.shared.b16 [%0], h;\nst.shared.b16 [%0+%2], h;\n}" :: "r"(a), "f"(v), "n"(SD_CPY - 2) : "memory");
}

__device__ __forceinline__ void named_bar(int id, int n) { asm volatile("bar.sync %0, %1;" :: "r"(id), "r"(n) : "memory"); }
__device__ __forceinline__ uint32_t pack_f16(float lo, float hi) {
    uint32_t r; asm("cvt.rn.f16x2.f32 %0, %1, %2;" : "=r"(r) : "f"(hi), "f"(lo)); return r;
}
__device__ __forceinline__ void cexp_t(float lr, float turns, float& re, float& im) {
    float m;
    asm("ex2.approx.ftz.f32 %0, %1;" : "=f"(m) : "f"(lr));
    const float a = (turns - rintf(turns)) * 6.283185307179586f;
    re = m * __cosf(a); im = m * __sinf(a);
}
__device__ __forceinline__ void csq(float& re, float& im) { const float r = re * re - im * im; im = 2.f * re * im; re = r; }
__device__ __forceinline__ void kb_state(const float* tp, float gf, uint32_t (&a)[4][2], uint32_t (&b)[5]) {
    const float4 p0 = *reinterpret_cast<const float4*>(tp), p1 = *reinterpret_cast<const float4*>(tp + 4);
    float wr, wi;
    cexp_t(p0.x * gf, p0.y * gf, wr, wi);
    float vr = wr * p1.x - wi * p1.y, vi = wr * p1.y + wi * p1.x;
#pragma unroll
    for (int c = 0; c < 4; c++) {
        a[c][0] = pack_f16(wr, wi); a[c][1] = pack_f16(vr, vi);
        csq(wr, wi);
        if (c < 3) csq(vr, vi);
    }
    b[0] = pack_f16(p0.z * wr - p0.w * wi, -p0.z * wi - p0.w * wr);
    float er = wr * p1.z - wi * p1.w, ei = wr * p1.w + wi * p1.z;
#pragma unroll
    for (int c = 0; c < 4; c++) {
        b[1 + c] = pack_f16(p0.z * er - p0.w * ei, -p0.z * ei - p0.w * er);
        if (c < 3) csq(er, ei);
    }
}
__device__ __forceinline__ uint32_t bf2_mul(uint32_t a, uint32_t b) { uint32_t r; asm("mul.rn.bf16x2 %0, %1, %2;" : "=r"(r) : "r"(a), "r"(b)); return r; }
__device__ __forceinline__ uint32_t bf2_add(uint32_t a, uint32_t b) { uint32_t r; asm("add.rn.bf16x2 %0, %1, %2;" : "=r"(r) : "r"(a), "r"(b)); return r; }
__device__ __forceinline__ uint32_t bf2_sub(uint32_t a, uint32_t b) { uint32_t r; asm("sub.rn.bf16x2 %0, %1, %2;" : "=r"(r) : "r"(a), "r"(b)); return r; }
__device__ __forceinline__ void wait_cnt(const unsigned* p, unsigned target) {
    unsigned it = 0;
    while ((int)(ld_acq(p) - target) < 0 && ++it < SPIN_LIMIT) __nanosleep(64);
}
__device__ __forceinline__ uint32_t gtime32() { uint32_t t; asm volatile("mov.u32 %0, %%globaltimer_lo;" : "=r"(t) :: "memory"); return t; }
__device__ __forceinline__ void gate(uint32_t tick_addr) {
    uint32_t t1, p;
    asm volatile("ld.volatile.shared.v2.u32 {%0,%1}, [%2];" : "=r"(t1), "=r"(p) : "r"(tick_addr) : "memory");
    uint32_t d = gtime32() - t1;
    if (d < 4u * p) {
        d -= d >= 2u * p ? 2u * p : 0u;
        d -= d >= p ? p : 0u;
        if (d + GATE_A >= p && d + GATE_B < p) {
            const uint32_t t2 = gtime32() + (p - GATE_B - d);
            while ((int)(gtime32() - t2) < 0) {}
        }
    }
}

__device__ __forceinline__ void read_tick(uint32_t tick_addr) {
    const uint2 tk = ld_vol_u2(&g_tick);
    uint32_t p = tk.x - tk.y;
    p = p > GATE_P + 100u ? GATE_P + 100u : p;
    asm volatile("st.volatile.shared.v2.u32 [%0], {%1,%2};" :: "r"(tick_addr), "r"(tk.x), "r"(p) : "memory");
}

__device__ __forceinline__ void s4d_phase(unsigned char* smem_raw, const bf16* __restrict__ x, const bf16* __restrict__ logA,
                                          const bf16* __restrict__ Aim, const bf16* __restrict__ Cre, const bf16* __restrict__ Cim,
                                          const bf16* __restrict__ logdt, const bf16* __restrict__ dskip, const bf16* __restrict__ wslice, unsigned ep, uint32_t tick) {
    const int tid = threadIdx.x, warp = __shfl_sync(0xffffffffu, tid >> 5, 0), lane = tid & 31;
    const int d0 = blockIdx.x * SD_CH;
    float* tab = reinterpret_cast<float*>(smem_raw + SD_CH * SD_U + warp * SD_WSTR);
    const uint32_t wb = smem_u32(tab);
    const int g = lane >> 2, tq = lane & 3;
    uint2 prm[4];
    float ldt;
    auto load_prm = [&](int d) {
        prm[0] = __ldg(reinterpret_cast<const uint2*>(logA + d * NST) + lane); prm[1] = __ldg(reinterpret_cast<const uint2*>(Aim + d * NST) + lane);
        prm[2] = __ldg(reinterpret_cast<const uint2*>(Cre + d * NST) + lane); prm[3] = __ldg(reinterpret_cast<const uint2*>(Cim + d * NST) + lane);
        ldt = __bfloat162float(logdt[d]);
    };
    load_prm(d0 + warp);
    for (int i = lane; i < 2 * SD_CPY / 16; i += 32) reinterpret_cast<uint4*>(tab + SD_TAP / 4)[i] = make_uint4(0u, 0u, 0u, 0u);
    TS3(20);
#pragma unroll 1
    for (int ch = 0; ch < 2; ch++) {
        const int d = d0 + 8 * ch + warp;
        const uint32_t ub = smem_u32(smem_raw) + (8 * ch + warp) * SD_U;
        float k2048 = 0.f, sinv;
        {
            const float dt = bf16r(expf(ldt));
            uint32_t cm = __vmaxu2(__vmaxu2(prm[2].x & 0x7fff7fffu, prm[2].y & 0x7fff7fffu), __vmaxu2(prm[3].x & 0x7fff7fffu, prm[3].y & 0x7fff7fffu));
            cm = __reduce_max_sync(0xffffffffu, max(cm << 16, cm & 0xffff0000u));
            int e = 134 - (int)(__float_as_uint(__uint_as_float(cm) * dt) >> 23);
            e = e > 100 ? 100 : (e < -100 ? -100 : e);
            const float s2 = __uint_as_float((uint32_t)(128 + e) << 23);
            sinv = __uint_as_float((uint32_t)(127 - e) << 23);
#pragma unroll
            for (int j = 0; j < 4; j++) {
                float q[4];
#pragma unroll
                for (int i = 0; i < 4; i++) { const uint32_t w = j < 2 ? prm[i].x : prm[i].y; q[i] = __uint_as_float((j & 1) ? w & 0xffff0000u : w << 16); }
                const float zl = -bf16r(expf(q[0])) * dt * 1.4426950408889634f;
                const float zt = q[1] * dt * 0.15915494309189535f;
                const float cr = s2 * (q[2] * dt), ci = s2 * (q[3] * dt);
                float ar, ai, br, bi, er, ei;
                cexp_t(zl * 8.f, zt * 8.f, ar, ai);
                cexp_t(zl * 128.f, zt * 128.f, br, bi);
                cexp_t(zl * 2048.f, zt * 2048.f, er, ei);
                k2048 += cr * er - ci * ei;
                *reinterpret_cast<float4*>(tab + (lane + 32 * j) * 8) = make_float4(zl, zt, cr, ci);
                *reinterpret_cast<float4*>(tab + (lane + 32 * j) * 8 + 4) = make_float4(ar, ai, br, bi);
            }
#pragma unroll
            for (int o = 16; o; o >>= 1) k2048 += __shfl_xor_sync(0xffffffffu, k2048, o);
        }
        __syncwarp();
        {
            float kc[5][4];
#pragma unroll
            for (int i = 0; i < 5; i++) { kc[i][0] = kc[i][1] = kc[i][2] = kc[i][3] = 0.f; }
            const float gf = (float)g;
#pragma unroll 2
            for (int ks = 0; ks < 16; ks++) {
                uint32_t a0[4][2], a1[4][2], b0[5], b1[5];
                kb_state(tab + (8 * ks + tq) * 8, gf, a0, b0);
                kb_state(tab + (8 * ks + 4 + tq) * 8, gf, a1, b1);
#pragma unroll
                for (int i = 0; i < 5; i++) {
                    const int c = i > 0 ? i - 1 : 0;
                    asm volatile("mma.sync.aligned.m16n8k16.row.col.f32.f16.f16.f32 {%0,%1,%2,%3}, {%4,%5,%6,%7}, {%8,%9}, {%0,%1,%2,%3};"
                                 : "+f"(kc[i][0]), "+f"(kc[i][1]), "+f"(kc[i][2]), "+f"(kc[i][3])
                                 : "r"(a0[c][0]), "r"(a0[c][1]), "r"(a1[c][0]), "r"(a1[c][1]), "r"(b0[i]), "r"(b1[i]));
                }
            }
            const uint32_t tp = wb + SD_TAP;
            const uint32_t a0 = tp + 2 * (O_U + 96 * g - 4 * tq);
            const uint32_t a2 = tp + 2 * (((g & 1) ? O_U + 96 * (2 * (g & 3)) : ((g & 2) ? O_W35 : O_W79 + 1)) - 32 - 8 * tq - (g >> 2));
            const uint32_t a3 = tp + 2 * (((g & 1) ? O_W35 : O_W610 + 1) - 64 - 16 * tq - (g >> 1));
            const uint32_t a4 = tp + 2 * (-128 - 32 * tq - g);
#pragma unroll
            for (int c = 0; c < 4; c++) {
                const int e = (c & 1) * 16 + (c >> 1) * 8;
                const bool first = c == 0 && lane == 0;
                put_tap(a0 - e / 4, kc[0][c] * sinv);
                put_tap(a0 - 32 - e / 4, kc[1][c] * sinv);
                put_tap(first ? tp + 2 * (O_U - 32) : a2 - e / 2, kc[2][c] * sinv);
                put_tap(first ? tp + 2 * (O_W79 - 63) : a3 - e, kc[3][c] * sinv);
                put_tap(first ? tp + 2 * (O_W610 - 127) : a4 + 2 * (O_W511 + 1 - e), kc[4][c] * sinv);
                if ((g & 1) == 0) {
                    put_tap(a4 + 2 * (O_U4 - e), kc[4][c] * sinv);
                    put_tap(first ? tp + 2 * (O_U3 - 128) : a4 + 2 * (O_U4 + 1 - e), kc[4][c] * sinv);
                }
            }
            if (lane == 0) {
                put_tap(tp + 2 * (O_U + 96 - 32), kc[2][0] * sinv);
                put_tap(tp + 2 * (O_U + 192 - 64), kc[3][0] * sinv);
                put_tap(tp + 2 * (O_W511 - 255), k2048 * sinv);
                put_tap(tp + 2 * (O_U4 - 255), k2048 * sinv);
            }
        }
        TS3(21 + 2 * ch);
        if (ch == 0) { if (!STAGGER || warp < 4) named_bar(1, 384); }
        else {
#pragma unroll
            for (int i = 0; i < 4; i++) asm volatile("prefetch.global.L2 [%0];" :: "l"(wslice + (size_t)((tid & 127) + 128 * i) * DM));
        }
        __syncwarp();
        if (tid == 0) TSS(18, 4 * ch);
        const uint32_t sh = wb + 80 + 11 * SD_ROW;
#pragma unroll
        for (int p = 0; p < 8; p++) {
            uint4 v;
            asm volatile("ld.shared.v4.u32 {%0,%1,%2,%3}, [%4];" : "=r"(v.x), "=r"(v.y), "=r"(v.z), "=r"(v.w) : "r"(ub + p * SD_ROW + lane * 16) : "memory");
            uint32_t pv = __shfl_up_sync(0xffffffffu, v.w, 1);
            pv = lane == 0 ? 0u : pv;
            asm volatile("st.shared.v4.u32 [%0], {%1,%2,%3,%4};" :: "r"(sh + (p - 8) * SD_ROW + lane * 16), "r"(__byte_perm(pv, v.x, 0x5432)), "r"(__byte_perm(v.x, v.y, 0x5432)),
                         "r"(__byte_perm(v.y, v.z, 0x5432)), "r"(__byte_perm(v.z, v.w, 0x5432)) : "memory");
            if (p >= 5) asm volatile("st.shared.v4.u32 [%0], {%1,%2,%3,%4};" :: "r"(sh + (p - 16) * SD_ROW + lane * 16), "r"(pv), "r"(v.x), "r"(v.y), "r"(v.z) : "memory");
        }
        __syncwarp();
        if (tid == 0) TSS(18, 4 * ch + 1);
        float acc[16][4];
#pragma unroll
        for (int i = 0; i < 16; i++) { acc[i][0] = acc[i][1] = acc[i][2] = acc[i][3] = 0.f; }
        {
            const uint32_t ka = wb + SD_TAP + ((g & 1) ? 0 : SD_CPY - 2) + 2 * (2 * tq - g);
            uint32_t b[16][2], b2[14][2];
#pragma unroll
            for (int k = 0; k < 16; k++) { b[k][0] = b[k][1] = 0u; if (k < 14) b2[k][0] = b2[k][1] = 0u; }
#pragma unroll 1
            for (int ps = 0; ps < 14; ps++) {
                const uint32_t pw = __shfl_sync(0xffffffffu, SD_PASS[ps], 0), type = pw & 3u, kp = ka + (pw >> 16);
                const int dl = (pw >> 2) & 7, d0 = (pw >> 8) & 15, d1 = (pw >> 12) & 15;
                uint32_t t[2][4];
                tap_tile(t[0], kp - 32 * d0);
                if (type == 0) {
                    const int p = (lane & 7) - dl;
                    const uint32_t ra = (p < 0 ? sh : ub) + p * SD_ROW + (lane >> 3) * 16;
#pragma unroll
                    for (int k = 0; k < 8; k++)
                        asm volatile("ldmatrix.sync.aligned.m8n8.x4.shared.b16 {%0,%1,%2,%3}, [%4];"
                                     : "=r"(b[2 * k][0]), "=r"(b[2 * k][1]), "=r"(b[2 * k + 1][0]), "=r"(b[2 * k + 1][1]) : "r"(ra + k * 64));
                } else if (type == 2) {
                    const int p = (lane & 15) - 11, xo = 2 * tq - g;
                    const uint32_t qa = (p < 0 ? sh : ub) + p * SD_ROW + (lane >> 4) * 16;
                    const int lx = 6 - 5 * dl, hx = 8 - 3 * dl, ly = 2 - 2 * dl, hy = 4 + 2 * dl;
                    const uint32_t sel[4] = {band2(xo, lx, hx), band2(xo, ly, hy), band2(xo + 8, lx, hx), band2(xo + 8, ly, hy)};
#pragma unroll
                    for (int k = 0; k < 14; k++) {
                        uint32_t q[4];
                        ldsm_x4_t(q, qa + k * 32);
#pragma unroll
                        for (int i = 0; i < 2; i++) {
                            float w[4];
                            mma_z(w, sel, q[2 * i], q[2 * i + 1]);
                            b[k][i] = pack_bf16(w[0], w[1]);
                            b2[k][i] = pack_bf16(w[2], w[3]);
                        }
                    }
                } else if (type == 3) {
#pragma unroll
                    for (int k = 0; k < 14; k++) { b[k][0] = b2[k][0]; b[k][1] = b2[k][1]; }
                }
#pragma unroll
                for (int d = 0; d < 16; d += 2) {
                    if (d >= 8 || d >= d0) {
                        tap_tile(t[1], kp - 32 * (d + 1));
#pragma unroll
                        for (int k = 0; k + d < 16; k++) mma_bf16(acc[k + d], t[0], b[k][0], b[k][1]);
                        if ((d == 2 || d == 4 || d == 8) && d == d1) break;
                        if (d < 14) tap_tile(t[0], kp - 32 * (d + 2));
#pragma unroll
                        for (int k = 0; k + d + 1 < 16; k++) mma_bf16(acc[k + d + 1], t[1], b[k][0], b[k][1]);
                    }
                }
            }
        }
        __syncwarp();
        if (tid == 0) TSS(18, 4 * ch + 2);
        load_prm(d0 + 8 + warp);
        if (ch == 0) { if (lane == 0) wait_cnt(&g_gcnt[0], SD_NCTA * ep); __syncwarp(); }
        if (tid == 0) TSS(18, 4 * ch + 3);
        uint4 gv[8];
#pragma unroll
        for (int i = 0; i < 8; i++) gv[i] = __ldcg(reinterpret_cast<const uint4*>(g_gate) + lane + 32 * i);
        const uint32_t dd = __byte_perm(*reinterpret_cast<const unsigned short*>(dskip + d), 0u, 0x1010);
#pragma unroll
        for (int i = 0; i < 8; i++) {
            uint32_t u[4];
            ldsm_x4_t(u, ub + (lane & 7) * SD_ROW + (lane >> 3) * 16 + i * 64);
            asm volatile("stmatrix.sync.aligned.m8n8.x4.shared.b16 [%0], {%1,%2,%3,%4};"
                         :: "r"(wb + (lane + 32 * i) * 16),
                            "r"(bf2_add(pack_bf16(acc[2 * i][0], acc[2 * i][1]), bf2_mul(u[0], dd))), "r"(bf2_add(pack_bf16(acc[2 * i][2], acc[2 * i][3]), bf2_mul(u[1], dd))),
                            "r"(bf2_add(pack_bf16(acc[2 * i + 1][0], acc[2 * i + 1][1]), bf2_mul(u[2], dd))), "r"(bf2_add(pack_bf16(acc[2 * i + 1][2], acc[2 * i + 1][3]), bf2_mul(u[3], dd))) : "memory");
        }
        if (GATE_Y) gate(tick);
        __syncwarp();
#pragma unroll
        for (int i = 0; i < 8; i++) {
            const uint4 y = *reinterpret_cast<const uint4*>(tab + (lane + 32 * i) * 4);
            *reinterpret_cast<uint4*>(g_y + (size_t)d * S_LEN + (lane + 32 * i) * 8) =
                make_uint4(bf2_mul(bf2_sub(0x3f803f80u, gv[i].x), y.x), bf2_mul(bf2_sub(0x3f803f80u, gv[i].y), y.y),
                           bf2_mul(bf2_sub(0x3f803f80u, gv[i].z), y.z), bf2_mul(bf2_sub(0x3f803f80u, gv[i].w), y.w));
        }
        __syncwarp();
        TS3(22 + 2 * ch);
    }
}
__device__ __forceinline__ void s4d_stage_u(unsigned char* smem_raw, const bf16* __restrict__ x, int pt) {
    const int p = pt & 7, w0 = pt >> 3;
    const uint4* src = reinterpret_cast<const uint4*>(x + (size_t)(16 * w0 + p) * DM + blockIdx.x * SD_CH);
    uint32_t* dst = reinterpret_cast<uint32_t*>(smem_raw + p * SD_ROW) + w0;
#pragma unroll 1
    for (int b = 0; b < 4; b++) {
        uint4 v[2][2][2];
#pragma unroll
        for (int i = 0; i < 8; i++) v[i >> 2][(i >> 1) & 1][i & 1] = src[((b * 2 + (i >> 2)) * 256 + ((i >> 1) & 1) * 8) * (DM / 8) + (i & 1)];
#pragma unroll
        for (int i = 0; i < 4; i++) {
            const uint32_t* lo = reinterpret_cast<const uint32_t*>(&v[i >> 1][0][i & 1]);
            const uint32_t* hi = reinterpret_cast<const uint32_t*>(&v[i >> 1][1][i & 1]);
#pragma unroll
            for (int c = 0; c < 8; c++) dst[((i & 1) * 8 + c) * (SD_U / 4) + (b * 2 + (i >> 1)) * 16] = __byte_perm(lo[c >> 1], hi[c >> 1], (c & 1) ? 0x7632 : 0x5410);
        }
    }
    asm volatile("bar.arrive 1, 384;" ::: "memory");
}

constexpr int WOC = DM / 3;
constexpr int TBUF = 5 * DH * 16;
constexpr int XBUF = SEG * DM * 2;
constexpr float ATT_SCALE = 0.08838834764831845f;
constexpr int SM_BAR = 0;
constexpr int B_SB = 0, B_VX = 16, B_XT = 32, B_W = 64, B_E = 136;
constexpr int SM_SC = 256;
constexpr int SM_F = SM_SC + 1280;
constexpr int SM_VM = SM_F + 2048;
constexpr int SM_S = SM_VM + 2048;
constexpr int SM_O = SM_S + 2560;
constexpr int SM_M = SM_O + 2048;
constexpr int SM_WS = 19456;
constexpr int SM_T = SM_WS + 32768;
constexpr int SM_VX = SM_T + 4 * TBUF;
constexpr int SM_X = SM_VX + 2 * 8192;
constexpr int SM_X01 = SM_WS + DM * DH * 2;
__host__ __device__ constexpr int x01_off(int b) { return b == 2 ? 2048 : SM_X01 + (b < 2 ? b + 6 : b - 3) * 8192; }
constexpr int SM_E = SM_WS + 6 * 16384;
constexpr int CH_SMEM = SM_X01 + 8 * 8192;
static_assert(SM_M + DM * 16 <= SM_WS && SM_X + 3 * XBUF <= CH_SMEM && CH_SMEM <= 232448 && SM_X % 1024 == 0 && SM_X01 % 1024 == 0 && SM_M >= 10240 && SM_F <= 2048, "smem");
__device__ __forceinline__ uint32_t clock32() { uint32_t t; asm volatile("mov.u32 %0, %%clock;" : "=r"(t) :: "memory"); return t; }

__device__ __forceinline__ uint32_t mapa(uint32_t a, uint32_t rank) {
    uint32_t r; asm volatile("mapa.shared::cluster.u32 %0, %1, %2;" : "=r"(r) : "r"(a), "r"(rank)); return r;
}
__device__ __forceinline__ void st_async32(uint32_t addr, uint32_t v, uint32_t mbar) {
    asm volatile("st.async.weak.shared::cluster.mbarrier::complete_tx::bytes.b32 [%0], %1, [%2];" :: "r"(addr), "r"(v), "r"(mbar) : "memory");
}
__device__ __forceinline__ void mbar_init(uint32_t bar, uint32_t cnt) {
    asm volatile("mbarrier.init.shared::cta.b64 [%0], %1;" :: "r"(bar), "r"(cnt) : "memory");
}
__device__ __forceinline__ void mbar_expect(uint32_t bar, uint32_t bytes) {
    asm volatile("mbarrier.arrive.expect_tx.shared::cta.b64 _, [%0], %1;" :: "r"(bar), "r"(bytes) : "memory");
}
__device__ __forceinline__ void mbar_wait(uint32_t bar, uint32_t parity) {
    unsigned it = 0;
    while (true) {
        uint32_t ok;
        asm volatile("{\n.reg .pred p;\nmbarrier.try_wait.parity.shared::cta.b64 p, [%1], %2;\nselp.u32 %0, 1, 0, p;\n}"
                     : "=r"(ok) : "r"(bar), "r"(parity) : "memory");
        if (ok || ++it >= SPIN_LIMIT) break;
    }
}
__device__ __forceinline__ void mbar_wait_long(uint32_t bar, uint32_t parity) {
    unsigned it = 0;
    while (true) {
        uint32_t ok;
        asm volatile("{\n.reg .pred p;\nmbarrier.try_wait.parity.shared::cta.b64 p, [%1], %2, %3;\nselp.u32 %0, 1, 0, p;\n}"
                     : "=r"(ok) : "r"(bar), "r"(parity), "r"(20000u) : "memory");
        if (ok || ++it >= SPIN_LIMIT) break;
    }
}
__device__ __forceinline__ uint64_t policy_evict_first() {
    uint64_t pol; asm volatile("createpolicy.fractional.L2::evict_first.b64 %0, 1.0;" : "=l"(pol)); return pol;
}
__device__ __forceinline__ void cluster_sync_all() {
    asm volatile("barrier.cluster.arrive.release.aligned;\nbarrier.cluster.wait.acquire.aligned;" ::: "memory");
}
__device__ __forceinline__ uint4 ld_vol_u4(const uint4* p) {
    uint4 v; asm volatile(LDV4 : "=r"(v.x), "=r"(v.y), "=r"(v.z), "=r"(v.w) : "l"(p) : "memory"); return v;
}
__device__ __forceinline__ void ld_vol_u4_p(uint4& v, const uint4* p, uint32_t pred) {
    asm volatile("{\n.reg .pred p;\nsetp.ne.u32 p, %5, 0;\n@p " LDV4 "\n}"
                 : "+r"(v.x), "+r"(v.y), "+r"(v.z), "+r"(v.w) : "l"(p), "r"(pred) : "memory");
}
__device__ __forceinline__ void st_vol_u4(uint4* p, uint4 v) {
    asm volatile(STV4 :: "l"(p), "r"(v.x), "r"(v.y), "r"(v.z), "r"(v.w) : "memory");
}
__device__ __forceinline__ void mma_bf16_r(float (&d)[4], uint32_t a0, uint32_t a1, uint32_t a2, uint32_t a3, uint32_t b0, uint32_t b1) {
    asm volatile("mma.sync.aligned.m16n8k16.row.col.f32.bf16.bf16.f32 {%0,%1,%2,%3}, {%4,%5,%6,%7}, {%8,%9}, {%0,%1,%2,%3};"
                 : "+f"(d[0]), "+f"(d[1]), "+f"(d[2]), "+f"(d[3])
                 : "r"(a0), "r"(a1), "r"(a2), "r"(a3), "r"(b0), "r"(b1));
}

__device__ __forceinline__ uint64_t smem_desc(uint32_t addr, uint32_t lbo, uint32_t sbo) {
    return (uint64_t)((addr & 0x3FFFF) >> 4) | ((uint64_t)(lbo >> 4) << 16) | ((uint64_t)(sbo >> 4) << 32);
}
__device__ __forceinline__ void wg_fence() { asm volatile("wgmma.fence.sync.aligned;" ::: "memory"); }
__device__ __forceinline__ void wg_commit() { asm volatile("wgmma.commit_group.sync.aligned;" ::: "memory"); }
__device__ __forceinline__ void wg_wait0() { asm volatile("wgmma.wait_group.sync.aligned 0;" ::: "memory"); }
__device__ __forceinline__ void fence_async() { asm volatile("fence.proxy.async.shared::cta;" ::: "memory"); }
__device__ __forceinline__ void wgmma_n32(float (&d)[16], const uint32_t (&a)[4], uint64_t bdesc, int scale_d) {
    asm volatile("{\n.reg .pred p;\nsetp.ne.b32 p, %21, 0;\n"
                 "wgmma.mma_async.sync.aligned.m64n32k16.f32.bf16.bf16 {%0,%1,%2,%3,%4,%5,%6,%7,%8,%9,%10,%11,%12,%13,%14,%15}, {%16,%17,%18,%19}, %20, p, 1, 1, 0;\n}"
                 : "+f"(d[0]), "+f"(d[1]), "+f"(d[2]), "+f"(d[3]), "+f"(d[4]), "+f"(d[5]), "+f"(d[6]), "+f"(d[7]),
                   "+f"(d[8]), "+f"(d[9]), "+f"(d[10]), "+f"(d[11]), "+f"(d[12]), "+f"(d[13]), "+f"(d[14]), "+f"(d[15])
                 : "r"(a[0]), "r"(a[1]), "r"(a[2]), "r"(a[3]), "l"(bdesc), "r"(scale_d));
}

__device__ __forceinline__ void wgmma_n32_ss(float (&d)[16], uint64_t adesc, uint64_t bdesc, int scale_d) {
    asm volatile("{\n.reg .pred p;\nsetp.ne.b32 p, %18, 0;\n"
                 "wgmma.mma_async.sync.aligned.m64n32k16.f32.bf16.bf16 {%0,%1,%2,%3,%4,%5,%6,%7,%8,%9,%10,%11,%12,%13,%14,%15}, %16, %17, p, 1, 1, 1, 0;\n}"
                 : "+f"(d[0]), "+f"(d[1]), "+f"(d[2]), "+f"(d[3]), "+f"(d[4]), "+f"(d[5]), "+f"(d[6]), "+f"(d[7]),
                   "+f"(d[8]), "+f"(d[9]), "+f"(d[10]), "+f"(d[11]), "+f"(d[12]), "+f"(d[13]), "+f"(d[14]), "+f"(d[15])
                 : "l"(adesc), "l"(bdesc), "r"(scale_d));
}

__device__ __forceinline__ void wgmma_n64_ss(float (&d)[32], uint64_t adesc, uint64_t bdesc) {
    asm volatile("{\n.reg .pred p;\nsetp.eq.b32 p, 0, 0;\n"
                 "wgmma.mma_async.sync.aligned.m64n64k16.f32.bf16.bf16 {%0,%1,%2,%3,%4,%5,%6,%7,%8,%9,%10,%11,%12,%13,%14,%15,%16,%17,%18,%19,%20,%21,%22,%23,"
                 "%24,%25,%26,%27,%28,%29,%30,%31}, %32, %33, p, 1, 1, 1, 0;\n}"
                 : "+f"(d[0]), "+f"(d[1]), "+f"(d[2]), "+f"(d[3]), "+f"(d[4]), "+f"(d[5]), "+f"(d[6]), "+f"(d[7]),
                   "+f"(d[8]), "+f"(d[9]), "+f"(d[10]), "+f"(d[11]), "+f"(d[12]), "+f"(d[13]), "+f"(d[14]), "+f"(d[15]),
                   "+f"(d[16]), "+f"(d[17]), "+f"(d[18]), "+f"(d[19]), "+f"(d[20]), "+f"(d[21]), "+f"(d[22]), "+f"(d[23]),
                   "+f"(d[24]), "+f"(d[25]), "+f"(d[26]), "+f"(d[27]), "+f"(d[28]), "+f"(d[29]), "+f"(d[30]), "+f"(d[31])
                 : "l"(adesc), "l"(bdesc));
}
__device__ __forceinline__ void tma_2d(uint32_t dst, const CUtensorMap* tm, int c0, int c1, uint32_t mbar) {
    asm volatile("cp.async.bulk.tensor.2d.shared::cluster.global.tile.mbarrier::complete_tx::bytes [%0], [%1, {%2, %3}], [%4];"
                 :: "r"(dst), "l"(tm), "r"(c0), "r"(c1), "r"(mbar) : "memory");
}

__device__ __forceinline__ void bulk_g2s(uint32_t dst, const void* src, uint32_t bytes, uint32_t mbar) {
    asm volatile("cp.async.bulk.shared::cluster.global.mbarrier::complete_tx::bytes [%0], [%1], %2, [%3];"
                 :: "r"(dst), "l"(src), "r"(bytes), "r"(mbar) : "memory");
}
__device__ __forceinline__ void bulk_g2s_h(uint32_t dst, const void* src, uint32_t bytes, uint32_t mbar, uint64_t pol) {
    asm volatile("cp.async.bulk.shared::cluster.global.mbarrier::complete_tx::bytes.L2::cache_hint [%0], [%1], %2, [%3], %4;"
                 :: "r"(dst), "l"(src), "r"(bytes), "r"(mbar), "l"(pol) : "memory");
}
__device__ __forceinline__ void tma_x(uint32_t dst, const CUtensorMap* tm, int seg, int part, uint32_t mbar) {
    asm volatile("cp.async.bulk.tensor.3d.shared::cluster.global.tile.mbarrier::complete_tx::bytes [%0], [%1, {%2, %3, %4}], [%5];"
                 :: "r"(dst + part * 12288), "l"(tm), "r"(0), "r"(seg * SEG), "r"(part * 3), "r"(mbar) : "memory");
}
__device__ __forceinline__ void tma_x_mc(uint32_t dst, const CUtensorMap* tm, int seg, int part, uint32_t mbar) {
    asm volatile("cp.async.bulk.tensor.3d.shared::cluster.global.tile.mbarrier::complete_tx::bytes.multicast::cluster [%0], [%1, {%2, %3, %4}], [%5], %6;"
                 :: "r"(dst + part * 12288), "l"(tm), "r"(0), "r"(seg * SEG), "r"(part * 3), "r"(mbar), "h"((unsigned short)7) : "memory");
}
__device__ __forceinline__ void bulk_s2s(uint32_t dst, uint32_t src, uint32_t bytes, uint32_t mbar) {
    asm volatile("cp.async.bulk.shared::cluster.shared::cta.mbarrier::complete_tx::bytes [%0], [%1], %2, [%3];"
                 :: "r"(dst), "r"(src), "r"(bytes), "r"(mbar) : "memory");
}
__device__ __forceinline__ void wgmma_n40_ss(float (&d)[20], uint64_t adesc, uint64_t bdesc, int scale_d) {
    asm volatile("{\n.reg .pred p;\nsetp.ne.b32 p, %22, 0;\n"
                 "wgmma.mma_async.sync.aligned.m64n40k16.f32.bf16.bf16 {%0,%1,%2,%3,%4,%5,%6,%7,%8,%9,%10,%11,%12,%13,%14,%15,%16,%17,%18,%19}, %20, %21, p, 1, 1, 1, 1;\n}"
                 : "+f"(d[0]), "+f"(d[1]), "+f"(d[2]), "+f"(d[3]), "+f"(d[4]), "+f"(d[5]), "+f"(d[6]), "+f"(d[7]),
                   "+f"(d[8]), "+f"(d[9]), "+f"(d[10]), "+f"(d[11]), "+f"(d[12]), "+f"(d[13]), "+f"(d[14]), "+f"(d[15]),
                   "+f"(d[16]), "+f"(d[17]), "+f"(d[18]), "+f"(d[19])
                 : "l"(adesc), "l"(bdesc), "r"(scale_d));
}
__device__ __forceinline__ void wgmma_n64_z(float (&d)[32], const uint32_t (&a)[4], uint64_t bdesc) {
    asm volatile("{\n.reg .pred p;\nsetp.ne.b32 p, 0, 0;\n"
                 "wgmma.mma_async.sync.aligned.m64n64k16.f32.bf16.bf16 {%0,%1,%2,%3,%4,%5,%6,%7,%8,%9,%10,%11,%12,%13,%14,%15,%16,%17,%18,%19,%20,%21,%22,%23,%24,%25,%26,%27,%28,%29,%30,%31}, {%32,%33,%34,%35}, %36, p, 1, 1, 0;\n}"
                 : "=f"(d[0]), "=f"(d[1]), "=f"(d[2]), "=f"(d[3]), "=f"(d[4]), "=f"(d[5]), "=f"(d[6]), "=f"(d[7]),
                   "=f"(d[8]), "=f"(d[9]), "=f"(d[10]), "=f"(d[11]), "=f"(d[12]), "=f"(d[13]), "=f"(d[14]), "=f"(d[15]),
                   "=f"(d[16]), "=f"(d[17]), "=f"(d[18]), "=f"(d[19]), "=f"(d[20]), "=f"(d[21]), "=f"(d[22]), "=f"(d[23]),
                   "=f"(d[24]), "=f"(d[25]), "=f"(d[26]), "=f"(d[27]), "=f"(d[28]), "=f"(d[29]), "=f"(d[30]), "=f"(d[31])
                 : "r"(a[0]), "r"(a[1]), "r"(a[2]), "r"(a[3]), "l"(bdesc));
}
__device__ __forceinline__ void wgmma_n64(float (&d)[32], const uint32_t (&a)[4], uint64_t bdesc, int scale_d) {
    asm volatile("{\n.reg .pred p;\nsetp.ne.b32 p, %37, 0;\n"
                 "wgmma.mma_async.sync.aligned.m64n64k16.f32.bf16.bf16 {%0,%1,%2,%3,%4,%5,%6,%7,%8,%9,%10,%11,%12,%13,%14,%15,%16,%17,%18,%19,%20,%21,%22,%23,%24,%25,%26,%27,%28,%29,%30,%31}, {%32,%33,%34,%35}, %36, p, 1, 1, 0;\n}"
                 : "+f"(d[0]), "+f"(d[1]), "+f"(d[2]), "+f"(d[3]), "+f"(d[4]), "+f"(d[5]), "+f"(d[6]), "+f"(d[7]),
                   "+f"(d[8]), "+f"(d[9]), "+f"(d[10]), "+f"(d[11]), "+f"(d[12]), "+f"(d[13]), "+f"(d[14]), "+f"(d[15]),
                   "+f"(d[16]), "+f"(d[17]), "+f"(d[18]), "+f"(d[19]), "+f"(d[20]), "+f"(d[21]), "+f"(d[22]), "+f"(d[23]),
                   "+f"(d[24]), "+f"(d[25]), "+f"(d[26]), "+f"(d[27]), "+f"(d[28]), "+f"(d[29]), "+f"(d[30]), "+f"(d[31])
                 : "r"(a[0]), "r"(a[1]), "r"(a[2]), "r"(a[3]), "l"(bdesc), "r"(scale_d));
}

constexpr int SB_FULL = 0, SB_EMPTY = 64, SB_QKF = 128, SB_VF = 144, SB_QKE = 160, SB_VE = 176, SB_OF = 192, SB_WO = 208, SB_TICK = 216, SB_SEEN = 224;
constexpr int AT_0 = 256, AT_ST = 10240 + 2 * 9216;
constexpr int FS_A = 58368;
constexpr int FS_P = FS_A + 131072;
constexpr int FS_I = FS_P + 16384;
constexpr int FS_O = FS_I + 12288;
constexpr int FS_Z = FS_O + 12288, FS_G = AT_0 + 2 * AT_ST;
constexpr int SIDE_SMEM = FS_Z + 2048;
static_assert(SIDE_SMEM <= 232448 && FS_G + 128 <= FS_A && FS_A + SD_SMEM <= SIDE_SMEM, "smem");

__device__ __forceinline__ void bf16r2(float& a, float& b) {
    uint32_t p = pack_bf16(a, b);
    a = __uint_as_float(p << 16); b = __uint_as_float(p & 0xffff0000u);
}
__device__ __forceinline__ void wg_wait1() { asm volatile("wgmma.wait_group.sync.aligned 1;" ::: "memory"); }
__device__ __forceinline__ void mbar_arrive(uint32_t bar) { asm volatile("mbarrier.arrive.shared::cta.b64 _, [%0];" :: "r"(bar) : "memory"); }
__device__ __forceinline__ void wait_cnt_rlx(const unsigned* p, unsigned target, bool urgent) {
    unsigned it = 0, v;
    while (true) {
        asm volatile("ld.relaxed.gpu.global.u32 %0, [%1];" : "=r"(v) : "l"(p) : "memory");
        if ((int)(v - target) >= 0 || ++it >= SPIN_LIMIT) break;
        if (!urgent) __nanosleep(RLX_SLEEP);
    }
}

__device__ __forceinline__ void xrow_softmax(float (&sc)[20], uint32_t (&pa)[3][4], int wq, int lane) {
    const int g = lane >> 2, tq = lane & 3;
    float mx0 = -INFINITY;
    const int q0 = MEMT + 8 * wq + g;
#pragma unroll
    for (int j = 0; j < 5; j++) {
        bf16r2(sc[4 * j], sc[4 * j + 1]);
        sc[4 * j] *= ATT_SCALE; sc[4 * j + 1] *= ATT_SCALE;
        bf16r2(sc[4 * j], sc[4 * j + 1]);
#pragma unroll
        for (int c = 0; c < 2; c++) {
            int key = 8 * j + 2 * tq + c;
            if (key > q0) sc[4 * j + c] = -INFINITY;
            mx0 = fmaxf(mx0, sc[4 * j + c]);
        }
    }
    mx0 = fmaxf(mx0, __shfl_xor_sync(0xffffffffu, mx0, 1)); mx0 = fmaxf(mx0, __shfl_xor_sync(0xffffffffu, mx0, 2));
    float sum0 = 0.f;
#pragma unroll
    for (int j = 0; j < 5; j++) {
#pragma unroll
        for (int c = 0; c < 2; c++) {
            float e0 = __expf(sc[4 * j + c] - mx0);
            sc[4 * j + c] = e0;
            sum0 += e0;
        }
    }
    sum0 += __shfl_xor_sync(0xffffffffu, sum0, 1); sum0 += __shfl_xor_sync(0xffffffffu, sum0, 2);
    const float i0 = 1.f / sum0;
#pragma unroll
    for (int ks = 0; ks < 3; ks++) {
        pa[ks][0] = pack_bf16(sc[8 * ks] * i0, sc[8 * ks + 1] * i0);
        pa[ks][1] = 0u;
        pa[ks][2] = ks < 2 ? pack_bf16(sc[8 * ks + 4] * i0, sc[8 * ks + 5] * i0) : 0u;
        pa[ks][3] = 0u;
    }
}

__device__ __forceinline__ void stsm_x4(uint32_t addr, uint32_t r0, uint32_t r1, uint32_t r2, uint32_t r3) {
    asm volatile("stmatrix.sync.aligned.m8n8.x4.shared.b16 [%0], {%1,%2,%3,%4};" :: "r"(addr), "r"(r0), "r"(r1), "r"(r2), "r"(r3) : "memory");
}
__device__ __forceinline__ uint32_t h2_to_bf2(uint32_t h) {
    uint32_t r;
    asm("{\n.reg .f16 l, h;\n.reg .f32 a, b;\nmov.b32 {l, h}, %1;\ncvt.f32.f16 a, l;\ncvt.f32.f16 b, h;\ncvt.rn.bf16x2.f32 %0, b, a;\n}" : "=r"(r) : "r"(h));
    return r;
}
__device__ __forceinline__ uint32_t max_abs2(uint32_t a, uint32_t b) { uint32_t r; asm("max.NaN.xorsign.abs.bf16x2 %0, %1, %2;" : "=r"(r) : "r"(a), "r"(b)); return r; }
__device__ __forceinline__ uint32_t movm(uint32_t v) {
    uint32_t r; asm volatile("movmatrix.sync.aligned.m8n8.trans.b16 %0, %1;" : "=r"(r) : "r"(v)); return r;
}
__device__ __forceinline__ void bar_arrive(int id, int n) { asm volatile("bar.arrive %0, %1;" :: "r"(id), "r"(n) : "memory"); }
__device__ __forceinline__ void lds64(uint32_t& a, uint32_t& b, uint32_t addr) {
    asm volatile("ld.shared.v2.u32 {%0,%1}, [%2];" : "=r"(a), "=r"(b) : "r"(addr) : "memory");
}
__device__ __forceinline__ void lds64f(float& a, float& b, uint32_t addr) {
    asm volatile("ld.shared.v2.f32 {%0,%1}, [%2];" : "=f"(a), "=f"(b) : "r"(addr) : "memory");
}
__device__ __forceinline__ void st_async64(uint32_t addr, uint32_t a, uint32_t b, uint32_t mbar) {
    asm volatile("st.async.weak.shared::cluster.mbarrier::complete_tx::bytes.v2.b32 [%0], {%1,%2}, [%3];" :: "r"(addr), "r"(a), "r"(b), "r"(mbar) : "memory");
}
__device__ __forceinline__ void mma_z(float (&d)[4], const uint32_t (&a)[4], uint32_t b0, uint32_t b1) {
    asm volatile("mma.sync.aligned.m16n8k16.row.col.f32.bf16.bf16.f32 {%0,%1,%2,%3}, {%4,%5,%6,%7}, {%8,%9}, {%10,%10,%10,%10};"
                 : "=f"(d[0]), "=f"(d[1]), "=f"(d[2]), "=f"(d[3])
                 : "r"(a[0]), "r"(a[1]), "r"(a[2]), "r"(a[3]), "r"(b0), "r"(b1), "f"(0.f));
}
__device__ __forceinline__ void mma_k8(float (&d)[4], uint32_t a0, uint32_t a1, uint32_t b) {
    asm volatile("mma.sync.aligned.m16n8k8.row.col.f32.bf16.bf16.f32 {%0,%1,%2,%3}, {%4,%5}, {%6}, {%0,%1,%2,%3};"
                 : "+f"(d[0]), "+f"(d[1]), "+f"(d[2]), "+f"(d[3]) : "r"(a0), "r"(a1), "r"(b));
}
__global__ void __launch_bounds__(512, 1) k_side(const __grid_constant__ CUtensorMap tmo, const bf16* __restrict__ x, const bf16* __restrict__ logA, const bf16* __restrict__ Aim,
                                                 const bf16* __restrict__ Cre, const bf16* __restrict__ Cim, const bf16* __restrict__ logdt,
                                                 const bf16* __restrict__ Wo, const bf16* __restrict__ dskip, const bf16* __restrict__ gw,
                                                 bf16* __restrict__ out) {
    extern __shared__ __align__(1024) unsigned char smem_raw[];
    const uint32_t sbase = smem_u32(smem_raw);
    const int tid = threadIdx.x, warp = __shfl_sync(0xffffffffu, tid >> 5, 0), lane = tid & 31, cta = blockIdx.x;
    const int cb = cta >> 2, kq = cta & 3;
    if (tid == 0) {
        for (int i = 0; i < 8; i++) { mbar_init(sbase + SB_FULL + 8 * i, 1); mbar_init(sbase + SB_EMPTY + 8 * i, 4); }
        for (int i = 0; i < 2; i++) {
            mbar_init(sbase + SB_QKF + 8 * i, 1); mbar_init(sbase + SB_VF + 8 * i, 1); mbar_init(sbase + SB_QKE + 8 * i, 4);
            mbar_init(sbase + SB_VE + 8 * i, 1); mbar_init(sbase + SB_OF + 8 * i, 4);
        }
        mbar_init(sbase + SB_WO, 1);
        *reinterpret_cast<uint2*>(smem_raw + SB_TICK) = make_uint2(0u, 0u);
        *reinterpret_cast<uint32_t*>(smem_raw + SB_SEEN) = 0u;
        asm volatile("fence.mbarrier_init.release.cluster;" ::: "memory");
    }
    TS3(0);
    unsigned ep;
    asm volatile("ld.volatile.global.u32 %0, [%1];" : "=r"(ep) : "l"(&g_epoch) : "memory");
    ep += 1u;
    asm volatile("fence.proxy.async;" ::: "memory");
    __syncthreads();
    if (warp >= 12) {
      asm volatile("setmaxnreg.dec.sync.aligned.u32 40;");
      {
        uint32_t gwv[9];
#pragma unroll
        for (int i = 0; i < 9; i++) gwv[i] = reinterpret_cast<const uint32_t*>(gw)[lane + 32 * i];
#pragma unroll 1
        for (int i = 0; i < 8; i++) {
            uint32_t xv[2][9];
            float sm[2];
#pragma unroll
            for (int j = 0; j < 2; j++) {
                const int t = min(cta * 57 + 8 * i + 4 * j + warp - 12, S_LEN - 1);
#pragma unroll
                for (int k = 0; k < 9; k++) xv[j][k] = reinterpret_cast<const uint32_t*>(x + t * DM)[lane + 32 * k];
            }
#pragma unroll
            for (int j = 0; j < 2; j++) {
                sm[j] = 0.f;
#pragma unroll
                for (int k = 0; k < 9; k++) {
                    const uint32_t pr = bf2_mul(xv[j][k], gwv[k]);
                    sm[j] += __uint_as_float(pr << 16) + __uint_as_float(pr & 0xffff0000u);
                }
            }
            float v = (lane < 16 ? sm[0] : sm[1]) + __shfl_xor_sync(0xffffffffu, lane < 16 ? sm[1] : sm[0], 16);
#pragma unroll
            for (int o = 8; o; o >>= 1) v += __shfl_xor_sync(0xffffffffu, v, o);
            const float gv = 1.f / (1.f + expf(-bf16r(v)));
            const int tt = 8 * i + 4 * (lane >> 4) + warp - 12;
            if ((lane & 15) == 0 && tt < 57 && cta * 57 + tt < S_LEN) g_gate[cta * 57 + tt] = __float2bfloat16_rn(gv);
        }
        named_bar(2, 128);
        if (tid == 480) {
            __threadfence();
            asm volatile("red.relaxed.gpu.global.add.u32 [%0], 1;" :: "l"(&g_gcnt[0]) : "memory");
        }
        __syncwarp();
      }
      if (warp == 12 || warp == 15) {
        named_bar(3, 320);
        if (tid == 384) {
            fence_async();
            mbar_expect(sbase + SB_WO, 131072);
#pragma unroll 1
            for (int i = 0; i < 8; i++) {
                gate(sbase + SB_TICK);
                tma_2d(sbase + FS_A + i * 16384, &tmo, cb * 64, kq * 1024 + i * 128, sbase + SB_WO);
                __nanosleep(150);
            }
            TSS(17, 2);
        }
        if (tid == 480) {
            __threadfence();
            asm volatile("red.relaxed.gpu.global.add.u32 [%0], 1;" :: "l"(&g_gcnt[32]) : "memory");
            TSS(17, 3);
        }
        __syncwarp();
        named_bar(7, 320);
        if (lane == 0) {
            const int pi = warp == 12 ? 0 : 1, kb = 2 * kq + pi;
            fence_async();
            for (int pr = 0; pr < NSEG / 2; pr++) {
                const bool gon = pr < NSEG / 2 - UNGATE_G;
                wait_cnt_rlx(&g_prog[pr * 8 + kb], 8u * ep, pr >= NSEG / 2 - 2);
                if (pi == 0) asm volatile("st.volatile.shared.u32 [%0], %1;" :: "r"(sbase + SB_SEEN), "r"(pr + 1) : "memory");
                if (pr >= 30 && pi == 0) TSS(4 + pr - 30, 0);
                if (pr == 31) TS3P(26);
                if (pr == 30) TS3P(1);
#pragma unroll
                for (int j = 0; j < 4; j++) {
                    const int st = 4 * pi + j;
                    mbar_wait_long(sbase + SB_EMPTY + 8 * st, ((uint32_t)pr & 1u) ^ 1u);
                    mbar_expect(sbase + SB_FULL + 8 * st, X_OXSZ);
                    if (gon) gate(sbase + SB_TICK);
                    bulk_g2s(sbase + FS_A + st * 16384, g_ox + ((size_t)(pr * NH + 4 * kb + j)) * 8192, X_OXSZ, sbase + SB_FULL + 8 * st);
                }
            }
        }
        __syncwarp();
      } else if (warp == 13) {
        if (lane == 0) {
            const uint64_t pol = policy_evict_first();
            bool next_ok = false;
            for (int seg = 0; seg < NATT; seg++) {
                const uint32_t st = seg & 1, ph = (uint32_t)(seg >> 1) & 1u, ab = sbase + AT_0 + st * AT_ST;
                if (!next_ok) {
                    const unsigned* fp = &g_flag[(cta & (NH - 1)) * NSEG + seg];
                    unsigned it = 0, v0, v1;
                    while (true) {
                        asm volatile("ld.relaxed.gpu.global.u32 %0, [%1];" : "=r"(v0) : "l"(fp) : "memory");
                        asm volatile("ld.relaxed.gpu.global.u32 %0, [%1+4];" : "=r"(v1) : "l"(fp) : "memory");
                        read_tick(sbase + SB_TICK);
                        if ((int)(v0 - 3u * ep) >= 0 || ++it >= SPIN_LIMIT) break;
                        if (seg < NSEG - UNGATE || cta >= NH) __nanosleep(RLX_SLEEP);
                    }
                    next_ok = (int)(v1 - 3u * ep) >= 0;
                } else next_ok = false;
                if (cta < NH) {
                    TSA(seg, 0);
                    mbar_wait_long(sbase + SB_QKE + 8 * st, ph ^ 1u);
                    TSA(seg, 1);
                    mbar_expect(sbase + SB_QKF + 8 * st, 2 * 9216);
                    if (seg < NSEG - UNGATE) gate(sbase + SB_TICK);
                    TSA(seg, 2);
                    bulk_g2s_h(ab + 10240, &g_qkv[seg][cta][0][1024], 9216, sbase + SB_QKF + 8 * st, pol);
                    bulk_g2s_h(ab + 10240 + 9216, &g_qkv[seg][cta][1][1024], 9216, sbase + SB_QKF + 8 * st, pol);
                    mbar_wait_long(sbase + SB_VE + 8 * st, ph ^ 1u);
                    mbar_expect(sbase + SB_VF + 8 * st, 10240);
                    if (seg < NSEG - UNGATE) gate(sbase + SB_TICK);
                    TSA(seg, 3);
                    bulk_g2s_h(ab, &g_qkv[seg][cta][2][0], 10240, sbase + SB_VF + 8 * st, pol);
                }
            }
        }
        __syncwarp();
      } else if (warp == 14) {
        if (lane == 0 && cta < NH) {
            for (int seg = 0; seg < NATT; seg++) {
                const uint32_t st = seg & 1, ab = sbase + AT_0 + st * AT_ST;
                mbar_wait_long(sbase + SB_OF + 8 * st, (uint32_t)(seg >> 1) & 1u);
                TSA(seg, 5);
                if (seg < NSEG - UNGATE) gate(sbase + SB_TICK);
                TSA(seg, 6);
                unsigned char* dst = reinterpret_cast<unsigned char*>(g_ox) + ((size_t)((seg >> 1) * NH + cta)) * 16384 + (seg & 1) * 4096;
                asm volatile("cp.async.bulk.global.shared::cta.bulk_group [%0], [%1], 4096;" :: "l"(dst), "r"(ab) : "memory");
                asm volatile("cp.async.bulk.global.shared::cta.bulk_group [%0], [%1], 4096;" :: "l"(dst + 8192), "r"(ab + 4096) : "memory");
                asm volatile("cp.async.bulk.commit_group;" ::: "memory");
                asm volatile("cp.async.bulk.wait_group.read 0;" ::: "memory");
                mbar_arrive(sbase + SB_VE + 8 * st);
                asm volatile("cp.async.bulk.wait_group 0;" ::: "memory");
                asm volatile("red.relaxed.gpu.global.add.u32 [%0], 1;" :: "l"(&g_prog[(seg >> 1) * 8 + (cta >> 2)]) : "memory");
                TSA(seg, 7);
            }
        }
        __syncwarp();
      }
    } else if (warp >= 8) {
        asm volatile("setmaxnreg.dec.sync.aligned.u32 88;");
        s4d_stage_u(smem_raw + FS_A, x, tid - 256);
        const int wq = warp - 8;
        for (int seg = 0; seg < (cta < NH ? NATT : 0); seg++) {
            const uint32_t st = seg & 1, ph = (uint32_t)(seg >> 1) & 1u, ab = sbase + AT_0 + st * AT_ST;
            float sc[20];
            mbar_wait_long(sbase + SB_QKF + 8 * st, ph);
            if (tid == 256) TSA(seg, 4);
            {
                const uint64_t da = smem_desc(ab + 10240 + 1024, 128, 1024), db = smem_desc(ab + 10240, 128, 2048);
                wg_fence();
#pragma unroll
                for (int ks = 0; ks < 8; ks++) wgmma_n40_ss(sc, da + (uint64_t)((ks >> 2) * 576 + (ks & 3) * 16), db + (uint64_t)((ks >> 2) * 576 + (ks & 3) * 16), ks > 0);
                wg_commit();
                wg_wait0();
            }
            if (lane == 0) mbar_arrive(sbase + SB_QKE + 8 * st);
            uint32_t pa[3][4], ob[16];
            xrow_softmax(sc, pa, wq, lane);
#pragma unroll
            for (int i = 0; i < 8; i++) ob[8 + i] = 0u;
            mbar_wait_long(sbase + SB_VF + 8 * st, ph);
#pragma unroll 1
            for (int hf = 0; hf < 2; hf++) {
                float o[32];
                const uint64_t dv = smem_desc(ab + hf * 1024, 2048, 128);
                wg_fence();
#pragma unroll
                for (int ks = 0; ks < 3; ks++) { if (ks == 0) wgmma_n64_z(o, pa[0], dv); else wgmma_n64(o, pa[ks], dv + (uint64_t)(ks * 256), 1); }
                wg_commit();
                wg_wait0();
#pragma unroll
                for (int i = 0; i < 8; i++) { ob[i] = ob[8 + i]; ob[8 + i] = pack_bf16(o[4 * i], o[4 * i + 1]); }
            }
            named_bar(6, 128);
#pragma unroll
            for (int i = 0; i < 4; i++) stsm_x4(ab + (i >> 1) * 4096 + wq * 1024 + (i & 1) * 512 + lane * 16, ob[4 * i], ob[4 * i + 1], ob[4 * i + 2], ob[4 * i + 3]);
            fence_async();
            __syncwarp();
            if (lane == 0) mbar_arrive(sbase + SB_OF + 8 * st);
        }
    } else {
        asm volatile("setmaxnreg.inc.sync.aligned.u32 192;");
        const int wg = warp >> 2, wq = warp & 3;
        s4d_phase(smem_raw + FS_A, x, logA, Aim, Cre, Cim, logdt, dskip, Wo + (size_t)((2 * kq + wg) * 512) * DM + cb * 64, ep, sbase + SB_TICK);
        TS3(2);
        if (lane == 0) TSS(16, warp);
        named_bar(3, 320);
        if (tid == 0) TSS(17, 0);
        uint32_t wa[32][4];
        mbar_wait_long(sbase + SB_WO, 0);
        if (tid == 0) TSS(17, 1);
        {
            const uint32_t a = sbase + FS_A + wg * 65536 + ((lane >> 4) * 8 + (lane & 7)) * 128 + (((wq * 2 + ((lane >> 3) & 1)) ^ (lane & 7)) << 4);
#pragma unroll
            for (int ks = 0; ks < 32; ks++) ldsm_x4_t(wa[ks], a + ks * 2048);
        }
        named_bar(7, 320);
        TS3(3);
        if (tid == 0) TSS(17, 4);
        auto product = [&](float (&acc)[32], int pr, const int wg) {
                if (pr + wg > 0 && pr + wg < NSEG / 2) named_bar(4 + wg, 256);
                const uint64_t db = smem_desc(sbase + FS_A + wg * 65536, 128, 1024);
                TSG(0);
#pragma unroll
                for (int j = 0; j < 4; j++) {
                    mbar_wait(sbase + SB_FULL + 8 * (4 * wg + j), (uint32_t)pr & 1u);
                    if (j == 0) TSG(1);
                    if (j == 3) TSG(2);
                    wg_fence();
#pragma unroll
                    for (int ks = 0; ks < 8; ks++) {
                        if ((j | ks) == 0) wgmma_n64_z(acc, wa[0], db);
                        else wgmma_n64(acc, wa[8 * j + ks], db + (uint64_t)(j * 1024 + (ks >> 2) * 512 + (ks & 3) * 16), 1);
                    }
                    wg_commit();
                    if (j == 3 && pr + 1 < NSEG / 2) bar_arrive(4 + (wg ^ 1), 256);
                    if (j > 0) { wg_wait1(); if (lane == 0) mbar_arrive(sbase + SB_EMPTY + 8 * (4 * wg + j - 1)); }
                }
                wg_wait0();
                if (pr == 31) TS3W(27);
                TSG(3);
                if (lane == 0) mbar_arrive(sbase + SB_EMPTY + 8 * (4 * wg + 3));
        };
        if (wg == 1) {
            for (int pr = 0; pr < NSEG / 2; pr++) {
                uint32_t t16 = (uint32_t)(wq * 32 + lane) * 16u;
                asm volatile("" : "+r"(t16));
                float acc[32];
                product(acc, pr, 1);
                    uint32_t tag = ((uint32_t)(pr >> 3) & 1u) ^ 1u;
                    tag = __shfl_sync(0xffffffffu, tag, lane);
                    if (GATE_S && pr < NSEG / 2 - UNGATE_G) gate(sbase + SB_TICK);
                    named_bar(8, 256);
                    unsigned char* dst = reinterpret_cast<unsigned char*>(&g_fp[pr & 7][4 * cb][2 * kq - 2][0]) + t16;
                    const uint32_t own = sbase + FS_O + (pr % 3) * 4096 + t16;
#pragma unroll
                    for (int q = 0; q < 8; q++) {
                        float4 p;
                        asm volatile("ld.shared.v4.f32 {%0,%1,%2,%3}, [%4];" : "=f"(p.x), "=f"(p.y), "=f"(p.z), "=f"(p.w) : "r"(sbase + FS_P + t16 + q * 2048) : "memory");
                        acc[4 * q] = __uint_as_float((__float_as_uint(acc[4 * q] + p.x) & ~1u) | tag); acc[4 * q + 1] = __uint_as_float((__float_as_uint(acc[4 * q + 1] + p.y) & ~1u) | tag);
                        acc[4 * q + 2] = __uint_as_float((__float_as_uint(acc[4 * q + 2] + p.z) & ~1u) | tag); acc[4 * q + 3] = __uint_as_float((__float_as_uint(acc[4 * q + 3] + p.w) & ~1u) | tag);
                    }
#pragma unroll
                    for (int q = 0; q < 8; q++) {
                        asm volatile("{\n.reg .pred p;\nsetp.ne.s32 p, %5, %6;\n@p st.volatile.global.v4.f32 [%0], {%1,%2,%3,%4};\n@!p st.shared.v4.f32 [%7], {%1,%2,%3,%4};\n}"
                                     :: "l"(dst + (q & 1) * 2048), "f"(acc[4 * q]), "f"(acc[4 * q + 1]), "f"(acc[4 * q + 2]), "f"(acc[4 * q + 3]), "r"(q >> 1), "r"(kq),
                                        "r"(own + (q & 1) * 2048) : "memory");
                        if (q & 1) dst += (q >> 1) == kq ? 12288 + 4096 : 12288;
                    }
                    bar_arrive(9, 256);
                    if (pr == 31) TS3W(28);
                TSG(4);
            }
        } else {
          int nsync = 0;
          int np = 0, nf = 0;
          while (nf < NSEG / 2) {
            bool dop = np < NSEG / 2;
            if (dop && nf < np && nf < NSEG / 2 - 2) {
                uint32_t r;
                asm volatile("{\n.reg .pred p, q;\n.reg .b32 v;\nld.volatile.shared.u32 v, [%1];\nsetp.gt.s32 p, v, %2;\nbar.red.or.pred q, 10, 128, p;\nselp.u32 %0, 1, 0, q;\n}"
                             : "=r"(r) : "r"(sbase + SB_SEEN), "r"(np) : "memory");
                dop = __shfl_sync(0xffffffffu, r, 0) != 0u;
            }
            const int pr = dop ? np++ : -1;
            const int pf = !dop || nf + (pr == NSEG / 2 - 1 ? 1 : 2) <= pr ? nf++ : -1;
            uint32_t t16 = (uint32_t)(wq * 32 + lane) * 16u;
            asm volatile("" : "+r"(t16));
            const int t0 = pf * 64 + kq * 16, c0 = cb * 64 + wq * 16;
            auto fetch = [&]() {
                const unsigned char* src = reinterpret_cast<const unsigned char*>(&g_fp[pf & 7][cta][0][0]) + t16;
#pragma unroll
                for (int r = 0; r < 6; r++) asm volatile("cp.async.cg.shared.global [%0], [%1], 16;" :: "r"(sbase + FS_I + t16 + r * 2048), "l"(src + r * 2048) : "memory");
                asm volatile("cp.async.commit_group;" ::: "memory");
            };
            if (pf >= 0) {
                if (pf == 0) { if (lane == 0) wait_cnt(&g_gcnt[32], SD_NCTA * ep); __syncwarp(); }
                asm volatile("cp.async.cg.shared.global [%0], [%1], 16;" :: "r"(sbase + FS_Z + t16), "l"(g_y + (size_t)(c0 + (lane & 15)) * S_LEN + t0 + (lane >> 4) * 8) : "memory");
                if (lane < 2) asm volatile("cp.async.cg.shared.global [%0], [%1], 16;" :: "r"(sbase + FS_G + wq * 32 + lane * 16), "l"(g_gate + t0 + lane * 8) : "memory");
            }
            if (pr < 0 && nsync <= pf) { named_bar(9, 256); nsync++; }
            if (pf >= 0) { if ((GATE_F == 1 || (GATE_F == 2 && pr < 0)) && pf < NSEG / 2 - UNGATE_G - 1) gate(sbase + SB_TICK); fetch(); }
            if (pr >= 0) {
                float acc[32];
                product(acc, pr, 0);
                    if (nsync < pr) { named_bar(9, 256); nsync++; }
#pragma unroll
                    for (int q = 0; q < 8; q++)
                        asm volatile("st.shared.v4.f32 [%0], {%1,%2,%3,%4};" :: "r"(sbase + FS_P + t16 + q * 2048), "f"(acc[4 * q]), "f"(acc[4 * q + 1]), "f"(acc[4 * q + 2]), "f"(acc[4 * q + 3]) : "memory");
                    bar_arrive(8, 256);
                TSG(4);
            }
            if (pf >= 0) {
                const uint32_t tag = ((uint32_t)(pf >> 3) & 1u) ^ 1u;
                uint4 v[8];
                unsigned n = 0;
                while (true) {
                    asm volatile("cp.async.wait_group 0;" ::: "memory");
                    uint32_t any = 0u;
#pragma unroll
                    for (int r = 0; r < 8; r++)
                        asm volatile("ld.shared.v4.u32 {%0,%1,%2,%3}, [%4];" : "=r"(v[r].x), "=r"(v[r].y), "=r"(v[r].z), "=r"(v[r].w)
                                     : "r"(sbase + t16 + (r < 6 ? FS_I + r * 2048 : FS_O + (pf % 3) * 4096 + (r - 6) * 2048)) : "memory");
#pragma unroll
                    for (int r = 0; r < 6; r++) {
                        uint32_t c0_, c1_;
                        asm("lop3.b32 %0, %1, %2, %3, 0x7e;" : "=r"(c0_) : "r"(v[r].x), "r"(v[r].y), "r"(tag));
                        asm("lop3.b32 %0, %1, %2, %3, 0x7e;" : "=r"(c1_) : "r"(v[r].z), "r"(v[r].w), "r"(tag));
                        asm("lop3.b32 %0, %1, %2, %3, 0xfe;" : "=r"(any) : "r"(any), "r"(c0_), "r"(c1_));
                    }
                    if (!__any_sync(0xffffffffu, (any & 1u) != 0u) || ++n >= SPIN_LIMIT) break;
                    if (pf + 1 < NSEG / 2) __nanosleep(200);
                    fetch();
                }
                if (pf == 31) TS3(29);
                TSG(5);
                uint32_t zv[4], gg[2];
                ldsm_x4_t(zv, sbase + FS_Z + t16);
#pragma unroll
                for (int k = 0; k < 2; k++) gg[k] = __byte_perm(*reinterpret_cast<const unsigned short*>(smem_raw + FS_G + wq * 32 + k * 16 + (lane >> 2) * 2), 0u, 0x1010);
                const uint32_t xo = (uint32_t)((t0 + (lane >> 2)) * DM + c0 + 2 * (lane & 3)) * 2u;
#define PQS(k, f) ((__uint_as_float(v[k].f) + __uint_as_float(v[2 + k].f)) + (__uint_as_float(v[4 + k].f) + __uint_as_float(v[6 + k].f)))
#pragma unroll
                for (int k = 0; k < 2; k++) {
                    unsigned char* op = reinterpret_cast<unsigned char*>(out) + xo + k * (16 * DM);
                    *reinterpret_cast<uint32_t*>(op) = bf2_add(bf2_mul(gg[k], movm(pack_bf16(PQS(k, x), PQS(k, y)))), zv[2 * k]);
                    *reinterpret_cast<uint32_t*>(op + 16) = bf2_add(bf2_mul(gg[k], movm(pack_bf16(PQS(k, z), PQS(k, w)))), zv[2 * k + 1]);
                }
#undef PQS
                if ((pf & 1) == 0) TS3(4 + pf / 2);
                if (pf == 31) TS3(25);
                TSG(6);
            }
        }
        }
        if (cta == 0 && tid == 0) asm volatile("red.relaxed.gpu.global.add.u32 [%0], 1;" :: "l"(&g_epoch) : "memory");
    }
    asm volatile("griddepcontrol.wait;" ::: "memory");
}

__device__ __forceinline__ uint32_t poll_mem(const uint4* src, uint32_t dst, uint32_t t0) {
    uint4 v[6];
    unsigned it = 0;
#pragma unroll
    for (int j = 0; j < 6; j++) v[j] = make_uint4(0u, 0u, 0u, 0u);
    while (clock32() - t0 < POLL_DELAY) {}
    FS(12, 0);
    bool more;
#pragma unroll 1
    do {
        asm volatile("{\n.reg .pred p<6>;\n"
                     "setp.ne.u32 p0, %3, 0x5000;\nsetp.ne.u32 p1, %7, 0x5000;\nsetp.ne.u32 p2, %11, 0x5000;\n"
                     "setp.ne.u32 p3, %15, 0x5000;\nsetp.ne.u32 p4, %19, 0x5000;\nsetp.ne.u32 p5, %23, 0x5000;\n"
                     "@p0 ld.volatile.global.v4.u32 {%0,%1,%2,%3}, [%24];\n@p1 ld.volatile.global.v4.u32 {%4,%5,%6,%7}, [%24+4096];\n"
                     "@p2 ld.volatile.global.v4.u32 {%8,%9,%10,%11}, [%24+8192];\n@p3 ld.volatile.global.v4.u32 {%12,%13,%14,%15}, [%24+12288];\n"
                     "@p4 ld.volatile.global.v4.u32 {%16,%17,%18,%19}, [%24+16384];\n@p5 ld.volatile.global.v4.u32 {%20,%21,%22,%23}, [%24+20480];\n}"
                     : "+r"(v[0].x), "+r"(v[0].y), "+r"(v[0].z), "+r"(v[0].w), "+r"(v[1].x), "+r"(v[1].y), "+r"(v[1].z), "+r"(v[1].w),
                       "+r"(v[2].x), "+r"(v[2].y), "+r"(v[2].z), "+r"(v[2].w), "+r"(v[3].x), "+r"(v[3].y), "+r"(v[3].z), "+r"(v[3].w),
                       "+r"(v[4].x), "+r"(v[4].y), "+r"(v[4].z), "+r"(v[4].w), "+r"(v[5].x), "+r"(v[5].y), "+r"(v[5].z), "+r"(v[5].w)
                     : "l"(src) : "memory");
        stsm_x4(dst, h2_to_bf2(v[0].x), h2_to_bf2(v[0].y), h2_to_bf2(v[0].z), h2_to_bf2(v[1].x));
        stsm_x4(dst + 512, h2_to_bf2(v[1].y), h2_to_bf2(v[1].z), h2_to_bf2(v[2].x), h2_to_bf2(v[2].y));
        stsm_x4(dst + 1024, h2_to_bf2(v[2].z), h2_to_bf2(v[3].x), h2_to_bf2(v[3].y), h2_to_bf2(v[3].z));
        asm volatile("stmatrix.sync.aligned.m8n8.x2.shared.b16 [%0], {%1,%2};" :: "r"(dst + 1536), "r"(h2_to_bf2(v[4].x)), "r"(h2_to_bf2(v[4].y)) : "memory");
        stsm_x4(dst + 1792, h2_to_bf2(v[4].z), h2_to_bf2(v[5].x), h2_to_bf2(v[5].y), h2_to_bf2(v[5].z));
        const uint32_t all = ((v[0].w & v[1].w) & (v[2].w & v[3].w)) & (v[4].w & v[5].w);
        more = __any_sync(0xffffffffu, (all & 0x5000u) != 0x5000u) && ++it < SPIN_LIMIT;
    } while (more);
    FS(13, it);
    bar_arrive(1, 384);
    FS(14, 0);
    uint32_t m = 0u;
#pragma unroll
    for (int j = 0; j < 6; j++) {
        asm volatile("max.NaN.xorsign.abs.f16x2 %0, %0, %1;" : "+r"(m) : "r"(v[j].x));
        asm volatile("max.NaN.xorsign.abs.f16x2 %0, %0, %1;" : "+r"(m) : "r"(v[j].y));
        asm volatile("max.NaN.xorsign.abs.f16x2 %0, %0, %1;" : "+r"(m) : "r"(v[j].z));
    }
    return h2_to_bf2(m) & 0x7fff7fffu;
}

template <bool V> struct Flag { static constexpr bool value = V; };
struct RFlag { bool value; };
__device__ __forceinline__ void score_group(const uint32_t (&a)[2][4], const uint32_t (&kf)[2][4], uint32_t d0, uint32_t d1, uint32_t m1, uint32_t d2, uint32_t m2) {
    FS(4, a[1][0]);
    float sc[4][4];
    mma_z(sc[0], a[0], kf[0][0], kf[0][1]);
    mma_z(sc[1], a[0], kf[0][2], kf[0][3]);
    mma_z(sc[2], a[1], kf[1][0], kf[1][1]);
    mma_z(sc[3], a[1], kf[1][2], kf[1][3]);
    const uint32_t v0 = __float_as_uint((sc[0][0] + sc[1][2]) + (sc[2][0] + sc[3][2])), v1 = __float_as_uint((sc[0][1] + sc[1][3]) + (sc[2][1] + sc[3][3]));
    FS(5, v0);
    st_async64(d2, v0, v1, m2);
    st_async64(d1, v0, v1, m1);
    asm volatile("st.shared.v2.u32 [%0], {%1,%2};" :: "r"(d0), "r"(v0), "r"(v1) : "memory");
}
__device__ __forceinline__ void store_tile(int s, int h, int role, uint32_t tile) {
    const uint32_t qoff = role != 2 ? 1024 : 0;
    asm volatile("cp.async.bulk.global.shared::cta.bulk_group.L2::cache_hint [%0], [%1], %2, %3;"
                 :: "l"(&g_qkv[s][h][role][qoff]), "r"(tile + qoff), "r"(10240u - qoff), "l"(policy_evict_first()) : "memory");
    asm volatile("cp.async.bulk.commit_group;" ::: "memory");
}
__device__ __forceinline__ uint32_t w_addr(uint32_t sbase, int warp, int lane) {
    return sbase + SM_WS + (warp >> 2) * 8192 + ((lane & 7) + ((lane >> 4) & 1) * 8) * 128 + ((((warp & 3) * 2 + ((lane >> 3) & 1)) ^ (lane & 7)) << 4);
}
__device__ __forceinline__ void vx_copy(uint32_t sbase, int j, int r) {
    bulk_s2s(mapa(sbase + SM_VX + (j & 1) * 8192, r), sbase + SM_T + (j & 3) * TBUF + DH * 16, 8192, mapa(sbase + B_VX + 8 * (j & 1), r));
}
__device__ __forceinline__ void norms_gather(int lane, float* scs) {
    uint2 v[3];
    uint32_t r[2];
    unsigned it = 0;
    do {
#pragma unroll
        for (int i = 0; i < 3; i++) v[i] = ld_vol_u2(&g_norm[3 * lane + i]);
#pragma unroll
        for (int i = 0; i < 2; i++) asm volatile("ld.volatile.global.u32 %0, [%1];" : "=r"(r[i]) : "l"(&g_rx[lane + 32 * i]) : "memory");
    } while (__any_sync(0xffffffffu, (v[0].x & v[1].x & v[2].x & v[2].y & r[0] & r[1] & 1u) == 0u) && ++it < SPIN_LIMIT);
    float c;
    asm("sqrt.approx.f32 %0, %1;" : "=f"(c) : "f"(__uint_as_float(max(max(v[0].x, v[1].x), v[2].x))));
    c *= __uint_as_float(v[2].y) * 272.f;
#pragma unroll
    for (int o = 16; o; o >>= 1) c += __shfl_xor_sync(0xffffffffu, c, o);
    scs[16 + lane] = __uint_as_float(r[0]); scs[48 + lane] = __uint_as_float(r[1]);
    if (lane == 0) scs[1] = c * (1.1f * 24.f);
}

__global__ void __cluster_dims__(3, 1, 1) __launch_bounds__(384, 1)
k_chain(const __grid_constant__ CUtensorMap tmx, const __grid_constant__ CUtensorMap tmq, const __grid_constant__ CUtensorMap tmk,
        const __grid_constant__ CUtensorMap tmv, const __grid_constant__ CUtensorMap tmx2, const __grid_constant__ CUtensorMap tmo, const bf16* __restrict__ mem0, const bf16* __restrict__ xg) {
    extern __shared__ __align__(1024) unsigned char smem_raw[];
    const uint32_t sbase = smem_u32(smem_raw);
    const int cta = blockIdx.x, h = cta / 3, role = cta - 3 * h;
    const int tid = threadIdx.x, warp = __shfl_sync(0xffffffffu, tid >> 5, 0), lane_o = tid & 31;
    TS3C(0);
    asm volatile("griddepcontrol.launch_dependents;" ::: "memory");
    auto stage_w = [&](int i) {
        tma_2d(sbase + SM_WS + i * 16384, role == 2 ? &tmv : &tmq, h * DH + (role == 1 ? 64 : 0), i * 64, sbase + B_W + 8 * i);
        tma_2d(sbase + SM_WS + i * 16384 + 8192, role == 2 ? &tmv : &tmk, h * DH + (role == 0 ? 0 : 64), i * 64, sbase + B_W + 8 * i);
    };
    auto stage_x = [&](int i) { tma_2d(sbase + x01_off(i), &tmx2, i * 64, 0, sbase + B_W + 8 * i); };
    if (tid == 0) {
#pragma unroll
        for (int i = 0; i < 10; i++) mbar_init(sbase + B_W + 8 * i, 1);
        fence_async();
        bulk_g2s(sbase + SM_E + XBUF, mem0, MEMT * DM * 2, sbase + B_E);
#pragma unroll
        for (int i = 0; i < 3; i++) tma_2d(sbase + SM_X01 + i * 16384, &tmo, role * WOC + i * 64, h * DH, sbase + B_E);
        if (cta < NSEG) bulk_g2s(sbase + SM_E, xg + (size_t)cta * SEG * DM, XBUF, sbase + B_E);
#pragma unroll 1
        for (int i = 0; i < 6; i++) { if (i < 3) stage_x(i); stage_w(i); }
        mbar_expect(sbase + B_E, 49152 + MEMT * DM * 2 + (cta < NSEG ? XBUF : 0));
#pragma unroll
        for (int i = 0; i < 9; i++) mbar_expect(sbase + B_W + 8 * i, 24576);
    } else if (tid == 32) {
#pragma unroll
        for (int i = 0; i < 7; i++) mbar_init(sbase + SM_BAR + 8 * i, 1);
        asm volatile("fence.mbarrier_init.release.cluster;" ::: "memory");
        for (int i = 0; i < 2; i++) {
            mbar_expect(sbase + B_SB + 8 * i, role == 2 ? 2560 : 1280 + 2048);
            mbar_expect(sbase + B_VX + 8 * i, role != 2 ? 8192 : 2 * 9216);
            mbar_arrive(sbase + B_XT + 8 * i);
        }
        mbar_expect(sbase + B_XT + 16, XBUF);
        reinterpret_cast<float*>(smem_raw + SM_SC)[2] = 1.f;
    } else if (tid >= 64 && tid < 88) {
        *reinterpret_cast<uint4*>(g_acc + cta * 1024 + (tid - 64) * 16) = make_uint4(0u, 0u, 0u, 0u);
        __threadfence();
    }
    __syncthreads();
    TS3C(8);
    if (warp < 8) {
        uint32_t wreg[36 - NS][4];
        {
            const int lane = lane_o;
            const uint32_t a = w_addr(sbase, warp, lane);
            const uint64_t da = smem_desc(sbase + SM_WS + (warp >> 2) * 8192, 1024, 1024) | (1ull << 62);
            float acc[32];
#pragma unroll
            for (int i = 0; i < 32; i++) acc[i] = 0.f;
#pragma unroll 1
            for (int b = 0; b < 9; b++) {
                if (b == 0) TSQ(0);
                mbar_wait(sbase + B_W + 8 * b, 0);
                TSQ(1 + b);
                if (b == 8) TS3C(2);
                const uint64_t db = smem_desc(sbase + x01_off(b), 16, 1024) | (1ull << 62);
                wg_fence();
#pragma unroll
                for (int k = 0; k < 4; k++) wgmma_n64_ss(acc, da + (uint64_t)(b * 1024 + k * 128), db + (uint64_t)(k * 2));
                wg_commit();
                if (b == 5) {
#pragma unroll
                    for (int ks = NS; ks < 24; ks++) ldsm_x4_t(wreg[ks - NS], a + (ks >> 2) * 16384 + (ks & 3) * 2048);
                }
            }
#pragma unroll
            for (int ks = 24; ks < 32; ks++) ldsm_x4_t(wreg[ks - NS], a + (ks >> 2) * 16384 + (ks & 3) * 2048);
            wg_wait0();
            named_bar(9, 384);
            const uint32_t off = sbase + SM_T + (DH + warp * 16 + (lane & 15)) * 16 + (lane >> 4) * (DH * 16);
#pragma unroll
            for (int i = 0; i < 4; i++)
                stsm_x4(off + (i >> 1) * TBUF + (i & 1) * (2 * DH * 16), pack_bf16(acc[8 * i], acc[8 * i + 1]), pack_bf16(acc[8 * i + 2], acc[8 * i + 3]),
                        pack_bf16(acc[8 * i + 4], acc[8 * i + 5]), pack_bf16(acc[8 * i + 6], acc[8 * i + 7]));
#pragma unroll
            for (int ks = 32; ks < 36; ks++) ldsm_x4_t(wreg[ks - NS], a + (ks >> 2) * 16384 + (ks & 3) * 2048);
            if (role == 2) fence_async();
            bar_arrive(8, 384);
            named_bar(7, 256);
            asm volatile("barrier.cluster.arrive.relaxed.aligned;" ::: "memory");
        }
        TS3C(3);
        auto xproj1 = [&](float (&acc)[16], int j) {
            const uint32_t dlo = __shfl_sync(0xffffffffu, (uint32_t)smem_desc(sbase + SM_X + (j % 3) * XBUF, 16, 1024), 0);
            wg_fence();
#pragma unroll
            for (int ks = NS; ks < NS + NC1; ks++)
                wgmma_n32(acc, wreg[ks - NS], ((uint64_t)0x40000040u << 32) | (uint64_t)(dlo + (uint32_t)((ks >> 2) * 256 + (ks & 3) * 2)), ks > NS);
            wg_commit();
            wg_wait0();
        };
        auto xproj2 = [&](float (&acc)[16], int j) {
            int lane = lane_o;
            asm volatile("" : "+r"(lane));
            const uint32_t dlo = __shfl_sync(0xffffffffu, (uint32_t)smem_desc(sbase + SM_X + (j % 3) * XBUF, 16, 1024), 0);
            const uint64_t da = smem_desc(sbase + SM_WS + (warp >> 2) * 8192, 1024, 1024) | (1ull << 62);
            wg_fence();
#pragma unroll
            for (int ks = NS + NC1; ks < NS + NC1 + SS_POS; ks++)
                wgmma_n32(acc, wreg[ks - NS], ((uint64_t)0x40000040u << 32) | (uint64_t)(dlo + (uint32_t)((ks >> 2) * 256 + (ks & 3) * 2)), 1);
#pragma unroll
            for (int ks = 0; ks < NS; ks++)
                wgmma_n32_ss(acc, da + (uint64_t)((ks >> 2) * 1024 + (ks & 3) * 128), ((uint64_t)0x40000040u << 32) | (uint64_t)(dlo + (uint32_t)((ks >> 2) * 256 + (ks & 3) * 2)), 1);
#pragma unroll
            for (int ks = NS + NC1 + SS_POS; ks < XK; ks++)
                wgmma_n32(acc, wreg[ks - NS], ((uint64_t)0x40000040u << 32) | (uint64_t)(dlo + (uint32_t)((ks >> 2) * 256 + (ks & 3) * 2)), 1);
            wg_commit();
            wg_wait0();
            const uint32_t off = sbase + SM_T + (j & 3) * TBUF + (DH + warp * 16 + (lane & 15)) * 16 + (lane >> 4) * (DH * 16);
            stsm_x4(off, pack_bf16(acc[0], acc[1]), pack_bf16(acc[2], acc[3]), pack_bf16(acc[4], acc[5]), pack_bf16(acc[6], acc[7]));
            stsm_x4(off + 2 * DH * 16, pack_bf16(acc[8], acc[9]), pack_bf16(acc[10], acc[11]), pack_bf16(acc[12], acc[13]), pack_bf16(acc[14], acc[15]));
        };
        uint32_t ws[NS][4];
#pragma unroll
        for (int ks = NS - NP; ks < NS; ks++) ldsm_x4_t(ws[ks], w_addr(sbase, warp, lane_o) + (ks >> 2) * 16384 + (ks & 3) * 2048);
        asm volatile("barrier.cluster.wait.aligned;" ::: "memory");
        if (lane_o == 0 && warp < 2 && role == 2) vx_copy(sbase, 0, warp);
        __syncwarp();
        TS3C(4);
        auto main_loop = [&](auto is_c) {
            const bool C = is_c.value;
            const uint32_t l16 = __shfl_sync(0xffffffffu, sbase + lane_o * 16, lane_o);
            const uint32_t ta = __shfl_sync(0xffffffffu, sbase + SM_T + warp * 256 + (lane_o & 15) * 16, lane_o);
            const uint32_t ka = __shfl_sync(0xffffffffu, sbase + SM_T + (64 + (lane_o & 7) + ((lane_o >> 3) & 1) * 16 + (lane_o >> 4) * 8) * 16, lane_o);
            uint32_t to = 0;
            for (int s = 0; s < NSEG; s++) {
                int lane = lane_o;
                asm volatile("" : "+r"(lane));
                uint32_t v0, v1;
                const uint32_t tb = sbase + SM_T + to;
                {
#pragma unroll
                    for (int ks = 0; ks < NS - NP; ks++) ldsm_x4_t(ws[ks], w_addr(sbase, warp, lane) + (ks >> 2) * 16384 + (ks & 3) * 2048);
                    FS(0, ws[0][0]);
                    named_bar(1, 384);
                    float acc[2][4], minv;
                    uint32_t b[3][4];
#pragma unroll
                    for (int kk = 0; kk < 3; kk++) ldsm_x4_t(b[kk], l16 + SM_M + kk * 512);
                    FS(1, b[0][0]);
#pragma unroll
                    for (int kk = 0; kk < 18; kk++) {
#pragma unroll
                        for (int i = 0; i < 2; i++) {
                            const int ks = 2 * kk + i;
                            if (ks < 2) mma_z(acc[i], ws[ks], b[kk % 3][2 * i], b[kk % 3][2 * i + 1]);
                            else if (ks < NS) mma_bf16(acc[i], ws[ks < NS ? ks : 0], b[kk % 3][2 * i], b[kk % 3][2 * i + 1]);
                            else mma_bf16(acc[i], wreg[ks >= NS ? ks - NS : 0], b[kk % 3][2 * i], b[kk % 3][2 * i + 1]);
                        }
                        if (kk + 3 < 18) ldsm_x4_t(b[kk % 3], l16 + SM_M + (kk + 3) * 512);
                        if (kk + 3 == 17) asm volatile("ld.shared.f32 %0, [%1];" : "=f"(minv) : "r"(sbase + SM_SC + 8) : "memory");
                    }
                    v0 = pack_bf16(fmaf(acc[1][0], minv, acc[0][0] * minv), fmaf(acc[1][1], minv, acc[0][1] * minv));
                    v1 = pack_bf16(fmaf(acc[1][2], minv, acc[0][2] * minv), fmaf(acc[1][3], minv, acc[0][3] * minv));
                    FS(2, v0);
                }
                asm volatile("stmatrix.sync.aligned.m8n8.x2.shared.b16 [%0], {%1,%2};" :: "r"(ta + to), "r"(v0), "r"(v1) : "memory");
                if (C) {
                    if (s + 1 < NSEG) {
                        const uint32_t fo = (uint32_t)(warp * 256 + lane * 8);
                        const uint32_t rb0 = mapa(sbase, 0), rb1 = mapa(sbase, 1);
                        st_async64(rb0 + SM_VM + fo, v0, v1, rb0 + B_SB + 8 * (s & 1));
                        st_async64(rb1 + SM_VM + fo, v0, v1, rb1 + B_SB + 8 * (s & 1));
                        asm volatile("st.shared.v2.u32 [%0], {%1,%2};" :: "r"(sbase + SM_VM + fo), "r"(v0), "r"(v1) : "memory");
                        bar_arrive(2, 384);
                    }
                } else {
                    named_bar(2, 384);
                    if (warp == 7) {
                        uint32_t kf[2][4], qf[2][4];
#pragma unroll
                        for (int k2 = 0; k2 < 2; k2++) { ldsm_x4_t(kf[k2], ka + to + k2 * 512); ldsm_x4_t(qf[k2], l16 + SM_T + to + k2 * 512); }
                        if (s + 1 < NSEG) {
                            const uint32_t d0 = sbase + SM_S + role * 1280 + lane * 8, bo = sbase + B_SB + 8 * (s & 1);
                            const uint32_t d1 = mapa(d0, role ^ 1), m1 = mapa(bo, role ^ 1), d2 = mapa(d0, 2), m2 = mapa(bo, 2);
                            score_group(qf, kf, d0, d1, m1, d2, m2);
                            bar_arrive(6, 160);
                        }
                    }
                    if (s + 1 == NSEG && warp >= 4) {
                        const uint32_t dk = mapa(sbase + SM_X + XBUF + (2 + role) * 9216 + (warp - 4) * 256 + lane * 4, 2), mb = mapa(sbase + B_VX + 8, 2);
                        st_async32(dk, v0, mb);
                        st_async32(dk + 128, v1, mb);
                    }
                }
                to = to == 3 * TBUF ? 0 : to + TBUF;
                FS(11, 0);
                if (s + 2 < NSEG) {
                    if (warp == 6) mbar_wait(sbase + B_XT + 8 * ((s + 2) % 3), (uint32_t)((s + 2) / 3) & 1u);
                    fence_async();
                    if (!C) named_bar(5, 384); else named_bar(7, 256);
                    if (tid == 64) store_tile(s, h, role, tb);
                    __syncwarp();
                    float xacc[16];
                    if (C1_DELAY > 0) { const uint32_t t1 = clock32(); while (clock32() - t1 < C1_DELAY) {} }
                    xproj1(xacc, s + 2);
                    FS(9, __float_as_uint(xacc[0]));
                    if (C && tid == 0) vx_copy(sbase, s + 1, 0);
                    if (tid == 64) {
                        asm volatile("cp.async.bulk.wait_group 0;" ::: "memory");
                        asm volatile("red.relaxed.gpu.global.add.u32 [%0], 1;" :: "l"(&g_flag[h * NSEG + s]) : "memory");
                    }
                    __syncwarp();
                    FS(14, 0);
                    named_bar(4, 384);
                    if (C2_DELAY > 0) { const uint32_t t1 = clock32(); while (clock32() - t1 < C2_DELAY) {} }
                    xproj2(xacc, s + 2);
                    FS(7, __float_as_uint(xacc[0]));
                } else if (s + 2 == NSEG) {
                    const uint32_t t0 = clock32();
                    const uint32_t dq = mapa(sbase + SM_X + XBUF + role * 9216, 2), mb = mapa(sbase + B_VX, 2);
                    if (!C) {
                        fence_async();
                        named_bar(5, 384);
                        if (tid == 64) { while (clock32() - t0 < TL_DELAY) {} bulk_s2s(dq, tb + 1024, 9216, mb); }
                        __syncwarp();
                    }
                    named_bar(4, 384);
                    if (!C && tid == 64) { const uint32_t t1 = clock32(); while (clock32() - t1 < VX_DELAY) {} bulk_s2s(dq + 2 * 9216 + 1024, sbase + SM_T + ((s + 1) & 3) * TBUF + 2048, 8192, mb + 8); }
                    __syncwarp();
                }
            }
            if (C) named_bar(7, 256);
        };
        if (role == 2) main_loop(Flag<true>()); else main_loop(Flag<false>());
    } else {
        float* scs = reinterpret_cast<float*>(smem_raw + SM_SC);
        uint32_t wo[3][8][4];
        uint32_t mx2 = 0u;
        {
            const int pt = tid - 256, lane = lane_o, wq = warp - 8, g = lane >> 2, tq = lane & 3;
            TSQ(7);
            mbar_wait(sbase + B_E, 0);
            TSQ(8);
#pragma unroll
            for (int t = 0; t < 3; t++) {
                const int T = 3 * wq + t;
                const uint32_t a = sbase + SM_X01 + (T >> 2) * 16384 + ((lane >> 4) * 8 + (lane & 7)) * 128 + ((((T & 3) * 2 + ((lane >> 3) & 1)) ^ (lane & 7)) << 4);
#pragma unroll
                for (int kk = 0; kk < 8; kk++) ldsm_x4_t(wo[t][kk], a + ((2 * wq + kk) & 7) * 2048);
            }
            uint32_t m = 0u;
#pragma unroll 6
            for (int j = 0; j < 18; j++) {
                const uint32_t v = lds32(sbase + SM_E + XBUF + (g * DM + wq * 144 + 8 * j) * 2 + tq * 4);
                asm volatile("stmatrix.sync.aligned.m8n8.x1.trans.shared.b16 [%0], {%1};" :: "r"(sbase + SM_M + (wq * 144 + 8 * j + (lane & 7)) * 16), "r"(v) : "memory");
                mx2 = __vmaxu2(mx2, v & 0x7fff7fffu);
                const uint4 xv = *reinterpret_cast<const uint4*>(smem_raw + SM_E + (pt + 128 * j) * 16);
                m = max_abs2(max_abs2(m, max_abs2(xv.x, xv.y)), max_abs2(xv.z, xv.w));
            }
            m = __reduce_max_sync(0xffffffffu, max((m << 16) & 0x7fff0000u, m & 0x7fff0000u));
            if (lane == 0) reinterpret_cast<uint32_t*>(scs)[260 + wq] = m;
            named_bar(3, 128);
            if (pt == 64) {
                fence_async();
#pragma unroll 1
                for (int i = 3; i < 9; i++) { stage_x(i); if (i >= 6) stage_w(i); }
            }
            if (pt == 96 && cta < NSEG) {
                const uint4 q = *reinterpret_cast<const uint4*>(scs + 260);
                asm volatile("st.volatile.global.u32 [%0], %1;" :: "l"(&g_rx[cta]), "r"(max(max(q.x, q.y), max(q.z, q.w)) | 1u) : "memory");
            }
            __syncwarp();
            bar_arrive(1, 384);
            TSQ(9);
            float c0 = 0.f;
#pragma unroll
            for (int t = 0; t < 3; t++) {
                float n[4][4];
#pragma unroll
                for (int i = 0; i < 4; i++) { n[i][0] = n[i][1] = n[i][2] = n[i][3] = 0.f; }
#pragma unroll
                for (int kk = 0; kk < 8; kk++)
#pragma unroll
                    for (int i = 0; i < 4; i++) mma_k8(n[i], wo[t][kk][i & 2], wo[t][kk][(i & 2) + 1], wo[t][kk][i]);
                if ((g >> 1) == tq) c0 = fmaxf(c0, (g & 1) ? fmaxf(n[0][1] + n[2][1], n[1][3] + n[3][3]) : fmaxf(n[0][0] + n[2][0], n[1][2] + n[3][2]));
            }
            c0 = __uint_as_float(__reduce_max_sync(0xffffffffu, __float_as_uint(c0)));
            m = 0u;
#pragma unroll 1
            for (int b = 0; b < 9; b++) {
                if (role == 2) {
                    mbar_wait(sbase + B_W + 8 * b, 0);
#pragma unroll
                    for (int j = 0; j < 8; j++) {
                        const uint4 xv = *reinterpret_cast<const uint4*>(smem_raw + SM_WS + b * 16384 + (pt + 128 * j) * 16);
                        m = max_abs2(max_abs2(m, max_abs2(xv.x, xv.y)), max_abs2(xv.z, xv.w));
                    }
                }
                if (b == 3) bar_arrive(9, 384);
            }
            asm volatile("barrier.cluster.arrive.relaxed.aligned;" ::: "memory");
            m = __reduce_max_sync(0xffffffffu, max((m << 16) & 0x7fff0000u, m & 0x7fff0000u));
            if (lane == 0) { scs[256 + wq] = c0; reinterpret_cast<uint32_t*>(scs)[8 + wq] = m; }
            TSQ(1);
            named_bar(3, 128);
            if (pt == 0) {
                const float a = fmaxf(fmaxf(scs[256], scs[257]), fmaxf(scs[258], scs[259]));
                const float b = fmaxf(fmaxf(scs[8], scs[9]), fmaxf(scs[10], scs[11]));
                st_vol_u2(&g_norm[cta], make_uint2(__float_as_uint(a) | 1u, __float_as_uint(b) | 1u));
            }
            __syncwarp();
            named_bar(8, 384);
            TSQ(2);
            if (pt == 32) {
                fence_async();
                for (int i = 0; i < 3; i++) tma_x(sbase + SM_X + 2 * XBUF, &tmx, 2, i, sbase + B_XT + 16);
            }
            __syncwarp();
            asm volatile("barrier.cluster.wait.aligned;" ::: "memory");
        }
        const int wq = warp - 8;
        auto helper_loop = [&](auto is_c) {
        const bool C = is_c.value;
        const uint32_t l8 = __shfl_sync(0xffffffffu, sbase + lane_o * 8, lane_o), l16 = __shfl_sync(0xffffffffu, sbase + lane_o * 16, lane_o);
        unsigned char* dst = g_acc + (role * 32 + wq * 8 + (lane_o >> 3)) * 1024 + (lane_o & 7) * 16;
        const uint32_t ka = __shfl_sync(0xffffffffu, sbase + SM_T + ((wq + 1) * DH + 64 + (lane_o & 7) + ((lane_o >> 3) & 1) * 16 + (lane_o >> 4) * 8) * 16, lane_o);
        const uint32_t vb = __shfl_sync(0xffffffffu, sbase + (lane_o >> 4) * 2048 + (32 * wq + (lane_o & 15)) * 16, lane_o);
        float minv = 1.f;
        uint32_t kf[2][4];
#pragma unroll
        for (int k2 = 0; k2 < 2; k2++) if (!C) ldsm_x4_t(kf[k2], ka + k2 * 512);
        int b3 = 0;
        for (int s = 0; s + 1 < NSEG; s++) {
            const int n3 = b3 == 2 ? 0 : b3 + 1;
            {
                int lane = lane_o;
                asm volatile("" : "+r"(lane));
                if (lane == 0) {
                    if (wq == 0 && cta == 0) {
                        const uint32_t t = gtime32();
                        st_vol_u2(&g_tick, make_uint2(t, reinterpret_cast<uint32_t*>(scs)[3]));
                        reinterpret_cast<uint32_t*>(scs)[3] = t;
                    }
                    if (wq == 1 && s + 3 < NSEG) tma_x_mc(sbase + SM_X + b3 * XBUF, &tmx, s + 3, role, sbase + B_XT + 8 * b3);
                    if (wq == 0 && s == 1) {
                        st_vol_u2(&g_norm[cta], make_uint2(0u, 0u));
                        if (cta < NSEG) asm volatile("st.volatile.global.u32 [%0], %1;" :: "l"(&g_rx[cta]), "r"(0u) : "memory");
                    }
                }
                __syncwarp();
                if (wq == 2 && s > 1 && lane < 8) {
                    *reinterpret_cast<uint4*>(g_acc + n3 * 128 + cta * 1024 + lane * 16) = make_uint4(0u, 0u, 0u, 0u);
                }
                const uint32_t mw = __reduce_max_sync(0xffffffffu, max(mx2 << 16, mx2 & 0xffff0000u));
                if (lane == 0) scs[4 + wq] = __uint_as_float(mw);
            }
            const uint32_t to = SM_T + (s & 3) * TBUF;
            const uint32_t ph = (uint32_t)(s >> 1) & 1u;
            if (!C) {
                const uint32_t so = SM_S + role * 1280 + (wq + 1) * 256, bo = sbase + B_SB + 8 * (s & 1);
                uint32_t d0 = l8 + so, qa = l16 + to;
                const uint32_t d1 = mapa(d0, role ^ 1), m1 = mapa(bo, role ^ 1), d2 = mapa(d0, 2), m2 = mapa(bo, 2);
                asm volatile("" : "+r"(d0), "+r"(qa));
                mbar_wait(sbase + B_VX + 8 * (s & 1), ph);
                FS(1, 0);
                named_bar(2, 384);
                uint32_t qf[2][4];
#pragma unroll
                for (int k2 = 0; k2 < 2; k2++) ldsm_x4_t(qf[k2], qa + k2 * 512);
                score_group(qf, kf, d0, d1, m1, d2, m2);
                bar_arrive(5, 384);
            } else named_bar(2, 384);
            if (s == 0) {
                TSQ(3);
                int lane = lane_o;
                asm volatile("" : "+r"(lane));
                if (wq == 1) norms_gather(lane, scs);
                named_bar(3, 128);
                TSQ(4);
            }
            const float4 m4 = *reinterpret_cast<const float4*>(scs + 4);
            const float c24 = scs[1], xb = scs[16 + s];
            uint32_t vf[2][2][4], vm[2][2];
            {
                const uint32_t va = vb + (C ? to + DH * 16 : SM_VX + (s & 1) * 8192);
#pragma unroll
                for (int i = 0; i < 4; i++) ldsm_x4(vf[i >> 1][i & 1], va + (i >> 1) * 256 + (i & 1) * 4096);
            }
            float scale;
            {
                const float bound = fmaxf(fmaxf(fmaxf(m4.x, m4.y), fmaxf(m4.z, m4.w)) * minv, xb) * c24;
                int e = 141 - (int)((__float_as_uint(bound) >> 23) & 255u);
                e = e > 100 ? 100 : e;
                scale = __uint_as_float((uint32_t)(127 + e) << 23);
            }
            uint32_t s0 = l8 + (role & 1) * 1280, s1 = l8 + ((role & 1) ^ 1) * 1280, oa = l16 + wq * 512;
            asm volatile("" : "+f"(scale), "+r"(s0), "+r"(s1), "+r"(oa));
            FS(7, vf[1][1][0]);
            constexpr float EC = (float)(1.4426950408889634 * 0.08838834764831845);
            if (!C) named_bar(6, 160);
            if (C) mbar_wait(sbase + B_SB + 8 * (s & 1), ph);
            float sv[5][2];
#pragma unroll
            for (int j = 0; j < 5; j++) lds64f(sv[j][0], sv[j][1], s0 + SM_S + j * 256);
            if (!C) {
#pragma unroll
                for (int j = 0; j < 5; j++) { sv[j][0] *= EC; sv[j][1] *= EC; asm volatile("" : "+f"(sv[j][0]), "+f"(sv[j][1])); }
                mbar_wait(sbase + B_SB + 8 * (s & 1), ph);
            }
            FS(6, 0);
            uint32_t p[5];
            {
                float sr[5][2];
#pragma unroll
                for (int j = 0; j < 5; j++) lds64f(sr[j][0], sr[j][1], s1 + SM_S + j * 256);
                lds64(vm[0][0], vm[0][1], l8 + SM_VM + wq * 512);
                lds64(vm[1][0], vm[1][1], l8 + SM_VM + wq * 512 + 256);
                if (C) {
#pragma unroll
                    for (int j = 0; j < 5; j++) { sv[j][0] *= EC; sv[j][1] *= EC; }
                }
#pragma unroll
                for (int j = 0; j < 5; j++) { sv[j][0] = fmaf(sr[j][0], EC, sv[j][0]); sv[j][1] = fmaf(sr[j][1], EC, sv[j][1]); }
                float mx = fmaxf(fmaxf(fmaxf(sv[0][0], sv[0][1]), fmaxf(sv[1][0], sv[1][1])), fmaxf(fmaxf(sv[2][0], sv[2][1]), fmaxf(sv[3][0], sv[3][1])));
                mx = fmaxf(mx, fmaxf(sv[4][0], sv[4][1]));
                {
                    const float m1 = __shfl_xor_sync(0xffffffffu, mx, 1), m2 = __shfl_xor_sync(0xffffffffu, mx, 2), m3 = __shfl_xor_sync(0xffffffffu, mx, 3);
                    mx = fmaxf(fmaxf(mx, m1), fmaxf(m2, m3));
                }
#pragma unroll
                for (int jj = 0; jj < 5; jj++) {
                    const int j = (jj + 1) % 5;
                    asm("ex2.approx.ftz.f32 %0, %1;" : "=f"(sv[j][0]) : "f"(sv[j][0] - mx));
                    asm("ex2.approx.ftz.f32 %0, %1;" : "=f"(sv[j][1]) : "f"(sv[j][1] - mx));
                    p[j] = pack_bf16(sv[j][0], sv[j][1]);
                }
            }
            FS(0, p[0]);
            uint32_t b[4][4];
            float zs[4];
            {
                float o0[2][4], o1[2][4];
                mma_z(o0[0], vf[0][0], p[1], p[2]);
                mma_z(o0[1], vf[1][0], p[1], p[2]);
                mma_z(o1[0], vf[0][1], p[3], p[4]);
                mma_z(o1[1], vf[1][1], p[3], p[4]);
                mma_k8(o0[0], vm[0][0], vm[0][1], p[0]);
                mma_k8(o0[1], vm[1][0], vm[1][1], p[0]);
                const uint32_t one4[4] = {0x3f803f80u, 0x3f803f80u, 0x3f803f80u, 0x3f803f80u};
                mma_z(zs, one4, p[1], p[2]);
                mma_bf16(zs, one4, p[3], p[4]);
                mma_k8(zs, one4[0], one4[1], p[0]);
                uint32_t ow[4];
#pragma unroll
                for (int m = 0; m < 2; m++) {
                    ow[2 * m] = pack_bf16(o0[m][0] + o1[m][0], o0[m][1] + o1[m][1]);
                    ow[2 * m + 1] = pack_bf16(o0[m][2] + o1[m][2], o0[m][3] + o1[m][3]);
                }
                stsm_x4(oa + SM_O, ow[0], ow[1], ow[2], ow[3]);
                FS(2, 0);
#pragma unroll
                for (int i = 0; i < 4; i++) b[0][i] = movm(ow[i]);
            }
            float acc[3][2][4];
            named_bar(3, 128);
#pragma unroll
            for (int i = 1; i < 4; i++) ldsm_x4_t(b[i], l16 + SM_O + ((wq + i) & 3) * 512);
#pragma unroll
            for (int c = 0; c < 2; c++)
#pragma unroll
                for (int t = 0; t < 3; t++) mma_z(acc[t][c], wo[t][c], b[0][2 * c], b[0][2 * c + 1]);
            float z0, z1;
            asm volatile("rcp.approx.ftz.f32 %0, %1;" : "=f"(z0) : "f"(zs[0]));
            asm volatile("rcp.approx.ftz.f32 %0, %1;" : "=f"(z1) : "f"(zs[1]));
            z0 *= scale; z1 *= scale;
            FS(3, b[1][0]);
#pragma unroll
            for (int i = 1; i < 4; i++)
#pragma unroll
                for (int c = 0; c < 2; c++)
#pragma unroll
                    for (int t = 0; t < 3; t++) mma_bf16(acc[t][c], wo[t][2 * i + c], b[i][2 * c], b[i][2 * c + 1]);
            {
                uint32_t w[6];
#pragma unroll
                for (int t = 0; t < 3; t++) {
                    w[2 * t] = pack_f16(fmaf(acc[t][1][0], z0, acc[t][0][0] * z0), fmaf(acc[t][1][1], z1, acc[t][0][1] * z1));
                    w[2 * t + 1] = pack_f16(fmaf(acc[t][1][2], z0, acc[t][0][2] * z0), fmaf(acc[t][1][3], z1, acc[t][0][3] * z1));
                }
                FS(8, w[5]);
                asm volatile("red.relaxed.gpu.global.add.noftz.v4.f16x2 [%0], {%1,%2,%3,%4};" :: "l"(dst), "r"(w[0]), "r"(w[1]), "r"(w[2]), "r"(0x3c00u) : "memory");
                asm volatile("red.relaxed.gpu.global.add.noftz.v4.f16x2 [%0], {%1,%2,%3,%4};" :: "l"(dst + 4096), "r"(w[3]), "r"(w[4]), "r"(w[5]), "r"(0x3c00u) : "memory");
            }
            FS(9, 0);
            if (s == 0) TSQ(5);
            bar_arrive(4, 384);
            const uint32_t t0 = clock32();
            minv = __uint_as_float(0x7f000000u - __float_as_uint(scale));
            if (lane_o == 0) {
                if (wq == 0) scs[2] = minv;
                if (wq == 2 && C && s + 2 < NSEG) { while (clock32() - t0 < VX_DELAY) {} vx_copy(sbase, s + 1, 1); }
                if (s + 3 < NSEG) {
                    if (wq == 0) mbar_expect(sbase + B_SB + 8 * (s & 1), C ? 2560 : 1280 + 2048);
                    if (wq == 1) mbar_expect(sbase + B_XT + 8 * b3, XBUF);
                    if (wq == 3 && !C) mbar_expect(sbase + B_VX + 8 * (s & 1), 8192);
                }
            }
            __syncwarp();
#pragma unroll
            for (int k2 = 0; k2 < 2; k2++) if (!C) ldsm_x4_t(kf[k2], ka + ((s + 1) & 3) * TBUF + k2 * 512);
            const uint4* src = reinterpret_cast<const uint4*>(dst + (wq * 16 - role * 32) * 1024);
            dst += n3 == 0 ? -256 : 128;
            asm volatile("" : "+l"(dst));
            mx2 = poll_mem(src, l16 + SM_M + wq * 2304, t0);
            if (s == 0) TSQ(6);
            b3 = n3;
        }
        if (!C) bar_arrive(2, 384);
        };
        if (role == 2) helper_loop(Flag<true>()); else helper_loop(Flag<false>());
    }
    TS3C(1);
    if (role == 2 && warp >= 4) {
        const int sg = warp < 8, wq = warp & 3, lane = lane_o;
        const uint32_t qk = sbase + SM_X + XBUF + sg * (2 * 9216), ob = sbase + SM_X + 2 * XBUF + sg * 8192;
        TST(0);
        mbar_wait(sbase + B_VX + 8 * sg, 0);
        fence_async();
        TST(1);
        float sc[20];
        {
            const uint64_t da = smem_desc(qk + 1024, 128, 1024), db = smem_desc(qk, 128, 2048);
            wg_fence();
#pragma unroll
            for (int ks = 0; ks < 8; ks++) wgmma_n40_ss(sc, da + (uint64_t)((ks >> 2) * 576 + (ks & 3) * 16), db + (uint64_t)((ks >> 2) * 576 + (ks & 3) * 16), ks > 0);
            wg_commit();
            wg_wait0();
        }
        uint32_t pa[3][4];
        xrow_softmax(sc, pa, wq, lane);
        float o[2][32];
        const uint64_t dv = smem_desc(sbase + SM_T + ((NSEG - 2 + sg) & 3) * TBUF, 2048, 128);
        wg_fence();
#pragma unroll
        for (int hf = 0; hf < 2; hf++)
#pragma unroll
            for (int ks = 0; ks < 3; ks++) { if (ks == 0) wgmma_n64_z(o[hf], pa[0], dv + (uint64_t)(hf * 64)); else wgmma_n64(o[hf], pa[ks], dv + (uint64_t)(hf * 64 + ks * 256), 1); }
        wg_commit();
        wg_wait0();
#pragma unroll
        for (int hf = 0; hf < 2; hf++)
#pragma unroll
            for (int i = 0; i < 2; i++)
                stsm_x4(ob + hf * 4096 + wq * 1024 + i * 512 + lane * 16, pack_bf16(o[hf][16 * i], o[hf][16 * i + 1]), pack_bf16(o[hf][16 * i + 4], o[hf][16 * i + 5]),
                        pack_bf16(o[hf][16 * i + 8], o[hf][16 * i + 9]), pack_bf16(o[hf][16 * i + 12], o[hf][16 * i + 13]));
        fence_async();
        named_bar(11 + sg, 128);
        TST(2);
        if ((tid & 127) == 0) {
            unsigned char* dst = reinterpret_cast<unsigned char*>(g_ox) + ((size_t)((NSEG / 2 - 1) * NH + h)) * 16384 + sg * 4096;
            asm volatile("cp.async.bulk.global.shared::cta.bulk_group [%0], [%1], 4096;" :: "l"(dst), "r"(ob) : "memory");
            asm volatile("cp.async.bulk.global.shared::cta.bulk_group [%0], [%1], 4096;" :: "l"(dst + 8192), "r"(ob + 4096) : "memory");
            asm volatile("cp.async.bulk.commit_group;" ::: "memory");
            asm volatile("cp.async.bulk.wait_group 0;" ::: "memory");
            asm volatile("red.relaxed.gpu.global.add.u32 [%0], 1;" :: "l"(&g_prog[(NSEG / 2 - 1) * 8 + (h >> 2)]) : "memory");
        }
        TST(3);
    }
    __syncwarp();
    cluster_sync_all();
}

extern "C" void kernel_launch(void* const* d_in, const int* in_sizes, int n_in, void* d_out, int out_size) {
    const bf16* x = (const bf16*)d_in[0];
    const bf16* mem0 = (const bf16*)d_in[1];
    const bf16* Wq = (const bf16*)d_in[2];
    const bf16* Wk = (const bf16*)d_in[3];
    const bf16* Wv = (const bf16*)d_in[4];
    const bf16* Wo = (const bf16*)d_in[5];
    const bf16* logA = (const bf16*)d_in[8];
    const bf16* Aim = (const bf16*)d_in[9];
    const bf16* Cre = (const bf16*)d_in[10];
    const bf16* Cim = (const bf16*)d_in[11];
    const bf16* logdt = (const bf16*)d_in[12];
    const bf16* dskip = (const bf16*)d_in[13];
    const bf16* gw = (const bf16*)d_in[14];
    bf16* out = (bf16*)d_out;
    static bool attr_done = false;
    typedef CUresult (*EncFn)(CUtensorMap*, CUtensorMapDataType, cuuint32_t, void*, const cuuint64_t*, const cuuint64_t*, const cuuint32_t*,
                              const cuuint32_t*, CUtensorMapInterleave, CUtensorMapSwizzle, CUtensorMapL2promotion, CUtensorMapFloatOOBfill);
    static EncFn enc = nullptr;
    if (!attr_done) {
        void* fn = nullptr;
        cudaDriverEntryPointQueryResult qr;
        cudaGetDriverEntryPoint("cuTensorMapEncodeTiled", &fn, cudaEnableDefault, &qr);
        enc = (EncFn)fn;
        cudaFuncSetAttribute(k_chain, cudaFuncAttributeMaxDynamicSharedMemorySize, 232448);
        cudaFuncSetAttribute(k_side, cudaFuncAttributeMaxDynamicSharedMemorySize, SIDE_SMEM);
        attr_done = true;
    }
    CUtensorMap tmx;
    {
        const cuuint64_t dims[3] = {64, (cuuint64_t)S_LEN, 9};
        const cuuint64_t strides[2] = {(cuuint64_t)DM * 2, 128};
        const cuuint32_t box[3] = {64, (cuuint32_t)SEG, 3};
        const cuuint32_t es[3] = {1, 1, 1};
        enc(&tmx, CU_TENSOR_MAP_DATA_TYPE_BFLOAT16, 3, (void*)x, dims, strides, box, es, CU_TENSOR_MAP_INTERLEAVE_NONE,
            CU_TENSOR_MAP_SWIZZLE_128B, CU_TENSOR_MAP_L2_PROMOTION_L2_128B, CU_TENSOR_MAP_FLOAT_OOB_FILL_NONE);
    }
    CUtensorMap tmw[3];
    for (int i = 0; i < 3; i++) {
        const cuuint64_t dims[2] = {(cuuint64_t)HD, (cuuint64_t)DM};
        const cuuint64_t strides[1] = {(cuuint64_t)HD * 2};
        const cuuint32_t box[2] = {64, 64};
        const cuuint32_t es[2] = {1, 1};
        enc(&tmw[i], CU_TENSOR_MAP_DATA_TYPE_BFLOAT16, 2, (void*)(i == 0 ? Wq : (i == 1 ? Wk : Wv)), dims, strides, box, es, CU_TENSOR_MAP_INTERLEAVE_NONE,
            CU_TENSOR_MAP_SWIZZLE_128B, CU_TENSOR_MAP_L2_PROMOTION_L2_256B, CU_TENSOR_MAP_FLOAT_OOB_FILL_NONE);
    }
    CUtensorMap tmo;
    {
        const cuuint64_t dims[2] = {(cuuint64_t)DM, (cuuint64_t)HD};
        const cuuint64_t strides[1] = {(cuuint64_t)DM * 2};
        const cuuint32_t box[2] = {64, 128};
        const cuuint32_t es[2] = {1, 1};
        enc(&tmo, CU_TENSOR_MAP_DATA_TYPE_BFLOAT16, 2, (void*)Wo, dims, strides, box, es, CU_TENSOR_MAP_INTERLEAVE_NONE,
            CU_TENSOR_MAP_SWIZZLE_128B, CU_TENSOR_MAP_L2_PROMOTION_L2_128B, CU_TENSOR_MAP_FLOAT_OOB_FILL_NONE);
    }
    CUtensorMap tmx2;
    {
        const cuuint64_t dims[2] = {(cuuint64_t)DM, (cuuint64_t)S_LEN};
        const cuuint64_t strides[1] = {(cuuint64_t)DM * 2};
        const cuuint32_t box[2] = {64, 64};
        const cuuint32_t es[2] = {1, 1};
        enc(&tmx2, CU_TENSOR_MAP_DATA_TYPE_BFLOAT16, 2, (void*)x, dims, strides, box, es, CU_TENSOR_MAP_INTERLEAVE_NONE,
            CU_TENSOR_MAP_SWIZZLE_128B, CU_TENSOR_MAP_L2_PROMOTION_L2_128B, CU_TENSOR_MAP_FLOAT_OOB_FILL_NONE);
    }
    k_chain<<<NCTA, 384, 232448>>>(tmx, tmw[0], tmw[1], tmw[2], tmx2, tmo, mem0, x);
    {
        cudaLaunchConfig_t cfg = {};
        cfg.gridDim = dim3(SD_NCTA); cfg.blockDim = dim3(512); cfg.dynamicSmemBytes = SIDE_SMEM; cfg.stream = cudaStreamPerThread;
        cudaLaunchAttribute at[1];
        at[0].id = cudaLaunchAttributeProgrammaticStreamSerialization;
        at[0].val.programmaticStreamSerializationAllowed = 1;
        cfg.attrs = at; cfg.numAttrs = 1;
        cudaLaunchKernelEx(&cfg, k_side, tmo, x, logA, Aim, Cre, Cim, logdt, Wo, dskip, gw, out);
    }
}
```

```cpp
#include <cuda_runtime.h>
#include <cuda.h>
#include <cuda_bf16.h>
#include <stdint.h>

typedef __nv_bfloat16 bf16;
#define LDV4 "ld.volatile.global.v4.u32 {%0,%1,%2,%3}, [%4];"
#define STV4 "st.volatile.global.v4.u32 [%0], {%1,%2,%3,%4};"
#define STV2 "st.volatile.global.v2.u32 [%0], {%1,%2};"

constexpr int S_LEN = 2048, DM = 576, NH = 32, DH = 128, HD = 4096, MEMT = 8, SEG = 32, NSEG = 64, NST = 128;

__device__ __align__(128) bf16 g_gate[S_LEN];
constexpr int NCTA = NH * 3;
__device__ __align__(1024) unsigned char g_acc[96 * 1024];
__device__ __align__(128) uint2 g_norm[NCTA];
__device__ __align__(128) uint32_t g_rx[NSEG];
__device__ __align__(128) unsigned char g_qkv[NSEG][NH][3][10240];
__device__ __align__(128) bf16 g_ox[S_LEN * HD];
__device__ __align__(128) uint4 g_fp[8][36][6][128];
__device__ __align__(128) unsigned g_flag[NH * NSEG];
__device__ unsigned g_prog[NSEG / 2 * 8];
__device__ unsigned g_gcnt[64];
__device__ unsigned g_epoch;
__device__ __align__(128) uint2 g_tick;
__device__ __align__(128) bf16 g_y[DM * S_LEN];

#define TS3(slot) do {} while (0)
#define TS3P(slot) do {} while (0)
#define TSQ(slot) do {} while (0)
#define TS3W(slot) do {} while (0)
#define TSS(row, slot) do {} while (0)
#define TS3C(slot) do {} while (0)
#define TST(slot) do {} while (0)
#define TSA(seg, slot) do {} while (0)
#define TSG(i) do {} while (0)
#define FS(i, dep) do {} while (0)
__device__ __forceinline__ uint32_t smem_u32(const void* p) { return (uint32_t)__cvta_generic_to_shared(p); }
__device__ __forceinline__ float bf16r(float x) { return __bfloat162float(__float2bfloat16_rn(x)); }
__device__ __forceinline__ uint32_t pack_bf16(float lo, float hi) {
    __nv_bfloat162 v = __floats2bfloat162_rn(lo, hi);
    return *reinterpret_cast<uint32_t*>(&v);
}
__device__ __forceinline__ void ldsm_x4(uint32_t (&r)[4], uint32_t addr) {
    asm volatile("ldmatrix.sync.aligned.m8n8.x4.shared.b16 {%0,%1,%2,%3}, [%4];"
                 : "=r"(r[0]), "=r"(r[1]), "=r"(r[2]), "=r"(r[3]) : "r"(addr));
}
__device__ __forceinline__ void ldsm_x4_t(uint32_t (&r)[4], uint32_t addr) {
    asm volatile("ldmatrix.sync.aligned.m8n8.x4.trans.shared.b16 {%0,%1,%2,%3}, [%4];"
                 : "=r"(r[0]), "=r"(r[1]), "=r"(r[2]), "=r"(r[3]) : "r"(addr));
}
__device__ __forceinline__ void mma_bf16(float (&d)[4], const uint32_t (&a)[4], uint32_t b0, uint32_t b1) {
    asm volatile("mma.sync.aligned.m16n8k16.row.col.f32.bf16.bf16.f32 {%0,%1,%2,%3}, {%4,%5,%6,%7}, {%8,%9}, {%0,%1,%2,%3};"
                 : "+f"(d[0]), "+f"(d[1]), "+f"(d[2]), "+f"(d[3])
                 : "r"(a[0]), "r"(a[1]), "r"(a[2]), "r"(a[3]), "r"(b0), "r"(b1));
}
__device__ __forceinline__ uint2 ld_vol_u2(const uint2* p) {
    uint2 v; asm volatile("ld.volatile.global.v2.u32 {%0,%1}, [%2];" : "=r"(v.x), "=r"(v.y) : "l"(p) : "memory"); return v;
}
__device__ __forceinline__ void st_vol_u2(uint2* p, uint2 v) {
    asm volatile(STV2 :: "l"(p), "r"(v.x), "r"(v.y) : "memory");
}
__device__ __forceinline__ unsigned ld_acq(const unsigned* p) {
    unsigned v; asm volatile("ld.acquire.gpu.global.u32 %0, [%1];" : "=r"(v) : "l"(p) : "memory"); return v;
}
#define XK 36
#define NC1 7
#define NS 6
#define NP 4
#define X_OXSZ 16384
#define GATE_A 1150
#define GATE_B 480
#define GATE_P 1880u
#define STAGGER 0
#define RLX_SLEEP 300
#define VX_DELAY 100
#define EARLY4 0
#define SPEC_M 1
#define SPEC_H 1
#define C1_DELAY 0
#define C2_DELAY 0
#define SS_POS 2
#define UNGATE_G 3
#define GATE_Y 0
#define GATE_S 0
#define GATE_F 1
#define W14_SLEEP 60
#define TL_DELAY 600
#define POLL_DELAY 500
#define UNGATE 6
constexpr unsigned SPIN_LIMIT = 1u << 20;
constexpr int NATT = NSEG - 2;

constexpr int SD_CH = 16;
constexpr int SD_NCTA = DM / SD_CH;
constexpr int SD_ROW = 528;
constexpr int SD_U = 8 * SD_ROW;
constexpr int SD_TAP = 5888;
constexpr int SD_CPY = 1376 * 2;
constexpr int SD_WSTR = SD_TAP + 2 * SD_CPY;
constexpr int SD_SMEM = SD_CH * SD_U + 8 * SD_WSTR;
constexpr int O_U = 79, O_U3 = 911, O_U4 = 1055, O_W79 = 1023, O_W35 = 1151, O_W610 = 1279, O_W511 = 1487;

__device__ __forceinline__ uint32_t lds32(uint32_t a) { uint32_t v; asm volatile("ld.shared.u32 %0, [%1];" : "=r"(v) : "r"(a)); return v; }
__device__ __forceinline__ void tap_tile(uint32_t (&t)[4], uint32_t a) {
    asm volatile("ld.volatile.shared.u32 %0, [%4];\nld.volatile.shared.u32 %1, [%4+-16];\nld.volatile.shared.u32 %2, [%4+16];\nld.volatile.shared.u32 %3, [%4];"
                 : "=r"(t[0]), "=r"(t[1]), "=r"(t[2]), "=r"(t[3]) : "r"(a));
}
constexpr uint32_t sd_pass(int type, int dl, int o, int d0, int d1) { return (uint32_t)(type | dl << 2 | d0 << 8 | d1 << 12 | o << 17); }
__constant__ uint32_t SD_PASS[14] = {sd_pass(0, 0, O_U, 0, 2), sd_pass(0, 1, O_U + 96, 0, 2), sd_pass(0, 2, O_U + 192, 0, 4), sd_pass(0, 3, O_U + 288, 0, 2), sd_pass(1, 0, O_U3, 8, 8),
                                     sd_pass(0, 4, O_U + 384, 0, 2), sd_pass(1, 0, O_U4, 8, 15), sd_pass(0, 5, O_U + 480, 0, 2), sd_pass(0, 6, O_U + 576, 0, 4), sd_pass(0, 7, O_U + 672, 0, 2),
                                     sd_pass(2, 0, O_W35, 2, 8), sd_pass(3, 0, O_W79, 2, 4), sd_pass(2, 1, O_W610, 4, 8), sd_pass(3, 0, O_W511, 8, 15)};
__device__ __forceinline__ uint32_t band2(int x, int lo, int hi) { return (x >= lo && x <= hi ? 0x3f80u : 0u) | (x + 1 >= lo && x + 1 <= hi ? 0x3f800000u : 0u); }
__device__ __forceinline__ void mma_z(float (&d)[4], const uint32_t (&a)[4], uint32_t b0, uint32_t b1);
__device__ __forceinline__ void put_tap(uint32_t a, float v) {
    asm volatile("{\n.reg .b16 h;\ncvt.rn.bf16.f32 h, %1;\nst.shared.b16 [%0], h;\nst.shared.b16 [%0+%2], h;\n}" :: "r"(a), "f"(v), "n"(SD_CPY - 2) : "memory");
}

__device__ __forceinline__ void named_bar(int id, int n) { asm volatile("bar.sync %0, %1;" :: "r"(id), "r"(n) : "memory"); }
__device__ __forceinline__ uint32_t pack_f16(float lo, float hi) {
    uint32_t r; asm("cvt.rn.f16x2.f32 %0, %1, %2;" : "=r"(r) : "f"(hi), "f"(lo)); return r;
}
__device__ __forceinline__ void cexp_t(float lr, float turns, float& re, float& im) {
    float m;
    asm("ex2.approx.ftz.f32 %0, %1;" : "=f"(m) : "f"(lr));
    const float a = (turns - rintf(turns)) * 6.283185307179586f;
    re = m * __cosf(a); im = m * __sinf(a);
}
__device__ __forceinline__ void csq(float& re, float& im) { const float r = re * re - im * im; im = 2.f * re * im; re = r; }
__device__ __forceinline__ void kb_state(const float* tp, float gf, uint32_t (&a)[4][2], uint32_t (&b)[5]) {
    const float4 p0 = *reinterpret_cast<const float4*>(tp), p1 = *reinterpret_cast<const float4*>(tp + 4);
    float wr, wi;
    cexp_t(p0.x * gf, p0.y * gf, wr, wi);
    float vr = wr * p1.x - wi * p1.y, vi = wr * p1.y + wi * p1.x;
#pragma unroll
    for (int c = 0; c < 4; c++) {
        a[c][0] = pack_f16(wr, wi); a[c][1] = pack_f16(vr, vi);
        csq(wr, wi);
        if (c < 3) csq(vr, vi);
    }
    b[0] = pack_f16(p0.z * wr - p0.w * wi, -p0.z * wi - p0.w * wr);
    float er = wr * p1.z - wi * p1.w, ei = wr * p1.w + wi * p1.z;
#pragma unroll
    for (int c = 0; c < 4; c++) {
        b[1 + c] = pack_f16(p0.z * er - p0.w * ei, -p0.z * ei - p0.w * er);
        if (c < 3) csq(er, ei);
    }
}
__device__ __forceinline__ uint32_t bf2_mul(uint32_t a, uint32_t b) { uint32_t r; asm("mul.rn.bf16x2 %0, %1, %2;" : "=r"(r) : "r"(a), "r"(b)); return r; }
__device__ __forceinline__ uint32_t bf2_add(uint32_t a, uint32_t b) { uint32_t r; asm("add.rn.bf16x2 %0, %1, %2;" : "=r"(r) : "r"(a), "r"(b)); return r; }
__device__ __forceinline__ uint32_t bf2_sub(uint32_t a, uint32_t b) { uint32_t r; asm("sub.rn.bf16x2 %0, %1, %2;" : "=r"(r) : "r"(a), "r"(b)); return r; }
__device__ __forceinline__ void wait_cnt(const unsigned* p, unsigned target) {
    unsigned it = 0;
    while ((int)(ld_acq(p) - target) < 0 && ++it < SPIN_LIMIT) __nanosleep(64);
}
__device__ __forceinline__ uint32_t gtime32() { uint32_t t; asm volatile("mov.u32 %0, %%globaltimer_lo;" : "=r"(t) :: "memory"); return t; }
__device__ __forceinline__ void gate(uint32_t tick_addr) {
    uint32_t t1, p;
    asm volatile("ld.volatile.shared.v2.u32 {%0,%1}, [%2];" : "=r"(t1), "=r"(p) : "r"(tick_addr) : "memory");
    uint32_t d = gtime32() - t1;
    if (d < 4u * p) {
        d -= d >= 2u * p ? 2u * p : 0u;
        d -= d >= p ? p : 0u;
        if (d + GATE_A >= p && d + GATE_B < p) {
            const uint32_t t2 = gtime32() + (p - GATE_B - d);
            while ((int)(gtime32() - t2) < 0) {}
        }
    }
}

__device__ __forceinline__ void read_tick(uint32_t tick_addr) {
    const uint2 tk = ld_vol_u2(&g_tick);
    uint32_t p = tk.x - tk.y;
    p = p > GATE_P + 100u ? GATE_P + 100u : p;
    asm volatile("st.volatile.shared.v2.u32 [%0], {%1,%2};" :: "r"(tick_addr), "r"(tk.x), "r"(p) : "memory");
}

__device__ __forceinline__ void s4d_phase(unsigned char* smem_raw, const bf16* __restrict__ x, const bf16* __restrict__ logA,
                                          const bf16* __restrict__ Aim, const bf16* __restrict__ Cre, const bf16* __restrict__ Cim,
                                          const bf16* __restrict__ logdt, const bf16* __restrict__ dskip, const bf16* __restrict__ wslice, unsigned ep, uint32_t tick) {
    const int tid = threadIdx.x, warp = __shfl_sync(0xffffffffu, tid >> 5, 0), lane = tid & 31;
    const int d0 = blockIdx.x * SD_CH;
    float* tab = reinterpret_cast<float*>(smem_raw + SD_CH * SD_U + warp * SD_WSTR);
    const uint32_t wb = smem_u32(tab);
    const int g = lane >> 2, tq = lane & 3;
    uint2 prm[4];
    float ldt;
    auto load_prm = [&](int d) {
        prm[0] = __ldg(reinterpret_cast<const uint2*>(logA + d * NST) + lane); prm[1] = __ldg(reinterpret_cast<const uint2*>(Aim + d * NST) + lane);
        prm[2] = __ldg(reinterpret_cast<const uint2*>(Cre + d * NST) + lane); prm[3] = __ldg(reinterpret_cast<const uint2*>(Cim + d * NST) + lane);
        ldt = __bfloat162float(logdt[d]);
    };
    load_prm(d0 + warp);
    for (int i = lane; i < 2 * SD_CPY / 16; i += 32) reinterpret_cast<uint4*>(tab + SD_TAP / 4)[i] = make_uint4(0u, 0u, 0u, 0u);
    TS3(20);
#pragma unroll 1
    for (int ch = 0; ch < 2; ch++) {
        const int d = d0 + 8 * ch + warp;
        const uint32_t ub = smem_u32(smem_raw) + (8 * ch + warp) * SD_U;
        float k2048 = 0.f, sinv;
        {
            const float dt = bf16r(expf(ldt));
            uint32_t cm = __vmaxu2(__vmaxu2(prm[2].x & 0x7fff7fffu, prm[2].y & 0x7fff7fffu), __vmaxu2(prm[3].x & 0x7fff7fffu, prm[3].y & 0x7fff7fffu));
            cm = __reduce_max_sync(0xffffffffu, max(cm << 16, cm & 0xffff0000u));
            int e = 134 - (int)(__float_as_uint(__uint_as_float(cm) * dt) >> 23);
            e = e > 100 ? 100 : (e < -100 ? -100 : e);
            const float s2 = __uint_as_float((uint32_t)(128 + e) << 23);
            sinv = __uint_as_float((uint32_t)(127 - e) << 23);
#pragma unroll
            for (int j = 0; j < 4; j++) {
                float q[4];
#pragma unroll
                for (int i = 0; i < 4; i++) { const uint32_t w = j < 2 ? prm[i].x : prm[i].y; q[i] = __uint_as_float((j & 1) ? w & 0xffff0000u : w << 16); }
                const float zl = -bf16r(expf(q[0])) * dt * 1.4426950408889634f;
                const float zt = q[1] * dt * 0.15915494309189535f;
                const float cr = s2 * (q[2] * dt), ci = s2 * (q[3] * dt);
                float ar, ai, br, bi, er, ei;
                cexp_t(zl * 8.f, zt * 8.f, ar, ai);
                cexp_t(zl * 128.f, zt * 128.f, br, bi);
                cexp_t(zl * 2048.f, zt * 2048.f, er, ei);
                k2048 += cr * er - ci * ei;
                *reinterpret_cast<float4*>(tab + (lane + 32 * j) * 8) = make_float4(zl, zt, cr, ci);
                *reinterpret_cast<float4*>(tab + (lane + 32 * j) * 8 + 4) = make_float4(ar, ai, br, bi);
            }
#pragma unroll
            for (int o = 16; o; o >>= 1) k2048 += __shfl_xor_sync(0xffffffffu, k2048, o);
        }
        __syncwarp();
        {
            float kc[5][4];
#pragma unroll
            for (int i = 0; i < 5; i++) { kc[i][0] = kc[i][1] = kc[i][2] = kc[i][3] = 0.f; }
            const float gf = (float)g;
#pragma unroll 2
            for (int ks = 0; ks < 16; ks++) {
                uint32_t a0[4][2], a1[4][2], b0[5], b1[5];
                kb_state(tab + (8 * ks + tq) * 8, gf, a0, b0);
                kb_state(tab + (8 * ks + 4 + tq) * 8, gf, a1, b1);
#pragma unroll
                for (int i = 0; i < 5; i++) {
                    const int c = i > 0 ? i - 1 : 0;
                    asm volatile("mma.sync.aligned.m16n8k16.row.col.f32.f16.f16.f32 {%0,%1,%2,%3}, {%4,%5,%6,%7}, {%8,%9}, {%0,%1,%2,%3};"
                                 : "+f"(kc[i][0]), "+f"(kc[i][1]), "+f"(kc[i][2]), "+f"(kc[i][3])
                                 : "r"(a0[c][0]), "r"(a0[c][1]), "r"(a1[c][0]), "r"(a1[c][1]), "r"(b0[i]), "r"(b1[i]));
                }
            }
            const uint32_t tp = wb + SD_TAP;
            const uint32_t a0 = tp + 2 * (O_U + 96 * g - 4 * tq);
            const uint32_t a2 = tp + 2 * (((g & 1) ? O_U + 96 * (2 * (g & 3)) : ((g & 2) ? O_W35 : O_W79 + 1)) - 32 - 8 * tq - (g >> 2));
            const uint32_t a3 = tp + 2 * (((g & 1) ? O_W35 : O_W610 + 1) - 64 - 16 * tq - (g >> 1));
            const uint32_t a4 = tp + 2 * (-128 - 32 * tq - g);
#pragma unroll
            for (int c = 0; c < 4; c++) {
                const int e = (c & 1) * 16 + (c >> 1) * 8;
                const bool first = c == 0 && lane == 0;
                put_tap(a0 - e / 4, kc[0][c] * sinv);
                put_tap(a0 - 32 - e / 4, kc[1][c] * sinv);
                put_tap(first ? tp + 2 * (O_U - 32) : a2 - e / 2, kc[2][c] * sinv);
                put_tap(first ? tp + 2 * (O_W79 - 63) : a3 - e, kc[3][c] * sinv);
                put_tap(first ? tp + 2 * (O_W610 - 127) : a4 + 2 * (O_W511 + 1 - e), kc[4][c] * sinv);
                if ((g & 1) == 0) {
                    put_tap(a4 + 2 * (O_U4 - e), kc[4][c] * sinv);
                    put_tap(first ? tp + 2 * (O_U3 - 128) : a4 + 2 * (O_U4 + 1 - e), kc[4][c] * sinv);
                }
            }
            if (lane == 0) {
                put_tap(tp + 2 * (O_U + 96 - 32), kc[2][0] * sinv);
                put_tap(tp + 2 * (O_U + 192 - 64), kc[3][0] * sinv);
                put_tap(tp + 2 * (O_W511 - 255), k2048 * sinv);
                put_tap(tp + 2 * (O_U4 - 255), k2048 * sinv);
            }
        }
        TS3(21 + 2 * ch);
        if (ch == 0) { if (!STAGGER || warp < 4) named_bar(1, 384); }
        else {
#pragma unroll
            for (int i = 0; i < 4; i++) asm volatile("prefetch.global.L2 [%0];" :: "l"(wslice + (size_t)((tid & 127) + 128 * i) * DM));
        }
        __syncwarp();
        if (tid == 0) TSS(18, 4 * ch);
        const uint32_t sh = wb + 80 + 11 * SD_ROW;
#pragma unroll
        for (int p = 0; p < 8; p++) {
            uint4 v;
            asm volatile("ld.shared.v4.u32 {%0,%1,%2,%3}, [%4];" : "=r"(v.x), "=r"(v.y), "=r"(v.z), "=r"(v.w) : "r"(ub + p * SD_ROW + lane * 16) : "memory");
            uint32_t pv = __shfl_up_sync(0xffffffffu, v.w, 1);
            pv = lane == 0 ? 0u : pv;
            asm volatile("st.shared.v4.u32 [%0], {%1,%2,%3,%4};" :: "r"(sh + (p - 8) * SD_ROW + lane * 16), "r"(__byte_perm(pv, v.x, 0x5432)), "r"(__byte_perm(v.x, v.y, 0x5432)),
                         "r"(__byte_perm(v.y, v.z, 0x5432)), "r"(__byte_perm(v.z, v.w, 0x5432)) : "memory");
            if (p >= 5) asm volatile("st.shared.v4.u32 [%0], {%1,%2,%3,%4};" :: "r"(sh + (p - 16) * SD_ROW + lane * 16), "r"(pv), "r"(v.x), "r"(v.y), "r"(v.z) : "memory");
        }
        __syncwarp();
        if (tid == 0) TSS(18, 4 * ch + 1);
        float acc[16][4];
#pragma unroll
        for (int i = 0; i < 16; i++) { acc[i][0] = acc[i][1] = acc[i][2] = acc[i][3] = 0.f; }
        {
            const uint32_t ka = wb + SD_TAP + ((g & 1) ? 0 : SD_CPY - 2) + 2 * (2 * tq - g);
            uint32_t b[16][2], b2[14][2];
#pragma unroll
            for (int k = 0; k < 16; k++) { b[k][0] = b[k][1] = 0u; if (k < 14) b2[k][0] = b2[k][1] = 0u; }
#pragma unroll 1
            for (int ps = 0; ps < 14; ps++) {
                const uint32_t pw = __shfl_sync(0xffffffffu, SD_PASS[ps], 0), type = pw & 3u, kp = ka + (pw >> 16);
                const int dl = (pw >> 2) & 7, d0 = (pw >> 8) & 15, d1 = (pw >> 12) & 15;
                uint32_t t[2][4];
                tap_tile(t[0], kp - 32 * d0);
                if (type == 0) {
                    const int p = (lane & 7) - dl;
                    const uint32_t ra = (p < 0 ? sh : ub) + p * SD_ROW + (lane >> 3) * 16;
#pragma unroll
                    for (int k = 0; k < 8; k++)
                        asm volatile("ldmatrix.sync.aligned.m8n8.x4.shared.b16 {%0,%1,%2,%3}, [%4];"
                                     : "=r"(b[2 * k][0]), "=r"(b[2 * k][1]), "=r"(b[2 * k + 1][0]), "=r"(b[2 * k + 1][1]) : "r"(ra + k * 64));
                } else if (type == 2) {
                    const int p = (lane & 15) - 11, xo = 2 * tq - g;
                    const uint32_t qa = (p < 0 ? sh : ub) + p * SD_ROW + (lane >> 4) * 16;
                    const int lx = 6 - 5 * dl, hx = 8 - 3 * dl, ly = 2 - 2 * dl, hy = 4 + 2 * dl;
                    const uint32_t sel[4] = {band2(xo, lx, hx), band2(xo, ly, hy), band2(xo + 8, lx, hx), band2(xo + 8, ly, hy)};
#pragma unroll
                    for (int k = 0; k < 14; k++) {
                        uint32_t q[4];
                        ldsm_x4_t(q, qa + k * 32);
#pragma unroll
                        for (int i = 0; i < 2; i++) {
                            float w[4];
                            mma_z(w, sel, q[2 * i], q[2 * i + 1]);
                            b[k][i] = pack_bf16(w[0], w[1]);
                            b2[k][i] = pack_bf16(w[2], w[3]);
                        }
                    }
                } else if (type == 3) {
#pragma unroll
                    for (int k = 0; k < 14; k++) { b[k][0] = b2[k][0]; b[k][1] = b2[k][1]; }
                }
#pragma unroll
                for (int d = 0; d < 16; d += 2) {
                    if (d >= 8 || d >= d0) {
                        tap_tile(t[1], kp - 32 * (d + 1));
#pragma unroll
                        for (int k = 0; k + d < 16; k++) mma_bf16(acc[k + d], t[0], b[k][0], b[k][1]);
                        if ((d == 2 || d == 4 || d == 8) && d == d1) break;
                        if (d < 14) tap_tile(t[0], kp - 32 * (d + 2));
#pragma unroll
                        for (int k = 0; k + d + 1 < 16; k++) mma_bf16(acc[k + d + 1], t[1], b[k][0], b[k][1]);
                    }
                }
            }
        }
        __syncwarp();
        if (tid == 0) TSS(18, 4 * ch + 2);
        load_prm(d0 + 8 + warp);
        if (ch == 0) { if (lane == 0) wait_cnt(&g_gcnt[0], SD_NCTA * ep); __syncwarp(); }
        if (tid == 0) TSS(18, 4 * ch + 3);
        uint4 gv[8];
#pragma unroll
        for (int i = 0; i < 8; i++) gv[i] = __ldcg(reinterpret_cast<const uint4*>(g_gate) + lane + 32 * i);
        const uint32_t dd = __byte_perm(*reinterpret_cast<const unsigned short*>(dskip + d), 0u, 0x1010);
#pragma unroll
        for (int i = 0; i < 8; i++) {
            uint32_t u[4];
            ldsm_x4_t(u, ub + (lane & 7) * SD_ROW + (lane >> 3) * 16 + i * 64);
            asm volatile("stmatrix.sync.aligned.m8n8.x4.shared.b16 [%0], {%1,%2,%3,%4};"
                         :: "r"(wb + (lane + 32 * i) * 16),
                            "r"(bf2_add(pack_bf16(acc[2 * i][0], acc[2 * i][1]), bf2_mul(u[0], dd))), "r"(bf2_add(pack_bf16(acc[2 * i][2], acc[2 * i][3]), bf2_mul(u[1], dd))),
                            "r"(bf2_add(pack_bf16(acc[2 * i + 1][0], acc[2 * i + 1][1]), bf2_mul(u[2], dd))), "r"(bf2_add(pack_bf16(acc[2 * i + 1][2], acc[2 * i + 1][3]), bf2_mul(u[3], dd))) : "memory");
        }
        if (GATE_Y) gate(tick);
        __syncwarp();
#pragma unroll
        for (int i = 0; i < 8; i++) {
            const uint4 y = *reinterpret_cast<const uint4*>(tab + (lane + 32 * i) * 4);
            *reinterpret_cast<uint4*>(g_y + (((lane >> 1) + 16 * i) * DM + d) * 16 + (lane & 1) * 8) =
                make_uint4(bf2_mul(bf2_sub(0x3f803f80u, gv[i].x), y.x), bf2_mul(bf2_sub(0x3f803f80u, gv[i].y), y.y),
                           bf2_mul(bf2_sub(0x3f803f80u, gv[i].z), y.z), bf2_mul(bf2_sub(0x3f803f80u, gv[i].w), y.w));
        }
        __syncwarp();
        TS3(22 + 2 * ch);
    }
}
__device__ __forceinline__ void s4d_stage_u(unsigned char* smem_raw, const bf16* __restrict__ x, int pt) {
    const int p = pt & 7, w0 = pt >> 3;
    const uint4* src = reinterpret_cast<const uint4*>(x + (size_t)(16 * w0 + p) * DM + blockIdx.x * SD_CH);
    uint32_t* dst = reinterpret_cast<uint32_t*>(smem_raw + p * SD_ROW) + w0;
#pragma unroll 1
    for (int b = 0; b < 4; b++) {
        uint4 v[2][2][2];
#pragma unroll
        for (int i = 0; i < 8; i++) v[i >> 2][(i >> 1) & 1][i & 1] = src[((b * 2 + (i >> 2)) * 256 + ((i >> 1) & 1) * 8) * (DM / 8) + (i & 1)];
#pragma unroll
        for (int i = 0; i < 4; i++) {
            const uint32_t* lo = reinterpret_cast<const uint32_t*>(&v[i >> 1][0][i & 1]);
            const uint32_t* hi = reinterpret_cast<const uint32_t*>(&v[i >> 1][1][i & 1]);
#pragma unroll
            for (int c = 0; c < 8; c++) dst[((i & 1) * 8 + c) * (SD_U / 4) + (b * 2 + (i >> 1)) * 16] = __byte_perm(lo[c >> 1], hi[c >> 1], (c & 1) ? 0x7632 : 0x5410);
        }
    }
    asm volatile("bar.arrive 1, 384;" ::: "memory");
}

constexpr int WOC = DM / 3;
constexpr int TBUF = 5 * DH * 16;
constexpr int XBUF = SEG * DM * 2;
constexpr float ATT_SCALE = 0.08838834764831845f;
constexpr int SM_BAR = 0;
constexpr int B_SB = 0, B_VX = 16, B_XT = 32, B_W = 64, B_E = 136;
constexpr int SM_SC = 256;
constexpr int SM_F = SM_SC + 1280;
constexpr int SM_VM = SM_F + 2048;
constexpr int SM_S = SM_VM + 2048;
constexpr int SM_O = SM_S + 2560;
constexpr int SM_M = SM_O + 2048;
constexpr int SM_WS = 19456;
constexpr int SM_T = SM_WS + 32768;
constexpr int SM_VX = SM_T + 4 * TBUF;
constexpr int SM_X = SM_VX + 2 * 8192;
constexpr int SM_X01 = SM_WS + DM * DH * 2;
__host__ __device__ constexpr int x01_off(int b) { return b == 2 ? 2048 : SM_X01 + (b < 2 ? b + 6 : b - 3) * 8192; }
constexpr int SM_E = SM_WS + 6 * 16384;
constexpr int CH_SMEM = SM_X01 + 8 * 8192;
static_assert(SM_M + DM * 16 <= SM_WS && SM_X + 3 * XBUF <= CH_SMEM && CH_SMEM <= 232448 && SM_X % 1024 == 0 && SM_X01 % 1024 == 0 && SM_M >= 10240 && SM_F <= 2048, "smem");
__device__ __forceinline__ uint32_t clock32() { uint32_t t; asm volatile("mov.u32 %0, %%clock;" : "=r"(t) :: "memory"); return t; }

__device__ __forceinline__ uint32_t mapa(uint32_t a, uint32_t rank) {
    uint32_t r; asm volatile("mapa.shared::cluster.u32 %0, %1, %2;" : "=r"(r) : "r"(a), "r"(rank)); return r;
}
__device__ __forceinline__ void st_async32(uint32_t addr, uint32_t v, uint32_t mbar) {
    asm volatile("st.async.weak.shared::cluster.mbarrier::complete_tx::bytes.b32 [%0], %1, [%2];" :: "r"(addr), "r"(v), "r"(mbar) : "memory");
}
__device__ __forceinline__ void mbar_init(uint32_t bar, uint32_t cnt) {
    asm volatile("mbarrier.init.shared::cta.b64 [%0], %1;" :: "r"(bar), "r"(cnt) : "memory");
}
__device__ __forceinline__ void mbar_expect(uint32_t bar, uint32_t bytes) {
    asm volatile("mbarrier.arrive.expect_tx.shared::cta.b64 _, [%0], %1;" :: "r"(bar), "r"(bytes) : "memory");
}
__device__ __forceinline__ void mbar_wait(uint32_t bar, uint32_t parity) {
    unsigned it = 0;
    while (true) {
        uint32_t ok;
        asm volatile("{\n.reg .pred p;\nmbarrier.try_wait.parity.shared::cta.b64 p, [%1], %2;\nselp.u32 %0, 1, 0, p;\n}"
                     : "=r"(ok) : "r"(bar), "r"(parity) : "memory");
        if (ok || ++it >= SPIN_LIMIT) break;
    }
}
__device__ __forceinline__ void mbar_wait_long(uint32_t bar, uint32_t parity) {
    unsigned it = 0;
    while (true) {
        uint32_t ok;
        asm volatile("{\n.reg .pred p;\nmbarrier.try_wait.parity.shared::cta.b64 p, [%1], %2, %3;\nselp.u32 %0, 1, 0, p;\n}"
                     : "=r"(ok) : "r"(bar), "r"(parity), "r"(20000u) : "memory");
        if (ok || ++it >= SPIN_LIMIT) break;
    }
}
__device__ __forceinline__ bool mbar_test(uint32_t bar, uint32_t parity) {
    uint32_t ok;
    asm volatile("{\n.reg .pred p;\nmbarrier.test_wait.parity.shared::cta.b64 p, [%1], %2;\nselp.u32 %0, 1, 0, p;\n}" : "=r"(ok) : "r"(bar), "r"(parity) : "memory");
    return ok != 0u;
}
__device__ __forceinline__ uint64_t policy_evict_first() {
    uint64_t pol; asm volatile("createpolicy.fractional.L2::evict_first.b64 %0, 1.0;" : "=l"(pol)); return pol;
}
__device__ __forceinline__ void cluster_sync_all() {
    asm volatile("barrier.cluster.arrive.release.aligned;\nbarrier.cluster.wait.acquire.aligned;" ::: "memory");
}
__device__ __forceinline__ uint4 ld_vol_u4(const uint4* p) {
    uint4 v; asm volatile(LDV4 : "=r"(v.x), "=r"(v.y), "=r"(v.z), "=r"(v.w) : "l"(p) : "memory"); return v;
}
__device__ __forceinline__ void ld_vol_u4_p(uint4& v, const uint4* p, uint32_t pred) {
    asm volatile("{\n.reg .pred p;\nsetp.ne.u32 p, %5, 0;\n@p " LDV4 "\n}"
                 : "+r"(v.x), "+r"(v.y), "+r"(v.z), "+r"(v.w) : "l"(p), "r"(pred) : "memory");
}
__device__ __forceinline__ void st_vol_u4(uint4* p, uint4 v) {
    asm volatile(STV4 :: "l"(p), "r"(v.x), "r"(v.y), "r"(v.z), "r"(v.w) : "memory");
}
__device__ __forceinline__ void mma_bf16_r(float (&d)[4], uint32_t a0, uint32_t a1, uint32_t a2, uint32_t a3, uint32_t b0, uint32_t b1) {
    asm volatile("mma.sync.aligned.m16n8k16.row.col.f32.bf16.bf16.f32 {%0,%1,%2,%3}, {%4,%5,%6,%7}, {%8,%9}, {%0,%1,%2,%3};"
                 : "+f"(d[0]), "+f"(d[1]), "+f"(d[2]), "+f"(d[3])
                 : "r"(a0), "r"(a1), "r"(a2), "r"(a3), "r"(b0), "r"(b1));
}

__device__ __forceinline__ uint64_t smem_desc(uint32_t addr, uint32_t lbo, uint32_t sbo) {
    return (uint64_t)((addr & 0x3FFFF) >> 4) | ((uint64_t)(lbo >> 4) << 16) | ((uint64_t)(sbo >> 4) << 32);
}
__device__ __forceinline__ void wg_fence() { asm volatile("wgmma.fence.sync.aligned;" ::: "memory"); }
__device__ __forceinline__ void wg_commit() { asm volatile("wgmma.commit_group.sync.aligned;" ::: "memory"); }
__device__ __forceinline__ void wg_wait0() { asm volatile("wgmma.wait_group.sync.aligned 0;" ::: "memory"); }
__device__ __forceinline__ void fence_async() { asm volatile("fence.proxy.async.shared::cta;" ::: "memory"); }
__device__ __forceinline__ void wgmma_n32(float (&d)[16], const uint32_t (&a)[4], uint64_t bdesc, int scale_d) {
    asm volatile("{\n.reg .pred p;\nsetp.ne.b32 p, %21, 0;\n"
                 "wgmma.mma_async.sync.aligned.m64n32k16.f32.bf16.bf16 {%0,%1,%2,%3,%4,%5,%6,%7,%8,%9,%10,%11,%12,%13,%14,%15}, {%16,%17,%18,%19}, %20, p, 1, 1, 0;\n}"
                 : "+f"(d[0]), "+f"(d[1]), "+f"(d[2]), "+f"(d[3]), "+f"(d[4]), "+f"(d[5]), "+f"(d[6]), "+f"(d[7]),
                   "+f"(d[8]), "+f"(d[9]), "+f"(d[10]), "+f"(d[11]), "+f"(d[12]), "+f"(d[13]), "+f"(d[14]), "+f"(d[15])
                 : "r"(a[0]), "r"(a[1]), "r"(a[2]), "r"(a[3]), "l"(bdesc), "r"(scale_d));
}

__device__ __forceinline__ void wgmma_n32_ss(float (&d)[16], uint64_t adesc, uint64_t bdesc, int scale_d) {
    asm volatile("{\n.reg .pred p;\nsetp.ne.b32 p, %18, 0;\n"
                 "wgmma.mma_async.sync.aligned.m64n32k16.f32.bf16.bf16 {%0,%1,%2,%3,%4,%5,%6,%7,%8,%9,%10,%11,%12,%13,%14,%15}, %16, %17, p, 1, 1, 1, 0;\n}"
                 : "+f"(d[0]), "+f"(d[1]), "+f"(d[2]), "+f"(d[3]), "+f"(d[4]), "+f"(d[5]), "+f"(d[6]), "+f"(d[7]),
                   "+f"(d[8]), "+f"(d[9]), "+f"(d[10]), "+f"(d[11]), "+f"(d[12]), "+f"(d[13]), "+f"(d[14]), "+f"(d[15])
                 : "l"(adesc), "l"(bdesc), "r"(scale_d));
}

__device__ __forceinline__ void wgmma_n64_ss(float (&d)[32], uint64_t adesc, uint64_t bdesc) {
    asm volatile("{\n.reg .pred p;\nsetp.eq.b32 p, 0, 0;\n"
                 "wgmma.mma_async.sync.aligned.m64n64k16.f32.bf16.bf16 {%0,%1,%2,%3,%4,%5,%6,%7,%8,%9,%10,%11,%12,%13,%14,%15,%16,%17,%18,%19,%20,%21,%22,%23,"
                 "%24,%25,%26,%27,%28,%29,%30,%31}, %32, %33, p, 1, 1, 1, 0;\n}"
                 : "+f"(d[0]), "+f"(d[1]), "+f"(d[2]), "+f"(d[3]), "+f"(d[4]), "+f"(d[5]), "+f"(d[6]), "+f"(d[7]),
                   "+f"(d[8]), "+f"(d[9]), "+f"(d[10]), "+f"(d[11]), "+f"(d[12]), "+f"(d[13]), "+f"(d[14]), "+f"(d[15]),
                   "+f"(d[16]), "+f"(d[17]), "+f"(d[18]), "+f"(d[19]), "+f"(d[20]), "+f"(d[21]), "+f"(d[22]), "+f"(d[23]),
                   "+f"(d[24]), "+f"(d[25]), "+f"(d[26]), "+f"(d[27]), "+f"(d[28]), "+f"(d[29]), "+f"(d[30]), "+f"(d[31])
                 : "l"(adesc), "l"(bdesc));
}
__device__ __forceinline__ void tma_2d(uint32_t dst, const CUtensorMap* tm, int c0, int c1, uint32_t mbar) {
    asm volatile("cp.async.bulk.tensor.2d.shared::cluster.global.tile.mbarrier::complete_tx::bytes [%0], [%1, {%2, %3}], [%4];"
                 :: "r"(dst), "l"(tm), "r"(c0), "r"(c1), "r"(mbar) : "memory");
}

__device__ __forceinline__ void bulk_g2s(uint32_t dst, const void* src, uint32_t bytes, uint32_t mbar) {
    asm volatile("cp.async.bulk.shared::cluster.global.mbarrier::complete_tx::bytes [%0], [%1], %2, [%3];"
                 :: "r"(dst), "l"(src), "r"(bytes), "r"(mbar) : "memory");
}
__device__ __forceinline__ void bulk_g2s_h(uint32_t dst, const void* src, uint32_t bytes, uint32_t mbar, uint64_t pol) {
    asm volatile("cp.async.bulk.shared::cluster.global.mbarrier::complete_tx::bytes.L2::cache_hint [%0], [%1], %2, [%3], %4;"
                 :: "r"(dst), "l"(src), "r"(bytes), "r"(mbar), "l"(pol) : "memory");
}
__device__ __forceinline__ void tma_x(uint32_t dst, const CUtensorMap* tm, int seg, int part, uint32_t mbar) {
    asm volatile("cp.async.bulk.tensor.3d.shared::cluster.global.tile.mbarrier::complete_tx::bytes [%0], [%1, {%2, %3, %4}], [%5];"
                 :: "r"(dst + part * 12288), "l"(tm), "r"(0), "r"(seg * SEG), "r"(part * 3), "r"(mbar) : "memory");
}
__device__ __forceinline__ void tma_x_mc(uint32_t dst, const CUtensorMap* tm, int seg, int part, uint32_t mbar) {
    asm volatile("cp.async.bulk.tensor.3d.shared::cluster.global.tile.mbarrier::complete_tx::bytes.multicast::cluster [%0], [%1, {%2, %3, %4}], [%5], %6;"
                 :: "r"(dst + part * 12288), "l"(tm), "r"(0), "r"(seg * SEG), "r"(part * 3), "r"(mbar), "h"((unsigned short)7) : "memory");
}
__device__ __forceinline__ void bulk_s2s(uint32_t dst, uint32_t src, uint32_t bytes, uint32_t mbar) {
    asm volatile("cp.async.bulk.shared::cluster.shared::cta.mbarrier::complete_tx::bytes [%0], [%1], %2, [%3];"
                 :: "r"(dst), "r"(src), "r"(bytes), "r"(mbar) : "memory");
}
__device__ __forceinline__ void wgmma_n40_ss(float (&d)[20], uint64_t adesc, uint64_t bdesc, int scale_d) {
    asm volatile("{\n.reg .pred p;\nsetp.ne.b32 p, %22, 0;\n"
                 "wgmma.mma_async.sync.aligned.m64n40k16.f32.bf16.bf16 {%0,%1,%2,%3,%4,%5,%6,%7,%8,%9,%10,%11,%12,%13,%14,%15,%16,%17,%18,%19}, %20, %21, p, 1, 1, 1, 1;\n}"
                 : "+f"(d[0]), "+f"(d[1]), "+f"(d[2]), "+f"(d[3]), "+f"(d[4]), "+f"(d[5]), "+f"(d[6]), "+f"(d[7]),
                   "+f"(d[8]), "+f"(d[9]), "+f"(d[10]), "+f"(d[11]), "+f"(d[12]), "+f"(d[13]), "+f"(d[14]), "+f"(d[15]),
                   "+f"(d[16]), "+f"(d[17]), "+f"(d[18]), "+f"(d[19])
                 : "l"(adesc), "l"(bdesc), "r"(scale_d));
}
__device__ __forceinline__ void wgmma_n64_z(float (&d)[32], const uint32_t (&a)[4], uint64_t bdesc) {
    asm volatile("{\n.reg .pred p;\nsetp.ne.b32 p, 0, 0;\n"
                 "wgmma.mma_async.sync.aligned.m64n64k16.f32.bf16.bf16 {%0,%1,%2,%3,%4,%5,%6,%7,%8,%9,%10,%11,%12,%13,%14,%15,%16,%17,%18,%19,%20,%21,%22,%23,%24,%25,%26,%27,%28,%29,%30,%31}, {%32,%33,%34,%35}, %36, p, 1, 1, 0;\n}"
                 : "=f"(d[0]), "=f"(d[1]), "=f"(d[2]), "=f"(d[3]), "=f"(d[4]), "=f"(d[5]), "=f"(d[6]), "=f"(d[7]),
                   "=f"(d[8]), "=f"(d[9]), "=f"(d[10]), "=f"(d[11]), "=f"(d[12]), "=f"(d[13]), "=f"(d[14]), "=f"(d[15]),
                   "=f"(d[16]), "=f"(d[17]), "=f"(d[18]), "=f"(d[19]), "=f"(d[20]), "=f"(d[21]), "=f"(d[22]), "=f"(d[23]),
                   "=f"(d[24]), "=f"(d[25]), "=f"(d[26]), "=f"(d[27]), "=f"(d[28]), "=f"(d[29]), "=f"(d[30]), "=f"(d[31])
                 : "r"(a[0]), "r"(a[1]), "r"(a[2]), "r"(a[3]), "l"(bdesc));
}
__device__ __forceinline__ void wgmma_n64(float (&d)[32], const uint32_t (&a)[4], uint64_t bdesc, int scale_d) {
    asm volatile("{\n.reg .pred p;\nsetp.ne.b32 p, %37, 0;\n"
                 "wgmma.mma_async.sync.aligned.m64n64k16.f32.bf16.bf16 {%0,%1,%2,%3,%4,%5,%6,%7,%8,%9,%10,%11,%12,%13,%14,%15,%16,%17,%18,%19,%20,%21,%22,%23,%24,%25,%26,%27,%28,%29,%30,%31}, {%32,%33,%34,%35}, %36, p, 1, 1, 0;\n}"
                 : "+f"(d[0]), "+f"(d[1]), "+f"(d[2]), "+f"(d[3]), "+f"(d[4]), "+f"(d[5]), "+f"(d[6]), "+f"(d[7]),
                   "+f"(d[8]), "+f"(d[9]), "+f"(d[10]), "+f"(d[11]), "+f"(d[12]), "+f"(d[13]), "+f"(d[14]), "+f"(d[15]),
                   "+f"(d[16]), "+f"(d[17]), "+f"(d[18]), "+f"(d[19]), "+f"(d[20]), "+f"(d[21]), "+f"(d[22]), "+f"(d[23]),
                   "+f"(d[24]), "+f"(d[25]), "+f"(d[26]), "+f"(d[27]), "+f"(d[28]), "+f"(d[29]), "+f"(d[30]), "+f"(d[31])
                 : "r"(a[0]), "r"(a[1]), "r"(a[2]), "r"(a[3]), "l"(bdesc), "r"(scale_d));
}

constexpr int SB_FULL = 0, SB_EMPTY = 64, SB_QKF = 128, SB_VF = 144, SB_QKE = 160, SB_VE = 176, SB_OF = 192, SB_WO = 208, SB_TICK = 216, SB_SEEN = 224, SB_FI = 232, SB_REQ = 240;
constexpr int AT_0 = 256, AT_ST = 10240 + 2 * 9216;
constexpr int FS_A = 58368;
constexpr int FS_P = FS_A + 131072;
constexpr int FS_I = FS_P + 16384;
constexpr int FS_O = FS_I + 12288;
constexpr int FS_Z = FS_O + 12288, FS_G = AT_0 + 2 * AT_ST;
constexpr int SIDE_SMEM = FS_Z + 2048;
static_assert(SIDE_SMEM <= 232448 && FS_G + 128 <= FS_A && FS_A + SD_SMEM <= SIDE_SMEM, "smem");

__device__ __forceinline__ void bf16r2(float& a, float& b) {
    uint32_t p = pack_bf16(a, b);
    a = __uint_as_float(p << 16); b = __uint_as_float(p & 0xffff0000u);
}
__device__ __forceinline__ void wg_wait1() { asm volatile("wgmma.wait_group.sync.aligned 1;" ::: "memory"); }
__device__ __forceinline__ void mbar_arrive(uint32_t bar) { asm volatile("mbarrier.arrive.shared::cta.b64 _, [%0];" :: "r"(bar) : "memory"); }
__device__ __forceinline__ void wait_cnt_rlx(const unsigned* p, unsigned target, bool urgent) {
    unsigned it = 0, v;
    while (true) {
        asm volatile("ld.relaxed.gpu.global.u32 %0, [%1];" : "=r"(v) : "l"(p) : "memory");
        if ((int)(v - target) >= 0 || ++it >= SPIN_LIMIT) break;
        if (!urgent) __nanosleep(RLX_SLEEP);
    }
}

__device__ __forceinline__ void xrow_softmax(float (&sc)[20], uint32_t (&pa)[3][4], int wq, int lane) {
    const int g = lane >> 2, tq = lane & 3;
    float mx0 = -INFINITY;
    const int q0 = MEMT + 8 * wq + g;
#pragma unroll
    for (int j = 0; j < 5; j++) {
        bf16r2(sc[4 * j], sc[4 * j + 1]);
        sc[4 * j] *= ATT_SCALE; sc[4 * j + 1] *= ATT_SCALE;
        bf16r2(sc[4 * j], sc[4 * j + 1]);
#pragma unroll
        for (int c = 0; c < 2; c++) {
            int key = 8 * j + 2 * tq + c;
            if (key > q0) sc[4 * j + c] = -INFINITY;
            mx0 = fmaxf(mx0, sc[4 * j + c]);
        }
    }
    mx0 = fmaxf(mx0, __shfl_xor_sync(0xffffffffu, mx0, 1)); mx0 = fmaxf(mx0, __shfl_xor_sync(0xffffffffu, mx0, 2));
    float sum0 = 0.f;
#pragma unroll
    for (int j = 0; j < 5; j++) {
#pragma unroll
        for (int c = 0; c < 2; c++) {
            float e0 = __expf(sc[4 * j + c] - mx0);
            sc[4 * j + c] = e0;
            sum0 += e0;
        }
    }
    sum0 += __shfl_xor_sync(0xffffffffu, sum0, 1); sum0 += __shfl_xor_sync(0xffffffffu, sum0, 2);
    const float i0 = 1.f / sum0;
#pragma unroll
    for (int ks = 0; ks < 3; ks++) {
        pa[ks][0] = pack_bf16(sc[8 * ks] * i0, sc[8 * ks + 1] * i0);
        pa[ks][1] = 0u;
        pa[ks][2] = ks < 2 ? pack_bf16(sc[8 * ks + 4] * i0, sc[8 * ks + 5] * i0) : 0u;
        pa[ks][3] = 0u;
    }
}

__device__ __forceinline__ void stsm_x4(uint32_t addr, uint32_t r0, uint32_t r1, uint32_t r2, uint32_t r3) {
    asm volatile("stmatrix.sync.aligned.m8n8.x4.shared.b16 [%0], {%1,%2,%3,%4};" :: "r"(addr), "r"(r0), "r"(r1), "r"(r2), "r"(r3) : "memory");
}
__device__ __forceinline__ uint32_t h2_to_bf2(uint32_t h) {
    uint32_t r;
    asm("{\n.reg .f16 l, h;\n.reg .f32 a, b;\nmov.b32 {l, h}, %1;\ncvt.f32.f16 a, l;\ncvt.f32.f16 b, h;\ncvt.rn.bf16x2.f32 %0, b, a;\n}" : "=r"(r) : "r"(h));
    return r;
}
__device__ __forceinline__ uint32_t max_abs2(uint32_t a, uint32_t b) { uint32_t r; asm("max.NaN.xorsign.abs.bf16x2 %0, %1, %2;" : "=r"(r) : "r"(a), "r"(b)); return r; }
__device__ __forceinline__ uint32_t movm(uint32_t v) {
    uint32_t r; asm volatile("movmatrix.sync.aligned.m8n8.trans.b16 %0, %1;" : "=r"(r) : "r"(v)); return r;
}
__device__ __forceinline__ void bar_arrive(int id, int n) { asm volatile("bar.arrive %0, %1;" :: "r"(id), "r"(n) : "memory"); }
__device__ __forceinline__ void lds64(uint32_t& a, uint32_t& b, uint32_t addr) {
    asm volatile("ld.shared.v2.u32 {%0,%1}, [%2];" : "=r"(a), "=r"(b) : "r"(addr) : "memory");
}
__device__ __forceinline__ void lds64f(float& a, float& b, uint32_t addr) {
    asm volatile("ld.shared.v2.f32 {%0,%1}, [%2];" : "=f"(a), "=f"(b) : "r"(addr) : "memory");
}
__device__ __forceinline__ void st_async64(uint32_t addr, uint32_t a, uint32_t b, uint32_t mbar) {
    asm volatile("st.async.weak.shared::cluster.mbarrier::complete_tx::bytes.v2.b32 [%0], {%1,%2}, [%3];" :: "r"(addr), "r"(a), "r"(b), "r"(mbar) : "memory");
}
__device__ __forceinline__ void mma_z(float (&d)[4], const uint32_t (&a)[4], uint32_t b0, uint32_t b1) {
    asm volatile("mma.sync.aligned.m16n8k16.row.col.f32.bf16.bf16.f32 {%0,%1,%2,%3}, {%4,%5,%6,%7}, {%8,%9}, {%10,%10,%10,%10};"
                 : "=f"(d[0]), "=f"(d[1]), "=f"(d[2]), "=f"(d[3])
                 : "r"(a[0]), "r"(a[1]), "r"(a[2]), "r"(a[3]), "r"(b0), "r"(b1), "f"(0.f));
}
__device__ __forceinline__ void mma_k8(float (&d)[4], uint32_t a0, uint32_t a1, uint32_t b) {
    asm volatile("mma.sync.aligned.m16n8k8.row.col.f32.bf16.bf16.f32 {%0,%1,%2,%3}, {%4,%5}, {%6}, {%0,%1,%2,%3};"
                 : "+f"(d[0]), "+f"(d[1]), "+f"(d[2]), "+f"(d[3]) : "r"(a0), "r"(a1), "r"(b));
}
__global__ void __launch_bounds__(512, 1) k_side(const __grid_constant__ CUtensorMap tmo, const bf16* __restrict__ x, const bf16* __restrict__ logA, const bf16* __restrict__ Aim,
                                                 const bf16* __restrict__ Cre, const bf16* __restrict__ Cim, const bf16* __restrict__ logdt,
                                                 const bf16* __restrict__ Wo, const bf16* __restrict__ dskip, const bf16* __restrict__ gw,
                                                 bf16* __restrict__ out) {
    extern __shared__ __align__(1024) unsigned char smem_raw[];
    const uint32_t sbase = smem_u32(smem_raw);
    const int tid = threadIdx.x, warp = __shfl_sync(0xffffffffu, tid >> 5, 0), lane = tid & 31, cta = blockIdx.x;
    const int cb = cta >> 2, kq = cta & 3;
    if (tid == 0) {
        for (int i = 0; i < 8; i++) { mbar_init(sbase + SB_FULL + 8 * i, 1); mbar_init(sbase + SB_EMPTY + 8 * i, 4); }
        for (int i = 0; i < 2; i++) {
            mbar_init(sbase + SB_QKF + 8 * i, 1); mbar_init(sbase + SB_VF + 8 * i, 1); mbar_init(sbase + SB_QKE + 8 * i, 4);
            mbar_init(sbase + SB_VE + 8 * i, 1); mbar_init(sbase + SB_OF + 8 * i, 4);
        }
        mbar_init(sbase + SB_WO, 1);
        mbar_init(sbase + SB_FI, 1);
        mbar_init(sbase + SB_REQ, 4);
        *reinterpret_cast<uint2*>(smem_raw + SB_TICK) = make_uint2(0u, 0u);
        *reinterpret_cast<uint32_t*>(smem_raw + SB_SEEN) = 0u;
        asm volatile("fence.mbarrier_init.release.cluster;" ::: "memory");
    }
    TS3(0);
    unsigned ep;
    asm volatile("ld.volatile.global.u32 %0, [%1];" : "=r"(ep) : "l"(&g_epoch) : "memory");
    ep += 1u;
    asm volatile("fence.proxy.async;" ::: "memory");
    __syncthreads();
    if (warp >= 12) {
      asm volatile("setmaxnreg.dec.sync.aligned.u32 40;");
      {
        uint32_t gwv[9];
#pragma unroll
        for (int i = 0; i < 9; i++) gwv[i] = reinterpret_cast<const uint32_t*>(gw)[lane + 32 * i];
#pragma unroll 1
        for (int i = 0; i < 8; i++) {
            uint32_t xv[2][9];
            float sm[2];
#pragma unroll
            for (int j = 0; j < 2; j++) {
                const int t = min(cta * 57 + 8 * i + 4 * j + warp - 12, S_LEN - 1);
#pragma unroll
                for (int k = 0; k < 9; k++) xv[j][k] = reinterpret_cast<const uint32_t*>(x + t * DM)[lane + 32 * k];
            }
#pragma unroll
            for (int j = 0; j < 2; j++) {
                sm[j] = 0.f;
#pragma unroll
                for (int k = 0; k < 9; k++) {
                    const uint32_t pr = bf2_mul(xv[j][k], gwv[k]);
                    sm[j] += __uint_as_float(pr << 16) + __uint_as_float(pr & 0xffff0000u);
                }
            }
            float v = (lane < 16 ? sm[0] : sm[1]) + __shfl_xor_sync(0xffffffffu, lane < 16 ? sm[1] : sm[0], 16);
#pragma unroll
            for (int o = 8; o; o >>= 1) v += __shfl_xor_sync(0xffffffffu, v, o);
            const float gv = 1.f / (1.f + expf(-bf16r(v)));
            const int tt = 8 * i + 4 * (lane >> 4) + warp - 12;
            if ((lane & 15) == 0 && tt < 57 && cta * 57 + tt < S_LEN) g_gate[cta * 57 + tt] = __float2bfloat16_rn(gv);
        }
        named_bar(2, 128);
        if (tid == 480) {
            __threadfence();
            asm volatile("red.relaxed.gpu.global.add.u32 [%0], 1;" :: "l"(&g_gcnt[0]) : "memory");
        }
        __syncwarp();
      }
      if (warp == 12 || warp == 15) {
        named_bar(3, 320);
        if (tid == 384) {
            fence_async();
            mbar_expect(sbase + SB_WO, 131072);
#pragma unroll 1
            for (int i = 0; i < 8; i++) {
                gate(sbase + SB_TICK);
                tma_2d(sbase + FS_A + i * 16384, &tmo, cb * 64, kq * 1024 + i * 128, sbase + SB_WO);
                __nanosleep(150);
            }
            TSS(17, 2);
        }
        if (tid == 480) {
            __threadfence();
            asm volatile("red.relaxed.gpu.global.add.u32 [%0], 1;" :: "l"(&g_gcnt[32]) : "memory");
            TSS(17, 3);
        }
        __syncwarp();
        named_bar(7, 320);
        if (lane == 0) {
            const int pi = warp == 12 ? 0 : 1, kb = 2 * kq + pi;
            fence_async();
            for (int pr = 0; pr < NSEG / 2; pr++) {
                const bool gon = pr < NSEG / 2 - UNGATE_G;
                wait_cnt_rlx(&g_prog[pr * 8 + kb], 8u * ep, pr >= NSEG / 2 - 2);
                if (pi == 0) asm volatile("st.volatile.shared.u32 [%0], %1;" :: "r"(sbase + SB_SEEN), "r"(pr + 1) : "memory");
                if (pr >= 30 && pi == 0) TSS(4 + pr - 30, 0);
                if (pr == 31) TS3P(26);
                if (pr == 30) TS3P(1);
#pragma unroll
                for (int j = 0; j < 4; j++) {
                    const int st = 4 * pi + j;
                    mbar_wait_long(sbase + SB_EMPTY + 8 * st, ((uint32_t)pr & 1u) ^ 1u);
                    mbar_expect(sbase + SB_FULL + 8 * st, X_OXSZ);
                    if (gon) gate(sbase + SB_TICK);
                    bulk_g2s(sbase + FS_A + st * 16384, g_ox + ((size_t)(pr * NH + 4 * kb + j)) * 8192, X_OXSZ, sbase + SB_FULL + 8 * st);
                }
            }
        }
        __syncwarp();
      } else if (warp == 13) {
        if (lane == 0) {
            const uint64_t pol = policy_evict_first();
            bool next_ok = false;
            for (int seg = 0; seg < NATT; seg++) {
                const uint32_t st = seg & 1, ph = (uint32_t)(seg >> 1) & 1u, ab = sbase + AT_0 + st * AT_ST;
                if (!next_ok) {
                    const unsigned* fp = &g_flag[(cta & (NH - 1)) * NSEG + seg];
                    unsigned it = 0, v0, v1;
                    while (true) {
                        asm volatile("ld.relaxed.gpu.global.u32 %0, [%1];" : "=r"(v0) : "l"(fp) : "memory");
                        asm volatile("ld.relaxed.gpu.global.u32 %0, [%1+4];" : "=r"(v1) : "l"(fp) : "memory");
                        read_tick(sbase + SB_TICK);
                        if ((int)(v0 - 3u * ep) >= 0 || ++it >= SPIN_LIMIT) break;
                        if (seg < NSEG - UNGATE || cta >= NH) __nanosleep(RLX_SLEEP);
                    }
                    next_ok = (int)(v1 - 3u * ep) >= 0;
                } else next_ok = false;
                if (cta < NH) {
                    TSA(seg, 0);
                    mbar_wait_long(sbase + SB_QKE + 8 * st, ph ^ 1u);
                    TSA(seg, 1);
                    mbar_expect(sbase + SB_QKF + 8 * st, 2 * 9216);
                    if (seg < NSEG - UNGATE) gate(sbase + SB_TICK);
                    TSA(seg, 2);
                    bulk_g2s_h(ab + 10240, &g_qkv[seg][cta][0][1024], 9216, sbase + SB_QKF + 8 * st, pol);
                    bulk_g2s_h(ab + 10240 + 9216, &g_qkv[seg][cta][1][1024], 9216, sbase + SB_QKF + 8 * st, pol);
                    mbar_wait_long(sbase + SB_VE + 8 * st, ph ^ 1u);
                    mbar_expect(sbase + SB_VF + 8 * st, 10240);
                    if (seg < NSEG - UNGATE) gate(sbase + SB_TICK);
                    TSA(seg, 3);
                    bulk_g2s_h(ab, &g_qkv[seg][cta][2][0], 10240, sbase + SB_VF + 8 * st, pol);
                }
            }
        }
        __syncwarp();
      } else if (warp == 14) {
        if (lane == 0) {
            int seg = cta < NH ? 0 : NATT, p = 0;
            unsigned it = 0;
            while ((seg < NATT || p < NSEG / 2 - 1) && ++it < 16 * SPIN_LIMIT) {
                if (p < NSEG / 2 - 1 && mbar_test(sbase + SB_REQ, (uint32_t)p & 1u)) {
                    if (p == 0) { wait_cnt(&g_gcnt[32], SD_NCTA * ep); asm volatile("fence.proxy.async;" ::: "memory"); }
                    mbar_expect(sbase + SB_FI, (p < NSEG / 2 - 2 ? 12288 : 2048 + 32) + 2048 + 32);
                    if (GATE_F && p < NSEG / 2 - UNGATE_G - 1) gate(sbase + SB_TICK);
                    if (p < NSEG / 2 - 2) bulk_g2s(sbase + FS_I, &g_fp[p & 7][cta][0][0], 12288, sbase + SB_FI);
                    else {
                        bulk_g2s(sbase + FS_I, g_y + ((p * 4 + 4 + kq) * DM + cb * 64) * 16, 2048, sbase + SB_FI);
                        bulk_g2s(sbase + FS_G + 32, g_gate + p * 64 + 64 + kq * 16, 32, sbase + SB_FI);
                    }
                    bulk_g2s(sbase + FS_Z, g_y + ((p * 4 + kq) * DM + cb * 64) * 16, 2048, sbase + SB_FI);
                    bulk_g2s(sbase + FS_G, g_gate + p * 64 + kq * 16, 32, sbase + SB_FI);
                    p++;
                } else if (seg < NATT && mbar_test(sbase + SB_OF + 8 * (seg & 1), (uint32_t)(seg >> 1) & 1u)) {
                    const uint32_t st = seg & 1, ab = sbase + AT_0 + st * AT_ST;
                    TSA(seg, 5);
                    if (seg < NSEG - UNGATE) gate(sbase + SB_TICK);
                    TSA(seg, 6);
                    unsigned char* dst = reinterpret_cast<unsigned char*>(g_ox) + ((size_t)((seg >> 1) * NH + cta)) * 16384 + (seg & 1) * 4096;
                    asm volatile("cp.async.bulk.global.shared::cta.bulk_group [%0], [%1], 4096;" :: "l"(dst), "r"(ab) : "memory");
                    asm volatile("cp.async.bulk.global.shared::cta.bulk_group [%0], [%1], 4096;" :: "l"(dst + 8192), "r"(ab + 4096) : "memory");
                    asm volatile("cp.async.bulk.commit_group;" ::: "memory");
                    asm volatile("cp.async.bulk.wait_group.read 0;" ::: "memory");
                    mbar_arrive(sbase + SB_VE + 8 * st);
                    asm volatile("cp.async.bulk.wait_group 0;" ::: "memory");
                    asm volatile("red.relaxed.gpu.global.add.u32 [%0], 1;" :: "l"(&g_prog[(seg >> 1) * 8 + (cta >> 2)]) : "memory");
                    TSA(seg, 7);
                    seg++;
                } else if (seg < NSEG - UNGATE) __nanosleep(W14_SLEEP);
            }
        }
        __syncwarp();
      }
    } else if (warp >= 8) {
        asm volatile("setmaxnreg.dec.sync.aligned.u32 88;");
        s4d_stage_u(smem_raw + FS_A, x, tid - 256);
        const int wq = warp - 8;
        for (int seg = 0; seg < (cta < NH ? NATT : 0); seg++) {
            const uint32_t st = seg & 1, ph = (uint32_t)(seg >> 1) & 1u, ab = sbase + AT_0 + st * AT_ST;
            float sc[20];
            mbar_wait_long(sbase + SB_QKF + 8 * st, ph);
            if (tid == 256) TSA(seg, 4);
            {
                const uint64_t da = smem_desc(ab + 10240 + 1024, 128, 1024), db = smem_desc(ab + 10240, 128, 2048);
                wg_fence();
#pragma unroll
                for (int ks = 0; ks < 8; ks++) wgmma_n40_ss(sc, da + (uint64_t)((ks >> 2) * 576 + (ks & 3) * 16), db + (uint64_t)((ks >> 2) * 576 + (ks & 3) * 16), ks > 0);
                wg_commit();
                wg_wait0();
            }
            if (lane == 0) mbar_arrive(sbase + SB_QKE + 8 * st);
            uint32_t pa[3][4], ob[16];
            xrow_softmax(sc, pa, wq, lane);
#pragma unroll
            for (int i = 0; i < 8; i++) ob[8 + i] = 0u;
            mbar_wait_long(sbase + SB_VF + 8 * st, ph);
#pragma unroll 1
            for (int hf = 0; hf < 2; hf++) {
                float o[32];
                const uint64_t dv = smem_desc(ab + hf * 1024, 2048, 128);
                wg_fence();
#pragma unroll
                for (int ks = 0; ks < 3; ks++) { if (ks == 0) wgmma_n64_z(o, pa[0], dv); else wgmma_n64(o, pa[ks], dv + (uint64_t)(ks * 256), 1); }
                wg_commit();
                wg_wait0();
#pragma unroll
                for (int i = 0; i < 8; i++) { ob[i] = ob[8 + i]; ob[8 + i] = pack_bf16(o[4 * i], o[4 * i + 1]); }
            }
            named_bar(6, 128);
#pragma unroll
            for (int i = 0; i < 4; i++) stsm_x4(ab + (i >> 1) * 4096 + wq * 1024 + (i & 1) * 512 + lane * 16, ob[4 * i], ob[4 * i + 1], ob[4 * i + 2], ob[4 * i + 3]);
            fence_async();
            __syncwarp();
            if (lane == 0) mbar_arrive(sbase + SB_OF + 8 * st);
        }
    } else {
        asm volatile("setmaxnreg.inc.sync.aligned.u32 192;");
        const int wg = warp >> 2, wq = warp & 3;
        s4d_phase(smem_raw + FS_A, x, logA, Aim, Cre, Cim, logdt, dskip, Wo + (size_t)((2 * kq + wg) * 512) * DM + cb * 64, ep, sbase + SB_TICK);
        TS3(2);
        if (lane == 0) TSS(16, warp);
        named_bar(3, 320);
        if (tid == 0) TSS(17, 0);
        uint32_t wa[32][4];
        mbar_wait_long(sbase + SB_WO, 0);
        if (tid == 0) TSS(17, 1);
        {
            const uint32_t a = sbase + FS_A + wg * 65536 + ((lane >> 4) * 8 + (lane & 7)) * 128 + (((wq * 2 + ((lane >> 3) & 1)) ^ (lane & 7)) << 4);
#pragma unroll
            for (int ks = 0; ks < 32; ks++) ldsm_x4_t(wa[ks], a + ks * 2048);
        }
        named_bar(7, 320);
        TS3(3);
        if (tid == 0) TSS(17, 4);
        auto product = [&](float (&acc)[32], int pr, const int wg) {
                if (pr + wg > 0 && pr + wg < NSEG / 2) named_bar(4 + wg, 256);
                const uint64_t db = smem_desc(sbase + FS_A + wg * 65536, 128, 1024);
                TSG(0);
#pragma unroll
                for (int j = 0; j < 4; j++) {
                    mbar_wait(sbase + SB_FULL + 8 * (4 * wg + j), (uint32_t)pr & 1u);
                    if (j == 0) TSG(1);
                    if (j == 3) TSG(2);
                    wg_fence();
#pragma unroll
                    for (int ks = 0; ks < 8; ks++) {
                        if ((j | ks) == 0) wgmma_n64_z(acc, wa[0], db);
                        else wgmma_n64(acc, wa[8 * j + ks], db + (uint64_t)(j * 1024 + (ks >> 2) * 512 + (ks & 3) * 16), 1);
                    }
                    wg_commit();
                    if (j == 3 && pr + 1 < NSEG / 2) bar_arrive(4 + (wg ^ 1), 256);
                    if (j > 0) { wg_wait1(); if (lane == 0) mbar_arrive(sbase + SB_EMPTY + 8 * (4 * wg + j - 1)); }
                }
                wg_wait0();
                if (pr == 31) TS3W(27);
                TSG(3);
                if (lane == 0) mbar_arrive(sbase + SB_EMPTY + 8 * (4 * wg + 3));
        };
        if (wg == 1) {
            for (int pr = 0; pr < NSEG / 2; pr++) {
                uint32_t t16 = (uint32_t)(wq * 32 + lane) * 16u;
                asm volatile("" : "+r"(t16));
                float acc[32];
                product(acc, pr, 1);
                    uint32_t tag = ((uint32_t)(pr >> 3) & 1u) ^ 1u;
                    tag = __shfl_sync(0xffffffffu, tag, lane);
                    if (GATE_S && pr < NSEG / 2 - UNGATE_G) gate(sbase + SB_TICK);
                    named_bar(8, 256);
                    unsigned char* dst = reinterpret_cast<unsigned char*>(&g_fp[pr & 7][4 * cb][2 * kq - 2][0]) + t16;
                    const uint32_t own = sbase + FS_O + (pr % 3) * 4096 + t16;
#pragma unroll
                    for (int q = 0; q < 8; q++) {
                        float4 p;
                        asm volatile("ld.shared.v4.f32 {%0,%1,%2,%3}, [%4];" : "=f"(p.x), "=f"(p.y), "=f"(p.z), "=f"(p.w) : "r"(sbase + FS_P + t16 + q * 2048) : "memory");
                        acc[4 * q] = __uint_as_float((__float_as_uint(acc[4 * q] + p.x) & ~1u) | tag); acc[4 * q + 1] = __uint_as_float((__float_as_uint(acc[4 * q + 1] + p.y) & ~1u) | tag);
                        acc[4 * q + 2] = __uint_as_float((__float_as_uint(acc[4 * q + 2] + p.z) & ~1u) | tag); acc[4 * q + 3] = __uint_as_float((__float_as_uint(acc[4 * q + 3] + p.w) & ~1u) | tag);
                    }
#pragma unroll
                    for (int q = 0; q < 8; q++) {
                        asm volatile("{\n.reg .pred p;\nsetp.ne.s32 p, %5, %6;\n@p st.volatile.global.v4.f32 [%0], {%1,%2,%3,%4};\n@!p st.shared.v4.f32 [%7], {%1,%2,%3,%4};\n}"
                                     :: "l"(dst + (q & 1) * 2048), "f"(acc[4 * q]), "f"(acc[4 * q + 1]), "f"(acc[4 * q + 2]), "f"(acc[4 * q + 3]), "r"(q >> 1), "r"(kq),
                                        "r"(own + (q & 1) * 2048) : "memory");
                        if (q & 1) dst += (q >> 1) == kq ? 12288 + 4096 : 12288;
                    }
                    bar_arrive(9, 256);
                    if (pr == 31) TS3W(28);
                TSG(4);
            }
        } else {
          int nsync = 0;
          int np = 1, nf = 0, pr = 0, pf = -1;
          while (true) {
            uint32_t t16 = (uint32_t)(wq * 32 + lane) * 16u;
            asm volatile("" : "+r"(t16));
            if (pr < 0) {
                if (nsync <= pf) { named_bar(9, 256); nsync++; }
                if (lane == 0 && pf < NSEG / 2 - 1) mbar_arrive(sbase + SB_REQ);
            } else {
                float acc[32];
                product(acc, pr, 0);
                if (nsync < pr) { named_bar(9, 256); nsync++; }
#pragma unroll
                for (int q = 0; q < 8; q++)
                    asm volatile("st.shared.v4.f32 [%0], {%1,%2,%3,%4};" :: "r"(sbase + FS_P + t16 + q * 2048), "f"(acc[4 * q]), "f"(acc[4 * q + 1]), "f"(acc[4 * q + 2]), "f"(acc[4 * q + 3]) : "memory");
                bar_arrive(8, 256);
                TSG(4);
            }
            uint32_t w[4] = {0u, 0u, 0u, 0u};
            const int pc = pf;
            if (pf >= 0) {
                const uint32_t tag = ((uint32_t)(pf >> 3) & 1u) ^ 1u;
                uint4 v[8];
                unsigned n = 0;
                const bool last = pf == NSEG / 2 - 1;
                const uint4* src = reinterpret_cast<const uint4*>(reinterpret_cast<const unsigned char*>(&g_fp[pf & 7][cta][0][0]) + t16);
                if (pf >= NSEG / 2 - 2) {
#pragma unroll
                    for (int r = 0; r < 6; r++) v[r] = ld_vol_u4(src + r * 128);
                    mbar_wait(sbase + SB_FI, 0u);
                } else {
                    mbar_wait(sbase + SB_FI, (uint32_t)pf & 1u);
#pragma unroll
                    for (int r = 0; r < 6; r++)
                        asm volatile("ld.shared.v4.u32 {%0,%1,%2,%3}, [%4];" : "=r"(v[r].x), "=r"(v[r].y), "=r"(v[r].z), "=r"(v[r].w) : "r"(sbase + t16 + FS_I + r * 2048) : "memory");
                }
                while (true) {
                    uint32_t any = 0u;
#pragma unroll
                    for (int r = 0; r < 6; r++) {
                        uint32_t c0_, c1_;
                        asm("lop3.b32 %0, %1, %2, %3, 0x7e;" : "=r"(c0_) : "r"(v[r].x), "r"(v[r].y), "r"(tag));
                        asm("lop3.b32 %0, %1, %2, %3, 0x7e;" : "=r"(c1_) : "r"(v[r].z), "r"(v[r].w), "r"(tag));
                        asm("lop3.b32 %0, %1, %2, %3, 0xfe;" : "=r"(any) : "r"(any), "r"(c0_), "r"(c1_));
                    }
                    if (!__any_sync(0xffffffffu, (any & 1u) != 0u) || ++n >= SPIN_LIMIT) break;
                    if (pf < NSEG / 2 - 2) __nanosleep(200);
#pragma unroll
                    for (int r = 0; r < 6; r++) v[r] = ld_vol_u4(src + r * 128);
                }
                if (pf == 31) TS3(29);
                TSG(5);
#pragma unroll
                for (int r = 6; r < 8; r++)
                    asm volatile("ld.shared.v4.u32 {%0,%1,%2,%3}, [%4];" : "=r"(v[r].x), "=r"(v[r].y), "=r"(v[r].z), "=r"(v[r].w)
                                 : "r"(sbase + t16 + FS_O + (pf % 3) * 4096 + (r - 6) * 2048) : "memory");
                uint32_t zv[4], gg[2];
                ldsm_x4_t(zv, sbase + (last ? FS_I : FS_Z) + (wq * 16 + (lane & 15)) * 32 + (lane >> 4) * 16);
#pragma unroll
                for (int k = 0; k < 2; k++) gg[k] = __byte_perm(*reinterpret_cast<const volatile unsigned short*>(smem_raw + FS_G + (last ? 32 : 0) + k * 16 + (lane >> 2) * 2), 0u, 0x1010);
#define PQS(k, f) (((__uint_as_float(v[k].f) + __uint_as_float(v[2 + k].f)) + __uint_as_float(v[4 + k].f)) + __uint_as_float(v[6 + k].f))
#pragma unroll
                for (int k = 0; k < 2; k++) {
                    w[2 * k] = bf2_add(bf2_mul(gg[k], movm(pack_bf16(PQS(k, x), PQS(k, y)))), zv[2 * k]);
                    w[2 * k + 1] = bf2_add(bf2_mul(gg[k], movm(pack_bf16(PQS(k, z), PQS(k, w)))), zv[2 * k + 1]);
                }
#undef PQS
            }
            const bool more = nf < NSEG / 2;
            if (more) {
                uint32_t r;
                asm volatile("{\n.reg .pred p, q;\n.reg .b32 v;\nld.volatile.shared.u32 v, [%1];\nsetp.gt.s32 p, v, %2;\nbar.red.or.pred q, 10, 128, p;\nselp.u32 %0, 1, 0, q;\n}"
                             : "=r"(r) : "r"(sbase + SB_SEEN), "r"(np) : "memory");
                const bool dop = np < NSEG / 2 && (__shfl_sync(0xffffffffu, r, 0) != 0u || nf == np || nf >= NSEG / 2 - 2);
                TSG(6);
                pr = dop ? np++ : -1;
                pf = !dop || nf + (pr == NSEG / 2 - 1 ? 1 : 2) <= pr ? nf++ : -1;
                if (dop && pf >= 0 && lane == 0) mbar_arrive(sbase + SB_REQ);
            }
            if (pc >= 0) {
                unsigned char* op = reinterpret_cast<unsigned char*>(out) + (uint32_t)((pc * 64 + kq * 16 + (lane >> 2)) * DM + cb * 64 + wq * 16 + 2 * (lane & 3)) * 2u;
#pragma unroll
                for (int k = 0; k < 4; k++) *reinterpret_cast<uint32_t*>(op + (k >> 1) * (16 * DM) + (k & 1) * 16) = w[k];
                if ((pc & 1) == 0) TS3(4 + pc / 2);
                if (pc == 31) TS3(25);
            }
            if (!more) break;
          }
        }
        if (cta == 0 && tid == 0) asm volatile("red.relaxed.gpu.global.add.u32 [%0], 1;" :: "l"(&g_epoch) : "memory");
    }
    asm volatile("griddepcontrol.wait;" ::: "memory");
}

__device__ __forceinline__ uint32_t poll_mem(const uint4* src, uint32_t dst, uint32_t t0) {
    uint4 v[6];
    unsigned it = 0;
#pragma unroll
    for (int j = 0; j < 6; j++) v[j] = make_uint4(0u, 0u, 0u, 0u);
    while (clock32() - t0 < POLL_DELAY) {}
    FS(12, 0);
    bool more;
#pragma unroll 1
    do {
        asm volatile("{\n.reg .pred p<6>;\n"
                     "setp.ne.u32 p0, %3, 0x5000;\nsetp.ne.u32 p1, %7, 0x5000;\nsetp.ne.u32 p2, %11, 0x5000;\n"
                     "setp.ne.u32 p3, %15, 0x5000;\nsetp.ne.u32 p4, %19, 0x5000;\nsetp.ne.u32 p5, %23, 0x5000;\n"
                     "@p0 ld.volatile.global.v4.u32 {%0,%1,%2,%3}, [%24];\n@p1 ld.volatile.global.v4.u32 {%4,%5,%6,%7}, [%24+4096];\n"
                     "@p2 ld.volatile.global.v4.u32 {%8,%9,%10,%11}, [%24+8192];\n@p3 ld.volatile.global.v4.u32 {%12,%13,%14,%15}, [%24+12288];\n"
                     "@p4 ld.volatile.global.v4.u32 {%16,%17,%18,%19}, [%24+16384];\n@p5 ld.volatile.global.v4.u32 {%20,%21,%22,%23}, [%24+20480];\n}"
                     : "+r"(v[0].x), "+r"(v[0].y), "+r"(v[0].z), "+r"(v[0].w), "+r"(v[1].x), "+r"(v[1].y), "+r"(v[1].z), "+r"(v[1].w),
                       "+r"(v[2].x), "+r"(v[2].y), "+r"(v[2].z), "+r"(v[2].w), "+r"(v[3].x), "+r"(v[3].y), "+r"(v[3].z), "+r"(v[3].w),
                       "+r"(v[4].x), "+r"(v[4].y), "+r"(v[4].z), "+r"(v[4].w), "+r"(v[5].x), "+r"(v[5].y), "+r"(v[5].z), "+r"(v[5].w)
                     : "l"(src) : "memory");
        stsm_x4(dst, h2_to_bf2(v[0].x), h2_to_bf2(v[0].y), h2_to_bf2(v[0].z), h2_to_bf2(v[1].x));
        stsm_x4(dst + 512, h2_to_bf2(v[1].y), h2_to_bf2(v[1].z), h2_to_bf2(v[2].x), h2_to_bf2(v[2].y));
        stsm_x4(dst + 1024, h2_to_bf2(v[2].z), h2_to_bf2(v[3].x), h2_to_bf2(v[3].y), h2_to_bf2(v[3].z));
        asm volatile("stmatrix.sync.aligned.m8n8.x2.shared.b16 [%0], {%1,%2};" :: "r"(dst + 1536), "r"(h2_to_bf2(v[4].x)), "r"(h2_to_bf2(v[4].y)) : "memory");
        stsm_x4(dst + 1792, h2_to_bf2(v[4].z), h2_to_bf2(v[5].x), h2_to_bf2(v[5].y), h2_to_bf2(v[5].z));
        const uint32_t all = ((v[0].w & v[1].w) & (v[2].w & v[3].w)) & (v[4].w & v[5].w);
        more = __any_sync(0xffffffffu, (all & 0x5000u) != 0x5000u) && ++it < SPIN_LIMIT;
    } while (more);
    FS(13, it);
    bar_arrive(1, 384);
    FS(14, 0);
    uint32_t m = 0u;
#pragma unroll
    for (int j = 0; j < 6; j++) {
        asm volatile("max.NaN.xorsign.abs.f16x2 %0, %0, %1;" : "+r"(m) : "r"(v[j].x));
        asm volatile("max.NaN.xorsign.abs.f16x2 %0, %0, %1;" : "+r"(m) : "r"(v[j].y));
        asm volatile("max.NaN.xorsign.abs.f16x2 %0, %0, %1;" : "+r"(m) : "r"(v[j].z));
    }
    return h2_to_bf2(m) & 0x7fff7fffu;
}

template <bool V> struct Flag { static constexpr bool value = V; };
struct RFlag { bool value; };
__device__ __forceinline__ void score_group(const uint32_t (&a)[2][4], const uint32_t (&kf)[2][4], uint32_t d0, uint32_t d1, uint32_t m1, uint32_t d2, uint32_t m2) {
    FS(4, a[1][0]);
    float sc[4][4];
    mma_z(sc[0], a[0], kf[0][0], kf[0][1]);
    mma_z(sc[1], a[0], kf[0][2], kf[0][3]);
    mma_z(sc[2], a[1], kf[1][0], kf[1][1]);
    mma_z(sc[3], a[1], kf[1][2], kf[1][3]);
    const uint32_t v0 = __float_as_uint((sc[0][0] + sc[1][2]) + (sc[2][0] + sc[3][2])), v1 = __float_as_uint((sc[0][1] + sc[1][3]) + (sc[2][1] + sc[3][3]));
    FS(5, v0);
    st_async64(d2, v0, v1, m2);
    st_async64(d1, v0, v1, m1);
    asm volatile("st.shared.v2.u32 [%0], {%1,%2};" :: "r"(d0), "r"(v0), "r"(v1) : "memory");
}
__device__ __forceinline__ void store_tile(int s, int h, int role, uint32_t tile) {
    const uint32_t qoff = role != 2 ? 1024 : 0;
    asm volatile("cp.async.bulk.global.shared::cta.bulk_group.L2::cache_hint [%0], [%1], %2, %3;"
                 :: "l"(&g_qkv[s][h][role][qoff]), "r"(tile + qoff), "r"(10240u - qoff), "l"(policy_evict_first()) : "memory");
    asm volatile("cp.async.bulk.commit_group;" ::: "memory");
}
__device__ __forceinline__ uint32_t w_addr(uint32_t sbase, int warp, int lane) {
    return sbase + SM_WS + (warp >> 2) * 8192 + ((lane & 7) + ((lane >> 4) & 1) * 8) * 128 + ((((warp & 3) * 2 + ((lane >> 3) & 1)) ^ (lane & 7)) << 4);
}
__device__ __forceinline__ void vx_copy(uint32_t sbase, int j, int r) {
    bulk_s2s(mapa(sbase + SM_VX + (j & 1) * 8192, r), sbase + SM_T + (j & 3) * TBUF + DH * 16, 8192, mapa(sbase + B_VX + 8 * (j & 1), r));
}
__device__ __forceinline__ void norms_gather(int lane, float* scs) {
    uint2 v[3];
    uint32_t r[2];
    unsigned it = 0;
    do {
#pragma unroll
        for (int i = 0; i < 3; i++) v[i] = ld_vol_u2(&g_norm[3 * lane + i]);
#pragma unroll
        for (int i = 0; i < 2; i++) asm volatile("ld.volatile.global.u32 %0, [%1];" : "=r"(r[i]) : "l"(&g_rx[lane + 32 * i]) : "memory");
    } while (__any_sync(0xffffffffu, (v[0].x & v[1].x & v[2].x & v[2].y & r[0] & r[1] & 1u) == 0u) && ++it < SPIN_LIMIT);
    float c;
    asm("sqrt.approx.f32 %0, %1;" : "=f"(c) : "f"(__uint_as_float(max(max(v[0].x, v[1].x), v[2].x))));
    c *= __uint_as_float(v[2].y) * 272.f;
#pragma unroll
    for (int o = 16; o; o >>= 1) c += __shfl_xor_sync(0xffffffffu, c, o);
    scs[16 + lane] = __uint_as_float(r[0]); scs[48 + lane] = __uint_as_float(r[1]);
    if (lane == 0) scs[1] = c * (1.1f * 24.f);
}

__global__ void __cluster_dims__(3, 1, 1) __launch_bounds__(384, 1)
k_chain(const __grid_constant__ CUtensorMap tmx, const __grid_constant__ CUtensorMap tmq, const __grid_constant__ CUtensorMap tmk,
        const __grid_constant__ CUtensorMap tmv, const __grid_constant__ CUtensorMap tmx2, const __grid_constant__ CUtensorMap tmo, const bf16* __restrict__ mem0, const bf16* __restrict__ xg) {
    extern __shared__ __align__(1024) unsigned char smem_raw[];
    const uint32_t sbase = smem_u32(smem_raw);
    const int cta = blockIdx.x, h = cta / 3, role = cta - 3 * h;
    const int tid = threadIdx.x, warp = __shfl_sync(0xffffffffu, tid >> 5, 0), lane_o = tid & 31;
    TS3C(0);
    asm volatile("griddepcontrol.launch_dependents;" ::: "memory");
    auto stage_w = [&](int i) {
        tma_2d(sbase + SM_WS + i * 16384, role == 2 ? &tmv : &tmq, h * DH + (role == 1 ? 64 : 0), i * 64, sbase + B_W + 8 * i);
        tma_2d(sbase + SM_WS + i * 16384 + 8192, role == 2 ? &tmv : &tmk, h * DH + (role == 0 ? 0 : 64), i * 64, sbase + B_W + 8 * i);
    };
    auto stage_x = [&](int i) { tma_2d(sbase + x01_off(i), &tmx2, i * 64, 0, sbase + B_W + 8 * i); };
    if (tid == 0) {
#pragma unroll
        for (int i = 0; i < 10; i++) mbar_init(sbase + B_W + 8 * i, 1);
        fence_async();
        bulk_g2s(sbase + SM_E + XBUF, mem0, MEMT * DM * 2, sbase + B_E);
#pragma unroll
        for (int i = 0; i < 3; i++) tma_2d(sbase + SM_X01 + i * 16384, &tmo, role * WOC + i * 64, h * DH, sbase + B_E);
        if (cta < NSEG) bulk_g2s(sbase + SM_E, xg + (size_t)cta * SEG * DM, XBUF, sbase + B_E);
#pragma unroll 1
        for (int i = 0; i < 6; i++) { if (i < 3) stage_x(i); stage_w(i); }
        mbar_expect(sbase + B_E, 49152 + MEMT * DM * 2 + (cta < NSEG ? XBUF : 0));
#pragma unroll
        for (int i = 0; i < 9; i++) mbar_expect(sbase + B_W + 8 * i, 24576);
    } else if (tid == 32) {
#pragma unroll
        for (int i = 0; i < 7; i++) mbar_init(sbase + SM_BAR + 8 * i, 1);
        asm volatile("fence.mbarrier_init.release.cluster;" ::: "memory");
        for (int i = 0; i < 2; i++) {
            mbar_expect(sbase + B_SB + 8 * i, role == 2 ? 2560 : 1280 + 2048);
            mbar_expect(sbase + B_VX + 8 * i, role != 2 ? 8192 : 2 * 9216);
            mbar_arrive(sbase + B_XT + 8 * i);
        }
        mbar_expect(sbase + B_XT + 16, XBUF);
        reinterpret_cast<float*>(smem_raw + SM_SC)[2] = 1.f;
    } else if (tid >= 64 && tid < 88) {
        *reinterpret_cast<uint4*>(g_acc + cta * 1024 + (tid - 64) * 16) = make_uint4(0u, 0u, 0u, 0u);
        __threadfence();
    }
    __syncthreads();
    TS3C(8);
    if (warp < 8) {
        uint32_t wreg[36 - NS][4];
        {
            const int lane = lane_o;
            const uint32_t a = w_addr(sbase, warp, lane);
            const uint64_t da = smem_desc(sbase + SM_WS + (warp >> 2) * 8192, 1024, 1024) | (1ull << 62);
            float acc[32];
#pragma unroll
            for (int i = 0; i < 32; i++) acc[i] = 0.f;
#pragma unroll 1
            for (int b = 0; b < 9; b++) {
                if (b == 0) TSQ(0);
                mbar_wait(sbase + B_W + 8 * b, 0);
                TSQ(1 + b);
                if (b == 8) TS3C(2);
                const uint64_t db = smem_desc(sbase + x01_off(b), 16, 1024) | (1ull << 62);
                wg_fence();
#pragma unroll
                for (int k = 0; k < 4; k++) wgmma_n64_ss(acc, da + (uint64_t)(b * 1024 + k * 128), db + (uint64_t)(k * 2));
                wg_commit();
                if (b == 5) {
#pragma unroll
                    for (int ks = NS; ks < 24; ks++) ldsm_x4_t(wreg[ks - NS], a + (ks >> 2) * 16384 + (ks & 3) * 2048);
                }
            }
#pragma unroll
            for (int ks = 24; ks < 32; ks++) ldsm_x4_t(wreg[ks - NS], a + (ks >> 2) * 16384 + (ks & 3) * 2048);
            wg_wait0();
            named_bar(9, 384);
            const uint32_t off = sbase + SM_T + (DH + warp * 16 + (lane & 15)) * 16 + (lane >> 4) * (DH * 16);
#pragma unroll
            for (int i = 0; i < 4; i++)
                stsm_x4(off + (i >> 1) * TBUF + (i & 1) * (2 * DH * 16), pack_bf16(acc[8 * i], acc[8 * i + 1]), pack_bf16(acc[8 * i + 2], acc[8 * i + 3]),
                        pack_bf16(acc[8 * i + 4], acc[8 * i + 5]), pack_bf16(acc[8 * i + 6], acc[8 * i + 7]));
#pragma unroll
            for (int ks = 32; ks < 36; ks++) ldsm_x4_t(wreg[ks - NS], a + (ks >> 2) * 16384 + (ks & 3) * 2048);
            if (role == 2) fence_async();
            bar_arrive(8, 384);
            named_bar(7, 256);
            asm volatile("barrier.cluster.arrive.relaxed.aligned;" ::: "memory");
        }
        TS3C(3);
        auto xproj1 = [&](float (&acc)[16], int j) {
            const uint32_t dlo = __shfl_sync(0xffffffffu, (uint32_t)smem_desc(sbase + SM_X + (j % 3) * XBUF, 16, 1024), 0);
            wg_fence();
#pragma unroll
            for (int ks = NS; ks < NS + NC1; ks++)
                wgmma_n32(acc, wreg[ks - NS], ((uint64_t)0x40000040u << 32) | (uint64_t)(dlo + (uint32_t)((ks >> 2) * 256 + (ks & 3) * 2)), ks > NS);
            wg_commit();
            wg_wait0();
        };
        auto xproj2 = [&](float (&acc)[16], int j) {
            int lane = lane_o;
            asm volatile("" : "+r"(lane));
            const uint32_t dlo = __shfl_sync(0xffffffffu, (uint32_t)smem_desc(sbase + SM_X + (j % 3) * XBUF, 16, 1024), 0);
            const uint64_t da = smem_desc(sbase + SM_WS + (warp >> 2) * 8192, 1024, 1024) | (1ull << 62);
            wg_fence();
#pragma unroll
            for (int ks = NS + NC1; ks < NS + NC1 + SS_POS; ks++)
                wgmma_n32(acc, wreg[ks - NS], ((uint64_t)0x40000040u << 32) | (uint64_t)(dlo + (uint32_t)((ks >> 2) * 256 + (ks & 3) * 2)), 1);
#pragma unroll
            for (int ks = 0; ks < NS; ks++)
                wgmma_n32_ss(acc, da + (uint64_t)((ks >> 2) * 1024 + (ks & 3) * 128), ((uint64_t)0x40000040u << 32) | (uint64_t)(dlo + (uint32_t)((ks >> 2) * 256 + (ks & 3) * 2)), 1);
#pragma unroll
            for (int ks = NS + NC1 + SS_POS; ks < XK; ks++)
                wgmma_n32(acc, wreg[ks - NS], ((uint64_t)0x40000040u << 32) | (uint64_t)(dlo + (uint32_t)((ks >> 2) * 256 + (ks & 3) * 2)), 1);
            wg_commit();
            wg_wait0();
            const uint32_t off = sbase + SM_T + (j & 3) * TBUF + (DH + warp * 16 + (lane & 15)) * 16 + (lane >> 4) * (DH * 16);
            stsm_x4(off, pack_bf16(acc[0], acc[1]), pack_bf16(acc[2], acc[3]), pack_bf16(acc[4], acc[5]), pack_bf16(acc[6], acc[7]));
            stsm_x4(off + 2 * DH * 16, pack_bf16(acc[8], acc[9]), pack_bf16(acc[10], acc[11]), pack_bf16(acc[12], acc[13]), pack_bf16(acc[14], acc[15]));
        };
        uint32_t ws[NS][4];
#pragma unroll
        for (int ks = NS - NP; ks < NS; ks++) ldsm_x4_t(ws[ks], w_addr(sbase, warp, lane_o) + (ks >> 2) * 16384 + (ks & 3) * 2048);
        asm volatile("barrier.cluster.wait.aligned;" ::: "memory");
        if (lane_o == 0 && warp < 2 && role == 2) vx_copy(sbase, 0, warp);
        __syncwarp();
        TS3C(4);
        auto main_loop = [&](auto is_c) {
            const bool C = is_c.value;
            const uint32_t l16 = __shfl_sync(0xffffffffu, sbase + lane_o * 16, lane_o);
            const uint32_t ta = __shfl_sync(0xffffffffu, sbase + SM_T + warp * 256 + (lane_o & 15) * 16, lane_o);
            const uint32_t ka = __shfl_sync(0xffffffffu, sbase + SM_T + (64 + (lane_o & 7) + ((lane_o >> 3) & 1) * 16 + (lane_o >> 4) * 8) * 16, lane_o);
            uint32_t to = 0;
            for (int s = 0; s < NSEG; s++) {
                int lane = lane_o;
                asm volatile("" : "+r"(lane));
                uint32_t v0, v1;
                const uint32_t tb = sbase + SM_T + to;
                {
#pragma unroll
                    for (int ks = 0; ks < NS - NP; ks++) ldsm_x4_t(ws[ks], w_addr(sbase, warp, lane) + (ks >> 2) * 16384 + (ks & 3) * 2048);
                    FS(0, ws[0][0]);
                    named_bar(1, 384);
                    float acc[2][4], minv;
                    uint32_t b[3][4];
#pragma unroll
                    for (int kk = 0; kk < 3; kk++) ldsm_x4_t(b[kk], l16 + SM_M + kk * 512);
                    FS(1, b[0][0]);
#pragma unroll
                    for (int kk = 0; kk < 18; kk++) {
#pragma unroll
                        for (int i = 0; i < 2; i++) {
                            const int ks = 2 * kk + i;
                            if (ks < 2) mma_z(acc[i], ws[ks], b[kk % 3][2 * i], b[kk % 3][2 * i + 1]);
                            else if (ks < NS) mma_bf16(acc[i], ws[ks < NS ? ks : 0], b[kk % 3][2 * i], b[kk % 3][2 * i + 1]);
                            else mma_bf16(acc[i], wreg[ks >= NS ? ks - NS : 0], b[kk % 3][2 * i], b[kk % 3][2 * i + 1]);
                        }
                        if (kk + 3 < 18) ldsm_x4_t(b[kk % 3], l16 + SM_M + (kk + 3) * 512);
                        if (kk + 3 == 17) asm volatile("ld.shared.f32 %0, [%1];" : "=f"(minv) : "r"(sbase + SM_SC + 8) : "memory");
                    }
                    v0 = pack_bf16(fmaf(acc[1][0], minv, acc[0][0] * minv), fmaf(acc[1][1], minv, acc[0][1] * minv));
                    v1 = pack_bf16(fmaf(acc[1][2], minv, acc[0][2] * minv), fmaf(acc[1][3], minv, acc[0][3] * minv));
                    FS(2, v0);
                }
                asm volatile("stmatrix.sync.aligned.m8n8.x2.shared.b16 [%0], {%1,%2};" :: "r"(ta + to), "r"(v0), "r"(v1) : "memory");
                if (C) {
                    if (s + 1 < NSEG) {
                        const uint32_t fo = (uint32_t)(warp * 256 + lane * 8);
                        const uint32_t rb0 = mapa(sbase, 0), rb1 = mapa(sbase, 1);
                        st_async64(rb0 + SM_VM + fo, v0, v1, rb0 + B_SB + 8 * (s & 1));
                        st_async64(rb1 + SM_VM + fo, v0, v1, rb1 + B_SB + 8 * (s & 1));
                        asm volatile("st.shared.v2.u32 [%0], {%1,%2};" :: "r"(sbase + SM_VM + fo), "r"(v0), "r"(v1) : "memory");
                        bar_arrive(2, 384);
                    }
                } else {
                    named_bar(2, 384);
                    if (warp == 7) {
                        uint32_t kf[2][4], qf[2][4];
#pragma unroll
                        for (int k2 = 0; k2 < 2; k2++) { ldsm_x4_t(kf[k2], ka + to + k2 * 512); ldsm_x4_t(qf[k2], l16 + SM_T + to + k2 * 512); }
                        if (s + 1 < NSEG) {
                            const uint32_t d0 = sbase + SM_S + role * 1280 + lane * 8, bo = sbase + B_SB + 8 * (s & 1);
                            const uint32_t d1 = mapa(d0, role ^ 1), m1 = mapa(bo, role ^ 1), d2 = mapa(d0, 2), m2 = mapa(bo, 2);
                            score_group(qf, kf, d0, d1, m1, d2, m2);
                            bar_arrive(6, 160);
                        }
                    }
                    if (s + 1 == NSEG && warp >= 4) {
                        const uint32_t dk = mapa(sbase + SM_X + XBUF + (2 + role) * 9216 + (warp - 4) * 256 + lane * 4, 2), mb = mapa(sbase + B_VX + 8, 2);
                        st_async32(dk, v0, mb);
                        st_async32(dk + 128, v1, mb);
                    }
                }
                to = to == 3 * TBUF ? 0 : to + TBUF;
                FS(11, 0);
                if (s + 2 < NSEG) {
                    if (warp == 6) mbar_wait(sbase + B_XT + 8 * ((s + 2) % 3), (uint32_t)((s + 2) / 3) & 1u);
                    fence_async();
                    if (!C) named_bar(5, 384); else named_bar(7, 256);
                    if (tid == 64) store_tile(s, h, role, tb);
                    __syncwarp();
                    float xacc[16];
                    if (C1_DELAY > 0) { const uint32_t t1 = clock32(); while (clock32() - t1 < C1_DELAY) {} }
                    xproj1(xacc, s + 2);
                    FS(9, __float_as_uint(xacc[0]));
                    if (C && tid == 0) vx_copy(sbase, s + 1, 0);
                    if (tid == 64) {
                        asm volatile("cp.async.bulk.wait_group 0;" ::: "memory");
                        asm volatile("red.relaxed.gpu.global.add.u32 [%0], 1;" :: "l"(&g_flag[h * NSEG + s]) : "memory");
                    }
                    __syncwarp();
                    FS(14, 0);
                    named_bar(4, 384);
                    if (C2_DELAY > 0) { const uint32_t t1 = clock32(); while (clock32() - t1 < C2_DELAY) {} }
                    xproj2(xacc, s + 2);
                    FS(7, __float_as_uint(xacc[0]));
                } else if (s + 2 == NSEG) {
                    const uint32_t t0 = clock32();
                    const uint32_t dq = mapa(sbase + SM_X + XBUF + role * 9216, 2), mb = mapa(sbase + B_VX, 2);
                    if (!C) {
                        fence_async();
                        named_bar(5, 384);
                        if (tid == 64) { while (clock32() - t0 < TL_DELAY) {} bulk_s2s(dq, tb + 1024, 9216, mb); }
                        __syncwarp();
                    }
                    named_bar(4, 384);
                    if (!C && tid == 64) { const uint32_t t1 = clock32(); while (clock32() - t1 < VX_DELAY) {} bulk_s2s(dq + 2 * 9216 + 1024, sbase + SM_T + ((s + 1) & 3) * TBUF + 2048, 8192, mb + 8); }
                    __syncwarp();
                }
            }
            if (C) named_bar(7, 256);
        };
        if (role == 2) main_loop(Flag<true>()); else main_loop(Flag<false>());
    } else {
        float* scs = reinterpret_cast<float*>(smem_raw + SM_SC);
        uint32_t wo[3][8][4];
        uint32_t mx2 = 0u;
        {
            const int pt = tid - 256, lane = lane_o, wq = warp - 8, g = lane >> 2, tq = lane & 3;
            TSQ(7);
            mbar_wait(sbase + B_E, 0);
            TSQ(8);
#pragma unroll
            for (int t = 0; t < 3; t++) {
                const int T = 3 * wq + t;
                const uint32_t a = sbase + SM_X01 + (T >> 2) * 16384 + ((lane >> 4) * 8 + (lane & 7)) * 128 + ((((T & 3) * 2 + ((lane >> 3) & 1)) ^ (lane & 7)) << 4);
#pragma unroll
                for (int kk = 0; kk < 8; kk++) ldsm_x4_t(wo[t][kk], a + ((2 * wq + kk) & 7) * 2048);
            }
            uint32_t m = 0u;
#pragma unroll 6
            for (int j = 0; j < 18; j++) {
                const uint32_t v = lds32(sbase + SM_E + XBUF + (g * DM + wq * 144 + 8 * j) * 2 + tq * 4);
                asm volatile("stmatrix.sync.aligned.m8n8.x1.trans.shared.b16 [%0], {%1};" :: "r"(sbase + SM_M + (wq * 144 + 8 * j + (lane & 7)) * 16), "r"(v) : "memory");
                mx2 = __vmaxu2(mx2, v & 0x7fff7fffu);
                const uint4 xv = *reinterpret_cast<const uint4*>(smem_raw + SM_E + (pt + 128 * j) * 16);
                m = max_abs2(max_abs2(m, max_abs2(xv.x, xv.y)), max_abs2(xv.z, xv.w));
            }
            m = __reduce_max_sync(0xffffffffu, max((m << 16) & 0x7fff0000u, m & 0x7fff0000u));
            if (lane == 0) reinterpret_cast<uint32_t*>(scs)[260 + wq] = m;
            named_bar(3, 128);
            if (pt == 64) {
                fence_async();
#pragma unroll 1
                for (int i = 3; i < 9; i++) { stage_x(i); if (i >= 6) stage_w(i); }
            }
            if (pt == 96 && cta < NSEG) {
                const uint4 q = *reinterpret_cast<const uint4*>(scs + 260);
                asm volatile("st.volatile.global.u32 [%0], %1;" :: "l"(&g_rx[cta]), "r"(max(max(q.x, q.y), max(q.z, q.w)) | 1u) : "memory");
            }
            __syncwarp();
            bar_arrive(1, 384);
            TSQ(9);
            float c0 = 0.f;
#pragma unroll
            for (int t = 0; t < 3; t++) {
                float n[4][4];
#pragma unroll
                for (int i = 0; i < 4; i++) { n[i][0] = n[i][1] = n[i][2] = n[i][3] = 0.f; }
#pragma unroll
                for (int kk = 0; kk < 8; kk++)
#pragma unroll
                    for (int i = 0; i < 4; i++) mma_k8(n[i], wo[t][kk][i & 2], wo[t][kk][(i & 2) + 1], wo[t][kk][i]);
                if ((g >> 1) == tq) c0 = fmaxf(c0, (g & 1) ? fmaxf(n[0][1] + n[2][1], n[1][3] + n[3][3]) : fmaxf(n[0][0] + n[2][0], n[1][2] + n[3][2]));
            }
            c0 = __uint_as_float(__reduce_max_sync(0xffffffffu, __float_as_uint(c0)));
            m = 0u;
#pragma unroll 1
            for (int b = 0; b < 9; b++) {
                if (role == 2) {
                    mbar_wait(sbase + B_W + 8 * b, 0);
#pragma unroll
                    for (int j = 0; j < 8; j++) {
                        const uint4 xv = *reinterpret_cast<const uint4*>(smem_raw + SM_WS + b * 16384 + (pt + 128 * j) * 16);
                        m = max_abs2(max_abs2(m, max_abs2(xv.x, xv.y)), max_abs2(xv.z, xv.w));
                    }
                }
                if (b == 3) bar_arrive(9, 384);
            }
            asm volatile("barrier.cluster.arrive.relaxed.aligned;" ::: "memory");
            m = __reduce_max_sync(0xffffffffu, max((m << 16) & 0x7fff0000u, m & 0x7fff0000u));
            if (lane == 0) { scs[256 + wq] = c0; reinterpret_cast<uint32_t*>(scs)[8 + wq] = m; }
            TSQ(1);
            named_bar(3, 128);
            if (pt == 0) {
                const float a = fmaxf(fmaxf(scs[256], scs[257]), fmaxf(scs[258], scs[259]));
                const float b = fmaxf(fmaxf(scs[8], scs[9]), fmaxf(scs[10], scs[11]));
                st_vol_u2(&g_norm[cta], make_uint2(__float_as_uint(a) | 1u, __float_as_uint(b) | 1u));
            }
            __syncwarp();
            named_bar(8, 384);
            TSQ(2);
            if (pt == 32) {
                fence_async();
                for (int i = 0; i < 3; i++) tma_x(sbase + SM_X + 2 * XBUF, &tmx, 2, i, sbase + B_XT + 16);
            }
            __syncwarp();
            asm volatile("barrier.cluster.wait.aligned;" ::: "memory");
        }
        const int wq = warp - 8;
        auto helper_loop = [&](auto is_c) {
        const bool C = is_c.value;
        const uint32_t l8 = __shfl_sync(0xffffffffu, sbase + lane_o * 8, lane_o), l16 = __shfl_sync(0xffffffffu, sbase + lane_o * 16, lane_o);
        unsigned char* dst = g_acc + (role * 32 + wq * 8 + (lane_o >> 3)) * 1024 + (lane_o & 7) * 16;
        const uint32_t ka = __shfl_sync(0xffffffffu, sbase + SM_T + ((wq + 1) * DH + 64 + (lane_o & 7) + ((lane_o >> 3) & 1) * 16 + (lane_o >> 4) * 8) * 16, lane_o);
        const uint32_t vb = __shfl_sync(0xffffffffu, sbase + (lane_o >> 4) * 2048 + (32 * wq + (lane_o & 15)) * 16, lane_o);
        float minv = 1.f;
        uint32_t kf[2][4];
#pragma unroll
        for (int k2 = 0; k2 < 2; k2++) if (!C) ldsm_x4_t(kf[k2], ka + k2 * 512);
        int b3 = 0;
        for (int s = 0; s + 1 < NSEG; s++) {
            const int n3 = b3 == 2 ? 0 : b3 + 1;
            {
                int lane = lane_o;
                asm volatile("" : "+r"(lane));
                if (lane == 0) {
                    if (wq == 0 && cta == 0) {
                        const uint32_t t = gtime32();
                        st_vol_u2(&g_tick, make_uint2(t, reinterpret_cast<uint32_t*>(scs)[3]));
                        reinterpret_cast<uint32_t*>(scs)[3] = t;
                    }
                    if (wq == 1 && s + 3 < NSEG) tma_x_mc(sbase + SM_X + b3 * XBUF, &tmx, s + 3, role, sbase + B_XT + 8 * b3);
                    if (wq == 0 && s == 1) {
                        st_vol_u2(&g_norm[cta], make_uint2(0u, 0u));
                        if (cta < NSEG) asm volatile("st.volatile.global.u32 [%0], %1;" :: "l"(&g_rx[cta]), "r"(0u) : "memory");
                    }
                }
                __syncwarp();
                if (wq == 2 && s > 1 && lane < 8) {
                    *reinterpret_cast<uint4*>(g_acc + n3 * 128 + cta * 1024 + lane * 16) = make_uint4(0u, 0u, 0u, 0u);
                }
                const uint32_t mw = __reduce_max_sync(0xffffffffu, max(mx2 << 16, mx2 & 0xffff0000u));
                if (lane == 0) scs[4 + wq] = __uint_as_float(mw);
            }
            const uint32_t to = SM_T + (s & 3) * TBUF;
            const uint32_t ph = (uint32_t)(s >> 1) & 1u;
            if (!C) {
                const uint32_t so = SM_S + role * 1280 + (wq + 1) * 256, bo = sbase + B_SB + 8 * (s & 1);
                uint32_t d0 = l8 + so, qa = l16 + to;
                const uint32_t d1 = mapa(d0, role ^ 1), m1 = mapa(bo, role ^ 1), d2 = mapa(d0, 2), m2 = mapa(bo, 2);
                asm volatile("" : "+r"(d0), "+r"(qa));
                mbar_wait(sbase + B_VX + 8 * (s & 1), ph);
                FS(1, 0);
                named_bar(2, 384);
                uint32_t qf[2][4];
#pragma unroll
                for (int k2 = 0; k2 < 2; k2++) ldsm_x4_t(qf[k2], qa + k2 * 512);
                score_group(qf, kf, d0, d1, m1, d2, m2);
                bar_arrive(5, 384);
            } else named_bar(2, 384);
            if (s == 0) {
                TSQ(3);
                int lane = lane_o;
                asm volatile("" : "+r"(lane));
                if (wq == 1) norms_gather(lane, scs);
                named_bar(3, 128);
                TSQ(4);
            }
            const float4 m4 = *reinterpret_cast<const float4*>(scs + 4);
            const float c24 = scs[1], xb = scs[16 + s];
            uint32_t vf[2][2][4], vm[2][2];
            {
                const uint32_t va = vb + (C ? to + DH * 16 : SM_VX + (s & 1) * 8192);
#pragma unroll
                for (int i = 0; i < 4; i++) ldsm_x4(vf[i >> 1][i & 1], va + (i >> 1) * 256 + (i & 1) * 4096);
            }
            float scale;
            {
                const float bound = fmaxf(fmaxf(fmaxf(m4.x, m4.y), fmaxf(m4.z, m4.w)) * minv, xb) * c24;
                int e = 141 - (int)((__float_as_uint(bound) >> 23) & 255u);
                e = e > 100 ? 100 : e;
                scale = __uint_as_float((uint32_t)(127 + e) << 23);
            }
            uint32_t s0 = l8 + (role & 1) * 1280, s1 = l8 + ((role & 1) ^ 1) * 1280, oa = l16 + wq * 512;
            asm volatile("" : "+f"(scale), "+r"(s0), "+r"(s1), "+r"(oa));
            FS(7, vf[1][1][0]);
            constexpr float EC = (float)(1.4426950408889634 * 0.08838834764831845);
            if (!C) named_bar(6, 160);
            if (C) mbar_wait(sbase + B_SB + 8 * (s & 1), ph);
            float sv[5][2];
#pragma unroll
            for (int j = 0; j < 5; j++) lds64f(sv[j][0], sv[j][1], s0 + SM_S + j * 256);
            if (!C) {
#pragma unroll
                for (int j = 0; j < 5; j++) { sv[j][0] *= EC; sv[j][1] *= EC; asm volatile("" : "+f"(sv[j][0]), "+f"(sv[j][1])); }
                mbar_wait(sbase + B_SB + 8 * (s & 1), ph);
            }
            FS(6, 0);
            uint32_t p[5];
            {
                float sr[5][2];
#pragma unroll
                for (int j = 0; j < 5; j++) lds64f(sr[j][0], sr[j][1], s1 + SM_S + j * 256);
                lds64(vm[0][0], vm[0][1], l8 + SM_VM + wq * 512);
                lds64(vm[1][0], vm[1][1], l8 + SM_VM + wq * 512 + 256);
                if (C) {
#pragma unroll
                    for (int j = 0; j < 5; j++) { sv[j][0] *= EC; sv[j][1] *= EC; }
                }
#pragma unroll
                for (int j = 0; j < 5; j++) { sv[j][0] = fmaf(sr[j][0], EC, sv[j][0]); sv[j][1] = fmaf(sr[j][1], EC, sv[j][1]); }
                float mx = fmaxf(fmaxf(fmaxf(sv[0][0], sv[0][1]), fmaxf(sv[1][0], sv[1][1])), fmaxf(fmaxf(sv[2][0], sv[2][1]), fmaxf(sv[3][0], sv[3][1])));
                mx = fmaxf(mx, fmaxf(sv[4][0], sv[4][1]));
                {
                    const float m1 = __shfl_xor_sync(0xffffffffu, mx, 1), m2 = __shfl_xor_sync(0xffffffffu, mx, 2), m3 = __shfl_xor_sync(0xffffffffu, mx, 3);
                    mx = fmaxf(fmaxf(mx, m1), fmaxf(m2, m3));
                }
#pragma unroll
                for (int jj = 0; jj < 5; jj++) {
                    const int j = (jj + 1) % 5;
                    asm("ex2.approx.ftz.f32 %0, %1;" : "=f"(sv[j][0]) : "f"(sv[j][0] - mx));
                    asm("ex2.approx.ftz.f32 %0, %1;" : "=f"(sv[j][1]) : "f"(sv[j][1] - mx));
                    p[j] = pack_bf16(sv[j][0], sv[j][1]);
                }
            }
            FS(0, p[0]);
            uint32_t b[4][4];
            float zs[4];
            {
                float o0[2][4], o1[2][4];
                mma_z(o0[0], vf[0][0], p[1], p[2]);
                mma_z(o0[1], vf[1][0], p[1], p[2]);
                mma_z(o1[0], vf[0][1], p[3], p[4]);
                mma_z(o1[1], vf[1][1], p[3], p[4]);
                mma_k8(o0[0], vm[0][0], vm[0][1], p[0]);
                mma_k8(o0[1], vm[1][0], vm[1][1], p[0]);
                const uint32_t one4[4] = {0x3f803f80u, 0x3f803f80u, 0x3f803f80u, 0x3f803f80u};
                mma_z(zs, one4, p[1], p[2]);
                mma_bf16(zs, one4, p[3], p[4]);
                mma_k8(zs, one4[0], one4[1], p[0]);
                uint32_t ow[4];
#pragma unroll
                for (int m = 0; m < 2; m++) {
                    ow[2 * m] = pack_bf16(o0[m][0] + o1[m][0], o0[m][1] + o1[m][1]);
                    ow[2 * m + 1] = pack_bf16(o0[m][2] + o1[m][2], o0[m][3] + o1[m][3]);
                }
                stsm_x4(oa + SM_O, ow[0], ow[1], ow[2], ow[3]);
                FS(2, 0);
#pragma unroll
                for (int i = 0; i < 4; i++) b[0][i] = movm(ow[i]);
            }
            float acc[3][2][4];
            named_bar(3, 128);
#pragma unroll
            for (int i = 1; i < 4; i++) ldsm_x4_t(b[i], l16 + SM_O + ((wq + i) & 3) * 512);
#pragma unroll
            for (int c = 0; c < 2; c++)
#pragma unroll
                for (int t = 0; t < 3; t++) mma_z(acc[t][c], wo[t][c], b[0][2 * c], b[0][2 * c + 1]);
            float z0, z1;
            asm volatile("rcp.approx.ftz.f32 %0, %1;" : "=f"(z0) : "f"(zs[0]));
            asm volatile("rcp.approx.ftz.f32 %0, %1;" : "=f"(z1) : "f"(zs[1]));
            z0 *= scale; z1 *= scale;
            FS(3, b[1][0]);
#pragma unroll
            for (int i = 1; i < 4; i++)
#pragma unroll
                for (int c = 0; c < 2; c++)
#pragma unroll
                    for (int t = 0; t < 3; t++) mma_bf16(acc[t][c], wo[t][2 * i + c], b[i][2 * c], b[i][2 * c + 1]);
            {
                uint32_t w[6];
#pragma unroll
                for (int t = 0; t < 3; t++) {
                    w[2 * t] = pack_f16(fmaf(acc[t][1][0], z0, acc[t][0][0] * z0), fmaf(acc[t][1][1], z1, acc[t][0][1] * z1));
                    w[2 * t + 1] = pack_f16(fmaf(acc[t][1][2], z0, acc[t][0][2] * z0), fmaf(acc[t][1][3], z1, acc[t][0][3] * z1));
                }
                FS(8, w[5]);
                asm volatile("red.relaxed.gpu.global.add.noftz.v4.f16x2 [%0], {%1,%2,%3,%4};" :: "l"(dst), "r"(w[0]), "r"(w[1]), "r"(w[2]), "r"(0x3c00u) : "memory");
                asm volatile("red.relaxed.gpu.global.add.noftz.v4.f16x2 [%0], {%1,%2,%3,%4};" :: "l"(dst + 4096), "r"(w[3]), "r"(w[4]), "r"(w[5]), "r"(0x3c00u) : "memory");
            }
            FS(9, 0);
            if (s == 0) TSQ(5);
            bar_arrive(4, 384);
            const uint32_t t0 = clock32();
            minv = __uint_as_float(0x7f000000u - __float_as_uint(scale));
            if (lane_o == 0) {
                if (wq == 0) scs[2] = minv;
                if (wq == 2 && C && s + 2 < NSEG) { while (clock32() - t0 < VX_DELAY) {} vx_copy(sbase, s + 1, 1); }
                if (s + 3 < NSEG) {
                    if (wq == 0) mbar_expect(sbase + B_SB + 8 * (s & 1), C ? 2560 : 1280 + 2048);
                    if (wq == 1) mbar_expect(sbase + B_XT + 8 * b3, XBUF);
                    if (wq == 3 && !C) mbar_expect(sbase + B_VX + 8 * (s & 1), 8192);
                }
            }
            __syncwarp();
#pragma unroll
            for (int k2 = 0; k2 < 2; k2++) if (!C) ldsm_x4_t(kf[k2], ka + ((s + 1) & 3) * TBUF + k2 * 512);
            const uint4* src = reinterpret_cast<const uint4*>(dst + (wq * 16 - role * 32) * 1024);
            dst += n3 == 0 ? -256 : 128;
            asm volatile("" : "+l"(dst));
            mx2 = poll_mem(src, l16 + SM_M + wq * 2304, t0);
            if (s == 0) TSQ(6);
            b3 = n3;
        }
        if (!C) bar_arrive(2, 384);
        };
        if (role == 2) helper_loop(Flag<true>()); else helper_loop(Flag<false>());
    }
    TS3C(1);
    if (role == 2 && warp >= 4) {
        const int sg = warp < 8, wq = warp & 3, lane = lane_o;
        const uint32_t qk = sbase + SM_X + XBUF + sg * (2 * 9216), ob = sbase + SM_X + 2 * XBUF + sg * 8192;
        TST(0);
        mbar_wait(sbase + B_VX + 8 * sg, 0);
        fence_async();
        TST(1);
        float sc[20];
        {
            const uint64_t da = smem_desc(qk + 1024, 128, 1024), db = smem_desc(qk, 128, 2048);
            wg_fence();
#pragma unroll
            for (int ks = 0; ks < 8; ks++) wgmma_n40_ss(sc, da + (uint64_t)((ks >> 2) * 576 + (ks & 3) * 16), db + (uint64_t)((ks >> 2) * 576 + (ks & 3) * 16), ks > 0);
            wg_commit();
            wg_wait0();
        }
        uint32_t pa[3][4];
        xrow_softmax(sc, pa, wq, lane);
        float o[2][32];
        const uint64_t dv = smem_desc(sbase + SM_T + ((NSEG - 2 + sg) & 3) * TBUF, 2048, 128);
        wg_fence();
#pragma unroll
        for (int hf = 0; hf < 2; hf++)
#pragma unroll
            for (int ks = 0; ks < 3; ks++) { if (ks == 0) wgmma_n64_z(o[hf], pa[0], dv + (uint64_t)(hf * 64)); else wgmma_n64(o[hf], pa[ks], dv + (uint64_t)(hf * 64 + ks * 256), 1); }
        wg_commit();
        wg_wait0();
#pragma unroll
        for (int hf = 0; hf < 2; hf++)
#pragma unroll
            for (int i = 0; i < 2; i++)
                stsm_x4(ob + hf * 4096 + wq * 1024 + i * 512 + lane * 16, pack_bf16(o[hf][16 * i], o[hf][16 * i + 1]), pack_bf16(o[hf][16 * i + 4], o[hf][16 * i + 5]),
                        pack_bf16(o[hf][16 * i + 8], o[hf][16 * i + 9]), pack_bf16(o[hf][16 * i + 12], o[hf][16 * i + 13]));
        fence_async();
        named_bar(11 + sg, 128);
        TST(2);
        if ((tid & 127) == 0) {
            unsigned char* dst = reinterpret_cast<unsigned char*>(g_ox) + ((size_t)((NSEG / 2 - 1) * NH + h)) * 16384 + sg * 4096;
            asm volatile("cp.async.bulk.global.shared::cta.bulk_group [%0], [%1], 4096;" :: "l"(dst), "r"(ob) : "memory");
            asm volatile("cp.async.bulk.global.shared::cta.bulk_group [%0], [%1], 4096;" :: "l"(dst + 8192), "r"(ob + 4096) : "memory");
            asm volatile("cp.async.bulk.commit_group;" ::: "memory");
            asm volatile("cp.async.bulk.wait_group 0;" ::: "memory");
            asm volatile("red.relaxed.gpu.global.add.u32 [%0], 1;" :: "l"(&g_prog[(NSEG / 2 - 1) * 8 + (h >> 2)]) : "memory");
        }
        TST(3);
    }
    __syncwarp();
    cluster_sync_all();
}

extern "C" void kernel_launch(void* const* d_in, const int* in_sizes, int n_in, void* d_out, int out_size) {
    const bf16* x = (const bf16*)d_in[0];
    const bf16* mem0 = (const bf16*)d_in[1];
    const bf16* Wq = (const bf16*)d_in[2];
    const bf16* Wk = (const bf16*)d_in[3];
    const bf16* Wv = (const bf16*)d_in[4];
    const bf16* Wo = (const bf16*)d_in[5];
    const bf16* logA = (const bf16*)d_in[8];
    const bf16* Aim = (const bf16*)d_in[9];
    const bf16* Cre = (const bf16*)d_in[10];
    const bf16* Cim = (const bf16*)d_in[11];
    const bf16* logdt = (const bf16*)d_in[12];
    const bf16* dskip = (const bf16*)d_in[13];
    const bf16* gw = (const bf16*)d_in[14];
    bf16* out = (bf16*)d_out;
    static bool attr_done = false;
    typedef CUresult (*EncFn)(CUtensorMap*, CUtensorMapDataType, cuuint32_t, void*, const cuuint64_t*, const cuuint64_t*, const cuuint32_t*,
                              const cuuint32_t*, CUtensorMapInterleave, CUtensorMapSwizzle, CUtensorMapL2promotion, CUtensorMapFloatOOBfill);
    static EncFn enc = nullptr;
    if (!attr_done) {
        void* fn = nullptr;
        cudaDriverEntryPointQueryResult qr;
        cudaGetDriverEntryPoint("cuTensorMapEncodeTiled", &fn, cudaEnableDefault, &qr);
        enc = (EncFn)fn;
        cudaFuncSetAttribute(k_chain, cudaFuncAttributeMaxDynamicSharedMemorySize, 232448);
        cudaFuncSetAttribute(k_side, cudaFuncAttributeMaxDynamicSharedMemorySize, SIDE_SMEM);
        attr_done = true;
    }
    CUtensorMap tmx;
    {
        const cuuint64_t dims[3] = {64, (cuuint64_t)S_LEN, 9};
        const cuuint64_t strides[2] = {(cuuint64_t)DM * 2, 128};
        const cuuint32_t box[3] = {64, (cuuint32_t)SEG, 3};
        const cuuint32_t es[3] = {1, 1, 1};
        enc(&tmx, CU_TENSOR_MAP_DATA_TYPE_BFLOAT16, 3, (void*)x, dims, strides, box, es, CU_TENSOR_MAP_INTERLEAVE_NONE,
            CU_TENSOR_MAP_SWIZZLE_128B, CU_TENSOR_MAP_L2_PROMOTION_L2_128B, CU_TENSOR_MAP_FLOAT_OOB_FILL_NONE);
    }
    CUtensorMap tmw[3];
    for (int i = 0; i < 3; i++) {
        const cuuint64_t dims[2] = {(cuuint64_t)HD, (cuuint64_t)DM};
        const cuuint64_t strides[1] = {(cuuint64_t)HD * 2};
        const cuuint32_t box[2] = {64, 64};
        const cuuint32_t es[2] = {1, 1};
        enc(&tmw[i], CU_TENSOR_MAP_DATA_TYPE_BFLOAT16, 2, (void*)(i == 0 ? Wq : (i == 1 ? Wk : Wv)), dims, strides, box, es, CU_TENSOR_MAP_INTERLEAVE_NONE,
            CU_TENSOR_MAP_SWIZZLE_128B, CU_TENSOR_MAP_L2_PROMOTION_L2_256B, CU_TENSOR_MAP_FLOAT_OOB_FILL_NONE);
    }
    CUtensorMap tmo;
    {
        const cuuint64_t dims[2] = {(cuuint64_t)DM, (cuuint64_t)HD};
        const cuuint64_t strides[1] = {(cuuint64_t)DM * 2};
        const cuuint32_t box[2] = {64, 128};
        const cuuint32_t es[2] = {1, 1};
        enc(&tmo, CU_TENSOR_MAP_DATA_TYPE_BFLOAT16, 2, (void*)Wo, dims, strides, box, es, CU_TENSOR_MAP_INTERLEAVE_NONE,
            CU_TENSOR_MAP_SWIZZLE_128B, CU_TENSOR_MAP_L2_PROMOTION_L2_128B, CU_TENSOR_MAP_FLOAT_OOB_FILL_NONE);
    }
    CUtensorMap tmx2;
    {
        const cuuint64_t dims[2] = {(cuuint64_t)DM, (cuuint64_t)S_LEN};
        const cuuint64_t strides[1] = {(cuuint64_t)DM * 2};
        const cuuint32_t box[2] = {64, 64};
        const cuuint32_t es[2] = {1, 1};
        enc(&tmx2, CU_TENSOR_MAP_DATA_TYPE_BFLOAT16, 2, (void*)x, dims, strides, box, es, CU_TENSOR_MAP_INTERLEAVE_NONE,
            CU_TENSOR_MAP_SWIZZLE_128B, CU_TENSOR_MAP_L2_PROMOTION_L2_128B, CU_TENSOR_MAP_FLOAT_OOB_FILL_NONE);
    }
    k_chain<<<NCTA, 384, 232448>>>(tmx, tmw[0], tmw[1], tmw[2], tmx2, tmo, mem0, x);
    {
        cudaLaunchConfig_t cfg = {};
        cfg.gridDim = dim3(SD_NCTA); cfg.blockDim = dim3(512); cfg.dynamicSmemBytes = SIDE_SMEM; cfg.stream = cudaStreamPerThread;
        cudaLaunchAttribute at[1];
        at[0].id = cudaLaunchAttributeProgrammaticStreamSerialization;
        at[0].val.programmaticStreamSerializationAllowed = 1;
        cfg.attrs = at; cfg.numAttrs = 1;
        cudaLaunchKernelEx(&cfg, k_side, tmo, x, logA, Aim, Cre, Cim, logdt, Wo, dskip, gw, out);
    }
}
```

```cpp
#include <cuda_runtime.h>
#include <cuda.h>
#include <cuda_bf16.h>
#include <stdint.h>

typedef __nv_bfloat16 bf16;
#define LDV4 "ld.volatile.global.v4.u32 {%0,%1,%2,%3}, [%4];"
#define STV4 "st.volatile.global.v4.u32 [%0], {%1,%2,%3,%4};"
#define STV2 "st.volatile.global.v2.u32 [%0], {%1,%2};"

constexpr int S_LEN = 2048, DM = 576, NH = 32, DH = 128, HD = 4096, MEMT = 8, SEG = 32, NSEG = 64, NST = 128;

__device__ __align__(128) bf16 g_gate[S_LEN];
constexpr int NCTA = NH * 3;
__device__ __align__(1024) unsigned char g_acc[96 * 1024];
__device__ __align__(128) uint2 g_norm[NCTA];
__device__ __align__(128) uint32_t g_rx[NSEG];
__device__ __align__(128) unsigned char g_qkv[NSEG][NH][3][10240];
__device__ __align__(128) bf16 g_ox[S_LEN * HD];
__device__ __align__(128) uint4 g_fp[8][36][6][128];
__device__ __align__(128) unsigned g_flag[NH * NSEG];
__device__ unsigned g_prog[NSEG / 2 * 8];
__device__ unsigned g_gcnt[64];
__device__ unsigned g_epoch;
__device__ __align__(128) uint2 g_tick;
__device__ __align__(128) bf16 g_y[DM * S_LEN];

#define TS3(slot) do {} while (0)
#define TS3P(slot) do {} while (0)
#define TSQ(slot) do {} while (0)
#define TS3W(slot) do {} while (0)
#define TSS(row, slot) do {} while (0)
#define TS3C(slot) do {} while (0)
#define TST(slot) do {} while (0)
#define TSA(seg, slot) do {} while (0)
#define TSG(i) do {} while (0)
#define FS(i, dep) do {} while (0)
__device__ __forceinline__ uint32_t smem_u32(const void* p) { return (uint32_t)__cvta_generic_to_shared(p); }
__device__ __forceinline__ float bf16r(float x) { return __bfloat162float(__float2bfloat16_rn(x)); }
__device__ __forceinline__ uint32_t pack_bf16(float lo, float hi) {
    __nv_bfloat162 v = __floats2bfloat162_rn(lo, hi);
    return *reinterpret_cast<uint32_t*>(&v);
}
__device__ __forceinline__ void ldsm_x4(uint32_t (&r)[4], uint32_t addr) {
    asm volatile("ldmatrix.sync.aligned.m8n8.x4.shared.b16 {%0,%1,%2,%3}, [%4];"
                 : "=r"(r[0]), "=r"(r[1]), "=r"(r[2]), "=r"(r[3]) : "r"(addr));
}
__device__ __forceinline__ void ldsm_x4_t(uint32_t (&r)[4], uint32_t addr) {
    asm volatile("ldmatrix.sync.aligned.m8n8.x4.trans.shared.b16 {%0,%1,%2,%3}, [%4];"
                 : "=r"(r[0]), "=r"(r[1]), "=r"(r[2]), "=r"(r[3]) : "r"(addr));
}
__device__ __forceinline__ void mma_bf16(float (&d)[4], const uint32_t (&a)[4], uint32_t b0, uint32_t b1) {
    asm volatile("mma.sync.aligned.m16n8k16.row.col.f32.bf16.bf16.f32 {%0,%1,%2,%3}, {%4,%5,%6,%7}, {%8,%9}, {%0,%1,%2,%3};"
                 : "+f"(d[0]), "+f"(d[1]), "+f"(d[2]), "+f"(d[3])
                 : "r"(a[0]), "r"(a[1]), "r"(a[2]), "r"(a[3]), "r"(b0), "r"(b1));
}
__device__ __forceinline__ uint2 ld_vol_u2(const uint2* p) {
    uint2 v; asm volatile("ld.volatile.global.v2.u32 {%0,%1}, [%2];" : "=r"(v.x), "=r"(v.y) : "l"(p) : "memory"); return v;
}
__device__ __forceinline__ void st_vol_u2(uint2* p, uint2 v) {
    asm volatile(STV2 :: "l"(p), "r"(v.x), "r"(v.y) : "memory");
}
__device__ __forceinline__ unsigned ld_acq(const unsigned* p) {
    unsigned v; asm volatile("ld.acquire.gpu.global.u32 %0, [%1];" : "=r"(v) : "l"(p) : "memory"); return v;
}
#define XK 36
#define NC1 6
#define NS 6
#define NP 4
#define X_OXSZ 16384
#define GATE_A 1050
#define GATE_B 300
#define GATE_P 1880u
#define STAGGER 0
#define RLX_SLEEP 300
#define VX_DELAY 100
#define EARLY4 0
#define SPEC_M 1
#define SPEC_H 1
#define C1_DELAY 0
#define C2_DELAY 0
#define SS_POS 2
#define UNGATE_G 3
#define GATE_Y 0
#define GATE_S 0
#define GATE_F 1
#define W14_SLEEP 60
#define WARM 0
#define TURN31 1
#define GL_A 1150
#define GL_B 480
#define GS_A 1400
#define GS_B 480
#define GATE_POLL 0
#define GP_A 900
#define GP_B 200
#define TL_DELAY 600
#define POLL_DELAY 545
#define UNGATE 6
constexpr unsigned SPIN_LIMIT = 1u << 20;
constexpr int NATT = NSEG - 2;

constexpr int SD_CH = 16;
constexpr int SD_NCTA = DM / SD_CH;
constexpr int SD_ROW = 528;
constexpr int SD_U = 8 * SD_ROW;
constexpr int SD_TAP = 5888;
constexpr int SD_CPY = 1376 * 2;
constexpr int SD_WSTR = SD_TAP + 2 * SD_CPY;
constexpr int SD_SMEM = SD_CH * SD_U + 8 * SD_WSTR;
constexpr int O_U = 79, O_U3 = 911, O_U4 = 1055, O_W79 = 1023, O_W35 = 1151, O_W610 = 1279, O_W511 = 1487;

__device__ __forceinline__ uint32_t lds32(uint32_t a) { uint32_t v; asm volatile("ld.shared.u32 %0, [%1];" : "=r"(v) : "r"(a)); return v; }
__device__ __forceinline__ void tap_tile(uint32_t (&t)[4], uint32_t a) {
    asm volatile("ld.volatile.shared.u32 %0, [%4];\nld.volatile.shared.u32 %1, [%4+-16];\nld.volatile.shared.u32 %2, [%4+16];\nld.volatile.shared.u32 %3, [%4];"
                 : "=r"(t[0]), "=r"(t[1]), "=r"(t[2]), "=r"(t[3]) : "r"(a));
}
constexpr uint32_t sd_pass(int type, int dl, int o, int d0, int d1) { return (uint32_t)(type | dl << 2 | d0 << 8 | d1 << 12 | o << 17); }
__constant__ uint32_t SD_PASS[14] = {sd_pass(0, 0, O_U, 0, 2), sd_pass(0, 1, O_U + 96, 0, 2), sd_pass(0, 2, O_U + 192, 0, 4), sd_pass(0, 3, O_U + 288, 0, 2), sd_pass(1, 0, O_U3, 8, 8),
                                     sd_pass(0, 4, O_U + 384, 0, 2), sd_pass(1, 0, O_U4, 8, 15), sd_pass(0, 5, O_U + 480, 0, 2), sd_pass(0, 6, O_U + 576, 0, 4), sd_pass(0, 7, O_U + 672, 0, 2),
                                     sd_pass(2, 0, O_W35, 2, 8), sd_pass(3, 0, O_W79, 2, 4), sd_pass(2, 1, O_W610, 4, 8), sd_pass(3, 0, O_W511, 8, 15)};
__device__ __forceinline__ uint32_t band2(int x, int lo, int hi) { return (x >= lo && x <= hi ? 0x3f80u : 0u) | (x + 1 >= lo && x + 1 <= hi ? 0x3f800000u : 0u); }
__device__ __forceinline__ void mma_z(float (&d)[4], const uint32_t (&a)[4], uint32_t b0, uint32_t b1);
__device__ __forceinline__ void put_tap(uint32_t a, float v) {
    asm volatile("{\n.reg .b16 h;\ncvt.rn.bf16.f32 h, %1;\nst.shared.b16 [%0], h;\nst.shared.b16 [%0+%2], h;\n}" :: "r"(a), "f"(v), "n"(SD_CPY - 2) : "memory");
}

__device__ __forceinline__ void named_bar(int id, int n) { asm volatile("bar.sync %0, %1;" :: "r"(id), "r"(n) : "memory"); }
__device__ __forceinline__ uint32_t pack_f16(float lo, float hi) {
    uint32_t r; asm("cvt.rn.f16x2.f32 %0, %1, %2;" : "=r"(r) : "f"(hi), "f"(lo)); return r;
}
__device__ __forceinline__ void cexp_t(float lr, float turns, float& re, float& im) {
    float m;
    asm("ex2.approx.ftz.f32 %0, %1;" : "=f"(m) : "f"(lr));
    const float a = (turns - rintf(turns)) * 6.283185307179586f;
    re = m * __cosf(a); im = m * __sinf(a);
}
__device__ __forceinline__ void csq(float& re, float& im) { const float r = re * re - im * im; im = 2.f * re * im; re = r; }
__device__ __forceinline__ void kb_state(const float* tp, float gf, uint32_t (&a)[4][2], uint32_t (&b)[5]) {
    const float4 p0 = *reinterpret_cast<const float4*>(tp), p1 = *reinterpret_cast<const float4*>(tp + 4);
    float wr, wi;
    cexp_t(p0.x * gf, p0.y * gf, wr, wi);
    float vr = wr * p1.x - wi * p1.y, vi = wr * p1.y + wi * p1.x;
#pragma unroll
    for (int c = 0; c < 4; c++) {
        a[c][0] = pack_f16(wr, wi); a[c][1] = pack_f16(vr, vi);
        csq(wr, wi);
        if (c < 3) csq(vr, vi);
    }
    b[0] = pack_f16(p0.z * wr - p0.w * wi, -p0.z * wi - p0.w * wr);
    float er = wr * p1.z - wi * p1.w, ei = wr * p1.w + wi * p1.z;
#pragma unroll
    for (int c = 0; c < 4; c++) {
        b[1 + c] = pack_f16(p0.z * er - p0.w * ei, -p0.z * ei - p0.w * er);
        if (c < 3) csq(er, ei);
    }
}
__device__ __forceinline__ uint32_t bf2_mul(uint32_t a, uint32_t b) { uint32_t r; asm("mul.rn.bf16x2 %0, %1, %2;" : "=r"(r) : "r"(a), "r"(b)); return r; }
__device__ __forceinline__ uint32_t bf2_add(uint32_t a, uint32_t b) { uint32_t r; asm("add.rn.bf16x2 %0, %1, %2;" : "=r"(r) : "r"(a), "r"(b)); return r; }
__device__ __forceinline__ uint32_t bf2_sub(uint32_t a, uint32_t b) { uint32_t r; asm("sub.rn.bf16x2 %0, %1, %2;" : "=r"(r) : "r"(a), "r"(b)); return r; }
__device__ __forceinline__ void wait_cnt(const unsigned* p, unsigned target) {
    unsigned it = 0;
    while ((int)(ld_acq(p) - target) < 0 && ++it < SPIN_LIMIT) __nanosleep(64);
}
__device__ __forceinline__ uint32_t gtime32() { uint32_t t; asm volatile("mov.u32 %0, %%globaltimer_lo;" : "=r"(t) :: "memory"); return t; }
__device__ __forceinline__ void gate(uint32_t tick_addr, uint32_t ga = GATE_A, uint32_t gb = GATE_B) {
    uint32_t t1, p;
    asm volatile("ld.volatile.shared.v2.u32 {%0,%1}, [%2];" : "=r"(t1), "=r"(p) : "r"(tick_addr) : "memory");
    uint32_t d = gtime32() - t1;
    if (d < 4u * p) {
        d -= d >= 2u * p ? 2u * p : 0u;
        d -= d >= p ? p : 0u;
        if (d + ga >= p && d + gb < p) {
            const uint32_t t2 = gtime32() + (p - gb - d);
            while ((int)(gtime32() - t2) < 0) {}
        }
    }
}

__device__ __forceinline__ void read_tick(uint32_t tick_addr) {
    const uint2 tk = ld_vol_u2(&g_tick);
    uint32_t p = tk.x - tk.y;
    p = p > GATE_P + 100u ? GATE_P + 100u : p;
    asm volatile("st.volatile.shared.v2.u32 [%0], {%1,%2};" :: "r"(tick_addr), "r"(tk.x), "r"(p) : "memory");
}

__device__ __forceinline__ void s4d_phase(unsigned char* smem_raw, const bf16* __restrict__ x, const bf16* __restrict__ logA,
                                          const bf16* __restrict__ Aim, const bf16* __restrict__ Cre, const bf16* __restrict__ Cim,
                                          const bf16* __restrict__ logdt, const bf16* __restrict__ dskip, const bf16* __restrict__ wslice, unsigned ep, uint32_t tick) {
    const int tid = threadIdx.x, warp = __shfl_sync(0xffffffffu, tid >> 5, 0), lane = tid & 31;
    const int d0 = blockIdx.x * SD_CH;
    float* tab = reinterpret_cast<float*>(smem_raw + SD_CH * SD_U + warp * SD_WSTR);
    const uint32_t wb = smem_u32(tab);
    const int g = lane >> 2, tq = lane & 3;
    uint2 prm[4];
    float ldt;
    auto load_prm = [&](int d) {
        prm[0] = __ldg(reinterpret_cast<const uint2*>(logA + d * NST) + lane); prm[1] = __ldg(reinterpret_cast<const uint2*>(Aim + d * NST) + lane);
        prm[2] = __ldg(reinterpret_cast<const uint2*>(Cre + d * NST) + lane); prm[3] = __ldg(reinterpret_cast<const uint2*>(Cim + d * NST) + lane);
        ldt = __bfloat162float(logdt[d]);
    };
    load_prm(d0 + warp);
    for (int i = lane; i < 2 * SD_CPY / 16; i += 32) reinterpret_cast<uint4*>(tab + SD_TAP / 4)[i] = make_uint4(0u, 0u, 0u, 0u);
    TS3(20);
#pragma unroll 1
    for (int ch = 0; ch < 2; ch++) {
        const int d = d0 + 8 * ch + warp;
        const uint32_t ub = smem_u32(smem_raw) + (8 * ch + warp) * SD_U;
        float k2048 = 0.f, sinv;
        {
            const float dt = bf16r(expf(ldt));
            uint32_t cm = __vmaxu2(__vmaxu2(prm[2].x & 0x7fff7fffu, prm[2].y & 0x7fff7fffu), __vmaxu2(prm[3].x & 0x7fff7fffu, prm[3].y & 0x7fff7fffu));
            cm = __reduce_max_sync(0xffffffffu, max(cm << 16, cm & 0xffff0000u));
            int e = 134 - (int)(__float_as_uint(__uint_as_float(cm) * dt) >> 23);
            e = e > 100 ? 100 : (e < -100 ? -100 : e);
            const float s2 = __uint_as_float((uint32_t)(128 + e) << 23);
            sinv = __uint_as_float((uint32_t)(127 - e) << 23);
#pragma unroll
            for (int j = 0; j < 4; j++) {
                float q[4];
#pragma unroll
                for (int i = 0; i < 4; i++) { const uint32_t w = j < 2 ? prm[i].x : prm[i].y; q[i] = __uint_as_float((j & 1) ? w & 0xffff0000u : w << 16); }
                const float zl = -bf16r(expf(q[0])) * dt * 1.4426950408889634f;
                const float zt = q[1] * dt * 0.15915494309189535f;
                const float cr = s2 * (q[2] * dt), ci = s2 * (q[3] * dt);
                float ar, ai, br, bi, er, ei;
                cexp_t(zl * 8.f, zt * 8.f, ar, ai);
                cexp_t(zl * 128.f, zt * 128.f, br, bi);
                cexp_t(zl * 2048.f, zt * 2048.f, er, ei);
                k2048 += cr * er - ci * ei;
                *reinterpret_cast<float4*>(tab + (lane + 32 * j) * 8) = make_float4(zl, zt, cr, ci);
                *reinterpret_cast<float4*>(tab + (lane + 32 * j) * 8 + 4) = make_float4(ar, ai, br, bi);
            }
#pragma unroll
            for (int o = 16; o; o >>= 1) k2048 += __shfl_xor_sync(0xffffffffu, k2048, o);
        }
        __syncwarp();
        {
            float kc[5][4];
#pragma unroll
            for (int i = 0; i < 5; i++) { kc[i][0] = kc[i][1] = kc[i][2] = kc[i][3] = 0.f; }
            const float gf = (float)g;
#pragma unroll 2
            for (int ks = 0; ks < 16; ks++) {
                uint32_t a0[4][2], a1[4][2], b0[5], b1[5];
                kb_state(tab + (8 * ks + tq) * 8, gf, a0, b0);
                kb_state(tab + (8 * ks + 4 + tq) * 8, gf, a1, b1);
#pragma unroll
                for (int i = 0; i < 5; i++) {
                    const int c = i > 0 ? i - 1 : 0;
                    asm volatile("mma.sync.aligned.m16n8k16.row.col.f32.f16.f16.f32 {%0,%1,%2,%3}, {%4,%5,%6,%7}, {%8,%9}, {%0,%1,%2,%3};"
                                 : "+f"(kc[i][0]), "+f"(kc[i][1]), "+f"(kc[i][2]), "+f"(kc[i][3])
                                 : "r"(a0[c][0]), "r"(a0[c][1]), "r"(a1[c][0]), "r"(a1[c][1]), "r"(b0[i]), "r"(b1[i]));
                }
            }
            const uint32_t tp = wb + SD_TAP;
            const uint32_t a0 = tp + 2 * (O_U + 96 * g - 4 * tq);
            const uint32_t a2 = tp + 2 * (((g & 1) ? O_U + 96 * (2 * (g & 3)) : ((g & 2) ? O_W35 : O_W79 + 1)) - 32 - 8 * tq - (g >> 2));
            const uint32_t a3 = tp + 2 * (((g & 1) ? O_W35 : O_W610 + 1) - 64 - 16 * tq - (g >> 1));
            const uint32_t a4 = tp + 2 * (-128 - 32 * tq - g);
#pragma unroll
            for (int c = 0; c < 4; c++) {
                const int e = (c & 1) * 16 + (c >> 1) * 8;
                const bool first = c == 0 && lane == 0;
                put_tap(a0 - e / 4, kc[0][c] * sinv);
                put_tap(a0 - 32 - e / 4, kc[1][c] * sinv);
                put_tap(first ? tp + 2 * (O_U - 32) : a2 - e / 2, kc[2][c] * sinv);
                put_tap(first ? tp + 2 * (O_W79 - 63) : a3 - e, kc[3][c] * sinv);
                put_tap(first ? tp + 2 * (O_W610 - 127) : a4 + 2 * (O_W511 + 1 - e), kc[4][c] * sinv);
                if ((g & 1) == 0) {
                    put_tap(a4 + 2 * (O_U4 - e), kc[4][c] * sinv);
                    put_tap(first ? tp + 2 * (O_U3 - 128) : a4 + 2 * (O_U4 + 1 - e), kc[4][c] * sinv);
                }
            }
            if (lane == 0) {
                put_tap(tp + 2 * (O_U + 96 - 32), kc[2][0] * sinv);
                put_tap(tp + 2 * (O_U + 192 - 64), kc[3][0] * sinv);
                put_tap(tp + 2 * (O_W511 - 255), k2048 * sinv);
                put_tap(tp + 2 * (O_U4 - 255), k2048 * sinv);
            }
        }
        TS3(21 + 2 * ch);
        if (ch == 0) { if (!STAGGER || warp < 4) named_bar(1, 384); }
        else {
#pragma unroll
            for (int i = 0; i < 4; i++) asm volatile("prefetch.global.L2 [%0];" :: "l"(wslice + (size_t)((tid & 127) + 128 * i) * DM));
        }
        __syncwarp();
        if (tid == 0) TSS(18, 4 * ch);
        const uint32_t sh = wb + 80 + 11 * SD_ROW;
#pragma unroll
        for (int p = 0; p < 8; p++) {
            uint4 v;
            asm volatile("ld.shared.v4.u32 {%0,%1,%2,%3}, [%4];" : "=r"(v.x), "=r"(v.y), "=r"(v.z), "=r"(v.w) : "r"(ub + p * SD_ROW + lane * 16) : "memory");
            uint32_t pv = __shfl_up_sync(0xffffffffu, v.w, 1);
            pv = lane == 0 ? 0u : pv;
            asm volatile("st.shared.v4.u32 [%0], {%1,%2,%3,%4};" :: "r"(sh + (p - 8) * SD_ROW + lane * 16), "r"(__byte_perm(pv, v.x, 0x5432)), "r"(__byte_perm(v.x, v.y, 0x5432)),
                         "r"(__byte_perm(v.y, v.z, 0x5432)), "r"(__byte_perm(v.z, v.w, 0x5432)) : "memory");
            if (p >= 5) asm volatile("st.shared.v4.u32 [%0], {%1,%2,%3,%4};" :: "r"(sh + (p - 16) * SD_ROW + lane * 16), "r"(pv), "r"(v.x), "r"(v.y), "r"(v.z) : "memory");
        }
        __syncwarp();
        if (tid == 0) TSS(18, 4 * ch + 1);
        float acc[16][4];
#pragma unroll
        for (int i = 0; i < 16; i++) { acc[i][0] = acc[i][1] = acc[i][2] = acc[i][3] = 0.f; }
        {
            const uint32_t ka = wb + SD_TAP + ((g & 1) ? 0 : SD_CPY - 2) + 2 * (2 * tq - g);
            uint32_t b[16][2], b2[14][2];
#pragma unroll
            for (int k = 0; k < 16; k++) { b[k][0] = b[k][1] = 0u; if (k < 14) b2[k][0] = b2[k][1] = 0u; }
#pragma unroll 1
            for (int ps = 0; ps < 14; ps++) {
                const uint32_t pw = __shfl_sync(0xffffffffu, SD_PASS[ps], 0), type = pw & 3u, kp = ka + (pw >> 16);
                const int dl = (pw >> 2) & 7, d0 = (pw >> 8) & 15, d1 = (pw >> 12) & 15;
                uint32_t t[2][4];
                tap_tile(t[0], kp - 32 * d0);
                if (type == 0) {
                    const int p = (lane & 7) - dl;
                    const uint32_t ra = (p < 0 ? sh : ub) + p * SD_ROW + (lane >> 3) * 16;
#pragma unroll
                    for (int k = 0; k < 8; k++)
                        asm volatile("ldmatrix.sync.aligned.m8n8.x4.shared.b16 {%0,%1,%2,%3}, [%4];"
                                     : "=r"(b[2 * k][0]), "=r"(b[2 * k][1]), "=r"(b[2 * k + 1][0]), "=r"(b[2 * k + 1][1]) : "r"(ra + k * 64));
                } else if (type == 2) {
                    const int p = (lane & 15) - 11, xo = 2 * tq - g;
                    const uint32_t qa = (p < 0 ? sh : ub) + p * SD_ROW + (lane >> 4) * 16;
                    const int lx = 6 - 5 * dl, hx = 8 - 3 * dl, ly = 2 - 2 * dl, hy = 4 + 2 * dl;
                    const uint32_t sel[4] = {band2(xo, lx, hx), band2(xo, ly, hy), band2(xo + 8, lx, hx), band2(xo + 8, ly, hy)};
#pragma unroll
                    for (int k = 0; k < 14; k++) {
                        uint32_t q[4];
                        ldsm_x4_t(q, qa + k * 32);
#pragma unroll
                        for (int i = 0; i < 2; i++) {
                            float w[4];
                            mma_z(w, sel, q[2 * i], q[2 * i + 1]);
                            b[k][i] = pack_bf16(w[0], w[1]);
                            b2[k][i] = pack_bf16(w[2], w[3]);
                        }
                    }
                } else if (type == 3) {
#pragma unroll
                    for (int k = 0; k < 14; k++) { b[k][0] = b2[k][0]; b[k][1] = b2[k][1]; }
                }
#pragma unroll
                for (int d = 0; d < 16; d += 2) {
                    if (d >= 8 || d >= d0) {
                        tap_tile(t[1], kp - 32 * (d + 1));
#pragma unroll
                        for (int k = 0; k + d < 16; k++) mma_bf16(acc[k + d], t[0], b[k][0], b[k][1]);
                        if ((d == 2 || d == 4 || d == 8) && d == d1) break;
                        if (d < 14) tap_tile(t[0], kp - 32 * (d + 2));
#pragma unroll
                        for (int k = 0; k + d + 1 < 16; k++) mma_bf16(acc[k + d + 1], t[1], b[k][0], b[k][1]);
                    }
                }
            }
        }
        __syncwarp();
        if (tid == 0) TSS(18, 4 * ch + 2);
        load_prm(d0 + 8 + warp);
        if (ch == 0) { if (lane == 0) wait_cnt(&g_gcnt[0], SD_NCTA * ep); __syncwarp(); }
        if (tid == 0) TSS(18, 4 * ch + 3);
        uint4 gv[8];
#pragma unroll
        for (int i = 0; i < 8; i++) gv[i] = __ldcg(reinterpret_cast<const uint4*>(g_gate) + lane + 32 * i);
        const uint32_t dd = __byte_perm(*reinterpret_cast<const unsigned short*>(dskip + d), 0u, 0x1010);
#pragma unroll
        for (int i = 0; i < 8; i++) {
            uint32_t u[4];
            ldsm_x4_t(u, ub + (lane & 7) * SD_ROW + (lane >> 3) * 16 + i * 64);
            asm volatile("stmatrix.sync.aligned.m8n8.x4.shared.b16 [%0], {%1,%2,%3,%4};"
                         :: "r"(wb + (lane + 32 * i) * 16),
                            "r"(bf2_add(pack_bf16(acc[2 * i][0], acc[2 * i][1]), bf2_mul(u[0], dd))), "r"(bf2_add(pack_bf16(acc[2 * i][2], acc[2 * i][3]), bf2_mul(u[1], dd))),
                            "r"(bf2_add(pack_bf16(acc[2 * i + 1][0], acc[2 * i + 1][1]), bf2_mul(u[2], dd))), "r"(bf2_add(pack_bf16(acc[2 * i + 1][2], acc[2 * i + 1][3]), bf2_mul(u[3], dd))) : "memory");
        }
        if (GATE_Y) gate(tick);
        __syncwarp();
#pragma unroll
        for (int i = 0; i < 8; i++) {
            const uint4 y = *reinterpret_cast<const uint4*>(tab + (lane + 32 * i) * 4);
            *reinterpret_cast<uint4*>(g_y + (((lane >> 1) + 16 * i) * DM + d) * 16 + (lane & 1) * 8) =
                make_uint4(bf2_mul(bf2_sub(0x3f803f80u, gv[i].x), y.x), bf2_mul(bf2_sub(0x3f803f80u, gv[i].y), y.y),
                           bf2_mul(bf2_sub(0x3f803f80u, gv[i].z), y.z), bf2_mul(bf2_sub(0x3f803f80u, gv[i].w), y.w));
        }
        __syncwarp();
        TS3(22 + 2 * ch);
    }
}
__device__ __forceinline__ void s4d_stage_u(unsigned char* smem_raw, const bf16* __restrict__ x, int pt) {
    const int p = pt & 7, w0 = pt >> 3;
    const uint4* src = reinterpret_cast<const uint4*>(x + (size_t)(16 * w0 + p) * DM + blockIdx.x * SD_CH);
    uint32_t* dst = reinterpret_cast<uint32_t*>(smem_raw + p * SD_ROW) + w0;
#pragma unroll 1
    for (int b = 0; b < 4; b++) {
        uint4 v[2][2][2];
#pragma unroll
        for (int i = 0; i < 8; i++) v[i >> 2][(i >> 1) & 1][i & 1] = src[((b * 2 + (i >> 2)) * 256 + ((i >> 1) & 1) * 8) * (DM / 8) + (i & 1)];
#pragma unroll
        for (int i = 0; i < 4; i++) {
            const uint32_t* lo = reinterpret_cast<const uint32_t*>(&v[i >> 1][0][i & 1]);
            const uint32_t* hi = reinterpret_cast<const uint32_t*>(&v[i >> 1][1][i & 1]);
#pragma unroll
            for (int c = 0; c < 8; c++) dst[((i & 1) * 8 + c) * (SD_U / 4) + (b * 2 + (i >> 1)) * 16] = __byte_perm(lo[c >> 1], hi[c >> 1], (c & 1) ? 0x7632 : 0x5410);
        }
    }
    asm volatile("bar.arrive 1, 384;" ::: "memory");
}

constexpr int WOC = DM / 3;
constexpr int TBUF = 5 * DH * 16;
constexpr int XBUF = SEG * DM * 2;
constexpr int SM_BAR = 0;
constexpr int B_SB = 0, B_VX = 16, B_XT = 32, B_W = 64, B_E = 136;
constexpr int SM_SC = 256;
constexpr int SM_F = SM_SC + 1280;
constexpr int SM_VM = SM_F + 2048;
constexpr int SM_S = SM_VM + 2048;
constexpr int SM_O = SM_S + 2560;
constexpr int SM_M = SM_O + 2048;
constexpr int SM_WS = 19456;
constexpr int SM_T = SM_WS + 32768;
constexpr int SM_VX = SM_T + 4 * TBUF;
constexpr int SM_X = SM_VX + 2 * 8192;
constexpr int SM_X01 = SM_WS + DM * DH * 2;
__host__ __device__ constexpr int x01_off(int b) { return b == 2 ? 2048 : SM_X01 + (b < 2 ? b + 6 : b - 3) * 8192; }
constexpr int SM_E = SM_WS + 6 * 16384;
constexpr int CH_SMEM = SM_X01 + 8 * 8192;
static_assert(SM_M + DM * 16 <= SM_WS && SM_X + 3 * XBUF <= CH_SMEM && CH_SMEM <= 232448 && SM_X % 1024 == 0 && SM_X01 % 1024 == 0 && SM_M >= 10240 && SM_F <= 2048, "smem");
__device__ __forceinline__ uint32_t clock32() { uint32_t t; asm volatile("mov.u32 %0, %%clock;" : "=r"(t) :: "memory"); return t; }

__device__ __forceinline__ uint32_t mapa(uint32_t a, uint32_t rank) {
    uint32_t r; asm volatile("mapa.shared::cluster.u32 %0, %1, %2;" : "=r"(r) : "r"(a), "r"(rank)); return r;
}
__device__ __forceinline__ void st_async32(uint32_t addr, uint32_t v, uint32_t mbar) {
    asm volatile("st.async.weak.shared::cluster.mbarrier::complete_tx::bytes.b32 [%0], %1, [%2];" :: "r"(addr), "r"(v), "r"(mbar) : "memory");
}
__device__ __forceinline__ void mbar_init(uint32_t bar, uint32_t cnt) {
    asm volatile("mbarrier.init.shared::cta.b64 [%0], %1;" :: "r"(bar), "r"(cnt) : "memory");
}
__device__ __forceinline__ void mbar_expect(uint32_t bar, uint32_t bytes) {
    asm volatile("mbarrier.arrive.expect_tx.shared::cta.b64 _, [%0], %1;" :: "r"(bar), "r"(bytes) : "memory");
}
__device__ __forceinline__ void mbar_wait(uint32_t bar, uint32_t parity) {
    unsigned it = 0;
    while (true) {
        uint32_t ok;
        asm volatile("{\n.reg .pred p;\nmbarrier.try_wait.parity.shared::cta.b64 p, [%1], %2;\nselp.u32 %0, 1, 0, p;\n}"
                     : "=r"(ok) : "r"(bar), "r"(parity) : "memory");
        if (ok || ++it >= SPIN_LIMIT) break;
    }
}
__device__ __forceinline__ void mbar_wait_long(uint32_t bar, uint32_t parity) {
    unsigned it = 0;
    while (true) {
        uint32_t ok;
        asm volatile("{\n.reg .pred p;\nmbarrier.try_wait.parity.shared::cta.b64 p, [%1], %2, %3;\nselp.u32 %0, 1, 0, p;\n}"
                     : "=r"(ok) : "r"(bar), "r"(parity), "r"(20000u) : "memory");
        if (ok || ++it >= SPIN_LIMIT) break;
    }
}
__device__ __forceinline__ bool mbar_test(uint32_t bar, uint32_t parity) {
    uint32_t ok;
    asm volatile("{\n.reg .pred p;\nmbarrier.test_wait.parity.shared::cta.b64 p, [%1], %2;\nselp.u32 %0, 1, 0, p;\n}" : "=r"(ok) : "r"(bar), "r"(parity) : "memory");
    return ok != 0u;
}
__device__ __forceinline__ uint64_t policy_evict_first() {
    uint64_t pol; asm volatile("createpolicy.fractional.L2::evict_first.b64 %0, 1.0;" : "=l"(pol)); return pol;
}
__device__ __forceinline__ void cluster_sync_all() {
    asm volatile("barrier.cluster.arrive.release.aligned;\nbarrier.cluster.wait.acquire.aligned;" ::: "memory");
}
__device__ __forceinline__ uint4 ld_vol_u4(const uint4* p) {
    uint4 v; asm volatile(LDV4 : "=r"(v.x), "=r"(v.y), "=r"(v.z), "=r"(v.w) : "l"(p) : "memory"); return v;
}
__device__ __forceinline__ void ld_vol_u4_p(uint4& v, const uint4* p, uint32_t pred) {
    asm volatile("{\n.reg .pred p;\nsetp.ne.u32 p, %5, 0;\n@p " LDV4 "\n}"
                 : "+r"(v.x), "+r"(v.y), "+r"(v.z), "+r"(v.w) : "l"(p), "r"(pred) : "memory");
}
__device__ __forceinline__ void st_vol_u4(uint4* p, uint4 v) {
    asm volatile(STV4 :: "l"(p), "r"(v.x), "r"(v.y), "r"(v.z), "r"(v.w) : "memory");
}
__device__ __forceinline__ void mma_bf16_r(float (&d)[4], uint32_t a0, uint32_t a1, uint32_t a2, uint32_t a3, uint32_t b0, uint32_t b1) {
    asm volatile("mma.sync.aligned.m16n8k16.row.col.f32.bf16.bf16.f32 {%0,%1,%2,%3}, {%4,%5,%6,%7}, {%8,%9}, {%0,%1,%2,%3};"
                 : "+f"(d[0]), "+f"(d[1]), "+f"(d[2]), "+f"(d[3])
                 : "r"(a0), "r"(a1), "r"(a2), "r"(a3), "r"(b0), "r"(b1));
}

__device__ __forceinline__ uint64_t smem_desc(uint32_t addr, uint32_t lbo, uint32_t sbo) {
    return (uint64_t)((addr & 0x3FFFF) >> 4) | ((uint64_t)(lbo >> 4) << 16) | ((uint64_t)(sbo >> 4) << 32);
}
__device__ __forceinline__ void wg_fence() { asm volatile("wgmma.fence.sync.aligned;" ::: "memory"); }
__device__ __forceinline__ void wg_commit() { asm volatile("wgmma.commit_group.sync.aligned;" ::: "memory"); }
__device__ __forceinline__ void wg_wait0() { asm volatile("wgmma.wait_group.sync.aligned 0;" ::: "memory"); }
__device__ __forceinline__ void fence_async() { asm volatile("fence.proxy.async.shared::cta;" ::: "memory"); }
__device__ __forceinline__ void wgmma_n32(float (&d)[16], const uint32_t (&a)[4], uint64_t bdesc, int scale_d) {
    asm volatile("{\n.reg .pred p;\nsetp.ne.b32 p, %21, 0;\n"
                 "wgmma.mma_async.sync.aligned.m64n32k16.f32.bf16.bf16 {%0,%1,%2,%3,%4,%5,%6,%7,%8,%9,%10,%11,%12,%13,%14,%15}, {%16,%17,%18,%19}, %20, p, 1, 1, 0;\n}"
                 : "+f"(d[0]), "+f"(d[1]), "+f"(d[2]), "+f"(d[3]), "+f"(d[4]), "+f"(d[5]), "+f"(d[6]), "+f"(d[7]),
                   "+f"(d[8]), "+f"(d[9]), "+f"(d[10]), "+f"(d[11]), "+f"(d[12]), "+f"(d[13]), "+f"(d[14]), "+f"(d[15])
                 : "r"(a[0]), "r"(a[1]), "r"(a[2]), "r"(a[3]), "l"(bdesc), "r"(scale_d));
}

__device__ __forceinline__ void wgmma_n32_z(float (&d)[16], const uint32_t (&a)[4], uint64_t bdesc) {
    asm volatile("{\n.reg .pred p;\nsetp.ne.b32 p, 0, 0;\n"
                 "wgmma.mma_async.sync.aligned.m64n32k16.f32.bf16.bf16 {%0,%1,%2,%3,%4,%5,%6,%7,%8,%9,%10,%11,%12,%13,%14,%15}, {%16,%17,%18,%19}, %20, p, 1, 1, 0;\n}"
                 : "=f"(d[0]), "=f"(d[1]), "=f"(d[2]), "=f"(d[3]), "=f"(d[4]), "=f"(d[5]), "=f"(d[6]), "=f"(d[7]),
                   "=f"(d[8]), "=f"(d[9]), "=f"(d[10]), "=f"(d[11]), "=f"(d[12]), "=f"(d[13]), "=f"(d[14]), "=f"(d[15])
                 : "r"(a[0]), "r"(a[1]), "r"(a[2]), "r"(a[3]), "l"(bdesc));
}
__device__ __forceinline__ void wgmma_n32_ss(float (&d)[16], uint64_t adesc, uint64_t bdesc, int scale_d) {
    asm volatile("{\n.reg .pred p;\nsetp.ne.b32 p, %18, 0;\n"
                 "wgmma.mma_async.sync.aligned.m64n32k16.f32.bf16.bf16 {%0,%1,%2,%3,%4,%5,%6,%7,%8,%9,%10,%11,%12,%13,%14,%15}, %16, %17, p, 1, 1, 1, 0;\n}"
                 : "+f"(d[0]), "+f"(d[1]), "+f"(d[2]), "+f"(d[3]), "+f"(d[4]), "+f"(d[5]), "+f"(d[6]), "+f"(d[7]),
                   "+f"(d[8]), "+f"(d[9]), "+f"(d[10]), "+f"(d[11]), "+f"(d[12]), "+f"(d[13]), "+f"(d[14]), "+f"(d[15])
                 : "l"(adesc), "l"(bdesc), "r"(scale_d));
}

__device__ __forceinline__ void wgmma_n64_ss(float (&d)[32], uint64_t adesc, uint64_t bdesc) {
    asm volatile("{\n.reg .pred p;\nsetp.eq.b32 p, 0, 0;\n"
                 "wgmma.mma_async.sync.aligned.m64n64k16.f32.bf16.bf16 {%0,%1,%2,%3,%4,%5,%6,%7,%8,%9,%10,%11,%12,%13,%14,%15,%16,%17,%18,%19,%20,%21,%22,%23,"
                 "%24,%25,%26,%27,%28,%29,%30,%31}, %32, %33, p, 1, 1, 1, 0;\n}"
                 : "+f"(d[0]), "+f"(d[1]), "+f"(d[2]), "+f"(d[3]), "+f"(d[4]), "+f"(d[5]), "+f"(d[6]), "+f"(d[7]),
                   "+f"(d[8]), "+f"(d[9]), "+f"(d[10]), "+f"(d[11]), "+f"(d[12]), "+f"(d[13]), "+f"(d[14]), "+f"(d[15]),
                   "+f"(d[16]), "+f"(d[17]), "+f"(d[18]), "+f"(d[19]), "+f"(d[20]), "+f"(d[21]), "+f"(d[22]), "+f"(d[23]),
                   "+f"(d[24]), "+f"(d[25]), "+f"(d[26]), "+f"(d[27]), "+f"(d[28]), "+f"(d[29]), "+f"(d[30]), "+f"(d[31])
                 : "l"(adesc), "l"(bdesc));
}
__device__ __forceinline__ void tma_2d(uint32_t dst, const CUtensorMap* tm, int c0, int c1, uint32_t mbar) {
    asm volatile("cp.async.bulk.tensor.2d.shared::cluster.global.tile.mbarrier::complete_tx::bytes [%0], [%1, {%2, %3}], [%4];"
                 :: "r"(dst), "l"(tm), "r"(c0), "r"(c1), "r"(mbar) : "memory");
}

__device__ __forceinline__ void bulk_g2s(uint32_t dst, const void* src, uint32_t bytes, uint32_t mbar) {
    asm volatile("cp.async.bulk.shared::cluster.global.mbarrier::complete_tx::bytes [%0], [%1], %2, [%3];"
                 :: "r"(dst), "l"(src), "r"(bytes), "r"(mbar) : "memory");
}
__device__ __forceinline__ void bulk_g2s_h(uint32_t dst, const void* src, uint32_t bytes, uint32_t mbar, uint64_t pol) {
    asm volatile("cp.async.bulk.shared::cluster.global.mbarrier::complete_tx::bytes.L2::cache_hint [%0], [%1], %2, [%3], %4;"
                 :: "r"(dst), "l"(src), "r"(bytes), "r"(mbar), "l"(pol) : "memory");
}
__device__ __forceinline__ void tma_x(uint32_t dst, const CUtensorMap* tm, int seg, int part, uint32_t mbar) {
    asm volatile("cp.async.bulk.tensor.3d.shared::cluster.global.tile.mbarrier::complete_tx::bytes [%0], [%1, {%2, %3, %4}], [%5];"
                 :: "r"(dst + part * 12288), "l"(tm), "r"(0), "r"(seg * SEG), "r"(part * 3), "r"(mbar) : "memory");
}
__device__ __forceinline__ void tma_x_mc(uint32_t dst, const CUtensorMap* tm, int seg, int part, uint32_t mbar) {
    asm volatile("cp.async.bulk.tensor.3d.shared::cluster.global.tile.mbarrier::complete_tx::bytes.multicast::cluster [%0], [%1, {%2, %3, %4}], [%5], %6;"
                 :: "r"(dst + part * 12288), "l"(tm), "r"(0), "r"(seg * SEG), "r"(part * 3), "r"(mbar), "h"((unsigned short)7) : "memory");
}
__device__ __forceinline__ void bulk_s2s(uint32_t dst, uint32_t src, uint32_t bytes, uint32_t mbar) {
    asm volatile("cp.async.bulk.shared::cluster.shared::cta.mbarrier::complete_tx::bytes [%0], [%1], %2, [%3];"
                 :: "r"(dst), "r"(src), "r"(bytes), "r"(mbar) : "memory");
}
__device__ __forceinline__ void wgmma_n40_ss(float (&d)[20], uint64_t adesc, uint64_t bdesc, int scale_d) {
    asm volatile("{\n.reg .pred p;\nsetp.ne.b32 p, %22, 0;\n"
                 "wgmma.mma_async.sync.aligned.m64n40k16.f32.bf16.bf16 {%0,%1,%2,%3,%4,%5,%6,%7,%8,%9,%10,%11,%12,%13,%14,%15,%16,%17,%18,%19}, %20, %21, p, 1, 1, 1, 1;\n}"
                 : "+f"(d[0]), "+f"(d[1]), "+f"(d[2]), "+f"(d[3]), "+f"(d[4]), "+f"(d[5]), "+f"(d[6]), "+f"(d[7]),
                   "+f"(d[8]), "+f"(d[9]), "+f"(d[10]), "+f"(d[11]), "+f"(d[12]), "+f"(d[13]), "+f"(d[14]), "+f"(d[15]),
                   "+f"(d[16]), "+f"(d[17]), "+f"(d[18]), "+f"(d[19])
                 : "l"(adesc), "l"(bdesc), "r"(scale_d));
}
__device__ __forceinline__ void wgmma_n64_z(float (&d)[32], const uint32_t (&a)[4], uint64_t bdesc) {
    asm volatile("{\n.reg .pred p;\nsetp.ne.b32 p, 0, 0;\n"
                 "wgmma.mma_async.sync.aligned.m64n64k16.f32.bf16.bf16 {%0,%1,%2,%3,%4,%5,%6,%7,%8,%9,%10,%11,%12,%13,%14,%15,%16,%17,%18,%19,%20,%21,%22,%23,%24,%25,%26,%27,%28,%29,%30,%31}, {%32,%33,%34,%35}, %36, p, 1, 1, 0;\n}"
                 : "=f"(d[0]), "=f"(d[1]), "=f"(d[2]), "=f"(d[3]), "=f"(d[4]), "=f"(d[5]), "=f"(d[6]), "=f"(d[7]),
                   "=f"(d[8]), "=f"(d[9]), "=f"(d[10]), "=f"(d[11]), "=f"(d[12]), "=f"(d[13]), "=f"(d[14]), "=f"(d[15]),
                   "=f"(d[16]), "=f"(d[17]), "=f"(d[18]), "=f"(d[19]), "=f"(d[20]), "=f"(d[21]), "=f"(d[22]), "=f"(d[23]),
                   "=f"(d[24]), "=f"(d[25]), "=f"(d[26]), "=f"(d[27]), "=f"(d[28]), "=f"(d[29]), "=f"(d[30]), "=f"(d[31])
                 : "r"(a[0]), "r"(a[1]), "r"(a[2]), "r"(a[3]), "l"(bdesc));
}
__device__ __forceinline__ void wgmma_n64(float (&d)[32], const uint32_t (&a)[4], uint64_t bdesc, int scale_d) {
    asm volatile("{\n.reg .pred p;\nsetp.ne.b32 p, %37, 0;\n"
                 "wgmma.mma_async.sync.aligned.m64n64k16.f32.bf16.bf16 {%0,%1,%2,%3,%4,%5,%6,%7,%8,%9,%10,%11,%12,%13,%14,%15,%16,%17,%18,%19,%20,%21,%22,%23,%24,%25,%26,%27,%28,%29,%30,%31}, {%32,%33,%34,%35}, %36, p, 1, 1, 0;\n}"
                 : "+f"(d[0]), "+f"(d[1]), "+f"(d[2]), "+f"(d[3]), "+f"(d[4]), "+f"(d[5]), "+f"(d[6]), "+f"(d[7]),
                   "+f"(d[8]), "+f"(d[9]), "+f"(d[10]), "+f"(d[11]), "+f"(d[12]), "+f"(d[13]), "+f"(d[14]), "+f"(d[15]),
                   "+f"(d[16]), "+f"(d[17]), "+f"(d[18]), "+f"(d[19]), "+f"(d[20]), "+f"(d[21]), "+f"(d[22]), "+f"(d[23]),
                   "+f"(d[24]), "+f"(d[25]), "+f"(d[26]), "+f"(d[27]), "+f"(d[28]), "+f"(d[29]), "+f"(d[30]), "+f"(d[31])
                 : "r"(a[0]), "r"(a[1]), "r"(a[2]), "r"(a[3]), "l"(bdesc), "r"(scale_d));
}

constexpr int SB_FULL = 0, SB_EMPTY = 64, SB_QKF = 128, SB_VF = 144, SB_QKE = 160, SB_VE = 176, SB_OF = 192, SB_WO = 208, SB_TICK = 216, SB_SEEN = 224, SB_FI = 232, SB_REQ = 240;
constexpr int AT_0 = 256, AT_ST = 10240 + 2 * 9216;
constexpr int FS_A = 58368;
constexpr int FS_P = FS_A + 131072;
constexpr int FS_I = FS_P + 16384;
constexpr int FS_O = FS_I + 12288;
constexpr int FS_Z = FS_O + 12288, FS_G = AT_0 + 2 * AT_ST;
constexpr int SIDE_SMEM = FS_Z + 2048;
static_assert(SIDE_SMEM <= 232448 && FS_G + 128 <= FS_A && FS_A + SD_SMEM <= SIDE_SMEM, "smem");

__device__ __forceinline__ void wg_wait1() { asm volatile("wgmma.wait_group.sync.aligned 1;" ::: "memory"); }
__device__ __forceinline__ void mbar_arrive(uint32_t bar) { asm volatile("mbarrier.arrive.shared::cta.b64 _, [%0];" :: "r"(bar) : "memory"); }
__device__ __forceinline__ void wait_cnt_rlx(const unsigned* p, unsigned target, bool urgent) {
    unsigned it = 0, v;
    while (true) {
        asm volatile("ld.relaxed.gpu.global.u32 %0, [%1];" : "=r"(v) : "l"(p) : "memory");
        if ((int)(v - target) >= 0 || ++it >= SPIN_LIMIT) break;
        if (!urgent) __nanosleep(RLX_SLEEP);
    }
}

__device__ __forceinline__ float xrow_softmax(float (&sc)[20], uint32_t (&p)[5], int wq, int lane) {
    constexpr float EC = (float)(1.4426950408889634 * 0.08838834764831845);
    const int lim = 8 * wq + (lane >> 2) - 2 * (lane & 3);
    float mx = fmaxf(sc[0], sc[1]);
#pragma unroll
    for (int j = 1; j < 5; j++) {
        sc[4 * j] = 8 * j - 8 > lim ? -INFINITY : sc[4 * j];
        sc[4 * j + 1] = 8 * j - 7 > lim ? -INFINITY : sc[4 * j + 1];
    }
    mx = fmaxf(fmaxf(mx, fmaxf(fmaxf(sc[4], sc[5]), fmaxf(sc[8], sc[9]))), fmaxf(fmaxf(sc[12], sc[13]), fmaxf(sc[16], sc[17])));
    {
        const float m1 = __shfl_xor_sync(0xffffffffu, mx, 1), m2 = __shfl_xor_sync(0xffffffffu, mx, 2), m3 = __shfl_xor_sync(0xffffffffu, mx, 3);
        mx = fmaxf(fmaxf(mx, m1), fmaxf(m2, m3)) * EC;
    }
    float sum = 0.f;
#pragma unroll
    for (int j = 0; j < 5; j++) {
        float e0, e1;
        asm("ex2.approx.ftz.f32 %0, %1;" : "=f"(e0) : "f"(fmaf(sc[4 * j], EC, -mx)));
        asm("ex2.approx.ftz.f32 %0, %1;" : "=f"(e1) : "f"(fmaf(sc[4 * j + 1], EC, -mx)));
        p[j] = pack_bf16(e0, e1);
        sum += e0 + e1;
    }
    return sum;
}
__device__ __forceinline__ float xrow_inv(float sum) {
    sum += __shfl_xor_sync(0xffffffffu, sum, 1);
    sum += __shfl_xor_sync(0xffffffffu, sum, 2);
    float r;
    asm("rcp.approx.ftz.f32 %0, %1;" : "=f"(r) : "f"(sum));
    return r;
}

__device__ __forceinline__ void stsm_x4(uint32_t addr, uint32_t r0, uint32_t r1, uint32_t r2, uint32_t r3) {
    asm volatile("stmatrix.sync.aligned.m8n8.x4.shared.b16 [%0], {%1,%2,%3,%4};" :: "r"(addr), "r"(r0), "r"(r1), "r"(r2), "r"(r3) : "memory");
}
__device__ __forceinline__ void xrow_pv(uint32_t (&ob)[16], const uint32_t (&p)[5], float psum, uint32_t vt) {
    float o[32];
    const uint64_t dv = smem_desc(vt, 2048, 128);
    uint32_t pa[6][4];
#pragma unroll
    for (int i = 0; i < 6; i++) {
        const int ks = i >> 1, hf = i & 1;
        pa[i][hf] = p[2 * ks]; pa[i][hf ^ 1] = 0u;
        pa[i][2 + hf] = ks < 2 ? p[ks < 2 ? 2 * ks + 1 : 0] : 0u; pa[i][3 - hf] = 0u;
    }
    wg_fence();
#pragma unroll
    for (int i = 0; i < 6; i++) { if (i == 0) wgmma_n64_z(o, pa[0], dv); else wgmma_n64(o, pa[i], dv + (uint64_t)((i & 1) * 64 + (i >> 1) * 256), 1); }
    wg_commit();
    const float inv = xrow_inv(psum);
    wg_wait0();
#pragma unroll
    for (int i = 0; i < 8; i++) { ob[i] = pack_bf16(o[4 * i] * inv, o[4 * i + 1] * inv); ob[8 + i] = pack_bf16(o[4 * i + 2] * inv, o[4 * i + 3] * inv); }
}
__device__ __forceinline__ uint32_t h2_to_bf2(uint32_t h) {
    uint32_t r;
    asm("{\n.reg .f16 l, h;\n.reg .f32 a, b;\nmov.b32 {l, h}, %1;\ncvt.f32.f16 a, l;\ncvt.f32.f16 b, h;\ncvt.rn.bf16x2.f32 %0, b, a;\n}" : "=r"(r) : "r"(h));
    return r;
}
__device__ __forceinline__ uint32_t max_abs2(uint32_t a, uint32_t b) { uint32_t r; asm("max.NaN.xorsign.abs.bf16x2 %0, %1, %2;" : "=r"(r) : "r"(a), "r"(b)); return r; }
__device__ __forceinline__ uint32_t movm(uint32_t v) {
    uint32_t r; asm volatile("movmatrix.sync.aligned.m8n8.trans.b16 %0, %1;" : "=r"(r) : "r"(v)); return r;
}
__device__ __forceinline__ void bar_arrive(int id, int n) { asm volatile("bar.arrive %0, %1;" :: "r"(id), "r"(n) : "memory"); }
__device__ __forceinline__ void lds64(uint32_t& a, uint32_t& b, uint32_t addr) {
    asm volatile("ld.shared.v2.u32 {%0,%1}, [%2];" : "=r"(a), "=r"(b) : "r"(addr) : "memory");
}
__device__ __forceinline__ void lds64f(float& a, float& b, uint32_t addr) {
    asm volatile("ld.shared.v2.f32 {%0,%1}, [%2];" : "=f"(a), "=f"(b) : "r"(addr) : "memory");
}
__device__ __forceinline__ void st_async64(uint32_t addr, uint32_t a, uint32_t b, uint32_t mbar) {
    asm volatile("st.async.weak.shared::cluster.mbarrier::complete_tx::bytes.v2.b32 [%0], {%1,%2}, [%3];" :: "r"(addr), "r"(a), "r"(b), "r"(mbar) : "memory");
}
__device__ __forceinline__ void mma_z(float (&d)[4], const uint32_t (&a)[4], uint32_t b0, uint32_t b1) {
    asm volatile("mma.sync.aligned.m16n8k16.row.col.f32.bf16.bf16.f32 {%0,%1,%2,%3}, {%4,%5,%6,%7}, {%8,%9}, {%10,%10,%10,%10};"
                 : "=f"(d[0]), "=f"(d[1]), "=f"(d[2]), "=f"(d[3])
                 : "r"(a[0]), "r"(a[1]), "r"(a[2]), "r"(a[3]), "r"(b0), "r"(b1), "f"(0.f));
}
__device__ __forceinline__ void mma_k8(float (&d)[4], uint32_t a0, uint32_t a1, uint32_t b) {
    asm volatile("mma.sync.aligned.m16n8k8.row.col.f32.bf16.bf16.f32 {%0,%1,%2,%3}, {%4,%5}, {%6}, {%0,%1,%2,%3};"
                 : "+f"(d[0]), "+f"(d[1]), "+f"(d[2]), "+f"(d[3]) : "r"(a0), "r"(a1), "r"(b));
}
__global__ void __launch_bounds__(512, 1) k_side(const __grid_constant__ CUtensorMap tmo, const bf16* __restrict__ x, const bf16* __restrict__ logA, const bf16* __restrict__ Aim,
                                                 const bf16* __restrict__ Cre, const bf16* __restrict__ Cim, const bf16* __restrict__ logdt,
                                                 const bf16* __restrict__ Wo, const bf16* __restrict__ dskip, const bf16* __restrict__ gw,
                                                 bf16* __restrict__ out) {
    extern __shared__ __align__(1024) unsigned char smem_raw[];
    const uint32_t sbase = smem_u32(smem_raw);
    const int tid = threadIdx.x, warp = __shfl_sync(0xffffffffu, tid >> 5, 0), lane = tid & 31, cta = blockIdx.x;
    const int cb = cta >> 2, kq = cta & 3;
    if (tid == 0) {
        for (int i = 0; i < 8; i++) { mbar_init(sbase + SB_FULL + 8 * i, 1); mbar_init(sbase + SB_EMPTY + 8 * i, 4); }
        for (int i = 0; i < 2; i++) {
            mbar_init(sbase + SB_QKF + 8 * i, 1); mbar_init(sbase + SB_VF + 8 * i, 1); mbar_init(sbase + SB_QKE + 8 * i, 4);
            mbar_init(sbase + SB_VE + 8 * i, 1); mbar_init(sbase + SB_OF + 8 * i, 4);
        }
        mbar_init(sbase + SB_WO, 1);
        mbar_init(sbase + SB_FI, 1);
        mbar_init(sbase + SB_REQ, 4);
        *reinterpret_cast<uint2*>(smem_raw + SB_TICK) = make_uint2(0u, 0u);
        *reinterpret_cast<uint32_t*>(smem_raw + SB_SEEN) = 0u;
        asm volatile("fence.mbarrier_init.release.cluster;" ::: "memory");
    }
    TS3(0);
    unsigned ep;
    asm volatile("ld.volatile.global.u32 %0, [%1];" : "=r"(ep) : "l"(&g_epoch) : "memory");
    ep += 1u;
    asm volatile("fence.proxy.async;" ::: "memory");
    __syncthreads();
    if (warp >= 12) {
      asm volatile("setmaxnreg.dec.sync.aligned.u32 40;");
      {
        uint32_t gwv[9];
#pragma unroll
        for (int i = 0; i < 9; i++) gwv[i] = reinterpret_cast<const uint32_t*>(gw)[lane + 32 * i];
#pragma unroll 1
        for (int i = 0; i < 8; i++) {
            uint32_t xv[2][9];
            float sm[2];
#pragma unroll
            for (int j = 0; j < 2; j++) {
                const int t = min(cta * 57 + 8 * i + 4 * j + warp - 12, S_LEN - 1);
#pragma unroll
                for (int k = 0; k < 9; k++) xv[j][k] = reinterpret_cast<const uint32_t*>(x + t * DM)[lane + 32 * k];
            }
#pragma unroll
            for (int j = 0; j < 2; j++) {
                sm[j] = 0.f;
#pragma unroll
                for (int k = 0; k < 9; k++) {
                    const uint32_t pr = bf2_mul(xv[j][k], gwv[k]);
                    sm[j] += __uint_as_float(pr << 16) + __uint_as_float(pr & 0xffff0000u);
                }
            }
            float v = (lane < 16 ? sm[0] : sm[1]) + __shfl_xor_sync(0xffffffffu, lane < 16 ? sm[1] : sm[0], 16);
#pragma unroll
            for (int o = 8; o; o >>= 1) v += __shfl_xor_sync(0xffffffffu, v, o);
            const float gv = 1.f / (1.f + expf(-bf16r(v)));
            const int tt = 8 * i + 4 * (lane >> 4) + warp - 12;
            if ((lane & 15) == 0 && tt < 57 && cta * 57 + tt < S_LEN) g_gate[cta * 57 + tt] = __float2bfloat16_rn(gv);
        }
        named_bar(2, 128);
        if (tid == 480) {
            __threadfence();
            asm volatile("red.relaxed.gpu.global.add.u32 [%0], 1;" :: "l"(&g_gcnt[0]) : "memory");
        }
        __syncwarp();
      }
      if (warp == 12 || warp == 15) {
        named_bar(3, 320);
        if (tid == 384) {
            fence_async();
            mbar_expect(sbase + SB_WO, 131072);
#pragma unroll 1
            for (int i = 0; i < 8; i++) {
                gate(sbase + SB_TICK);
                tma_2d(sbase + FS_A + i * 16384, &tmo, cb * 64, kq * 1024 + i * 128, sbase + SB_WO);
                __nanosleep(150);
            }
            TSS(17, 2);
        }
        if (tid == 480) {
            __threadfence();
            asm volatile("red.relaxed.gpu.global.add.u32 [%0], 1;" :: "l"(&g_gcnt[32]) : "memory");
            TSS(17, 3);
        }
        __syncwarp();
        named_bar(7, 320);
        if (lane == 0) {
            const int pi = warp == 12 ? 0 : 1, kb = 2 * kq + pi;
            fence_async();
            for (int pr = 0; pr < NSEG / 2; pr++) {
                const bool gon = pr < NSEG / 2 - UNGATE_G;
                wait_cnt_rlx(&g_prog[pr * 8 + kb], 8u * ep, pr >= NSEG / 2 - 2);
                if (pi == 0) asm volatile("st.volatile.shared.u32 [%0], %1;" :: "r"(sbase + SB_SEEN), "r"(pr + 1) : "memory");
                if (pr >= 30 && pi == 0) TSS(4 + pr - 30, 0);
                if (pr == 31) TS3P(26);
                if (pr == 30) TS3P(1);
#pragma unroll
                for (int j = 0; j < 4; j++) {
                    const int st = 4 * pi + j;
                    mbar_wait_long(sbase + SB_EMPTY + 8 * st, ((uint32_t)pr & 1u) ^ 1u);
                    mbar_expect(sbase + SB_FULL + 8 * st, X_OXSZ);
                    if (gon) gate(sbase + SB_TICK);
                    bulk_g2s(sbase + FS_A + st * 16384, g_ox + ((size_t)(pr * NH + 4 * kb + j)) * 8192, X_OXSZ, sbase + SB_FULL + 8 * st);
                }
            }
        }
        __syncwarp();
      } else if (warp == 13) {
        if (lane == 0) {
            const uint64_t pol = policy_evict_first();
            bool next_ok = false;
            for (int seg = 0; seg < NATT; seg++) {
                const uint32_t st = seg & 1, ph = (uint32_t)(seg >> 1) & 1u, ab = sbase + AT_0 + st * AT_ST;
                if (!next_ok) {
                    const unsigned* fp = &g_flag[(cta & (NH - 1)) * NSEG + seg];
                    unsigned it = 0, v0, v1;
                    while (true) {
                        asm volatile("ld.relaxed.gpu.global.u32 %0, [%1];" : "=r"(v0) : "l"(fp) : "memory");
                        asm volatile("ld.relaxed.gpu.global.u32 %0, [%1+4];" : "=r"(v1) : "l"(fp) : "memory");
                        read_tick(sbase + SB_TICK);
                        if ((int)(v0 - 3u * ep) >= 0 || ++it >= SPIN_LIMIT) break;
                        if (seg < NSEG - UNGATE || cta >= NH) { __nanosleep(RLX_SLEEP); if (GATE_POLL) gate(sbase + SB_TICK, GP_A, GP_B); }
                    }
                    next_ok = (int)(v1 - 3u * ep) >= 0;
                } else next_ok = false;
                if (cta < NH) {
                    TSA(seg, 0);
                    mbar_wait_long(sbase + SB_QKE + 8 * st, ph ^ 1u);
                    TSA(seg, 1);
                    mbar_expect(sbase + SB_QKF + 8 * st, 2 * 9216);
                    if (seg < NSEG - UNGATE) gate(sbase + SB_TICK, GL_A, GL_B);
                    TSA(seg, 2);
                    bulk_g2s_h(ab + 10240, &g_qkv[seg][cta][0][1024], 9216, sbase + SB_QKF + 8 * st, pol);
                    bulk_g2s_h(ab + 10240 + 9216, &g_qkv[seg][cta][1][1024], 9216, sbase + SB_QKF + 8 * st, pol);
                    mbar_wait_long(sbase + SB_VE + 8 * st, ph ^ 1u);
                    mbar_expect(sbase + SB_VF + 8 * st, 10240);
                    if (seg < NSEG - UNGATE) gate(sbase + SB_TICK, GL_A, GL_B);
                    TSA(seg, 3);
                    bulk_g2s_h(ab, &g_qkv[seg][cta][2][0], 10240, sbase + SB_VF + 8 * st, pol);
                }
            }
        }
        __syncwarp();
      } else if (warp == 14) {
        if (lane == 0) {
            int seg = cta < NH ? 0 : NATT, p = 0;
            unsigned it = 0;
            while ((seg < NATT || p < NSEG / 2 - 1) && ++it < 16 * SPIN_LIMIT) {
                if (p < NSEG / 2 - 1 && mbar_test(sbase + SB_REQ, (uint32_t)p & 1u)) {
                    if (p == 0) { wait_cnt(&g_gcnt[32], SD_NCTA * ep); asm volatile("fence.proxy.async;" ::: "memory"); }
                    mbar_expect(sbase + SB_FI, (p < NSEG / 2 - 2 ? 12288 : 2048 + 32) + 2048 + 32);
                    if (GATE_F && p < NSEG / 2 - UNGATE_G - 1) gate(sbase + SB_TICK);
                    if (p < NSEG / 2 - 2) bulk_g2s(sbase + FS_I, &g_fp[p & 7][cta][0][0], 12288, sbase + SB_FI);
                    else {
                        bulk_g2s(sbase + FS_I, g_y + ((p * 4 + 4 + kq) * DM + cb * 64) * 16, 2048, sbase + SB_FI);
                        bulk_g2s(sbase + FS_G + 32, g_gate + p * 64 + 64 + kq * 16, 32, sbase + SB_FI);
                    }
                    bulk_g2s(sbase + FS_Z, g_y + ((p * 4 + kq) * DM + cb * 64) * 16, 2048, sbase + SB_FI);
                    bulk_g2s(sbase + FS_G, g_gate + p * 64 + kq * 16, 32, sbase + SB_FI);
                    p++;
                } else if (seg < NATT && mbar_test(sbase + SB_OF + 8 * (seg & 1), (uint32_t)(seg >> 1) & 1u)) {
                    const uint32_t st = seg & 1, ab = sbase + AT_0 + st * AT_ST;
                    TSA(seg, 5);
                    if (seg < NSEG - UNGATE) gate(sbase + SB_TICK, GS_A, GS_B);
                    TSA(seg, 6);
                    unsigned char* dst = reinterpret_cast<unsigned char*>(g_ox) + ((size_t)((seg >> 1) * NH + cta)) * 16384 + (seg & 1) * 4096;
                    asm volatile("cp.async.bulk.global.shared::cta.bulk_group [%0], [%1], 4096;" :: "l"(dst), "r"(ab) : "memory");
                    asm volatile("cp.async.bulk.global.shared::cta.bulk_group [%0], [%1], 4096;" :: "l"(dst + 8192), "r"(ab + 4096) : "memory");
                    asm volatile("cp.async.bulk.commit_group;" ::: "memory");
                    asm volatile("cp.async.bulk.wait_group.read 0;" ::: "memory");
                    mbar_arrive(sbase + SB_VE + 8 * st);
                    asm volatile("cp.async.bulk.wait_group 0;" ::: "memory");
                    asm volatile("red.relaxed.gpu.global.add.u32 [%0], 1;" :: "l"(&g_prog[(seg >> 1) * 8 + (cta >> 2)]) : "memory");
                    TSA(seg, 7);
                    seg++;
                } else if (seg < NSEG - UNGATE) __nanosleep(W14_SLEEP);
            }
        }
        __syncwarp();
      }
    } else if (warp >= 8) {
        asm volatile("setmaxnreg.dec.sync.aligned.u32 88;");
        s4d_stage_u(smem_raw + FS_A, x, tid - 256);
        const int wq = warp - 8;
        for (int seg = 0; seg < (cta < NH ? NATT : 0); seg++) {
            const uint32_t st = seg & 1, ph = (uint32_t)(seg >> 1) & 1u, ab = sbase + AT_0 + st * AT_ST;
            float sc[20];
            if (seg < NSEG - UNGATE) mbar_wait_long(sbase + SB_QKF + 8 * st, ph); else mbar_wait(sbase + SB_QKF + 8 * st, ph);
            if (tid == 256) TSA(seg, 4);
            {
                const uint64_t da = smem_desc(ab + 10240 + 1024, 128, 1024), db = smem_desc(ab + 10240, 128, 2048);
                wg_fence();
#pragma unroll
                for (int ks = 0; ks < 8; ks++) wgmma_n40_ss(sc, da + (uint64_t)((ks >> 2) * 576 + (ks & 3) * 16), db + (uint64_t)((ks >> 2) * 576 + (ks & 3) * 16), ks > 0);
                wg_commit();
                wg_wait0();
            }
            if (lane == 0) mbar_arrive(sbase + SB_QKE + 8 * st);
            uint32_t p[5], ob[16];
            const float psum = xrow_softmax(sc, p, wq, lane);
            mbar_wait(sbase + SB_VF + 8 * st, ph);
            xrow_pv(ob, p, psum, ab);
            named_bar(6, 128);
#pragma unroll
            for (int i = 0; i < 4; i++) stsm_x4(ab + (i >> 1) * 4096 + wq * 1024 + (i & 1) * 512 + lane * 16, ob[4 * i], ob[4 * i + 1], ob[4 * i + 2], ob[4 * i + 3]);
            fence_async();
            __syncwarp();
            if (lane == 0) mbar_arrive(sbase + SB_OF + 8 * st);
        }
    } else {
        asm volatile("setmaxnreg.inc.sync.aligned.u32 192;");
        const int wg = warp >> 2, wq = warp & 3;
        s4d_phase(smem_raw + FS_A, x, logA, Aim, Cre, Cim, logdt, dskip, Wo + (size_t)((2 * kq + wg) * 512) * DM + cb * 64, ep, sbase + SB_TICK);
        TS3(2);
        if (lane == 0) TSS(16, warp);
        named_bar(3, 320);
        if (tid == 0) TSS(17, 0);
        uint32_t wa[32][4];
        mbar_wait_long(sbase + SB_WO, 0);
        if (tid == 0) TSS(17, 1);
        {
            const uint32_t a = sbase + FS_A + wg * 65536 + ((lane >> 4) * 8 + (lane & 7)) * 128 + (((wq * 2 + ((lane >> 3) & 1)) ^ (lane & 7)) << 4);
#pragma unroll
            for (int ks = 0; ks < 32; ks++) ldsm_x4_t(wa[ks], a + ks * 2048);
        }
        named_bar(7, 320);
        TS3(3);
        if (tid == 0) TSS(17, 4);
        auto product = [&](float (&acc)[32], int pr, const int wg) {
                if (pr + wg > 0 && (TURN31 || pr + wg < NSEG / 2)) named_bar(4 + wg, 256);
                const uint64_t db = smem_desc(sbase + FS_A + wg * 65536, 128, 1024);
                TSG(0);
#pragma unroll
                for (int j = 0; j < 4; j++) {
                    mbar_wait(sbase + SB_FULL + 8 * (4 * wg + j), (uint32_t)pr & 1u);
                    if (j == 0) TSG(1);
                    if (j == 3) TSG(2);
                    wg_fence();
#pragma unroll
                    for (int ks = 0; ks < 8; ks++) {
                        if ((j | ks) == 0) wgmma_n64_z(acc, wa[0], db);
                        else wgmma_n64(acc, wa[8 * j + ks], db + (uint64_t)(j * 1024 + (ks >> 2) * 512 + (ks & 3) * 16), 1);
                    }
                    wg_commit();
                    if (j == 3 && pr + (TURN31 ? wg : 1) < NSEG / 2) bar_arrive(4 + (wg ^ 1), 256);
                    if (j > 0) { wg_wait1(); if (lane == 0) mbar_arrive(sbase + SB_EMPTY + 8 * (4 * wg + j - 1)); }
                }
                wg_wait0();
                if (pr == 31) TS3W(27);
                TSG(3);
                if (lane == 0) mbar_arrive(sbase + SB_EMPTY + 8 * (4 * wg + 3));
        };
        if (wg == 1) {
            for (int pr = 0; pr < NSEG / 2; pr++) {
                uint32_t t16 = (uint32_t)(wq * 32 + lane) * 16u;
                asm volatile("" : "+r"(t16));
                float acc[32];
                product(acc, pr, 1);
                    uint32_t tag = ((uint32_t)(pr >> 3) & 1u) ^ 1u;
                    tag = __shfl_sync(0xffffffffu, tag, lane);
                    if (GATE_S && pr < NSEG / 2 - UNGATE_G) gate(sbase + SB_TICK);
                    named_bar(8, 256);
                    unsigned char* dst = reinterpret_cast<unsigned char*>(&g_fp[pr & 7][4 * cb][2 * kq - 2][0]) + t16;
                    const uint32_t own = sbase + FS_O + (pr % 3) * 4096 + t16;
#pragma unroll
                    for (int q = 0; q < 8; q++) {
                        float4 p;
                        asm volatile("ld.shared.v4.f32 {%0,%1,%2,%3}, [%4];" : "=f"(p.x), "=f"(p.y), "=f"(p.z), "=f"(p.w) : "r"(sbase + FS_P + t16 + q * 2048) : "memory");
                        acc[4 * q] = __uint_as_float((__float_as_uint(acc[4 * q] + p.x) & ~1u) | tag); acc[4 * q + 1] = __uint_as_float((__float_as_uint(acc[4 * q + 1] + p.y) & ~1u) | tag);
                        acc[4 * q + 2] = __uint_as_float((__float_as_uint(acc[4 * q + 2] + p.z) & ~1u) | tag); acc[4 * q + 3] = __uint_as_float((__float_as_uint(acc[4 * q + 3] + p.w) & ~1u) | tag);
                    }
#pragma unroll
                    for (int q = 0; q < 8; q++) {
                        asm volatile("{\n.reg .pred p;\nsetp.ne.s32 p, %5, %6;\n@p st.volatile.global.v4.f32 [%0], {%1,%2,%3,%4};\n@!p st.shared.v4.f32 [%7], {%1,%2,%3,%4};\n}"
                                     :: "l"(dst + (q & 1) * 2048), "f"(acc[4 * q]), "f"(acc[4 * q + 1]), "f"(acc[4 * q + 2]), "f"(acc[4 * q + 3]), "r"(q >> 1), "r"(kq),
                                        "r"(own + (q & 1) * 2048) : "memory");
                        if (q & 1) dst += (q >> 1) == kq ? 12288 + 4096 : 12288;
                    }
                    bar_arrive(9, 256);
                    if (pr == 31) TS3W(28);
                TSG(4);
            }
        } else {
          int nsync = 0;
          int np = 1, nf = 0, pr = 0, pf = -1;
          while (true) {
            uint32_t t16 = (uint32_t)(wq * 32 + lane) * 16u;
            asm volatile("" : "+r"(t16));
            if (pr < 0) {
                if (nsync <= pf) { named_bar(9, 256); nsync++; }
                if (lane == 0 && pf < NSEG / 2 - 1) mbar_arrive(sbase + SB_REQ);
            } else {
                float acc[32];
                product(acc, pr, 0);
                if (nsync < pr) { named_bar(9, 256); nsync++; }
#pragma unroll
                for (int q = 0; q < 8; q++)
                    asm volatile("st.shared.v4.f32 [%0], {%1,%2,%3,%4};" :: "r"(sbase + FS_P + t16 + q * 2048), "f"(acc[4 * q]), "f"(acc[4 * q + 1]), "f"(acc[4 * q + 2]), "f"(acc[4 * q + 3]) : "memory");
                bar_arrive(8, 256);
                TSG(4);
            }
            uint32_t w[4] = {0u, 0u, 0u, 0u};
            const int pc = pf;
            if (pf >= 0) {
                const uint32_t tag = ((uint32_t)(pf >> 3) & 1u) ^ 1u;
                uint4 v[8];
                unsigned n = 0;
                const bool last = pf == NSEG / 2 - 1;
                const uint4* src = reinterpret_cast<const uint4*>(reinterpret_cast<const unsigned char*>(&g_fp[pf & 7][cta][0][0]) + t16);
                if (pf >= NSEG / 2 - 2) {
#pragma unroll
                    for (int r = 0; r < 6; r++) v[r] = ld_vol_u4(src + r * 128);
                    mbar_wait(sbase + SB_FI, 0u);
                } else {
                    mbar_wait(sbase + SB_FI, (uint32_t)pf & 1u);
#pragma unroll
                    for (int r = 0; r < 6; r++)
                        asm volatile("ld.shared.v4.u32 {%0,%1,%2,%3}, [%4];" : "=r"(v[r].x), "=r"(v[r].y), "=r"(v[r].z), "=r"(v[r].w) : "r"(sbase + t16 + FS_I + r * 2048) : "memory");
                }
                while (true) {
                    uint32_t any = 0u;
#pragma unroll
                    for (int r = 0; r < 6; r++) {
                        uint32_t c0_, c1_;
                        asm("lop3.b32 %0, %1, %2, %3, 0x7e;" : "=r"(c0_) : "r"(v[r].x), "r"(v[r].y), "r"(tag));
                        asm("lop3.b32 %0, %1, %2, %3, 0x7e;" : "=r"(c1_) : "r"(v[r].z), "r"(v[r].w), "r"(tag));
                        asm("lop3.b32 %0, %1, %2, %3, 0xfe;" : "=r"(any) : "r"(any), "r"(c0_), "r"(c1_));
                    }
                    if (!__any_sync(0xffffffffu, (any & 1u) != 0u) || ++n >= SPIN_LIMIT) break;
                    if (pf < NSEG / 2 - 2) __nanosleep(200);
#pragma unroll
                    for (int r = 0; r < 6; r++) v[r] = ld_vol_u4(src + r * 128);
                }
                if (pf == 31) TS3(29);
                TSG(5);
#pragma unroll
                for (int r = 6; r < 8; r++)
                    asm volatile("ld.shared.v4.u32 {%0,%1,%2,%3}, [%4];" : "=r"(v[r].x), "=r"(v[r].y), "=r"(v[r].z), "=r"(v[r].w)
                                 : "r"(sbase + t16 + FS_O + (pf % 3) * 4096 + (r - 6) * 2048) : "memory");
                uint32_t zv[4], gg[2];
                ldsm_x4_t(zv, sbase + (last ? FS_I : FS_Z) + (wq * 16 + (lane & 15)) * 32 + (lane >> 4) * 16);
#pragma unroll
                for (int k = 0; k < 2; k++) gg[k] = __byte_perm(*reinterpret_cast<const volatile unsigned short*>(smem_raw + FS_G + (last ? 32 : 0) + k * 16 + (lane >> 2) * 2), 0u, 0x1010);
#define PQS(k, f) (((__uint_as_float(v[k].f) + __uint_as_float(v[2 + k].f)) + __uint_as_float(v[4 + k].f)) + __uint_as_float(v[6 + k].f))
#pragma unroll
                for (int k = 0; k < 2; k++) {
                    w[2 * k] = bf2_add(bf2_mul(gg[k], movm(pack_bf16(PQS(k, x), PQS(k, y)))), zv[2 * k]);
                    w[2 * k + 1] = bf2_add(bf2_mul(gg[k], movm(pack_bf16(PQS(k, z), PQS(k, w)))), zv[2 * k + 1]);
                }
#undef PQS
            }
            const bool more = nf < NSEG / 2;
            if (more) {
                uint32_t r;
                asm volatile("{\n.reg .pred p, q;\n.reg .b32 v;\nld.volatile.shared.u32 v, [%1];\nsetp.gt.s32 p, v, %2;\nbar.red.or.pred q, 10, 128, p;\nselp.u32 %0, 1, 0, q;\n}"
                             : "=r"(r) : "r"(sbase + SB_SEEN), "r"(np) : "memory");
                const bool dop = np < NSEG / 2 && (__shfl_sync(0xffffffffu, r, 0) != 0u || nf == np || nf >= NSEG / 2 - 2);
                TSG(6);
                pr = dop ? np++ : -1;
                pf = !dop || nf + (pr == NSEG / 2 - 1 ? 1 : 2) <= pr ? nf++ : -1;
                if (dop && pf >= 0 && lane == 0) mbar_arrive(sbase + SB_REQ);
            }
            if (pc >= 0) {
                unsigned char* op = reinterpret_cast<unsigned char*>(out) + (uint32_t)((pc * 64 + kq * 16 + (lane >> 2)) * DM + cb * 64 + wq * 16 + 2 * (lane & 3)) * 2u;
#pragma unroll
                for (int k = 0; k < 4; k++) *reinterpret_cast<uint32_t*>(op + (k >> 1) * (16 * DM) + (k & 1) * 16) = w[k];
                if ((pc & 1) == 0) TS3(4 + pc / 2);
                if (pc == 31) TS3(25);
            }
            if (!more) break;
          }
        }
        if (cta == 0 && tid == 0) asm volatile("red.relaxed.gpu.global.add.u32 [%0], 1;" :: "l"(&g_epoch) : "memory");
    }
    asm volatile("griddepcontrol.wait;" ::: "memory");
}

__device__ __forceinline__ uint32_t poll_mem(const uint4* src, uint32_t dst, uint32_t t0) {
    uint4 v[6];
    unsigned it = 0;
#pragma unroll
    for (int j = 0; j < 6; j++) v[j] = make_uint4(0u, 0u, 0u, 0u);
    while (clock32() - t0 < POLL_DELAY) {}
    FS(12, 0);
    bool more;
#pragma unroll 1
    do {
        asm volatile("{\n.reg .pred p<6>;\n"
                     "setp.ne.u32 p0, %3, 0x5000;\nsetp.ne.u32 p1, %7, 0x5000;\nsetp.ne.u32 p2, %11, 0x5000;\n"
                     "setp.ne.u32 p3, %15, 0x5000;\nsetp.ne.u32 p4, %19, 0x5000;\nsetp.ne.u32 p5, %23, 0x5000;\n"
                     "@p0 ld.volatile.global.v4.u32 {%0,%1,%2,%3}, [%24];\n@p1 ld.volatile.global.v4.u32 {%4,%5,%6,%7}, [%24+4096];\n"
                     "@p2 ld.volatile.global.v4.u32 {%8,%9,%10,%11}, [%24+8192];\n@p3 ld.volatile.global.v4.u32 {%12,%13,%14,%15}, [%24+12288];\n"
                     "@p4 ld.volatile.global.v4.u32 {%16,%17,%18,%19}, [%24+16384];\n@p5 ld.volatile.global.v4.u32 {%20,%21,%22,%23}, [%24+20480];\n}"
                     : "+r"(v[0].x), "+r"(v[0].y), "+r"(v[0].z), "+r"(v[0].w), "+r"(v[1].x), "+r"(v[1].y), "+r"(v[1].z), "+r"(v[1].w),
                       "+r"(v[2].x), "+r"(v[2].y), "+r"(v[2].z), "+r"(v[2].w), "+r"(v[3].x), "+r"(v[3].y), "+r"(v[3].z), "+r"(v[3].w),
                       "+r"(v[4].x), "+r"(v[4].y), "+r"(v[4].z), "+r"(v[4].w), "+r"(v[5].x), "+r"(v[5].y), "+r"(v[5].z), "+r"(v[5].w)
                     : "l"(src) : "memory");
        stsm_x4(dst, h2_to_bf2(v[0].x), h2_to_bf2(v[0].y), h2_to_bf2(v[0].z), h2_to_bf2(v[1].x));
        stsm_x4(dst + 512, h2_to_bf2(v[1].y), h2_to_bf2(v[1].z), h2_to_bf2(v[2].x), h2_to_bf2(v[2].y));
        stsm_x4(dst + 1024, h2_to_bf2(v[2].z), h2_to_bf2(v[3].x), h2_to_bf2(v[3].y), h2_to_bf2(v[3].z));
        asm volatile("stmatrix.sync.aligned.m8n8.x2.shared.b16 [%0], {%1,%2};" :: "r"(dst + 1536), "r"(h2_to_bf2(v[4].x)), "r"(h2_to_bf2(v[4].y)) : "memory");
        stsm_x4(dst + 1792, h2_to_bf2(v[4].z), h2_to_bf2(v[5].x), h2_to_bf2(v[5].y), h2_to_bf2(v[5].z));
        const uint32_t all = ((v[0].w & v[1].w) & (v[2].w & v[3].w)) & (v[4].w & v[5].w);
        more = __any_sync(0xffffffffu, (all & 0x5000u) != 0x5000u) && ++it < SPIN_LIMIT;
    } while (more);
    FS(13, it);
    bar_arrive(1, 384);
    FS(14, 0);
    uint32_t m = 0u;
#pragma unroll
    for (int j = 0; j < 6; j++) {
        asm volatile("max.NaN.xorsign.abs.f16x2 %0, %0, %1;" : "+r"(m) : "r"(v[j].x));
        asm volatile("max.NaN.xorsign.abs.f16x2 %0, %0, %1;" : "+r"(m) : "r"(v[j].y));
        asm volatile("max.NaN.xorsign.abs.f16x2 %0, %0, %1;" : "+r"(m) : "r"(v[j].z));
    }
    return h2_to_bf2(m) & 0x7fff7fffu;
}

template <bool V> struct Flag { static constexpr bool value = V; };
struct RFlag { bool value; };
__device__ __forceinline__ void score_group(const uint32_t (&a)[2][4], const uint32_t (&kf)[2][4], uint32_t d0, uint32_t d1, uint32_t m1, uint32_t d2, uint32_t m2) {
    FS(4, a[1][0]);
    float sc[4][4];
    mma_z(sc[0], a[0], kf[0][0], kf[0][1]);
    mma_z(sc[1], a[0], kf[0][2], kf[0][3]);
    mma_z(sc[2], a[1], kf[1][0], kf[1][1]);
    mma_z(sc[3], a[1], kf[1][2], kf[1][3]);
    const uint32_t v0 = __float_as_uint((sc[0][0] + sc[1][2]) + (sc[2][0] + sc[3][2])), v1 = __float_as_uint((sc[0][1] + sc[1][3]) + (sc[2][1] + sc[3][3]));
    FS(5, v0);
    st_async64(d2, v0, v1, m2);
    st_async64(d1, v0, v1, m1);
    asm volatile("st.shared.v2.u32 [%0], {%1,%2};" :: "r"(d0), "r"(v0), "r"(v1) : "memory");
}
__device__ __forceinline__ void store_tile(int s, int h, int role, uint32_t tile) {
    const uint32_t qoff = role != 2 ? 1024 : 0;
    asm volatile("cp.async.bulk.global.shared::cta.bulk_group.L2::cache_hint [%0], [%1], %2, %3;"
                 :: "l"(&g_qkv[s][h][role][qoff]), "r"(tile + qoff), "r"(10240u - qoff), "l"(policy_evict_first()) : "memory");
    asm volatile("cp.async.bulk.commit_group;" ::: "memory");
}
__device__ __forceinline__ uint32_t w_addr(uint32_t sbase, int warp, int lane) {
    return sbase + SM_WS + (warp >> 2) * 8192 + ((lane & 7) + ((lane >> 4) & 1) * 8) * 128 + ((((warp & 3) * 2 + ((lane >> 3) & 1)) ^ (lane & 7)) << 4);
}
__device__ __forceinline__ void vx_copy(uint32_t sbase, int j, int r) {
    bulk_s2s(mapa(sbase + SM_VX + (j & 1) * 8192, r), sbase + SM_T + (j & 3) * TBUF + DH * 16, 8192, mapa(sbase + B_VX + 8 * (j & 1), r));
}
__device__ __forceinline__ void norms_gather(int lane, float* scs) {
    uint2 v[3];
    uint32_t r[2];
    unsigned it = 0;
    do {
#pragma unroll
        for (int i = 0; i < 3; i++) v[i] = ld_vol_u2(&g_norm[3 * lane + i]);
#pragma unroll
        for (int i = 0; i < 2; i++) asm volatile("ld.volatile.global.u32 %0, [%1];" : "=r"(r[i]) : "l"(&g_rx[lane + 32 * i]) : "memory");
    } while (__any_sync(0xffffffffu, (v[0].x & v[1].x & v[2].x & v[2].y & r[0] & r[1] & 1u) == 0u) && ++it < SPIN_LIMIT);
    float c;
    asm("sqrt.approx.f32 %0, %1;" : "=f"(c) : "f"(__uint_as_float(max(max(v[0].x, v[1].x), v[2].x))));
    c *= __uint_as_float(v[2].y) * 272.f;
#pragma unroll
    for (int o = 16; o; o >>= 1) c += __shfl_xor_sync(0xffffffffu, c, o);
    scs[16 + lane] = __uint_as_float(r[0]); scs[48 + lane] = __uint_as_float(r[1]);
    if (lane == 0) scs[1] = c * (1.1f * 24.f);
}

__device__ __forceinline__ void last_rows(int pass) {
    extern __shared__ __align__(1024) unsigned char smem_raw[];
    const uint32_t sbase = smem_u32(smem_raw);
    const int tid = threadIdx.x, warp = __shfl_sync(0xffffffffu, tid >> 5, 0), h = blockIdx.x / 3;
    {
        const int sg = warp < 8, wq = warp & 3, lane = tid & 31;
        const uint32_t qk = sbase + SM_X + XBUF + sg * (2 * 9216), ob = sbase + SM_X + 2 * XBUF + sg * 8192;
        TST(0);
        if (pass) mbar_wait(sbase + B_VX + 8 * sg, 0);
        fence_async();
        TST(1);
        float sc[20];
#pragma unroll
        for (int i = 0; i < 20; i++) sc[i] = 0.f;
        {
            const uint64_t da = smem_desc(qk + 1024, 128, 1024), db = smem_desc(qk, 128, 2048);
            wg_fence();
#pragma unroll
            for (int ks = 0; ks < 8; ks++) wgmma_n40_ss(sc, da + (uint64_t)((ks >> 2) * 576 + (ks & 3) * 16), db + (uint64_t)((ks >> 2) * 576 + (ks & 3) * 16), ks > 0);
            wg_commit();
            wg_wait0();
        }
        uint32_t p[5], o[16];
        const float psum = xrow_softmax(sc, p, wq, lane);
        xrow_pv(o, p, psum, sbase + SM_T + ((NSEG - 2 + sg) & 3) * TBUF);
        if (pass) {
#pragma unroll
            for (int i = 0; i < 4; i++) stsm_x4(ob + (i >> 1) * 4096 + wq * 1024 + (i & 1) * 512 + lane * 16, o[4 * i], o[4 * i + 1], o[4 * i + 2], o[4 * i + 3]);
        }
        fence_async();
        named_bar(11 + sg, 128);
        TST(2);
        if ((tid & 127) == 0 && pass) {
            unsigned char* dst = reinterpret_cast<unsigned char*>(g_ox) + ((size_t)((NSEG / 2 - 1) * NH + h)) * 16384 + sg * 4096;
            asm volatile("cp.async.bulk.global.shared::cta.bulk_group [%0], [%1], 4096;" :: "l"(dst), "r"(ob) : "memory");
            asm volatile("cp.async.bulk.global.shared::cta.bulk_group [%0], [%1], 4096;" :: "l"(dst + 8192), "r"(ob + 4096) : "memory");
            asm volatile("cp.async.bulk.commit_group;" ::: "memory");
            asm volatile("cp.async.bulk.wait_group 0;" ::: "memory");
            asm volatile("red.relaxed.gpu.global.add.u32 [%0], 1;" :: "l"(&g_prog[(NSEG / 2 - 1) * 8 + (h >> 2)]) : "memory");
        }
        TST(3);
    }
    __syncwarp();
}

__global__ void __cluster_dims__(3, 1, 1) __launch_bounds__(384, 1)
k_chain(const __grid_constant__ CUtensorMap tmx, const __grid_constant__ CUtensorMap tmq, const __grid_constant__ CUtensorMap tmk,
        const __grid_constant__ CUtensorMap tmv, const __grid_constant__ CUtensorMap tmx2, const __grid_constant__ CUtensorMap tmo, const bf16* __restrict__ mem0, const bf16* __restrict__ xg) {
    extern __shared__ __align__(1024) unsigned char smem_raw[];
    const uint32_t sbase = smem_u32(smem_raw);
    const int cta = blockIdx.x, h = cta / 3, role = cta - 3 * h;
    const int tid = threadIdx.x, warp = __shfl_sync(0xffffffffu, tid >> 5, 0), lane_o = tid & 31;
    TS3C(0);
    asm volatile("griddepcontrol.launch_dependents;" ::: "memory");
    auto stage_w = [&](int i) {
        tma_2d(sbase + SM_WS + i * 16384, role == 2 ? &tmv : &tmq, h * DH + (role == 1 ? 64 : 0), i * 64, sbase + B_W + 8 * i);
        tma_2d(sbase + SM_WS + i * 16384 + 8192, role == 2 ? &tmv : &tmk, h * DH + (role == 0 ? 0 : 64), i * 64, sbase + B_W + 8 * i);
    };
    auto stage_x = [&](int i) { tma_2d(sbase + x01_off(i), &tmx2, i * 64, 0, sbase + B_W + 8 * i); };
    if (tid == 0) {
#pragma unroll
        for (int i = 0; i < 10; i++) mbar_init(sbase + B_W + 8 * i, 1);
        fence_async();
        bulk_g2s(sbase + SM_E + XBUF, mem0, MEMT * DM * 2, sbase + B_E);
#pragma unroll
        for (int i = 0; i < 3; i++) tma_2d(sbase + SM_X01 + i * 16384, &tmo, role * WOC + i * 64, h * DH, sbase + B_E);
        if (cta < NSEG) bulk_g2s(sbase + SM_E, xg + (size_t)cta * SEG * DM, XBUF, sbase + B_E);
#pragma unroll 1
        for (int i = 0; i < 6; i++) { if (i < 3) stage_x(i); stage_w(i); }
        mbar_expect(sbase + B_E, 49152 + MEMT * DM * 2 + (cta < NSEG ? XBUF : 0));
#pragma unroll
        for (int i = 0; i < 9; i++) mbar_expect(sbase + B_W + 8 * i, 24576);
    } else if (tid == 32) {
#pragma unroll
        for (int i = 0; i < 7; i++) mbar_init(sbase + SM_BAR + 8 * i, 1);
        asm volatile("fence.mbarrier_init.release.cluster;" ::: "memory");
        for (int i = 0; i < 2; i++) {
            mbar_expect(sbase + B_SB + 8 * i, role == 2 ? 2560 : 1280 + 2048);
            mbar_expect(sbase + B_VX + 8 * i, role != 2 ? 8192 : 2 * 9216);
            mbar_arrive(sbase + B_XT + 8 * i);
        }
        mbar_expect(sbase + B_XT + 16, XBUF);
        reinterpret_cast<float*>(smem_raw + SM_SC)[2] = 1.f;
    } else if (tid >= 64 && tid < 88) {
        *reinterpret_cast<uint4*>(g_acc + cta * 1024 + (tid - 64) * 16) = make_uint4(0u, 0u, 0u, 0u);
        __threadfence();
    }
    __syncthreads();
    TS3C(8);
    if (warp < 8) {
        uint32_t wreg[36 - NS][4];
        {
            const int lane = lane_o;
            const uint32_t a = w_addr(sbase, warp, lane);
            const uint64_t da = smem_desc(sbase + SM_WS + (warp >> 2) * 8192, 1024, 1024) | (1ull << 62);
            float acc[32];
#pragma unroll
            for (int i = 0; i < 32; i++) acc[i] = 0.f;
#pragma unroll 1
            for (int b = 0; b < 9; b++) {
                if (b == 0) TSQ(0);
                mbar_wait(sbase + B_W + 8 * b, 0);
                TSQ(1 + b);
                if (b == 8) TS3C(2);
                const uint64_t db = smem_desc(sbase + x01_off(b), 16, 1024) | (1ull << 62);
                wg_fence();
#pragma unroll
                for (int k = 0; k < 4; k++) wgmma_n64_ss(acc, da + (uint64_t)(b * 1024 + k * 128), db + (uint64_t)(k * 2));
                wg_commit();
                if (b == 5) {
#pragma unroll
                    for (int ks = NS; ks < 24; ks++) ldsm_x4_t(wreg[ks - NS], a + (ks >> 2) * 16384 + (ks & 3) * 2048);
                }
            }
#pragma unroll
            for (int ks = 24; ks < 32; ks++) ldsm_x4_t(wreg[ks - NS], a + (ks >> 2) * 16384 + (ks & 3) * 2048);
            wg_wait0();
            named_bar(9, 384);
            const uint32_t off = sbase + SM_T + (DH + warp * 16 + (lane & 15)) * 16 + (lane >> 4) * (DH * 16);
#pragma unroll
            for (int i = 0; i < 4; i++)
                stsm_x4(off + (i >> 1) * TBUF + (i & 1) * (2 * DH * 16), pack_bf16(acc[8 * i], acc[8 * i + 1]), pack_bf16(acc[8 * i + 2], acc[8 * i + 3]),
                        pack_bf16(acc[8 * i + 4], acc[8 * i + 5]), pack_bf16(acc[8 * i + 6], acc[8 * i + 7]));
#pragma unroll
            for (int ks = 32; ks < 36; ks++) ldsm_x4_t(wreg[ks - NS], a + (ks >> 2) * 16384 + (ks & 3) * 2048);
            if (role == 2) fence_async();
            bar_arrive(8, 384);
            named_bar(7, 256);
            asm volatile("barrier.cluster.arrive.relaxed.aligned;" ::: "memory");
        }
        TS3C(3);
        auto xproj1 = [&](float (&acc)[16], int j) {
            const uint32_t dlo = __shfl_sync(0xffffffffu, (uint32_t)smem_desc(sbase + SM_X + (j % 3) * XBUF, 16, 1024), 0);
            wg_fence();
#pragma unroll
            for (int ks = NS; ks < NS + NC1; ks++) {
                if (ks == NS) wgmma_n32_z(acc, wreg[0], ((uint64_t)0x40000040u << 32) | (uint64_t)(dlo + (uint32_t)((ks >> 2) * 256 + (ks & 3) * 2)));
                else wgmma_n32(acc, wreg[ks - NS], ((uint64_t)0x40000040u << 32) | (uint64_t)(dlo + (uint32_t)((ks >> 2) * 256 + (ks & 3) * 2)), 1);
            }
            wg_commit();
            wg_wait0();
        };
        auto xproj2 = [&](float (&acc)[16], int j) {
            int lane = lane_o;
            asm volatile("" : "+r"(lane));
            const uint32_t dlo = __shfl_sync(0xffffffffu, (uint32_t)smem_desc(sbase + SM_X + (j % 3) * XBUF, 16, 1024), 0);
            const uint64_t da = smem_desc(sbase + SM_WS + (warp >> 2) * 8192, 1024, 1024) | (1ull << 62);
            wg_fence();
#pragma unroll
            for (int ks = NS + NC1; ks < NS + NC1 + SS_POS; ks++)
                wgmma_n32(acc, wreg[ks - NS], ((uint64_t)0x40000040u << 32) | (uint64_t)(dlo + (uint32_t)((ks >> 2) * 256 + (ks & 3) * 2)), 1);
#pragma unroll
            for (int ks = 0; ks < NS; ks++)
                wgmma_n32_ss(acc, da + (uint64_t)((ks >> 2) * 1024 + (ks & 3) * 128), ((uint64_t)0x40000040u << 32) | (uint64_t)(dlo + (uint32_t)((ks >> 2) * 256 + (ks & 3) * 2)), 1);
#pragma unroll
            for (int ks = NS + NC1 + SS_POS; ks < XK; ks++)
                wgmma_n32(acc, wreg[ks - NS], ((uint64_t)0x40000040u << 32) | (uint64_t)(dlo + (uint32_t)((ks >> 2) * 256 + (ks & 3) * 2)), 1);
            wg_commit();
            wg_wait0();
            const uint32_t off = sbase + SM_T + (j & 3) * TBUF + (DH + warp * 16 + (lane & 15)) * 16 + (lane >> 4) * (DH * 16);
            stsm_x4(off, pack_bf16(acc[0], acc[1]), pack_bf16(acc[2], acc[3]), pack_bf16(acc[4], acc[5]), pack_bf16(acc[6], acc[7]));
            stsm_x4(off + 2 * DH * 16, pack_bf16(acc[8], acc[9]), pack_bf16(acc[10], acc[11]), pack_bf16(acc[12], acc[13]), pack_bf16(acc[14], acc[15]));
        };
        uint32_t ws[NS][4];
#pragma unroll
        for (int ks = NS - NP; ks < NS; ks++) ldsm_x4_t(ws[ks], w_addr(sbase, warp, lane_o) + (ks >> 2) * 16384 + (ks & 3) * 2048);
        asm volatile("barrier.cluster.wait.aligned;" ::: "memory");
        if (lane_o == 0 && warp < 2 && role == 2) vx_copy(sbase, 0, warp);
        __syncwarp();
        TS3C(4);
        auto main_loop = [&](auto is_c) {
            const bool C = is_c.value;
            const uint32_t l16 = __shfl_sync(0xffffffffu, sbase + lane_o * 16, lane_o);
            const uint32_t ka = __shfl_sync(0xffffffffu, sbase + SM_T + (64 + (lane_o & 7) + ((lane_o >> 3) & 1) * 16 + (lane_o >> 4) * 8) * 16, lane_o);
            uint32_t to = 0;
            for (int s = 0; s < NSEG; s++) {
                int lane = lane_o;
                asm volatile("" : "+r"(lane));
                uint32_t v0, v1;
                const uint32_t tb = sbase + SM_T + to;
                {
#pragma unroll
                    for (int ks = 0; ks < NS - NP; ks++) ldsm_x4_t(ws[ks], w_addr(sbase, warp, lane) + (ks >> 2) * 16384 + (ks & 3) * 2048);
                    FS(0, ws[0][0]);
                    named_bar(1, 384);
                    float acc[2][4], minv;
                    uint32_t b[3][4];
#pragma unroll
                    for (int kk = 0; kk < 3; kk++) ldsm_x4_t(b[kk], l16 + SM_M + kk * 512);
                    FS(1, b[0][0]);
#pragma unroll
                    for (int kk = 0; kk < 18; kk++) {
#pragma unroll
                        for (int i = 0; i < 2; i++) {
                            const int ks = 2 * kk + i;
                            if (ks < 2) mma_z(acc[i], ws[ks], b[kk % 3][2 * i], b[kk % 3][2 * i + 1]);
                            else if (ks < NS) mma_bf16(acc[i], ws[ks < NS ? ks : 0], b[kk % 3][2 * i], b[kk % 3][2 * i + 1]);
                            else mma_bf16(acc[i], wreg[ks >= NS ? ks - NS : 0], b[kk % 3][2 * i], b[kk % 3][2 * i + 1]);
                        }
                        if (kk + 3 < 18) ldsm_x4_t(b[kk % 3], l16 + SM_M + (kk + 3) * 512);
                        if (kk + 3 == 17) asm volatile("ld.shared.f32 %0, [%1];" : "=f"(minv) : "r"(sbase + SM_SC + 8) : "memory");
                    }
                    v0 = pack_bf16(fmaf(acc[1][0], minv, acc[0][0] * minv), fmaf(acc[1][1], minv, acc[0][1] * minv));
                    v1 = pack_bf16(fmaf(acc[1][2], minv, acc[0][2] * minv), fmaf(acc[1][3], minv, acc[0][3] * minv));
                    FS(2, v0);
                }
                asm volatile("stmatrix.sync.aligned.m8n8.x2.shared.b16 [%0], {%1,%2};" :: "r"(l16 + (SM_T + warp * 256 + to)), "r"(v0), "r"(v1) : "memory");
                if (C) {
                    if (s + 1 < NSEG) {
                        const uint32_t fo = (uint32_t)(warp * 256 + lane * 8);
                        const uint32_t rb0 = mapa(sbase, 0), rb1 = mapa(sbase, 1);
                        st_async64(rb0 + SM_VM + fo, v0, v1, rb0 + B_SB + 8 * (s & 1));
                        st_async64(rb1 + SM_VM + fo, v0, v1, rb1 + B_SB + 8 * (s & 1));
                        asm volatile("st.shared.v2.u32 [%0], {%1,%2};" :: "r"(sbase + SM_VM + fo), "r"(v0), "r"(v1) : "memory");
                        bar_arrive(2, 384);
                    }
                } else {
                    named_bar(2, 384);
                    if (warp == 7) {
                        uint32_t kf[2][4], qf[2][4];
#pragma unroll
                        for (int k2 = 0; k2 < 2; k2++) { ldsm_x4_t(kf[k2], ka + to + k2 * 512); ldsm_x4_t(qf[k2], l16 + SM_T + to + k2 * 512); }
                        if (s + 1 < NSEG) {
                            const uint32_t d0 = sbase + SM_S + role * 1280 + lane * 8, bo = sbase + B_SB + 8 * (s & 1);
                            const uint32_t d1 = mapa(d0, role ^ 1), m1 = mapa(bo, role ^ 1), d2 = mapa(d0, 2), m2 = mapa(bo, 2);
                            score_group(qf, kf, d0, d1, m1, d2, m2);
                            bar_arrive(6, 160);
                        }
                    }
                    if (s + 1 == NSEG && warp >= 4) {
                        const uint32_t dk = mapa(sbase + SM_X + XBUF + (2 + role) * 9216 + (warp - 4) * 256 + lane * 4, 2), mb = mapa(sbase + B_VX + 8, 2);
                        st_async32(dk, v0, mb);
                        st_async32(dk + 128, v1, mb);
                    }
                }
                to = to == 3 * TBUF ? 0 : to + TBUF;
                FS(11, 0);
                if (s + 2 < NSEG) {
                    if (warp == 6) mbar_wait(sbase + B_XT + 8 * ((s + 2) % 3), (uint32_t)((s + 2) / 3) & 1u);
                    fence_async();
                    if (!C) named_bar(5, 384); else named_bar(7, 256);
                    if (tid == 64) store_tile(s, h, role, tb);
                    __syncwarp();
                    float xacc[16];
                    if (C1_DELAY > 0) { const uint32_t t1 = clock32(); while (clock32() - t1 < C1_DELAY) {} }
                    xproj1(xacc, s + 2);
                    FS(9, __float_as_uint(xacc[0]));
                    if (C && tid == 0) vx_copy(sbase, s + 1, 0);
                    if (tid == 64) {
                        asm volatile("cp.async.bulk.wait_group 0;" ::: "memory");
                        asm volatile("red.relaxed.gpu.global.add.u32 [%0], 1;" :: "l"(&g_flag[h * NSEG + s]) : "memory");
                    }
                    __syncwarp();
                    FS(14, 0);
                    named_bar(4, 384);
                    if (C2_DELAY > 0) { const uint32_t t1 = clock32(); while (clock32() - t1 < C2_DELAY) {} }
                    xproj2(xacc, s + 2);
                    FS(7, __float_as_uint(xacc[0]));
                } else if (s + 2 == NSEG) {
                    const uint32_t t0 = clock32();
                    const uint32_t dq = mapa(sbase + SM_X + XBUF + role * 9216, 2), mb = mapa(sbase + B_VX, 2);
                    if (!C) {
                        fence_async();
                        named_bar(5, 384);
                        if (tid == 64) { while (clock32() - t0 < TL_DELAY) {} bulk_s2s(dq, tb + 1024, 9216, mb); }
                        __syncwarp();
                    }
                    named_bar(4, 384);
                    if (!C && tid == 64) { const uint32_t t1 = clock32(); while (clock32() - t1 < VX_DELAY) {} bulk_s2s(dq + 2 * 9216 + 1024, sbase + SM_T + ((s + 1) & 3) * TBUF + 2048, 8192, mb + 8); }
                    __syncwarp();
                    if (WARM && !C && warp < 4) {
                        bar_arrive(1, 384);
                        bar_arrive(2, 384);
                        break;
                    }
                }
            }
            if (C) named_bar(7, 256);
        };
        if (role == 2) main_loop(Flag<true>()); else main_loop(Flag<false>());
    } else {
        float* scs = reinterpret_cast<float*>(smem_raw + SM_SC);
        uint32_t wo[3][8][4];
        uint32_t mx2 = 0u;
        {
            const int pt = tid - 256, lane = lane_o, wq = warp - 8, g = lane >> 2, tq = lane & 3;
            TSQ(7);
            mbar_wait(sbase + B_E, 0);
            TSQ(8);
#pragma unroll
            for (int t = 0; t < 3; t++) {
                const int T = 3 * wq + t;
                const uint32_t a = sbase + SM_X01 + (T >> 2) * 16384 + ((lane >> 4) * 8 + (lane & 7)) * 128 + ((((T & 3) * 2 + ((lane >> 3) & 1)) ^ (lane & 7)) << 4);
#pragma unroll
                for (int kk = 0; kk < 8; kk++) ldsm_x4_t(wo[t][kk], a + ((2 * wq + kk) & 7) * 2048);
            }
            uint32_t m = 0u;
#pragma unroll 6
            for (int j = 0; j < 18; j++) {
                const uint32_t v = lds32(sbase + SM_E + XBUF + (g * DM + wq * 144 + 8 * j) * 2 + tq * 4);
                asm volatile("stmatrix.sync.aligned.m8n8.x1.trans.shared.b16 [%0], {%1};" :: "r"(sbase + SM_M + (wq * 144 + 8 * j + (lane & 7)) * 16), "r"(v) : "memory");
                mx2 = __vmaxu2(mx2, v & 0x7fff7fffu);
                const uint4 xv = *reinterpret_cast<const uint4*>(smem_raw + SM_E + (pt + 128 * j) * 16);
                m = max_abs2(max_abs2(m, max_abs2(xv.x, xv.y)), max_abs2(xv.z, xv.w));
            }
            m = __reduce_max_sync(0xffffffffu, max((m << 16) & 0x7fff0000u, m & 0x7fff0000u));
            if (lane == 0) reinterpret_cast<uint32_t*>(scs)[260 + wq] = m;
            named_bar(3, 128);
            if (pt == 64) {
                fence_async();
#pragma unroll 1
                for (int i = 3; i < 9; i++) { stage_x(i); if (i >= 6) stage_w(i); }
            }
            if (pt == 96 && cta < NSEG) {
                const uint4 q = *reinterpret_cast<const uint4*>(scs + 260);
                asm volatile("st.volatile.global.u32 [%0], %1;" :: "l"(&g_rx[cta]), "r"(max(max(q.x, q.y), max(q.z, q.w)) | 1u) : "memory");
            }
            __syncwarp();
            bar_arrive(1, 384);
            TSQ(9);
            float c0 = 0.f;
#pragma unroll
            for (int t = 0; t < 3; t++) {
                float n[4][4];
#pragma unroll
                for (int i = 0; i < 4; i++) { n[i][0] = n[i][1] = n[i][2] = n[i][3] = 0.f; }
#pragma unroll
                for (int kk = 0; kk < 8; kk++)
#pragma unroll
                    for (int i = 0; i < 4; i++) mma_k8(n[i], wo[t][kk][i & 2], wo[t][kk][(i & 2) + 1], wo[t][kk][i]);
                if ((g >> 1) == tq) c0 = fmaxf(c0, (g & 1) ? fmaxf(n[0][1] + n[2][1], n[1][3] + n[3][3]) : fmaxf(n[0][0] + n[2][0], n[1][2] + n[3][2]));
            }
            c0 = __uint_as_float(__reduce_max_sync(0xffffffffu, __float_as_uint(c0)));
            m = 0u;
#pragma unroll 1
            for (int b = 0; b < 9; b++) {
                if (role == 2) {
                    mbar_wait(sbase + B_W + 8 * b, 0);
#pragma unroll
                    for (int j = 0; j < 8; j++) {
                        const uint4 xv = *reinterpret_cast<const uint4*>(smem_raw + SM_WS + b * 16384 + (pt + 128 * j) * 16);
                        m = max_abs2(max_abs2(m, max_abs2(xv.x, xv.y)), max_abs2(xv.z, xv.w));
                    }
                }
                if (b == 3) bar_arrive(9, 384);
            }
            asm volatile("barrier.cluster.arrive.relaxed.aligned;" ::: "memory");
            m = __reduce_max_sync(0xffffffffu, max((m << 16) & 0x7fff0000u, m & 0x7fff0000u));
            if (lane == 0) { scs[256 + wq] = c0; reinterpret_cast<uint32_t*>(scs)[8 + wq] = m; }
            TSQ(1);
            named_bar(3, 128);
            if (pt == 0) {
                const float a = fmaxf(fmaxf(scs[256], scs[257]), fmaxf(scs[258], scs[259]));
                const float b = fmaxf(fmaxf(scs[8], scs[9]), fmaxf(scs[10], scs[11]));
                st_vol_u2(&g_norm[cta], make_uint2(__float_as_uint(a) | 1u, __float_as_uint(b) | 1u));
            }
            __syncwarp();
            named_bar(8, 384);
            TSQ(2);
            if (pt == 32) {
                fence_async();
                for (int i = 0; i < 3; i++) tma_x(sbase + SM_X + 2 * XBUF, &tmx, 2, i, sbase + B_XT + 16);
            }
            __syncwarp();
            asm volatile("barrier.cluster.wait.aligned;" ::: "memory");
        }
        const int wq = warp - 8;
        auto helper_loop = [&](auto is_c) {
        const bool C = is_c.value;
        const uint32_t l8 = __shfl_sync(0xffffffffu, sbase + lane_o * 8, lane_o), l16 = __shfl_sync(0xffffffffu, sbase + lane_o * 16, lane_o);
        unsigned char* dst = g_acc + (role * 32 + wq * 8 + (lane_o >> 3)) * 1024 + (lane_o & 7) * 16;
        const uint32_t ka = __shfl_sync(0xffffffffu, sbase + SM_T + ((wq + 1) * DH + 64 + (lane_o & 7) + ((lane_o >> 3) & 1) * 16 + (lane_o >> 4) * 8) * 16, lane_o);
        const uint32_t vb = __shfl_sync(0xffffffffu, sbase + (lane_o >> 4) * 2048 + (32 * wq + (lane_o & 15)) * 16, lane_o);
        float minv = 1.f;
        uint32_t kf[2][4];
#pragma unroll
        for (int k2 = 0; k2 < 2; k2++) if (!C) ldsm_x4_t(kf[k2], ka + k2 * 512);
        int b3 = 0;
        for (int s = 0; s + 1 < NSEG; s++) {
            const int n3 = b3 == 2 ? 0 : b3 + 1;
            {
                int lane = lane_o;
                asm volatile("" : "+r"(lane));
                if (lane == 0) {
                    if (wq == 0 && cta == 0) {
                        const uint32_t t = gtime32();
                        st_vol_u2(&g_tick, make_uint2(t, reinterpret_cast<uint32_t*>(scs)[3]));
                        reinterpret_cast<uint32_t*>(scs)[3] = t;
                    }
                    if (wq == 1 && s + 3 < NSEG) tma_x_mc(sbase + SM_X + b3 * XBUF, &tmx, s + 3, role, sbase + B_XT + 8 * b3);
                    if (wq == 0 && s == 1) {
                        st_vol_u2(&g_norm[cta], make_uint2(0u, 0u));
                        if (cta < NSEG) asm volatile("st.volatile.global.u32 [%0], %1;" :: "l"(&g_rx[cta]), "r"(0u) : "memory");
                    }
                }
                __syncwarp();
                if (wq == 2 && s > 1 && lane < 8) {
                    *reinterpret_cast<uint4*>(g_acc + n3 * 128 + cta * 1024 + lane * 16) = make_uint4(0u, 0u, 0u, 0u);
                }
                const uint32_t mw = __reduce_max_sync(0xffffffffu, max(mx2 << 16, mx2 & 0xffff0000u));
                if (lane == 0) scs[4 + wq] = __uint_as_float(mw);
            }
            const uint32_t to = SM_T + (s & 3) * TBUF;
            const uint32_t ph = (uint32_t)(s >> 1) & 1u;
            if (!C) {
                const uint32_t so = SM_S + role * 1280 + (wq + 1) * 256, bo = sbase + B_SB + 8 * (s & 1);
                uint32_t d0 = l8 + so, qa = l16 + to;
                const uint32_t d1 = mapa(d0, role ^ 1), m1 = mapa(bo, role ^ 1), d2 = mapa(d0, 2), m2 = mapa(bo, 2);
                asm volatile("" : "+r"(d0), "+r"(qa));
                mbar_wait(sbase + B_VX + 8 * (s & 1), ph);
                FS(1, 0);
                named_bar(2, 384);
                uint32_t qf[2][4];
#pragma unroll
                for (int k2 = 0; k2 < 2; k2++) ldsm_x4_t(qf[k2], qa + k2 * 512);
                score_group(qf, kf, d0, d1, m1, d2, m2);
                bar_arrive(5, 384);
            } else named_bar(2, 384);
            if (s == 0) {
                TSQ(3);
                int lane = lane_o;
                asm volatile("" : "+r"(lane));
                if (wq == 1) norms_gather(lane, scs);
                named_bar(3, 128);
                TSQ(4);
            }
            const float4 m4 = *reinterpret_cast<const float4*>(scs + 4);
            const float c24 = scs[1], xb = scs[16 + s];
            uint32_t vf[2][2][4], vm[2][2];
            {
                const uint32_t va = vb + (C ? to + DH * 16 : SM_VX + (s & 1) * 8192);
#pragma unroll
                for (int i = 0; i < 4; i++) ldsm_x4(vf[i >> 1][i & 1], va + (i >> 1) * 256 + (i & 1) * 4096);
            }
            float scale;
            {
                const float bound = fmaxf(fmaxf(fmaxf(m4.x, m4.y), fmaxf(m4.z, m4.w)) * minv, xb) * c24;
                int e = 141 - (int)((__float_as_uint(bound) >> 23) & 255u);
                e = e > 100 ? 100 : e;
                scale = __uint_as_float((uint32_t)(127 + e) << 23);
            }
            uint32_t s0 = l8 + (role & 1) * 1280, s1 = l8 + ((role & 1) ^ 1) * 1280, oa = l16 + wq * 512;
            asm volatile("" : "+f"(scale), "+r"(s0), "+r"(s1), "+r"(oa));
            FS(7, vf[1][1][0]);
            constexpr float EC = (float)(1.4426950408889634 * 0.08838834764831845);
            if (!C) named_bar(6, 160);
            if (C) mbar_wait(sbase + B_SB + 8 * (s & 1), ph);
            float sv[5][2];
#pragma unroll
            for (int j = 0; j < 5; j++) lds64f(sv[j][0], sv[j][1], s0 + SM_S + j * 256);
            if (!C) {
#pragma unroll
                for (int j = 0; j < 5; j++) { sv[j][0] *= EC; sv[j][1] *= EC; asm volatile("" : "+f"(sv[j][0]), "+f"(sv[j][1])); }
                mbar_wait(sbase + B_SB + 8 * (s & 1), ph);
            }
            FS(6, 0);
            uint32_t p[5];
            {
                float sr[5][2];
#pragma unroll
                for (int j = 0; j < 5; j++) lds64f(sr[j][0], sr[j][1], s1 + SM_S + j * 256);
                lds64(vm[0][0], vm[0][1], l8 + SM_VM + wq * 512);
                lds64(vm[1][0], vm[1][1], l8 + SM_VM + wq * 512 + 256);
                if (C) {
#pragma unroll
                    for (int j = 0; j < 5; j++) { sv[j][0] *= EC; sv[j][1] *= EC; }
                }
#pragma unroll
                for (int j = 0; j < 5; j++) { sv[j][0] = fmaf(sr[j][0], EC, sv[j][0]); sv[j][1] = fmaf(sr[j][1], EC, sv[j][1]); }
                float mx = fmaxf(fmaxf(fmaxf(sv[0][0], sv[0][1]), fmaxf(sv[1][0], sv[1][1])), fmaxf(fmaxf(sv[2][0], sv[2][1]), fmaxf(sv[3][0], sv[3][1])));
                mx = fmaxf(mx, fmaxf(sv[4][0], sv[4][1]));
                {
                    const float m1 = __shfl_xor_sync(0xffffffffu, mx, 1), m2 = __shfl_xor_sync(0xffffffffu, mx, 2), m3 = __shfl_xor_sync(0xffffffffu, mx, 3);
                    mx = fmaxf(fmaxf(mx, m1), fmaxf(m2, m3));
                }
#pragma unroll
                for (int jj = 0; jj < 5; jj++) {
                    const int j = (jj + 1) % 5;
                    asm("ex2.approx.ftz.f32 %0, %1;" : "=f"(sv[j][0]) : "f"(sv[j][0] - mx));
                    asm("ex2.approx.ftz.f32 %0, %1;" : "=f"(sv[j][1]) : "f"(sv[j][1] - mx));
                    p[j] = pack_bf16(sv[j][0], sv[j][1]);
                }
            }
            FS(0, p[0]);
            uint32_t b[4][4];
            float zs[4];
            {
                float o0[2][4], o1[2][4];
                mma_z(o0[0], vf[0][0], p[1], p[2]);
                mma_z(o0[1], vf[1][0], p[1], p[2]);
                mma_z(o1[0], vf[0][1], p[3], p[4]);
                mma_z(o1[1], vf[1][1], p[3], p[4]);
                mma_k8(o0[0], vm[0][0], vm[0][1], p[0]);
                mma_k8(o0[1], vm[1][0], vm[1][1], p[0]);
                const uint32_t one4[4] = {0x3f803f80u, 0x3f803f80u, 0x3f803f80u, 0x3f803f80u};
                mma_z(zs, one4, p[1], p[2]);
                mma_bf16(zs, one4, p[3], p[4]);
                mma_k8(zs, one4[0], one4[1], p[0]);
                uint32_t ow[4];
#pragma unroll
                for (int m = 0; m < 2; m++) {
                    ow[2 * m] = pack_bf16(o0[m][0] + o1[m][0], o0[m][1] + o1[m][1]);
                    ow[2 * m + 1] = pack_bf16(o0[m][2] + o1[m][2], o0[m][3] + o1[m][3]);
                }
                stsm_x4(oa + SM_O, ow[0], ow[1], ow[2], ow[3]);
                FS(2, 0);
#pragma unroll
                for (int i = 0; i < 4; i++) b[0][i] = movm(ow[i]);
            }
            float acc[3][2][4];
            named_bar(3, 128);
#pragma unroll
            for (int i = 1; i < 4; i++) ldsm_x4_t(b[i], l16 + SM_O + ((wq + i) & 3) * 512);
#pragma unroll
            for (int c = 0; c < 2; c++)
#pragma unroll
                for (int t = 0; t < 3; t++) mma_z(acc[t][c], wo[t][c], b[0][2 * c], b[0][2 * c + 1]);
            float z0, z1;
            asm volatile("rcp.approx.ftz.f32 %0, %1;" : "=f"(z0) : "f"(zs[0]));
            asm volatile("rcp.approx.ftz.f32 %0, %1;" : "=f"(z1) : "f"(zs[1]));
            z0 *= scale; z1 *= scale;
            FS(3, b[1][0]);
#pragma unroll
            for (int i = 1; i < 4; i++)
#pragma unroll
                for (int c = 0; c < 2; c++)
#pragma unroll
                    for (int t = 0; t < 3; t++) mma_bf16(acc[t][c], wo[t][2 * i + c], b[i][2 * c], b[i][2 * c + 1]);
            {
                uint32_t w[6];
#pragma unroll
                for (int t = 0; t < 3; t++) {
                    w[2 * t] = pack_f16(fmaf(acc[t][1][0], z0, acc[t][0][0] * z0), fmaf(acc[t][1][1], z1, acc[t][0][1] * z1));
                    w[2 * t + 1] = pack_f16(fmaf(acc[t][1][2], z0, acc[t][0][2] * z0), fmaf(acc[t][1][3], z1, acc[t][0][3] * z1));
                }
                FS(8, w[5]);
                asm volatile("red.relaxed.gpu.global.add.noftz.v4.f16x2 [%0], {%1,%2,%3,%4};" :: "l"(dst), "r"(w[0]), "r"(w[1]), "r"(w[2]), "r"(0x3c00u) : "memory");
                asm volatile("red.relaxed.gpu.global.add.noftz.v4.f16x2 [%0], {%1,%2,%3,%4};" :: "l"(dst + 4096), "r"(w[3]), "r"(w[4]), "r"(w[5]), "r"(0x3c00u) : "memory");
            }
            FS(9, 0);
            if (s == 0) TSQ(5);
            bar_arrive(4, 384);
            const uint32_t t0 = clock32();
            minv = __uint_as_float(0x7f000000u - __float_as_uint(scale));
            if (lane_o == 0) {
                if (wq == 0) scs[2] = minv;
                if (wq == 2 && C && s + 2 < NSEG) { while (clock32() - t0 < VX_DELAY) {} vx_copy(sbase, s + 1, 1); }
                if (s + 3 < NSEG) {
                    if (wq == 0) mbar_expect(sbase + B_SB + 8 * (s & 1), C ? 2560 : 1280 + 2048);
                    if (wq == 1) mbar_expect(sbase + B_XT + 8 * b3, XBUF);
                    if (wq == 3 && !C) mbar_expect(sbase + B_VX + 8 * (s & 1), 8192);
                }
            }
            __syncwarp();
#pragma unroll
            for (int k2 = 0; k2 < 2; k2++) if (!C) ldsm_x4_t(kf[k2], ka + ((s + 1) & 3) * TBUF + k2 * 512);
            const uint4* src = reinterpret_cast<const uint4*>(dst + (wq * 16 - role * 32) * 1024);
            dst += n3 == 0 ? -256 : 128;
            asm volatile("" : "+l"(dst));
            mx2 = poll_mem(src, l16 + SM_M + wq * 2304, t0);
            if (s == 0) TSQ(6);
            b3 = n3;
        }
        if (!C) bar_arrive(2, 384);
        };
        if (role == 2) helper_loop(Flag<true>()); else helper_loop(Flag<false>());
    }
    TS3C(1);
    if (role == 2 ? warp >= 4 : (WARM && warp < 4 && (WARM == 1 || (WARM == 2 && cta % 12 == 0) || (WARM == 3 && role == 0)))) last_rows(role == 2);
    cluster_sync_all();
}

extern "C" void kernel_launch(void* const* d_in, const int* in_sizes, int n_in, void* d_out, int out_size) {
    const bf16* x = (const bf16*)d_in[0];
    const bf16* mem0 = (const bf16*)d_in[1];
    const bf16* Wq = (const bf16*)d_in[2];
    const bf16* Wk = (const bf16*)d_in[3];
    const bf16* Wv = (const bf16*)d_in[4];
    const bf16* Wo = (const bf16*)d_in[5];
    const bf16* logA = (const bf16*)d_in[8];
    const bf16* Aim = (const bf16*)d_in[9];
    const bf16* Cre = (const bf16*)d_in[10];
    const bf16* Cim = (const bf16*)d_in[11];
    const bf16* logdt = (const bf16*)d_in[12];
    const bf16* dskip = (const bf16*)d_in[13];
    const bf16* gw = (const bf16*)d_in[14];
    bf16* out = (bf16*)d_out;
    static bool attr_done = false;
    typedef CUresult (*EncFn)(CUtensorMap*, CUtensorMapDataType, cuuint32_t, void*, const cuuint64_t*, const cuuint64_t*, const cuuint32_t*,
                              const cuuint32_t*, CUtensorMapInterleave, CUtensorMapSwizzle, CUtensorMapL2promotion, CUtensorMapFloatOOBfill);
    static EncFn enc = nullptr;
    if (!attr_done) {
        void* fn = nullptr;
        cudaDriverEntryPointQueryResult qr;
        cudaGetDriverEntryPoint("cuTensorMapEncodeTiled", &fn, cudaEnableDefault, &qr);
        enc = (EncFn)fn;
        cudaFuncSetAttribute(k_chain, cudaFuncAttributeMaxDynamicSharedMemorySize, 232448);
        cudaFuncSetAttribute(k_side, cudaFuncAttributeMaxDynamicSharedMemorySize, SIDE_SMEM);
        attr_done = true;
    }
    CUtensorMap tmx;
    {
        const cuuint64_t dims[3] = {64, (cuuint64_t)S_LEN, 9};
        const cuuint64_t strides[2] = {(cuuint64_t)DM * 2, 128};
        const cuuint32_t box[3] = {64, (cuuint32_t)SEG, 3};
        const cuuint32_t es[3] = {1, 1, 1};
        enc(&tmx, CU_TENSOR_MAP_DATA_TYPE_BFLOAT16, 3, (void*)x, dims, strides, box, es, CU_TENSOR_MAP_INTERLEAVE_NONE,
            CU_TENSOR_MAP_SWIZZLE_128B, CU_TENSOR_MAP_L2_PROMOTION_L2_128B, CU_TENSOR_MAP_FLOAT_OOB_FILL_NONE);
    }
    CUtensorMap tmw[3];
    for (int i = 0; i < 3; i++) {
        const cuuint64_t dims[2] = {(cuuint64_t)HD, (cuuint64_t)DM};
        const cuuint64_t strides[1] = {(cuuint64_t)HD * 2};
        const cuuint32_t box[2] = {64, 64};
        const cuuint32_t es[2] = {1, 1};
        enc(&tmw[i], CU_TENSOR_MAP_DATA_TYPE_BFLOAT16, 2, (void*)(i == 0 ? Wq : (i == 1 ? Wk : Wv)), dims, strides, box, es, CU_TENSOR_MAP_INTERLEAVE_NONE,
            CU_TENSOR_MAP_SWIZZLE_128B, CU_TENSOR_MAP_L2_PROMOTION_L2_256B, CU_TENSOR_MAP_FLOAT_OOB_FILL_NONE);
    }
    CUtensorMap tmo;
    {
        const cuuint64_t dims[2] = {(cuuint64_t)DM, (cuuint64_t)HD};
        const cuuint64_t strides[1] = {(cuuint64_t)DM * 2};
        const cuuint32_t box[2] = {64, 128};
        const cuuint32_t es[2] = {1, 1};
        enc(&tmo, CU_TENSOR_MAP_DATA_TYPE_BFLOAT16, 2, (void*)Wo, dims, strides, box, es, CU_TENSOR_MAP_INTERLEAVE_NONE,
            CU_TENSOR_MAP_SWIZZLE_128B, CU_TENSOR_MAP_L2_PROMOTION_L2_128B, CU_TENSOR_MAP_FLOAT_OOB_FILL_NONE);
    }
    CUtensorMap tmx2;
    {
        const cuuint64_t dims[2] = {(cuuint64_t)DM, (cuuint64_t)S_LEN};
        const cuuint64_t strides[1] = {(cuuint64_t)DM * 2};
        const cuuint32_t box[2] = {64, 64};
        const cuuint32_t es[2] = {1, 1};
        enc(&tmx2, CU_TENSOR_MAP_DATA_TYPE_BFLOAT16, 2, (void*)x, dims, strides, box, es, CU_TENSOR_MAP_INTERLEAVE_NONE,
            CU_TENSOR_MAP_SWIZZLE_128B, CU_TENSOR_MAP_L2_PROMOTION_L2_128B, CU_TENSOR_MAP_FLOAT_OOB_FILL_NONE);
    }
    k_chain<<<NCTA, 384, 232448>>>(tmx, tmw[0], tmw[1], tmw[2], tmx2, tmo, mem0, x);
    {
        cudaLaunchConfig_t cfg = {};
        cfg.gridDim = dim3(SD_NCTA); cfg.blockDim = dim3(512); cfg.dynamicSmemBytes = SIDE_SMEM; cfg.stream = cudaStreamPerThread;
        cudaLaunchAttribute at[1];
        at[0].id = cudaLaunchAttributeProgrammaticStreamSerialization;
        at[0].val.programmaticStreamSerializationAllowed = 1;
        cfg.attrs = at; cfg.numAttrs = 1;
        cudaLaunchKernelEx(&cfg, k_side, tmo, x, logA, Aim, Cre, Cim, logdt, Wo, dskip, gw, out);
    }
}
```

```cpp
#include <cuda_runtime.h>
#include <cuda.h>
#include <cuda_bf16.h>
#include <stdint.h>

typedef __nv_bfloat16 bf16;
#define LDV4 "ld.volatile.global.v4.u32 {%0,%1,%2,%3}, [%4];"
#define STV4 "st.volatile.global.v4.u32 [%0], {%1,%2,%3,%4};"
#define STV2 "st.volatile.global.v2.u32 [%0], {%1,%2};"

constexpr int S_LEN = 2048, DM = 576, NH = 32, DH = 128, HD = 4096, MEMT = 8, SEG = 32, NSEG = 64, NST = 128;

__device__ __align__(128) bf16 g_gate[S_LEN];
constexpr int NCTA = NH * 3;
__device__ __align__(1024) unsigned char g_acc[96 * 1024];
__device__ __align__(128) uint2 g_norm[NCTA];
__device__ __align__(128) uint4 g_wv[NH][2];
__device__ __align__(128) uint4 g_rx[NSEG][2];
__device__ __align__(128) unsigned char g_qkv[NSEG][NH][3][10240];
__device__ __align__(128) bf16 g_ox[S_LEN * HD];
__device__ __align__(128) uint4 g_fp[8][36][6][128];
__device__ __align__(128) unsigned g_flag[NH * NSEG];
__device__ unsigned g_prog[NSEG / 2 * 8];
__device__ unsigned g_gcnt[64];
__device__ unsigned g_epoch;
__device__ __align__(128) uint2 g_tick;
__device__ __align__(128) bf16 g_y[DM * S_LEN];

#define TS3(slot) do {} while (0)
#define TS3P(slot) do {} while (0)
#define TSQ(slot) do {} while (0)
#define TS3W(slot) do {} while (0)
#define TSS(row, slot) do {} while (0)
#define TS3C(slot) do {} while (0)
#define TST(slot) do {} while (0)
#define TSA(seg, slot) do {} while (0)
#define TSG(i) do {} while (0)
#define FS(i, dep) do {} while (0)
__device__ __forceinline__ uint32_t smem_u32(const void* p) { return (uint32_t)__cvta_generic_to_shared(p); }
__device__ __forceinline__ float bf16r(float x) { return __bfloat162float(__float2bfloat16_rn(x)); }
__device__ __forceinline__ uint32_t pack_bf16(float lo, float hi) {
    __nv_bfloat162 v = __floats2bfloat162_rn(lo, hi);
    return *reinterpret_cast<uint32_t*>(&v);
}
__device__ __forceinline__ void ldsm_x4(uint32_t (&r)[4], uint32_t addr) {
    asm volatile("ldmatrix.sync.aligned.m8n8.x4.shared.b16 {%0,%1,%2,%3}, [%4];"
                 : "=r"(r[0]), "=r"(r[1]), "=r"(r[2]), "=r"(r[3]) : "r"(addr));
}
__device__ __forceinline__ void ldsm_x4_t(uint32_t (&r)[4], uint32_t addr) {
    asm volatile("ldmatrix.sync.aligned.m8n8.x4.trans.shared.b16 {%0,%1,%2,%3}, [%4];"
                 : "=r"(r[0]), "=r"(r[1]), "=r"(r[2]), "=r"(r[3]) : "r"(addr));
}
__device__ __forceinline__ void mma_bf16(float (&d)[4], const uint32_t (&a)[4], uint32_t b0, uint32_t b1) {
    asm volatile("mma.sync.aligned.m16n8k16.row.col.f32.bf16.bf16.f32 {%0,%1,%2,%3}, {%4,%5,%6,%7}, {%8,%9}, {%0,%1,%2,%3};"
                 : "+f"(d[0]), "+f"(d[1]), "+f"(d[2]), "+f"(d[3])
                 : "r"(a[0]), "r"(a[1]), "r"(a[2]), "r"(a[3]), "r"(b0), "r"(b1));
}
__device__ __forceinline__ uint2 ld_vol_u2(const uint2* p) {
    uint2 v; asm volatile("ld.volatile.global.v2.u32 {%0,%1}, [%2];" : "=r"(v.x), "=r"(v.y) : "l"(p) : "memory"); return v;
}
__device__ __forceinline__ void st_vol_u2(uint2* p, uint2 v) {
    asm volatile(STV2 :: "l"(p), "r"(v.x), "r"(v.y) : "memory");
}
__device__ __forceinline__ unsigned ld_acq(const unsigned* p) {
    unsigned v; asm volatile("ld.acquire.gpu.global.u32 %0, [%1];" : "=r"(v) : "l"(p) : "memory"); return v;
}
#define NS 10
#define NP 4
#define X_OXSZ 16384
#define GATE_A 1050
#define GATE_B 300
#define GATE_P 1880u
#define STAGGER 0
#define RLX_SLEEP 300
#define VX_DELAY 100
#define EARLY4 0
#define SPEC_M 1
#define SPEC_H 1
#define C2_DELAY 0
#define SS_POS 2
#define UNGATE_G 3
#define GATE_Y 0
#define GATE_S 0
#define GATE_F 1
#define W14_SLEEP 60
#define TURN31 1
#define GL_A 1150
#define GL_B 480
#define GS_A 1400
#define GS_B 480
#define GATE_POLL 0
#define GP_A 900
#define GP_B 200
#define NUP 3
#define SIDE_WAIT 0
#define FASTW 0
#define NC1 5
#define NC1C NC1
#define C1_DELAY 0
#define XSKIP 0
#define LATEW 0
#define VFP 0
#define CC_DELAY 0
#define KPRE 34
#define SMR 0
#define TL_DELAY 600
#define POLL_DELAY 545
#define UNGATE 6
constexpr unsigned SPIN_LIMIT = 1u << 20;
constexpr int NATT = NSEG - 2;

constexpr int SD_CH = 16;
constexpr int SD_NCTA = DM / SD_CH;
constexpr int SD_ROW = 528;
constexpr int SD_U = 8 * SD_ROW;
constexpr int SD_TAP = 5888;
constexpr int SD_CPY = 1376 * 2;
constexpr int SD_WSTR = SD_TAP + 2 * SD_CPY;
constexpr int SD_SMEM = SD_CH * SD_U + 8 * SD_WSTR;
constexpr int O_U = 79, O_U3 = 911, O_U4 = 1055, O_W79 = 1023, O_W35 = 1151, O_W610 = 1279, O_W511 = 1487;

__device__ __forceinline__ uint32_t lds32(uint32_t a) { uint32_t v; asm volatile("ld.shared.u32 %0, [%1];" : "=r"(v) : "r"(a)); return v; }
__device__ __forceinline__ void tap_tile(uint32_t (&t)[4], uint32_t a) {
    asm volatile("ld.volatile.shared.u32 %0, [%4];\nld.volatile.shared.u32 %1, [%4+-16];\nld.volatile.shared.u32 %2, [%4+16];\nld.volatile.shared.u32 %3, [%4];"
                 : "=r"(t[0]), "=r"(t[1]), "=r"(t[2]), "=r"(t[3]) : "r"(a));
}
constexpr uint32_t sd_pass(int type, int dl, int o, int d0, int d1) { return (uint32_t)(type | dl << 2 | d0 << 8 | d1 << 12 | o << 17); }
__constant__ uint32_t SD_PASS[14] = {sd_pass(0, 0, O_U, 0, 2), sd_pass(0, 1, O_U + 96, 0, 2), sd_pass(0, 2, O_U + 192, 0, 4), sd_pass(0, 3, O_U + 288, 0, 2), sd_pass(1, 0, O_U3, 8, 8),
                                     sd_pass(0, 4, O_U + 384, 0, 2), sd_pass(1, 0, O_U4, 8, 15), sd_pass(0, 5, O_U + 480, 0, 2), sd_pass(0, 6, O_U + 576, 0, 4), sd_pass(0, 7, O_U + 672, 0, 2),
                                     sd_pass(2, 0, O_W35, 2, 8), sd_pass(3, 0, O_W79, 2, 4), sd_pass(2, 1, O_W610, 4, 8), sd_pass(3, 0, O_W511, 8, 15)};
__device__ __forceinline__ uint32_t band2(int x, int lo, int hi) { return (x >= lo && x <= hi ? 0x3f80u : 0u) | (x + 1 >= lo && x + 1 <= hi ? 0x3f800000u : 0u); }
__device__ __forceinline__ void mma_z(float (&d)[4], const uint32_t (&a)[4], uint32_t b0, uint32_t b1);
__device__ __forceinline__ void put_tap(uint32_t a, float v) {
    asm volatile("{\n.reg .b16 h;\ncvt.rn.bf16.f32 h, %1;\nst.shared.b16 [%0], h;\nst.shared.b16 [%0+%2], h;\n}" :: "r"(a), "f"(v), "n"(SD_CPY - 2) : "memory");
}

__device__ __forceinline__ void named_bar(int id, int n) { asm volatile("bar.sync %0, %1;" :: "r"(id), "r"(n) : "memory"); }
__device__ __forceinline__ uint32_t pack_f16(float lo, float hi) {
    uint32_t r; asm("cvt.rn.f16x2.f32 %0, %1, %2;" : "=r"(r) : "f"(hi), "f"(lo)); return r;
}
__device__ __forceinline__ void cexp_t(float lr, float turns, float& re, float& im) {
    float m;
    asm("ex2.approx.ftz.f32 %0, %1;" : "=f"(m) : "f"(lr));
    const float a = (turns - rintf(turns)) * 6.283185307179586f;
    re = m * __cosf(a); im = m * __sinf(a);
}
__device__ __forceinline__ void csq(float& re, float& im) { const float r = re * re - im * im; im = 2.f * re * im; re = r; }
__device__ __forceinline__ void kb_state(const float* tp, float gf, uint32_t (&a)[4][2], uint32_t (&b)[5]) {
    const float4 p0 = *reinterpret_cast<const float4*>(tp), p1 = *reinterpret_cast<const float4*>(tp + 4);
    float wr, wi;
    cexp_t(p0.x * gf, p0.y * gf, wr, wi);
    float vr = wr * p1.x - wi * p1.y, vi = wr * p1.y + wi * p1.x;
#pragma unroll
    for (int c = 0; c < 4; c++) {
        a[c][0] = pack_f16(wr, wi); a[c][1] = pack_f16(vr, vi);
        csq(wr, wi);
        if (c < 3) csq(vr, vi);
    }
    b[0] = pack_f16(p0.z * wr - p0.w * wi, -p0.z * wi - p0.w * wr);
    float er = wr * p1.z - wi * p1.w, ei = wr * p1.w + wi * p1.z;
#pragma unroll
    for (int c = 0; c < 4; c++) {
        b[1 + c] = pack_f16(p0.z * er - p0.w * ei, -p0.z * ei - p0.w * er);
        if (c < 3) csq(er, ei);
    }
}
__device__ __forceinline__ uint32_t bf2_mul(uint32_t a, uint32_t b) { uint32_t r; asm("mul.rn.bf16x2 %0, %1, %2;" : "=r"(r) : "r"(a), "r"(b)); return r; }
__device__ __forceinline__ uint32_t bf2_add(uint32_t a, uint32_t b) { uint32_t r; asm("add.rn.bf16x2 %0, %1, %2;" : "=r"(r) : "r"(a), "r"(b)); return r; }
__device__ __forceinline__ uint32_t bf2_sub(uint32_t a, uint32_t b) { uint32_t r; asm("sub.rn.bf16x2 %0, %1, %2;" : "=r"(r) : "r"(a), "r"(b)); return r; }
__device__ __forceinline__ void wait_cnt(const unsigned* p, unsigned target) {
    unsigned it = 0;
    while ((int)(ld_acq(p) - target) < 0 && ++it < SPIN_LIMIT) __nanosleep(64);
}
__device__ __forceinline__ uint32_t gtime32() { uint32_t t; asm volatile("mov.u32 %0, %%globaltimer_lo;" : "=r"(t) :: "memory"); return t; }
__device__ __forceinline__ void gate(uint32_t tick_addr, uint32_t ga = GATE_A, uint32_t gb = GATE_B) {
    uint32_t t1, p;
    asm volatile("ld.volatile.shared.v2.u32 {%0,%1}, [%2];" : "=r"(t1), "=r"(p) : "r"(tick_addr) : "memory");
    uint32_t d = gtime32() - t1;
    if (d < 4u * p) {
        d -= d >= 2u * p ? 2u * p : 0u;
        d -= d >= p ? p : 0u;
        if (d + ga >= p && d + gb < p) {
            const uint32_t t2 = gtime32() + (p - gb - d);
            while ((int)(gtime32() - t2) < 0) {}
        }
    }
}

__device__ __forceinline__ void read_tick(uint32_t tick_addr) {
    const uint2 tk = ld_vol_u2(&g_tick);
    uint32_t p = tk.x - tk.y;
    p = p > GATE_P + 100u ? GATE_P + 100u : p;
    asm volatile("st.volatile.shared.v2.u32 [%0], {%1,%2};" :: "r"(tick_addr), "r"(tk.x), "r"(p) : "memory");
}

__device__ __forceinline__ void s4d_phase(unsigned char* smem_raw, const bf16* __restrict__ x, const bf16* __restrict__ logA,
                                          const bf16* __restrict__ Aim, const bf16* __restrict__ Cre, const bf16* __restrict__ Cim,
                                          const bf16* __restrict__ logdt, const bf16* __restrict__ dskip, const bf16* __restrict__ wslice, unsigned ep, uint32_t tick) {
    const int tid = threadIdx.x, warp = __shfl_sync(0xffffffffu, tid >> 5, 0), lane = tid & 31;
    const int d0 = blockIdx.x * SD_CH;
    float* tab = reinterpret_cast<float*>(smem_raw + SD_CH * SD_U + warp * SD_WSTR);
    const uint32_t wb = smem_u32(tab);
    const int g = lane >> 2, tq = lane & 3;
    uint2 prm[4];
    float ldt;
    auto load_prm = [&](int d) {
        prm[0] = __ldg(reinterpret_cast<const uint2*>(logA + d * NST) + lane); prm[1] = __ldg(reinterpret_cast<const uint2*>(Aim + d * NST) + lane);
        prm[2] = __ldg(reinterpret_cast<const uint2*>(Cre + d * NST) + lane); prm[3] = __ldg(reinterpret_cast<const uint2*>(Cim + d * NST) + lane);
        ldt = __bfloat162float(logdt[d]);
    };
    load_prm(d0 + warp);
    for (int i = lane; i < 2 * SD_CPY / 16; i += 32) reinterpret_cast<uint4*>(tab + SD_TAP / 4)[i] = make_uint4(0u, 0u, 0u, 0u);
    TS3(20);
#pragma unroll 1
    for (int ch = 0; ch < 2; ch++) {
        const int d = d0 + 8 * ch + warp;
        const uint32_t ub = smem_u32(smem_raw) + (8 * ch + warp) * SD_U;
        float k2048 = 0.f, sinv;
        {
            const float dt = bf16r(expf(ldt));
            uint32_t cm = __vmaxu2(__vmaxu2(prm[2].x & 0x7fff7fffu, prm[2].y & 0x7fff7fffu), __vmaxu2(prm[3].x & 0x7fff7fffu, prm[3].y & 0x7fff7fffu));
            cm = __reduce_max_sync(0xffffffffu, max(cm << 16, cm & 0xffff0000u));
            int e = 134 - (int)(__float_as_uint(__uint_as_float(cm) * dt) >> 23);
            e = e > 100 ? 100 : (e < -100 ? -100 : e);
            const float s2 = __uint_as_float((uint32_t)(128 + e) << 23);
            sinv = __uint_as_float((uint32_t)(127 - e) << 23);
#pragma unroll
            for (int j = 0; j < 4; j++) {
                float q[4];
#pragma unroll
                for (int i = 0; i < 4; i++) { const uint32_t w = j < 2 ? prm[i].x : prm[i].y; q[i] = __uint_as_float((j & 1) ? w & 0xffff0000u : w << 16); }
                const float zl = -bf16r(expf(q[0])) * dt * 1.4426950408889634f;
                const float zt = q[1] * dt * 0.15915494309189535f;
                const float cr = s2 * (q[2] * dt), ci = s2 * (q[3] * dt);
                float ar, ai, br, bi, er, ei;
                cexp_t(zl * 8.f, zt * 8.f, ar, ai);
                cexp_t(zl * 128.f, zt * 128.f, br, bi);
                cexp_t(zl * 2048.f, zt * 2048.f, er, ei);
                k2048 += cr * er - ci * ei;
                *reinterpret_cast<float4*>(tab + (lane + 32 * j) * 8) = make_float4(zl, zt, cr, ci);
                *reinterpret_cast<float4*>(tab + (lane + 32 * j) * 8 + 4) = make_float4(ar, ai, br, bi);
            }
#pragma unroll
            for (int o = 16; o; o >>= 1) k2048 += __shfl_xor_sync(0xffffffffu, k2048, o);
        }
        __syncwarp();
        {
            float kc[5][4];
#pragma unroll
            for (int i = 0; i < 5; i++) { kc[i][0] = kc[i][1] = kc[i][2] = kc[i][3] = 0.f; }
            const float gf = (float)g;
#pragma unroll 2
            for (int ks = 0; ks < 16; ks++) {
                uint32_t a0[4][2], a1[4][2], b0[5], b1[5];
                kb_state(tab + (8 * ks + tq) * 8, gf, a0, b0);
                kb_state(tab + (8 * ks + 4 + tq) * 8, gf, a1, b1);
#pragma unroll
                for (int i = 0; i < 5; i++) {
                    const int c = i > 0 ? i - 1 : 0;
                    asm volatile("mma.sync.aligned.m16n8k16.row.col.f32.f16.f16.f32 {%0,%1,%2,%3}, {%4,%5,%6,%7}, {%8,%9}, {%0,%1,%2,%3};"
                                 : "+f"(kc[i][0]), "+f"(kc[i][1]), "+f"(kc[i][2]), "+f"(kc[i][3])
                                 : "r"(a0[c][0]), "r"(a0[c][1]), "r"(a1[c][0]), "r"(a1[c][1]), "r"(b0[i]), "r"(b1[i]));
                }
            }
            const uint32_t tp = wb + SD_TAP;
            const uint32_t a0 = tp + 2 * (O_U + 96 * g - 4 * tq);
            const uint32_t a2 = tp + 2 * (((g & 1) ? O_U + 96 * (2 * (g & 3)) : ((g & 2) ? O_W35 : O_W79 + 1)) - 32 - 8 * tq - (g >> 2));
            const uint32_t a3 = tp + 2 * (((g & 1) ? O_W35 : O_W610 + 1) - 64 - 16 * tq - (g >> 1));
            const uint32_t a4 = tp + 2 * (-128 - 32 * tq - g);
#pragma unroll
            for (int c = 0; c < 4; c++) {
                const int e = (c & 1) * 16 + (c >> 1) * 8;
                const bool first = c == 0 && lane == 0;
                put_tap(a0 - e / 4, kc[0][c] * sinv);
                put_tap(a0 - 32 - e / 4, kc[1][c] * sinv);
                put_tap(first ? tp + 2 * (O_U - 32) : a2 - e / 2, kc[2][c] * sinv);
                put_tap(first ? tp + 2 * (O_W79 - 63) : a3 - e, kc[3][c] * sinv);
                put_tap(first ? tp + 2 * (O_W610 - 127) : a4 + 2 * (O_W511 + 1 - e), kc[4][c] * sinv);
                if ((g & 1) == 0) {
                    put_tap(a4 + 2 * (O_U4 - e), kc[4][c] * sinv);
                    put_tap(first ? tp + 2 * (O_U3 - 128) : a4 + 2 * (O_U4 + 1 - e), kc[4][c] * sinv);
                }
            }
            if (lane == 0) {
                put_tap(tp + 2 * (O_U + 96 - 32), kc[2][0] * sinv);
                put_tap(tp + 2 * (O_U + 192 - 64), kc[3][0] * sinv);
                put_tap(tp + 2 * (O_W511 - 255), k2048 * sinv);
                put_tap(tp + 2 * (O_U4 - 255), k2048 * sinv);
            }
        }
        TS3(21 + 2 * ch);
        if (ch == 0) { if (!STAGGER || warp < 4) named_bar(1, 384); }
        else {
#pragma unroll
            for (int i = 0; i < 4; i++) asm volatile("prefetch.global.L2 [%0];" :: "l"(wslice + (size_t)((tid & 127) + 128 * i) * DM));
        }
        __syncwarp();
        if (tid == 0) TSS(18, 4 * ch);
        const uint32_t sh = wb + 80 + 11 * SD_ROW;
#pragma unroll
        for (int p = 0; p < 8; p++) {
            uint4 v;
            asm volatile("ld.shared.v4.u32 {%0,%1,%2,%3}, [%4];" : "=r"(v.x), "=r"(v.y), "=r"(v.z), "=r"(v.w) : "r"(ub + p * SD_ROW + lane * 16) : "memory");
            uint32_t pv = __shfl_up_sync(0xffffffffu, v.w, 1);
            pv = lane == 0 ? 0u : pv;
            asm volatile("st.shared.v4.u32 [%0], {%1,%2,%3,%4};" :: "r"(sh + (p - 8) * SD_ROW + lane * 16), "r"(__byte_perm(pv, v.x, 0x5432)), "r"(__byte_perm(v.x, v.y, 0x5432)),
                         "r"(__byte_perm(v.y, v.z, 0x5432)), "r"(__byte_perm(v.z, v.w, 0x5432)) : "memory");
            if (p >= 5) asm volatile("st.shared.v4.u32 [%0], {%1,%2,%3,%4};" :: "r"(sh + (p - 16) * SD_ROW + lane * 16), "r"(pv), "r"(v.x), "r"(v.y), "r"(v.z) : "memory");
        }
        __syncwarp();
        if (tid == 0) TSS(18, 4 * ch + 1);
        float acc[16][4];
#pragma unroll
        for (int i = 0; i < 16; i++) { acc[i][0] = acc[i][1] = acc[i][2] = acc[i][3] = 0.f; }
        {
            const uint32_t ka = wb + SD_TAP + ((g & 1) ? 0 : SD_CPY - 2) + 2 * (2 * tq - g);
            uint32_t b[16][2], b2[14][2];
#pragma unroll
            for (int k = 0; k < 16; k++) { b[k][0] = b[k][1] = 0u; if (k < 14) b2[k][0] = b2[k][1] = 0u; }
#pragma unroll 1
            for (int ps = 0; ps < 14; ps++) {
                const uint32_t pw = __shfl_sync(0xffffffffu, SD_PASS[ps], 0), type = pw & 3u, kp = ka + (pw >> 16);
                const int dl = (pw >> 2) & 7, d0 = (pw >> 8) & 15, d1 = (pw >> 12) & 15;
                uint32_t t[2][4];
                tap_tile(t[0], kp - 32 * d0);
                if (type == 0) {
                    const int p = (lane & 7) - dl;
                    const uint32_t ra = (p < 0 ? sh : ub) + p * SD_ROW + (lane >> 3) * 16;
#pragma unroll
                    for (int k = 0; k < 8; k++)
                        asm volatile("ldmatrix.sync.aligned.m8n8.x4.shared.b16 {%0,%1,%2,%3}, [%4];"
                                     : "=r"(b[2 * k][0]), "=r"(b[2 * k][1]), "=r"(b[2 * k + 1][0]), "=r"(b[2 * k + 1][1]) : "r"(ra + k * 64));
                } else if (type == 2) {
                    const int p = (lane & 15) - 11, xo = 2 * tq - g;
                    const uint32_t qa = (p < 0 ? sh : ub) + p * SD_ROW + (lane >> 4) * 16;
                    const int lx = 6 - 5 * dl, hx = 8 - 3 * dl, ly = 2 - 2 * dl, hy = 4 + 2 * dl;
                    const uint32_t sel[4] = {band2(xo, lx, hx), band2(xo, ly, hy), band2(xo + 8, lx, hx), band2(xo + 8, ly, hy)};
#pragma unroll
                    for (int k = 0; k < 14; k++) {
                        uint32_t q[4];
                        ldsm_x4_t(q, qa + k * 32);
#pragma unroll
                        for (int i = 0; i < 2; i++) {
                            float w[4];
                            mma_z(w, sel, q[2 * i], q[2 * i + 1]);
                            b[k][i] = pack_bf16(w[0], w[1]);
                            b2[k][i] = pack_bf16(w[2], w[3]);
                        }
                    }
                } else if (type == 3) {
#pragma unroll
                    for (int k = 0; k < 14; k++) { b[k][0] = b2[k][0]; b[k][1] = b2[k][1]; }
                }
#pragma unroll
                for (int d = 0; d < 16; d += 2) {
                    if (d >= 8 || d >= d0) {
                        tap_tile(t[1], kp - 32 * (d + 1));
#pragma unroll
                        for (int k = 0; k + d < 16; k++) mma_bf16(acc[k + d], t[0], b[k][0], b[k][1]);
                        if ((d == 2 || d == 4 || d == 8) && d == d1) break;
                        if (d < 14) tap_tile(t[0], kp - 32 * (d + 2));
#pragma unroll
                        for (int k = 0; k + d + 1 < 16; k++) mma_bf16(acc[k + d + 1], t[1], b[k][0], b[k][1]);
                    }
                }
            }
        }
        __syncwarp();
        if (tid == 0) TSS(18, 4 * ch + 2);
        load_prm(d0 + 8 + warp);
        if (ch == 0) { if (lane == 0) wait_cnt(&g_gcnt[0], SD_NCTA * ep); __syncwarp(); }
        if (tid == 0) TSS(18, 4 * ch + 3);
        uint4 gv[8];
#pragma unroll
        for (int i = 0; i < 8; i++) gv[i] = __ldcg(reinterpret_cast<const uint4*>(g_gate) + lane + 32 * i);
        const uint32_t dd = __byte_perm(*reinterpret_cast<const unsigned short*>(dskip + d), 0u, 0x1010);
#pragma unroll
        for (int i = 0; i < 8; i++) {
            uint32_t u[4];
            ldsm_x4_t(u, ub + (lane & 7) * SD_ROW + (lane >> 3) * 16 + i * 64);
            asm volatile("stmatrix.sync.aligned.m8n8.x4.shared.b16 [%0], {%1,%2,%3,%4};"
                         :: "r"(wb + (lane + 32 * i) * 16),
                            "r"(bf2_add(pack_bf16(acc[2 * i][0], acc[2 * i][1]), bf2_mul(u[0], dd))), "r"(bf2_add(pack_bf16(acc[2 * i][2], acc[2 * i][3]), bf2_mul(u[1], dd))),
                            "r"(bf2_add(pack_bf16(acc[2 * i + 1][0], acc[2 * i + 1][1]), bf2_mul(u[2], dd))), "r"(bf2_add(pack_bf16(acc[2 * i + 1][2], acc[2 * i + 1][3]), bf2_mul(u[3], dd))) : "memory");
        }
        if (GATE_Y) gate(tick);
        __syncwarp();
#pragma unroll
        for (int i = 0; i < 8; i++) {
            const uint4 y = *reinterpret_cast<const uint4*>(tab + (lane + 32 * i) * 4);
            *reinterpret_cast<uint4*>(g_y + (((lane >> 1) + 16 * i) * DM + d) * 16 + (lane & 1) * 8) =
                make_uint4(bf2_mul(bf2_sub(0x3f803f80u, gv[i].x), y.x), bf2_mul(bf2_sub(0x3f803f80u, gv[i].y), y.y),
                           bf2_mul(bf2_sub(0x3f803f80u, gv[i].z), y.z), bf2_mul(bf2_sub(0x3f803f80u, gv[i].w), y.w));
        }
        __syncwarp();
        TS3(22 + 2 * ch);
    }
}
__device__ __forceinline__ void s4d_stage_u(unsigned char* smem_raw, const bf16* __restrict__ x, int pt) {
    const int p = pt & 7, w0 = pt >> 3;
    const uint4* src = reinterpret_cast<const uint4*>(x + (size_t)(16 * w0 + p) * DM + blockIdx.x * SD_CH);
    uint32_t* dst = reinterpret_cast<uint32_t*>(smem_raw + p * SD_ROW) + w0;
#pragma unroll 1
    for (int b = 0; b < 4; b++) {
        uint4 v[2][2][2];
#pragma unroll
        for (int i = 0; i < 8; i++) v[i >> 2][(i >> 1) & 1][i & 1] = src[((b * 2 + (i >> 2)) * 256 + ((i >> 1) & 1) * 8) * (DM / 8) + (i & 1)];
#pragma unroll
        for (int i = 0; i < 4; i++) {
            const uint32_t* lo = reinterpret_cast<const uint32_t*>(&v[i >> 1][0][i & 1]);
            const uint32_t* hi = reinterpret_cast<const uint32_t*>(&v[i >> 1][1][i & 1]);
#pragma unroll
            for (int c = 0; c < 8; c++) dst[((i & 1) * 8 + c) * (SD_U / 4) + (b * 2 + (i >> 1)) * 16] = __byte_perm(lo[c >> 1], hi[c >> 1], (c & 1) ? 0x7632 : 0x5410);
        }
    }
    asm volatile("bar.arrive 1, 384;" ::: "memory");
}

constexpr int WOC = DM / 3;
constexpr int TBUF = 5 * DH * 16;
constexpr int XBUF = SEG * DM * 2;
constexpr int SM_BAR = 0;
constexpr int B_SB = 0, B_VX = 16, B_XT = 32, B_XF = 144, B_W = 64, B_E = 136;
constexpr int SM_SC = 256;
constexpr int SM_F = SM_SC + 1280;
constexpr int SM_VM = SM_F + 2048;
constexpr int SM_S = SM_VM + 2048;
constexpr int SM_O = SM_S + 2560;
constexpr int SM_M = SM_O + 2048;
constexpr int SM_WS = 19456;
constexpr int SM_T = SM_WS + 49152;
constexpr int SM_VX = SM_T + 4 * TBUF;
constexpr int SM_X = SM_VX + 2 * 8192;
constexpr int SM_X01 = SM_WS + DM * DH * 2;
__host__ __device__ constexpr int x01_off(int b) { return b < 2 ? 1024 + b * 9216 : SM_X01 + (b == 2 ? 6 : b - 3) * 9216; }
constexpr int CH_SMEM = SM_X01 + 8 * 8192;
static_assert(SM_M + DM * 16 <= SM_WS && SM_X + 13 * 8192 <= CH_SMEM && NS <= 10 && CH_SMEM <= 232448 && SM_X % 1024 == 0 && SM_X01 % 1024 == 0 && 1024 + 2 * 9216 <= SM_WS, "smem");
__device__ __forceinline__ uint32_t clock32() { uint32_t t; asm volatile("mov.u32 %0, %%clock;" : "=r"(t) :: "memory"); return t; }

__device__ __forceinline__ uint32_t mapa(uint32_t a, uint32_t rank) {
    uint32_t r; asm volatile("mapa.shared::cluster.u32 %0, %1, %2;" : "=r"(r) : "r"(a), "r"(rank)); return r;
}
__device__ __forceinline__ void st_async32(uint32_t addr, uint32_t v, uint32_t mbar) {
    asm volatile("st.async.weak.shared::cluster.mbarrier::complete_tx::bytes.b32 [%0], %1, [%2];" :: "r"(addr), "r"(v), "r"(mbar) : "memory");
}
__device__ __forceinline__ void mbar_init(uint32_t bar, uint32_t cnt) {
    asm volatile("mbarrier.init.shared::cta.b64 [%0], %1;" :: "r"(bar), "r"(cnt) : "memory");
}
__device__ __forceinline__ void mbar_expect(uint32_t bar, uint32_t bytes) {
    asm volatile("mbarrier.arrive.expect_tx.shared::cta.b64 _, [%0], %1;" :: "r"(bar), "r"(bytes) : "memory");
}
__device__ __forceinline__ void mbar_wait(uint32_t bar, uint32_t parity) {
    unsigned it = 0;
    uint32_t ok;
    do {
        ++it;
        asm volatile("{\n.reg .pred p;\nmbarrier.try_wait.parity.shared::cta.b64 p, [%1], %2;\nselp.u32 %0, 1, 0, p;\n}" : "=r"(ok) : "r"(bar), "r"(parity) : "memory");
    } while ((ok == 0u) & (it < SPIN_LIMIT));
}
__device__ __forceinline__ void mbar_wait_fast(uint32_t bar, uint32_t parity) {
    mbar_wait(bar, parity);
}
__device__ __forceinline__ void mbar_wait_long(uint32_t bar, uint32_t parity) {
    unsigned it = 0;
    while (true) {
        uint32_t ok;
        asm volatile("{\n.reg .pred p;\nmbarrier.try_wait.parity.shared::cta.b64 p, [%1], %2, %3;\nselp.u32 %0, 1, 0, p;\n}"
                     : "=r"(ok) : "r"(bar), "r"(parity), "r"(20000u) : "memory");
        if (ok || ++it >= SPIN_LIMIT) break;
    }
}
__device__ __forceinline__ bool mbar_test(uint32_t bar, uint32_t parity) {
    uint32_t ok;
    asm volatile("{\n.reg .pred p;\nmbarrier.test_wait.parity.shared::cta.b64 p, [%1], %2;\nselp.u32 %0, 1, 0, p;\n}" : "=r"(ok) : "r"(bar), "r"(parity) : "memory");
    return ok != 0u;
}
__device__ __forceinline__ uint64_t policy_evict_first() {
    uint64_t pol; asm volatile("createpolicy.fractional.L2::evict_first.b64 %0, 1.0;" : "=l"(pol)); return pol;
}
__device__ __forceinline__ void cluster_sync_all() {
    asm volatile("barrier.cluster.arrive.release.aligned;\nbarrier.cluster.wait.acquire.aligned;" ::: "memory");
}
__device__ __forceinline__ uint4 ld_vol_u4(const uint4* p) {
    uint4 v; asm volatile(LDV4 : "=r"(v.x), "=r"(v.y), "=r"(v.z), "=r"(v.w) : "l"(p) : "memory"); return v;
}
__device__ __forceinline__ void ld_vol_u4_p(uint4& v, const uint4* p, uint32_t pred) {
    asm volatile("{\n.reg .pred p;\nsetp.ne.u32 p, %5, 0;\n@p " LDV4 "\n}"
                 : "+r"(v.x), "+r"(v.y), "+r"(v.z), "+r"(v.w) : "l"(p), "r"(pred) : "memory");
}
__device__ __forceinline__ void st_vol_u4(uint4* p, uint4 v) {
    asm volatile(STV4 :: "l"(p), "r"(v.x), "r"(v.y), "r"(v.z), "r"(v.w) : "memory");
}
__device__ __forceinline__ void mma_bf16_r(float (&d)[4], uint32_t a0, uint32_t a1, uint32_t a2, uint32_t a3, uint32_t b0, uint32_t b1) {
    asm volatile("mma.sync.aligned.m16n8k16.row.col.f32.bf16.bf16.f32 {%0,%1,%2,%3}, {%4,%5,%6,%7}, {%8,%9}, {%0,%1,%2,%3};"
                 : "+f"(d[0]), "+f"(d[1]), "+f"(d[2]), "+f"(d[3])
                 : "r"(a0), "r"(a1), "r"(a2), "r"(a3), "r"(b0), "r"(b1));
}

__device__ __forceinline__ uint64_t smem_desc(uint32_t addr, uint32_t lbo, uint32_t sbo) {
    return (uint64_t)((addr & 0x3FFFF) >> 4) | ((uint64_t)(lbo >> 4) << 16) | ((uint64_t)(sbo >> 4) << 32);
}
__device__ __forceinline__ void wg_fence() { asm volatile("wgmma.fence.sync.aligned;" ::: "memory"); }
__device__ __forceinline__ void wg_commit() { asm volatile("wgmma.commit_group.sync.aligned;" ::: "memory"); }
__device__ __forceinline__ void wg_wait0() { asm volatile("wgmma.wait_group.sync.aligned 0;" ::: "memory"); }
__device__ __forceinline__ void fence_async() { asm volatile("fence.proxy.async.shared::cta;" ::: "memory"); }
__device__ __forceinline__ void wgmma_n64_ss(float (&d)[32], uint64_t adesc, uint64_t bdesc) {
    asm volatile("{\n.reg .pred p;\nsetp.eq.b32 p, 0, 0;\n"
                 "wgmma.mma_async.sync.aligned.m64n64k16.f32.bf16.bf16 {%0,%1,%2,%3,%4,%5,%6,%7,%8,%9,%10,%11,%12,%13,%14,%15,%16,%17,%18,%19,%20,%21,%22,%23,%24,%25,%26,%27,%28,%29,%30,%31}, %32, %33, p, 1, 1, 1, 0;\n}"
                 : "+f"(d[0]), "+f"(d[1]), "+f"(d[2]), "+f"(d[3]), "+f"(d[4]), "+f"(d[5]), "+f"(d[6]), "+f"(d[7]), "+f"(d[8]), "+f"(d[9]), "+f"(d[10]), "+f"(d[11]), "+f"(d[12]), "+f"(d[13]), "+f"(d[14]), "+f"(d[15]), "+f"(d[16]), "+f"(d[17]), "+f"(d[18]), "+f"(d[19]), "+f"(d[20]), "+f"(d[21]), "+f"(d[22]), "+f"(d[23]), "+f"(d[24]), "+f"(d[25]), "+f"(d[26]), "+f"(d[27]), "+f"(d[28]), "+f"(d[29]), "+f"(d[30]), "+f"(d[31])
                 : "l"(adesc), "l"(bdesc));
}
__device__ __forceinline__ void wgmma_n72_ss(float (&d)[36], uint64_t adesc, uint64_t bdesc) {
    asm volatile("{\n.reg .pred p;\nsetp.eq.b32 p, 0, 0;\n"
                 "wgmma.mma_async.sync.aligned.m64n72k16.f32.bf16.bf16 {%0,%1,%2,%3,%4,%5,%6,%7,%8,%9,%10,%11,%12,%13,%14,%15,%16,%17,%18,%19,%20,%21,%22,%23,%24,%25,%26,%27,%28,%29,%30,%31,%32,%33,%34,%35}, %36, %37, p, 1, 1, 1, 0;\n}"
                 : "+f"(d[0]), "+f"(d[1]), "+f"(d[2]), "+f"(d[3]), "+f"(d[4]), "+f"(d[5]), "+f"(d[6]), "+f"(d[7]), "+f"(d[8]), "+f"(d[9]), "+f"(d[10]), "+f"(d[11]), "+f"(d[12]), "+f"(d[13]), "+f"(d[14]), "+f"(d[15]), "+f"(d[16]), "+f"(d[17]), "+f"(d[18]), "+f"(d[19]), "+f"(d[20]), "+f"(d[21]), "+f"(d[22]), "+f"(d[23]), "+f"(d[24]), "+f"(d[25]), "+f"(d[26]), "+f"(d[27]), "+f"(d[28]), "+f"(d[29]), "+f"(d[30]), "+f"(d[31]), "+f"(d[32]), "+f"(d[33]), "+f"(d[34]), "+f"(d[35])
                 : "l"(adesc), "l"(bdesc));
}
__device__ __forceinline__ void tma_2d(uint32_t dst, const CUtensorMap* tm, int c0, int c1, uint32_t mbar) {
    asm volatile("cp.async.bulk.tensor.2d.shared::cluster.global.tile.mbarrier::complete_tx::bytes [%0], [%1, {%2, %3}], [%4];"
                 :: "r"(dst), "l"(tm), "r"(c0), "r"(c1), "r"(mbar) : "memory");
}

__device__ __forceinline__ void bulk_g2s(uint32_t dst, const void* src, uint32_t bytes, uint32_t mbar) {
    asm volatile("cp.async.bulk.shared::cluster.global.mbarrier::complete_tx::bytes [%0], [%1], %2, [%3];"
                 :: "r"(dst), "l"(src), "r"(bytes), "r"(mbar) : "memory");
}
__device__ __forceinline__ void bulk_g2s_h(uint32_t dst, const void* src, uint32_t bytes, uint32_t mbar, uint64_t pol) {
    asm volatile("cp.async.bulk.shared::cluster.global.mbarrier::complete_tx::bytes.L2::cache_hint [%0], [%1], %2, [%3], %4;"
                 :: "r"(dst), "l"(src), "r"(bytes), "r"(mbar), "l"(pol) : "memory");
}
__device__ __forceinline__ void tma_2d_mc(uint32_t dst, const CUtensorMap* tm, int c0, int c1, uint32_t mbar) {
    asm volatile("cp.async.bulk.tensor.2d.shared::cluster.global.tile.mbarrier::complete_tx::bytes.multicast::cluster [%0], [%1, {%2, %3}], [%4], %5;"
                 :: "r"(dst), "l"(tm), "r"(c0), "r"(c1), "r"(mbar), "h"((unsigned short)7) : "memory");
}
__device__ __forceinline__ void bulk_s2s(uint32_t dst, uint32_t src, uint32_t bytes, uint32_t mbar) {
    asm volatile("cp.async.bulk.shared::cluster.shared::cta.mbarrier::complete_tx::bytes [%0], [%1], %2, [%3];"
                 :: "r"(dst), "r"(src), "r"(bytes), "r"(mbar) : "memory");
}
__device__ __forceinline__ void wgmma_n40_ss(float (&d)[20], uint64_t adesc, uint64_t bdesc, int scale_d) {
    asm volatile("{\n.reg .pred p;\nsetp.ne.b32 p, %22, 0;\n"
                 "wgmma.mma_async.sync.aligned.m64n40k16.f32.bf16.bf16 {%0,%1,%2,%3,%4,%5,%6,%7,%8,%9,%10,%11,%12,%13,%14,%15,%16,%17,%18,%19}, %20, %21, p, 1, 1, 1, 1;\n}"
                 : "+f"(d[0]), "+f"(d[1]), "+f"(d[2]), "+f"(d[3]), "+f"(d[4]), "+f"(d[5]), "+f"(d[6]), "+f"(d[7]),
                   "+f"(d[8]), "+f"(d[9]), "+f"(d[10]), "+f"(d[11]), "+f"(d[12]), "+f"(d[13]), "+f"(d[14]), "+f"(d[15]),
                   "+f"(d[16]), "+f"(d[17]), "+f"(d[18]), "+f"(d[19])
                 : "l"(adesc), "l"(bdesc), "r"(scale_d));
}
__device__ __forceinline__ void wgmma_n64_z(float (&d)[32], const uint32_t (&a)[4], uint64_t bdesc) {
    asm volatile("{\n.reg .pred p;\nsetp.ne.b32 p, 0, 0;\n"
                 "wgmma.mma_async.sync.aligned.m64n64k16.f32.bf16.bf16 {%0,%1,%2,%3,%4,%5,%6,%7,%8,%9,%10,%11,%12,%13,%14,%15,%16,%17,%18,%19,%20,%21,%22,%23,%24,%25,%26,%27,%28,%29,%30,%31}, {%32,%33,%34,%35}, %36, p, 1, 1, 0;\n}"
                 : "=f"(d[0]), "=f"(d[1]), "=f"(d[2]), "=f"(d[3]), "=f"(d[4]), "=f"(d[5]), "=f"(d[6]), "=f"(d[7]),
                   "=f"(d[8]), "=f"(d[9]), "=f"(d[10]), "=f"(d[11]), "=f"(d[12]), "=f"(d[13]), "=f"(d[14]), "=f"(d[15]),
                   "=f"(d[16]), "=f"(d[17]), "=f"(d[18]), "=f"(d[19]), "=f"(d[20]), "=f"(d[21]), "=f"(d[22]), "=f"(d[23]),
                   "=f"(d[24]), "=f"(d[25]), "=f"(d[26]), "=f"(d[27]), "=f"(d[28]), "=f"(d[29]), "=f"(d[30]), "=f"(d[31])
                 : "r"(a[0]), "r"(a[1]), "r"(a[2]), "r"(a[3]), "l"(bdesc));
}
__device__ __forceinline__ void wgmma_n64(float (&d)[32], const uint32_t (&a)[4], uint64_t bdesc, int scale_d) {
    asm volatile("{\n.reg .pred p;\nsetp.ne.b32 p, %37, 0;\n"
                 "wgmma.mma_async.sync.aligned.m64n64k16.f32.bf16.bf16 {%0,%1,%2,%3,%4,%5,%6,%7,%8,%9,%10,%11,%12,%13,%14,%15,%16,%17,%18,%19,%20,%21,%22,%23,%24,%25,%26,%27,%28,%29,%30,%31}, {%32,%33,%34,%35}, %36, p, 1, 1, 0;\n}"
                 : "+f"(d[0]), "+f"(d[1]), "+f"(d[2]), "+f"(d[3]), "+f"(d[4]), "+f"(d[5]), "+f"(d[6]), "+f"(d[7]),
                   "+f"(d[8]), "+f"(d[9]), "+f"(d[10]), "+f"(d[11]), "+f"(d[12]), "+f"(d[13]), "+f"(d[14]), "+f"(d[15]),
                   "+f"(d[16]), "+f"(d[17]), "+f"(d[18]), "+f"(d[19]), "+f"(d[20]), "+f"(d[21]), "+f"(d[22]), "+f"(d[23]),
                   "+f"(d[24]), "+f"(d[25]), "+f"(d[26]), "+f"(d[27]), "+f"(d[28]), "+f"(d[29]), "+f"(d[30]), "+f"(d[31])
                 : "r"(a[0]), "r"(a[1]), "r"(a[2]), "r"(a[3]), "l"(bdesc), "r"(scale_d));
}

constexpr int SB_FULL = 0, SB_EMPTY = 64, SB_QKF = 128, SB_VF = 144, SB_QKE = 160, SB_VE = 176, SB_OF = 192, SB_WO = 208, SB_TICK = 216, SB_SEEN = 224, SB_FI = 232, SB_REQ = 240;
constexpr int AT_0 = 256, AT_ST = 10240 + 2 * 9216;
constexpr int FS_A = 58368;
constexpr int FS_P = FS_A + 131072;
constexpr int FS_I = FS_P + 16384;
constexpr int FS_O = FS_I + 12288;
constexpr int FS_Z = FS_O + 12288, FS_G = AT_0 + 2 * AT_ST;
constexpr int SIDE_SMEM = FS_Z + 2048;
static_assert(SIDE_SMEM <= 232448 && FS_G + 128 <= FS_A && FS_A + SD_SMEM <= SIDE_SMEM, "smem");

__device__ __forceinline__ void wg_wait1() { asm volatile("wgmma.wait_group.sync.aligned 1;" ::: "memory"); }
__device__ __forceinline__ void mbar_arrive(uint32_t bar) { asm volatile("mbarrier.arrive.shared::cta.b64 _, [%0];" :: "r"(bar) : "memory"); }
__device__ __forceinline__ void wait_cnt_rlx(const unsigned* p, unsigned target, bool urgent) {
    unsigned it = 0, v;
    while (true) {
        asm volatile("ld.relaxed.gpu.global.u32 %0, [%1];" : "=r"(v) : "l"(p) : "memory");
        if ((int)(v - target) >= 0 || ++it >= SPIN_LIMIT) break;
        if (!urgent) __nanosleep(RLX_SLEEP);
    }
}

__device__ __forceinline__ float xrow_softmax(float (&sc)[20], uint32_t (&p)[5], int wq, int lane) {
    constexpr float EC = (float)(1.4426950408889634 * 0.08838834764831845);
    const int lim = 8 * wq + (lane >> 2) - 2 * (lane & 3);
    float mx = fmaxf(sc[0], sc[1]);
#pragma unroll
    for (int j = 1; j < 5; j++) {
        sc[4 * j] = 8 * j - 8 > lim ? -INFINITY : sc[4 * j];
        sc[4 * j + 1] = 8 * j - 7 > lim ? -INFINITY : sc[4 * j + 1];
    }
    mx = fmaxf(fmaxf(mx, fmaxf(fmaxf(sc[4], sc[5]), fmaxf(sc[8], sc[9]))), fmaxf(fmaxf(sc[12], sc[13]), fmaxf(sc[16], sc[17])));
    {
        const float m1 = __shfl_xor_sync(0xffffffffu, mx, 1), m2 = __shfl_xor_sync(0xffffffffu, mx, 2), m3 = __shfl_xor_sync(0xffffffffu, mx, 3);
        mx = fmaxf(fmaxf(mx, m1), fmaxf(m2, m3)) * EC;
    }
    float sum = 0.f;
#pragma unroll
    for (int j = 0; j < 5; j++) {
        float e0, e1;
        asm("ex2.approx.ftz.f32 %0, %1;" : "=f"(e0) : "f"(fmaf(sc[4 * j], EC, -mx)));
        asm("ex2.approx.ftz.f32 %0, %1;" : "=f"(e1) : "f"(fmaf(sc[4 * j + 1], EC, -mx)));
        p[j] = pack_bf16(e0, e1);
        sum += e0 + e1;
    }
    return sum;
}
__device__ __forceinline__ float xrow_inv(float sum) {
    sum += __shfl_xor_sync(0xffffffffu, sum, 1);
    sum += __shfl_xor_sync(0xffffffffu, sum, 2);
    float r;
    asm("rcp.approx.ftz.f32 %0, %1;" : "=f"(r) : "f"(sum));
    return r;
}

__device__ __forceinline__ void stsm_x4(uint32_t addr, uint32_t r0, uint32_t r1, uint32_t r2, uint32_t r3) {
    asm volatile("stmatrix.sync.aligned.m8n8.x4.shared.b16 [%0], {%1,%2,%3,%4};" :: "r"(addr), "r"(r0), "r"(r1), "r"(r2), "r"(r3) : "memory");
}
__device__ __forceinline__ void xrow_pv(uint32_t (&ob)[16], const uint32_t (&p)[5], float psum, uint32_t vt) {
    float o[32];
    const uint64_t dv = smem_desc(vt, 2048, 128);
    uint32_t pa[6][4];
#pragma unroll
    for (int i = 0; i < 6; i++) {
        const int ks = i >> 1, hf = i & 1;
        pa[i][hf] = p[2 * ks]; pa[i][hf ^ 1] = 0u;
        pa[i][2 + hf] = ks < 2 ? p[ks < 2 ? 2 * ks + 1 : 0] : 0u; pa[i][3 - hf] = 0u;
    }
    wg_fence();
#pragma unroll
    for (int i = 0; i < 6; i++) { if (i == 0) wgmma_n64_z(o, pa[0], dv); else wgmma_n64(o, pa[i], dv + (uint64_t)((i & 1) * 64 + (i >> 1) * 256), 1); }
    wg_commit();
    const float inv = xrow_inv(psum);
    wg_wait0();
#pragma unroll
    for (int i = 0; i < 8; i++) { ob[i] = pack_bf16(o[4 * i] * inv, o[4 * i + 1] * inv); ob[8 + i] = pack_bf16(o[4 * i + 2] * inv, o[4 * i + 3] * inv); }
}
__device__ __forceinline__ uint32_t h2_to_bf2(uint32_t h) {
    uint32_t r;
    asm("{\n.reg .f16 l, h;\n.reg .f32 a, b;\nmov.b32 {l, h}, %1;\ncvt.f32.f16 a, l;\ncvt.f32.f16 b, h;\ncvt.rn.bf16x2.f32 %0, b, a;\n}" : "=r"(r) : "r"(h));
    return r;
}
__device__ __forceinline__ uint32_t max_abs2(uint32_t a, uint32_t b) { uint32_t r; asm("max.NaN.xorsign.abs.bf16x2 %0, %1, %2;" : "=r"(r) : "r"(a), "r"(b)); return r; }
__device__ __forceinline__ uint32_t movm(uint32_t v) {
    uint32_t r; asm volatile("movmatrix.sync.aligned.m8n8.trans.b16 %0, %1;" : "=r"(r) : "r"(v)); return r;
}
__device__ __forceinline__ void bar_arrive(int id, int n) { asm volatile("bar.arrive %0, %1;" :: "r"(id), "r"(n) : "memory"); }
__device__ __forceinline__ void lds64(uint32_t& a, uint32_t& b, uint32_t addr) {
    asm volatile("ld.shared.v2.u32 {%0,%1}, [%2];" : "=r"(a), "=r"(b) : "r"(addr) : "memory");
}
__device__ __forceinline__ void lds64f(float& a, float& b, uint32_t addr) {
    asm volatile("ld.shared.v2.f32 {%0,%1}, [%2];" : "=f"(a), "=f"(b) : "r"(addr) : "memory");
}
__device__ __forceinline__ void st_async64(uint32_t addr, uint32_t a, uint32_t b, uint32_t mbar) {
    asm volatile("st.async.weak.shared::cluster.mbarrier::complete_tx::bytes.v2.b32 [%0], {%1,%2}, [%3];" :: "r"(addr), "r"(a), "r"(b), "r"(mbar) : "memory");
}
__device__ __forceinline__ void mma_z(float (&d)[4], const uint32_t (&a)[4], uint32_t b0, uint32_t b1) {
    asm volatile("mma.sync.aligned.m16n8k16.row.col.f32.bf16.bf16.f32 {%0,%1,%2,%3}, {%4,%5,%6,%7}, {%8,%9}, {%10,%10,%10,%10};"
                 : "=f"(d[0]), "=f"(d[1]), "=f"(d[2]), "=f"(d[3])
                 : "r"(a[0]), "r"(a[1]), "r"(a[2]), "r"(a[3]), "r"(b0), "r"(b1), "f"(0.f));
}
__device__ __forceinline__ void mma_k8(float (&d)[4], uint32_t a0, uint32_t a1, uint32_t b) {
    asm volatile("mma.sync.aligned.m16n8k8.row.col.f32.bf16.bf16.f32 {%0,%1,%2,%3}, {%4,%5}, {%6}, {%0,%1,%2,%3};"
                 : "+f"(d[0]), "+f"(d[1]), "+f"(d[2]), "+f"(d[3]) : "r"(a0), "r"(a1), "r"(b));
}
__global__ void __launch_bounds__(512, 1) k_side(const __grid_constant__ CUtensorMap tmo, const bf16* __restrict__ x, const bf16* __restrict__ logA, const bf16* __restrict__ Aim,
                                                 const bf16* __restrict__ Cre, const bf16* __restrict__ Cim, const bf16* __restrict__ logdt,
                                                 const bf16* __restrict__ Wo, const bf16* __restrict__ dskip, const bf16* __restrict__ gw,
                                                 bf16* __restrict__ out) {
    extern __shared__ __align__(1024) unsigned char smem_raw[];
    const uint32_t sbase = smem_u32(smem_raw);
    const int tid = threadIdx.x, warp = __shfl_sync(0xffffffffu, tid >> 5, 0), lane = tid & 31, cta = blockIdx.x;
    const int cb = cta >> 2, kq = cta & 3;
    if (tid == 0) {
        for (int i = 0; i < 8; i++) { mbar_init(sbase + SB_FULL + 8 * i, 1); mbar_init(sbase + SB_EMPTY + 8 * i, 4); }
        for (int i = 0; i < 2; i++) {
            mbar_init(sbase + SB_QKF + 8 * i, 1); mbar_init(sbase + SB_VF + 8 * i, 1); mbar_init(sbase + SB_QKE + 8 * i, 4);
            mbar_init(sbase + SB_VE + 8 * i, 1); mbar_init(sbase + SB_OF + 8 * i, 4);
        }
        mbar_init(sbase + SB_WO, 1);
        mbar_init(sbase + SB_FI, 1);
        mbar_init(sbase + SB_REQ, 4);
        *reinterpret_cast<uint2*>(smem_raw + SB_TICK) = make_uint2(0u, 0u);
        *reinterpret_cast<uint32_t*>(smem_raw + SB_SEEN) = 0u;
        asm volatile("fence.mbarrier_init.release.cluster;" ::: "memory");
    }
    TS3(0);
    unsigned ep;
    asm volatile("ld.volatile.global.u32 %0, [%1];" : "=r"(ep) : "l"(&g_epoch) : "memory");
    ep += 1u;
    asm volatile("fence.proxy.async;" ::: "memory");
    __syncthreads();
    if (warp >= 12) {
      asm volatile("setmaxnreg.dec.sync.aligned.u32 40;");
      if (SIDE_WAIT > 0) __nanosleep(SIDE_WAIT);
      {
        uint32_t gwv[9];
#pragma unroll
        for (int i = 0; i < 9; i++) gwv[i] = reinterpret_cast<const uint32_t*>(gw)[lane + 32 * i];
#pragma unroll 1
        for (int i = 0; i < 8; i++) {
            uint32_t xv[2][9];
            float sm[2];
#pragma unroll
            for (int j = 0; j < 2; j++) {
                const int t = min(cta * 57 + 8 * i + 4 * j + warp - 12, S_LEN - 1);
#pragma unroll
                for (int k = 0; k < 9; k++) xv[j][k] = reinterpret_cast<const uint32_t*>(x + t * DM)[lane + 32 * k];
            }
#pragma unroll
            for (int j = 0; j < 2; j++) {
                sm[j] = 0.f;
#pragma unroll
                for (int k = 0; k < 9; k++) {
                    const uint32_t pr = bf2_mul(xv[j][k], gwv[k]);
                    sm[j] += __uint_as_float(pr << 16) + __uint_as_float(pr & 0xffff0000u);
                }
            }
            float v = (lane < 16 ? sm[0] : sm[1]) + __shfl_xor_sync(0xffffffffu, lane < 16 ? sm[1] : sm[0], 16);
#pragma unroll
            for (int o = 8; o; o >>= 1) v += __shfl_xor_sync(0xffffffffu, v, o);
            const float gv = 1.f / (1.f + expf(-bf16r(v)));
            const int tt = 8 * i + 4 * (lane >> 4) + warp - 12;
            if ((lane & 15) == 0 && tt < 57 && cta * 57 + tt < S_LEN) g_gate[cta * 57 + tt] = __float2bfloat16_rn(gv);
        }
        named_bar(2, 128);
        if (tid == 480) {
            __threadfence();
            asm volatile("red.relaxed.gpu.global.add.u32 [%0], 1;" :: "l"(&g_gcnt[0]) : "memory");
        }
        __syncwarp();
      }
      if (warp == 12 || warp == 15) {
        named_bar(3, 320);
        if (tid == 384) {
            fence_async();
            mbar_expect(sbase + SB_WO, 131072);
#pragma unroll 1
            for (int i = 0; i < 8; i++) {
                gate(sbase + SB_TICK);
                tma_2d(sbase + FS_A + i * 16384, &tmo, cb * 64, kq * 1024 + i * 128, sbase + SB_WO);
                __nanosleep(150);
            }
            TSS(17, 2);
        }
        if (tid == 480) {
            __threadfence();
            asm volatile("red.relaxed.gpu.global.add.u32 [%0], 1;" :: "l"(&g_gcnt[32]) : "memory");
            TSS(17, 3);
        }
        __syncwarp();
        named_bar(7, 320);
        if (lane == 0) {
            const int pi = warp == 12 ? 0 : 1, kb = 2 * kq + pi;
            fence_async();
            for (int pr = 0; pr < NSEG / 2; pr++) {
                const bool gon = pr < NSEG / 2 - UNGATE_G;
                wait_cnt_rlx(&g_prog[pr * 8 + kb], 8u * ep, pr >= NSEG / 2 - 2);
                if (pi == 0) asm volatile("st.volatile.shared.u32 [%0], %1;" :: "r"(sbase + SB_SEEN), "r"(pr + 1) : "memory");
                if (pr >= 30 && pi == 0) TSS(4 + pr - 30, 0);
                if (pr == 31) TS3P(26);
                if (pr == 30) TS3P(1);
#pragma unroll
                for (int j = 0; j < 4; j++) {
                    const int st = 4 * pi + j;
                    mbar_wait_long(sbase + SB_EMPTY + 8 * st, ((uint32_t)pr & 1u) ^ 1u);
                    mbar_expect(sbase + SB_FULL + 8 * st, X_OXSZ);
                    if (gon) gate(sbase + SB_TICK);
                    bulk_g2s(sbase + FS_A + st * 16384, g_ox + ((size_t)(pr * NH + 4 * kb + j)) * 8192, X_OXSZ, sbase + SB_FULL + 8 * st);
                }
            }
        }
        __syncwarp();
      } else if (warp == 13) {
        if (lane == 0) {
            const uint64_t pol = policy_evict_first();
            bool next_ok = false;
            for (int seg = 0; seg < NATT; seg++) {
                const uint32_t st = seg & 1, ph = (uint32_t)(seg >> 1) & 1u, ab = sbase + AT_0 + st * AT_ST;
                if (!next_ok) {
                    const unsigned* fp = &g_flag[(cta & (NH - 1)) * NSEG + seg];
                    unsigned it = 0, v0, v1;
                    while (true) {
                        asm volatile("ld.relaxed.gpu.global.u32 %0, [%1];" : "=r"(v0) : "l"(fp) : "memory");
                        asm volatile("ld.relaxed.gpu.global.u32 %0, [%1+4];" : "=r"(v1) : "l"(fp) : "memory");
                        read_tick(sbase + SB_TICK);
                        if ((int)(v0 - 3u * ep) >= 0 || ++it >= SPIN_LIMIT) break;
                        if (seg < NSEG - UNGATE || cta >= NH) { __nanosleep(RLX_SLEEP); if (GATE_POLL) gate(sbase + SB_TICK, GP_A, GP_B); }
                    }
                    next_ok = (int)(v1 - 3u * ep) >= 0;
                } else next_ok = false;
                if (cta < NH) {
                    TSA(seg, 0);
                    mbar_wait_long(sbase + SB_QKE + 8 * st, ph ^ 1u);
                    TSA(seg, 1);
                    mbar_expect(sbase + SB_QKF + 8 * st, 2 * 9216);
                    if (seg < NSEG - UNGATE) gate(sbase + SB_TICK, GL_A, GL_B);
                    TSA(seg, 2);
                    bulk_g2s_h(ab + 10240, &g_qkv[seg][cta][0][1024], 9216, sbase + SB_QKF + 8 * st, pol);
                    bulk_g2s_h(ab + 10240 + 9216, &g_qkv[seg][cta][1][1024], 9216, sbase + SB_QKF + 8 * st, pol);
                    mbar_wait_long(sbase + SB_VE + 8 * st, ph ^ 1u);
                    mbar_expect(sbase + SB_VF + 8 * st, 10240);
                    if (seg < NSEG - UNGATE) gate(sbase + SB_TICK, GL_A, GL_B);
                    TSA(seg, 3);
                    bulk_g2s_h(ab, &g_qkv[seg][cta][2][0], 10240, sbase + SB_VF + 8 * st, pol);
                }
            }
        }
        __syncwarp();
      } else if (warp == 14) {
        if (lane == 0) {
            int seg = cta < NH ? 0 : NATT, p = 0;
            unsigned it = 0;
            while ((seg < NATT || p < NSEG / 2 - 1) && ++it < 16 * SPIN_LIMIT) {
                if (p < NSEG / 2 - 1 && mbar_test(sbase + SB_REQ, (uint32_t)p & 1u)) {
                    if (p == 0) { wait_cnt(&g_gcnt[32], SD_NCTA * ep); asm volatile("fence.proxy.async;" ::: "memory"); }
                    mbar_expect(sbase + SB_FI, (p < NSEG / 2 - 2 ? 12288 : 2048 + 32) + 2048 + 32);
                    if (GATE_F && p < NSEG / 2 - UNGATE_G - 1) gate(sbase + SB_TICK);
                    if (p < NSEG / 2 - 2) bulk_g2s(sbase + FS_I, &g_fp[p & 7][cta][0][0], 12288, sbase + SB_FI);
                    else {
                        bulk_g2s(sbase + FS_I, g_y + ((p * 4 + 4 + kq) * DM + cb * 64) * 16, 2048, sbase + SB_FI);
                        bulk_g2s(sbase + FS_G + 32, g_gate + p * 64 + 64 + kq * 16, 32, sbase + SB_FI);
                    }
                    bulk_g2s(sbase + FS_Z, g_y + ((p * 4 + kq) * DM + cb * 64) * 16, 2048, sbase + SB_FI);
                    bulk_g2s(sbase + FS_G, g_gate + p * 64 + kq * 16, 32, sbase + SB_FI);
                    p++;
                } else if (seg < NATT && mbar_test(sbase + SB_OF + 8 * (seg & 1), (uint32_t)(seg >> 1) & 1u)) {
                    const uint32_t st = seg & 1, ab = sbase + AT_0 + st * AT_ST;
                    TSA(seg, 5);
                    if (seg < NSEG - UNGATE) gate(sbase + SB_TICK, GS_A, GS_B);
                    TSA(seg, 6);
                    unsigned char* dst = reinterpret_cast<unsigned char*>(g_ox) + ((size_t)((seg >> 1) * NH + cta)) * 16384 + (seg & 1) * 4096;
                    asm volatile("cp.async.bulk.global.shared::cta.bulk_group [%0], [%1], 4096;" :: "l"(dst), "r"(ab) : "memory");
                    asm volatile("cp.async.bulk.global.shared::cta.bulk_group [%0], [%1], 4096;" :: "l"(dst + 8192), "r"(ab + 4096) : "memory");
                    asm volatile("cp.async.bulk.commit_group;" ::: "memory");
                    asm volatile("cp.async.bulk.wait_group.read 0;" ::: "memory");
                    mbar_arrive(sbase + SB_VE + 8 * st);
                    asm volatile("cp.async.bulk.wait_group 0;" ::: "memory");
                    asm volatile("red.relaxed.gpu.global.add.u32 [%0], 1;" :: "l"(&g_prog[(seg >> 1) * 8 + (cta >> 2)]) : "memory");
                    TSA(seg, 7);
                    seg++;
                } else if (seg < NSEG - UNGATE) __nanosleep(W14_SLEEP);
            }
        }
        __syncwarp();
      }
    } else if (warp >= 8) {
        asm volatile("setmaxnreg.dec.sync.aligned.u32 88;");
        if (SIDE_WAIT > 0) __nanosleep(SIDE_WAIT);
        s4d_stage_u(smem_raw + FS_A, x, tid - 256);
        const int wq = warp - 8;
        for (int seg = 0; seg < (cta < NH ? NATT : 0); seg++) {
            const uint32_t st = seg & 1, ph = (uint32_t)(seg >> 1) & 1u, ab = sbase + AT_0 + st * AT_ST;
            float sc[20];
            if (seg < NSEG - UNGATE) mbar_wait_long(sbase + SB_QKF + 8 * st, ph); else mbar_wait(sbase + SB_QKF + 8 * st, ph);
            if (tid == 256) TSA(seg, 4);
            {
                const uint64_t da = smem_desc(ab + 10240 + 1024, 128, 1024), db = smem_desc(ab + 10240, 128, 2048);
                wg_fence();
#pragma unroll
                for (int ks = 0; ks < 8; ks++) wgmma_n40_ss(sc, da + (uint64_t)((ks >> 2) * 576 + (ks & 3) * 16), db + (uint64_t)((ks >> 2) * 576 + (ks & 3) * 16), ks > 0);
                wg_commit();
                wg_wait0();
            }
            if (lane == 0) mbar_arrive(sbase + SB_QKE + 8 * st);
            uint32_t p[5], ob[16];
            const float psum = xrow_softmax(sc, p, wq, lane);
            mbar_wait(sbase + SB_VF + 8 * st, ph);
            xrow_pv(ob, p, psum, ab);
            named_bar(6, 128);
#pragma unroll
            for (int i = 0; i < 4; i++) stsm_x4(ab + (i >> 1) * 4096 + wq * 1024 + (i & 1) * 512 + lane * 16, ob[4 * i], ob[4 * i + 1], ob[4 * i + 2], ob[4 * i + 3]);
            fence_async();
            __syncwarp();
            if (lane == 0) mbar_arrive(sbase + SB_OF + 8 * st);
        }
    } else {
        asm volatile("setmaxnreg.inc.sync.aligned.u32 192;");
        const int wg = warp >> 2, wq = warp & 3;
        s4d_phase(smem_raw + FS_A, x, logA, Aim, Cre, Cim, logdt, dskip, Wo + (size_t)((2 * kq + wg) * 512) * DM + cb * 64, ep, sbase + SB_TICK);
        TS3(2);
        if (lane == 0) TSS(16, warp);
        named_bar(3, 320);
        if (tid == 0) TSS(17, 0);
        uint32_t wa[32][4];
        mbar_wait_long(sbase + SB_WO, 0);
        if (tid == 0) TSS(17, 1);
        {
            const uint32_t a = sbase + FS_A + wg * 65536 + ((lane >> 4) * 8 + (lane & 7)) * 128 + (((wq * 2 + ((lane >> 3) & 1)) ^ (lane & 7)) << 4);
#pragma unroll
            for (int ks = 0; ks < 32; ks++) ldsm_x4_t(wa[ks], a + ks * 2048);
        }
        named_bar(7, 320);
        TS3(3);
        if (tid == 0) TSS(17, 4);
        auto product = [&](float (&acc)[32], int pr, const int wg) {
                if (pr + wg > 0 && (TURN31 || pr + wg < NSEG / 2)) named_bar(4 + wg, 256);
                const uint64_t db = smem_desc(sbase + FS_A + wg * 65536, 128, 1024);
                TSG(0);
#pragma unroll
                for (int j = 0; j < 4; j++) {
                    mbar_wait(sbase + SB_FULL + 8 * (4 * wg + j), (uint32_t)pr & 1u);
                    if (j == 0) TSG(1);
                    if (j == 3) TSG(2);
                    wg_fence();
#pragma unroll
                    for (int ks = 0; ks < 8; ks++) {
                        if ((j | ks) == 0) wgmma_n64_z(acc, wa[0], db);
                        else wgmma_n64(acc, wa[8 * j + ks], db + (uint64_t)(j * 1024 + (ks >> 2) * 512 + (ks & 3) * 16), 1);
                    }
                    wg_commit();
                    if (j == 3 && pr + (TURN31 ? wg : 1) < NSEG / 2) bar_arrive(4 + (wg ^ 1), 256);
                    if (j > 0) { wg_wait1(); if (lane == 0) mbar_arrive(sbase + SB_EMPTY + 8 * (4 * wg + j - 1)); }
                }
                wg_wait0();
                if (pr == 31) TS3W(27);
                TSG(3);
                if (lane == 0) mbar_arrive(sbase + SB_EMPTY + 8 * (4 * wg + 3));
        };
        if (wg == 1) {
            for (int pr = 0; pr < NSEG / 2; pr++) {
                uint32_t t16 = (uint32_t)(wq * 32 + lane) * 16u;
                asm volatile("" : "+r"(t16));
                float acc[32];
                product(acc, pr, 1);
                    uint32_t tag = ((uint32_t)(pr >> 3) & 1u) ^ 1u;
                    tag = __shfl_sync(0xffffffffu, tag, lane);
                    if (GATE_S && pr < NSEG / 2 - UNGATE_G) gate(sbase + SB_TICK);
                    named_bar(8, 256);
                    unsigned char* dst = reinterpret_cast<unsigned char*>(&g_fp[pr & 7][4 * cb][2 * kq - 2][0]) + t16;
                    const uint32_t own = sbase + FS_O + (pr % 3) * 4096 + t16;
#pragma unroll
                    for (int q = 0; q < 8; q++) {
                        float4 p;
                        asm volatile("ld.shared.v4.f32 {%0,%1,%2,%3}, [%4];" : "=f"(p.x), "=f"(p.y), "=f"(p.z), "=f"(p.w) : "r"(sbase + FS_P + t16 + q * 2048) : "memory");
                        acc[4 * q] = __uint_as_float((__float_as_uint(acc[4 * q] + p.x) & ~1u) | tag); acc[4 * q + 1] = __uint_as_float((__float_as_uint(acc[4 * q + 1] + p.y) & ~1u) | tag);
                        acc[4 * q + 2] = __uint_as_float((__float_as_uint(acc[4 * q + 2] + p.z) & ~1u) | tag); acc[4 * q + 3] = __uint_as_float((__float_as_uint(acc[4 * q + 3] + p.w) & ~1u) | tag);
                    }
#pragma unroll
                    for (int q = 0; q < 8; q++) {
                        asm volatile("{\n.reg .pred p;\nsetp.ne.s32 p, %5, %6;\n@p st.volatile.global.v4.f32 [%0], {%1,%2,%3,%4};\n@!p st.shared.v4.f32 [%7], {%1,%2,%3,%4};\n}"
                                     :: "l"(dst + (q & 1) * 2048), "f"(acc[4 * q]), "f"(acc[4 * q + 1]), "f"(acc[4 * q + 2]), "f"(acc[4 * q + 3]), "r"(q >> 1), "r"(kq),
                                        "r"(own + (q & 1) * 2048) : "memory");
                        if (q & 1) dst += (q >> 1) == kq ? 12288 + 4096 : 12288;
                    }
                    bar_arrive(9, 256);
                    if (pr == 31) TS3W(28);
                TSG(4);
            }
        } else {
          int nsync = 0;
          int np = 1, nf = 0, pr = 0, pf = -1;
          while (true) {
            uint32_t t16 = (uint32_t)(wq * 32 + lane) * 16u;
            asm volatile("" : "+r"(t16));
            if (pr < 0) {
                if (nsync <= pf) { named_bar(9, 256); nsync++; }
                if (lane == 0 && pf < NSEG / 2 - 1) mbar_arrive(sbase + SB_REQ);
            } else {
                float acc[32];
                product(acc, pr, 0);
                if (nsync < pr) { named_bar(9, 256); nsync++; }
#pragma unroll
                for (int q = 0; q < 8; q++)
                    asm volatile("st.shared.v4.f32 [%0], {%1,%2,%3,%4};" :: "r"(sbase + FS_P + t16 + q * 2048), "f"(acc[4 * q]), "f"(acc[4 * q + 1]), "f"(acc[4 * q + 2]), "f"(acc[4 * q + 3]) : "memory");
                bar_arrive(8, 256);
                TSG(4);
            }
            uint32_t w[4] = {0u, 0u, 0u, 0u};
            const int pc = pf;
            if (pf >= 0) {
                const uint32_t tag = ((uint32_t)(pf >> 3) & 1u) ^ 1u;
                uint4 v[8];
                unsigned n = 0;
                const bool last = pf == NSEG / 2 - 1;
                const uint4* src = reinterpret_cast<const uint4*>(reinterpret_cast<const unsigned char*>(&g_fp[pf & 7][cta][0][0]) + t16);
                if (pf >= NSEG / 2 - 2) {
#pragma unroll
                    for (int r = 0; r < 6; r++) v[r] = ld_vol_u4(src + r * 128);
                    mbar_wait(sbase + SB_FI, 0u);
                } else {
                    mbar_wait(sbase + SB_FI, (uint32_t)pf & 1u);
#pragma unroll
                    for (int r = 0; r < 6; r++)
                        asm volatile("ld.shared.v4.u32 {%0,%1,%2,%3}, [%4];" : "=r"(v[r].x), "=r"(v[r].y), "=r"(v[r].z), "=r"(v[r].w) : "r"(sbase + t16 + FS_I + r * 2048) : "memory");
                }
                while (true) {
                    uint32_t any = 0u;
#pragma unroll
                    for (int r = 0; r < 6; r++) {
                        uint32_t c0_, c1_;
                        asm("lop3.b32 %0, %1, %2, %3, 0x7e;" : "=r"(c0_) : "r"(v[r].x), "r"(v[r].y), "r"(tag));
                        asm("lop3.b32 %0, %1, %2, %3, 0x7e;" : "=r"(c1_) : "r"(v[r].z), "r"(v[r].w), "r"(tag));
                        asm("lop3.b32 %0, %1, %2, %3, 0xfe;" : "=r"(any) : "r"(any), "r"(c0_), "r"(c1_));
                    }
                    if (!__any_sync(0xffffffffu, (any & 1u) != 0u) || ++n >= SPIN_LIMIT) break;
                    if (pf < NSEG / 2 - 2) __nanosleep(200);
#pragma unroll
                    for (int r = 0; r < 6; r++) v[r] = ld_vol_u4(src + r * 128);
                }
                if (pf == 31) TS3(29);
                TSG(5);
#pragma unroll
                for (int r = 6; r < 8; r++)
                    asm volatile("ld.shared.v4.u32 {%0,%1,%2,%3}, [%4];" : "=r"(v[r].x), "=r"(v[r].y), "=r"(v[r].z), "=r"(v[r].w)
                                 : "r"(sbase + t16 + FS_O + (pf % 3) * 4096 + (r - 6) * 2048) : "memory");
                uint32_t zv[4], gg[2];
                ldsm_x4_t(zv, sbase + (last ? FS_I : FS_Z) + (wq * 16 + (lane & 15)) * 32 + (lane >> 4) * 16);
#pragma unroll
                for (int k = 0; k < 2; k++) gg[k] = __byte_perm(*reinterpret_cast<const volatile unsigned short*>(smem_raw + FS_G + (last ? 32 : 0) + k * 16 + (lane >> 2) * 2), 0u, 0x1010);
#define PQS(k, f) (((__uint_as_float(v[k].f) + __uint_as_float(v[2 + k].f)) + __uint_as_float(v[4 + k].f)) + __uint_as_float(v[6 + k].f))
#pragma unroll
                for (int k = 0; k < 2; k++) {
                    w[2 * k] = bf2_add(bf2_mul(gg[k], movm(pack_bf16(PQS(k, x), PQS(k, y)))), zv[2 * k]);
                    w[2 * k + 1] = bf2_add(bf2_mul(gg[k], movm(pack_bf16(PQS(k, z), PQS(k, w)))), zv[2 * k + 1]);
                }
#undef PQS
            }
            const bool more = nf < NSEG / 2;
            if (more) {
                uint32_t r;
                asm volatile("{\n.reg .pred p, q;\n.reg .b32 v;\nld.volatile.shared.u32 v, [%1];\nsetp.gt.s32 p, v, %2;\nbar.red.or.pred q, 10, 128, p;\nselp.u32 %0, 1, 0, q;\n}"
                             : "=r"(r) : "r"(sbase + SB_SEEN), "r"(np) : "memory");
                const bool dop = np < NSEG / 2 && (__shfl_sync(0xffffffffu, r, 0) != 0u || nf == np || nf >= NSEG / 2 - 2);
                TSG(6);
                pr = dop ? np++ : -1;
                pf = !dop || nf + (pr == NSEG / 2 - 1 ? 1 : 2) <= pr ? nf++ : -1;
                if (dop && pf >= 0 && lane == 0) mbar_arrive(sbase + SB_REQ);
            }
            if (pc >= 0) {
                unsigned char* op = reinterpret_cast<unsigned char*>(out) + (uint32_t)((pc * 64 + kq * 16 + (lane >> 2)) * DM + cb * 64 + wq * 16 + 2 * (lane & 3)) * 2u;
#pragma unroll
                for (int k = 0; k < 4; k++) *reinterpret_cast<uint32_t*>(op + (k >> 1) * (16 * DM) + (k & 1) * 16) = w[k];
                if ((pc & 1) == 0) TS3(4 + pc / 2);
                if (pc == 31) TS3(25);
            }
            if (!more) break;
          }
        }
        if (cta == 0 && tid == 0) asm volatile("red.relaxed.gpu.global.add.u32 [%0], 1;" :: "l"(&g_epoch) : "memory");
    }
    asm volatile("griddepcontrol.wait;" ::: "memory");
}

template <class F>
__device__ __forceinline__ uint32_t poll_mem(const uint4* src, uint32_t dst, uint32_t t0, F next) {
    uint4 v[6];
    unsigned it = 0;
#pragma unroll
    for (int j = 0; j < 6; j++) v[j] = make_uint4(0u, 0u, 0u, 0u);
    while (clock32() - t0 < POLL_DELAY) {}
    FS(12, 0);
    bool more;
#pragma unroll 1
    do {
        asm volatile("{\n.reg .pred p<6>;\n"
                     "setp.ne.u32 p0, %3, 0x5000;\nsetp.ne.u32 p1, %7, 0x5000;\nsetp.ne.u32 p2, %11, 0x5000;\n"
                     "setp.ne.u32 p3, %15, 0x5000;\nsetp.ne.u32 p4, %19, 0x5000;\nsetp.ne.u32 p5, %23, 0x5000;\n"
                     "@p0 ld.volatile.global.v4.u32 {%0,%1,%2,%3}, [%24];\n@p1 ld.volatile.global.v4.u32 {%4,%5,%6,%7}, [%24+4096];\n"
                     "@p2 ld.volatile.global.v4.u32 {%8,%9,%10,%11}, [%24+8192];\n@p3 ld.volatile.global.v4.u32 {%12,%13,%14,%15}, [%24+12288];\n"
                     "@p4 ld.volatile.global.v4.u32 {%16,%17,%18,%19}, [%24+16384];\n@p5 ld.volatile.global.v4.u32 {%20,%21,%22,%23}, [%24+20480];\n}"
                     : "+r"(v[0].x), "+r"(v[0].y), "+r"(v[0].z), "+r"(v[0].w), "+r"(v[1].x), "+r"(v[1].y), "+r"(v[1].z), "+r"(v[1].w),
                       "+r"(v[2].x), "+r"(v[2].y), "+r"(v[2].z), "+r"(v[2].w), "+r"(v[3].x), "+r"(v[3].y), "+r"(v[3].z), "+r"(v[3].w),
                       "+r"(v[4].x), "+r"(v[4].y), "+r"(v[4].z), "+r"(v[4].w), "+r"(v[5].x), "+r"(v[5].y), "+r"(v[5].z), "+r"(v[5].w)
                     : "l"(src) : "memory");
        stsm_x4(dst, h2_to_bf2(v[0].x), h2_to_bf2(v[0].y), h2_to_bf2(v[0].z), h2_to_bf2(v[1].x));
        stsm_x4(dst + 512, h2_to_bf2(v[1].y), h2_to_bf2(v[1].z), h2_to_bf2(v[2].x), h2_to_bf2(v[2].y));
        const uint32_t all = ((v[0].w & v[1].w) & (v[2].w & v[3].w)) & (v[4].w & v[5].w);
        more = __any_sync(0xffffffffu, (all & 0x5000u) != 0x5000u && ++it < SPIN_LIMIT);
        stsm_x4(dst + 1024, h2_to_bf2(v[2].z), h2_to_bf2(v[3].x), h2_to_bf2(v[3].y), h2_to_bf2(v[3].z));
        asm volatile("stmatrix.sync.aligned.m8n8.x2.shared.b16 [%0], {%1,%2};" :: "r"(dst + 1536), "r"(h2_to_bf2(v[4].x)), "r"(h2_to_bf2(v[4].y)) : "memory");
        stsm_x4(dst + 1792, h2_to_bf2(v[4].z), h2_to_bf2(v[5].x), h2_to_bf2(v[5].y), h2_to_bf2(v[5].z));
        asm volatile("{\n.reg .pred p;\nsetp.eq.u32 p, %0, 0;\n@p bar.sync 1, 384;\n}" :: "r"((uint32_t)more) : "memory");
    } while (more);
    next();
    FS(13, it);
    FS(14, 0);
    uint32_t m = v[0].x, m1 = v[0].y, m2 = v[0].z;
#pragma unroll
    for (int j = 1; j < 6; j++) {
        asm volatile("max.NaN.xorsign.abs.f16x2 %0, %0, %1;" : "+r"(m) : "r"(v[j].x));
        asm volatile("max.NaN.xorsign.abs.f16x2 %0, %0, %1;" : "+r"(m1) : "r"(v[j].y));
        asm volatile("max.NaN.xorsign.abs.f16x2 %0, %0, %1;" : "+r"(m2) : "r"(v[j].z));
    }
    asm volatile("max.NaN.xorsign.abs.f16x2 %0, %0, %1;" : "+r"(m) : "r"(m1));
    asm volatile("max.NaN.xorsign.abs.f16x2 %0, %0, %1;" : "+r"(m) : "r"(m2));
    return h2_to_bf2(m) & 0x7fff7fffu;
}

template <bool V> struct Flag { static constexpr bool value = V; };
struct RFlag { bool value; };
__device__ __forceinline__ void score_group(const uint32_t (&a)[2][4], const uint32_t (&kf)[2][4], uint32_t d0, uint32_t d1, uint32_t m1, uint32_t d2, uint32_t m2) {
    FS(4, a[1][0]);
    float sc[4][4];
    mma_z(sc[0], a[0], kf[0][0], kf[0][1]);
    mma_z(sc[1], a[0], kf[0][2], kf[0][3]);
    mma_z(sc[2], a[1], kf[1][0], kf[1][1]);
    mma_z(sc[3], a[1], kf[1][2], kf[1][3]);
    const uint32_t v0 = __float_as_uint((sc[0][0] + sc[1][2]) + (sc[2][0] + sc[3][2])), v1 = __float_as_uint((sc[0][1] + sc[1][3]) + (sc[2][1] + sc[3][3]));
    FS(5, v0);
    st_async64(d2, v0, v1, m2);
    st_async64(d1, v0, v1, m1);
    asm volatile("st.shared.v2.u32 [%0], {%1,%2};" :: "r"(d0), "r"(v0), "r"(v1) : "memory");
}
__device__ __forceinline__ void store_tile(int s, int h, int role, uint32_t tile, uint32_t b0, uint32_t b1) {
    asm volatile("cp.async.bulk.global.shared::cta.bulk_group.L2::cache_hint [%0], [%1], %2, %3;"
                 :: "l"(&g_qkv[s][h][role][b0]), "r"(tile + b0), "r"(b1 - b0), "l"(policy_evict_first()) : "memory");
}
__device__ __forceinline__ uint32_t w_addr(uint32_t sbase, int warp, int lane) {
    return sbase + SM_WS + (warp >> 2) * 8192 + ((lane & 7) + ((lane >> 4) & 1) * 8) * 128 + ((((warp & 3) * 2 + ((lane >> 3) & 1)) ^ (lane & 7)) << 4);
}
__device__ __forceinline__ void vx_copy(uint32_t sbase, int j, int r) {
    bulk_s2s(mapa(sbase + SM_VX + (j & 1) * 8192, r), sbase + SM_T + (j & 3) * TBUF + DH * 16, 8192, mapa(sbase + B_VX + 8 * (j & 1), r));
}
__device__ __forceinline__ void norms_gather(int lane, float* scs) {
    uint2 v[3];
    uint4 w[2];
    unsigned it = 0;
    do {
#pragma unroll
        for (int i = 0; i < 3; i++) v[i] = ld_vol_u2(&g_norm[3 * lane + i]);
#pragma unroll
        for (int i = 0; i < 2; i++) w[i] = ld_vol_u4(&g_wv[lane][i]);
    } while (__any_sync(0xffffffffu, (v[0].x & v[1].x & v[2].x & v[0].y & w[0].x & w[0].y & w[0].z & w[0].w & w[1].x & w[1].y & w[1].z & w[1].w & 1u) == 0u) && ++it < SPIN_LIMIT);
    float c;
    asm("sqrt.approx.f32 %0, %1;" : "=f"(c) : "f"(__uint_as_float(max(max(v[0].x, v[1].x), v[2].x))));
    c *= __uint_as_float(max(max(max(w[0].x, w[0].y), max(w[0].z, w[0].w)), max(max(w[1].x, w[1].y), max(w[1].z, w[1].w)))) * 272.f;
#pragma unroll
    for (int o = 16; o; o >>= 1) c += __shfl_xor_sync(0xffffffffu, c, o);
    const uint32_t r = __reduce_max_sync(0xffffffffu, v[0].y);
    if (lane == 0) { scs[1] = c * (1.1f * 24.f); scs[16] = scs[17] = __uint_as_float(r); }
}
__device__ __forceinline__ void xmax_gather(int lane, float* scs) {
    uint4 v[4];
    unsigned it = 0;
    uint32_t ok;
    do {
#pragma unroll
        for (int i = 0; i < 4; i++) v[i] = ld_vol_u4(&g_rx[lane + 32 * (i >> 1)][i & 1]);
        ok = 1u;
#pragma unroll
        for (int i = 0; i < 4; i++) ok &= (v[i].x & v[i].y) & (v[i].z & v[i].w);
    } while (__any_sync(0xffffffffu, ok == 0u) && ++it < SPIN_LIMIT);
#pragma unroll
    for (int i = 0; i < 2; i++)
        scs[16 + lane + 32 * i] = __uint_as_float(max(max(max(v[2 * i].x, v[2 * i].y), max(v[2 * i].z, v[2 * i].w)), max(max(v[2 * i + 1].x, v[2 * i + 1].y), max(v[2 * i + 1].z, v[2 * i + 1].w))));
}
__device__ __forceinline__ uint32_t max_abs8(uint32_t m, uint32_t a, uint32_t b, uint32_t c, uint32_t d) { return max_abs2(max_abs2(m, max_abs2(a, b)), max_abs2(c, d)); }
__device__ __forceinline__ uint32_t warp_max_abs(uint32_t m) { return __reduce_max_sync(0xffffffffu, max((m << 16) & 0x7fff0000u, m & 0x7fff0000u)); }

__device__ __forceinline__ void last_rows(int pass) {
    extern __shared__ __align__(1024) unsigned char smem_raw[];
    const uint32_t sbase = smem_u32(smem_raw);
    const int tid = threadIdx.x, warp = __shfl_sync(0xffffffffu, tid >> 5, 0), h = blockIdx.x / 3;
    {
        const int sg = warp < 8, wq = warp & 3, lane = tid & 31;
        const uint32_t qk = sbase + SM_X + XBUF + sg * (2 * 9216), ob = sbase + SM_X + 2 * XBUF + sg * 8192;
        TST(0);
        if (pass) mbar_wait(sbase + B_VX + 8 * sg, 0);
        fence_async();
        TST(1);
        float sc[20];
#pragma unroll
        for (int i = 0; i < 20; i++) sc[i] = 0.f;
        {
            const uint64_t da = smem_desc(qk + 1024, 128, 1024), db = smem_desc(qk, 128, 2048);
            wg_fence();
#pragma unroll
            for (int ks = 0; ks < 8; ks++) wgmma_n40_ss(sc, da + (uint64_t)((ks >> 2) * 576 + (ks & 3) * 16), db + (uint64_t)((ks >> 2) * 576 + (ks & 3) * 16), ks > 0);
            wg_commit();
            wg_wait0();
        }
        uint32_t p[5], o[16];
        const float psum = xrow_softmax(sc, p, wq, lane);
        xrow_pv(o, p, psum, sbase + SM_T + ((NSEG - 2 + sg) & 3) * TBUF);
        if (pass) {
#pragma unroll
            for (int i = 0; i < 4; i++) stsm_x4(ob + (i >> 1) * 4096 + wq * 1024 + (i & 1) * 512 + lane * 16, o[4 * i], o[4 * i + 1], o[4 * i + 2], o[4 * i + 3]);
        }
        fence_async();
        named_bar(11 + sg, 128);
        TST(2);
        if ((tid & 127) == 0 && pass) {
            unsigned char* dst = reinterpret_cast<unsigned char*>(g_ox) + ((size_t)((NSEG / 2 - 1) * NH + h)) * 16384 + sg * 4096;
            asm volatile("cp.async.bulk.global.shared::cta.bulk_group [%0], [%1], 4096;" :: "l"(dst), "r"(ob) : "memory");
            asm volatile("cp.async.bulk.global.shared::cta.bulk_group [%0], [%1], 4096;" :: "l"(dst + 8192), "r"(ob + 4096) : "memory");
            asm volatile("cp.async.bulk.commit_group;" ::: "memory");
            asm volatile("cp.async.bulk.wait_group 0;" ::: "memory");
            asm volatile("red.relaxed.gpu.global.add.u32 [%0], 1;" :: "l"(&g_prog[(NSEG / 2 - 1) * 8 + (h >> 2)]) : "memory");
        }
        TST(3);
    }
    __syncwarp();
}

__global__ void __cluster_dims__(3, 1, 1) __launch_bounds__(384, 1)
k_chain(const __grid_constant__ CUtensorMap tmq, const __grid_constant__ CUtensorMap tmk,
        const __grid_constant__ CUtensorMap tmv, const __grid_constant__ CUtensorMap tmx2, const __grid_constant__ CUtensorMap tmo,
        const __grid_constant__ CUtensorMap tmm, const bf16* __restrict__ xg) {
    extern __shared__ __align__(1024) unsigned char smem_raw[];
    const uint32_t sbase = smem_u32(smem_raw);
    const int cta = blockIdx.x, h = cta / 3, role = cta - 3 * h;
    const int tid = threadIdx.x, warp = __shfl_sync(0xffffffffu, tid >> 5, 0), lane_o = tid & 31;
    TS3C(0);
    asm volatile("griddepcontrol.launch_dependents;" ::: "memory");
    auto stage_w = [&](int i) {
        tma_2d(sbase + SM_WS + i * 16384, role == 2 ? &tmv : &tmq, h * DH + (role == 1 ? 64 : 0), i * 64, sbase + B_W + 8 * i);
        tma_2d(sbase + SM_WS + i * 16384 + 8192, role == 2 ? &tmv : &tmk, h * DH + (role == 0 ? 0 : 64), i * 64, sbase + B_W + 8 * i);
    };
    auto stage_x = [&](int i) {
        tma_2d(sbase + x01_off(i), &tmx2, i * 64, 0, sbase + B_W + 8 * i);
        tma_2d(sbase + x01_off(i) + 8192, &tmm, i * 64, 0, sbase + B_W + 8 * i);
    };
    if (tid == 0) {
#pragma unroll
        for (int i = 0; i < 10; i++) mbar_init(sbase + B_W + 8 * i, 1);
        fence_async();
        TSQ(10);
#pragma unroll
        for (int i = 0; i < 3; i++) tma_2d(sbase + SM_X01 + i * 16384, &tmo, role * WOC + i * 64, h * DH, sbase + B_E);
        stage_x(0); stage_w(0);
        TSQ(11);
        mbar_expect(sbase + B_E, 49152);
#pragma unroll
        for (int i = 0; i < 9; i++) mbar_expect(sbase + B_W + 8 * i, 16384 + 9216);
    } else if (tid == 32) {
#pragma unroll
        for (int i = 0; i < 8; i++) mbar_init(sbase + SM_BAR + 8 * i, 1);
        mbar_init(sbase + B_XF, 3);
        asm volatile("fence.mbarrier_init.release.cluster;" ::: "memory");
        for (int i = 0; i < 2; i++) {
            mbar_expect(sbase + B_SB + 8 * i, role == 2 ? 2560 : 1280 + 2048);
            mbar_expect(sbase + B_VX + 8 * i, role != 2 ? 8192 : 2 * 9216);
            mbar_expect(sbase + B_XT + 8 * i, 32768);
            mbar_expect(sbase + B_XT + 16 + 8 * i, 40960);
        }
    }
    __syncthreads();
    TS3C(8);
    if (tid == 0) {
#pragma unroll 1
        for (int i = 1; i < NUP; i++) { if (i < 3) stage_x(i); stage_w(i); }
        TSQ(12);
    }
    __syncwarp();
    if (warp < 8) {
        uint32_t wreg[36 - NS][4];
        uint32_t v0, v1;
        {
            const int lane = lane_o;
            const uint32_t a = w_addr(sbase, warp, lane);
            const uint64_t da = smem_desc(sbase + SM_WS + (warp >> 2) * 8192, 1024, 1024) | (1ull << 62);
            float acc[36];
            uint32_t m = 0u;
#pragma unroll
            for (int i = 0; i < 36; i++) acc[i] = 0.f;
#pragma unroll 1
            for (int b = 0; b < 9; b++) {
                if (b == 0) TSQ(0);
                mbar_wait(sbase + B_W + 8 * b, 0);
                TSQ(1 + b);
                if (b == 8) TS3C(2);
                const uint64_t db = smem_desc(sbase + x01_off(b), 16, 1024) | (1ull << 62);
                wg_fence();
#pragma unroll
                for (int k = 0; k < 4; k++) wgmma_n72_ss(acc, da + (uint64_t)(b * 1024 + k * 128), db + (uint64_t)(k * 2));
                wg_commit();
                if (b == 3) {
                    if (role == 2) {
#pragma unroll
                        for (int ks = 0; ks < NS; ks++) {
                            uint32_t t[4];
                            ldsm_x4_t(t, a + (ks >> 2) * 16384 + (ks & 3) * 2048);
                            m = max_abs8(m, t[0], t[1], t[2], t[3]);
                        }
                    }
#pragma unroll
                    for (int ks = NS; ks < 16; ks++) ldsm_x4_t(wreg[ks - NS], a + (ks >> 2) * 16384 + (ks & 3) * 2048);
                }
                if (b == 5) {
#pragma unroll
                    for (int ks = 16; ks < 24; ks++) ldsm_x4_t(wreg[ks - NS], a + (ks >> 2) * 16384 + (ks & 3) * 2048);
                    if (role == 2) {
#pragma unroll
                        for (int ks = NS; ks < 24; ks++) m = max_abs8(m, wreg[ks - NS][0], wreg[ks - NS][1], wreg[ks - NS][2], wreg[ks - NS][3]);
                    }
                }
            }
#pragma unroll
            for (int ks = 24; ks < KPRE; ks++) ldsm_x4_t(wreg[ks - NS], a + (ks >> 2) * 16384 + (ks & 3) * 2048);
            if (role == 2) {
#pragma unroll
                for (int ks = KPRE; ks < 36; ks++) {
                    uint32_t t[4];
                    ldsm_x4_t(t, a + (ks >> 2) * 16384 + (ks & 3) * 2048);
                    m = max_abs8(m, t[0], t[1], t[2], t[3]);
                }
#pragma unroll
                for (int ks = 24; ks < KPRE; ks++) m = max_abs8(m, wreg[ks - NS][0], wreg[ks - NS][1], wreg[ks - NS][2], wreg[ks - NS][3]);
                m = warp_max_abs(m);
                if (lane == 0) asm volatile("st.volatile.global.u32 [%0], %1;" :: "l"(reinterpret_cast<uint32_t*>(&g_wv[h][0]) + warp), "r"(m | 1u) : "memory");
                __syncwarp();
            }
            wg_wait0();
            named_bar(9, 256);
            const uint32_t off = sbase + SM_T + (DH + warp * 16 + (lane & 15)) * 16 + (lane >> 4) * (DH * 16);
#pragma unroll
            for (int i = 0; i < 4; i++)
                stsm_x4(off + (i >> 1) * TBUF + (i & 1) * (2 * DH * 16), pack_bf16(acc[8 * i], acc[8 * i + 1]), pack_bf16(acc[8 * i + 2], acc[8 * i + 3]),
                        pack_bf16(acc[8 * i + 4], acc[8 * i + 5]), pack_bf16(acc[8 * i + 6], acc[8 * i + 7]));
            v0 = pack_bf16(acc[32], acc[33]);
            v1 = pack_bf16(acc[34], acc[35]);
#pragma unroll
            for (int ks = KPRE; ks < 36; ks++) ldsm_x4_t(wreg[ks - NS], a + (ks >> 2) * 16384 + (ks & 3) * 2048);
            if (role == 2) fence_async();
            bar_arrive(8, 384);
            named_bar(7, 256);
            asm volatile("barrier.cluster.arrive.relaxed.aligned;" ::: "memory");
        }
        TS3C(3);
        uint32_t ws[NS][4];
#pragma unroll
        for (int ks = NS - NP; ks < NS; ks++) ldsm_x4_t(ws[ks], w_addr(sbase, warp, lane_o) + (ks >> 2) * 16384 + (ks & 3) * 2048);
        asm volatile("barrier.cluster.wait.aligned;" ::: "memory");
        if (lane_o == 0 && role == 2) {
            if (warp < 2) vx_copy(sbase, 0, warp);
#pragma unroll 1
            for (int j = warp - 4; j >= 0 && j < 9; j += 4) tma_2d_mc(sbase + SM_X + j * 8192, &tmx2, (j < 4 ? j + 5 : j - 4) * 64, 64, sbase + B_XT + (j < 4 ? 8 : 24));
        }
        __syncwarp();
        TS3C(4);
        auto main_loop = [&](auto is_c) {
            const bool C = is_c.value;
            const uint32_t l16 = __shfl_sync(0xffffffffu, sbase + lane_o * 16, lane_o);
            const uint32_t ka = __shfl_sync(0xffffffffu, sbase + SM_T + (64 + (lane_o & 7) + ((lane_o >> 3) & 1) * 16 + (lane_o >> 4) * 8) * 16, lane_o);
            const uint32_t wa = __shfl_sync(0xffffffffu, w_addr(sbase, warp, lane_o), lane_o);
            auto post = [&](int s, uint32_t to, uint32_t ta, int scw, uint32_t v0, uint32_t v1) {
                int lane = lane_o;
                asm volatile("" : "+r"(lane));
                asm volatile("stmatrix.sync.aligned.m8n8.x2.shared.b16 [%0], {%1,%2};" :: "r"(l16 + ta), "r"(v0), "r"(v1) : "memory");
                if (C) {
                    if (s + 1 < NSEG) {
                        const uint32_t fo = (uint32_t)(warp * 256 + lane * 8);
                        const uint32_t rb0 = mapa(sbase, 0), rb1 = mapa(sbase, 1);
                        st_async64(rb0 + SM_VM + fo, v0, v1, rb0 + B_SB + 8 * (s & 1));
                        st_async64(rb1 + SM_VM + fo, v0, v1, rb1 + B_SB + 8 * (s & 1));
                        asm volatile("st.shared.v2.u32 [%0], {%1,%2};" :: "r"(sbase + SM_VM + fo), "r"(v0), "r"(v1) : "memory");
                        bar_arrive(2, 384);
                    }
                } else {
                    named_bar(2, 384);
                    if (scw == 0) {
                        uint32_t kf[2][4], qf[2][4];
#pragma unroll
                        for (int k2 = 0; k2 < 2; k2++) { ldsm_x4_t(kf[k2], ka + to + k2 * 512); ldsm_x4_t(qf[k2], l16 + SM_T + to + k2 * 512); }
                        const uint32_t d0 = sbase + SM_S + lane * 8, bo = sbase + B_SB + 8 * (s & 1);
                        const uint32_t d1 = mapa(d0 + 1280, role ^ 1), m1 = mapa(bo, role ^ 1), d2 = mapa(d0 + role * 1280, 2), m2 = mapa(bo, 2);
                        score_group(qf, kf, d0, d1, m1, d2, m2);
                        bar_arrive(6, 160);
                        bar_arrive(5, 384);
                    }
                    if (scw == 8) {
                        const uint32_t dk = mapa(sbase + SM_X + XBUF + (2 + role) * 9216 + (warp - 4) * 256 + lane * 4, 2), mb = mapa(sbase + B_VX + 8, 2);
                        st_async32(dk, v0, mb);
                        st_async32(dk + 128, v1, mb);
                    }
                }
                FS(11, 0);
            };
            post(0, 0, SM_T + warp * 256, warp ^ 7, v0, v1);
            int scw = warp ^ 7;
            uint32_t to = 0;
            int r0 = 0;
            for (int s = 0; s + 1 < NSEG; s++) {
                int lane = lane_o;
                asm volatile("" : "+r"(lane));
                const uint32_t tb = sbase + SM_T + to;
                const int rc = r0;
                const bool b5 = scw != 0;
                uint32_t ta;
                auto advance = [&]() {
                    to = to == 3 * TBUF ? 0 : to + TBUF;
                    ta = SM_T + warp * 256 + to;
                    scw = s + 2 < NSEG ? scw ^ 4 : (warp & 4) + 4;
                    if ((s & 1) == 0) r0 = r0 >= 4 ? r0 - 4 : r0 + 9;
                    asm volatile("" : "+r"(ta), "+r"(scw), "+r"(r0));
                };
                auto chores = [&](bool idle) {
                    const int hw = (s & 1) ? warp : warp - 4;
                    if (idle) { if (hw != 2) named_bar(4, 384); else bar_arrive(4, 384); }
                    if (hw == 2) {
                        if (lane == 0) {
                            if (C || !idle) fence_async();
                            if (C) {
                                store_tile(s + 1, h, 2, sbase + SM_T + ((s + 1) & 3) * TBUF, 2048, 10240);
                                store_tile(s, h, 2, tb, 0, s == 0 ? 10240 : 2048);
                            } else store_tile(s, h, role, tb, 1024, 10240);
                            asm volatile("cp.async.bulk.commit_group;" ::: "memory");
                            asm volatile("cp.async.bulk.wait_group 0;" ::: "memory");
                            if (C) {
                                asm volatile("cp.async.bulk.shared::cluster.global.mbarrier::complete_tx::bytes.multicast::cluster [%0], [%1], 8192, [%2], %3;"
                                             :: "r"(sbase + SM_VX + ((s + 1) & 1) * 8192), "l"(&g_qkv[s + 1][h][2][2048]), "r"(sbase + B_VX + 8 * ((s + 1) & 1)), "h"((unsigned short)3) : "memory");
                            }
                            asm volatile("red.relaxed.gpu.global.add.u32 [%0], 1;" :: "l"(&g_flag[h * NSEG + s]) : "memory");
                        }
                        __syncwarp();
                        if (!C && (s & 1) && s + 4 < NSEG) bar_arrive(13, 160);
                    }
                    __syncwarp();
                };
                const int p = (s + 3) >> 1;
                if (p < NSEG / 2 && (s == 0 || (warp >> 2) == (s & 1))) {
                    const uint32_t dlo = (uint32_t)smem_desc(sbase + SM_X, 16, 1024) + rc * 512;
                    const uint64_t da = smem_desc(sbase + SM_WS + (warp >> 2) * 8192, 1024, 1024) | (1ull << 62);
                    auto db = [&](int ks) {
                        const int j = ((ks >> 2) + 4) % 9;
                        return ((uint64_t)0x40000040u << 32) | (uint64_t)(dlo + (uint32_t)((j - (rc + j >= 13 ? 13 : 0)) * 512 + (ks & 3) * 2));
                    };
                    const uint32_t xph = (uint32_t)((p - 1) >> 1) & 1u;
                    float acc[32];
                    mbar_wait(sbase + B_XT + 8 * (p & 1), xph);
                    if (C) named_bar(7, 256); else if (b5) named_bar(5, 384);
                    if (NC1 > 0) {
                        if ((C ? CC_DELAY : C1_DELAY) > 0) { const uint32_t t1 = clock32(); while (clock32() - t1 < (C ? CC_DELAY : C1_DELAY)) {} }
                        wg_fence();
#pragma unroll
                        for (int ks = 35; ks > 35 - (C ? NC1C : NC1); ks--) { if (ks == 35) wgmma_n64_z(acc, wreg[ks - NS], db(ks)); else wgmma_n64(acc, wreg[ks - NS], db(ks), 1); }
                        wg_commit();
                        wg_wait0();
                    }
                    FS(9, __float_as_uint(acc[0]));
                    if (s == 0) {
                        chores(false);
                        if (cta < NSEG) {
                            uint32_t m = 0u;
                            mbar_wait(sbase + B_E, 1);
#pragma unroll 1
                            for (int j = 0; j < 9; j++) {
                                uint4 xv;
                                asm volatile("ld.shared.v4.u32 {%0,%1,%2,%3}, [%4];" : "=r"(xv.x), "=r"(xv.y), "=r"(xv.z), "=r"(xv.w)
                                             : "r"(l16 + warp * 512 + (j < 8 ? SM_X + 9 * 8192 + j * 4096 : SM_WS + 32768 + 4096)) : "memory");
                                m = max_abs8(m, xv.x, xv.y, xv.z, xv.w);
                            }
                            m = warp_max_abs(m);
                            if (lane == 0) asm volatile("st.volatile.global.u32 [%0], %1;" :: "l"(reinterpret_cast<uint32_t*>(&g_rx[cta][0]) + warp), "r"(m | 1u) : "memory");
                            __syncwarp();
                        }
                    }
                    const uint32_t off = sbase + SM_T + (p & 1) * (2 * TBUF) + (DH + warp * 16 + (lane & 15)) * 16 + (lane >> 4) * (DH * 16);
                    advance();
                    if (!LATEW) mbar_wait(sbase + B_XT + 16 + 8 * (p & 1), xph);
                    FS(8, 0);
                    named_bar(4, 384);
                    FS(3, 0);
                    if (C2_DELAY > 0) { const uint32_t t1 = clock32(); while (clock32() - t1 < C2_DELAY) {} }
                    constexpr int KE = 36 - SS_POS;
                    wg_fence();
#pragma unroll
                    for (int ks = 35 - (C ? NC1C : NC1); ks >= KE - (C ? NC1C : NC1); ks--) { if (ks == 35) wgmma_n64_z(acc, wreg[ks - NS], db(ks)); else wgmma_n64(acc, wreg[ks - NS], db(ks), 1); }
                    if (LATEW) {
                        wg_commit();
                        mbar_wait(sbase + B_XT + 16 + 8 * (p & 1), xph);
                        wg_fence();
                    }
#pragma unroll
                    for (int ks = 0; ks < NS; ks++) wgmma_n64_ss(acc, da + (uint64_t)((ks >> 2) * 1024 + (ks & 3) * 128), db(ks));
#pragma unroll
                    for (int ks = NS; ks < KE - (C ? NC1C : NC1) - XSKIP; ks++) wgmma_n64(acc, wreg[ks - NS], db(ks), 1);
                    wg_commit();
                    if (!C && (s & 1)) named_bar(13, 160);
                    wg_wait0();
#pragma unroll
                    for (int i = 0; i < 4; i++)
                        stsm_x4(off + (i >> 1) * TBUF + (i & 1) * (2 * DH * 16), pack_bf16(acc[8 * i], acc[8 * i + 1]), pack_bf16(acc[8 * i + 2], acc[8 * i + 3]),
                                pack_bf16(acc[8 * i + 4], acc[8 * i + 5]), pack_bf16(acc[8 * i + 6], acc[8 * i + 7]));
                    FS(7, __float_as_uint(acc[0]));
                } else if (s + 2 < NSEG) {
                    if (!C && (warp & 3) == 2) fence_async();
                    if (C) named_bar(7, 256); else if (b5) named_bar(5, 384);
                    chores(true);
                    advance();
                } else {
                    const uint32_t t0 = clock32();
                    const uint32_t dq = mapa(sbase + SM_X + XBUF + role * 9216, 2), mb = mapa(sbase + B_VX, 2);
                    if (!C) {
                        if (b5) named_bar(5, 384);
                        if (tid == 64) { fence_async(); while (clock32() - t0 < TL_DELAY) {} bulk_s2s(dq, tb + 1024, 9216, mb); }
                        __syncwarp();
                    }
                    advance();
                    named_bar(4, 384);
                    if (!C && tid == 64) { const uint32_t t1 = clock32(); while (clock32() - t1 < VX_DELAY) {} bulk_s2s(dq + 2 * 9216 + 1024, sbase + SM_T + to + 2048, 8192, mb + 8); }
                    __syncwarp();
                }
#pragma unroll
                for (int ks = 0; ks < NS - NP; ks++) ldsm_x4_t(ws[ks], wa + (ks >> 2) * 16384 + (ks & 3) * 2048);
                FS(0, ws[0][0]);
                named_bar(1, 384);
                float acc[2][4], minv;
                uint32_t b[3][4];
#pragma unroll
                for (int kk = 0; kk < 3; kk++) ldsm_x4_t(b[kk], l16 + SM_M + kk * 512);
                FS(1, b[0][0]);
#pragma unroll
                for (int kk = 0; kk < 18; kk++) {
#pragma unroll
                    for (int i = 0; i < 2; i++) {
                        const int ks = 2 * kk + i;
                        if (ks < 2) mma_z(acc[i], ws[ks], b[kk % 3][2 * i], b[kk % 3][2 * i + 1]);
                        else if (ks < NS) mma_bf16(acc[i], ws[ks < NS ? ks : 0], b[kk % 3][2 * i], b[kk % 3][2 * i + 1]);
                        else mma_bf16(acc[i], wreg[ks >= NS ? ks - NS : 0], b[kk % 3][2 * i], b[kk % 3][2 * i + 1]);
                    }
                    if (kk + 3 < 18) ldsm_x4_t(b[kk % 3], l16 + SM_M + (kk + 3) * 512);
                    if (kk + 3 == 17) asm volatile("ld.shared.f32 %0, [%1];" : "=f"(minv) : "r"(sbase + SM_SC + 8) : "memory");
                }
                const uint32_t u0 = pack_bf16(fmaf(acc[1][0], minv, acc[0][0] * minv), fmaf(acc[1][1], minv, acc[0][1] * minv));
                FS(2, u0);
                post(s + 1, to, ta, scw, u0, pack_bf16(fmaf(acc[1][2], minv, acc[0][2] * minv), fmaf(acc[1][3], minv, acc[0][3] * minv)));
            }
            if (C) named_bar(7, 256);
        };
        if (role == 2) main_loop(Flag<true>()); else main_loop(Flag<false>());
    } else {
        float* scs = reinterpret_cast<float*>(smem_raw + SM_SC);
        uint32_t wo[3][8][4];
        uint32_t mx2 = 0u;
        {
            const int pt = tid - 256, lane = lane_o, wq = warp - 8, g = lane >> 2, tq = lane & 3;
            TSQ(7);
            mbar_wait(sbase + B_E, 0);
            TSQ(8);
#pragma unroll
            for (int t = 0; t < 3; t++) {
                const int T = 3 * wq + t;
                const uint32_t a = sbase + SM_X01 + (T >> 2) * 16384 + ((lane >> 4) * 8 + (lane & 7)) * 128 + ((((T & 3) * 2 + ((lane >> 3) & 1)) ^ (lane & 7)) << 4);
#pragma unroll
                for (int kk = 0; kk < 8; kk++) ldsm_x4_t(wo[t][kk], a + ((2 * wq + kk) & 7) * 2048);
            }
            named_bar(3, 128);
            if (pt == 64) {
                fence_async();
#pragma unroll 1
                for (int i = 3; i < 9; i++) { stage_x(i); if (i >= NUP) stage_w(i); }
            }
            if (pt >= 96 && pt < 120) {
                *reinterpret_cast<uint4*>(g_acc + cta * 1024 + (pt - 96) * 16) = make_uint4(0u, 0u, 0u, 0u);
                __threadfence();
            }
            __syncwarp();
            TSQ(9);
            float c0 = 0.f;
#pragma unroll
            for (int t = 0; t < 3; t++) {
                float n[4][4];
#pragma unroll
                for (int i = 0; i < 4; i++) { n[i][0] = n[i][1] = n[i][2] = n[i][3] = 0.f; }
#pragma unroll
                for (int kk = 0; kk < 8; kk++)
#pragma unroll
                    for (int i = 0; i < 4; i++) mma_k8(n[i], wo[t][kk][i & 2], wo[t][kk][(i & 2) + 1], wo[t][kk][i]);
                if ((g >> 1) == tq) c0 = fmaxf(c0, (g & 1) ? fmaxf(n[0][1] + n[2][1], n[1][3] + n[3][3]) : fmaxf(n[0][0] + n[2][0], n[1][2] + n[3][2]));
            }
            c0 = __uint_as_float(__reduce_max_sync(0xffffffffu, __float_as_uint(c0)));
            uint32_t m = 0u;
            if (role == 0) {
                const int b = h % 9;
                mbar_wait(sbase + B_W + 8 * b, 0);
#pragma unroll
                for (int j = 0; j < 5; j++) {
                    const uint4 xv = *reinterpret_cast<const uint4*>(smem_raw + x01_off(b) + (j < 4 ? pt + 128 * j : 512 + (pt & 63)) * 16);
                    m = max_abs8(m, xv.x, xv.y, xv.z, xv.w);
                }
            }
            asm volatile("barrier.cluster.arrive.relaxed.aligned;" ::: "memory");
            m = warp_max_abs(m);
            if (lane == 0) { scs[80 + wq] = c0; reinterpret_cast<uint32_t*>(scs)[84 + wq] = m; }
            TSQ(1);
            named_bar(3, 128);
            if (pt == 0) {
                const uint4 a = *reinterpret_cast<const uint4*>(scs + 80), b = *reinterpret_cast<const uint4*>(scs + 84);
                st_vol_u2(&g_norm[cta], make_uint2(max(max(a.x, a.y), max(a.z, a.w)) | 1u, max(max(b.x, b.y), max(b.z, b.w)) | 1u));
            }
            __syncwarp();
            named_bar(8, 384);
            TSQ(2);
            if (pt == 32) {
                fence_async();
                if (cta < NSEG) {
                    mbar_expect(sbase + B_E, XBUF);
                    bulk_g2s(sbase + SM_X + 9 * 8192, xg + (size_t)cta * SEG * DM, 32768, sbase + B_E);
                    bulk_g2s(sbase + SM_WS + 32768 + 4096, xg + (size_t)cta * SEG * DM + 16384, 4096, sbase + B_E);
                }
            }
            __syncwarp();
            asm volatile("barrier.cluster.wait.aligned;" ::: "memory");
        }
        const int wq = warp - 8;
        auto helper_loop = [&](auto is_c) {
        const bool C = is_c.value;
        const uint32_t l8_o = __shfl_sync(0xffffffffu, sbase + lane_o * 8, lane_o), l16_o = __shfl_sync(0xffffffffu, sbase + lane_o * 16, lane_o);
        unsigned char* dst = g_acc + (role * 32 + wq * 8 + (lane_o >> 3)) * 1024 + (lane_o & 7) * 16;
        auto load_kf = [&](uint32_t (&kf)[2][4], int slot) {
            int lane = lane_o;
            asm volatile("" : "+r"(lane));
            const uint32_t ka = sbase + SM_T + slot * TBUF + ((wq + 1) * DH + 64 + (lane & 7) + ((lane >> 3) & 1) * 16 + (lane >> 4) * 8) * 16;
#pragma unroll
            for (int k2 = 0; k2 < 2; k2++) ldsm_x4_t(kf[k2], ka + k2 * 512);
        };
        float minv = 1.f;
        uint32_t kf[2][4];
        if (!C) load_kf(kf, 0);
        int b3 = 0;
        int rx = 9;
        for (int s = 0; s + 1 < NSEG; s++) {
            const int n3 = b3 == 2 ? 0 : b3 + 1;
            uint32_t l8 = l8_o, l16 = l16_o;
            asm volatile("" : "+r"(l8), "+r"(l16));
            {
                int lane = lane_o;
                asm volatile("" : "+r"(lane));
                if (C) {
                    if (lane == 0) {
                        if (wq == 3 && h == 0) {
                            const uint32_t t = gtime32();
                            st_vol_u2(&g_tick, make_uint2(t, reinterpret_cast<uint32_t*>(scs)[3]));
                            reinterpret_cast<uint32_t*>(scs)[3] = t;
                        }
                    }
                    __syncwarp();
                    if (wq == 2 && s > 1 && lane < 24) {
                        *reinterpret_cast<uint4*>(g_acc + n3 * 128 + (3 * h + (lane >> 3)) * 1024 + (lane & 7) * 16) = make_uint4(0u, 0u, 0u, 0u);
                    }
                    if (wq == 1 && s == 3 && lane < 3) {
                        const int c = 3 * h + lane;
                        st_vol_u2(&g_norm[c], make_uint2(0u, 0u));
                        uint4* z = c < NSEG ? g_rx[c] : g_wv[c - NSEG];
                        st_vol_u4(z, make_uint4(0u, 0u, 0u, 0u)); st_vol_u4(z + 1, make_uint4(0u, 0u, 0u, 0u));
                    }
                    __syncwarp();
                }
                const uint32_t mw = __reduce_max_sync(0xffffffffu, max(mx2 << 16, mx2 & 0xffff0000u));
                if (lane == 0) scs[4 + wq] = __uint_as_float(mw);
            }
            const uint32_t to = SM_T + (s & 3) * TBUF;
            const uint32_t ph = (uint32_t)(s >> 1) & 1u;
            if (!C) {
                const uint32_t bo = sbase + B_SB + 8 * (s & 1);
                uint32_t d0 = l8 + SM_S + (wq + 1) * 256, qa = l16 + to;
                const uint32_t d1 = mapa(d0 + 1280, role ^ 1), m1 = mapa(bo, role ^ 1), d2 = mapa(d0 + role * 1280, 2), m2 = mapa(bo, 2);
                asm volatile("" : "+r"(d0), "+r"(qa));
                mbar_wait(sbase + (s > 0 ? B_VX + 8 * (s & 1) : B_W), ph);
                FS(1, 0);
                named_bar(2, 384);
                uint32_t qf[2][4];
#pragma unroll
                for (int k2 = 0; k2 < 2; k2++) ldsm_x4_t(qf[k2], qa + k2 * 512);
                score_group(qf, kf, d0, d1, m1, d2, m2);
                bar_arrive(5, 384);
            } else named_bar(2, 384);
            if (s == 0) {
                TSQ(3);
                int lane = lane_o;
                asm volatile("" : "+r"(lane));
                if (wq == 1) norms_gather(lane, scs);
                if (!C) mbar_wait(sbase + B_VX, 0);
                named_bar(3, 128);
                TSQ(4);
            }
            const float4 m4 = *reinterpret_cast<const float4*>(scs + 4);
            const float c24 = scs[1], xb = scs[16 + s];
            uint32_t vf[2][2][4], vm[2][2];
            uint32_t va = l16 + ((l16 >> 8) & 1) * 1792 + wq * 512 + (C ? to + DH * 16 : SM_VX + (s & 1) * 8192);
            auto load_vf = [&]() {
#pragma unroll
                for (int i = 0; i < 4; i++) ldsm_x4(vf[i & 1][i >> 1], va + (i & 1) * 256 + (i >> 1) * 4096);
            };
            if (C || VFP == 0) load_vf();
            float scale;
            {
                const float bound = fmaxf(fmaxf(fmaxf(m4.x, m4.y), fmaxf(m4.z, m4.w)) * minv, xb) * c24;
                int e = 141 - (int)((__float_as_uint(bound) >> 23) & 255u);
                e = e > 100 ? 100 : e;
                scale = __uint_as_float((uint32_t)(127 + e) << 23);
            }
            uint32_t oa = l16 + wq * 512;
            asm volatile("" : "+f"(scale), "+r"(oa), "+r"(va));
            FS(7, __float_as_uint(scale));
            constexpr float EC = (float)(1.4426950408889634 * 0.08838834764831845);
            if (!C) named_bar(6, 160);
            if (C) mbar_wait_fast(sbase + B_SB + 8 * (s & 1), ph);
            float sv[5][2];
#pragma unroll
            for (int j = 0; j < 5; j++) lds64f(sv[j][0], sv[j][1], l8 + SM_S + j * 256);
            if (!C) {
#pragma unroll
                for (int j = 0; j < 5; j++) { sv[j][0] *= EC; sv[j][1] *= EC; asm volatile("" : "+f"(sv[j][0]), "+f"(sv[j][1])); }
                mbar_wait_fast(sbase + B_SB + 8 * (s & 1), ph);
            }
            FS(6, 0);
            uint32_t p[5];
            {
                float sr[5][2];
#pragma unroll
                for (int j = 0; j < 5; j++) lds64f(sr[j][0], sr[j][1], l8 + SM_S + 1280 + j * 256);
                if (!C && VFP == 1) load_vf();
                lds64(vm[0][0], vm[0][1], l8 + SM_VM + wq * 512);
                lds64(vm[1][0], vm[1][1], l8 + SM_VM + wq * 512 + 256);
#pragma unroll
                for (int j = 0; j < 5; j++) {
                    sv[j][0] = C ? sv[j][0] + sr[j][0] : fmaf(sr[j][0], EC, sv[j][0]);
                    sv[j][1] = C ? sv[j][1] + sr[j][1] : fmaf(sr[j][1], EC, sv[j][1]);
                }
                float mx = fmaxf(fmaxf(fmaxf(sv[0][0], sv[0][1]), fmaxf(sv[1][0], sv[1][1])), fmaxf(fmaxf(sv[2][0], sv[2][1]), fmaxf(sv[3][0], sv[3][1])));
                mx = fmaxf(mx, fmaxf(sv[4][0], sv[4][1]));
                {
                    const float m1 = __shfl_xor_sync(0xffffffffu, mx, 1), m2 = __shfl_xor_sync(0xffffffffu, mx, 2), m3 = __shfl_xor_sync(0xffffffffu, mx, 3);
                    if (!C && VFP == 2) { va += __float_as_uint(mx) & l16 & 3u; load_vf(); }
                    if (C) {
#pragma unroll
                        for (int j = 0; j < 5; j++) { sv[j][0] *= EC; sv[j][1] *= EC; }
                        mx = fmaxf(fmaxf(mx * EC, m1 * EC), fmaxf(m2 * EC, m3 * EC));
                    } else mx = fmaxf(fmaxf(mx, m1), fmaxf(m2, m3));
                }
#pragma unroll
                for (int jj = 0; jj < 5; jj++) {
                    const int j = (jj + 1) % 5;
                    asm("ex2.approx.ftz.f32 %0, %1;" : "=f"(sv[j][0]) : "f"(sv[j][0] - mx));
                    asm("ex2.approx.ftz.f32 %0, %1;" : "=f"(sv[j][1]) : "f"(sv[j][1] - mx));
                    p[j] = pack_bf16(sv[j][0], sv[j][1]);
                }
            }
            FS(0, p[0]);
            uint32_t b[4][4];
            float zs[4];
            {
                float o0[2][4], o1[2][4];
                mma_z(o0[0], vf[0][0], p[1], p[2]);
                mma_z(o0[1], vf[1][0], p[1], p[2]);
                mma_z(o1[0], vf[0][1], p[3], p[4]);
                mma_z(o1[1], vf[1][1], p[3], p[4]);
                mma_k8(o0[0], vm[0][0], vm[0][1], p[0]);
                mma_k8(o0[1], vm[1][0], vm[1][1], p[0]);
                const uint32_t one4[4] = {0x3f803f80u, 0x3f803f80u, 0x3f803f80u, 0x3f803f80u};
                mma_z(zs, one4, p[1], p[2]);
                mma_bf16(zs, one4, p[3], p[4]);
                mma_k8(zs, one4[0], one4[1], p[0]);
                uint32_t ow[4];
#pragma unroll
                for (int m = 0; m < 2; m++) {
                    ow[2 * m] = pack_bf16(o0[m][0] + o1[m][0], o0[m][1] + o1[m][1]);
                    ow[2 * m + 1] = pack_bf16(o0[m][2] + o1[m][2], o0[m][3] + o1[m][3]);
                }
                stsm_x4(oa + SM_O, ow[0], ow[1], ow[2], ow[3]);
                FS(2, 0);
#pragma unroll
                for (int i = 0; i < 4; i++) b[0][i] = movm(ow[i]);
            }
            float acc[3][2][4];
            named_bar(3, 128);
#pragma unroll
            for (int i = 1; i < 4; i++) ldsm_x4_t(b[i], l16 + SM_O + ((wq + i) & 3) * 512);
#pragma unroll
            for (int c = 0; c < 2; c++)
#pragma unroll
                for (int t = 0; t < 3; t++) mma_z(acc[t][c], wo[t][c], b[0][2 * c], b[0][2 * c + 1]);
            float z0, z1;
            asm volatile("rcp.approx.ftz.f32 %0, %1;" : "=f"(z0) : "f"(zs[0]));
            asm volatile("rcp.approx.ftz.f32 %0, %1;" : "=f"(z1) : "f"(zs[1]));
            z0 *= scale; z1 *= scale;
            FS(3, b[1][0]);
#pragma unroll
            for (int i = 1; i < 4; i++)
#pragma unroll
                for (int c = 0; c < 2; c++)
#pragma unroll
                    for (int t = 0; t < 3; t++) mma_bf16(acc[t][c], wo[t][2 * i + c], b[i][2 * c], b[i][2 * c + 1]);
            {
                uint32_t w[6];
#pragma unroll
                for (int t = 0; t < 3; t++) {
                    w[2 * t] = pack_f16(fmaf(acc[t][1][0], z0, acc[t][0][0] * z0), fmaf(acc[t][1][1], z1, acc[t][0][1] * z1));
                    w[2 * t + 1] = pack_f16(fmaf(acc[t][1][2], z0, acc[t][0][2] * z0), fmaf(acc[t][1][3], z1, acc[t][0][3] * z1));
                }
                FS(8, w[5]);
                asm volatile("red.relaxed.gpu.global.add.noftz.v4.f16x2 [%0], {%1,%2,%3,%4};" :: "l"(dst), "r"(w[0]), "r"(w[1]), "r"(w[2]), "r"(0x3c00u) : "memory");
                asm volatile("red.relaxed.gpu.global.add.noftz.v4.f16x2 [%0], {%1,%2,%3,%4};" :: "l"(dst + 4096), "r"(w[3]), "r"(w[4]), "r"(w[5]), "r"(0x3c00u) : "memory");
            }
            FS(9, 0);
            if (s == 0) TSQ(5);
            bar_arrive(4, 384);
            const uint32_t t0 = clock32();
            minv = __uint_as_float(0x7f000000u - __float_as_uint(scale));
            if (lane_o == 0) {
                if (wq == 0) scs[2] = minv;
                if (s + 3 < NSEG) {
                    if (wq == 0) mbar_expect(sbase + B_SB + 8 * (s & 1), C ? 2560 : 1280 + 2048);
                    if (wq == 1 && s > 0 && s + 5 < NSEG) mbar_expect(sbase + B_XT + ((s & 1) ? 0 : 16) + 4 * ((s + 1) & 2), (s & 1) ? 32768 : 40960);
                    if (wq == 3 && !C) mbar_expect(sbase + B_VX + 8 * (s & 1), 8192);
                }
            }
            __syncwarp();
            if (s == 1) {
                int lane = lane_o;
                asm volatile("" : "+r"(lane));
                if (wq == 3) xmax_gather(lane, scs);
                __syncwarp();
            }
            if (!C) load_kf(kf, (s + 1) & 3);
            const uint4* src = reinterpret_cast<const uint4*>(dst + (wq * 16 - role * 32) * 1024);
            dst += n3 == 0 ? -256 : 128;
            asm volatile("" : "+l"(dst));
            const int xp = (s + 5) >> 1, kb = wq + ((s & 1) ? 2 * role : 4 + 3 * role);
            const bool xl = !C && xp < NSEG / 2 && wq < ((s & 1) ? 2 : 3 - role);
            const uint32_t xs = wq == 3 && (s & 1) == 0 && xp < NSEG / 2;
            const uint32_t xd = sbase + SM_X + (rx + kb >= 13 ? rx + kb - 13 : rx + kb) * 8192;
            mx2 = poll_mem(src, l16 + SM_M + wq * 2304, t0, [&]() {
                if (xs && lane_o < 2) asm volatile("mbarrier.arrive.relaxed.cluster.shared::cluster.b64 _, [%0];" :: "r"(mapa(sbase + B_XF, lane_o)) : "memory");
                if (!C && (xl || s == 0) && (s & 1) == 0) mbar_wait(sbase + B_XF, (uint32_t)(s >> 1) & 1u);
                if (lane_o == 0) {
                    if (xl) tma_2d_mc(xd, &tmx2, ((s & 1) ? kb + 5 : kb - 4) * 64, xp * 64, sbase + B_XT + ((s & 1) ? 0 : 16) + 8 * (xp & 1));
                    if (!C && s == 0 && role == 1) tma_2d_mc(sbase + SM_X + (9 + wq) * 8192, &tmx2, (wq + 5) * 64, 128, sbase + B_XT);
                }
                __syncwarp();
            });
            if ((s & 1) == 0) rx = rx >= 4 ? rx - 4 : rx + 9;
            if (s == 0) TSQ(6);
            b3 = n3;
        }
        if (!C) bar_arrive(2, 384);
        };
        if (role == 2) helper_loop(Flag<true>()); else helper_loop(Flag<false>());
    }
    TS3C(1);
    if (role == 2 && warp >= 4) last_rows(1);
    cluster_sync_all();
}

extern "C" void kernel_launch(void* const* d_in, const int* in_sizes, int n_in, void* d_out, int out_size) {
    const bf16* x = (const bf16*)d_in[0];
    const bf16* mem0 = (const bf16*)d_in[1];
    const bf16* Wq = (const bf16*)d_in[2];
    const bf16* Wk = (const bf16*)d_in[3];
    const bf16* Wv = (const bf16*)d_in[4];
    const bf16* Wo = (const bf16*)d_in[5];
    const bf16* logA = (const bf16*)d_in[8];
    const bf16* Aim = (const bf16*)d_in[9];
    const bf16* Cre = (const bf16*)d_in[10];
    const bf16* Cim = (const bf16*)d_in[11];
    const bf16* logdt = (const bf16*)d_in[12];
    const bf16* dskip = (const bf16*)d_in[13];
    const bf16* gw = (const bf16*)d_in[14];
    bf16* out = (bf16*)d_out;
    static bool attr_done = false;
    typedef CUresult (*EncFn)(CUtensorMap*, CUtensorMapDataType, cuuint32_t, void*, const cuuint64_t*, const cuuint64_t*, const cuuint32_t*,
                              const cuuint32_t*, CUtensorMapInterleave, CUtensorMapSwizzle, CUtensorMapL2promotion, CUtensorMapFloatOOBfill);
    static EncFn enc = nullptr;
    if (!attr_done) {
        void* fn = nullptr;
        cudaDriverEntryPointQueryResult qr;
        cudaGetDriverEntryPoint("cuTensorMapEncodeTiled", &fn, cudaEnableDefault, &qr);
        enc = (EncFn)fn;
        cudaFuncSetAttribute(k_chain, cudaFuncAttributeMaxDynamicSharedMemorySize, 232448);
        cudaFuncSetAttribute(k_side, cudaFuncAttributeMaxDynamicSharedMemorySize, SIDE_SMEM);
        attr_done = true;
    }
    CUtensorMap tmw[3];
    for (int i = 0; i < 3; i++) {
        const cuuint64_t dims[2] = {(cuuint64_t)HD, (cuuint64_t)DM};
        const cuuint64_t strides[1] = {(cuuint64_t)HD * 2};
        const cuuint32_t box[2] = {64, 64};
        const cuuint32_t es[2] = {1, 1};
        enc(&tmw[i], CU_TENSOR_MAP_DATA_TYPE_BFLOAT16, 2, (void*)(i == 0 ? Wq : (i == 1 ? Wk : Wv)), dims, strides, box, es, CU_TENSOR_MAP_INTERLEAVE_NONE,
            CU_TENSOR_MAP_SWIZZLE_128B, CU_TENSOR_MAP_L2_PROMOTION_L2_256B, CU_TENSOR_MAP_FLOAT_OOB_FILL_NONE);
    }
    CUtensorMap tmo;
    {
        const cuuint64_t dims[2] = {(cuuint64_t)DM, (cuuint64_t)HD};
        const cuuint64_t strides[1] = {(cuuint64_t)DM * 2};
        const cuuint32_t box[2] = {64, 128};
        const cuuint32_t es[2] = {1, 1};
        enc(&tmo, CU_TENSOR_MAP_DATA_TYPE_BFLOAT16, 2, (void*)Wo, dims, strides, box, es, CU_TENSOR_MAP_INTERLEAVE_NONE,
            CU_TENSOR_MAP_SWIZZLE_128B, CU_TENSOR_MAP_L2_PROMOTION_L2_128B, CU_TENSOR_MAP_FLOAT_OOB_FILL_NONE);
    }
    CUtensorMap tmx2;
    {
        const cuuint64_t dims[2] = {(cuuint64_t)DM, (cuuint64_t)S_LEN};
        const cuuint64_t strides[1] = {(cuuint64_t)DM * 2};
        const cuuint32_t box[2] = {64, 64};
        const cuuint32_t es[2] = {1, 1};
        enc(&tmx2, CU_TENSOR_MAP_DATA_TYPE_BFLOAT16, 2, (void*)x, dims, strides, box, es, CU_TENSOR_MAP_INTERLEAVE_NONE,
            CU_TENSOR_MAP_SWIZZLE_128B, CU_TENSOR_MAP_L2_PROMOTION_L2_128B, CU_TENSOR_MAP_FLOAT_OOB_FILL_NONE);
    }
    CUtensorMap tmm;
    {
        const cuuint64_t dims[2] = {(cuuint64_t)DM, (cuuint64_t)MEMT};
        const cuuint64_t strides[1] = {(cuuint64_t)DM * 2};
        const cuuint32_t box[2] = {64, (cuuint32_t)MEMT};
        const cuuint32_t es[2] = {1, 1};
        enc(&tmm, CU_TENSOR_MAP_DATA_TYPE_BFLOAT16, 2, (void*)mem0, dims, strides, box, es, CU_TENSOR_MAP_INTERLEAVE_NONE,
            CU_TENSOR_MAP_SWIZZLE_128B, CU_TENSOR_MAP_L2_PROMOTION_L2_128B, CU_TENSOR_MAP_FLOAT_OOB_FILL_NONE);
    }
    k_chain<<<NCTA, 384, 232448>>>(tmw[0], tmw[1], tmw[2], tmx2, tmo, tmm, x);
    {
        cudaLaunchConfig_t cfg = {};
        cfg.gridDim = dim3(SD_NCTA); cfg.blockDim = dim3(512); cfg.dynamicSmemBytes = SIDE_SMEM; cfg.stream = cudaStreamPerThread;
        cudaLaunchAttribute at[1];
        at[0].id = cudaLaunchAttributeProgrammaticStreamSerialization;
        at[0].val.programmaticStreamSerializationAllowed = 1;
        cfg.attrs = at; cfg.numAttrs = 1;
        cudaLaunchKernelEx(&cfg, k_side, tmo, x, logA, Aim, Cre, Cim, logdt, Wo, dskip, gw, out);
    }
}
```

```cpp
#include <cuda_runtime.h>
#include <cuda.h>
#include <cuda_bf16.h>
#include <stdint.h>

typedef __nv_bfloat16 bf16;
#define LDV4 "ld.volatile.global.v4.u32 {%0,%1,%2,%3}, [%4];"
#define STV4 "st.volatile.global.v4.u32 [%0], {%1,%2,%3,%4};"
#define STV2 "st.volatile.global.v2.u32 [%0], {%1,%2};"

constexpr int S_LEN = 2048, DM = 576, NH = 32, DH = 128, HD = 4096, MEMT = 8, SEG = 32, NSEG = 64, NST = 128;

__device__ __align__(128) bf16 g_gate[S_LEN];
constexpr int NCTA = NH * 3;
__device__ __align__(1024) unsigned char g_acc[96 * 1024];
__device__ __align__(128) uint2 g_norm[NCTA];
__device__ __align__(128) uint4 g_wv[NH][2];
__device__ __align__(128) uint4 g_rx[NSEG][2];
__device__ __align__(128) unsigned char g_qkv[NSEG][NH][3][10240];
__device__ __align__(128) bf16 g_ox[S_LEN * HD];
__device__ __align__(128) uint4 g_fp[8][36][6][128];
__device__ __align__(128) unsigned g_flag[NH * NSEG];
__device__ unsigned g_prog[NSEG / 2 * 8];
__device__ unsigned g_gcnt[64];
__device__ unsigned g_epoch;
__device__ __align__(128) uint2 g_tick;
__device__ __align__(128) bf16 g_y[DM * S_LEN];

#define TS3(slot) do {} while (0)
#define TS3P(slot) do {} while (0)
#define TSQ(slot) do {} while (0)
#define TS3W(slot) do {} while (0)
#define TSS(row, slot) do {} while (0)
#define TS3C(slot) do {} while (0)
#define TST(slot) do {} while (0)
#define TSA(seg, slot) do {} while (0)
#define TSG(i) do {} while (0)
#define FS(i, dep) do {} while (0)
__device__ __forceinline__ uint32_t smem_u32(const void* p) { return (uint32_t)__cvta_generic_to_shared(p); }
__device__ __forceinline__ float bf16r(float x) { return __bfloat162float(__float2bfloat16_rn(x)); }
__device__ __forceinline__ uint32_t pack_bf16(float lo, float hi) {
    __nv_bfloat162 v = __floats2bfloat162_rn(lo, hi);
    return *reinterpret_cast<uint32_t*>(&v);
}
__device__ __forceinline__ void ldsm_x4(uint32_t (&r)[4], uint32_t addr) {
    asm volatile("ldmatrix.sync.aligned.m8n8.x4.shared.b16 {%0,%1,%2,%3}, [%4];"
                 : "=r"(r[0]), "=r"(r[1]), "=r"(r[2]), "=r"(r[3]) : "r"(addr));
}
__device__ __forceinline__ void ldsm_x4_t(uint32_t (&r)[4], uint32_t addr) {
    asm volatile("ldmatrix.sync.aligned.m8n8.x4.trans.shared.b16 {%0,%1,%2,%3}, [%4];"
                 : "=r"(r[0]), "=r"(r[1]), "=r"(r[2]), "=r"(r[3]) : "r"(addr));
}
__device__ __forceinline__ void mma_bf16(float (&d)[4], const uint32_t (&a)[4], uint32_t b0, uint32_t b1) {
    asm volatile("mma.sync.aligned.m16n8k16.row.col.f32.bf16.bf16.f32 {%0,%1,%2,%3}, {%4,%5,%6,%7}, {%8,%9}, {%0,%1,%2,%3};"
                 : "+f"(d[0]), "+f"(d[1]), "+f"(d[2]), "+f"(d[3])
                 : "r"(a[0]), "r"(a[1]), "r"(a[2]), "r"(a[3]), "r"(b0), "r"(b1));
}
__device__ __forceinline__ uint2 ld_vol_u2(const uint2* p) {
    uint2 v; asm volatile("ld.volatile.global.v2.u32 {%0,%1}, [%2];" : "=r"(v.x), "=r"(v.y) : "l"(p) : "memory"); return v;
}
__device__ __forceinline__ void st_vol_u2(uint2* p, uint2 v) {
    asm volatile(STV2 :: "l"(p), "r"(v.x), "r"(v.y) : "memory");
}
__device__ __forceinline__ unsigned ld_acq(const unsigned* p) {
    unsigned v; asm volatile("ld.acquire.gpu.global.u32 %0, [%1];" : "=r"(v) : "l"(p) : "memory"); return v;
}
#define NS 10
#define NP 4
#define X_OXSZ 16384
#define GATE_A 1050
#define GATE_B 300
#define GATE_P 1880u
#define STAGGER 0
#define RLX_SLEEP 300
#define VX_DELAY 100
#define EARLY4 0
#define SPEC_M 1
#define SPEC_H 1
#define C2_DELAY 0
#define SS_POS 10
#define UNGATE_G 3
#define GATE_Y 0
#define GATE_S 0
#define GATE_F 1
#define W14_SLEEP 60
#define TURN31 1
#define GL_A 1150
#define GL_B 480
#define GS_A 1400
#define GS_B 480
#define GATE_POLL 0
#define GP_A 900
#define GP_B 200
#define NUP 3
#define SIDE_WAIT 0
#define FASTW 0
#define NC1 5
#define NC1C NC1
#define C1_DELAY 0
#define XSKIP 0
#define LATEW 1
#define VFP 0
#define CC_DELAY 0
#define KPRE 34
#define P0A 1
#define P0B 1
#define P0C 0
#define P0D 0
#define GPRED 1
#define P0W 0
#define XRARE 1
#define RARE(c) __builtin_expect(!!(c), 0)
#define PADB 0
#define PADC 0
#define PADD 0
#define PADE 0
#define PAD1 0
#define PAD2 0
#define PAD3 0
#define PAD4 0
#define SMR 0
#define TL_DELAY 600
#define POLL_DELAY 590
#define UNGATE 6
constexpr unsigned SPIN_LIMIT = 1u << 20;
constexpr int NATT = NSEG - 2;

constexpr int SD_CH = 16;
constexpr int SD_NCTA = DM / SD_CH;
constexpr int SD_ROW = 528;
constexpr int SD_U = 8 * SD_ROW;
constexpr int SD_TAP = 5888;
constexpr int SD_CPY = 1376 * 2;
constexpr int SD_WSTR = SD_TAP + 2 * SD_CPY;
constexpr int SD_SMEM = SD_CH * SD_U + 8 * SD_WSTR;
constexpr int O_U = 79, O_U3 = 911, O_U4 = 1055, O_W79 = 1023, O_W35 = 1151, O_W610 = 1279, O_W511 = 1487;

__device__ __forceinline__ uint32_t lds32(uint32_t a) { uint32_t v; asm volatile("ld.shared.u32 %0, [%1];" : "=r"(v) : "r"(a)); return v; }
__device__ __forceinline__ void tap_tile(uint32_t (&t)[4], uint32_t a) {
    asm volatile("ld.volatile.shared.u32 %0, [%4];\nld.volatile.shared.u32 %1, [%4+-16];\nld.volatile.shared.u32 %2, [%4+16];\nld.volatile.shared.u32 %3, [%4];"
                 : "=r"(t[0]), "=r"(t[1]), "=r"(t[2]), "=r"(t[3]) : "r"(a));
}
constexpr uint32_t sd_pass(int type, int dl, int o, int d0, int d1) { return (uint32_t)(type | dl << 2 | d0 << 8 | d1 << 12 | o << 17); }
__constant__ uint32_t SD_PASS[14] = {sd_pass(0, 0, O_U, 0, 2), sd_pass(0, 1, O_U + 96, 0, 2), sd_pass(0, 2, O_U + 192, 0, 4), sd_pass(0, 3, O_U + 288, 0, 2), sd_pass(1, 0, O_U3, 8, 8),
                                     sd_pass(0, 4, O_U + 384, 0, 2), sd_pass(1, 0, O_U4, 8, 15), sd_pass(0, 5, O_U + 480, 0, 2), sd_pass(0, 6, O_U + 576, 0, 4), sd_pass(0, 7, O_U + 672, 0, 2),
                                     sd_pass(2, 0, O_W35, 2, 8), sd_pass(3, 0, O_W79, 2, 4), sd_pass(2, 1, O_W610, 4, 8), sd_pass(3, 0, O_W511, 8, 15)};
__device__ __forceinline__ uint32_t band2(int x, int lo, int hi) { return (x >= lo && x <= hi ? 0x3f80u : 0u) | (x + 1 >= lo && x + 1 <= hi ? 0x3f800000u : 0u); }
__device__ __forceinline__ void mma_z(float (&d)[4], const uint32_t (&a)[4], uint32_t b0, uint32_t b1);
__device__ __forceinline__ void put_tap(uint32_t a, float v) {
    asm volatile("{\n.reg .b16 h;\ncvt.rn.bf16.f32 h, %1;\nst.shared.b16 [%0], h;\nst.shared.b16 [%0+%2], h;\n}" :: "r"(a), "f"(v), "n"(SD_CPY - 2) : "memory");
}

__device__ __forceinline__ void named_bar(int id, int n) { asm volatile("bar.sync %0, %1;" :: "r"(id), "r"(n) : "memory"); }
__device__ __forceinline__ uint32_t pack_f16(float lo, float hi) {
    uint32_t r; asm("cvt.rn.f16x2.f32 %0, %1, %2;" : "=r"(r) : "f"(hi), "f"(lo)); return r;
}
__device__ __forceinline__ void cexp_t(float lr, float turns, float& re, float& im) {
    float m;
    asm("ex2.approx.ftz.f32 %0, %1;" : "=f"(m) : "f"(lr));
    const float a = (turns - rintf(turns)) * 6.283185307179586f;
    re = m * __cosf(a); im = m * __sinf(a);
}
__device__ __forceinline__ void csq(float& re, float& im) { const float r = re * re - im * im; im = 2.f * re * im; re = r; }
__device__ __forceinline__ void kb_state(const float* tp, float gf, uint32_t (&a)[4][2], uint32_t (&b)[5]) {
    const float4 p0 = *reinterpret_cast<const float4*>(tp), p1 = *reinterpret_cast<const float4*>(tp + 4);
    float wr, wi;
    cexp_t(p0.x * gf, p0.y * gf, wr, wi);
    float vr = wr * p1.x - wi * p1.y, vi = wr * p1.y + wi * p1.x;
#pragma unroll
    for (int c = 0; c < 4; c++) {
        a[c][0] = pack_f16(wr, wi); a[c][1] = pack_f16(vr, vi);
        csq(wr, wi);
        if (c < 3) csq(vr, vi);
    }
    b[0] = pack_f16(p0.z * wr - p0.w * wi, -p0.z * wi - p0.w * wr);
    float er = wr * p1.z - wi * p1.w, ei = wr * p1.w + wi * p1.z;
#pragma unroll
    for (int c = 0; c < 4; c++) {
        b[1 + c] = pack_f16(p0.z * er - p0.w * ei, -p0.z * ei - p0.w * er);
        if (c < 3) csq(er, ei);
    }
}
__device__ __forceinline__ uint32_t bf2_mul(uint32_t a, uint32_t b) { uint32_t r; asm("mul.rn.bf16x2 %0, %1, %2;" : "=r"(r) : "r"(a), "r"(b)); return r; }
__device__ __forceinline__ uint32_t bf2_add(uint32_t a, uint32_t b) { uint32_t r; asm("add.rn.bf16x2 %0, %1, %2;" : "=r"(r) : "r"(a), "r"(b)); return r; }
__device__ __forceinline__ uint32_t bf2_sub(uint32_t a, uint32_t b) { uint32_t r; asm("sub.rn.bf16x2 %0, %1, %2;" : "=r"(r) : "r"(a), "r"(b)); return r; }
__device__ __forceinline__ void wait_cnt(const unsigned* p, unsigned target) {
    unsigned it = 0;
    while ((int)(ld_acq(p) - target) < 0 && ++it < SPIN_LIMIT) __nanosleep(64);
}
__device__ __forceinline__ uint32_t gtime32() { uint32_t t; asm volatile("mov.u32 %0, %%globaltimer_lo;" : "=r"(t) :: "memory"); return t; }
__device__ __forceinline__ void gate(uint32_t tick_addr, uint32_t ga = GATE_A, uint32_t gb = GATE_B) {
    uint32_t t1, p;
    asm volatile("ld.volatile.shared.v2.u32 {%0,%1}, [%2];" : "=r"(t1), "=r"(p) : "r"(tick_addr) : "memory");
    uint32_t d = gtime32() - t1;
    if (d < 4u * p) {
        d -= d >= 2u * p ? 2u * p : 0u;
        d -= d >= p ? p : 0u;
        if (d + ga >= p && d + gb < p) {
            const uint32_t t2 = gtime32() + (p - gb - d);
            while ((int)(gtime32() - t2) < 0) {}
        }
    }
}

__device__ __forceinline__ void read_tick(uint32_t tick_addr) {
    const uint2 tk = ld_vol_u2(&g_tick);
    uint32_t p = tk.x - tk.y;
    p = p > GATE_P + 100u ? GATE_P + 100u : p;
    asm volatile("st.volatile.shared.v2.u32 [%0], {%1,%2};" :: "r"(tick_addr), "r"(tk.x), "r"(p) : "memory");
}

__device__ __forceinline__ void s4d_phase(unsigned char* smem_raw, const bf16* __restrict__ x, const bf16* __restrict__ logA,
                                          const bf16* __restrict__ Aim, const bf16* __restrict__ Cre, const bf16* __restrict__ Cim,
                                          const bf16* __restrict__ logdt, const bf16* __restrict__ dskip, const bf16* __restrict__ wslice, unsigned ep, uint32_t tick) {
    const int tid = threadIdx.x, warp = __shfl_sync(0xffffffffu, tid >> 5, 0), lane = tid & 31;
    const int d0 = blockIdx.x * SD_CH;
    float* tab = reinterpret_cast<float*>(smem_raw + SD_CH * SD_U + warp * SD_WSTR);
    const uint32_t wb = smem_u32(tab);
    const int g = lane >> 2, tq = lane & 3;
    uint2 prm[4];
    float ldt;
    auto load_prm = [&](int d) {
        prm[0] = __ldg(reinterpret_cast<const uint2*>(logA + d * NST) + lane); prm[1] = __ldg(reinterpret_cast<const uint2*>(Aim + d * NST) + lane);
        prm[2] = __ldg(reinterpret_cast<const uint2*>(Cre + d * NST) + lane); prm[3] = __ldg(reinterpret_cast<const uint2*>(Cim + d * NST) + lane);
        ldt = __bfloat162float(logdt[d]);
    };
    load_prm(d0 + warp);
    for (int i = lane; i < 2 * SD_CPY / 16; i += 32) reinterpret_cast<uint4*>(tab + SD_TAP / 4)[i] = make_uint4(0u, 0u, 0u, 0u);
    TS3(20);
#pragma unroll 1
    for (int ch = 0; ch < 2; ch++) {
        const int d = d0 + 8 * ch + warp;
        const uint32_t ub = smem_u32(smem_raw) + (8 * ch + warp) * SD_U;
        float k2048 = 0.f, sinv;
        {
            const float dt = bf16r(expf(ldt));
            uint32_t cm = __vmaxu2(__vmaxu2(prm[2].x & 0x7fff7fffu, prm[2].y & 0x7fff7fffu), __vmaxu2(prm[3].x & 0x7fff7fffu, prm[3].y & 0x7fff7fffu));
            cm = __reduce_max_sync(0xffffffffu, max(cm << 16, cm & 0xffff0000u));
            int e = 134 - (int)(__float_as_uint(__uint_as_float(cm) * dt) >> 23);
            e = e > 100 ? 100 : (e < -100 ? -100 : e);
            const float s2 = __uint_as_float((uint32_t)(128 + e) << 23);
            sinv = __uint_as_float((uint32_t)(127 - e) << 23);
#pragma unroll
            for (int j = 0; j < 4; j++) {
                float q[4];
#pragma unroll
                for (int i = 0; i < 4; i++) { const uint32_t w = j < 2 ? prm[i].x : prm[i].y; q[i] = __uint_as_float((j & 1) ? w & 0xffff0000u : w << 16); }
                const float zl = -bf16r(expf(q[0])) * dt * 1.4426950408889634f;
                const float zt = q[1] * dt * 0.15915494309189535f;
                const float cr = s2 * (q[2] * dt), ci = s2 * (q[3] * dt);
                float ar, ai, br, bi, er, ei;
                cexp_t(zl * 8.f, zt * 8.f, ar, ai);
                cexp_t(zl * 128.f, zt * 128.f, br, bi);
                cexp_t(zl * 2048.f, zt * 2048.f, er, ei);
                k2048 += cr * er - ci * ei;
                *reinterpret_cast<float4*>(tab + (lane + 32 * j) * 8) = make_float4(zl, zt, cr, ci);
                *reinterpret_cast<float4*>(tab + (lane + 32 * j) * 8 + 4) = make_float4(ar, ai, br, bi);
            }
#pragma unroll
            for (int o = 16; o; o >>= 1) k2048 += __shfl_xor_sync(0xffffffffu, k2048, o);
        }
        __syncwarp();
        {
            float kc[5][4];
#pragma unroll
            for (int i = 0; i < 5; i++) { kc[i][0] = kc[i][1] = kc[i][2] = kc[i][3] = 0.f; }
            const float gf = (float)g;
#pragma unroll 2
            for (int ks = 0; ks < 16; ks++) {
                uint32_t a0[4][2], a1[4][2], b0[5], b1[5];
                kb_state(tab + (8 * ks + tq) * 8, gf, a0, b0);
                kb_state(tab + (8 * ks + 4 + tq) * 8, gf, a1, b1);
#pragma unroll
                for (int i = 0; i < 5; i++) {
                    const int c = i > 0 ? i - 1 : 0;
                    asm volatile("mma.sync.aligned.m16n8k16.row.col.f32.f16.f16.f32 {%0,%1,%2,%3}, {%4,%5,%6,%7}, {%8,%9}, {%0,%1,%2,%3};"
                                 : "+f"(kc[i][0]), "+f"(kc[i][1]), "+f"(kc[i][2]), "+f"(kc[i][3])
                                 : "r"(a0[c][0]), "r"(a0[c][1]), "r"(a1[c][0]), "r"(a1[c][1]), "r"(b0[i]), "r"(b1[i]));
                }
            }
            const uint32_t tp = wb + SD_TAP;
            const uint32_t a0 = tp + 2 * (O_U + 96 * g - 4 * tq);
            const uint32_t a2 = tp + 2 * (((g & 1) ? O_U + 96 * (2 * (g & 3)) : ((g & 2) ? O_W35 : O_W79 + 1)) - 32 - 8 * tq - (g >> 2));
            const uint32_t a3 = tp + 2 * (((g & 1) ? O_W35 : O_W610 + 1) - 64 - 16 * tq - (g >> 1));
            const uint32_t a4 = tp + 2 * (-128 - 32 * tq - g);
#pragma unroll
            for (int c = 0; c < 4; c++) {
                const int e = (c & 1) * 16 + (c >> 1) * 8;
                const bool first = c == 0 && lane == 0;
                put_tap(a0 - e / 4, kc[0][c] * sinv);
                put_tap(a0 - 32 - e / 4, kc[1][c] * sinv);
                put_tap(first ? tp + 2 * (O_U - 32) : a2 - e / 2, kc[2][c] * sinv);
                put_tap(first ? tp + 2 * (O_W79 - 63) : a3 - e, kc[3][c] * sinv);
                put_tap(first ? tp + 2 * (O_W610 - 127) : a4 + 2 * (O_W511 + 1 - e), kc[4][c] * sinv);
                if ((g & 1) == 0) {
                    put_tap(a4 + 2 * (O_U4 - e), kc[4][c] * sinv);
                    put_tap(first ? tp + 2 * (O_U3 - 128) : a4 + 2 * (O_U4 + 1 - e), kc[4][c] * sinv);
                }
            }
            if (lane == 0) {
                put_tap(tp + 2 * (O_U + 96 - 32), kc[2][0] * sinv);
                put_tap(tp + 2 * (O_U + 192 - 64), kc[3][0] * sinv);
                put_tap(tp + 2 * (O_W511 - 255), k2048 * sinv);
                put_tap(tp + 2 * (O_U4 - 255), k2048 * sinv);
            }
        }
        TS3(21 + 2 * ch);
        if (ch == 0) { if (!STAGGER || warp < 4) named_bar(1, 384); }
        else {
#pragma unroll
            for (int i = 0; i < 4; i++) asm volatile("prefetch.global.L2 [%0];" :: "l"(wslice + (size_t)((tid & 127) + 128 * i) * DM));
        }
        __syncwarp();
        if (tid == 0) TSS(18, 4 * ch);
        const uint32_t sh = wb + 80 + 11 * SD_ROW;
#pragma unroll
        for (int p = 0; p < 8; p++) {
            uint4 v;
            asm volatile("ld.shared.v4.u32 {%0,%1,%2,%3}, [%4];" : "=r"(v.x), "=r"(v.y), "=r"(v.z), "=r"(v.w) : "r"(ub + p * SD_ROW + lane * 16) : "memory");
            uint32_t pv = __shfl_up_sync(0xffffffffu, v.w, 1);
            pv = lane == 0 ? 0u : pv;
            asm volatile("st.shared.v4.u32 [%0], {%1,%2,%3,%4};" :: "r"(sh + (p - 8) * SD_ROW + lane * 16), "r"(__byte_perm(pv, v.x, 0x5432)), "r"(__byte_perm(v.x, v.y, 0x5432)),
                         "r"(__byte_perm(v.y, v.z, 0x5432)), "r"(__byte_perm(v.z, v.w, 0x5432)) : "memory");
            if (p >= 5) asm volatile("st.shared.v4.u32 [%0], {%1,%2,%3,%4};" :: "r"(sh + (p - 16) * SD_ROW + lane * 16), "r"(pv), "r"(v.x), "r"(v.y), "r"(v.z) : "memory");
        }
        __syncwarp();
        if (tid == 0) TSS(18, 4 * ch + 1);
        float acc[16][4];
#pragma unroll
        for (int i = 0; i < 16; i++) { acc[i][0] = acc[i][1] = acc[i][2] = acc[i][3] = 0.f; }
        {
            const uint32_t ka = wb + SD_TAP + ((g & 1) ? 0 : SD_CPY - 2) + 2 * (2 * tq - g);
            uint32_t b[16][2], b2[14][2];
#pragma unroll
            for (int k = 0; k < 16; k++) { b[k][0] = b[k][1] = 0u; if (k < 14) b2[k][0] = b2[k][1] = 0u; }
#pragma unroll 1
            for (int ps = 0; ps < 14; ps++) {
                const uint32_t pw = __shfl_sync(0xffffffffu, SD_PASS[ps], 0), type = pw & 3u, kp = ka + (pw >> 16);
                const int dl = (pw >> 2) & 7, d0 = (pw >> 8) & 15, d1 = (pw >> 12) & 15;
                uint32_t t[2][4];
                tap_tile(t[0], kp - 32 * d0);
                if (type == 0) {
                    const int p = (lane & 7) - dl;
                    const uint32_t ra = (p < 0 ? sh : ub) + p * SD_ROW + (lane >> 3) * 16;
#pragma unroll
                    for (int k = 0; k < 8; k++)
                        asm volatile("ldmatrix.sync.aligned.m8n8.x4.shared.b16 {%0,%1,%2,%3}, [%4];"
                                     : "=r"(b[2 * k][0]), "=r"(b[2 * k][1]), "=r"(b[2 * k + 1][0]), "=r"(b[2 * k + 1][1]) : "r"(ra + k * 64));
                } else if (type == 2) {
                    const int p = (lane & 15) - 11, xo = 2 * tq - g;
                    const uint32_t qa = (p < 0 ? sh : ub) + p * SD_ROW + (lane >> 4) * 16;
                    const int lx = 6 - 5 * dl, hx = 8 - 3 * dl, ly = 2 - 2 * dl, hy = 4 + 2 * dl;
                    const uint32_t sel[4] = {band2(xo, lx, hx), band2(xo, ly, hy), band2(xo + 8, lx, hx), band2(xo + 8, ly, hy)};
#pragma unroll
                    for (int k = 0; k < 14; k++) {
                        uint32_t q[4];
                        ldsm_x4_t(q, qa + k * 32);
#pragma unroll
                        for (int i = 0; i < 2; i++) {
                            float w[4];
                            mma_z(w, sel, q[2 * i], q[2 * i + 1]);
                            b[k][i] = pack_bf16(w[0], w[1]);
                            b2[k][i] = pack_bf16(w[2], w[3]);
                        }
                    }
                } else if (type == 3) {
#pragma unroll
                    for (int k = 0; k < 14; k++) { b[k][0] = b2[k][0]; b[k][1] = b2[k][1]; }
                }
#pragma unroll
                for (int d = 0; d < 16; d += 2) {
                    if (d >= 8 || d >= d0) {
                        tap_tile(t[1], kp - 32 * (d + 1));
#pragma unroll
                        for (int k = 0; k + d < 16; k++) mma_bf16(acc[k + d], t[0], b[k][0], b[k][1]);
                        if ((d == 2 || d == 4 || d == 8) && d == d1) break;
                        if (d < 14) tap_tile(t[0], kp - 32 * (d + 2));
#pragma unroll
                        for (int k = 0; k + d + 1 < 16; k++) mma_bf16(acc[k + d + 1], t[1], b[k][0], b[k][1]);
                    }
                }
            }
        }
        __syncwarp();
        if (tid == 0) TSS(18, 4 * ch + 2);
        load_prm(d0 + 8 + warp);
        if (ch == 0) { if (lane == 0) wait_cnt(&g_gcnt[0], SD_NCTA * ep); __syncwarp(); }
        if (tid == 0) TSS(18, 4 * ch + 3);
        uint4 gv[8];
#pragma unroll
        for (int i = 0; i < 8; i++) gv[i] = __ldcg(reinterpret_cast<const uint4*>(g_gate) + lane + 32 * i);
        const uint32_t dd = __byte_perm(*reinterpret_cast<const unsigned short*>(dskip + d), 0u, 0x1010);
#pragma unroll
        for (int i = 0; i < 8; i++) {
            uint32_t u[4];
            ldsm_x4_t(u, ub + (lane & 7) * SD_ROW + (lane >> 3) * 16 + i * 64);
            asm volatile("stmatrix.sync.aligned.m8n8.x4.shared.b16 [%0], {%1,%2,%3,%4};"
                         :: "r"(wb + (lane + 32 * i) * 16),
                            "r"(bf2_add(pack_bf16(acc[2 * i][0], acc[2 * i][1]), bf2_mul(u[0], dd))), "r"(bf2_add(pack_bf16(acc[2 * i][2], acc[2 * i][3]), bf2_mul(u[1], dd))),
                            "r"(bf2_add(pack_bf16(acc[2 * i + 1][0], acc[2 * i + 1][1]), bf2_mul(u[2], dd))), "r"(bf2_add(pack_bf16(acc[2 * i + 1][2], acc[2 * i + 1][3]), bf2_mul(u[3], dd))) : "memory");
        }
        if (GATE_Y) gate(tick);
        __syncwarp();
#pragma unroll
        for (int i = 0; i < 8; i++) {
            const uint4 y = *reinterpret_cast<const uint4*>(tab + (lane + 32 * i) * 4);
            *reinterpret_cast<uint4*>(g_y + (((lane >> 1) + 16 * i) * DM + d) * 16 + (lane & 1) * 8) =
                make_uint4(bf2_mul(bf2_sub(0x3f803f80u, gv[i].x), y.x), bf2_mul(bf2_sub(0x3f803f80u, gv[i].y), y.y),
                           bf2_mul(bf2_sub(0x3f803f80u, gv[i].z), y.z), bf2_mul(bf2_sub(0x3f803f80u, gv[i].w), y.w));
        }
        __syncwarp();
        TS3(22 + 2 * ch);
    }
}
__device__ __forceinline__ void s4d_stage_u(unsigned char* smem_raw, const bf16* __restrict__ x, int pt) {
    const int p = pt & 7, w0 = pt >> 3;
    const uint4* src = reinterpret_cast<const uint4*>(x + (size_t)(16 * w0 + p) * DM + blockIdx.x * SD_CH);
    uint32_t* dst = reinterpret_cast<uint32_t*>(smem_raw + p * SD_ROW) + w0;
#pragma unroll 1
    for (int b = 0; b < 4; b++) {
        uint4 v[2][2][2];
#pragma unroll
        for (int i = 0; i < 8; i++) v[i >> 2][(i >> 1) & 1][i & 1] = src[((b * 2 + (i >> 2)) * 256 + ((i >> 1) & 1) * 8) * (DM / 8) + (i & 1)];
#pragma unroll
        for (int i = 0; i < 4; i++) {
            const uint32_t* lo = reinterpret_cast<const uint32_t*>(&v[i >> 1][0][i & 1]);
            const uint32_t* hi = reinterpret_cast<const uint32_t*>(&v[i >> 1][1][i & 1]);
#pragma unroll
            for (int c = 0; c < 8; c++) dst[((i & 1) * 8 + c) * (SD_U / 4) + (b * 2 + (i >> 1)) * 16] = __byte_perm(lo[c >> 1], hi[c >> 1], (c & 1) ? 0x7632 : 0x5410);
        }
    }
    asm volatile("bar.arrive 1, 384;" ::: "memory");
}

constexpr int WOC = DM / 3;
constexpr int TBUF = 5 * DH * 16;
constexpr int XBUF = SEG * DM * 2;
constexpr int SM_BAR = 0;
constexpr int B_SB = 0, B_VX = 16, B_XT = 32, B_XF = 144, B_W = 64, B_E = 136;
constexpr int SM_SC = 256;
constexpr int SM_F = SM_SC + 1280;
constexpr int SM_VM = SM_F + 2048;
constexpr int SM_S = SM_VM + 2048;
constexpr int SM_O = SM_S + 2560;
constexpr int SM_M = SM_O + 2048;
constexpr int SM_WS = 19456;
constexpr int SM_T = SM_WS + 49152;
constexpr int SM_VX = SM_T + 4 * TBUF;
constexpr int SM_X = SM_VX + 2 * 8192;
constexpr int SM_X01 = SM_WS + DM * DH * 2;
__host__ __device__ constexpr int x01_off(int b) { return b < 2 ? 1024 + b * 9216 : SM_X01 + (b == 2 ? 6 : b - 3) * 9216; }
constexpr int CH_SMEM = SM_X01 + 8 * 8192;
static_assert(SM_M + DM * 16 <= SM_WS && SM_X + 13 * 8192 <= CH_SMEM && NS <= 10 && CH_SMEM <= 232448 && SM_X % 1024 == 0 && SM_X01 % 1024 == 0 && 1024 + 2 * 9216 <= SM_WS, "smem");
__device__ __forceinline__ uint32_t clock32() { uint32_t t; asm volatile("mov.u32 %0, %%clock;" : "=r"(t) :: "memory"); return t; }

__device__ __forceinline__ uint32_t mapa(uint32_t a, uint32_t rank) {
    uint32_t r; asm volatile("mapa.shared::cluster.u32 %0, %1, %2;" : "=r"(r) : "r"(a), "r"(rank)); return r;
}
__device__ __forceinline__ void st_async32(uint32_t addr, uint32_t v, uint32_t mbar) {
    asm volatile("st.async.weak.shared::cluster.mbarrier::complete_tx::bytes.b32 [%0], %1, [%2];" :: "r"(addr), "r"(v), "r"(mbar) : "memory");
}
__device__ __forceinline__ void mbar_init(uint32_t bar, uint32_t cnt) {
    asm volatile("mbarrier.init.shared::cta.b64 [%0], %1;" :: "r"(bar), "r"(cnt) : "memory");
}
__device__ __forceinline__ void mbar_expect(uint32_t bar, uint32_t bytes) {
    asm volatile("mbarrier.arrive.expect_tx.shared::cta.b64 _, [%0], %1;" :: "r"(bar), "r"(bytes) : "memory");
}
__device__ __forceinline__ void mbar_wait(uint32_t bar, uint32_t parity) {
    unsigned it = 0;
    uint32_t ok;
    do {
        ++it;
        asm volatile("{\n.reg .pred p;\nmbarrier.try_wait.parity.shared::cta.b64 p, [%1], %2;\nselp.u32 %0, 1, 0, p;\n}" : "=r"(ok) : "r"(bar), "r"(parity) : "memory");
    } while ((ok == 0u) & (it < SPIN_LIMIT));
}
__device__ __forceinline__ void mbar_wait_fast(uint32_t bar, uint32_t parity) {
    mbar_wait(bar, parity);
}
__device__ __forceinline__ void mbar_wait_long(uint32_t bar, uint32_t parity) {
    unsigned it = 0;
    while (true) {
        uint32_t ok;
        asm volatile("{\n.reg .pred p;\nmbarrier.try_wait.parity.shared::cta.b64 p, [%1], %2, %3;\nselp.u32 %0, 1, 0, p;\n}"
                     : "=r"(ok) : "r"(bar), "r"(parity), "r"(20000u) : "memory");
        if (ok || ++it >= SPIN_LIMIT) break;
    }
}
__device__ __forceinline__ bool mbar_test(uint32_t bar, uint32_t parity) {
    uint32_t ok;
    asm volatile("{\n.reg .pred p;\nmbarrier.test_wait.parity.shared::cta.b64 p, [%1], %2;\nselp.u32 %0, 1, 0, p;\n}" : "=r"(ok) : "r"(bar), "r"(parity) : "memory");
    return ok != 0u;
}
__device__ __forceinline__ uint64_t policy_evict_first() {
    uint64_t pol; asm volatile("createpolicy.fractional.L2::evict_first.b64 %0, 1.0;" : "=l"(pol)); return pol;
}
__device__ __forceinline__ void cluster_sync_all() {
    asm volatile("barrier.cluster.arrive.release.aligned;\nbarrier.cluster.wait.acquire.aligned;" ::: "memory");
}
__device__ __forceinline__ uint4 ld_vol_u4(const uint4* p) {
    uint4 v; asm volatile(LDV4 : "=r"(v.x), "=r"(v.y), "=r"(v.z), "=r"(v.w) : "l"(p) : "memory"); return v;
}
__device__ __forceinline__ void ld_vol_u4_p(uint4& v, const uint4* p, uint32_t pred) {
    asm volatile("{\n.reg .pred p;\nsetp.ne.u32 p, %5, 0;\n@p " LDV4 "\n}"
                 : "+r"(v.x), "+r"(v.y), "+r"(v.z), "+r"(v.w) : "l"(p), "r"(pred) : "memory");
}
__device__ __forceinline__ void st_vol_u4(uint4* p, uint4 v) {
    asm volatile(STV4 :: "l"(p), "r"(v.x), "r"(v.y), "r"(v.z), "r"(v.w) : "memory");
}
__device__ __forceinline__ void mma_bf16_r(float (&d)[4], uint32_t a0, uint32_t a1, uint32_t a2, uint32_t a3, uint32_t b0, uint32_t b1) {
    asm volatile("mma.sync.aligned.m16n8k16.row.col.f32.bf16.bf16.f32 {%0,%1,%2,%3}, {%4,%5,%6,%7}, {%8,%9}, {%0,%1,%2,%3};"
                 : "+f"(d[0]), "+f"(d[1]), "+f"(d[2]), "+f"(d[3])
                 : "r"(a0), "r"(a1), "r"(a2), "r"(a3), "r"(b0), "r"(b1));
}

__device__ __forceinline__ uint64_t smem_desc(uint32_t addr, uint32_t lbo, uint32_t sbo) {
    return (uint64_t)((addr & 0x3FFFF) >> 4) | ((uint64_t)(lbo >> 4) << 16) | ((uint64_t)(sbo >> 4) << 32);
}
__device__ __forceinline__ void wg_fence() { asm volatile("wgmma.fence.sync.aligned;" ::: "memory"); }
__device__ __forceinline__ void wg_commit() { asm volatile("wgmma.commit_group.sync.aligned;" ::: "memory"); }
__device__ __forceinline__ void wg_wait0() { asm volatile("wgmma.wait_group.sync.aligned 0;" ::: "memory"); }
__device__ __forceinline__ void fence_async() { asm volatile("fence.proxy.async.shared::cta;" ::: "memory"); }
__device__ __forceinline__ void wgmma_n64_ss(float (&d)[32], uint64_t adesc, uint64_t bdesc) {
    asm volatile("{\n.reg .pred p;\nsetp.eq.b32 p, 0, 0;\n"
                 "wgmma.mma_async.sync.aligned.m64n64k16.f32.bf16.bf16 {%0,%1,%2,%3,%4,%5,%6,%7,%8,%9,%10,%11,%12,%13,%14,%15,%16,%17,%18,%19,%20,%21,%22,%23,%24,%25,%26,%27,%28,%29,%30,%31}, %32, %33, p, 1, 1, 1, 0;\n}"
                 : "+f"(d[0]), "+f"(d[1]), "+f"(d[2]), "+f"(d[3]), "+f"(d[4]), "+f"(d[5]), "+f"(d[6]), "+f"(d[7]), "+f"(d[8]), "+f"(d[9]), "+f"(d[10]), "+f"(d[11]), "+f"(d[12]), "+f"(d[13]), "+f"(d[14]), "+f"(d[15]), "+f"(d[16]), "+f"(d[17]), "+f"(d[18]), "+f"(d[19]), "+f"(d[20]), "+f"(d[21]), "+f"(d[22]), "+f"(d[23]), "+f"(d[24]), "+f"(d[25]), "+f"(d[26]), "+f"(d[27]), "+f"(d[28]), "+f"(d[29]), "+f"(d[30]), "+f"(d[31])
                 : "l"(adesc), "l"(bdesc));
}
__device__ __forceinline__ void wgmma_n72_ss(float (&d)[36], uint64_t adesc, uint64_t bdesc) {
    asm volatile("{\n.reg .pred p;\nsetp.eq.b32 p, 0, 0;\n"
                 "wgmma.mma_async.sync.aligned.m64n72k16.f32.bf16.bf16 {%0,%1,%2,%3,%4,%5,%6,%7,%8,%9,%10,%11,%12,%13,%14,%15,%16,%17,%18,%19,%20,%21,%22,%23,%24,%25,%26,%27,%28,%29,%30,%31,%32,%33,%34,%35}, %36, %37, p, 1, 1, 1, 0;\n}"
                 : "+f"(d[0]), "+f"(d[1]), "+f"(d[2]), "+f"(d[3]), "+f"(d[4]), "+f"(d[5]), "+f"(d[6]), "+f"(d[7]), "+f"(d[8]), "+f"(d[9]), "+f"(d[10]), "+f"(d[11]), "+f"(d[12]), "+f"(d[13]), "+f"(d[14]), "+f"(d[15]), "+f"(d[16]), "+f"(d[17]), "+f"(d[18]), "+f"(d[19]), "+f"(d[20]), "+f"(d[21]), "+f"(d[22]), "+f"(d[23]), "+f"(d[24]), "+f"(d[25]), "+f"(d[26]), "+f"(d[27]), "+f"(d[28]), "+f"(d[29]), "+f"(d[30]), "+f"(d[31]), "+f"(d[32]), "+f"(d[33]), "+f"(d[34]), "+f"(d[35])
                 : "l"(adesc), "l"(bdesc));
}
__device__ __forceinline__ void tma_2d(uint32_t dst, const CUtensorMap* tm, int c0, int c1, uint32_t mbar) {
    asm volatile("cp.async.bulk.tensor.2d.shared::cluster.global.tile.mbarrier::complete_tx::bytes [%0], [%1, {%2, %3}], [%4];"
                 :: "r"(dst), "l"(tm), "r"(c0), "r"(c1), "r"(mbar) : "memory");
}

__device__ __forceinline__ void bulk_g2s(uint32_t dst, const void* src, uint32_t bytes, uint32_t mbar) {
    asm volatile("cp.async.bulk.shared::cluster.global.mbarrier::complete_tx::bytes [%0], [%1], %2, [%3];"
                 :: "r"(dst), "l"(src), "r"(bytes), "r"(mbar) : "memory");
}
__device__ __forceinline__ void bulk_g2s_h(uint32_t dst, const void* src, uint32_t bytes, uint32_t mbar, uint64_t pol) {
    asm volatile("cp.async.bulk.shared::cluster.global.mbarrier::complete_tx::bytes.L2::cache_hint [%0], [%1], %2, [%3], %4;"
                 :: "r"(dst), "l"(src), "r"(bytes), "r"(mbar), "l"(pol) : "memory");
}
__device__ __forceinline__ void tma_2d_mc(uint32_t dst, const CUtensorMap* tm, int c0, int c1, uint32_t mbar) {
    asm volatile("cp.async.bulk.tensor.2d.shared::cluster.global.tile.mbarrier::complete_tx::bytes.multicast::cluster [%0], [%1, {%2, %3}], [%4], %5;"
                 :: "r"(dst), "l"(tm), "r"(c0), "r"(c1), "r"(mbar), "h"((unsigned short)7) : "memory");
}
__device__ __forceinline__ void bulk_s2s(uint32_t dst, uint32_t src, uint32_t bytes, uint32_t mbar) {
    asm volatile("cp.async.bulk.shared::cluster.shared::cta.mbarrier::complete_tx::bytes [%0], [%1], %2, [%3];"
                 :: "r"(dst), "r"(src), "r"(bytes), "r"(mbar) : "memory");
}
__device__ __forceinline__ void wgmma_n40_ss(float (&d)[20], uint64_t adesc, uint64_t bdesc, int scale_d) {
    asm volatile("{\n.reg .pred p;\nsetp.ne.b32 p, %22, 0;\n"
                 "wgmma.mma_async.sync.aligned.m64n40k16.f32.bf16.bf16 {%0,%1,%2,%3,%4,%5,%6,%7,%8,%9,%10,%11,%12,%13,%14,%15,%16,%17,%18,%19}, %20, %21, p, 1, 1, 1, 1;\n}"
                 : "+f"(d[0]), "+f"(d[1]), "+f"(d[2]), "+f"(d[3]), "+f"(d[4]), "+f"(d[5]), "+f"(d[6]), "+f"(d[7]),
                   "+f"(d[8]), "+f"(d[9]), "+f"(d[10]), "+f"(d[11]), "+f"(d[12]), "+f"(d[13]), "+f"(d[14]), "+f"(d[15]),
                   "+f"(d[16]), "+f"(d[17]), "+f"(d[18]), "+f"(d[19])
                 : "l"(adesc), "l"(bdesc), "r"(scale_d));
}
__device__ __forceinline__ void wgmma_n64_z(float (&d)[32], const uint32_t (&a)[4], uint64_t bdesc) {
    asm volatile("{\n.reg .pred p;\nsetp.ne.b32 p, 0, 0;\n"
                 "wgmma.mma_async.sync.aligned.m64n64k16.f32.bf16.bf16 {%0,%1,%2,%3,%4,%5,%6,%7,%8,%9,%10,%11,%12,%13,%14,%15,%16,%17,%18,%19,%20,%21,%22,%23,%24,%25,%26,%27,%28,%29,%30,%31}, {%32,%33,%34,%35}, %36, p, 1, 1, 0;\n}"
                 : "=f"(d[0]), "=f"(d[1]), "=f"(d[2]), "=f"(d[3]), "=f"(d[4]), "=f"(d[5]), "=f"(d[6]), "=f"(d[7]),
                   "=f"(d[8]), "=f"(d[9]), "=f"(d[10]), "=f"(d[11]), "=f"(d[12]), "=f"(d[13]), "=f"(d[14]), "=f"(d[15]),
                   "=f"(d[16]), "=f"(d[17]), "=f"(d[18]), "=f"(d[19]), "=f"(d[20]), "=f"(d[21]), "=f"(d[22]), "=f"(d[23]),
                   "=f"(d[24]), "=f"(d[25]), "=f"(d[26]), "=f"(d[27]), "=f"(d[28]), "=f"(d[29]), "=f"(d[30]), "=f"(d[31])
                 : "r"(a[0]), "r"(a[1]), "r"(a[2]), "r"(a[3]), "l"(bdesc));
}
__device__ __forceinline__ void wgmma_n64(float (&d)[32], const uint32_t (&a)[4], uint64_t bdesc, int scale_d) {
    asm volatile("{\n.reg .pred p;\nsetp.ne.b32 p, %37, 0;\n"
                 "wgmma.mma_async.sync.aligned.m64n64k16.f32.bf16.bf16 {%0,%1,%2,%3,%4,%5,%6,%7,%8,%9,%10,%11,%12,%13,%14,%15,%16,%17,%18,%19,%20,%21,%22,%23,%24,%25,%26,%27,%28,%29,%30,%31}, {%32,%33,%34,%35}, %36, p, 1, 1, 0;\n}"
                 : "+f"(d[0]), "+f"(d[1]), "+f"(d[2]), "+f"(d[3]), "+f"(d[4]), "+f"(d[5]), "+f"(d[6]), "+f"(d[7]),
                   "+f"(d[8]), "+f"(d[9]), "+f"(d[10]), "+f"(d[11]), "+f"(d[12]), "+f"(d[13]), "+f"(d[14]), "+f"(d[15]),
                   "+f"(d[16]), "+f"(d[17]), "+f"(d[18]), "+f"(d[19]), "+f"(d[20]), "+f"(d[21]), "+f"(d[22]), "+f"(d[23]),
                   "+f"(d[24]), "+f"(d[25]), "+f"(d[26]), "+f"(d[27]), "+f"(d[28]), "+f"(d[29]), "+f"(d[30]), "+f"(d[31])
                 : "r"(a[0]), "r"(a[1]), "r"(a[2]), "r"(a[3]), "l"(bdesc), "r"(scale_d));
}

constexpr int SB_FULL = 0, SB_EMPTY = 64, SB_QKF = 128, SB_VF = 144, SB_QKE = 160, SB_VE = 176, SB_OF = 192, SB_WO = 208, SB_TICK = 216, SB_SEEN = 224, SB_FI = 232, SB_REQ = 240;
constexpr int AT_0 = 256, AT_ST = 10240 + 2 * 9216;
constexpr int FS_A = 58368;
constexpr int FS_P = FS_A + 131072;
constexpr int FS_I = FS_P + 16384;
constexpr int FS_O = FS_I + 12288;
constexpr int FS_Z = FS_O + 12288, FS_G = AT_0 + 2 * AT_ST;
constexpr int SIDE_SMEM = FS_Z + 2048;
static_assert(SIDE_SMEM <= 232448 && FS_G + 128 <= FS_A && FS_A + SD_SMEM <= SIDE_SMEM, "smem");

__device__ __forceinline__ void wg_wait1() { asm volatile("wgmma.wait_group.sync.aligned 1;" ::: "memory"); }
__device__ __forceinline__ void mbar_arrive(uint32_t bar) { asm volatile("mbarrier.arrive.shared::cta.b64 _, [%0];" :: "r"(bar) : "memory"); }
__device__ __forceinline__ void wait_cnt_rlx(const unsigned* p, unsigned target, bool urgent) {
    unsigned it = 0, v;
    while (true) {
        asm volatile("ld.relaxed.gpu.global.u32 %0, [%1];" : "=r"(v) : "l"(p) : "memory");
        if ((int)(v - target) >= 0 || ++it >= SPIN_LIMIT) break;
        if (!urgent) __nanosleep(RLX_SLEEP);
    }
}

__device__ __forceinline__ float xrow_softmax(float (&sc)[20], uint32_t (&p)[5], int wq, int lane) {
    constexpr float EC = (float)(1.4426950408889634 * 0.08838834764831845);
    const int lim = 8 * wq + (lane >> 2) - 2 * (lane & 3);
    float mx = fmaxf(sc[0], sc[1]);
#pragma unroll
    for (int j = 1; j < 5; j++) {
        sc[4 * j] = 8 * j - 8 > lim ? -INFINITY : sc[4 * j];
        sc[4 * j + 1] = 8 * j - 7 > lim ? -INFINITY : sc[4 * j + 1];
    }
    mx = fmaxf(fmaxf(mx, fmaxf(fmaxf(sc[4], sc[5]), fmaxf(sc[8], sc[9]))), fmaxf(fmaxf(sc[12], sc[13]), fmaxf(sc[16], sc[17])));
    {
        const float m1 = __shfl_xor_sync(0xffffffffu, mx, 1), m2 = __shfl_xor_sync(0xffffffffu, mx, 2), m3 = __shfl_xor_sync(0xffffffffu, mx, 3);
        mx = fmaxf(fmaxf(mx, m1), fmaxf(m2, m3)) * EC;
    }
    float sum = 0.f;
#pragma unroll
    for (int j = 0; j < 5; j++) {
        float e0, e1;
        asm("ex2.approx.ftz.f32 %0, %1;" : "=f"(e0) : "f"(fmaf(sc[4 * j], EC, -mx)));
        asm("ex2.approx.ftz.f32 %0, %1;" : "=f"(e1) : "f"(fmaf(sc[4 * j + 1], EC, -mx)));
        p[j] = pack_bf16(e0, e1);
        sum += e0 + e1;
    }
    return sum;
}
__device__ __forceinline__ float xrow_inv(float sum) {
    sum += __shfl_xor_sync(0xffffffffu, sum, 1);
    sum += __shfl_xor_sync(0xffffffffu, sum, 2);
    float r;
    asm("rcp.approx.ftz.f32 %0, %1;" : "=f"(r) : "f"(sum));
    return r;
}

__device__ __forceinline__ void stsm_x4(uint32_t addr, uint32_t r0, uint32_t r1, uint32_t r2, uint32_t r3) {
    asm volatile("stmatrix.sync.aligned.m8n8.x4.shared.b16 [%0], {%1,%2,%3,%4};" :: "r"(addr), "r"(r0), "r"(r1), "r"(r2), "r"(r3) : "memory");
}
__device__ __forceinline__ void xrow_pv(uint32_t (&ob)[16], const uint32_t (&p)[5], float psum, uint32_t vt) {
    float o[32];
    const uint64_t dv = smem_desc(vt, 2048, 128);
    uint32_t pa[6][4];
#pragma unroll
    for (int i = 0; i < 6; i++) {
        const int ks = i >> 1, hf = i & 1;
        pa[i][hf] = p[2 * ks]; pa[i][hf ^ 1] = 0u;
        pa[i][2 + hf] = ks < 2 ? p[ks < 2 ? 2 * ks + 1 : 0] : 0u; pa[i][3 - hf] = 0u;
    }
    wg_fence();
#pragma unroll
    for (int i = 0; i < 6; i++) { if (i == 0) wgmma_n64_z(o, pa[0], dv); else wgmma_n64(o, pa[i], dv + (uint64_t)((i & 1) * 64 + (i >> 1) * 256), 1); }
    wg_commit();
    const float inv = xrow_inv(psum);
    wg_wait0();
#pragma unroll
    for (int i = 0; i < 8; i++) { ob[i] = pack_bf16(o[4 * i] * inv, o[4 * i + 1] * inv); ob[8 + i] = pack_bf16(o[4 * i + 2] * inv, o[4 * i + 3] * inv); }
}
__device__ __forceinline__ uint32_t h2_to_bf2(uint32_t h) {
    uint32_t r;
    asm("{\n.reg .f16 l, h;\n.reg .f32 a, b;\nmov.b32 {l, h}, %1;\ncvt.f32.f16 a, l;\ncvt.f32.f16 b, h;\ncvt.rn.bf16x2.f32 %0, b, a;\n}" : "=r"(r) : "r"(h));
    return r;
}
__device__ __forceinline__ uint32_t max_abs2(uint32_t a, uint32_t b) { uint32_t r; asm("max.NaN.xorsign.abs.bf16x2 %0, %1, %2;" : "=r"(r) : "r"(a), "r"(b)); return r; }
__device__ __forceinline__ uint32_t movm(uint32_t v) {
    uint32_t r; asm volatile("movmatrix.sync.aligned.m8n8.trans.b16 %0, %1;" : "=r"(r) : "r"(v)); return r;
}
__device__ __forceinline__ void bar_arrive(int id, int n) { asm volatile("bar.arrive %0, %1;" :: "r"(id), "r"(n) : "memory"); }
__device__ __forceinline__ void lds64(uint32_t& a, uint32_t& b, uint32_t addr) {
    asm volatile("ld.shared.v2.u32 {%0,%1}, [%2];" : "=r"(a), "=r"(b) : "r"(addr) : "memory");
}
__device__ __forceinline__ void lds64f(float& a, float& b, uint32_t addr) {
    asm volatile("ld.shared.v2.f32 {%0,%1}, [%2];" : "=f"(a), "=f"(b) : "r"(addr) : "memory");
}
__device__ __forceinline__ void st_async64(uint32_t addr, uint32_t a, uint32_t b, uint32_t mbar) {
    asm volatile("st.async.weak.shared::cluster.mbarrier::complete_tx::bytes.v2.b32 [%0], {%1,%2}, [%3];" :: "r"(addr), "r"(a), "r"(b), "r"(mbar) : "memory");
}
__device__ __forceinline__ void mma_z(float (&d)[4], const uint32_t (&a)[4], uint32_t b0, uint32_t b1) {
    asm volatile("mma.sync.aligned.m16n8k16.row.col.f32.bf16.bf16.f32 {%0,%1,%2,%3}, {%4,%5,%6,%7}, {%8,%9}, {%10,%10,%10,%10};"
                 : "=f"(d[0]), "=f"(d[1]), "=f"(d[2]), "=f"(d[3])
                 : "r"(a[0]), "r"(a[1]), "r"(a[2]), "r"(a[3]), "r"(b0), "r"(b1), "f"(0.f));
}
__device__ __forceinline__ void mma_k8(float (&d)[4], uint32_t a0, uint32_t a1, uint32_t b) {
    asm volatile("mma.sync.aligned.m16n8k8.row.col.f32.bf16.bf16.f32 {%0,%1,%2,%3}, {%4,%5}, {%6}, {%0,%1,%2,%3};"
                 : "+f"(d[0]), "+f"(d[1]), "+f"(d[2]), "+f"(d[3]) : "r"(a0), "r"(a1), "r"(b));
}
__global__ void __launch_bounds__(512, 1) k_side(const __grid_constant__ CUtensorMap tmo, const bf16* __restrict__ x, const bf16* __restrict__ logA, const bf16* __restrict__ Aim,
                                                 const bf16* __restrict__ Cre, const bf16* __restrict__ Cim, const bf16* __restrict__ logdt,
                                                 const bf16* __restrict__ Wo, const bf16* __restrict__ dskip, const bf16* __restrict__ gw,
                                                 bf16* __restrict__ out) {
    extern __shared__ __align__(1024) unsigned char smem_raw[];
    const uint32_t sbase = smem_u32(smem_raw);
    const int tid = threadIdx.x, warp = __shfl_sync(0xffffffffu, tid >> 5, 0), lane = tid & 31, cta = blockIdx.x;
    const int cb = cta >> 2, kq = cta & 3;
    if (tid == 0) {
        for (int i = 0; i < 8; i++) { mbar_init(sbase + SB_FULL + 8 * i, 1); mbar_init(sbase + SB_EMPTY + 8 * i, 4); }
        for (int i = 0; i < 2; i++) {
            mbar_init(sbase + SB_QKF + 8 * i, 1); mbar_init(sbase + SB_VF + 8 * i, 1); mbar_init(sbase + SB_QKE + 8 * i, 4);
            mbar_init(sbase + SB_VE + 8 * i, 1); mbar_init(sbase + SB_OF + 8 * i, 4);
        }
        mbar_init(sbase + SB_WO, 1);
        mbar_init(sbase + SB_FI, 1);
        mbar_init(sbase + SB_REQ, 4);
        *reinterpret_cast<uint2*>(smem_raw + SB_TICK) = make_uint2(0u, 0u);
        *reinterpret_cast<uint32_t*>(smem_raw + SB_SEEN) = 0u;
        asm volatile("fence.mbarrier_init.release.cluster;" ::: "memory");
    }
    TS3(0);
    unsigned ep;
    asm volatile("ld.volatile.global.u32 %0, [%1];" : "=r"(ep) : "l"(&g_epoch) : "memory");
    ep += 1u;
    asm volatile("fence.proxy.async;" ::: "memory");
    __syncthreads();
    if (warp >= 12) {
      asm volatile("setmaxnreg.dec.sync.aligned.u32 40;");
      if (SIDE_WAIT > 0) __nanosleep(SIDE_WAIT);
      {
        uint32_t gwv[9];
#pragma unroll
        for (int i = 0; i < 9; i++) gwv[i] = reinterpret_cast<const uint32_t*>(gw)[lane + 32 * i];
#pragma unroll 1
        for (int i = 0; i < 8; i++) {
            uint32_t xv[2][9];
            float sm[2];
#pragma unroll
            for (int j = 0; j < 2; j++) {
                const int t = min(cta * 57 + 8 * i + 4 * j + warp - 12, S_LEN - 1);
#pragma unroll
                for (int k = 0; k < 9; k++) xv[j][k] = reinterpret_cast<const uint32_t*>(x + t * DM)[lane + 32 * k];
            }
#pragma unroll
            for (int j = 0; j < 2; j++) {
                sm[j] = 0.f;
#pragma unroll
                for (int k = 0; k < 9; k++) {
                    const uint32_t pr = bf2_mul(xv[j][k], gwv[k]);
                    sm[j] += __uint_as_float(pr << 16) + __uint_as_float(pr & 0xffff0000u);
                }
            }
            float v = (lane < 16 ? sm[0] : sm[1]) + __shfl_xor_sync(0xffffffffu, lane < 16 ? sm[1] : sm[0], 16);
#pragma unroll
            for (int o = 8; o; o >>= 1) v += __shfl_xor_sync(0xffffffffu, v, o);
            const float gv = 1.f / (1.f + expf(-bf16r(v)));
            const int tt = 8 * i + 4 * (lane >> 4) + warp - 12;
            if ((lane & 15) == 0 && tt < 57 && cta * 57 + tt < S_LEN) g_gate[cta * 57 + tt] = __float2bfloat16_rn(gv);
        }
        named_bar(2, 128);
        if (tid == 480) {
            __threadfence();
            asm volatile("red.relaxed.gpu.global.add.u32 [%0], 1;" :: "l"(&g_gcnt[0]) : "memory");
        }
        __syncwarp();
      }
      if (warp == 12 || warp == 15) {
        named_bar(3, 320);
        if (tid == 384) {
            fence_async();
            mbar_expect(sbase + SB_WO, 131072);
#pragma unroll 1
            for (int i = 0; i < 8; i++) {
                gate(sbase + SB_TICK);
                tma_2d(sbase + FS_A + i * 16384, &tmo, cb * 64, kq * 1024 + i * 128, sbase + SB_WO);
                __nanosleep(150);
            }
            TSS(17, 2);
        }
        if (tid == 480) {
            __threadfence();
            asm volatile("red.relaxed.gpu.global.add.u32 [%0], 1;" :: "l"(&g_gcnt[32]) : "memory");
            TSS(17, 3);
        }
        __syncwarp();
        named_bar(7, 320);
        if (lane == 0) {
            const int pi = warp == 12 ? 0 : 1, kb = 2 * kq + pi;
            fence_async();
            for (int pr = 0; pr < NSEG / 2; pr++) {
                const bool gon = pr < NSEG / 2 - UNGATE_G;
                wait_cnt_rlx(&g_prog[pr * 8 + kb], 8u * ep, pr >= NSEG / 2 - 2);
                if (pi == 0) asm volatile("st.volatile.shared.u32 [%0], %1;" :: "r"(sbase + SB_SEEN), "r"(pr + 1) : "memory");
                if (pr >= 30 && pi == 0) TSS(4 + pr - 30, 0);
                if (pr == 31) TS3P(26);
                if (pr == 30) TS3P(1);
#pragma unroll
                for (int j = 0; j < 4; j++) {
                    const int st = 4 * pi + j;
                    mbar_wait_long(sbase + SB_EMPTY + 8 * st, ((uint32_t)pr & 1u) ^ 1u);
                    mbar_expect(sbase + SB_FULL + 8 * st, X_OXSZ);
                    if (gon) gate(sbase + SB_TICK);
                    bulk_g2s(sbase + FS_A + st * 16384, g_ox + ((size_t)(pr * NH + 4 * kb + j)) * 8192, X_OXSZ, sbase + SB_FULL + 8 * st);
                }
            }
        }
        __syncwarp();
      } else if (warp == 13) {
        if (lane == 0) {
            const uint64_t pol = policy_evict_first();
            bool next_ok = false;
            for (int seg = 0; seg < NATT; seg++) {
                const uint32_t st = seg & 1, ph = (uint32_t)(seg >> 1) & 1u, ab = sbase + AT_0 + st * AT_ST;
                if (!next_ok) {
                    const unsigned* fp = &g_flag[(cta & (NH - 1)) * NSEG + seg];
                    unsigned it = 0, v0, v1;
                    while (true) {
                        asm volatile("ld.relaxed.gpu.global.u32 %0, [%1];" : "=r"(v0) : "l"(fp) : "memory");
                        asm volatile("ld.relaxed.gpu.global.u32 %0, [%1+4];" : "=r"(v1) : "l"(fp) : "memory");
                        read_tick(sbase + SB_TICK);
                        if ((int)(v0 - 3u * ep) >= 0 || ++it >= SPIN_LIMIT) break;
                        if (seg < NSEG - UNGATE || cta >= NH) { __nanosleep(RLX_SLEEP); if (GATE_POLL) gate(sbase + SB_TICK, GP_A, GP_B); }
                    }
                    next_ok = (int)(v1 - 3u * ep) >= 0;
                } else next_ok = false;
                if (cta < NH) {
                    TSA(seg, 0);
                    mbar_wait_long(sbase + SB_QKE + 8 * st, ph ^ 1u);
                    TSA(seg, 1);
                    mbar_expect(sbase + SB_QKF + 8 * st, 2 * 9216);
                    if (seg < NSEG - UNGATE) gate(sbase + SB_TICK, GL_A, GL_B);
                    TSA(seg, 2);
                    bulk_g2s_h(ab + 10240, &g_qkv[seg][cta][0][1024], 9216, sbase + SB_QKF + 8 * st, pol);
                    bulk_g2s_h(ab + 10240 + 9216, &g_qkv[seg][cta][1][1024], 9216, sbase + SB_QKF + 8 * st, pol);
                    mbar_wait_long(sbase + SB_VE + 8 * st, ph ^ 1u);
                    mbar_expect(sbase + SB_VF + 8 * st, 10240);
                    if (seg < NSEG - UNGATE) gate(sbase + SB_TICK, GL_A, GL_B);
                    TSA(seg, 3);
                    bulk_g2s_h(ab, &g_qkv[seg][cta][2][0], 10240, sbase + SB_VF + 8 * st, pol);
                }
            }
        }
        __syncwarp();
      } else if (warp == 14) {
        if (lane == 0) {
            int seg = cta < NH ? 0 : NATT, p = 0;
            unsigned it = 0;
            while ((seg < NATT || p < NSEG / 2 - 1) && ++it < 16 * SPIN_LIMIT) {
                if (p < NSEG / 2 - 1 && mbar_test(sbase + SB_REQ, (uint32_t)p & 1u)) {
                    if (p == 0) { wait_cnt(&g_gcnt[32], SD_NCTA * ep); asm volatile("fence.proxy.async;" ::: "memory"); }
                    mbar_expect(sbase + SB_FI, (p < NSEG / 2 - 2 ? 12288 : 2048 + 32) + 2048 + 32);
                    if (GATE_F && p < NSEG / 2 - UNGATE_G - 1) gate(sbase + SB_TICK);
                    if (p < NSEG / 2 - 2) bulk_g2s(sbase + FS_I, &g_fp[p & 7][cta][0][0], 12288, sbase + SB_FI);
                    else {
                        bulk_g2s(sbase + FS_I, g_y + ((p * 4 + 4 + kq) * DM + cb * 64) * 16, 2048, sbase + SB_FI);
                        bulk_g2s(sbase + FS_G + 32, g_gate + p * 64 + 64 + kq * 16, 32, sbase + SB_FI);
                    }
                    bulk_g2s(sbase + FS_Z, g_y + ((p * 4 + kq) * DM + cb * 64) * 16, 2048, sbase + SB_FI);
                    bulk_g2s(sbase + FS_G, g_gate + p * 64 + kq * 16, 32, sbase + SB_FI);
                    p++;
                } else if (seg < NATT && mbar_test(sbase + SB_OF + 8 * (seg & 1), (uint32_t)(seg >> 1) & 1u)) {
                    const uint32_t st = seg & 1, ab = sbase + AT_0 + st * AT_ST;
                    TSA(seg, 5);
                    if (seg < NSEG - UNGATE) gate(sbase + SB_TICK, GS_A, GS_B);
                    TSA(seg, 6);
                    unsigned char* dst = reinterpret_cast<unsigned char*>(g_ox) + ((size_t)((seg >> 1) * NH + cta)) * 16384 + (seg & 1) * 4096;
                    asm volatile("cp.async.bulk.global.shared::cta.bulk_group [%0], [%1], 4096;" :: "l"(dst), "r"(ab) : "memory");
                    asm volatile("cp.async.bulk.global.shared::cta.bulk_group [%0], [%1], 4096;" :: "l"(dst + 8192), "r"(ab + 4096) : "memory");
                    asm volatile("cp.async.bulk.commit_group;" ::: "memory");
                    asm volatile("cp.async.bulk.wait_group.read 0;" ::: "memory");
                    mbar_arrive(sbase + SB_VE + 8 * st);
                    asm volatile("cp.async.bulk.wait_group 0;" ::: "memory");
                    asm volatile("red.relaxed.gpu.global.add.u32 [%0], 1;" :: "l"(&g_prog[(seg >> 1) * 8 + (cta >> 2)]) : "memory");
                    TSA(seg, 7);
                    seg++;
                } else if (seg < NSEG - UNGATE) __nanosleep(W14_SLEEP);
            }
        }
        __syncwarp();
      }
    } else if (warp >= 8) {
        asm volatile("setmaxnreg.dec.sync.aligned.u32 88;");
        if (SIDE_WAIT > 0) __nanosleep(SIDE_WAIT);
        s4d_stage_u(smem_raw + FS_A, x, tid - 256);
        const int wq = warp - 8;
        for (int seg = 0; seg < (cta < NH ? NATT : 0); seg++) {
            const uint32_t st = seg & 1, ph = (uint32_t)(seg >> 1) & 1u, ab = sbase + AT_0 + st * AT_ST;
            float sc[20];
            if (seg < NSEG - UNGATE) mbar_wait_long(sbase + SB_QKF + 8 * st, ph); else mbar_wait(sbase + SB_QKF + 8 * st, ph);
            if (tid == 256) TSA(seg, 4);
            {
                const uint64_t da = smem_desc(ab + 10240 + 1024, 128, 1024), db = smem_desc(ab + 10240, 128, 2048);
                wg_fence();
#pragma unroll
                for (int ks = 0; ks < 8; ks++) wgmma_n40_ss(sc, da + (uint64_t)((ks >> 2) * 576 + (ks & 3) * 16), db + (uint64_t)((ks >> 2) * 576 + (ks & 3) * 16), ks > 0);
                wg_commit();
                wg_wait0();
            }
            if (lane == 0) mbar_arrive(sbase + SB_QKE + 8 * st);
            uint32_t p[5], ob[16];
            const float psum = xrow_softmax(sc, p, wq, lane);
            mbar_wait(sbase + SB_VF + 8 * st, ph);
            xrow_pv(ob, p, psum, ab);
            named_bar(6, 128);
#pragma unroll
            for (int i = 0; i < 4; i++) stsm_x4(ab + (i >> 1) * 4096 + wq * 1024 + (i & 1) * 512 + lane * 16, ob[4 * i], ob[4 * i + 1], ob[4 * i + 2], ob[4 * i + 3]);
            fence_async();
            __syncwarp();
            if (lane == 0) mbar_arrive(sbase + SB_OF + 8 * st);
        }
    } else {
        asm volatile("setmaxnreg.inc.sync.aligned.u32 192;");
        const int wg = warp >> 2, wq = warp & 3;
        s4d_phase(smem_raw + FS_A, x, logA, Aim, Cre, Cim, logdt, dskip, Wo + (size_t)((2 * kq + wg) * 512) * DM + cb * 64, ep, sbase + SB_TICK);
        TS3(2);
        if (lane == 0) TSS(16, warp);
        named_bar(3, 320);
        if (tid == 0) TSS(17, 0);
        uint32_t wa[32][4];
        mbar_wait_long(sbase + SB_WO, 0);
        if (tid == 0) TSS(17, 1);
        {
            const uint32_t a = sbase + FS_A + wg * 65536 + ((lane >> 4) * 8 + (lane & 7)) * 128 + (((wq * 2 + ((lane >> 3) & 1)) ^ (lane & 7)) << 4);
#pragma unroll
            for (int ks = 0; ks < 32; ks++) ldsm_x4_t(wa[ks], a + ks * 2048);
        }
        named_bar(7, 320);
        TS3(3);
        if (tid == 0) TSS(17, 4);
        auto product = [&](float (&acc)[32], int pr, const int wg) {
                if (pr + wg > 0 && (TURN31 || pr + wg < NSEG / 2)) named_bar(4 + wg, 256);
                const uint64_t db = smem_desc(sbase + FS_A + wg * 65536, 128, 1024);
                TSG(0);
#pragma unroll
                for (int j = 0; j < 4; j++) {
                    mbar_wait(sbase + SB_FULL + 8 * (4 * wg + j), (uint32_t)pr & 1u);
                    if (j == 0) TSG(1);
                    if (j == 3) TSG(2);
                    wg_fence();
#pragma unroll
                    for (int ks = 0; ks < 8; ks++) {
                        if ((j | ks) == 0) wgmma_n64_z(acc, wa[0], db);
                        else wgmma_n64(acc, wa[8 * j + ks], db + (uint64_t)(j * 1024 + (ks >> 2) * 512 + (ks & 3) * 16), 1);
                    }
                    wg_commit();
                    if (j == 3 && pr + (TURN31 ? wg : 1) < NSEG / 2) bar_arrive(4 + (wg ^ 1), 256);
                    if (j > 0) { wg_wait1(); if (lane == 0) mbar_arrive(sbase + SB_EMPTY + 8 * (4 * wg + j - 1)); }
                }
                wg_wait0();
                if (pr == 31) TS3W(27);
                TSG(3);
                if (lane == 0) mbar_arrive(sbase + SB_EMPTY + 8 * (4 * wg + 3));
        };
        if (wg == 1) {
            for (int pr = 0; pr < NSEG / 2; pr++) {
                uint32_t t16 = (uint32_t)(wq * 32 + lane) * 16u;
                asm volatile("" : "+r"(t16));
                float acc[32];
                product(acc, pr, 1);
                    uint32_t tag = ((uint32_t)(pr >> 3) & 1u) ^ 1u;
                    tag = __shfl_sync(0xffffffffu, tag, lane);
                    if (GATE_S && pr < NSEG / 2 - UNGATE_G) gate(sbase + SB_TICK);
                    named_bar(8, 256);
                    unsigned char* dst = reinterpret_cast<unsigned char*>(&g_fp[pr & 7][4 * cb][2 * kq - 2][0]) + t16;
                    const uint32_t own = sbase + FS_O + (pr % 3) * 4096 + t16;
#pragma unroll
                    for (int q = 0; q < 8; q++) {
                        float4 p;
                        asm volatile("ld.shared.v4.f32 {%0,%1,%2,%3}, [%4];" : "=f"(p.x), "=f"(p.y), "=f"(p.z), "=f"(p.w) : "r"(sbase + FS_P + t16 + q * 2048) : "memory");
                        acc[4 * q] = __uint_as_float((__float_as_uint(acc[4 * q] + p.x) & ~1u) | tag); acc[4 * q + 1] = __uint_as_float((__float_as_uint(acc[4 * q + 1] + p.y) & ~1u) | tag);
                        acc[4 * q + 2] = __uint_as_float((__float_as_uint(acc[4 * q + 2] + p.z) & ~1u) | tag); acc[4 * q + 3] = __uint_as_float((__float_as_uint(acc[4 * q + 3] + p.w) & ~1u) | tag);
                    }
#pragma unroll
                    for (int q = 0; q < 8; q++) {
                        asm volatile("{\n.reg .pred p;\nsetp.ne.s32 p, %5, %6;\n@p st.volatile.global.v4.f32 [%0], {%1,%2,%3,%4};\n@!p st.shared.v4.f32 [%7], {%1,%2,%3,%4};\n}"
                                     :: "l"(dst + (q & 1) * 2048), "f"(acc[4 * q]), "f"(acc[4 * q + 1]), "f"(acc[4 * q + 2]), "f"(acc[4 * q + 3]), "r"(q >> 1), "r"(kq),
                                        "r"(own + (q & 1) * 2048) : "memory");
                        if (q & 1) dst += (q >> 1) == kq ? 12288 + 4096 : 12288;
                    }
                    bar_arrive(9, 256);
                    if (pr == 31) TS3W(28);
                TSG(4);
            }
        } else {
          int nsync = 0;
          int np = 1, nf = 0, pr = 0, pf = -1;
          while (true) {
            uint32_t t16 = (uint32_t)(wq * 32 + lane) * 16u;
            asm volatile("" : "+r"(t16));
            if (pr < 0) {
                if (nsync <= pf) { named_bar(9, 256); nsync++; }
                if (lane == 0 && pf < NSEG / 2 - 1) mbar_arrive(sbase + SB_REQ);
            } else {
                float acc[32];
                product(acc, pr, 0);
                if (nsync < pr) { named_bar(9, 256); nsync++; }
#pragma unroll
                for (int q = 0; q < 8; q++)
                    asm volatile("st.shared.v4.f32 [%0], {%1,%2,%3,%4};" :: "r"(sbase + FS_P + t16 + q * 2048), "f"(acc[4 * q]), "f"(acc[4 * q + 1]), "f"(acc[4 * q + 2]), "f"(acc[4 * q + 3]) : "memory");
                bar_arrive(8, 256);
                TSG(4);
            }
            uint32_t w[4] = {0u, 0u, 0u, 0u};
            const int pc = pf;
            if (pf >= 0) {
                const uint32_t tag = ((uint32_t)(pf >> 3) & 1u) ^ 1u;
                uint4 v[8];
                unsigned n = 0;
                const bool last = pf == NSEG / 2 - 1;
                const uint4* src = reinterpret_cast<const uint4*>(reinterpret_cast<const unsigned char*>(&g_fp[pf & 7][cta][0][0]) + t16);
                if (pf >= NSEG / 2 - 2) {
#pragma unroll
                    for (int r = 0; r < 6; r++) v[r] = ld_vol_u4(src + r * 128);
                    mbar_wait(sbase + SB_FI, 0u);
                } else {
                    mbar_wait(sbase + SB_FI, (uint32_t)pf & 1u);
#pragma unroll
                    for (int r = 0; r < 6; r++)
                        asm volatile("ld.shared.v4.u32 {%0,%1,%2,%3}, [%4];" : "=r"(v[r].x), "=r"(v[r].y), "=r"(v[r].z), "=r"(v[r].w) : "r"(sbase + t16 + FS_I + r * 2048) : "memory");
                }
                while (true) {
                    uint32_t any = 0u;
#pragma unroll
                    for (int r = 0; r < 6; r++) {
                        uint32_t c0_, c1_;
                        asm("lop3.b32 %0, %1, %2, %3, 0x7e;" : "=r"(c0_) : "r"(v[r].x), "r"(v[r].y), "r"(tag));
                        asm("lop3.b32 %0, %1, %2, %3, 0x7e;" : "=r"(c1_) : "r"(v[r].z), "r"(v[r].w), "r"(tag));
                        asm("lop3.b32 %0, %1, %2, %3, 0xfe;" : "=r"(any) : "r"(any), "r"(c0_), "r"(c1_));
                    }
                    if (!__any_sync(0xffffffffu, (any & 1u) != 0u) || ++n >= SPIN_LIMIT) break;
                    if (pf < NSEG / 2 - 2) __nanosleep(200);
#pragma unroll
                    for (int r = 0; r < 6; r++) v[r] = ld_vol_u4(src + r * 128);
                }
                if (pf == 31) TS3(29);
                TSG(5);
#pragma unroll
                for (int r = 6; r < 8; r++)
                    asm volatile("ld.shared.v4.u32 {%0,%1,%2,%3}, [%4];" : "=r"(v[r].x), "=r"(v[r].y), "=r"(v[r].z), "=r"(v[r].w)
                                 : "r"(sbase + t16 + FS_O + (pf % 3) * 4096 + (r - 6) * 2048) : "memory");
                uint32_t zv[4], gg[2];
                ldsm_x4_t(zv, sbase + (last ? FS_I : FS_Z) + (wq * 16 + (lane & 15)) * 32 + (lane >> 4) * 16);
#pragma unroll
                for (int k = 0; k < 2; k++) gg[k] = __byte_perm(*reinterpret_cast<const volatile unsigned short*>(smem_raw + FS_G + (last ? 32 : 0) + k * 16 + (lane >> 2) * 2), 0u, 0x1010);
#define PQS(k, f) (((__uint_as_float(v[k].f) + __uint_as_float(v[2 + k].f)) + __uint_as_float(v[4 + k].f)) + __uint_as_float(v[6 + k].f))
#pragma unroll
                for (int k = 0; k < 2; k++) {
                    w[2 * k] = bf2_add(bf2_mul(gg[k], movm(pack_bf16(PQS(k, x), PQS(k, y)))), zv[2 * k]);
                    w[2 * k + 1] = bf2_add(bf2_mul(gg[k], movm(pack_bf16(PQS(k, z), PQS(k, w)))), zv[2 * k + 1]);
                }
#undef PQS
            }
            const bool more = nf < NSEG / 2;
            if (more) {
                uint32_t r;
                asm volatile("{\n.reg .pred p, q;\n.reg .b32 v;\nld.volatile.shared.u32 v, [%1];\nsetp.gt.s32 p, v, %2;\nbar.red.or.pred q, 10, 128, p;\nselp.u32 %0, 1, 0, q;\n}"
                             : "=r"(r) : "r"(sbase + SB_SEEN), "r"(np) : "memory");
                const bool dop = np < NSEG / 2 && (__shfl_sync(0xffffffffu, r, 0) != 0u || nf == np || nf >= NSEG / 2 - 2);
                TSG(6);
                pr = dop ? np++ : -1;
                pf = !dop || nf + (pr == NSEG / 2 - 1 ? 1 : 2) <= pr ? nf++ : -1;
                if (dop && pf >= 0 && lane == 0) mbar_arrive(sbase + SB_REQ);
            }
            if (pc >= 0) {
                unsigned char* op = reinterpret_cast<unsigned char*>(out) + (uint32_t)((pc * 64 + kq * 16 + (lane >> 2)) * DM + cb * 64 + wq * 16 + 2 * (lane & 3)) * 2u;
#pragma unroll
                for (int k = 0; k < 4; k++) *reinterpret_cast<uint32_t*>(op + (k >> 1) * (16 * DM) + (k & 1) * 16) = w[k];
                if ((pc & 1) == 0) TS3(4 + pc / 2);
                if (pc == 31) TS3(25);
            }
            if (!more) break;
          }
        }
        if (cta == 0 && tid == 0) asm volatile("red.relaxed.gpu.global.add.u32 [%0], 1;" :: "l"(&g_epoch) : "memory");
    }
    asm volatile("griddepcontrol.wait;" ::: "memory");
}

template <class F>
__device__ __forceinline__ uint32_t poll_mem(const uint4* src, uint32_t dst, uint32_t t0, F next) {
    uint4 v[6];
    unsigned it = 0;
#pragma unroll
    for (int j = 0; j < 6; j++) v[j] = make_uint4(0u, 0u, 0u, 0u);
    while (clock32() - t0 < POLL_DELAY) {}
    FS(12, 0);
    bool more;
#pragma unroll 1
    do {
        asm volatile("{\n.reg .pred p<6>;\n"
                     "setp.ne.u32 p0, %3, 0x5000;\nsetp.ne.u32 p1, %7, 0x5000;\nsetp.ne.u32 p2, %11, 0x5000;\n"
                     "setp.ne.u32 p3, %15, 0x5000;\nsetp.ne.u32 p4, %19, 0x5000;\nsetp.ne.u32 p5, %23, 0x5000;\n"
                     "@p0 ld.volatile.global.v4.u32 {%0,%1,%2,%3}, [%24];\n@p1 ld.volatile.global.v4.u32 {%4,%5,%6,%7}, [%24+4096];\n"
                     "@p2 ld.volatile.global.v4.u32 {%8,%9,%10,%11}, [%24+8192];\n@p3 ld.volatile.global.v4.u32 {%12,%13,%14,%15}, [%24+12288];\n"
                     "@p4 ld.volatile.global.v4.u32 {%16,%17,%18,%19}, [%24+16384];\n@p5 ld.volatile.global.v4.u32 {%20,%21,%22,%23}, [%24+20480];\n}"
                     : "+r"(v[0].x), "+r"(v[0].y), "+r"(v[0].z), "+r"(v[0].w), "+r"(v[1].x), "+r"(v[1].y), "+r"(v[1].z), "+r"(v[1].w),
                       "+r"(v[2].x), "+r"(v[2].y), "+r"(v[2].z), "+r"(v[2].w), "+r"(v[3].x), "+r"(v[3].y), "+r"(v[3].z), "+r"(v[3].w),
                       "+r"(v[4].x), "+r"(v[4].y), "+r"(v[4].z), "+r"(v[4].w), "+r"(v[5].x), "+r"(v[5].y), "+r"(v[5].z), "+r"(v[5].w)
                     : "l"(src) : "memory");
        stsm_x4(dst, h2_to_bf2(v[0].x), h2_to_bf2(v[0].y), h2_to_bf2(v[0].z), h2_to_bf2(v[1].x));
        stsm_x4(dst + 512, h2_to_bf2(v[1].y), h2_to_bf2(v[1].z), h2_to_bf2(v[2].x), h2_to_bf2(v[2].y));
        const uint32_t all = ((v[0].w & v[1].w) & (v[2].w & v[3].w)) & (v[4].w & v[5].w);
        more = __any_sync(0xffffffffu, (all & 0x5000u) != 0x5000u && ++it < SPIN_LIMIT);
        stsm_x4(dst + 1024, h2_to_bf2(v[2].z), h2_to_bf2(v[3].x), h2_to_bf2(v[3].y), h2_to_bf2(v[3].z));
        asm volatile("stmatrix.sync.aligned.m8n8.x2.shared.b16 [%0], {%1,%2};" :: "r"(dst + 1536), "r"(h2_to_bf2(v[4].x)), "r"(h2_to_bf2(v[4].y)) : "memory");
        stsm_x4(dst + 1792, h2_to_bf2(v[4].z), h2_to_bf2(v[5].x), h2_to_bf2(v[5].y), h2_to_bf2(v[5].z));
        asm volatile("{\n.reg .pred p;\nsetp.eq.u32 p, %0, 0;\n@p bar.sync 1, 384;\n}" :: "r"((uint32_t)more) : "memory");
    } while (more);
    next();
    FS(13, it);
    FS(14, 0);
    uint32_t m = v[0].x, m1 = v[0].y, m2 = v[0].z;
#pragma unroll
    for (int j = 1; j < 6; j++) {
        asm volatile("max.NaN.xorsign.abs.f16x2 %0, %0, %1;" : "+r"(m) : "r"(v[j].x));
        asm volatile("max.NaN.xorsign.abs.f16x2 %0, %0, %1;" : "+r"(m1) : "r"(v[j].y));
        asm volatile("max.NaN.xorsign.abs.f16x2 %0, %0, %1;" : "+r"(m2) : "r"(v[j].z));
    }
    asm volatile("max.NaN.xorsign.abs.f16x2 %0, %0, %1;" : "+r"(m) : "r"(m1));
    asm volatile("max.NaN.xorsign.abs.f16x2 %0, %0, %1;" : "+r"(m) : "r"(m2));
    return h2_to_bf2(m) & 0x7fff7fffu;
}

template <int N> __device__ __forceinline__ void pad_code() {
#pragma unroll
    for (int i = 0; i < N; i++) asm volatile("pmevent 7;" ::: "memory");
}
template <bool V> struct Flag { static constexpr bool value = V; };
struct RFlag { bool value; };
__device__ __forceinline__ void score_group(const uint32_t (&a)[2][4], const uint32_t (&kf)[2][4], uint32_t d0, uint32_t d1, uint32_t m1, uint32_t d2, uint32_t m2) {
    FS(4, a[1][0]);
    float sc[4][4];
    mma_z(sc[0], a[0], kf[0][0], kf[0][1]);
    mma_z(sc[1], a[0], kf[0][2], kf[0][3]);
    mma_z(sc[2], a[1], kf[1][0], kf[1][1]);
    mma_z(sc[3], a[1], kf[1][2], kf[1][3]);
    const uint32_t v0 = __float_as_uint((sc[0][0] + sc[1][2]) + (sc[2][0] + sc[3][2])), v1 = __float_as_uint((sc[0][1] + sc[1][3]) + (sc[2][1] + sc[3][3]));
    FS(5, v0);
    st_async64(d2, v0, v1, m2);
    st_async64(d1, v0, v1, m1);
    asm volatile("st.shared.v2.u32 [%0], {%1,%2};" :: "r"(d0), "r"(v0), "r"(v1) : "memory");
}
__device__ __forceinline__ void store_tile(int s, int h, int role, uint32_t tile, uint32_t b0, uint32_t b1) {
    asm volatile("cp.async.bulk.global.shared::cta.bulk_group.L2::cache_hint [%0], [%1], %2, %3;"
                 :: "l"(&g_qkv[s][h][role][b0]), "r"(tile + b0), "r"(b1 - b0), "l"(policy_evict_first()) : "memory");
}
__device__ __forceinline__ uint32_t w_addr(uint32_t sbase, int warp, int lane) {
    return sbase + SM_WS + (warp >> 2) * 8192 + ((lane & 7) + ((lane >> 4) & 1) * 8) * 128 + ((((warp & 3) * 2 + ((lane >> 3) & 1)) ^ (lane & 7)) << 4);
}
__device__ __forceinline__ void vx_copy(uint32_t sbase, int j, int r) {
    bulk_s2s(mapa(sbase + SM_VX + (j & 1) * 8192, r), sbase + SM_T + (j & 3) * TBUF + DH * 16, 8192, mapa(sbase + B_VX + 8 * (j & 1), r));
}
__device__ __forceinline__ void norms_gather(int lane, float* scs, unsigned lim) {
    uint2 v[3];
    uint4 w[2];
    unsigned it = 0;
#pragma unroll
    for (int i = 0; i < 3; i++) v[i] = make_uint2(0u, 0u);
    w[0] = w[1] = make_uint4(0u, 0u, 0u, 0u);
    bool more;
    do {
#pragma unroll
        for (int i = 0; i < 3; i++) if (!GPRED || (v[i].x & 1u) == 0u) v[i] = ld_vol_u2(&g_norm[3 * lane + i]);
#pragma unroll
        for (int i = 0; i < 2; i++) if (!GPRED || (w[i].x & w[i].y & w[i].z & w[i].w & 1u) == 0u) w[i] = ld_vol_u4(&g_wv[lane][i]);
        more = __any_sync(0xffffffffu, (v[0].x & v[1].x & v[2].x & w[0].x & w[0].y & w[0].z & w[0].w & w[1].x & w[1].y & w[1].z & w[1].w & 1u) == 0u);
    } while (more && ++it < lim);
    if (more) return;
    float c;
    asm("sqrt.approx.f32 %0, %1;" : "=f"(c) : "f"(__uint_as_float(max(max(v[0].x, v[1].x), v[2].x))));
    c *= __uint_as_float(max(max(max(w[0].x, w[0].y), max(w[0].z, w[0].w)), max(max(w[1].x, w[1].y), max(w[1].z, w[1].w)))) * 272.f;
#pragma unroll
    for (int o = 16; o; o >>= 1) c += __shfl_xor_sync(0xffffffffu, c, o);
    const uint32_t r = __reduce_max_sync(0xffffffffu, v[0].y);
    if (lane == 0) { scs[1] = c * (1.1f * 24.f); scs[16] = scs[17] = __uint_as_float(r); }
}
__device__ __forceinline__ void xmax_gather(int lane, float* scs) {
    uint4 v[4];
    unsigned it = 0;
    uint32_t ok;
    do {
#pragma unroll
        for (int i = 0; i < 4; i++) v[i] = ld_vol_u4(&g_rx[lane + 32 * (i >> 1)][i & 1]);
        ok = 1u;
#pragma unroll
        for (int i = 0; i < 4; i++) ok &= (v[i].x & v[i].y) & (v[i].z & v[i].w);
    } while (__any_sync(0xffffffffu, ok == 0u) && ++it < SPIN_LIMIT);
#pragma unroll
    for (int i = 0; i < 2; i++)
        scs[16 + lane + 32 * i] = __uint_as_float(max(max(max(v[2 * i].x, v[2 * i].y), max(v[2 * i].z, v[2 * i].w)), max(max(v[2 * i + 1].x, v[2 * i + 1].y), max(v[2 * i + 1].z, v[2 * i + 1].w))));
}
__device__ __forceinline__ uint32_t max_abs8(uint32_t m, uint32_t a, uint32_t b, uint32_t c, uint32_t d) { return max_abs2(max_abs2(m, max_abs2(a, b)), max_abs2(c, d)); }
__device__ __forceinline__ uint32_t warp_max_abs(uint32_t m) { return __reduce_max_sync(0xffffffffu, max((m << 16) & 0x7fff0000u, m & 0x7fff0000u)); }

__device__ __forceinline__ void last_rows(int pass) {
    extern __shared__ __align__(1024) unsigned char smem_raw[];
    const uint32_t sbase = smem_u32(smem_raw);
    const int tid = threadIdx.x, warp = __shfl_sync(0xffffffffu, tid >> 5, 0), h = blockIdx.x / 3;
    {
        const int sg = warp < 8, wq = warp & 3, lane = tid & 31;
        const uint32_t qk = sbase + SM_X + XBUF + sg * (2 * 9216), ob = sbase + SM_X + 2 * XBUF + sg * 8192;
        TST(0);
        if (pass) mbar_wait(sbase + B_VX + 8 * sg, 0);
        fence_async();
        TST(1);
        float sc[20];
#pragma unroll
        for (int i = 0; i < 20; i++) sc[i] = 0.f;
        {
            const uint64_t da = smem_desc(qk + 1024, 128, 1024), db = smem_desc(qk, 128, 2048);
            wg_fence();
#pragma unroll
            for (int ks = 0; ks < 8; ks++) wgmma_n40_ss(sc, da + (uint64_t)((ks >> 2) * 576 + (ks & 3) * 16), db + (uint64_t)((ks >> 2) * 576 + (ks & 3) * 16), ks > 0);
            wg_commit();
            wg_wait0();
        }
        uint32_t p[5], o[16];
        const float psum = xrow_softmax(sc, p, wq, lane);
        xrow_pv(o, p, psum, sbase + SM_T + ((NSEG - 2 + sg) & 3) * TBUF);
        if (pass) {
#pragma unroll
            for (int i = 0; i < 4; i++) stsm_x4(ob + (i >> 1) * 4096 + wq * 1024 + (i & 1) * 512 + lane * 16, o[4 * i], o[4 * i + 1], o[4 * i + 2], o[4 * i + 3]);
        }
        fence_async();
        named_bar(11 + sg, 128);
        TST(2);
        if ((tid & 127) == 0 && pass) {
            unsigned char* dst = reinterpret_cast<unsigned char*>(g_ox) + ((size_t)((NSEG / 2 - 1) * NH + h)) * 16384 + sg * 4096;
            asm volatile("cp.async.bulk.global.shared::cta.bulk_group [%0], [%1], 4096;" :: "l"(dst), "r"(ob) : "memory");
            asm volatile("cp.async.bulk.global.shared::cta.bulk_group [%0], [%1], 4096;" :: "l"(dst + 8192), "r"(ob + 4096) : "memory");
            asm volatile("cp.async.bulk.commit_group;" ::: "memory");
            asm volatile("cp.async.bulk.wait_group 0;" ::: "memory");
            asm volatile("red.relaxed.gpu.global.add.u32 [%0], 1;" :: "l"(&g_prog[(NSEG / 2 - 1) * 8 + (h >> 2)]) : "memory");
        }
        TST(3);
    }
    __syncwarp();
}

__global__ void __cluster_dims__(3, 1, 1) __launch_bounds__(384, 1)
k_chain(const __grid_constant__ CUtensorMap tmq, const __grid_constant__ CUtensorMap tmk,
        const __grid_constant__ CUtensorMap tmv, const __grid_constant__ CUtensorMap tmx2, const __grid_constant__ CUtensorMap tmo,
        const __grid_constant__ CUtensorMap tmm, const bf16* __restrict__ xg) {
    extern __shared__ __align__(1024) unsigned char smem_raw[];
    const uint32_t sbase = smem_u32(smem_raw);
    const int cta = blockIdx.x, h = cta / 3, role = cta - 3 * h;
    const int tid = threadIdx.x, warp = __shfl_sync(0xffffffffu, tid >> 5, 0), lane_o = tid & 31;
    TS3C(0);
    asm volatile("griddepcontrol.launch_dependents;" ::: "memory");
    auto stage_w = [&](int i) {
        tma_2d(sbase + SM_WS + i * 16384, role == 2 ? &tmv : &tmq, h * DH + (role == 1 ? 64 : 0), i * 64, sbase + B_W + 8 * i);
        tma_2d(sbase + SM_WS + i * 16384 + 8192, role == 2 ? &tmv : &tmk, h * DH + (role == 0 ? 0 : 64), i * 64, sbase + B_W + 8 * i);
    };
    auto stage_x = [&](int i) {
        tma_2d(sbase + x01_off(i), &tmx2, i * 64, 0, sbase + B_W + 8 * i);
        tma_2d(sbase + x01_off(i) + 8192, &tmm, i * 64, 0, sbase + B_W + 8 * i);
    };
    if (tid == 0) {
#pragma unroll
        for (int i = 0; i < 10; i++) mbar_init(sbase + B_W + 8 * i, 1);
        fence_async();
        TSQ(10);
#pragma unroll
        for (int i = 0; i < 3; i++) tma_2d(sbase + SM_X01 + i * 16384, &tmo, role * WOC + i * 64, h * DH, sbase + B_E);
        stage_x(0); stage_w(0);
        TSQ(11);
        mbar_expect(sbase + B_E, 49152);
#pragma unroll
        for (int i = 0; i < 9; i++) mbar_expect(sbase + B_W + 8 * i, 16384 + 9216);
    } else if (tid == 32) {
#pragma unroll
        for (int i = 0; i < 8; i++) mbar_init(sbase + SM_BAR + 8 * i, 1);
        mbar_init(sbase + B_XF, 3);
        asm volatile("fence.mbarrier_init.release.cluster;" ::: "memory");
        for (int i = 0; i < 2; i++) {
            mbar_expect(sbase + B_SB + 8 * i, role == 2 ? 2560 : 1280 + 2048);
            mbar_expect(sbase + B_VX + 8 * i, role != 2 ? 8192 : 2 * 9216);
            mbar_expect(sbase + B_XT + 8 * i, 32768);
            mbar_expect(sbase + B_XT + 16 + 8 * i, 40960);
        }
    }
    __syncthreads();
    TS3C(8);
    if (tid == 0) {
#pragma unroll 1
        for (int i = 1; i < NUP; i++) { if (i < 3) stage_x(i); stage_w(i); }
        TSQ(12);
    }
    __syncwarp();
    if (warp < 8) {
        uint32_t wreg[36 - NS][4];
        uint32_t v0, v1;
        {
            const int lane = lane_o;
            const uint32_t a = w_addr(sbase, warp, lane);
            const uint64_t da = smem_desc(sbase + SM_WS + (warp >> 2) * 8192, 1024, 1024) | (1ull << 62);
            float acc[36];
            uint32_t m = 0u;
#pragma unroll
            for (int i = 0; i < 36; i++) acc[i] = 0.f;
#pragma unroll 1
            for (int b = 0; b < 9; b++) {
                if (b == 0) TSQ(0);
                mbar_wait(sbase + B_W + 8 * b, 0);
                TSQ(1 + b);
                if (b == 8) TS3C(2);
                const uint64_t db = smem_desc(sbase + x01_off(b), 16, 1024) | (1ull << 62);
                wg_fence();
#pragma unroll
                for (int k = 0; k < 4; k++) wgmma_n72_ss(acc, da + (uint64_t)(b * 1024 + k * 128), db + (uint64_t)(k * 2));
                wg_commit();
                if (b == 3) {
                    if (role == 2) {
#pragma unroll
                        for (int ks = 0; ks < NS; ks++) {
                            uint32_t t[4];
                            ldsm_x4_t(t, a + (ks >> 2) * 16384 + (ks & 3) * 2048);
                            m = max_abs8(m, t[0], t[1], t[2], t[3]);
                        }
                    }
#pragma unroll
                    for (int ks = NS; ks < 16; ks++) ldsm_x4_t(wreg[ks - NS], a + (ks >> 2) * 16384 + (ks & 3) * 2048);
                }
                if (b == 5) {
#pragma unroll
                    for (int ks = 16; ks < 24; ks++) ldsm_x4_t(wreg[ks - NS], a + (ks >> 2) * 16384 + (ks & 3) * 2048);
                    if (role == 2) {
#pragma unroll
                        for (int ks = NS; ks < 24; ks++) m = max_abs8(m, wreg[ks - NS][0], wreg[ks - NS][1], wreg[ks - NS][2], wreg[ks - NS][3]);
                    }
                }
                if (P0C && b == 7) {
#pragma unroll
                    for (int ks = 24; ks < 32; ks++) ldsm_x4_t(wreg[ks - NS], a + (ks >> 2) * 16384 + (ks & 3) * 2048);
                    if (role == 2) {
#pragma unroll
                        for (int ks = 24; ks < 32; ks++) m = max_abs8(m, wreg[ks - NS][0], wreg[ks - NS][1], wreg[ks - NS][2], wreg[ks - NS][3]);
                    }
                }
            }
#pragma unroll
            for (int ks = P0C ? 32 : 24; ks < KPRE; ks++) ldsm_x4_t(wreg[ks - NS], a + (ks >> 2) * 16384 + (ks & 3) * 2048);
            if (role == 2) {
#pragma unroll
                for (int ks = KPRE; ks < 36; ks++) {
                    uint32_t t[4];
                    ldsm_x4_t(t, a + (ks >> 2) * 16384 + (ks & 3) * 2048);
                    m = max_abs8(m, t[0], t[1], t[2], t[3]);
                }
#pragma unroll
                for (int ks = P0C ? 32 : 24; ks < KPRE; ks++) m = max_abs8(m, wreg[ks - NS][0], wreg[ks - NS][1], wreg[ks - NS][2], wreg[ks - NS][3]);
                m = warp_max_abs(m);
                if (lane == 0) asm volatile("st.volatile.global.u32 [%0], %1;" :: "l"(reinterpret_cast<uint32_t*>(&g_wv[h][0]) + warp), "r"(m | 1u) : "memory");
                __syncwarp();
            }
            wg_wait0();
            named_bar(9, 256);
            const uint32_t off = sbase + SM_T + (DH + warp * 16 + (lane & 15)) * 16 + (lane >> 4) * (DH * 16);
#pragma unroll
            for (int i = 0; i < 4; i++)
                stsm_x4(off + (i >> 1) * TBUF + (i & 1) * (2 * DH * 16), pack_bf16(acc[8 * i], acc[8 * i + 1]), pack_bf16(acc[8 * i + 2], acc[8 * i + 3]),
                        pack_bf16(acc[8 * i + 4], acc[8 * i + 5]), pack_bf16(acc[8 * i + 6], acc[8 * i + 7]));
            v0 = pack_bf16(acc[32], acc[33]);
            v1 = pack_bf16(acc[34], acc[35]);
#pragma unroll
            for (int ks = KPRE; ks < 36; ks++) ldsm_x4_t(wreg[ks - NS], a + (ks >> 2) * 16384 + (ks & 3) * 2048);
            if (role == 2) fence_async();
            bar_arrive(8, 384);
            named_bar(7, 256);
            asm volatile("barrier.cluster.arrive.relaxed.aligned;" ::: "memory");
        }
        TS3C(3);
        uint32_t ws[NS][4];
#pragma unroll
        for (int ks = NS - NP; ks < NS; ks++) ldsm_x4_t(ws[ks], w_addr(sbase, warp, lane_o) + (ks >> 2) * 16384 + (ks & 3) * 2048);
        asm volatile("barrier.cluster.wait.aligned;" ::: "memory");
        if (!P0B && lane_o == 0 && role == 2) {
            if (warp < 2) vx_copy(sbase, 0, warp);
#pragma unroll 1
            for (int j = warp - 4; j >= 0 && j < 9; j += 4) tma_2d_mc(sbase + SM_X + j * 8192, &tmx2, (j < 4 ? j + 5 : j - 4) * 64, 64, sbase + B_XT + (j < 4 ? 8 : 24));
        }
        __syncwarp();
        TS3C(4);
        auto main_loop = [&](auto is_c) {
            const bool C = is_c.value;
            if (C) pad_code<PAD4>(); else pad_code<PAD3>();
            const uint32_t l16 = __shfl_sync(0xffffffffu, sbase + lane_o * 16, lane_o);
            const uint32_t ka = __shfl_sync(0xffffffffu, sbase + SM_T + (64 + (lane_o & 7) + ((lane_o >> 3) & 1) * 16 + (lane_o >> 4) * 8) * 16, lane_o);
            const uint32_t wa = __shfl_sync(0xffffffffu, w_addr(sbase, warp, lane_o), lane_o);
            auto post = [&](int s, uint32_t to, uint32_t ta, int scw, uint32_t v0, uint32_t v1) {
                int lane = lane_o;
                asm volatile("" : "+r"(lane));
                asm volatile("stmatrix.sync.aligned.m8n8.x2.shared.b16 [%0], {%1,%2};" :: "r"(l16 + ta), "r"(v0), "r"(v1) : "memory");
                if (C) {
                    if (s + 1 < NSEG) {
                        const uint32_t fo = (uint32_t)(warp * 256 + lane * 8);
                        const uint32_t rb0 = mapa(sbase, 0), rb1 = mapa(sbase, 1);
                        st_async64(rb0 + SM_VM + fo, v0, v1, rb0 + B_SB + 8 * (s & 1));
                        st_async64(rb1 + SM_VM + fo, v0, v1, rb1 + B_SB + 8 * (s & 1));
                        asm volatile("st.shared.v2.u32 [%0], {%1,%2};" :: "r"(sbase + SM_VM + fo), "r"(v0), "r"(v1) : "memory");
                        bar_arrive(2, 384);
                    }
                } else {
                    named_bar(2, 384);
                    if (scw == 0) {
                        uint32_t kf[2][4], qf[2][4];
#pragma unroll
                        for (int k2 = 0; k2 < 2; k2++) { ldsm_x4_t(kf[k2], ka + to + k2 * 512); ldsm_x4_t(qf[k2], l16 + SM_T + to + k2 * 512); }
                        const uint32_t d0 = sbase + SM_S + lane * 8, bo = sbase + B_SB + 8 * (s & 1);
                        const uint32_t d1 = mapa(d0 + 1280, role ^ 1), m1 = mapa(bo, role ^ 1), d2 = mapa(d0 + role * 1280, 2), m2 = mapa(bo, 2);
                        score_group(qf, kf, d0, d1, m1, d2, m2);
                        bar_arrive(6, 160);
                        bar_arrive(5, 384);
                    }
                    if (RARE(scw == 8)) {
                        const uint32_t dk = mapa(sbase + SM_X + XBUF + (2 + role) * 9216 + (warp - 4) * 256 + lane * 4, 2), mb = mapa(sbase + B_VX + 8, 2);
                        st_async32(dk, v0, mb);
                        st_async32(dk + 128, v1, mb);
                    }
                }
                FS(11, 0);
            };
            post(0, 0, SM_T + warp * 256, warp ^ 7, v0, v1);
            int scw = warp ^ 7;
            uint32_t to = 0;
            int r0 = 0;
            for (int s = 0; s + 1 < NSEG; s++) {
                int lane = lane_o;
                asm volatile("" : "+r"(lane));
                const uint32_t tb = sbase + SM_T + to;
                const int rc = r0;
                const bool b5 = scw != 0;
                uint32_t ta;
                auto advance = [&]() {
                    to = to == 3 * TBUF ? 0 : to + TBUF;
                    ta = SM_T + warp * 256 + to;
                    scw = s + 2 < NSEG ? scw ^ 4 : (warp & 4) + 4;
                    if ((s & 1) == 0) r0 = r0 >= 4 ? r0 - 4 : r0 + 9;
                    asm volatile("" : "+r"(ta), "+r"(scw), "+r"(r0));
                };
                auto chores = [&](bool idle) {
                    const int hw = (s & 1) ? warp : warp - 4;
                    if (idle) { if (hw != 2) named_bar(4, 384); else bar_arrive(4, 384); }
                    if (hw == 2) {
                        if (lane == 0) {
                            if (C || !idle) fence_async();
                            if (C) {
                                store_tile(s + 1, h, 2, sbase + SM_T + ((s + 1) & 3) * TBUF, 2048, 10240);
                                store_tile(s, h, 2, tb, 0, s == 0 ? 10240 : 2048);
                            } else store_tile(s, h, role, tb, 1024, 10240);
                            asm volatile("cp.async.bulk.commit_group;" ::: "memory");
                            asm volatile("cp.async.bulk.wait_group 0;" ::: "memory");
                            if (C) {
                                asm volatile("cp.async.bulk.shared::cluster.global.mbarrier::complete_tx::bytes.multicast::cluster [%0], [%1], 8192, [%2], %3;"
                                             :: "r"(sbase + SM_VX + ((s + 1) & 1) * 8192), "l"(&g_qkv[s + 1][h][2][2048]), "r"(sbase + B_VX + 8 * ((s + 1) & 1)), "h"((unsigned short)3) : "memory");
                            }
                            asm volatile("red.relaxed.gpu.global.add.u32 [%0], 1;" :: "l"(&g_flag[h * NSEG + s]) : "memory");
                        }
                        __syncwarp();
                        if (!C && (s & 1) && s + 4 < NSEG) bar_arrive(13, 160);
                    }
                    __syncwarp();
                };
                const int p = (s + 3) >> 1;
                if (p < NSEG / 2 && (s == 0 || (warp >> 2) == (s & 1))) {
                    const uint32_t dlo = (uint32_t)smem_desc(sbase + SM_X, 16, 1024) + rc * 512;
                    const uint64_t da = smem_desc(sbase + SM_WS + (warp >> 2) * 8192, 1024, 1024) | (1ull << 62);
                    auto db = [&](int ks) {
                        const int j = ((ks >> 2) + 4) % 9;
                        return ((uint64_t)0x40000040u << 32) | (uint64_t)(dlo + (uint32_t)((j - (rc + j >= 13 ? 13 : 0)) * 512 + (ks & 3) * 2));
                    };
                    const uint32_t xph = (uint32_t)((p - 1) >> 1) & 1u;
                    auto xseg_max = [&]() {
                        if (cta < NSEG) {
                            if (!C) pad_code<PADE>();
                            uint32_t m = 0u;
                            mbar_wait(sbase + B_E, 1);
#pragma unroll 1
                            for (int j = 0; j < 9; j++) {
                                uint4 xv;
                                asm volatile("ld.shared.v4.u32 {%0,%1,%2,%3}, [%4];" : "=r"(xv.x), "=r"(xv.y), "=r"(xv.z), "=r"(xv.w)
                                             : "r"(l16 + warp * 512 + (j < 8 ? SM_X + 9 * 8192 + j * 4096 : SM_WS + 32768 + 4096)) : "memory");
                                m = max_abs8(m, xv.x, xv.y, xv.z, xv.w);
                            }
                            m = warp_max_abs(m);
                            if (lane == 0) asm volatile("st.volatile.global.u32 [%0], %1;" :: "l"(reinterpret_cast<uint32_t*>(&g_rx[cta][0]) + warp), "r"(m | 1u) : "memory");
                            __syncwarp();
                        }
                    };
                    float acc[32];
                    mbar_wait(sbase + B_XT + 8 * (p & 1), xph);
                    if (C) named_bar(7, 256); else if (b5) named_bar(5, 384);
                    if (NC1 > 0) {
                        if ((C ? CC_DELAY : C1_DELAY) > 0) { const uint32_t t1 = clock32(); while (clock32() - t1 < (C ? CC_DELAY : C1_DELAY)) {} }
                        wg_fence();
#pragma unroll
                        for (int ks = 35; ks > 35 - (C ? NC1C : NC1); ks--) { if (ks == 35) wgmma_n64_z(acc, wreg[ks - NS], db(ks)); else wgmma_n64(acc, wreg[ks - NS], db(ks), 1); }
                        wg_commit();
                        wg_wait0();
                    }
                    FS(9, __float_as_uint(acc[0]));
                    if (RARE(s == 0)) {
                        if (!C) pad_code<PADD>();
                        chores(false);
                        if (!P0A) xseg_max();
                    }
                    const uint32_t off = sbase + SM_T + (p & 1) * (2 * TBUF) + (DH + warp * 16 + (lane & 15)) * 16 + (lane >> 4) * (DH * 16);
                    advance();
                    if (!LATEW) mbar_wait(sbase + B_XT + 16 + 8 * (p & 1), xph);
                    FS(8, 0);
                    if (P0A) asm volatile("{\n.reg .pred p;\nsetp.eq.s32 p, %0, 0;\n@p bar.arrive 4, 384;\n@!p bar.sync 4, 384;\n}" :: "r"(P0W == 2 ? s : s + ((warp >> 2) ^ P0W)) : "memory");
                    else named_bar(4, 384);
                    FS(3, 0);
                    if (C2_DELAY > 0) { const uint32_t t1 = clock32(); while (clock32() - t1 < C2_DELAY) {} }
                    constexpr int KE = 36 - SS_POS;
                    wg_fence();
#pragma unroll
                    for (int ks = 35 - (C ? NC1C : NC1); ks >= KE - (C ? NC1C : NC1); ks--) { if (ks == 35) wgmma_n64_z(acc, wreg[ks - NS], db(ks)); else wgmma_n64(acc, wreg[ks - NS], db(ks), 1); }
                    if (LATEW) {
                        wg_commit();
                        mbar_wait(sbase + B_XT + 16 + 8 * (p & 1), xph);
                        wg_fence();
                    }
#pragma unroll
                    for (int ks = 0; ks < NS; ks++) wgmma_n64_ss(acc, da + (uint64_t)((ks >> 2) * 1024 + (ks & 3) * 128), db(ks));
#pragma unroll
                    for (int ks = NS; ks < KE - (C ? NC1C : NC1) - XSKIP; ks++) wgmma_n64(acc, wreg[ks - NS], db(ks), 1);
                    wg_commit();
                    if (!C && (s & 1)) named_bar(13, 160);
                    if (P0A == 1 && RARE(s == 0)) xseg_max();
                    wg_wait0();
#pragma unroll
                    for (int i = 0; i < 4; i++)
                        stsm_x4(off + (i >> 1) * TBUF + (i & 1) * (2 * DH * 16), pack_bf16(acc[8 * i], acc[8 * i + 1]), pack_bf16(acc[8 * i + 2], acc[8 * i + 3]),
                                pack_bf16(acc[8 * i + 4], acc[8 * i + 5]), pack_bf16(acc[8 * i + 6], acc[8 * i + 7]));
                    FS(7, __float_as_uint(acc[0]));
                    if (P0A == 2 && s == 0) xseg_max();
                } else if (!RARE(s + 2 >= NSEG)) {
                    if (!C && (warp & 3) == 2) fence_async();
                    if (C) named_bar(7, 256); else if (b5) named_bar(5, 384);
                    chores(true);
                    advance();
                } else {
                    const uint32_t t0 = clock32();
                    const uint32_t dq = mapa(sbase + SM_X + XBUF + role * 9216, 2), mb = mapa(sbase + B_VX, 2);
                    if (!C) {
                        if (b5) named_bar(5, 384);
                        if (tid == 64) { fence_async(); while (clock32() - t0 < TL_DELAY) {} bulk_s2s(dq, tb + 1024, 9216, mb); }
                        __syncwarp();
                    }
                    advance();
                    named_bar(4, 384);
                    if (!C && tid == 64) { const uint32_t t1 = clock32(); while (clock32() - t1 < VX_DELAY) {} bulk_s2s(dq + 2 * 9216 + 1024, sbase + SM_T + to + 2048, 8192, mb + 8); }
                    __syncwarp();
                }
#pragma unroll
                for (int ks = 0; ks < NS - NP; ks++) ldsm_x4_t(ws[ks], wa + (ks >> 2) * 16384 + (ks & 3) * 2048);
                FS(0, ws[0][0]);
                named_bar(1, 384);
                float acc[2][4], minv;
                uint32_t b[3][4];
#pragma unroll
                for (int kk = 0; kk < 3; kk++) ldsm_x4_t(b[kk], l16 + SM_M + kk * 512);
                FS(1, b[0][0]);
#pragma unroll
                for (int kk = 0; kk < 18; kk++) {
#pragma unroll
                    for (int i = 0; i < 2; i++) {
                        const int ks = 2 * kk + i;
                        if (ks < 2) mma_z(acc[i], ws[ks], b[kk % 3][2 * i], b[kk % 3][2 * i + 1]);
                        else if (ks < NS) mma_bf16(acc[i], ws[ks < NS ? ks : 0], b[kk % 3][2 * i], b[kk % 3][2 * i + 1]);
                        else mma_bf16(acc[i], wreg[ks >= NS ? ks - NS : 0], b[kk % 3][2 * i], b[kk % 3][2 * i + 1]);
                    }
                    if (kk + 3 < 18) ldsm_x4_t(b[kk % 3], l16 + SM_M + (kk + 3) * 512);
                    if (kk + 3 == 17) asm volatile("ld.shared.f32 %0, [%1];" : "=f"(minv) : "r"(sbase + SM_SC + 8) : "memory");
                }
                const uint32_t u0 = pack_bf16(fmaf(acc[1][0], minv, acc[0][0] * minv), fmaf(acc[1][1], minv, acc[0][1] * minv));
                FS(2, u0);
                post(s + 1, to, ta, scw, u0, pack_bf16(fmaf(acc[1][2], minv, acc[0][2] * minv), fmaf(acc[1][3], minv, acc[0][3] * minv)));
            }
            if (C) named_bar(7, 256);
        };
        if (role == 2) main_loop(Flag<true>()); else main_loop(Flag<false>());
    } else {
        float* scs = reinterpret_cast<float*>(smem_raw + SM_SC);
        uint32_t wo[3][8][4];
        uint32_t mx2 = 0u;
        {
            const int pt = tid - 256, lane = lane_o, wq = warp - 8, g = lane >> 2, tq = lane & 3;
            TSQ(7);
            mbar_wait(sbase + B_E, 0);
            TSQ(8);
#pragma unroll
            for (int t = 0; t < 3; t++) {
                const int T = 3 * wq + t;
                const uint32_t a = sbase + SM_X01 + (T >> 2) * 16384 + ((lane >> 4) * 8 + (lane & 7)) * 128 + ((((T & 3) * 2 + ((lane >> 3) & 1)) ^ (lane & 7)) << 4);
#pragma unroll
                for (int kk = 0; kk < 8; kk++) ldsm_x4_t(wo[t][kk], a + ((2 * wq + kk) & 7) * 2048);
            }
            named_bar(3, 128);
            if (pt == 64) {
                fence_async();
#pragma unroll 1
                for (int i = 3; i < 9; i++) { stage_x(i); if (i >= NUP) stage_w(i); }
            }
            if (pt >= 96 && pt < 120) {
                *reinterpret_cast<uint4*>(g_acc + cta * 1024 + (pt - 96) * 16) = make_uint4(0u, 0u, 0u, 0u);
                __threadfence();
            }
            __syncwarp();
            TSQ(9);
            float c0 = 0.f;
#pragma unroll
            for (int t = 0; t < 3; t++) {
                float n[4][4];
#pragma unroll
                for (int i = 0; i < 4; i++) { n[i][0] = n[i][1] = n[i][2] = n[i][3] = 0.f; }
#pragma unroll
                for (int kk = 0; kk < 8; kk++)
#pragma unroll
                    for (int i = 0; i < 4; i++) mma_k8(n[i], wo[t][kk][i & 2], wo[t][kk][(i & 2) + 1], wo[t][kk][i]);
                if ((g >> 1) == tq) c0 = fmaxf(c0, (g & 1) ? fmaxf(n[0][1] + n[2][1], n[1][3] + n[3][3]) : fmaxf(n[0][0] + n[2][0], n[1][2] + n[3][2]));
            }
            c0 = __uint_as_float(__reduce_max_sync(0xffffffffu, __float_as_uint(c0)));
            uint32_t m = 0u;
            if (role == 0) {
                const int b = h % 9;
                mbar_wait(sbase + B_W + 8 * b, 0);
#pragma unroll
                for (int j = 0; j < 5; j++) {
                    const uint4 xv = *reinterpret_cast<const uint4*>(smem_raw + x01_off(b) + (j < 4 ? pt + 128 * j : 512 + (pt & 63)) * 16);
                    m = max_abs8(m, xv.x, xv.y, xv.z, xv.w);
                }
            }
            asm volatile("barrier.cluster.arrive.relaxed.aligned;" ::: "memory");
            m = warp_max_abs(m);
            if (lane == 0) { scs[80 + wq] = c0; reinterpret_cast<uint32_t*>(scs)[84 + wq] = m; }
            TSQ(1);
            named_bar(3, 128);
            if (pt == 0) {
                const uint4 a = *reinterpret_cast<const uint4*>(scs + 80), b = *reinterpret_cast<const uint4*>(scs + 84);
                st_vol_u2(&g_norm[cta], make_uint2(max(max(a.x, a.y), max(a.z, a.w)) | 1u, max(max(b.x, b.y), max(b.z, b.w)) | 1u));
            }
            __syncwarp();
            if (pt == 32) scs[1] = -1.f;
            named_bar(8, 384);
            TSQ(2);
            if (P0D && wq == 1) norms_gather(lane, scs, role == 2 ? SPIN_LIMIT : 1u);
            if ((!P0B || role != 2) && pt == 64) {
                fence_async();
                if (cta < NSEG) {
                    mbar_expect(sbase + B_E, XBUF);
                    bulk_g2s(sbase + SM_X + 9 * 8192, xg + (size_t)cta * SEG * DM, 32768, sbase + B_E);
                    bulk_g2s(sbase + SM_WS + 32768 + 4096, xg + (size_t)cta * SEG * DM + 16384, 4096, sbase + B_E);
                }
            }
            __syncwarp();
            asm volatile("barrier.cluster.wait.aligned;" ::: "memory");
            if (P0B && lane == 0 && wq != 1) {
                if (role == 2) {
                    fence_async();
                    const int w3 = (wq + 1) >> 1;
                    if (w3 < 2) vx_copy(sbase, 0, w3);
#pragma unroll 1
                    for (int j = 2 - w3; j < 9; j += 3) tma_2d_mc(sbase + SM_X + j * 8192, &tmx2, (j < 4 ? j + 5 : j - 4) * 64, 64, sbase + B_XT + (j < 4 ? 8 : 24));
                    if (w3 == 2 && cta < NSEG) {
                        mbar_expect(sbase + B_E, XBUF);
                        bulk_g2s(sbase + SM_X + 9 * 8192, xg + (size_t)cta * SEG * DM, 32768, sbase + B_E);
                        bulk_g2s(sbase + SM_WS + 32768 + 4096, xg + (size_t)cta * SEG * DM + 16384, 4096, sbase + B_E);
                    }
                }
            }
            __syncwarp();
        }
        const int wq = warp - 8;
        auto helper_loop = [&](auto is_c) {
        const bool C = is_c.value;
        if (C) pad_code<PAD2>(); else pad_code<PAD1>();
        const uint32_t l8_o = __shfl_sync(0xffffffffu, sbase + lane_o * 8, lane_o), l16_o = __shfl_sync(0xffffffffu, sbase + lane_o * 16, lane_o);
        unsigned char* dst = g_acc + (role * 32 + wq * 8 + (lane_o >> 3)) * 1024 + (lane_o & 7) * 16;
        auto load_kf = [&](uint32_t (&kf)[2][4], int slot) {
            int lane = lane_o;
            asm volatile("" : "+r"(lane));
            const uint32_t ka = sbase + SM_T + slot * TBUF + ((wq + 1) * DH + 64 + (lane & 7) + ((lane >> 3) & 1) * 16 + (lane >> 4) * 8) * 16;
#pragma unroll
            for (int k2 = 0; k2 < 2; k2++) ldsm_x4_t(kf[k2], ka + k2 * 512);
        };
        float minv = 1.f;
        uint32_t kf[2][4];
        if (!C) load_kf(kf, 0);
        int b3 = 0;
        int rx = 9;
        for (int s = 0; s + 1 < NSEG; s++) {
            const int n3 = b3 == 2 ? 0 : b3 + 1;
            uint32_t l8 = l8_o, l16 = l16_o;
            asm volatile("" : "+r"(l8), "+r"(l16));
            {
                int lane = lane_o;
                asm volatile("" : "+r"(lane));
                if (C) {
                    if (lane == 0) {
                        if (wq == 3 && h == 0) {
                            const uint32_t t = gtime32();
                            st_vol_u2(&g_tick, make_uint2(t, reinterpret_cast<uint32_t*>(scs)[3]));
                            reinterpret_cast<uint32_t*>(scs)[3] = t;
                        }
                    }
                    __syncwarp();
                    if (wq == 2 && s > 1 && lane < 24) {
                        *reinterpret_cast<uint4*>(g_acc + n3 * 128 + (3 * h + (lane >> 3)) * 1024 + (lane & 7) * 16) = make_uint4(0u, 0u, 0u, 0u);
                    }
                    if (RARE(wq == 1 && s == 3 && lane < 3)) {
                        const int c = 3 * h + lane;
                        st_vol_u2(&g_norm[c], make_uint2(0u, 0u));
                        uint4* z = c < NSEG ? g_rx[c] : g_wv[c - NSEG];
                        st_vol_u4(z, make_uint4(0u, 0u, 0u, 0u)); st_vol_u4(z + 1, make_uint4(0u, 0u, 0u, 0u));
                    }
                    __syncwarp();
                }
                const uint32_t mw = __reduce_max_sync(0xffffffffu, max(mx2 << 16, mx2 & 0xffff0000u));
                if (lane == 0) scs[4 + wq] = __uint_as_float(mw);
            }
            const uint32_t to = SM_T + (s & 3) * TBUF;
            const uint32_t ph = (uint32_t)(s >> 1) & 1u;
            if (!C) {
                const uint32_t bo = sbase + B_SB + 8 * (s & 1);
                uint32_t d0 = l8 + SM_S + (wq + 1) * 256, qa = l16 + to;
                const uint32_t d1 = mapa(d0 + 1280, role ^ 1), m1 = mapa(bo, role ^ 1), d2 = mapa(d0 + role * 1280, 2), m2 = mapa(bo, 2);
                asm volatile("" : "+r"(d0), "+r"(qa));
                mbar_wait(sbase + (s > 0 ? B_VX + 8 * (s & 1) : B_W), ph);
                FS(1, 0);
                named_bar(2, 384);
                uint32_t qf[2][4];
#pragma unroll
                for (int k2 = 0; k2 < 2; k2++) ldsm_x4_t(qf[k2], qa + k2 * 512);
                score_group(qf, kf, d0, d1, m1, d2, m2);
                bar_arrive(5, 384);
            } else named_bar(2, 384);
            if (RARE(s == 0)) {
                if (!C) pad_code<PADB>();
                TSQ(3);
                int lane = lane_o;
                asm volatile("" : "+r"(lane));
                if (wq == 1 && (!P0D || (!C && scs[1] < 0.f))) norms_gather(lane, scs, SPIN_LIMIT);
                if (!C) mbar_wait(sbase + B_VX, 0);
                if (!P0D || !C) named_bar(3, 128);
                TSQ(4);
            }
            const float4 m4 = *reinterpret_cast<const float4*>(scs + 4);
            const float c24 = scs[1], xb = scs[16 + s];
            uint32_t vf[2][2][4], vm[2][2];
            uint32_t va = l16 + ((l16 >> 8) & 1) * 1792 + wq * 512 + (C ? to + DH * 16 : SM_VX + (s & 1) * 8192);
            auto load_vf = [&]() {
#pragma unroll
                for (int i = 0; i < 4; i++) ldsm_x4(vf[i & 1][i >> 1], va + (i & 1) * 256 + (i >> 1) * 4096);
            };
            if (C || VFP == 0) load_vf();
            float scale;
            {
                const float bound = fmaxf(fmaxf(fmaxf(m4.x, m4.y), fmaxf(m4.z, m4.w)) * minv, xb) * c24;
                int e = 141 - (int)((__float_as_uint(bound) >> 23) & 255u);
                e = e > 100 ? 100 : e;
                scale = __uint_as_float((uint32_t)(127 + e) << 23);
            }
            uint32_t oa = l16 + wq * 512;
            asm volatile("" : "+f"(scale), "+r"(oa), "+r"(va));
            FS(7, __float_as_uint(scale));
            constexpr float EC = (float)(1.4426950408889634 * 0.08838834764831845);
            if (!C) named_bar(6, 160);
            if (C) mbar_wait_fast(sbase + B_SB + 8 * (s & 1), ph);
            float sv[5][2];
#pragma unroll
            for (int j = 0; j < 5; j++) lds64f(sv[j][0], sv[j][1], l8 + SM_S + j * 256);
            if (!C) {
#pragma unroll
                for (int j = 0; j < 5; j++) { sv[j][0] *= EC; sv[j][1] *= EC; asm volatile("" : "+f"(sv[j][0]), "+f"(sv[j][1])); }
                mbar_wait_fast(sbase + B_SB + 8 * (s & 1), ph);
            }
            FS(6, 0);
            uint32_t p[5];
            {
                float sr[5][2];
#pragma unroll
                for (int j = 0; j < 5; j++) lds64f(sr[j][0], sr[j][1], l8 + SM_S + 1280 + j * 256);
                if (!C && VFP == 1) load_vf();
                lds64(vm[0][0], vm[0][1], l8 + SM_VM + wq * 512);
                lds64(vm[1][0], vm[1][1], l8 + SM_VM + wq * 512 + 256);
#pragma unroll
                for (int j = 0; j < 5; j++) {
                    sv[j][0] = C ? sv[j][0] + sr[j][0] : fmaf(sr[j][0], EC, sv[j][0]);
                    sv[j][1] = C ? sv[j][1] + sr[j][1] : fmaf(sr[j][1], EC, sv[j][1]);
                }
                float mx = fmaxf(fmaxf(fmaxf(sv[0][0], sv[0][1]), fmaxf(sv[1][0], sv[1][1])), fmaxf(fmaxf(sv[2][0], sv[2][1]), fmaxf(sv[3][0], sv[3][1])));
                mx = fmaxf(mx, fmaxf(sv[4][0], sv[4][1]));
                {
                    const float m1 = __shfl_xor_sync(0xffffffffu, mx, 1), m2 = __shfl_xor_sync(0xffffffffu, mx, 2), m3 = __shfl_xor_sync(0xffffffffu, mx, 3);
                    if (!C && VFP == 2) { va += __float_as_uint(mx) & l16 & 3u; load_vf(); }
                    if (C) {
#pragma unroll
                        for (int j = 0; j < 5; j++) { sv[j][0] *= EC; sv[j][1] *= EC; }
                        mx = fmaxf(fmaxf(mx * EC, m1 * EC), fmaxf(m2 * EC, m3 * EC));
                    } else mx = fmaxf(fmaxf(mx, m1), fmaxf(m2, m3));
                }
#pragma unroll
                for (int jj = 0; jj < 5; jj++) {
                    const int j = (jj + 1) % 5;
                    asm("ex2.approx.ftz.f32 %0, %1;" : "=f"(sv[j][0]) : "f"(sv[j][0] - mx));
                    asm("ex2.approx.ftz.f32 %0, %1;" : "=f"(sv[j][1]) : "f"(sv[j][1] - mx));
                    p[j] = pack_bf16(sv[j][0], sv[j][1]);
                }
            }
            FS(0, p[0]);
            uint32_t b[4][4];
            float zs[4];
            {
                float o0[2][4], o1[2][4];
                mma_z(o0[0], vf[0][0], p[1], p[2]);
                mma_z(o0[1], vf[1][0], p[1], p[2]);
                mma_z(o1[0], vf[0][1], p[3], p[4]);
                mma_z(o1[1], vf[1][1], p[3], p[4]);
                mma_k8(o0[0], vm[0][0], vm[0][1], p[0]);
                mma_k8(o0[1], vm[1][0], vm[1][1], p[0]);
                const uint32_t one4[4] = {0x3f803f80u, 0x3f803f80u, 0x3f803f80u, 0x3f803f80u};
                mma_z(zs, one4, p[1], p[2]);
                mma_bf16(zs, one4, p[3], p[4]);
                mma_k8(zs, one4[0], one4[1], p[0]);
                uint32_t ow[4];
#pragma unroll
                for (int m = 0; m < 2; m++) {
                    ow[2 * m] = pack_bf16(o0[m][0] + o1[m][0], o0[m][1] + o1[m][1]);
                    ow[2 * m + 1] = pack_bf16(o0[m][2] + o1[m][2], o0[m][3] + o1[m][3]);
                }
                stsm_x4(oa + SM_O, ow[0], ow[1], ow[2], ow[3]);
                FS(2, 0);
#pragma unroll
                for (int i = 0; i < 4; i++) b[0][i] = movm(ow[i]);
            }
            float acc[3][2][4];
            named_bar(3, 128);
#pragma unroll
            for (int i = 1; i < 4; i++) ldsm_x4_t(b[i], l16 + SM_O + ((wq + i) & 3) * 512);
#pragma unroll
            for (int c = 0; c < 2; c++)
#pragma unroll
                for (int t = 0; t < 3; t++) mma_z(acc[t][c], wo[t][c], b[0][2 * c], b[0][2 * c + 1]);
            float z0, z1;
            asm volatile("rcp.approx.ftz.f32 %0, %1;" : "=f"(z0) : "f"(zs[0]));
            asm volatile("rcp.approx.ftz.f32 %0, %1;" : "=f"(z1) : "f"(zs[1]));
            z0 *= scale; z1 *= scale;
            FS(3, b[1][0]);
#pragma unroll
            for (int i = 1; i < 4; i++)
#pragma unroll
                for (int c = 0; c < 2; c++)
#pragma unroll
                    for (int t = 0; t < 3; t++) mma_bf16(acc[t][c], wo[t][2 * i + c], b[i][2 * c], b[i][2 * c + 1]);
            {
                uint32_t w[6];
#pragma unroll
                for (int t = 0; t < 3; t++) {
                    w[2 * t] = pack_f16(fmaf(acc[t][1][0], z0, acc[t][0][0] * z0), fmaf(acc[t][1][1], z1, acc[t][0][1] * z1));
                    w[2 * t + 1] = pack_f16(fmaf(acc[t][1][2], z0, acc[t][0][2] * z0), fmaf(acc[t][1][3], z1, acc[t][0][3] * z1));
                }
                FS(8, w[5]);
                asm volatile("red.relaxed.gpu.global.add.noftz.v4.f16x2 [%0], {%1,%2,%3,%4};" :: "l"(dst), "r"(w[0]), "r"(w[1]), "r"(w[2]), "r"(0x3c00u) : "memory");
                asm volatile("red.relaxed.gpu.global.add.noftz.v4.f16x2 [%0], {%1,%2,%3,%4};" :: "l"(dst + 4096), "r"(w[3]), "r"(w[4]), "r"(w[5]), "r"(0x3c00u) : "memory");
            }
            FS(9, 0);
            if (s == 0) TSQ(5);
            bar_arrive(4, 384);
            const uint32_t t0 = clock32();
            minv = __uint_as_float(0x7f000000u - __float_as_uint(scale));
            if (lane_o == 0) {
                if (wq == 0) scs[2] = minv;
                if (s + 3 < NSEG) {
                    if (wq == 0) mbar_expect(sbase + B_SB + 8 * (s & 1), C ? 2560 : 1280 + 2048);
                    if (wq == 1 && s > 0 && s + 5 < NSEG) mbar_expect(sbase + B_XT + ((s & 1) ? 0 : 16) + 4 * ((s + 1) & 2), (s & 1) ? 32768 : 40960);
                    if (wq == 3 && !C) mbar_expect(sbase + B_VX + 8 * (s & 1), 8192);
                }
            }
            __syncwarp();
            if (RARE(s == 1)) {
                if (!C) pad_code<PADC>();
                int lane = lane_o;
                asm volatile("" : "+r"(lane));
                if (wq == 3) xmax_gather(lane, scs);
                __syncwarp();
            }
            if (!C) load_kf(kf, (s + 1) & 3);
            const uint4* src = reinterpret_cast<const uint4*>(dst + (wq * 16 - role * 32) * 1024);
            dst += n3 == 0 ? -256 : 128;
            asm volatile("" : "+l"(dst));
            const int xp = (s + 5) >> 1, kb = wq + ((s & 1) ? 2 * role : 4 + 3 * role);
            const bool xl = !C && xp < NSEG / 2 && wq < ((s & 1) ? 2 : 3 - role);
            const uint32_t xs = wq == 3 && (s & 1) == 0 && xp < NSEG / 2;
            const uint32_t xd = sbase + SM_X + (rx + kb >= 13 ? rx + kb - 13 : rx + kb) * 8192;
            mx2 = poll_mem(src, l16 + SM_M + wq * 2304, t0, [&]() {
                if (xs && lane_o < 2) asm volatile("mbarrier.arrive.relaxed.cluster.shared::cluster.b64 _, [%0];" :: "r"(mapa(sbase + B_XF, lane_o)) : "memory");
                if (!C && (xl || s == 0) && (s & 1) == 0) mbar_wait(sbase + B_XF, (uint32_t)(s >> 1) & 1u);
                if (lane_o == 0) {
                    if (xl) tma_2d_mc(xd, &tmx2, ((s & 1) ? kb + 5 : kb - 4) * 64, xp * 64, sbase + B_XT + ((s & 1) ? 0 : 16) + 8 * (xp & 1));
                    if (!C && s == 0 && role == 1) tma_2d_mc(sbase + SM_X + (9 + wq) * 8192, &tmx2, (wq + 5) * 64, 128, sbase + B_XT);
                }
                __syncwarp();
            });
            if ((s & 1) == 0) rx = rx >= 4 ? rx - 4 : rx + 9;
            if (s == 0) TSQ(6);
            b3 = n3;
        }
        if (!C) bar_arrive(2, 384);
        };
        if (role == 2) helper_loop(Flag<true>()); else helper_loop(Flag<false>());
    }
    TS3C(1);
    if (role == 2 && warp >= 4) last_rows(1);
    cluster_sync_all();
}

extern "C" void kernel_launch(void* const* d_in, const int* in_sizes, int n_in, void* d_out, int out_size) {
    const bf16* x = (const bf16*)d_in[0];
    const bf16* mem0 = (const bf16*)d_in[1];
    const bf16* Wq = (const bf16*)d_in[2];
    const bf16* Wk = (const bf16*)d_in[3];
    const bf16* Wv = (const bf16*)d_in[4];
    const bf16* Wo = (const bf16*)d_in[5];
    const bf16* logA = (const bf16*)d_in[8];
    const bf16* Aim = (const bf16*)d_in[9];
    const bf16* Cre = (const bf16*)d_in[10];
    const bf16* Cim = (const bf16*)d_in[11];
    const bf16* logdt = (const bf16*)d_in[12];
    const bf16* dskip = (const bf16*)d_in[13];
    const bf16* gw = (const bf16*)d_in[14];
    bf16* out = (bf16*)d_out;
    static bool attr_done = false;
    typedef CUresult (*EncFn)(CUtensorMap*, CUtensorMapDataType, cuuint32_t, void*, const cuuint64_t*, const cuuint64_t*, const cuuint32_t*,
                              const cuuint32_t*, CUtensorMapInterleave, CUtensorMapSwizzle, CUtensorMapL2promotion, CUtensorMapFloatOOBfill);
    static EncFn enc = nullptr;
    if (!attr_done) {
        void* fn = nullptr;
        cudaDriverEntryPointQueryResult qr;
        cudaGetDriverEntryPoint("cuTensorMapEncodeTiled", &fn, cudaEnableDefault, &qr);
        enc = (EncFn)fn;
        cudaFuncSetAttribute(k_chain, cudaFuncAttributeMaxDynamicSharedMemorySize, 232448);
        cudaFuncSetAttribute(k_side, cudaFuncAttributeMaxDynamicSharedMemorySize, SIDE_SMEM);
        attr_done = true;
    }
    CUtensorMap tmw[3];
    for (int i = 0; i < 3; i++) {
        const cuuint64_t dims[2] = {(cuuint64_t)HD, (cuuint64_t)DM};
        const cuuint64_t strides[1] = {(cuuint64_t)HD * 2};
        const cuuint32_t box[2] = {64, 64};
        const cuuint32_t es[2] = {1, 1};
        enc(&tmw[i], CU_TENSOR_MAP_DATA_TYPE_BFLOAT16, 2, (void*)(i == 0 ? Wq : (i == 1 ? Wk : Wv)), dims, strides, box, es, CU_TENSOR_MAP_INTERLEAVE_NONE,
            CU_TENSOR_MAP_SWIZZLE_128B, CU_TENSOR_MAP_L2_PROMOTION_L2_256B, CU_TENSOR_MAP_FLOAT_OOB_FILL_NONE);
    }
    CUtensorMap tmo;
    {
        const cuuint64_t dims[2] = {(cuuint64_t)DM, (cuuint64_t)HD};
        const cuuint64_t strides[1] = {(cuuint64_t)DM * 2};
        const cuuint32_t box[2] = {64, 128};
        const cuuint32_t es[2] = {1, 1};
        enc(&tmo, CU_TENSOR_MAP_DATA_TYPE_BFLOAT16, 2, (void*)Wo, dims, strides, box, es, CU_TENSOR_MAP_INTERLEAVE_NONE,
            CU_TENSOR_MAP_SWIZZLE_128B, CU_TENSOR_MAP_L2_PROMOTION_L2_128B, CU_TENSOR_MAP_FLOAT_OOB_FILL_NONE);
    }
    CUtensorMap tmx2;
    {
        const cuuint64_t dims[2] = {(cuuint64_t)DM, (cuuint64_t)S_LEN};
        const cuuint64_t strides[1] = {(cuuint64_t)DM * 2};
        const cuuint32_t box[2] = {64, 64};
        const cuuint32_t es[2] = {1, 1};
        enc(&tmx2, CU_TENSOR_MAP_DATA_TYPE_BFLOAT16, 2, (void*)x, dims, strides, box, es, CU_TENSOR_MAP_INTERLEAVE_NONE,
            CU_TENSOR_MAP_SWIZZLE_128B, CU_TENSOR_MAP_L2_PROMOTION_L2_128B, CU_TENSOR_MAP_FLOAT_OOB_FILL_NONE);
    }
    CUtensorMap tmm;
    {
        const cuuint64_t dims[2] = {(cuuint64_t)DM, (cuuint64_t)MEMT};
        const cuuint64_t strides[1] = {(cuuint64_t)DM * 2};
        const cuuint32_t box[2] = {64, (cuuint32_t)MEMT};
        const cuuint32_t es[2] = {1, 1};
        enc(&tmm, CU_TENSOR_MAP_DATA_TYPE_BFLOAT16, 2, (void*)mem0, dims, strides, box, es, CU_TENSOR_MAP_INTERLEAVE_NONE,
            CU_TENSOR_MAP_SWIZZLE_128B, CU_TENSOR_MAP_L2_PROMOTION_L2_128B, CU_TENSOR_MAP_FLOAT_OOB_FILL_NONE);
    }
    k_chain<<<NCTA, 384, 232448>>>(tmw[0], tmw[1], tmw[2], tmx2, tmo, tmm, x);
    {
        cudaLaunchConfig_t cfg = {};
        cfg.gridDim = dim3(SD_NCTA); cfg.blockDim = dim3(512); cfg.dynamicSmemBytes = SIDE_SMEM; cfg.stream = cudaStreamPerThread;
        cudaLaunchAttribute at[1];
        at[0].id = cudaLaunchAttributeProgrammaticStreamSerialization;
        at[0].val.programmaticStreamSerializationAllowed = 1;
        cfg.attrs = at; cfg.numAttrs = 1;
        cudaLaunchKernelEx(&cfg, k_side, tmo, x, logA, Aim, Cre, Cim, logdt, Wo, dskip, gw, out);
    }
}
```

```cpp
#include <cuda_runtime.h>
#include <cuda.h>
#include <cuda_bf16.h>
#include <stdint.h>

typedef __nv_bfloat16 bf16;
#define LDV4 "ld.volatile.global.v4.u32 {%0,%1,%2,%3}, [%4];"
#define STV4 "st.volatile.global.v4.u32 [%0], {%1,%2,%3,%4};"
#define STV2 "st.volatile.global.v2.u32 [%0], {%1,%2};"

constexpr int S_LEN = 2048, DM = 576, NH = 32, DH = 128, HD = 4096, MEMT = 8, SEG = 32, NSEG = 64, NST = 128;

__device__ __align__(128) bf16 g_gate[S_LEN];
constexpr int NCTA = NH * 3;
__device__ __align__(1024) unsigned char g_acc[96 * 1024];
__device__ __align__(128) uint2 g_norm[NCTA];
__device__ __align__(128) uint4 g_wv[NH][2];
__device__ __align__(128) uint4 g_rx[NSEG][2];
__device__ __align__(128) unsigned char g_qkv[NSEG][NH][3][10240];
__device__ __align__(128) bf16 g_ox[S_LEN * HD];
__device__ __align__(128) uint4 g_fp[8][36][6][128];
__device__ __align__(128) unsigned g_flag[NH * NSEG];
__device__ unsigned g_prog[NSEG / 2 * 8];
__device__ unsigned g_gcnt[64];
__device__ unsigned g_epoch;
__device__ __align__(128) uint2 g_tick;
__device__ __align__(128) bf16 g_y[DM * S_LEN];

#define TS3(slot) do {} while (0)
#define TS3P(slot) do {} while (0)
#define TSQ(slot) do {} while (0)
#define TS3W(slot) do {} while (0)
#define TSS(row, slot) do {} while (0)
#define TS3C(slot) do {} while (0)
#define TST(slot) do {} while (0)
#define TSA(seg, slot) do {} while (0)
#define TSG(i) do {} while (0)
#define FS(i, dep) do {} while (0)
__device__ __forceinline__ uint32_t smem_u32(const void* p) { return (uint32_t)__cvta_generic_to_shared(p); }
__device__ __forceinline__ float bf16r(float x) { return __bfloat162float(__float2bfloat16_rn(x)); }
__device__ __forceinline__ uint32_t pack_bf16(float lo, float hi) {
    __nv_bfloat162 v = __floats2bfloat162_rn(lo, hi);
    return *reinterpret_cast<uint32_t*>(&v);
}
__device__ __forceinline__ void ldsm_x4(uint32_t (&r)[4], uint32_t addr) {
    asm volatile("ldmatrix.sync.aligned.m8n8.x4.shared.b16 {%0,%1,%2,%3}, [%4];"
                 : "=r"(r[0]), "=r"(r[1]), "=r"(r[2]), "=r"(r[3]) : "r"(addr));
}
__device__ __forceinline__ void ldsm_x4_t(uint32_t (&r)[4], uint32_t addr) {
    asm volatile("ldmatrix.sync.aligned.m8n8.x4.trans.shared.b16 {%0,%1,%2,%3}, [%4];"
                 : "=r"(r[0]), "=r"(r[1]), "=r"(r[2]), "=r"(r[3]) : "r"(addr));
}
__device__ __forceinline__ void mma_bf16(float (&d)[4], const uint32_t (&a)[4], uint32_t b0, uint32_t b1) {
    asm volatile("mma.sync.aligned.m16n8k16.row.col.f32.bf16.bf16.f32 {%0,%1,%2,%3}, {%4,%5,%6,%7}, {%8,%9}, {%0,%1,%2,%3};"
                 : "+f"(d[0]), "+f"(d[1]), "+f"(d[2]), "+f"(d[3])
                 : "r"(a[0]), "r"(a[1]), "r"(a[2]), "r"(a[3]), "r"(b0), "r"(b1));
}
__device__ __forceinline__ uint2 ld_vol_u2(const uint2* p) {
    uint2 v; asm volatile("ld.volatile.global.v2.u32 {%0,%1}, [%2];" : "=r"(v.x), "=r"(v.y) : "l"(p) : "memory"); return v;
}
__device__ __forceinline__ void st_vol_u2(uint2* p, uint2 v) {
    asm volatile(STV2 :: "l"(p), "r"(v.x), "r"(v.y) : "memory");
}
__device__ __forceinline__ unsigned ld_acq(const unsigned* p) {
    unsigned v; asm volatile("ld.acquire.gpu.global.u32 %0, [%1];" : "=r"(v) : "l"(p) : "memory"); return v;
}
#define NS 10
#define NP 4
#define X_OXSZ 16384
#define GATE_A 1050
#define GATE_B 300
#define GATE_P 1880u
#define STAGGER 0
#define RLX_SLEEP 300
#define VX_DELAY 100
#define EARLY4 0
#define SPEC_M 1
#define SPEC_H 1
#define C2_DELAY 0
#define SS_POS 10
#define UNGATE_G 3
#define GATE_Y 0
#define GATE_S 0
#define GATE_F 1
#define W14_SLEEP 60
#define TURN31 1
#define GL_A 1150
#define GL_B 480
#define GS_A 1400
#define GS_B 480
#define GATE_POLL 0
#define GP_A 900
#define GP_B 200
#define NUP 3
#define SIDE_WAIT 0
#define FASTW 0
#define NC1 5
#define NC1C NC1
#define C1_DELAY 0
#define XSKIP 0
#define LATEW 1
#define VFP 0
#define CC_DELAY 0
#define KPRE 34
#define P0A 1
#define P0B 1
#define P0C 0
#define P0D 0
#define GPRED 1
#define P0W 3
#define XRARE 1
#define RARE(c) __builtin_expect(!!(c), 0)
#define PADB 0
#define PADC 0
#define PADD 0
#define PADE 0
#define PAD1 0
#define PAD2 0
#define PAD3 0
#define PAD4 0
#define B4P 1
#define XPF 0
#define NC0 4
#define KG1 20
#define SMR 0
#define TL_DELAY 600
#define POLL_DELAY 590
#define UNGATE 6
constexpr unsigned SPIN_LIMIT = 1u << 20;
constexpr int NATT = NSEG - 2;

constexpr int SD_CH = 16;
constexpr int SD_NCTA = DM / SD_CH;
constexpr int SD_ROW = 528;
constexpr int SD_U = 8 * SD_ROW;
constexpr int SD_TAP = 5888;
constexpr int SD_CPY = 1376 * 2;
constexpr int SD_WSTR = SD_TAP + 2 * SD_CPY;
constexpr int SD_SMEM = SD_CH * SD_U + 8 * SD_WSTR;
constexpr int O_U = 79, O_U3 = 911, O_U4 = 1055, O_W79 = 1023, O_W35 = 1151, O_W610 = 1279, O_W511 = 1487;

__device__ __forceinline__ uint32_t lds32(uint32_t a) { uint32_t v; asm volatile("ld.shared.u32 %0, [%1];" : "=r"(v) : "r"(a)); return v; }
__device__ __forceinline__ void sts32(uint32_t a, uint32_t v) { asm volatile("st.shared.u32 [%0], %1;" :: "r"(a), "r"(v) : "memory"); }
__device__ __forceinline__ uint4 lds128(uint32_t a) {
    uint4 v; asm volatile("ld.shared.v4.u32 {%0,%1,%2,%3}, [%4];" : "=r"(v.x), "=r"(v.y), "=r"(v.z), "=r"(v.w) : "r"(a) : "memory"); return v;
}
__device__ __forceinline__ void tap_tile(uint32_t (&t)[4], uint32_t a) {
    asm volatile("ld.volatile.shared.u32 %0, [%4];\nld.volatile.shared.u32 %1, [%4+-16];\nld.volatile.shared.u32 %2, [%4+16];\nld.volatile.shared.u32 %3, [%4];"
                 : "=r"(t[0]), "=r"(t[1]), "=r"(t[2]), "=r"(t[3]) : "r"(a));
}
constexpr uint32_t sd_pass(int type, int dl, int o, int d0, int d1) { return (uint32_t)(type | dl << 2 | d0 << 8 | d1 << 12 | o << 17); }
__constant__ uint32_t SD_PASS[14] = {sd_pass(0, 0, O_U, 0, 2), sd_pass(0, 1, O_U + 96, 0, 2), sd_pass(0, 2, O_U + 192, 0, 4), sd_pass(0, 3, O_U + 288, 0, 2), sd_pass(1, 0, O_U3, 8, 8),
                                     sd_pass(0, 4, O_U + 384, 0, 2), sd_pass(1, 0, O_U4, 8, 15), sd_pass(0, 5, O_U + 480, 0, 2), sd_pass(0, 6, O_U + 576, 0, 4), sd_pass(0, 7, O_U + 672, 0, 2),
                                     sd_pass(2, 0, O_W35, 2, 8), sd_pass(3, 0, O_W79, 2, 4), sd_pass(2, 1, O_W610, 4, 8), sd_pass(3, 0, O_W511, 8, 15)};
__device__ __forceinline__ uint32_t band2(int x, int lo, int hi) { return (x >= lo && x <= hi ? 0x3f80u : 0u) | (x + 1 >= lo && x + 1 <= hi ? 0x3f800000u : 0u); }
__device__ __forceinline__ void mma_z(float (&d)[4], const uint32_t (&a)[4], uint32_t b0, uint32_t b1);
__device__ __forceinline__ void put_tap(uint32_t a, float v) {
    asm volatile("{\n.reg .b16 h;\ncvt.rn.bf16.f32 h, %1;\nst.shared.b16 [%0], h;\nst.shared.b16 [%0+%2], h;\n}" :: "r"(a), "f"(v), "n"(SD_CPY - 2) : "memory");
}

__device__ __forceinline__ void named_bar(int id, int n) { asm volatile("bar.sync %0, %1;" :: "r"(id), "r"(n) : "memory"); }
__device__ __forceinline__ uint32_t pack_f16(float lo, float hi) {
    uint32_t r; asm("cvt.rn.f16x2.f32 %0, %1, %2;" : "=r"(r) : "f"(hi), "f"(lo)); return r;
}
__device__ __forceinline__ void cexp_t(float lr, float turns, float& re, float& im) {
    float m;
    asm("ex2.approx.ftz.f32 %0, %1;" : "=f"(m) : "f"(lr));
    const float a = (turns - rintf(turns)) * 6.283185307179586f;
    re = m * __cosf(a); im = m * __sinf(a);
}
__device__ __forceinline__ void csq(float& re, float& im) { const float r = re * re - im * im; im = 2.f * re * im; re = r; }
__device__ __forceinline__ void kb_state(const float* tp, float gf, uint32_t (&a)[4][2], uint32_t (&b)[5]) {
    const float4 p0 = *reinterpret_cast<const float4*>(tp), p1 = *reinterpret_cast<const float4*>(tp + 4);
    float wr, wi;
    cexp_t(p0.x * gf, p0.y * gf, wr, wi);
    float vr = wr * p1.x - wi * p1.y, vi = wr * p1.y + wi * p1.x;
#pragma unroll
    for (int c = 0; c < 4; c++) {
        a[c][0] = pack_f16(wr, wi); a[c][1] = pack_f16(vr, vi);
        csq(wr, wi);
        if (c < 3) csq(vr, vi);
    }
    b[0] = pack_f16(p0.z * wr - p0.w * wi, -p0.z * wi - p0.w * wr);
    float er = wr * p1.z - wi * p1.w, ei = wr * p1.w + wi * p1.z;
#pragma unroll
    for (int c = 0; c < 4; c++) {
        b[1 + c] = pack_f16(p0.z * er - p0.w * ei, -p0.z * ei - p0.w * er);
        if (c < 3) csq(er, ei);
    }
}
__device__ __forceinline__ uint32_t bf2_mul(uint32_t a, uint32_t b) { uint32_t r; asm("mul.rn.bf16x2 %0, %1, %2;" : "=r"(r) : "r"(a), "r"(b)); return r; }
__device__ __forceinline__ uint32_t bf2_add(uint32_t a, uint32_t b) { uint32_t r; asm("add.rn.bf16x2 %0, %1, %2;" : "=r"(r) : "r"(a), "r"(b)); return r; }
__device__ __forceinline__ uint32_t bf2_sub(uint32_t a, uint32_t b) { uint32_t r; asm("sub.rn.bf16x2 %0, %1, %2;" : "=r"(r) : "r"(a), "r"(b)); return r; }
__device__ __forceinline__ void wait_cnt(const unsigned* p, unsigned target) {
    unsigned it = 0;
    while ((int)(ld_acq(p) - target) < 0 && ++it < SPIN_LIMIT) __nanosleep(64);
}
__device__ __forceinline__ uint32_t gtime32() { uint32_t t; asm volatile("mov.u32 %0, %%globaltimer_lo;" : "=r"(t) :: "memory"); return t; }
__device__ __forceinline__ void gate(uint32_t tick_addr, uint32_t ga = GATE_A, uint32_t gb = GATE_B) {
    uint32_t t1, p;
    asm volatile("ld.volatile.shared.v2.u32 {%0,%1}, [%2];" : "=r"(t1), "=r"(p) : "r"(tick_addr) : "memory");
    uint32_t d = gtime32() - t1;
    if (d < 4u * p) {
        d -= d >= 2u * p ? 2u * p : 0u;
        d -= d >= p ? p : 0u;
        if (d + ga >= p && d + gb < p) {
            const uint32_t t2 = gtime32() + (p - gb - d);
            while ((int)(gtime32() - t2) < 0) {}
        }
    }
}

__device__ __forceinline__ void read_tick(uint32_t tick_addr) {
    const uint2 tk = ld_vol_u2(&g_tick);
    uint32_t p = tk.x - tk.y;
    p = p > GATE_P + 100u ? GATE_P + 100u : p;
    asm volatile("st.volatile.shared.v2.u32 [%0], {%1,%2};" :: "r"(tick_addr), "r"(tk.x), "r"(p) : "memory");
}

__device__ __forceinline__ void s4d_phase(unsigned char* smem_raw, const bf16* __restrict__ x, const bf16* __restrict__ logA,
                                          const bf16* __restrict__ Aim, const bf16* __restrict__ Cre, const bf16* __restrict__ Cim,
                                          const bf16* __restrict__ logdt, const bf16* __restrict__ dskip, const bf16* __restrict__ wslice, unsigned ep, uint32_t tick) {
    const int tid = threadIdx.x, warp = __shfl_sync(0xffffffffu, tid >> 5, 0), lane = tid & 31;
    const int d0 = blockIdx.x * SD_CH;
    float* tab = reinterpret_cast<float*>(smem_raw + SD_CH * SD_U + warp * SD_WSTR);
    const uint32_t wb = smem_u32(tab);
    const int g = lane >> 2, tq = lane & 3;
    uint2 prm[4];
    float ldt;
    auto load_prm = [&](int d) {
        prm[0] = __ldg(reinterpret_cast<const uint2*>(logA + d * NST) + lane); prm[1] = __ldg(reinterpret_cast<const uint2*>(Aim + d * NST) + lane);
        prm[2] = __ldg(reinterpret_cast<const uint2*>(Cre + d * NST) + lane); prm[3] = __ldg(reinterpret_cast<const uint2*>(Cim + d * NST) + lane);
        ldt = __bfloat162float(logdt[d]);
    };
    load_prm(d0 + warp);
    for (int i = lane; i < 2 * SD_CPY / 16; i += 32) reinterpret_cast<uint4*>(tab + SD_TAP / 4)[i] = make_uint4(0u, 0u, 0u, 0u);
    TS3(20);
#pragma unroll 1
    for (int ch = 0; ch < 2; ch++) {
        const int d = d0 + 8 * ch + warp;
        const uint32_t ub = smem_u32(smem_raw) + (8 * ch + warp) * SD_U;
        float k2048 = 0.f, sinv;
        {
            const float dt = bf16r(expf(ldt));
            uint32_t cm = __vmaxu2(__vmaxu2(prm[2].x & 0x7fff7fffu, prm[2].y & 0x7fff7fffu), __vmaxu2(prm[3].x & 0x7fff7fffu, prm[3].y & 0x7fff7fffu));
            cm = __reduce_max_sync(0xffffffffu, max(cm << 16, cm & 0xffff0000u));
            int e = 134 - (int)(__float_as_uint(__uint_as_float(cm) * dt) >> 23);
            e = e > 100 ? 100 : (e < -100 ? -100 : e);
            const float s2 = __uint_as_float((uint32_t)(128 + e) << 23);
            sinv = __uint_as_float((uint32_t)(127 - e) << 23);
#pragma unroll
            for (int j = 0; j < 4; j++) {
                float q[4];
#pragma unroll
                for (int i = 0; i < 4; i++) { const uint32_t w = j < 2 ? prm[i].x : prm[i].y; q[i] = __uint_as_float((j & 1) ? w & 0xffff0000u : w << 16); }
                const float zl = -bf16r(expf(q[0])) * dt * 1.4426950408889634f;
                const float zt = q[1] * dt * 0.15915494309189535f;
                const float cr = s2 * (q[2] * dt), ci = s2 * (q[3] * dt);
                float ar, ai, br, bi, er, ei;
                cexp_t(zl * 8.f, zt * 8.f, ar, ai);
                cexp_t(zl * 128.f, zt * 128.f, br, bi);
                cexp_t(zl * 2048.f, zt * 2048.f, er, ei);
                k2048 += cr * er - ci * ei;
                *reinterpret_cast<float4*>(tab + (lane + 32 * j) * 8) = make_float4(zl, zt, cr, ci);
                *reinterpret_cast<float4*>(tab + (lane + 32 * j) * 8 + 4) = make_float4(ar, ai, br, bi);
            }
#pragma unroll
            for (int o = 16; o; o >>= 1) k2048 += __shfl_xor_sync(0xffffffffu, k2048, o);
        }
        __syncwarp();
        {
            float kc[5][4];
#pragma unroll
            for (int i = 0; i < 5; i++) { kc[i][0] = kc[i][1] = kc[i][2] = kc[i][3] = 0.f; }
            const float gf = (float)g;
#pragma unroll 2
            for (int ks = 0; ks < 16; ks++) {
                uint32_t a0[4][2], a1[4][2], b0[5], b1[5];
                kb_state(tab + (8 * ks + tq) * 8, gf, a0, b0);
                kb_state(tab + (8 * ks + 4 + tq) * 8, gf, a1, b1);
#pragma unroll
                for (int i = 0; i < 5; i++) {
                    const int c = i > 0 ? i - 1 : 0;
                    asm volatile("mma.sync.aligned.m16n8k16.row.col.f32.f16.f16.f32 {%0,%1,%2,%3}, {%4,%5,%6,%7}, {%8,%9}, {%0,%1,%2,%3};"
                                 : "+f"(kc[i][0]), "+f"(kc[i][1]), "+f"(kc[i][2]), "+f"(kc[i][3])
                                 : "r"(a0[c][0]), "r"(a0[c][1]), "r"(a1[c][0]), "r"(a1[c][1]), "r"(b0[i]), "r"(b1[i]));
                }
            }
            const uint32_t tp = wb + SD_TAP;
            const uint32_t a0 = tp + 2 * (O_U + 96 * g - 4 * tq);
            const uint32_t a2 = tp + 2 * (((g & 1) ? O_U + 96 * (2 * (g & 3)) : ((g & 2) ? O_W35 : O_W79 + 1)) - 32 - 8 * tq - (g >> 2));
            const uint32_t a3 = tp + 2 * (((g & 1) ? O_W35 : O_W610 + 1) - 64 - 16 * tq - (g >> 1));
            const uint32_t a4 = tp + 2 * (-128 - 32 * tq - g);
#pragma unroll
            for (int c = 0; c < 4; c++) {
                const int e = (c & 1) * 16 + (c >> 1) * 8;
                const bool first = c == 0 && lane == 0;
                put_tap(a0 - e / 4, kc[0][c] * sinv);
                put_tap(a0 - 32 - e / 4, kc[1][c] * sinv);
                put_tap(first ? tp + 2 * (O_U - 32) : a2 - e / 2, kc[2][c] * sinv);
                put_tap(first ? tp + 2 * (O_W79 - 63) : a3 - e, kc[3][c] * sinv);
                put_tap(first ? tp + 2 * (O_W610 - 127) : a4 + 2 * (O_W511 + 1 - e), kc[4][c] * sinv);
                if ((g & 1) == 0) {
                    put_tap(a4 + 2 * (O_U4 - e), kc[4][c] * sinv);
                    put_tap(first ? tp + 2 * (O_U3 - 128) : a4 + 2 * (O_U4 + 1 - e), kc[4][c] * sinv);
                }
            }
            if (lane == 0) {
                put_tap(tp + 2 * (O_U + 96 - 32), kc[2][0] * sinv);
                put_tap(tp + 2 * (O_U + 192 - 64), kc[3][0] * sinv);
                put_tap(tp + 2 * (O_W511 - 255), k2048 * sinv);
                put_tap(tp + 2 * (O_U4 - 255), k2048 * sinv);
            }
        }
        TS3(21 + 2 * ch);
        if (ch == 0) { if (!STAGGER || warp < 4) named_bar(1, 384); }
        else {
#pragma unroll
            for (int i = 0; i < 4; i++) asm volatile("prefetch.global.L2 [%0];" :: "l"(wslice + (size_t)((tid & 127) + 128 * i) * DM));
        }
        __syncwarp();
        if (tid == 0) TSS(18, 4 * ch);
        const uint32_t sh = wb + 80 + 11 * SD_ROW;
#pragma unroll
        for (int p = 0; p < 8; p++) {
            uint4 v;
            asm volatile("ld.shared.v4.u32 {%0,%1,%2,%3}, [%4];" : "=r"(v.x), "=r"(v.y), "=r"(v.z), "=r"(v.w) : "r"(ub + p * SD_ROW + lane * 16) : "memory");
            uint32_t pv = __shfl_up_sync(0xffffffffu, v.w, 1);
            pv = lane == 0 ? 0u : pv;
            asm volatile("st.shared.v4.u32 [%0], {%1,%2,%3,%4};" :: "r"(sh + (p - 8) * SD_ROW + lane * 16), "r"(__byte_perm(pv, v.x, 0x5432)), "r"(__byte_perm(v.x, v.y, 0x5432)),
                         "r"(__byte_perm(v.y, v.z, 0x5432)), "r"(__byte_perm(v.z, v.w, 0x5432)) : "memory");
            if (p >= 5) asm volatile("st.shared.v4.u32 [%0], {%1,%2,%3,%4};" :: "r"(sh + (p - 16) * SD_ROW + lane * 16), "r"(pv), "r"(v.x), "r"(v.y), "r"(v.z) : "memory");
        }
        __syncwarp();
        if (tid == 0) TSS(18, 4 * ch + 1);
        float acc[16][4];
#pragma unroll
        for (int i = 0; i < 16; i++) { acc[i][0] = acc[i][1] = acc[i][2] = acc[i][3] = 0.f; }
        {
            const uint32_t ka = wb + SD_TAP + ((g & 1) ? 0 : SD_CPY - 2) + 2 * (2 * tq - g);
            uint32_t b[16][2], b2[14][2];
#pragma unroll
            for (int k = 0; k < 16; k++) { b[k][0] = b[k][1] = 0u; if (k < 14) b2[k][0] = b2[k][1] = 0u; }
#pragma unroll 1
            for (int ps = 0; ps < 14; ps++) {
                const uint32_t pw = __shfl_sync(0xffffffffu, SD_PASS[ps], 0), type = pw & 3u, kp = ka + (pw >> 16);
                const int dl = (pw >> 2) & 7, d0 = (pw >> 8) & 15, d1 = (pw >> 12) & 15;
                uint32_t t[2][4];
                tap_tile(t[0], kp - 32 * d0);
                if (type == 0) {
                    const int p = (lane & 7) - dl;
                    const uint32_t ra = (p < 0 ? sh : ub) + p * SD_ROW + (lane >> 3) * 16;
#pragma unroll
                    for (int k = 0; k < 8; k++)
                        asm volatile("ldmatrix.sync.aligned.m8n8.x4.shared.b16 {%0,%1,%2,%3}, [%4];"
                                     : "=r"(b[2 * k][0]), "=r"(b[2 * k][1]), "=r"(b[2 * k + 1][0]), "=r"(b[2 * k + 1][1]) : "r"(ra + k * 64));
                } else if (type == 2) {
                    const int p = (lane & 15) - 11, xo = 2 * tq - g;
                    const uint32_t qa = (p < 0 ? sh : ub) + p * SD_ROW + (lane >> 4) * 16;
                    const int lx = 6 - 5 * dl, hx = 8 - 3 * dl, ly = 2 - 2 * dl, hy = 4 + 2 * dl;
                    const uint32_t sel[4] = {band2(xo, lx, hx), band2(xo, ly, hy), band2(xo + 8, lx, hx), band2(xo + 8, ly, hy)};
#pragma unroll
                    for (int k = 0; k < 14; k++) {
                        uint32_t q[4];
                        ldsm_x4_t(q, qa + k * 32);
#pragma unroll
                        for (int i = 0; i < 2; i++) {
                            float w[4];
                            mma_z(w, sel, q[2 * i], q[2 * i + 1]);
                            b[k][i] = pack_bf16(w[0], w[1]);
                            b2[k][i] = pack_bf16(w[2], w[3]);
                        }
                    }
                } else if (type == 3) {
#pragma unroll
                    for (int k = 0; k < 14; k++) { b[k][0] = b2[k][0]; b[k][1] = b2[k][1]; }
                }
#pragma unroll
                for (int d = 0; d < 16; d += 2) {
                    if (d >= 8 || d >= d0) {
                        tap_tile(t[1], kp - 32 * (d + 1));
#pragma unroll
                        for (int k = 0; k + d < 16; k++) mma_bf16(acc[k + d], t[0], b[k][0], b[k][1]);
                        if ((d == 2 || d == 4 || d == 8) && d == d1) break;
                        if (d < 14) tap_tile(t[0], kp - 32 * (d + 2));
#pragma unroll
                        for (int k = 0; k + d + 1 < 16; k++) mma_bf16(acc[k + d + 1], t[1], b[k][0], b[k][1]);
                    }
                }
            }
        }
        __syncwarp();
        if (tid == 0) TSS(18, 4 * ch + 2);
        load_prm(d0 + 8 + warp);
        if (ch == 0) { if (lane == 0) wait_cnt(&g_gcnt[0], SD_NCTA * ep); __syncwarp(); }
        if (tid == 0) TSS(18, 4 * ch + 3);
        uint4 gv[8];
#pragma unroll
        for (int i = 0; i < 8; i++) gv[i] = __ldcg(reinterpret_cast<const uint4*>(g_gate) + lane + 32 * i);
        const uint32_t dd = __byte_perm(*reinterpret_cast<const unsigned short*>(dskip + d), 0u, 0x1010);
#pragma unroll
        for (int i = 0; i < 8; i++) {
            uint32_t u[4];
            ldsm_x4_t(u, ub + (lane & 7) * SD_ROW + (lane >> 3) * 16 + i * 64);
            asm volatile("stmatrix.sync.aligned.m8n8.x4.shared.b16 [%0], {%1,%2,%3,%4};"
                         :: "r"(wb + (lane + 32 * i) * 16),
                            "r"(bf2_add(pack_bf16(acc[2 * i][0], acc[2 * i][1]), bf2_mul(u[0], dd))), "r"(bf2_add(pack_bf16(acc[2 * i][2], acc[2 * i][3]), bf2_mul(u[1], dd))),
                            "r"(bf2_add(pack_bf16(acc[2 * i + 1][0], acc[2 * i + 1][1]), bf2_mul(u[2], dd))), "r"(bf2_add(pack_bf16(acc[2 * i + 1][2], acc[2 * i + 1][3]), bf2_mul(u[3], dd))) : "memory");
        }
        if (GATE_Y) gate(tick);
        __syncwarp();
#pragma unroll
        for (int i = 0; i < 8; i++) {
            const uint4 y = *reinterpret_cast<const uint4*>(tab + (lane + 32 * i) * 4);
            *reinterpret_cast<uint4*>(g_y + (((lane >> 1) + 16 * i) * DM + d) * 16 + (lane & 1) * 8) =
                make_uint4(bf2_mul(bf2_sub(0x3f803f80u, gv[i].x), y.x), bf2_mul(bf2_sub(0x3f803f80u, gv[i].y), y.y),
                           bf2_mul(bf2_sub(0x3f803f80u, gv[i].z), y.z), bf2_mul(bf2_sub(0x3f803f80u, gv[i].w), y.w));
        }
        __syncwarp();
        TS3(22 + 2 * ch);
    }
}
__device__ __forceinline__ void s4d_stage_u(unsigned char* smem_raw, const bf16* __restrict__ x, int pt) {
    const int p = pt & 7, w0 = pt >> 3;
    const uint4* src = reinterpret_cast<const uint4*>(x + (size_t)(16 * w0 + p) * DM + blockIdx.x * SD_CH);
    uint32_t* dst = reinterpret_cast<uint32_t*>(smem_raw + p * SD_ROW) + w0;
#pragma unroll 1
    for (int b = 0; b < 4; b++) {
        uint4 v[2][2][2];
#pragma unroll
        for (int i = 0; i < 8; i++) v[i >> 2][(i >> 1) & 1][i & 1] = src[((b * 2 + (i >> 2)) * 256 + ((i >> 1) & 1) * 8) * (DM / 8) + (i & 1)];
#pragma unroll
        for (int i = 0; i < 4; i++) {
            const uint32_t* lo = reinterpret_cast<const uint32_t*>(&v[i >> 1][0][i & 1]);
            const uint32_t* hi = reinterpret_cast<const uint32_t*>(&v[i >> 1][1][i & 1]);
#pragma unroll
            for (int c = 0; c < 8; c++) dst[((i & 1) * 8 + c) * (SD_U / 4) + (b * 2 + (i >> 1)) * 16] = __byte_perm(lo[c >> 1], hi[c >> 1], (c & 1) ? 0x7632 : 0x5410);
        }
    }
    asm volatile("bar.arrive 1, 384;" ::: "memory");
}

constexpr int WOC = DM / 3;
constexpr int TBUF = 5 * DH * 16;
constexpr int XBUF = SEG * DM * 2;
constexpr int SM_BAR = 0;
constexpr int B_SB = 0, B_VX = 16, B_XT = 32, B_XF = 144, B_W = 64, B_E = 136;
constexpr int SM_SC = 256;
constexpr int SM_F = SM_SC + 1280;
constexpr int SM_VM = SM_F + 2048;
constexpr int SM_S = SM_VM + 2048;
constexpr int SM_O = SM_S + 2560;
constexpr int SM_M = SM_O + 2048;
constexpr int SM_WS = 19456;
constexpr int SM_T = SM_WS + 49152;
constexpr int SM_VX = SM_T + 4 * TBUF;
constexpr int SM_X = SM_VX + 2 * 8192;
constexpr int SM_X01 = SM_WS + DM * DH * 2;
__host__ __device__ constexpr int x01_off(int b) { return b < 2 ? 1024 + b * 9216 : SM_X01 + (b == 2 ? 6 : b - 3) * 9216; }
__host__ __device__ constexpr int x23_off(int b) { return b < 3 ? SM_WS + 7 * 16384 + b * 8192 : x01_off(b - 3); }
constexpr int CH_SMEM = SM_X01 + 8 * 8192;
static_assert(SM_M + DM * 16 <= SM_WS && SM_X + 13 * 8192 <= CH_SMEM && NS <= 10 && CH_SMEM <= 232448 && SM_X % 1024 == 0 && SM_X01 % 1024 == 0 && 1024 + 2 * 9216 <= SM_WS, "smem");
__device__ __forceinline__ uint32_t clock32() { uint32_t t; asm volatile("mov.u32 %0, %%clock;" : "=r"(t) :: "memory"); return t; }

__device__ __forceinline__ uint32_t mapa(uint32_t a, uint32_t rank) {
    uint32_t r; asm volatile("mapa.shared::cluster.u32 %0, %1, %2;" : "=r"(r) : "r"(a), "r"(rank)); return r;
}
__device__ __forceinline__ void st_async32(uint32_t addr, uint32_t v, uint32_t mbar) {
    asm volatile("st.async.weak.shared::cluster.mbarrier::complete_tx::bytes.b32 [%0], %1, [%2];" :: "r"(addr), "r"(v), "r"(mbar) : "memory");
}
__device__ __forceinline__ void mbar_init(uint32_t bar, uint32_t cnt) {
    asm volatile("mbarrier.init.shared::cta.b64 [%0], %1;" :: "r"(bar), "r"(cnt) : "memory");
}
__device__ __forceinline__ void mbar_expect(uint32_t bar, uint32_t bytes) {
    asm volatile("mbarrier.arrive.expect_tx.shared::cta.b64 _, [%0], %1;" :: "r"(bar), "r"(bytes) : "memory");
}
__device__ __forceinline__ void mbar_wait(uint32_t bar, uint32_t parity) {
    unsigned it = 0;
    uint32_t ok;
    do {
        ++it;
        asm volatile("{\n.reg .pred p;\nmbarrier.try_wait.parity.shared::cta.b64 p, [%1], %2;\nselp.u32 %0, 1, 0, p;\n}" : "=r"(ok) : "r"(bar), "r"(parity) : "memory");
    } while ((ok == 0u) & (it < SPIN_LIMIT));
}
__device__ __forceinline__ void mbar_wait_fast(uint32_t bar, uint32_t parity) {
    mbar_wait(bar, parity);
}
__device__ __forceinline__ void mbar_wait_long(uint32_t bar, uint32_t parity) {
    unsigned it = 0;
    while (true) {
        uint32_t ok;
        asm volatile("{\n.reg .pred p;\nmbarrier.try_wait.parity.shared::cta.b64 p, [%1], %2, %3;\nselp.u32 %0, 1, 0, p;\n}"
                     : "=r"(ok) : "r"(bar), "r"(parity), "r"(20000u) : "memory");
        if (ok || ++it >= SPIN_LIMIT) break;
    }
}
__device__ __forceinline__ bool mbar_test(uint32_t bar, uint32_t parity) {
    uint32_t ok;
    asm volatile("{\n.reg .pred p;\nmbarrier.test_wait.parity.shared::cta.b64 p, [%1], %2;\nselp.u32 %0, 1, 0, p;\n}" : "=r"(ok) : "r"(bar), "r"(parity) : "memory");
    return ok != 0u;
}
__device__ __forceinline__ uint64_t policy_evict_first() {
    uint64_t pol; asm volatile("createpolicy.fractional.L2::evict_first.b64 %0, 1.0;" : "=l"(pol)); return pol;
}
__device__ __forceinline__ void cluster_sync_all() {
    asm volatile("barrier.cluster.arrive.release.aligned;\nbarrier.cluster.wait.acquire.aligned;" ::: "memory");
}
__device__ __forceinline__ uint4 ld_vol_u4(const uint4* p) {
    uint4 v; asm volatile(LDV4 : "=r"(v.x), "=r"(v.y), "=r"(v.z), "=r"(v.w) : "l"(p) : "memory"); return v;
}
__device__ __forceinline__ void ld_vol_u4_p(uint4& v, const uint4* p, uint32_t pred) {
    asm volatile("{\n.reg .pred p;\nsetp.ne.u32 p, %5, 0;\n@p " LDV4 "\n}"
                 : "+r"(v.x), "+r"(v.y), "+r"(v.z), "+r"(v.w) : "l"(p), "r"(pred) : "memory");
}
__device__ __forceinline__ void st_vol_u4(uint4* p, uint4 v) {
    asm volatile(STV4 :: "l"(p), "r"(v.x), "r"(v.y), "r"(v.z), "r"(v.w) : "memory");
}
__device__ __forceinline__ void mma_bf16_r(float (&d)[4], uint32_t a0, uint32_t a1, uint32_t a2, uint32_t a3, uint32_t b0, uint32_t b1) {
    asm volatile("mma.sync.aligned.m16n8k16.row.col.f32.bf16.bf16.f32 {%0,%1,%2,%3}, {%4,%5,%6,%7}, {%8,%9}, {%0,%1,%2,%3};"
                 : "+f"(d[0]), "+f"(d[1]), "+f"(d[2]), "+f"(d[3])
                 : "r"(a0), "r"(a1), "r"(a2), "r"(a3), "r"(b0), "r"(b1));
}

__device__ __forceinline__ uint64_t smem_desc(uint32_t addr, uint32_t lbo, uint32_t sbo) {
    return (uint64_t)((addr & 0x3FFFF) >> 4) | ((uint64_t)(lbo >> 4) << 16) | ((uint64_t)(sbo >> 4) << 32);
}
__device__ __forceinline__ void wg_fence() { asm volatile("wgmma.fence.sync.aligned;" ::: "memory"); }
__device__ __forceinline__ void wg_commit() { asm volatile("wgmma.commit_group.sync.aligned;" ::: "memory"); }
__device__ __forceinline__ void wg_wait0() { asm volatile("wgmma.wait_group.sync.aligned 0;" ::: "memory"); }
__device__ __forceinline__ void fence_async() { asm volatile("fence.proxy.async.shared::cta;" ::: "memory"); }
__device__ __forceinline__ void wgmma_n64_ss(float (&d)[32], uint64_t adesc, uint64_t bdesc) {
    asm volatile("{\n.reg .pred p;\nsetp.eq.b32 p, 0, 0;\n"
                 "wgmma.mma_async.sync.aligned.m64n64k16.f32.bf16.bf16 {%0,%1,%2,%3,%4,%5,%6,%7,%8,%9,%10,%11,%12,%13,%14,%15,%16,%17,%18,%19,%20,%21,%22,%23,%24,%25,%26,%27,%28,%29,%30,%31}, %32, %33, p, 1, 1, 1, 0;\n}"
                 : "+f"(d[0]), "+f"(d[1]), "+f"(d[2]), "+f"(d[3]), "+f"(d[4]), "+f"(d[5]), "+f"(d[6]), "+f"(d[7]), "+f"(d[8]), "+f"(d[9]), "+f"(d[10]), "+f"(d[11]), "+f"(d[12]), "+f"(d[13]), "+f"(d[14]), "+f"(d[15]), "+f"(d[16]), "+f"(d[17]), "+f"(d[18]), "+f"(d[19]), "+f"(d[20]), "+f"(d[21]), "+f"(d[22]), "+f"(d[23]), "+f"(d[24]), "+f"(d[25]), "+f"(d[26]), "+f"(d[27]), "+f"(d[28]), "+f"(d[29]), "+f"(d[30]), "+f"(d[31])
                 : "l"(adesc), "l"(bdesc));
}
__device__ __forceinline__ void wgmma_n72_ss(float (&d)[36], uint64_t adesc, uint64_t bdesc) {
    asm volatile("{\n.reg .pred p;\nsetp.eq.b32 p, 0, 0;\n"
                 "wgmma.mma_async.sync.aligned.m64n72k16.f32.bf16.bf16 {%0,%1,%2,%3,%4,%5,%6,%7,%8,%9,%10,%11,%12,%13,%14,%15,%16,%17,%18,%19,%20,%21,%22,%23,%24,%25,%26,%27,%28,%29,%30,%31,%32,%33,%34,%35}, %36, %37, p, 1, 1, 1, 0;\n}"
                 : "+f"(d[0]), "+f"(d[1]), "+f"(d[2]), "+f"(d[3]), "+f"(d[4]), "+f"(d[5]), "+f"(d[6]), "+f"(d[7]), "+f"(d[8]), "+f"(d[9]), "+f"(d[10]), "+f"(d[11]), "+f"(d[12]), "+f"(d[13]), "+f"(d[14]), "+f"(d[15]), "+f"(d[16]), "+f"(d[17]), "+f"(d[18]), "+f"(d[19]), "+f"(d[20]), "+f"(d[21]), "+f"(d[22]), "+f"(d[23]), "+f"(d[24]), "+f"(d[25]), "+f"(d[26]), "+f"(d[27]), "+f"(d[28]), "+f"(d[29]), "+f"(d[30]), "+f"(d[31]), "+f"(d[32]), "+f"(d[33]), "+f"(d[34]), "+f"(d[35])
                 : "l"(adesc), "l"(bdesc));
}
__device__ __forceinline__ void tma_2d(uint32_t dst, const CUtensorMap* tm, int c0, int c1, uint32_t mbar) {
    asm volatile("cp.async.bulk.tensor.2d.shared::cluster.global.tile.mbarrier::complete_tx::bytes [%0], [%1, {%2, %3}], [%4];"
                 :: "r"(dst), "l"(tm), "r"(c0), "r"(c1), "r"(mbar) : "memory");
}

__device__ __forceinline__ void bulk_g2s(uint32_t dst, const void* src, uint32_t bytes, uint32_t mbar) {
    asm volatile("cp.async.bulk.shared::cluster.global.mbarrier::complete_tx::bytes [%0], [%1], %2, [%3];"
                 :: "r"(dst), "l"(src), "r"(bytes), "r"(mbar) : "memory");
}
__device__ __forceinline__ void bulk_g2s_h(uint32_t dst, const void* src, uint32_t bytes, uint32_t mbar, uint64_t pol) {
    asm volatile("cp.async.bulk.shared::cluster.global.mbarrier::complete_tx::bytes.L2::cache_hint [%0], [%1], %2, [%3], %4;"
                 :: "r"(dst), "l"(src), "r"(bytes), "r"(mbar), "l"(pol) : "memory");
}
__device__ __forceinline__ void tma_2d_mc(uint32_t dst, const CUtensorMap* tm, int c0, int c1, uint32_t mbar) {
    asm volatile("cp.async.bulk.tensor.2d.shared::cluster.global.tile.mbarrier::complete_tx::bytes.multicast::cluster [%0], [%1, {%2, %3}], [%4], %5;"
                 :: "r"(dst), "l"(tm), "r"(c0), "r"(c1), "r"(mbar), "h"((unsigned short)7) : "memory");
}
__device__ __forceinline__ void bulk_s2s(uint32_t dst, uint32_t src, uint32_t bytes, uint32_t mbar) {
    asm volatile("cp.async.bulk.shared::cluster.shared::cta.mbarrier::complete_tx::bytes [%0], [%1], %2, [%3];"
                 :: "r"(dst), "r"(src), "r"(bytes), "r"(mbar) : "memory");
}
__device__ __forceinline__ void wgmma_n40_ss(float (&d)[20], uint64_t adesc, uint64_t bdesc, int scale_d) {
    asm volatile("{\n.reg .pred p;\nsetp.ne.b32 p, %22, 0;\n"
                 "wgmma.mma_async.sync.aligned.m64n40k16.f32.bf16.bf16 {%0,%1,%2,%3,%4,%5,%6,%7,%8,%9,%10,%11,%12,%13,%14,%15,%16,%17,%18,%19}, %20, %21, p, 1, 1, 1, 1;\n}"
                 : "+f"(d[0]), "+f"(d[1]), "+f"(d[2]), "+f"(d[3]), "+f"(d[4]), "+f"(d[5]), "+f"(d[6]), "+f"(d[7]),
                   "+f"(d[8]), "+f"(d[9]), "+f"(d[10]), "+f"(d[11]), "+f"(d[12]), "+f"(d[13]), "+f"(d[14]), "+f"(d[15]),
                   "+f"(d[16]), "+f"(d[17]), "+f"(d[18]), "+f"(d[19])
                 : "l"(adesc), "l"(bdesc), "r"(scale_d));
}
__device__ __forceinline__ void wgmma_n64_z(float (&d)[32], const uint32_t (&a)[4], uint64_t bdesc) {
    asm volatile("{\n.reg .pred p;\nsetp.ne.b32 p, 0, 0;\n"
                 "wgmma.mma_async.sync.aligned.m64n64k16.f32.bf16.bf16 {%0,%1,%2,%3,%4,%5,%6,%7,%8,%9,%10,%11,%12,%13,%14,%15,%16,%17,%18,%19,%20,%21,%22,%23,%24,%25,%26,%27,%28,%29,%30,%31}, {%32,%33,%34,%35}, %36, p, 1, 1, 0;\n}"
                 : "=f"(d[0]), "=f"(d[1]), "=f"(d[2]), "=f"(d[3]), "=f"(d[4]), "=f"(d[5]), "=f"(d[6]), "=f"(d[7]),
                   "=f"(d[8]), "=f"(d[9]), "=f"(d[10]), "=f"(d[11]), "=f"(d[12]), "=f"(d[13]), "=f"(d[14]), "=f"(d[15]),
                   "=f"(d[16]), "=f"(d[17]), "=f"(d[18]), "=f"(d[19]), "=f"(d[20]), "=f"(d[21]), "=f"(d[22]), "=f"(d[23]),
                   "=f"(d[24]), "=f"(d[25]), "=f"(d[26]), "=f"(d[27]), "=f"(d[28]), "=f"(d[29]), "=f"(d[30]), "=f"(d[31])
                 : "r"(a[0]), "r"(a[1]), "r"(a[2]), "r"(a[3]), "l"(bdesc));
}
__device__ __forceinline__ void wgmma_n64(float (&d)[32], const uint32_t (&a)[4], uint64_t bdesc, int scale_d) {
    asm volatile("{\n.reg .pred p;\nsetp.ne.b32 p, %37, 0;\n"
                 "wgmma.mma_async.sync.aligned.m64n64k16.f32.bf16.bf16 {%0,%1,%2,%3,%4,%5,%6,%7,%8,%9,%10,%11,%12,%13,%14,%15,%16,%17,%18,%19,%20,%21,%22,%23,%24,%25,%26,%27,%28,%29,%30,%31}, {%32,%33,%34,%35}, %36, p, 1, 1, 0;\n}"
                 : "+f"(d[0]), "+f"(d[1]), "+f"(d[2]), "+f"(d[3]), "+f"(d[4]), "+f"(d[5]), "+f"(d[6]), "+f"(d[7]),
                   "+f"(d[8]), "+f"(d[9]), "+f"(d[10]), "+f"(d[11]), "+f"(d[12]), "+f"(d[13]), "+f"(d[14]), "+f"(d[15]),
                   "+f"(d[16]), "+f"(d[17]), "+f"(d[18]), "+f"(d[19]), "+f"(d[20]), "+f"(d[21]), "+f"(d[22]), "+f"(d[23]),
                   "+f"(d[24]), "+f"(d[25]), "+f"(d[26]), "+f"(d[27]), "+f"(d[28]), "+f"(d[29]), "+f"(d[30]), "+f"(d[31])
                 : "r"(a[0]), "r"(a[1]), "r"(a[2]), "r"(a[3]), "l"(bdesc), "r"(scale_d));
}

constexpr int SB_FULL = 0, SB_EMPTY = 64, SB_QKF = 128, SB_VF = 144, SB_QKE = 160, SB_VE = 176, SB_OF = 192, SB_WO = 208, SB_TICK = 216, SB_SEEN = 224, SB_FI = 232, SB_REQ = 240;
constexpr int AT_0 = 256, AT_ST = 10240 + 2 * 9216;
constexpr int FS_A = 58368;
constexpr int FS_P = FS_A + 131072;
constexpr int FS_I = FS_P + 16384;
constexpr int FS_O = FS_I + 12288;
constexpr int FS_Z = FS_O + 12288, FS_G = AT_0 + 2 * AT_ST;
constexpr int SIDE_SMEM = FS_Z + 2048;
static_assert(SIDE_SMEM <= 232448 && FS_G + 128 <= FS_A && FS_A + SD_SMEM <= SIDE_SMEM, "smem");

__device__ __forceinline__ void wg_wait1() { asm volatile("wgmma.wait_group.sync.aligned 1;" ::: "memory"); }
__device__ __forceinline__ void mbar_arrive(uint32_t bar) { asm volatile("mbarrier.arrive.shared::cta.b64 _, [%0];" :: "r"(bar) : "memory"); }
__device__ __forceinline__ void wait_cnt_rlx(const unsigned* p, unsigned target, bool urgent) {
    unsigned it = 0, v;
    while (true) {
        asm volatile("ld.relaxed.gpu.global.u32 %0, [%1];" : "=r"(v) : "l"(p) : "memory");
        if ((int)(v - target) >= 0 || ++it >= SPIN_LIMIT) break;
        if (!urgent) __nanosleep(RLX_SLEEP);
    }
}

__device__ __forceinline__ float xrow_softmax(float (&sc)[20], uint32_t (&p)[5], int wq, int lane) {
    constexpr float EC = (float)(1.4426950408889634 * 0.08838834764831845);
    const int lim = 8 * wq + (lane >> 2) - 2 * (lane & 3);
    float mx = fmaxf(sc[0], sc[1]);
#pragma unroll
    for (int j = 1; j < 5; j++) {
        sc[4 * j] = 8 * j - 8 > lim ? -INFINITY : sc[4 * j];
        sc[4 * j + 1] = 8 * j - 7 > lim ? -INFINITY : sc[4 * j + 1];
    }
    mx = fmaxf(fmaxf(mx, fmaxf(fmaxf(sc[4], sc[5]), fmaxf(sc[8], sc[9]))), fmaxf(fmaxf(sc[12], sc[13]), fmaxf(sc[16], sc[17])));
    {
        const float m1 = __shfl_xor_sync(0xffffffffu, mx, 1), m2 = __shfl_xor_sync(0xffffffffu, mx, 2), m3 = __shfl_xor_sync(0xffffffffu, mx, 3);
        mx = fmaxf(fmaxf(mx, m1), fmaxf(m2, m3)) * EC;
    }
    float sum = 0.f;
#pragma unroll
    for (int j = 0; j < 5; j++) {
        float e0, e1;
        asm("ex2.approx.ftz.f32 %0, %1;" : "=f"(e0) : "f"(fmaf(sc[4 * j], EC, -mx)));
        asm("ex2.approx.ftz.f32 %0, %1;" : "=f"(e1) : "f"(fmaf(sc[4 * j + 1], EC, -mx)));
        p[j] = pack_bf16(e0, e1);
        sum += e0 + e1;
    }
    return sum;
}
__device__ __forceinline__ float xrow_inv(float sum) {
    sum += __shfl_xor_sync(0xffffffffu, sum, 1);
    sum += __shfl_xor_sync(0xffffffffu, sum, 2);
    float r;
    asm("rcp.approx.ftz.f32 %0, %1;" : "=f"(r) : "f"(sum));
    return r;
}

__device__ __forceinline__ void stsm_x4(uint32_t addr, uint32_t r0, uint32_t r1, uint32_t r2, uint32_t r3) {
    asm volatile("stmatrix.sync.aligned.m8n8.x4.shared.b16 [%0], {%1,%2,%3,%4};" :: "r"(addr), "r"(r0), "r"(r1), "r"(r2), "r"(r3) : "memory");
}
__device__ __forceinline__ void xrow_pv(uint32_t (&ob)[16], const uint32_t (&p)[5], float psum, uint32_t vt) {
    float o[32];
    const uint64_t dv = smem_desc(vt, 2048, 128);
    uint32_t pa[6][4];
#pragma unroll
    for (int i = 0; i < 6; i++) {
        const int ks = i >> 1, hf = i & 1;
        pa[i][hf] = p[2 * ks]; pa[i][hf ^ 1] = 0u;
        pa[i][2 + hf] = ks < 2 ? p[ks < 2 ? 2 * ks + 1 : 0] : 0u; pa[i][3 - hf] = 0u;
    }
    wg_fence();
#pragma unroll
    for (int i = 0; i < 6; i++) { if (i == 0) wgmma_n64_z(o, pa[0], dv); else wgmma_n64(o, pa[i], dv + (uint64_t)((i & 1) * 64 + (i >> 1) * 256), 1); }
    wg_commit();
    const float inv = xrow_inv(psum);
    wg_wait0();
#pragma unroll
    for (int i = 0; i < 8; i++) { ob[i] = pack_bf16(o[4 * i] * inv, o[4 * i + 1] * inv); ob[8 + i] = pack_bf16(o[4 * i + 2] * inv, o[4 * i + 3] * inv); }
}
__device__ __forceinline__ uint32_t h2_to_bf2(uint32_t h) {
    uint32_t r;
    asm("{\n.reg .f16 l, h;\n.reg .f32 a, b;\nmov.b32 {l, h}, %1;\ncvt.f32.f16 a, l;\ncvt.f32.f16 b, h;\ncvt.rn.bf16x2.f32 %0, b, a;\n}" : "=r"(r) : "r"(h));
    return r;
}
__device__ __forceinline__ uint32_t max_abs2(uint32_t a, uint32_t b) { uint32_t r; asm("max.NaN.xorsign.abs.bf16x2 %0, %1, %2;" : "=r"(r) : "r"(a), "r"(b)); return r; }
__device__ __forceinline__ uint32_t movm(uint32_t v) {
    uint32_t r; asm volatile("movmatrix.sync.aligned.m8n8.trans.b16 %0, %1;" : "=r"(r) : "r"(v)); return r;
}
__device__ __forceinline__ void bar_arrive(int id, int n) { asm volatile("bar.arrive %0, %1;" :: "r"(id), "r"(n) : "memory"); }
__device__ __forceinline__ void lds64(uint32_t& a, uint32_t& b, uint32_t addr) {
    asm volatile("ld.shared.v2.u32 {%0,%1}, [%2];" : "=r"(a), "=r"(b) : "r"(addr) : "memory");
}
__device__ __forceinline__ void lds64f(float& a, float& b, uint32_t addr) {
    asm volatile("ld.shared.v2.f32 {%0,%1}, [%2];" : "=f"(a), "=f"(b) : "r"(addr) : "memory");
}
__device__ __forceinline__ void st_async64(uint32_t addr, uint32_t a, uint32_t b, uint32_t mbar) {
    asm volatile("st.async.weak.shared::cluster.mbarrier::complete_tx::bytes.v2.b32 [%0], {%1,%2}, [%3];" :: "r"(addr), "r"(a), "r"(b), "r"(mbar) : "memory");
}
__device__ __forceinline__ void mma_z(float (&d)[4], const uint32_t (&a)[4], uint32_t b0, uint32_t b1) {
    asm volatile("mma.sync.aligned.m16n8k16.row.col.f32.bf16.bf16.f32 {%0,%1,%2,%3}, {%4,%5,%6,%7}, {%8,%9}, {%10,%10,%10,%10};"
                 : "=f"(d[0]), "=f"(d[1]), "=f"(d[2]), "=f"(d[3])
                 : "r"(a[0]), "r"(a[1]), "r"(a[2]), "r"(a[3]), "r"(b0), "r"(b1), "f"(0.f));
}
__device__ __forceinline__ void mma_k8(float (&d)[4], uint32_t a0, uint32_t a1, uint32_t b) {
    asm volatile("mma.sync.aligned.m16n8k8.row.col.f32.bf16.bf16.f32 {%0,%1,%2,%3}, {%4,%5}, {%6}, {%0,%1,%2,%3};"
                 : "+f"(d[0]), "+f"(d[1]), "+f"(d[2]), "+f"(d[3]) : "r"(a0), "r"(a1), "r"(b));
}
__global__ void __launch_bounds__(512, 1) k_side(const __grid_constant__ CUtensorMap tmo, const bf16* __restrict__ x, const bf16* __restrict__ logA, const bf16* __restrict__ Aim,
                                                 const bf16* __restrict__ Cre, const bf16* __restrict__ Cim, const bf16* __restrict__ logdt,
                                                 const bf16* __restrict__ Wo, const bf16* __restrict__ dskip, const bf16* __restrict__ gw,
                                                 bf16* __restrict__ out) {
    extern __shared__ __align__(1024) unsigned char smem_raw[];
    const uint32_t sbase = smem_u32(smem_raw);
    const int tid = threadIdx.x, warp = __shfl_sync(0xffffffffu, tid >> 5, 0), lane = tid & 31, cta = blockIdx.x;
    const int cb = cta >> 2, kq = cta & 3;
    if (tid == 0) {
        for (int i = 0; i < 8; i++) { mbar_init(sbase + SB_FULL + 8 * i, 1); mbar_init(sbase + SB_EMPTY + 8 * i, 4); }
        for (int i = 0; i < 2; i++) {
            mbar_init(sbase + SB_QKF + 8 * i, 1); mbar_init(sbase + SB_VF + 8 * i, 1); mbar_init(sbase + SB_QKE + 8 * i, 4);
            mbar_init(sbase + SB_VE + 8 * i, 1); mbar_init(sbase + SB_OF + 8 * i, 4);
        }
        mbar_init(sbase + SB_WO, 1);
        mbar_init(sbase + SB_FI, 1);
        mbar_init(sbase + SB_REQ, 4);
        *reinterpret_cast<uint2*>(smem_raw + SB_TICK) = make_uint2(0u, 0u);
        *reinterpret_cast<uint32_t*>(smem_raw + SB_SEEN) = 0u;
        asm volatile("fence.mbarrier_init.release.cluster;" ::: "memory");
    }
    TS3(0);
    unsigned ep;
    asm volatile("ld.volatile.global.u32 %0, [%1];" : "=r"(ep) : "l"(&g_epoch) : "memory");
    ep += 1u;
    asm volatile("fence.proxy.async;" ::: "memory");
    __syncthreads();
    if (warp >= 12) {
      asm volatile("setmaxnreg.dec.sync.aligned.u32 40;");
      if (SIDE_WAIT > 0) __nanosleep(SIDE_WAIT);
      {
        uint32_t gwv[9];
#pragma unroll
        for (int i = 0; i < 9; i++) gwv[i] = reinterpret_cast<const uint32_t*>(gw)[lane + 32 * i];
#pragma unroll 1
        for (int i = 0; i < 8; i++) {
            uint32_t xv[2][9];
            float sm[2];
#pragma unroll
            for (int j = 0; j < 2; j++) {
                const int t = min(cta * 57 + 8 * i + 4 * j + warp - 12, S_LEN - 1);
#pragma unroll
                for (int k = 0; k < 9; k++) xv[j][k] = reinterpret_cast<const uint32_t*>(x + t * DM)[lane + 32 * k];
            }
#pragma unroll
            for (int j = 0; j < 2; j++) {
                sm[j] = 0.f;
#pragma unroll
                for (int k = 0; k < 9; k++) {
                    const uint32_t pr = bf2_mul(xv[j][k], gwv[k]);
                    sm[j] += __uint_as_float(pr << 16) + __uint_as_float(pr & 0xffff0000u);
                }
            }
            float v = (lane < 16 ? sm[0] : sm[1]) + __shfl_xor_sync(0xffffffffu, lane < 16 ? sm[1] : sm[0], 16);
#pragma unroll
            for (int o = 8; o; o >>= 1) v += __shfl_xor_sync(0xffffffffu, v, o);
            const float gv = 1.f / (1.f + expf(-bf16r(v)));
            const int tt = 8 * i + 4 * (lane >> 4) + warp - 12;
            if ((lane & 15) == 0 && tt < 57 && cta * 57 + tt < S_LEN) g_gate[cta * 57 + tt] = __float2bfloat16_rn(gv);
        }
        named_bar(2, 128);
        if (tid == 480) {
            __threadfence();
            asm volatile("red.relaxed.gpu.global.add.u32 [%0], 1;" :: "l"(&g_gcnt[0]) : "memory");
        }
        __syncwarp();
      }
      if (warp == 12 || warp == 15) {
        named_bar(3, 320);
        if (tid == 384) {
            fence_async();
            mbar_expect(sbase + SB_WO, 131072);
#pragma unroll 1
            for (int i = 0; i < 8; i++) {
                gate(sbase + SB_TICK);
                tma_2d(sbase + FS_A + i * 16384, &tmo, cb * 64, kq * 1024 + i * 128, sbase + SB_WO);
                __nanosleep(150);
            }
            TSS(17, 2);
        }
        if (tid == 480) {
            __threadfence();
            asm volatile("red.relaxed.gpu.global.add.u32 [%0], 1;" :: "l"(&g_gcnt[32]) : "memory");
            TSS(17, 3);
        }
        __syncwarp();
        named_bar(7, 320);
        if (lane == 0) {
            const int pi = warp == 12 ? 0 : 1, kb = 2 * kq + pi;
            fence_async();
            for (int pr = 0; pr < NSEG / 2; pr++) {
                const bool gon = pr < NSEG / 2 - UNGATE_G;
                wait_cnt_rlx(&g_prog[pr * 8 + kb], 8u * ep, pr >= NSEG / 2 - 2);
                if (pi == 0) asm volatile("st.volatile.shared.u32 [%0], %1;" :: "r"(sbase + SB_SEEN), "r"(pr + 1) : "memory");
                if (pr >= 30 && pi == 0) TSS(4 + pr - 30, 0);
                if (pr == 31) TS3P(26);
                if (pr == 30) TS3P(1);
#pragma unroll
                for (int j = 0; j < 4; j++) {
                    const int st = 4 * pi + j;
                    mbar_wait_long(sbase + SB_EMPTY + 8 * st, ((uint32_t)pr & 1u) ^ 1u);
                    mbar_expect(sbase + SB_FULL + 8 * st, X_OXSZ);
                    if (gon) gate(sbase + SB_TICK);
                    bulk_g2s(sbase + FS_A + st * 16384, g_ox + ((size_t)(pr * NH + 4 * kb + j)) * 8192, X_OXSZ, sbase + SB_FULL + 8 * st);
                }
            }
        }
        __syncwarp();
      } else if (warp == 13) {
        if (lane == 0) {
            const uint64_t pol = policy_evict_first();
            bool next_ok = false;
            for (int seg = 0; seg < NATT; seg++) {
                const uint32_t st = seg & 1, ph = (uint32_t)(seg >> 1) & 1u, ab = sbase + AT_0 + st * AT_ST;
                if (!next_ok) {
                    const unsigned* fp = &g_flag[(cta & (NH - 1)) * NSEG + seg];
                    unsigned it = 0, v0, v1;
                    while (true) {
                        asm volatile("ld.relaxed.gpu.global.u32 %0, [%1];" : "=r"(v0) : "l"(fp) : "memory");
                        asm volatile("ld.relaxed.gpu.global.u32 %0, [%1+4];" : "=r"(v1) : "l"(fp) : "memory");
                        read_tick(sbase + SB_TICK);
                        if ((int)(v0 - 3u * ep) >= 0 || ++it >= SPIN_LIMIT) break;
                        if (seg < NSEG - UNGATE || cta >= NH) { __nanosleep(RLX_SLEEP); if (GATE_POLL) gate(sbase + SB_TICK, GP_A, GP_B); }
                    }
                    next_ok = (int)(v1 - 3u * ep) >= 0;
                } else next_ok = false;
                if (cta < NH) {
                    TSA(seg, 0);
                    mbar_wait_long(sbase + SB_QKE + 8 * st, ph ^ 1u);
                    TSA(seg, 1);
                    mbar_expect(sbase + SB_QKF + 8 * st, 2 * 9216);
                    if (seg < NSEG - UNGATE) gate(sbase + SB_TICK, GL_A, GL_B);
                    TSA(seg, 2);
                    bulk_g2s_h(ab + 10240, &g_qkv[seg][cta][0][1024], 9216, sbase + SB_QKF + 8 * st, pol);
                    bulk_g2s_h(ab + 10240 + 9216, &g_qkv[seg][cta][1][1024], 9216, sbase + SB_QKF + 8 * st, pol);
                    mbar_wait_long(sbase + SB_VE + 8 * st, ph ^ 1u);
                    mbar_expect(sbase + SB_VF + 8 * st, 10240);
                    if (seg < NSEG - UNGATE) gate(sbase + SB_TICK, GL_A, GL_B);
                    TSA(seg, 3);
                    bulk_g2s_h(ab, &g_qkv[seg][cta][2][0], 10240, sbase + SB_VF + 8 * st, pol);
                }
            }
        }
        __syncwarp();
      } else if (warp == 14) {
        if (lane == 0) {
            int seg = cta < NH ? 0 : NATT, p = 0;
            unsigned it = 0;
            while ((seg < NATT || p < NSEG / 2 - 1) && ++it < 16 * SPIN_LIMIT) {
                if (p < NSEG / 2 - 1 && mbar_test(sbase + SB_REQ, (uint32_t)p & 1u)) {
                    if (p == 0) { wait_cnt(&g_gcnt[32], SD_NCTA * ep); asm volatile("fence.proxy.async;" ::: "memory"); }
                    mbar_expect(sbase + SB_FI, (p < NSEG / 2 - 2 ? 12288 : 2048 + 32) + 2048 + 32);
                    if (GATE_F && p < NSEG / 2 - UNGATE_G - 1) gate(sbase + SB_TICK);
                    if (p < NSEG / 2 - 2) bulk_g2s(sbase + FS_I, &g_fp[p & 7][cta][0][0], 12288, sbase + SB_FI);
                    else {
                        bulk_g2s(sbase + FS_I, g_y + ((p * 4 + 4 + kq) * DM + cb * 64) * 16, 2048, sbase + SB_FI);
                        bulk_g2s(sbase + FS_G + 32, g_gate + p * 64 + 64 + kq * 16, 32, sbase + SB_FI);
                    }
                    bulk_g2s(sbase + FS_Z, g_y + ((p * 4 + kq) * DM + cb * 64) * 16, 2048, sbase + SB_FI);
                    bulk_g2s(sbase + FS_G, g_gate + p * 64 + kq * 16, 32, sbase + SB_FI);
                    p++;
                } else if (seg < NATT && mbar_test(sbase + SB_OF + 8 * (seg & 1), (uint32_t)(seg >> 1) & 1u)) {
                    const uint32_t st = seg & 1, ab = sbase + AT_0 + st * AT_ST;
                    TSA(seg, 5);
                    if (seg < NSEG - UNGATE) gate(sbase + SB_TICK, GS_A, GS_B);
                    TSA(seg, 6);
                    unsigned char* dst = reinterpret_cast<unsigned char*>(g_ox) + ((size_t)((seg >> 1) * NH + cta)) * 16384 + (seg & 1) * 4096;
                    asm volatile("cp.async.bulk.global.shared::cta.bulk_group [%0], [%1], 4096;" :: "l"(dst), "r"(ab) : "memory");
                    asm volatile("cp.async.bulk.global.shared::cta.bulk_group [%0], [%1], 4096;" :: "l"(dst + 8192), "r"(ab + 4096) : "memory");
                    asm volatile("cp.async.bulk.commit_group;" ::: "memory");
                    asm volatile("cp.async.bulk.wait_group.read 0;" ::: "memory");
                    mbar_arrive(sbase + SB_VE + 8 * st);
                    asm volatile("cp.async.bulk.wait_group 0;" ::: "memory");
                    asm volatile("red.relaxed.gpu.global.add.u32 [%0], 1;" :: "l"(&g_prog[(seg >> 1) * 8 + (cta >> 2)]) : "memory");
                    TSA(seg, 7);
                    seg++;
                } else if (seg < NSEG - UNGATE) __nanosleep(W14_SLEEP);
            }
        }
        __syncwarp();
      }
    } else if (warp >= 8) {
        asm volatile("setmaxnreg.dec.sync.aligned.u32 88;");
        if (SIDE_WAIT > 0) __nanosleep(SIDE_WAIT);
        s4d_stage_u(smem_raw + FS_A, x, tid - 256);
        const int wq = warp - 8;
        for (int seg = 0; seg < (cta < NH ? NATT : 0); seg++) {
            const uint32_t st = seg & 1, ph = (uint32_t)(seg >> 1) & 1u, ab = sbase + AT_0 + st * AT_ST;
            float sc[20];
            if (seg < NSEG - UNGATE) mbar_wait_long(sbase + SB_QKF + 8 * st, ph); else mbar_wait(sbase + SB_QKF + 8 * st, ph);
            if (tid == 256) TSA(seg, 4);
            {
                const uint64_t da = smem_desc(ab + 10240 + 1024, 128, 1024), db = smem_desc(ab + 10240, 128, 2048);
                wg_fence();
#pragma unroll
                for (int ks = 0; ks < 8; ks++) wgmma_n40_ss(sc, da + (uint64_t)((ks >> 2) * 576 + (ks & 3) * 16), db + (uint64_t)((ks >> 2) * 576 + (ks & 3) * 16), ks > 0);
                wg_commit();
                wg_wait0();
            }
            if (lane == 0) mbar_arrive(sbase + SB_QKE + 8 * st);
            uint32_t p[5], ob[16];
            const float psum = xrow_softmax(sc, p, wq, lane);
            mbar_wait(sbase + SB_VF + 8 * st, ph);
            xrow_pv(ob, p, psum, ab);
            named_bar(6, 128);
#pragma unroll
            for (int i = 0; i < 4; i++) stsm_x4(ab + (i >> 1) * 4096 + wq * 1024 + (i & 1) * 512 + lane * 16, ob[4 * i], ob[4 * i + 1], ob[4 * i + 2], ob[4 * i + 3]);
            fence_async();
            __syncwarp();
            if (lane == 0) mbar_arrive(sbase + SB_OF + 8 * st);
        }
    } else {
        asm volatile("setmaxnreg.inc.sync.aligned.u32 192;");
        const int wg = warp >> 2, wq = warp & 3;
        s4d_phase(smem_raw + FS_A, x, logA, Aim, Cre, Cim, logdt, dskip, Wo + (size_t)((2 * kq + wg) * 512) * DM + cb * 64, ep, sbase + SB_TICK);
        TS3(2);
        if (lane == 0) TSS(16, warp);
        named_bar(3, 320);
        if (tid == 0) TSS(17, 0);
        uint32_t wa[32][4];
        mbar_wait_long(sbase + SB_WO, 0);
        if (tid == 0) TSS(17, 1);
        {
            const uint32_t a = sbase + FS_A + wg * 65536 + ((lane >> 4) * 8 + (lane & 7)) * 128 + (((wq * 2 + ((lane >> 3) & 1)) ^ (lane & 7)) << 4);
#pragma unroll
            for (int ks = 0; ks < 32; ks++) ldsm_x4_t(wa[ks], a + ks * 2048);
        }
        named_bar(7, 320);
        TS3(3);
        if (tid == 0) TSS(17, 4);
        auto product = [&](float (&acc)[32], int pr, const int wg) {
                if (pr + wg > 0 && (TURN31 || pr + wg < NSEG / 2)) named_bar(4 + wg, 256);
                const uint64_t db = smem_desc(sbase + FS_A + wg * 65536, 128, 1024);
                TSG(0);
#pragma unroll
                for (int j = 0; j < 4; j++) {
                    mbar_wait(sbase + SB_FULL + 8 * (4 * wg + j), (uint32_t)pr & 1u);
                    if (j == 0) TSG(1);
                    if (j == 3) TSG(2);
                    wg_fence();
#pragma unroll
                    for (int ks = 0; ks < 8; ks++) {
                        if ((j | ks) == 0) wgmma_n64_z(acc, wa[0], db);
                        else wgmma_n64(acc, wa[8 * j + ks], db + (uint64_t)(j * 1024 + (ks >> 2) * 512 + (ks & 3) * 16), 1);
                    }
                    wg_commit();
                    if (j == 3 && pr + (TURN31 ? wg : 1) < NSEG / 2) bar_arrive(4 + (wg ^ 1), 256);
                    if (j > 0) { wg_wait1(); if (lane == 0) mbar_arrive(sbase + SB_EMPTY + 8 * (4 * wg + j - 1)); }
                }
                wg_wait0();
                if (pr == 31) TS3W(27);
                TSG(3);
                if (lane == 0) mbar_arrive(sbase + SB_EMPTY + 8 * (4 * wg + 3));
        };
        if (wg == 1) {
            for (int pr = 0; pr < NSEG / 2; pr++) {
                uint32_t t16 = (uint32_t)(wq * 32 + lane) * 16u;
                asm volatile("" : "+r"(t16));
                float acc[32];
                product(acc, pr, 1);
                    uint32_t tag = ((uint32_t)(pr >> 3) & 1u) ^ 1u;
                    tag = __shfl_sync(0xffffffffu, tag, lane);
                    if (GATE_S && pr < NSEG / 2 - UNGATE_G) gate(sbase + SB_TICK);
                    named_bar(8, 256);
                    unsigned char* dst = reinterpret_cast<unsigned char*>(&g_fp[pr & 7][4 * cb][2 * kq - 2][0]) + t16;
                    const uint32_t own = sbase + FS_O + (pr % 3) * 4096 + t16;
#pragma unroll
                    for (int q = 0; q < 8; q++) {
                        float4 p;
                        asm volatile("ld.shared.v4.f32 {%0,%1,%2,%3}, [%4];" : "=f"(p.x), "=f"(p.y), "=f"(p.z), "=f"(p.w) : "r"(sbase + FS_P + t16 + q * 2048) : "memory");
                        acc[4 * q] = __uint_as_float((__float_as_uint(acc[4 * q] + p.x) & ~1u) | tag); acc[4 * q + 1] = __uint_as_float((__float_as_uint(acc[4 * q + 1] + p.y) & ~1u) | tag);
                        acc[4 * q + 2] = __uint_as_float((__float_as_uint(acc[4 * q + 2] + p.z) & ~1u) | tag); acc[4 * q + 3] = __uint_as_float((__float_as_uint(acc[4 * q + 3] + p.w) & ~1u) | tag);
                    }
#pragma unroll
                    for (int q = 0; q < 8; q++) {
                        asm volatile("{\n.reg .pred p;\nsetp.ne.s32 p, %5, %6;\n@p st.volatile.global.v4.f32 [%0], {%1,%2,%3,%4};\n@!p st.shared.v4.f32 [%7], {%1,%2,%3,%4};\n}"
                                     :: "l"(dst + (q & 1) * 2048), "f"(acc[4 * q]), "f"(acc[4 * q + 1]), "f"(acc[4 * q + 2]), "f"(acc[4 * q + 3]), "r"(q >> 1), "r"(kq),
                                        "r"(own + (q & 1) * 2048) : "memory");
                        if (q & 1) dst += (q >> 1) == kq ? 12288 + 4096 : 12288;
                    }
                    bar_arrive(9, 256);
                    if (pr == 31) TS3W(28);
                TSG(4);
            }
        } else {
          int nsync = 0;
          int np = 1, nf = 0, pr = 0, pf = -1;
          while (true) {
            uint32_t t16 = (uint32_t)(wq * 32 + lane) * 16u;
            asm volatile("" : "+r"(t16));
            if (pr < 0) {
                if (nsync <= pf) { named_bar(9, 256); nsync++; }
                if (lane == 0 && pf < NSEG / 2 - 1) mbar_arrive(sbase + SB_REQ);
            } else {
                float acc[32];
                product(acc, pr, 0);
                if (nsync < pr) { named_bar(9, 256); nsync++; }
#pragma unroll
                for (int q = 0; q < 8; q++)
                    asm volatile("st.shared.v4.f32 [%0], {%1,%2,%3,%4};" :: "r"(sbase + FS_P + t16 + q * 2048), "f"(acc[4 * q]), "f"(acc[4 * q + 1]), "f"(acc[4 * q + 2]), "f"(acc[4 * q + 3]) : "memory");
                bar_arrive(8, 256);
                TSG(4);
            }
            uint32_t w[4] = {0u, 0u, 0u, 0u};
            const int pc = pf;
            if (pf >= 0) {
                const uint32_t tag = ((uint32_t)(pf >> 3) & 1u) ^ 1u;
                uint4 v[8];
                unsigned n = 0;
                const bool last = pf == NSEG / 2 - 1;
                const uint4* src = reinterpret_cast<const uint4*>(reinterpret_cast<const unsigned char*>(&g_fp[pf & 7][cta][0][0]) + t16);
                if (pf >= NSEG / 2 - 2) {
#pragma unroll
                    for (int r = 0; r < 6; r++) v[r] = ld_vol_u4(src + r * 128);
                    mbar_wait(sbase + SB_FI, 0u);
                } else {
                    mbar_wait(sbase + SB_FI, (uint32_t)pf & 1u);
#pragma unroll
                    for (int r = 0; r < 6; r++)
                        asm volatile("ld.shared.v4.u32 {%0,%1,%2,%3}, [%4];" : "=r"(v[r].x), "=r"(v[r].y), "=r"(v[r].z), "=r"(v[r].w) : "r"(sbase + t16 + FS_I + r * 2048) : "memory");
                }
                while (true) {
                    uint32_t any = 0u;
#pragma unroll
                    for (int r = 0; r < 6; r++) {
                        uint32_t c0_, c1_;
                        asm("lop3.b32 %0, %1, %2, %3, 0x7e;" : "=r"(c0_) : "r"(v[r].x), "r"(v[r].y), "r"(tag));
                        asm("lop3.b32 %0, %1, %2, %3, 0x7e;" : "=r"(c1_) : "r"(v[r].z), "r"(v[r].w), "r"(tag));
                        asm("lop3.b32 %0, %1, %2, %3, 0xfe;" : "=r"(any) : "r"(any), "r"(c0_), "r"(c1_));
                    }
                    if (!__any_sync(0xffffffffu, (any & 1u) != 0u) || ++n >= SPIN_LIMIT) break;
                    if (pf < NSEG / 2 - 2) __nanosleep(200);
#pragma unroll
                    for (int r = 0; r < 6; r++) v[r] = ld_vol_u4(src + r * 128);
                }
                if (pf == 31) TS3(29);
                TSG(5);
#pragma unroll
                for (int r = 6; r < 8; r++)
                    asm volatile("ld.shared.v4.u32 {%0,%1,%2,%3}, [%4];" : "=r"(v[r].x), "=r"(v[r].y), "=r"(v[r].z), "=r"(v[r].w)
                                 : "r"(sbase + t16 + FS_O + (pf % 3) * 4096 + (r - 6) * 2048) : "memory");
                uint32_t zv[4], gg[2];
                ldsm_x4_t(zv, sbase + (last ? FS_I : FS_Z) + (wq * 16 + (lane & 15)) * 32 + (lane >> 4) * 16);
#pragma unroll
                for (int k = 0; k < 2; k++) gg[k] = __byte_perm(*reinterpret_cast<const volatile unsigned short*>(smem_raw + FS_G + (last ? 32 : 0) + k * 16 + (lane >> 2) * 2), 0u, 0x1010);
#define PQS(k, f) (((__uint_as_float(v[k].f) + __uint_as_float(v[2 + k].f)) + __uint_as_float(v[4 + k].f)) + __uint_as_float(v[6 + k].f))
#pragma unroll
                for (int k = 0; k < 2; k++) {
                    w[2 * k] = bf2_add(bf2_mul(gg[k], movm(pack_bf16(PQS(k, x), PQS(k, y)))), zv[2 * k]);
                    w[2 * k + 1] = bf2_add(bf2_mul(gg[k], movm(pack_bf16(PQS(k, z), PQS(k, w)))), zv[2 * k + 1]);
                }
#undef PQS
            }
            const bool more = nf < NSEG / 2;
            if (more) {
                uint32_t r;
                asm volatile("{\n.reg .pred p, q;\n.reg .b32 v;\nld.volatile.shared.u32 v, [%1];\nsetp.gt.s32 p, v, %2;\nbar.red.or.pred q, 10, 128, p;\nselp.u32 %0, 1, 0, q;\n}"
                             : "=r"(r) : "r"(sbase + SB_SEEN), "r"(np) : "memory");
                const bool dop = np < NSEG / 2 && (__shfl_sync(0xffffffffu, r, 0) != 0u || nf == np || nf >= NSEG / 2 - 2);
                TSG(6);
                pr = dop ? np++ : -1;
                pf = !dop || nf + (pr == NSEG / 2 - 1 ? 1 : 2) <= pr ? nf++ : -1;
                if (dop && pf >= 0 && lane == 0) mbar_arrive(sbase + SB_REQ);
            }
            if (pc >= 0) {
                unsigned char* op = reinterpret_cast<unsigned char*>(out) + (uint32_t)((pc * 64 + kq * 16 + (lane >> 2)) * DM + cb * 64 + wq * 16 + 2 * (lane & 3)) * 2u;
#pragma unroll
                for (int k = 0; k < 4; k++) *reinterpret_cast<uint32_t*>(op + (k >> 1) * (16 * DM) + (k & 1) * 16) = w[k];
                if ((pc & 1) == 0) TS3(4 + pc / 2);
                if (pc == 31) TS3(25);
            }
            if (!more) break;
          }
        }
        if (cta == 0 && tid == 0) asm volatile("red.relaxed.gpu.global.add.u32 [%0], 1;" :: "l"(&g_epoch) : "memory");
    }
    asm volatile("griddepcontrol.wait;" ::: "memory");
}

template <class F>
__device__ __forceinline__ uint32_t poll_mem(const uint4* src, uint32_t dst, uint32_t t0, F next) {
    uint4 v[6];
    unsigned it = 0;
#pragma unroll
    for (int j = 0; j < 6; j++) v[j] = make_uint4(0u, 0u, 0u, 0u);
    while (clock32() - t0 < POLL_DELAY) {}
    FS(12, 0);
    bool more;
#pragma unroll 1
    do {
        asm volatile("{\n.reg .pred p<6>;\n"
                     "setp.ne.u32 p0, %3, 0x5000;\nsetp.ne.u32 p1, %7, 0x5000;\nsetp.ne.u32 p2, %11, 0x5000;\n"
                     "setp.ne.u32 p3, %15, 0x5000;\nsetp.ne.u32 p4, %19, 0x5000;\nsetp.ne.u32 p5, %23, 0x5000;\n"
                     "@p0 ld.volatile.global.v4.u32 {%0,%1,%2,%3}, [%24];\n@p1 ld.volatile.global.v4.u32 {%4,%5,%6,%7}, [%24+4096];\n"
                     "@p2 ld.volatile.global.v4.u32 {%8,%9,%10,%11}, [%24+8192];\n@p3 ld.volatile.global.v4.u32 {%12,%13,%14,%15}, [%24+12288];\n"
                     "@p4 ld.volatile.global.v4.u32 {%16,%17,%18,%19}, [%24+16384];\n@p5 ld.volatile.global.v4.u32 {%20,%21,%22,%23}, [%24+20480];\n}"
                     : "+r"(v[0].x), "+r"(v[0].y), "+r"(v[0].z), "+r"(v[0].w), "+r"(v[1].x), "+r"(v[1].y), "+r"(v[1].z), "+r"(v[1].w),
                       "+r"(v[2].x), "+r"(v[2].y), "+r"(v[2].z), "+r"(v[2].w), "+r"(v[3].x), "+r"(v[3].y), "+r"(v[3].z), "+r"(v[3].w),
                       "+r"(v[4].x), "+r"(v[4].y), "+r"(v[4].z), "+r"(v[4].w), "+r"(v[5].x), "+r"(v[5].y), "+r"(v[5].z), "+r"(v[5].w)
                     : "l"(src) : "memory");
        stsm_x4(dst, h2_to_bf2(v[0].x), h2_to_bf2(v[0].y), h2_to_bf2(v[0].z), h2_to_bf2(v[1].x));
        stsm_x4(dst + 512, h2_to_bf2(v[1].y), h2_to_bf2(v[1].z), h2_to_bf2(v[2].x), h2_to_bf2(v[2].y));
        const uint32_t all = ((v[0].w & v[1].w) & (v[2].w & v[3].w)) & (v[4].w & v[5].w);
        more = __any_sync(0xffffffffu, (all & 0x5000u) != 0x5000u && ++it < SPIN_LIMIT);
        stsm_x4(dst + 1024, h2_to_bf2(v[2].z), h2_to_bf2(v[3].x), h2_to_bf2(v[3].y), h2_to_bf2(v[3].z));
        asm volatile("stmatrix.sync.aligned.m8n8.x2.shared.b16 [%0], {%1,%2};" :: "r"(dst + 1536), "r"(h2_to_bf2(v[4].x)), "r"(h2_to_bf2(v[4].y)) : "memory");
        stsm_x4(dst + 1792, h2_to_bf2(v[4].z), h2_to_bf2(v[5].x), h2_to_bf2(v[5].y), h2_to_bf2(v[5].z));
        asm volatile("{\n.reg .pred p;\nsetp.eq.u32 p, %0, 0;\n@p bar.sync 1, 384;\n}" :: "r"((uint32_t)more) : "memory");
    } while (more);
    next();
    FS(13, it);
    FS(14, 0);
    uint32_t m = v[0].x, m1 = v[0].y, m2 = v[0].z;
#pragma unroll
    for (int j = 1; j < 6; j++) {
        asm volatile("max.NaN.xorsign.abs.f16x2 %0, %0, %1;" : "+r"(m) : "r"(v[j].x));
        asm volatile("max.NaN.xorsign.abs.f16x2 %0, %0, %1;" : "+r"(m1) : "r"(v[j].y));
        asm volatile("max.NaN.xorsign.abs.f16x2 %0, %0, %1;" : "+r"(m2) : "r"(v[j].z));
    }
    asm volatile("max.NaN.xorsign.abs.f16x2 %0, %0, %1;" : "+r"(m) : "r"(m1));
    asm volatile("max.NaN.xorsign.abs.f16x2 %0, %0, %1;" : "+r"(m) : "r"(m2));
    return h2_to_bf2(m) & 0x7fff7fffu;
}

template <int N> __device__ __forceinline__ void pad_code() {
#pragma unroll
    for (int i = 0; i < N; i++) asm volatile("pmevent 7;" ::: "memory");
}
template <bool V> struct Flag { static constexpr bool value = V; };
struct RFlag { bool value; };
__device__ __forceinline__ void score_group(const uint32_t (&a)[2][4], const uint32_t (&kf)[2][4], uint32_t d0, uint32_t d1, uint32_t m1, uint32_t d2, uint32_t m2) {
    FS(4, a[1][0]);
    float sc[4][4];
    mma_z(sc[0], a[0], kf[0][0], kf[0][1]);
    mma_z(sc[1], a[0], kf[0][2], kf[0][3]);
    mma_z(sc[2], a[1], kf[1][0], kf[1][1]);
    mma_z(sc[3], a[1], kf[1][2], kf[1][3]);
    const uint32_t v0 = __float_as_uint((sc[0][0] + sc[1][2]) + (sc[2][0] + sc[3][2])), v1 = __float_as_uint((sc[0][1] + sc[1][3]) + (sc[2][1] + sc[3][3]));
    FS(5, v0);
    st_async64(d2, v0, v1, m2);
    st_async64(d1, v0, v1, m1);
    asm volatile("st.shared.v2.u32 [%0], {%1,%2};" :: "r"(d0), "r"(v0), "r"(v1) : "memory");
}
__device__ __forceinline__ void store_tile(int s, int h, int role, uint32_t tile, uint32_t b0, uint32_t b1) {
    asm volatile("cp.async.bulk.global.shared::cta.bulk_group.L2::cache_hint [%0], [%1], %2, %3;"
                 :: "l"(&g_qkv[s][h][role][b0]), "r"(tile + b0), "r"(b1 - b0), "l"(policy_evict_first()) : "memory");
}
__device__ __forceinline__ uint32_t w_addr(uint32_t sbase, int warp, int lane) {
    return sbase + SM_WS + (warp >> 2) * 8192 + ((lane & 7) + ((lane >> 4) & 1) * 8) * 128 + ((((warp & 3) * 2 + ((lane >> 3) & 1)) ^ (lane & 7)) << 4);
}
__device__ __forceinline__ void vx_copy(uint32_t sbase, int j, int r) {
    bulk_s2s(mapa(sbase + SM_VX + (j & 1) * 8192, r), sbase + SM_T + (j & 3) * TBUF + DH * 16, 8192, mapa(sbase + B_VX + 8 * (j & 1), r));
}
__device__ __forceinline__ float to_scale(float bound) {
    int e = 141 - (int)((__float_as_uint(bound) >> 23) & 255u);
    e = e > 100 ? 100 : e;
    return __uint_as_float((uint32_t)(127 + e) << 23);
}
__device__ __forceinline__ void norms_gather(int lane, uint32_t sbase) {
    uint2 v[3];
    uint4 w[2];
    unsigned it = 0;
#pragma unroll
    for (int i = 0; i < 3; i++) v[i] = make_uint2(0u, 0u);
    w[0] = w[1] = make_uint4(0u, 0u, 0u, 0u);
    bool more;
    do {
#pragma unroll
        for (int i = 0; i < 3; i++) if (!GPRED || (v[i].x & 1u) == 0u) v[i] = ld_vol_u2(&g_norm[3 * lane + i]);
#pragma unroll
        for (int i = 0; i < 2; i++) if (!GPRED || (w[i].x & w[i].y & w[i].z & w[i].w & 1u) == 0u) w[i] = ld_vol_u4(&g_wv[lane][i]);
        more = __any_sync(0xffffffffu, (v[0].x & v[1].x & v[2].x & w[0].x & w[0].y & w[0].z & w[0].w & w[1].x & w[1].y & w[1].z & w[1].w & 1u) == 0u);
    } while (more && ++it < SPIN_LIMIT);
    float c;
    asm("sqrt.approx.f32 %0, %1;" : "=f"(c) : "f"(__uint_as_float(max(max(v[0].x, v[1].x), v[2].x))));
    c *= __uint_as_float(max(max(max(w[0].x, w[0].y), max(w[0].z, w[0].w)), max(max(w[1].x, w[1].y), max(w[1].z, w[1].w)))) * 272.f;
#pragma unroll
    for (int o = 16; o; o >>= 1) c += __shfl_xor_sync(0xffffffffu, c, o);
    const uint32_t r = __reduce_max_sync(0xffffffffu, v[0].y);
    if (lane < 3) {
        const uint32_t rb = mapa(sbase, lane);
        c *= 1.1f * 24.f;
        st_async64(rb + SM_SC, __float_as_uint(to_scale(__uint_as_float(r) * c)), __float_as_uint(c), rb + B_W + 8);
        st_async32(rb + SM_SC + 68, r, rb + B_W + 8);
    }
    __syncwarp();
}
__device__ __forceinline__ void xmax_gather(int lane, uint32_t sb) {
    uint4 v[4];
    unsigned it = 0;
    uint32_t ok;
    do {
#pragma unroll
        for (int i = 0; i < 4; i++) v[i] = ld_vol_u4(&g_rx[lane + 32 * (i >> 1)][i & 1]);
        ok = 1u;
#pragma unroll
        for (int i = 0; i < 4; i++) ok &= (v[i].x & v[i].y) & (v[i].z & v[i].w);
    } while (__any_sync(0xffffffffu, ok == 0u) && ++it < SPIN_LIMIT);
#pragma unroll
    for (int i = 0; i < 2; i++)
        sts32(sb + SM_SC + 64 + 4 * lane + 128 * i, max(max(max(v[2 * i].x, v[2 * i].y), max(v[2 * i].z, v[2 * i].w)), max(max(v[2 * i + 1].x, v[2 * i + 1].y), max(v[2 * i + 1].z, v[2 * i + 1].w))));
}
__device__ __forceinline__ uint32_t max_abs8(uint32_t m, uint32_t a, uint32_t b, uint32_t c, uint32_t d) { return max_abs2(max_abs2(m, max_abs2(a, b)), max_abs2(c, d)); }
__device__ __forceinline__ uint32_t warp_max_abs(uint32_t m) { return __reduce_max_sync(0xffffffffu, max((m << 16) & 0x7fff0000u, m & 0x7fff0000u)); }

__device__ __forceinline__ void last_rows(int pass) {
    extern __shared__ __align__(1024) unsigned char smem_raw[];
    const uint32_t sbase = smem_u32(smem_raw);
    const int tid = threadIdx.x, warp = __shfl_sync(0xffffffffu, tid >> 5, 0), h = blockIdx.x / 3;
    {
        const int sg = warp < 8, wq = warp & 3, lane = tid & 31;
        const uint32_t qk = sbase + SM_X + XBUF + sg * (2 * 9216), ob = sbase + SM_X + 2 * XBUF + sg * 8192;
        TST(0);
        if (pass) mbar_wait(sbase + B_VX + 8 * sg, 0);
        fence_async();
        TST(1);
        float sc[20];
#pragma unroll
        for (int i = 0; i < 20; i++) sc[i] = 0.f;
        {
            const uint64_t da = smem_desc(qk + 1024, 128, 1024), db = smem_desc(qk, 128, 2048);
            wg_fence();
#pragma unroll
            for (int ks = 0; ks < 8; ks++) wgmma_n40_ss(sc, da + (uint64_t)((ks >> 2) * 576 + (ks & 3) * 16), db + (uint64_t)((ks >> 2) * 576 + (ks & 3) * 16), ks > 0);
            wg_commit();
            wg_wait0();
        }
        uint32_t p[5], o[16];
        const float psum = xrow_softmax(sc, p, wq, lane);
        xrow_pv(o, p, psum, sbase + SM_T + ((NSEG - 2 + sg) & 3) * TBUF);
        if (pass) {
#pragma unroll
            for (int i = 0; i < 4; i++) stsm_x4(ob + (i >> 1) * 4096 + wq * 1024 + (i & 1) * 512 + lane * 16, o[4 * i], o[4 * i + 1], o[4 * i + 2], o[4 * i + 3]);
        }
        fence_async();
        named_bar(11 + sg, 128);
        TST(2);
        if ((tid & 127) == 0 && pass) {
            unsigned char* dst = reinterpret_cast<unsigned char*>(g_ox) + ((size_t)((NSEG / 2 - 1) * NH + h)) * 16384 + sg * 4096;
            asm volatile("cp.async.bulk.global.shared::cta.bulk_group [%0], [%1], 4096;" :: "l"(dst), "r"(ob) : "memory");
            asm volatile("cp.async.bulk.global.shared::cta.bulk_group [%0], [%1], 4096;" :: "l"(dst + 8192), "r"(ob + 4096) : "memory");
            asm volatile("cp.async.bulk.commit_group;" ::: "memory");
            asm volatile("cp.async.bulk.wait_group 0;" ::: "memory");
            asm volatile("red.relaxed.gpu.global.add.u32 [%0], 1;" :: "l"(&g_prog[(NSEG / 2 - 1) * 8 + (h >> 2)]) : "memory");
        }
        TST(3);
    }
    __syncwarp();
}

__global__ void __cluster_dims__(3, 1, 1) __launch_bounds__(384, 1)
k_chain(const __grid_constant__ CUtensorMap tmq, const __grid_constant__ CUtensorMap tmk,
        const __grid_constant__ CUtensorMap tmv, const __grid_constant__ CUtensorMap tmx2, const __grid_constant__ CUtensorMap tmo,
        const __grid_constant__ CUtensorMap tmm, const bf16* __restrict__ xg) {
    extern __shared__ __align__(1024) unsigned char smem_raw[];
    const uint32_t sbase = smem_u32(smem_raw);
    const int cta = blockIdx.x, h = cta / 3, role = cta - 3 * h;
    const int tid = threadIdx.x, warp = __shfl_sync(0xffffffffu, tid >> 5, 0), lane_o = tid & 31;
    TS3C(0);
    asm volatile("griddepcontrol.launch_dependents;" ::: "memory");
    auto stage_w = [&](int i) {
        tma_2d(sbase + SM_WS + i * 16384, role == 2 ? &tmv : &tmq, h * DH + (role == 1 ? 64 : 0), i * 64, sbase + B_W + 8 * i);
        tma_2d(sbase + SM_WS + i * 16384 + 8192, role == 2 ? &tmv : &tmk, h * DH + (role == 0 ? 0 : 64), i * 64, sbase + B_W + 8 * i);
    };
    auto stage_x = [&](int i) {
        tma_2d(sbase + x01_off(i), &tmx2, i * 64, 0, sbase + B_W + 8 * i);
        tma_2d(sbase + x01_off(i) + 8192, &tmm, i * 64, 0, sbase + B_W + 8 * i);
        if (i < 3) tma_2d(sbase + x23_off(i), &tmx2, i * 64, 64, sbase + B_W + 8 * i);
    };
    if (tid == 0) {
#pragma unroll
        for (int i = 0; i < 10; i++) mbar_init(sbase + B_W + 8 * i, 1);
        fence_async();
        TSQ(10);
#pragma unroll
        for (int i = 0; i < 3; i++) tma_2d(sbase + SM_X01 + i * 16384, &tmo, role * WOC + i * 64, h * DH, sbase + B_E);
        stage_x(0); stage_w(0);
        TSQ(11);
        mbar_expect(sbase + B_E, 49152);
#pragma unroll
        for (int i = 0; i < 9; i++) mbar_expect(sbase + B_W + 8 * i, 16384 + 9216 + (i < 3 ? 8192 : 0));
    } else if (tid == 32) {
#pragma unroll
        for (int i = 0; i < 8; i++) mbar_init(sbase + SM_BAR + 8 * i, 1);
        mbar_init(sbase + B_XF, 3);
        asm volatile("fence.mbarrier_init.release.cluster;" ::: "memory");
        for (int i = 0; i < 2; i++) {
            mbar_expect(sbase + B_SB + 8 * i, role == 2 ? 2560 : 1280 + 2048);
            mbar_expect(sbase + B_VX + 8 * i, role != 2 ? 8192 : 2 * 9216);
            mbar_expect(sbase + B_XT + 8 * i, 32768);
            mbar_expect(sbase + B_XT + 16 + 8 * i, i == 0 ? 40960 : 0);
        }
    }
    __syncthreads();
    TS3C(8);
    if (tid == 0) {
#pragma unroll 1
        for (int i = 1; i < NUP; i++) { if (i < 3) stage_x(i); stage_w(i); }
        TSQ(12);
    }
    __syncwarp();
    if (warp < 8) {
        uint32_t wreg[36 - NS][4];
        uint32_t v0, v1;
        {
            const int lane = lane_o;
            const uint32_t a = w_addr(sbase, warp, lane);
            const uint64_t da = smem_desc(sbase + SM_WS + (warp >> 2) * 8192, 1024, 1024) | (1ull << 62);
            float acc[36], acc1[32];
            uint32_t m = 0u;
#pragma unroll
            for (int i = 0; i < 36; i++) acc[i] = 0.f;
#pragma unroll
            for (int i = 0; i < 32; i++) acc1[i] = 0.f;
#pragma unroll 1
            for (int b = 0; b < 7; b++) {
                if (b == 0) TSQ(0);
                mbar_wait(sbase + B_W + 8 * b, 0);
                TSQ(1 + b);
                const uint64_t db = smem_desc(sbase + x01_off(b), 16, 1024) | (1ull << 62);
                wg_fence();
#pragma unroll
                for (int k = 0; k < 4; k++) wgmma_n72_ss(acc, da + (uint64_t)(b * 1024 + k * 128), db + (uint64_t)(k * 2));
                wg_commit();
                if (b < 3) {
                    const uint64_t d1 = smem_desc(sbase + x23_off(b), 16, 1024) | (1ull << 62);
                    wg_fence();
#pragma unroll
                    for (int k = 0; k < 4; k++) wgmma_n64_ss(acc1, da + (uint64_t)(b * 1024 + k * 128), d1 + (uint64_t)(k * 2));
                    wg_commit();
                }
                if (b == 2) {
                    wg_wait0();
                    bar_arrive(10, 384);
                }
                if (b == 3) {
                    if (tid == 0) mbar_expect(sbase + B_W + 8, 12);
                    __syncwarp();
                    if (role == 2) {
#pragma unroll
                        for (int ks = 0; ks < NS; ks++) {
                            uint32_t t[4];
                            ldsm_x4_t(t, a + (ks >> 2) * 16384 + (ks & 3) * 2048);
                            m = max_abs8(m, t[0], t[1], t[2], t[3]);
                        }
                    }
#pragma unroll
                    for (int ks = NS; ks < 16; ks++) ldsm_x4_t(wreg[ks - NS], a + (ks >> 2) * 16384 + (ks & 3) * 2048);
                }
                if (b == 5) {
#pragma unroll
                    for (int ks = 16; ks < 24; ks++) ldsm_x4_t(wreg[ks - NS], a + (ks >> 2) * 16384 + (ks & 3) * 2048);
                    if (role == 2) {
#pragma unroll
                        for (int ks = NS; ks < 24; ks++) m = max_abs8(m, wreg[ks - NS][0], wreg[ks - NS][1], wreg[ks - NS][2], wreg[ks - NS][3]);
                    }
                }
            }
            mbar_wait(sbase + B_W + 16, 1);
            TSQ(13);
            wg_fence();
#pragma unroll
            for (int k = 12; k < 20; k++)
                wgmma_n64_ss(acc1, da + (uint64_t)((k >> 2) * 1024 + (k & 3) * 128), (smem_desc(sbase + x23_off(k >> 2), 16, 1024) | (1ull << 62)) + (uint64_t)((k & 3) * 2));
            wg_commit();
            wg_wait0();
            named_bar(11, 384);
#pragma unroll
            for (int i = 0; i < 8; i++)
                asm volatile("st.shared.v4.f32 [%0], {%1,%2,%3,%4};" :: "r"(sbase + SM_X + 5 * 8192 + i * 4096 + tid * 16),
                             "f"(acc1[4 * i]), "f"(acc1[4 * i + 1]), "f"(acc1[4 * i + 2]), "f"(acc1[4 * i + 3]) : "memory");
#pragma unroll
            for (int b = 7; b < 9; b++) {
#pragma unroll
                for (int ks = 4 * b - 4; ks < 4 * b; ks++) ldsm_x4_t(wreg[ks - NS], a + (ks >> 2) * 16384 + (ks & 3) * 2048);
                if (role == 2) {
#pragma unroll
                    for (int ks = 4 * b - 4; ks < 4 * b; ks++) m = max_abs8(m, wreg[ks - NS][0], wreg[ks - NS][1], wreg[ks - NS][2], wreg[ks - NS][3]);
                }
                const uint64_t db = smem_desc(sbase + x01_off(b), 16, 1024) | (1ull << 62);
                mbar_wait(sbase + B_W + 8 * b, 0);
                TSQ(1 + b);
                if (b == 8) TS3C(2);
                wg_fence();
#pragma unroll
                for (int k = 0; k < 4; k++) wgmma_n72_ss(acc, da + (uint64_t)(b * 1024 + k * 128), db + (uint64_t)(k * 2));
                wg_commit();
            }
#pragma unroll
            for (int ks = 32; ks < KPRE; ks++) ldsm_x4_t(wreg[ks - NS], a + (ks >> 2) * 16384 + (ks & 3) * 2048);
            if (role == 2) {
#pragma unroll
                for (int ks = KPRE; ks < 36; ks++) {
                    uint32_t t[4];
                    ldsm_x4_t(t, a + (ks >> 2) * 16384 + (ks & 3) * 2048);
                    m = max_abs8(m, t[0], t[1], t[2], t[3]);
                }
#pragma unroll
                for (int ks = 32; ks < KPRE; ks++) m = max_abs8(m, wreg[ks - NS][0], wreg[ks - NS][1], wreg[ks - NS][2], wreg[ks - NS][3]);
                m = warp_max_abs(m);
                if (lane == 0) asm volatile("st.volatile.global.u32 [%0], %1;" :: "l"(reinterpret_cast<uint32_t*>(&g_wv[h][0]) + warp), "r"(m | 1u) : "memory");
                __syncwarp();
            }
            wg_wait0();
            named_bar(9, 256);
            const uint32_t off = sbase + SM_T + (DH + warp * 16 + (lane & 15)) * 16 + (lane >> 4) * (DH * 16);
#pragma unroll
            for (int i = 0; i < 4; i++)
                stsm_x4(off + (i >> 1) * TBUF + (i & 1) * (2 * DH * 16), pack_bf16(acc[8 * i], acc[8 * i + 1]), pack_bf16(acc[8 * i + 2], acc[8 * i + 3]),
                        pack_bf16(acc[8 * i + 4], acc[8 * i + 5]), pack_bf16(acc[8 * i + 6], acc[8 * i + 7]));
            v0 = pack_bf16(acc[32], acc[33]);
            v1 = pack_bf16(acc[34], acc[35]);
#pragma unroll
            for (int ks = KPRE; ks < 36; ks++) ldsm_x4_t(wreg[ks - NS], a + (ks >> 2) * 16384 + (ks & 3) * 2048);
            if (role == 2) fence_async();
            bar_arrive(8, 384);
            named_bar(7, 256);
            asm volatile("barrier.cluster.arrive.relaxed.aligned;" ::: "memory");
        }
        TS3C(3);
        uint32_t ws[NS][4];
#pragma unroll
        for (int ks = NS - NP; ks < NS; ks++) ldsm_x4_t(ws[ks], w_addr(sbase, warp, lane_o) + (ks >> 2) * 16384 + (ks & 3) * 2048);
        asm volatile("barrier.cluster.wait.aligned;" ::: "memory");
        if (lane_o == 0 && role != 2 && warp < 2) tma_2d_mc(sbase + SM_X + (2 * role + warp) * 8192, &tmx2, (2 * role + warp + 5) * 64, 64, sbase + B_XT + 8);
        __syncwarp();
        TS3C(4);
        auto main_loop = [&](auto is_c) {
            constexpr bool C = decltype(is_c)::value;
            if (C) pad_code<PAD4>(); else pad_code<PAD3>();
            const uint32_t l16 = __shfl_sync(0xffffffffu, sbase + lane_o * 16, lane_o);
            const uint32_t ka = __shfl_sync(0xffffffffu, sbase + SM_T + (64 + (lane_o & 7) + ((lane_o >> 3) & 1) * 16 + (lane_o >> 4) * 8) * 16, lane_o);
            const uint32_t wa = __shfl_sync(0xffffffffu, w_addr(sbase, warp, lane_o), lane_o);
            auto post = [&](bool act, int s, uint32_t to, uint32_t ta, int scw, uint32_t v0, uint32_t v1) {
                int lane = lane_o;
                asm volatile("" : "+r"(lane));
                asm volatile("stmatrix.sync.aligned.m8n8.x2.shared.b16 [%0], {%1,%2};" :: "r"(l16 + ta), "r"(v0), "r"(v1) : "memory");
                if (C) {
                    if (act || s + 1 < NSEG) {
                        const uint32_t fo = (uint32_t)(warp * 256 + lane * 8);
                        const uint32_t rb0 = mapa(sbase, 0), rb1 = mapa(sbase, 1);
                        st_async64(rb0 + SM_VM + fo, v0, v1, rb0 + B_SB + 8 * (s & 1));
                        st_async64(rb1 + SM_VM + fo, v0, v1, rb1 + B_SB + 8 * (s & 1));
                        asm volatile("st.shared.v2.u32 [%0], {%1,%2};" :: "r"(sbase + SM_VM + fo), "r"(v0), "r"(v1) : "memory");
                        bar_arrive(2, 384);
                    }
                } else if (act) bar_arrive(2, 384);
                else {
                    named_bar(2, 384);
                    if (scw == 0) {
                        uint32_t kf[2][4], qf[2][4];
#pragma unroll
                        for (int k2 = 0; k2 < 2; k2++) { ldsm_x4_t(kf[k2], ka + to + k2 * 512); ldsm_x4_t(qf[k2], l16 + SM_T + to + k2 * 512); }
                        const uint32_t d0 = sbase + SM_S + lane * 8, bo = sbase + B_SB + 8 * (s & 1);
                        const uint32_t d1 = mapa(d0 + 1280, role ^ 1), m1 = mapa(bo, role ^ 1), d2 = mapa(d0 + role * 1280, 2), m2 = mapa(bo, 2);
                        score_group(qf, kf, d0, d1, m1, d2, m2);
                        bar_arrive(6, 160);
                        bar_arrive(5, 384);
                    }
                    if (RARE(scw == 8)) {
                        const uint32_t dk = mapa(sbase + SM_X + XBUF + (2 + role) * 9216 + (warp - 4) * 256 + lane * 4, 2), mb = mapa(sbase + B_VX + 8, 2);
                        st_async32(dk, v0, mb);
                        st_async32(dk + 128, v1, mb);
                    }
                }
                FS(11, 0);
            };
            post(false, 0, 0, SM_T + warp * 256, warp ^ 7, v0, v1);
            if (tid == 128 && cta < NSEG) {
                fence_async();
                mbar_expect(sbase + B_E, XBUF);
                bulk_g2s(sbase + SM_X + 9 * 8192, xg + (size_t)cta * SEG * DM, 32768, sbase + B_E);
                bulk_g2s(sbase + SM_WS + 32768 + 4096, xg + (size_t)cta * SEG * DM + 16384, 4096, sbase + B_E);
            }
            __syncwarp();
            if (C) {
                named_bar(7, 256);
                if (warp == 1) norms_gather(lane_o, sbase);
            }
            auto chores = [&](int s, bool idle) {
                int lane = lane_o;
                asm volatile("" : "+r"(lane));
                const int hw = (s & 1) ? warp : warp - 4;
                const uint32_t tb = sbase + SM_T + (s & 3) * TBUF;
                if (idle) { if (hw != 2) named_bar(4, 384); else bar_arrive(4, 384); }
                if (hw == 2) {
                    if (lane == 0) {
                        if (C || !idle) fence_async();
                        if (C) {
                            store_tile(s + 1, h, 2, sbase + SM_T + ((s + 1) & 3) * TBUF, 2048, 10240);
                            store_tile(s, h, 2, tb, 0, idle ? 2048 : 10240);
                        } else store_tile(s, h, role, tb, 1024, 10240);
                        asm volatile("cp.async.bulk.commit_group;" ::: "memory");
                        asm volatile("cp.async.bulk.wait_group 0;" ::: "memory");
                        if (C) {
                            asm volatile("cp.async.bulk.shared::cluster.global.mbarrier::complete_tx::bytes.multicast::cluster [%0], [%1], 8192, [%2], %3;"
                                         :: "r"(sbase + SM_VX + ((s + 1) & 1) * 8192), "l"(&g_qkv[s + 1][h][2][2048]), "r"(sbase + B_VX + 8 * ((s + 1) & 1)), "h"((unsigned short)3) : "memory");
                        }
                        asm volatile("red.relaxed.gpu.global.add.u32 [%0], 1;" :: "l"(&g_flag[h * NSEG + s]) : "memory");
                    }
                    __syncwarp();
                    if (!C && (s & 1) && s + 4 < NSEG) bar_arrive(13, 160);
                }
                __syncwarp();
            };
            auto put_tiles = [&](const float (&acc)[32], uint32_t off) {
#pragma unroll
                for (int i = 0; i < 4; i++)
                    stsm_x4(off + (i >> 1) * TBUF + (i & 1) * (2 * DH * 16), pack_bf16(acc[8 * i], acc[8 * i + 1]), pack_bf16(acc[8 * i + 2], acc[8 * i + 3]),
                            pack_bf16(acc[8 * i + 4], acc[8 * i + 5]), pack_bf16(acc[8 * i + 6], acc[8 * i + 7]));
            };
            auto tile_off = [&](int p) {
                int lane = lane_o;
                asm volatile("" : "+r"(lane));
                return sbase + SM_T + (p & 1) * (2 * TBUF) + (DH + warp * 16 + (lane & 15)) * 16 + (lane >> 4) * (DH * 16);
            };
            {
                auto db = [&](int ks) { return (smem_desc(sbase + SM_X, 16, 1024) | (1ull << 62)) + (uint64_t)(((ks >> 2) - 5) * 512 + (ks & 3) * 2); };
                float acc[32];
#pragma unroll
                for (int i = 0; i < 8; i++)
                    asm volatile("ld.shared.v4.f32 {%0,%1,%2,%3}, [%4];" : "=f"(acc[4 * i]), "=f"(acc[4 * i + 1]), "=f"(acc[4 * i + 2]), "=f"(acc[4 * i + 3])
                                 : "r"(l16 + warp * 512 + SM_X + 5 * 8192 + i * 4096) : "memory");
                mbar_wait(sbase + B_XT + 8, 0);
                if (C) { if (warp < 4) named_bar(4, 384); } else if (warp != 7) named_bar(5, 384);
                wg_fence();
#pragma unroll
                for (int ks = 35; ks > 35 - NC0; ks--) wgmma_n64(acc, wreg[ks - NS], db(ks), 1);
                wg_commit();
                wg_wait0();
                if (warp == 5) {
                    mbar_wait(sbase + B_W + 8, 1);
                    bar_arrive(12, 160);
                }
                chores(0, false);
                if (!C || warp >= 4) named_bar(4, 384);
                wg_fence();
#pragma unroll
                for (int ks = 35 - NC0; ks >= 20; ks--) wgmma_n64(acc, wreg[ks - NS], db(ks), 1);
                wg_commit();
                if (cta < NSEG) {
                    uint32_t m = 0u;
                    mbar_wait(sbase + B_E, 1);
#pragma unroll 1
                    for (int j = 0; j < 9; j++) {
                        const uint4 xv = lds128(l16 + warp * 512 + (j < 8 ? SM_X + 9 * 8192 + j * 4096 : SM_WS + 32768 + 4096));
                        m = max_abs8(m, xv.x, xv.y, xv.z, xv.w);
                    }
                    m = warp_max_abs(m);
                    if (lane_o == 0) asm volatile("st.volatile.global.u32 [%0], %1;" :: "l"(reinterpret_cast<uint32_t*>(&g_rx[cta][0]) + warp), "r"(m | 1u) : "memory");
                    __syncwarp();
                }
                wg_wait0();
                put_tiles(acc, tile_off(1));
            }
            auto mem_proj = [&](uint32_t& u0, uint32_t& u1) {
#pragma unroll
                for (int ks = 0; ks < NS - NP; ks++) ldsm_x4_t(ws[ks], wa + (ks >> 2) * 16384 + (ks & 3) * 2048);
                FS(0, ws[0][0]);
                named_bar(1, 384);
                float acc[2][4], minv;
                uint32_t b[3][4];
#pragma unroll
                for (int kk = 0; kk < 3; kk++) ldsm_x4_t(b[kk], l16 + SM_M + kk * 512);
                FS(1, b[0][0]);
#pragma unroll
                for (int kk = 0; kk < 18; kk++) {
#pragma unroll
                    for (int i = 0; i < 2; i++) {
                        const int ks = 2 * kk + i;
                        if (ks < 2) mma_z(acc[i], ws[ks], b[kk % 3][2 * i], b[kk % 3][2 * i + 1]);
                        else if (ks < NS) mma_bf16(acc[i], ws[ks < NS ? ks : 0], b[kk % 3][2 * i], b[kk % 3][2 * i + 1]);
                        else mma_bf16(acc[i], wreg[ks >= NS ? ks - NS : 0], b[kk % 3][2 * i], b[kk % 3][2 * i + 1]);
                    }
                    if (kk + 3 < 18) ldsm_x4_t(b[kk % 3], l16 + SM_M + (kk + 3) * 512);
                    if (kk + 3 == 17) asm volatile("ld.shared.f32 %0, [%1];" : "=f"(minv) : "r"(sbase + SM_SC + 8) : "memory");
                }
                u0 = pack_bf16(fmaf(acc[1][0], minv, acc[0][0] * minv), fmaf(acc[1][1], minv, acc[0][1] * minv));
                u1 = pack_bf16(fmaf(acc[1][2], minv, acc[0][2] * minv), fmaf(acc[1][3], minv, acc[0][3] * minv));
                FS(2, u0);
            };
            int s = 0, rc = 9;
            bool act = warp >= 4;
            uint32_t to = TBUF, ta = SM_T + warp * 256 + TBUF;
            auto next_slot = [&]() {
                const uint32_t d = (s & 3) == 3 ? -3 * TBUF : TBUF;
                to += d; ta += d;
                asm volatile("" : "+r"(to), "+r"(ta));
            };
#pragma unroll 1
            for (;;) {
                uint32_t u0, u1;
                if (act) {
                    mem_proj(u0, u1);
                    s++;
                    post(true, s, to, ta, 1, u0, u1);
                    const int p = (s + 3) >> 1;
                    const uint32_t dlo = (uint32_t)smem_desc(sbase + SM_X, 16, 1024) + rc * 512;
                    const uint64_t da = smem_desc(sbase + SM_WS + (warp >> 2) * 8192, 1024, 1024) | (1ull << 62);
                    auto db = [&](int ks) {
                        const int j = ((ks >> 2) + 4) % 9;
                        return ((uint64_t)0x40000040u << 32) | (uint64_t)(dlo + (uint32_t)((j - (rc + j >= 13 ? 13 : 0)) * 512 + (ks & 3) * 2));
                    };
                    const uint32_t xph = (uint32_t)((p - 1) >> 1) & 1u;
                    float acc[32];
                    mbar_wait(sbase + B_XT + 8 * (p & 1), xph);
                    if (C) named_bar(7, 256); else named_bar(5, 384);
                    if ((C ? CC_DELAY : C1_DELAY) > 0) { const uint32_t t1 = clock32(); while (clock32() - t1 < (C ? CC_DELAY : C1_DELAY)) {} }
                    constexpr int N1 = C ? NC1C : NC1;
                    wg_fence();
#pragma unroll
                    for (int ks = 35; ks > 35 - N1; ks--) { if (ks == 35) wgmma_n64_z(acc, wreg[ks - NS], db(ks)); else wgmma_n64(acc, wreg[ks - NS], db(ks), 1); }
                    wg_commit();
                    wg_wait0();
                    FS(9, __float_as_uint(acc[0]));
                    next_slot();
                    FS(8, 0);
                    if (B4P) asm volatile("{\n.reg .pred p;\nsetp.ge.s32 p, %0, 0;\n@p bar.sync 4, 384;\n}" :: "r"(s) : "memory");
                    else named_bar(4, 384);
                    FS(3, 0);
                    wg_fence();
#pragma unroll
                    for (int ks = 35 - N1; ks >= KG1; ks--) wgmma_n64(acc, wreg[ks - NS], db(ks), 1);
                    wg_commit();
                    mbar_wait(sbase + B_XT + 16 + 8 * (p & 1), xph);
                    wg_fence();
#pragma unroll
                    for (int ks = 0; ks < NS; ks++) wgmma_n64_ss(acc, da + (uint64_t)((ks >> 2) * 1024 + (ks & 3) * 128), db(ks));
#pragma unroll
                    for (int ks = NS; ks < KG1; ks++) wgmma_n64(acc, wreg[ks - NS], db(ks), 1);
                    wg_commit();
                    if (!C && warp >= 4) named_bar(13, 160);
                    uint32_t off = tile_off(p);
                    rc = rc >= 4 ? rc - 4 : rc + 9;
                    asm volatile("" : "+r"(off), "+r"(rc));
                    wg_wait0();
                    put_tiles(acc, off);
                    FS(7, __float_as_uint(acc[0]));
                }
                int scw = s + 2 < NSEG ? warp ^ ((s & 1) ? 7 : 3) : (warp & 4) + 4;
                asm volatile("" : "+r"(scw));
                mem_proj(u0, u1);
                s++;
                post(false, s, to, ta, scw, u0, u1);
                if (s + 1 == NSEG) break;
                if (s + 2 < NSEG) {
                    if (!C && (warp & 3) == 2) fence_async();
                    if (C) named_bar(7, 256); else if (scw != 0) named_bar(5, 384);
                    chores(s, true);
                } else {
                    const uint32_t t0 = clock32();
                    const uint32_t dq = mapa(sbase + SM_X + XBUF + role * 9216, 2), mb = mapa(sbase + B_VX, 2);
                    if (!C) {
                        if (scw != 0) named_bar(5, 384);
                        if (tid == 64) { fence_async(); while (clock32() - t0 < TL_DELAY) {} bulk_s2s(dq, sbase + SM_T + 2 * TBUF + 1024, 9216, mb); }
                        __syncwarp();
                    }
                    named_bar(4, 384);
                    if (!C && tid == 64) { const uint32_t t1 = clock32(); while (clock32() - t1 < VX_DELAY) {} bulk_s2s(dq + 2 * 9216 + 1024, sbase + SM_T + 3 * TBUF + 2048, 8192, mb + 8); }
                    __syncwarp();
                }
                next_slot();
                act = s + 4 < NSEG;
            }
            if (C) named_bar(7, 256);
        };
        if (role == 2) main_loop(Flag<true>()); else main_loop(Flag<false>());
    } else {
        uint32_t wo[3][8][4];
        uint32_t mx2 = 0u;
        {
            const int pt = tid - 256, lane = lane_o, wq = warp - 8, g = lane >> 2, tq = lane & 3;
            TSQ(7);
            if (XPF && cta < 9) asm volatile("prefetch.global.L2 [%0];" :: "l"(xg + 64 * DM + (cta * 128 + pt) * 64));
            mbar_wait(sbase + B_E, 0);
            TSQ(8);
#pragma unroll
            for (int t = 0; t < 3; t++) {
                const int T = 3 * wq + t;
                const uint32_t a = sbase + SM_X01 + (T >> 2) * 16384 + ((lane >> 4) * 8 + (lane & 7)) * 128 + ((((T & 3) * 2 + ((lane >> 3) & 1)) ^ (lane & 7)) << 4);
#pragma unroll
                for (int kk = 0; kk < 8; kk++) ldsm_x4_t(wo[t][kk], a + ((2 * wq + kk) & 7) * 2048);
            }
            named_bar(3, 128);
            if (pt == 64) {
                fence_async();
#pragma unroll 1
                for (int i = 3; i < 9; i++) { stage_x(i); if (i < 7) stage_w(i); }
            }
            if (pt >= 96 && pt < 120) {
                *reinterpret_cast<uint4*>(g_acc + cta * 1024 + (pt - 96) * 16) = make_uint4(0u, 0u, 0u, 0u);
                __threadfence();
            }
            __syncwarp();
            TSQ(9);
            float c0 = 0.f;
#pragma unroll
            for (int t = 0; t < 3; t++) {
                float n[4][4];
#pragma unroll
                for (int i = 0; i < 4; i++) { n[i][0] = n[i][1] = n[i][2] = n[i][3] = 0.f; }
#pragma unroll
                for (int kk = 0; kk < 8; kk++)
#pragma unroll
                    for (int i = 0; i < 4; i++) mma_k8(n[i], wo[t][kk][i & 2], wo[t][kk][(i & 2) + 1], wo[t][kk][i]);
                if ((g >> 1) == tq) c0 = fmaxf(c0, (g & 1) ? fmaxf(n[0][1] + n[2][1], n[1][3] + n[3][3]) : fmaxf(n[0][0] + n[2][0], n[1][2] + n[3][2]));
            }
            c0 = __uint_as_float(__reduce_max_sync(0xffffffffu, __float_as_uint(c0)));
            uint32_t m = 0u;
            const int xb = role == 0 ? h % 9 : 9;
            auto x_max = [&]() {
                mbar_wait(sbase + B_W + 8 * xb, 0);
#pragma unroll
                for (int j = 0; j < 5; j++) {
                    uint4 xv;
                    asm volatile("ld.shared.v4.u32 {%0,%1,%2,%3}, [%4];" : "=r"(xv.x), "=r"(xv.y), "=r"(xv.z), "=r"(xv.w)
                                 : "r"(sbase + x01_off(xb) + (j < 4 ? pt + 128 * j : 512 + (pt & 63)) * 16) : "memory");
                    m = max_abs8(m, xv.x, xv.y, xv.z, xv.w);
                }
            };
            if (xb < 3) x_max();
            named_bar(10, 384);
            TSQ(10);
            if (pt == 64) {
                fence_async();
                mbar_expect(sbase + B_W + 16, 16384);
#pragma unroll
                for (int i = 3; i < 5; i++) tma_2d(sbase + x23_off(i), &tmx2, i * 64, 64, sbase + B_W + 16);
#pragma unroll 1
                for (int i = 7; i < 9; i++) stage_w(i);
            }
            __syncwarp();
            if (xb >= 3 && xb < 7) x_max();
            bar_arrive(11, 384);
            if (xb == 7 || xb == 8) x_max();
            asm volatile("barrier.cluster.arrive.relaxed.aligned;" ::: "memory");
            m = warp_max_abs(m);
            if (lane == 0) { sts32(sbase + SM_SC + 320 + 4 * wq, __float_as_uint(c0)); sts32(sbase + SM_SC + 336 + 4 * wq, m); }
            TSQ(1);
            named_bar(3, 128);
            if (pt == 0) {
                const uint4 a = lds128(sbase + SM_SC + 320), b = lds128(sbase + SM_SC + 336);
                st_vol_u2(&g_norm[cta], make_uint2(max(max(a.x, a.y), max(a.z, a.w)) | 1u, max(max(b.x, b.y), max(b.z, b.w)) | 1u));
            }
            __syncwarp();
            named_bar(8, 384);
            TSQ(2);
            asm volatile("barrier.cluster.wait.aligned;" ::: "memory");
            if (role == 2 && lane == 0 && wq < 2) vx_copy(sbase, 0, wq);
            __syncwarp();
        }
        const int wq = warp - 8;
        auto helper_loop = [&](auto is_c) {
        const bool C = is_c.value;
        if (C) pad_code<PAD2>(); else pad_code<PAD1>();
        const uint32_t sb = sbase;
        const uint32_t l8_o = __shfl_sync(0xffffffffu, sb + lane_o * 8, lane_o), l16_o = __shfl_sync(0xffffffffu, sb + lane_o * 16, lane_o);
        unsigned char* dst = g_acc + (role * 32 + wq * 8 + (lane_o >> 3)) * 1024 + (lane_o & 7) * 16;
        auto load_kf = [&](uint32_t (&kf)[2][4], int slot) {
            int lane = lane_o;
            asm volatile("" : "+r"(lane));
            const uint32_t ka = sb + SM_T + slot * TBUF + ((wq + 1) * DH + 64 + (lane & 7) + ((lane >> 3) & 1) * 16 + (lane >> 4) * 8) * 16;
#pragma unroll
            for (int k2 = 0; k2 < 2; k2++) ldsm_x4_t(kf[k2], ka + k2 * 512);
        };
        float minv = 1.f;
        uint32_t kf[2][4];
        if (!C) load_kf(kf, 0);
        int b3 = 0;
        int rx = 9;
        for (int s = 0; s + 1 < NSEG; s++) {
            const int n3 = b3 == 2 ? 0 : b3 + 1;
            uint32_t l8 = l8_o, l16 = l16_o;
            asm volatile("" : "+r"(l8), "+r"(l16));
            {
                int lane = lane_o;
                asm volatile("" : "+r"(lane));
                if (C) {
                    if (lane == 0) {
                        if (wq == 3 && h == 0) {
                            const uint32_t t = gtime32();
                            st_vol_u2(&g_tick, make_uint2(t, lds32(sb + SM_SC + 12)));
                            sts32(sb + SM_SC + 12, t);
                        }
                    }
                    __syncwarp();
                    if (wq == 2 && s > 1 && lane < 24) {
                        *reinterpret_cast<uint4*>(g_acc + n3 * 128 + (3 * h + (lane >> 3)) * 1024 + (lane & 7) * 16) = make_uint4(0u, 0u, 0u, 0u);
                    }
                    if (RARE(wq == 1 && s == 3 && lane < 3)) {
                        const int c = 3 * h + lane;
                        st_vol_u2(&g_norm[c], make_uint2(0u, 0u));
                        uint4* z = c < NSEG ? g_rx[c] : g_wv[c - NSEG];
                        st_vol_u4(z, make_uint4(0u, 0u, 0u, 0u)); st_vol_u4(z + 1, make_uint4(0u, 0u, 0u, 0u));
                    }
                    __syncwarp();
                }
                const uint32_t mw = __reduce_max_sync(0xffffffffu, max(mx2 << 16, mx2 & 0xffff0000u));
                if (lane == 0) sts32(sb + SM_SC + 16 + 4 * wq, mw);
            }
            const uint32_t to = SM_T + (s & 3) * TBUF;
            const uint32_t ph = (uint32_t)(s >> 1) & 1u;
            if (!C) {
                const uint32_t bo = sb + B_SB + 8 * (s & 1);
                uint32_t d0 = l8 + SM_S + (wq + 1) * 256, qa = l16 + to;
                const uint32_t d1 = mapa(d0 + 1280, role ^ 1), m1 = mapa(bo, role ^ 1), d2 = mapa(d0 + role * 1280, 2), m2 = mapa(bo, 2);
                asm volatile("" : "+r"(d0), "+r"(qa));
                mbar_wait(sb + (s > 0 ? B_VX + 8 * (s & 1) : B_W), ph);
                FS(1, 0);
                named_bar(2, 384);
                uint32_t qf[2][4];
#pragma unroll
                for (int k2 = 0; k2 < 2; k2++) ldsm_x4_t(qf[k2], qa + k2 * 512);
                score_group(qf, kf, d0, d1, m1, d2, m2);
                bar_arrive(5, 384);
            } else named_bar(2, 384);
            if (!C && s == 0) {
                TSQ(3);
                mbar_wait(sb + B_VX, 0);
                TSQ(4);
            }
            float4 m4;
            asm volatile("ld.shared.v4.f32 {%0,%1,%2,%3}, [%4];" : "=f"(m4.x), "=f"(m4.y), "=f"(m4.z), "=f"(m4.w) : "r"(sb + SM_SC + 16) : "memory");
            const float c24 = __uint_as_float(lds32(sb + SM_SC + 4)), xb = __uint_as_float(lds32(sb + SM_SC + 64 + 4 * s));
            uint32_t vf[2][2][4], vm[2][2];
            uint32_t va = l16 + ((l16 >> 8) & 1) * 1792 + wq * 512 + (C ? to + DH * 16 : SM_VX + (s & 1) * 8192);
            auto load_vf = [&]() {
#pragma unroll
                for (int i = 0; i < 4; i++) ldsm_x4(vf[i & 1][i >> 1], va + (i & 1) * 256 + (i >> 1) * 4096);
            };
            if (C || VFP == 0) load_vf();
            float scale = to_scale(fmaxf(fmaxf(fmaxf(m4.x, m4.y), fmaxf(m4.z, m4.w)) * minv, xb) * c24);
            uint32_t oa = l16 + wq * 512;
            asm volatile("" : "+f"(scale), "+r"(oa), "+r"(va));
            FS(7, __float_as_uint(scale));
            constexpr float EC = (float)(1.4426950408889634 * 0.08838834764831845);
            if (!C) named_bar(6, 160);
            if (C) mbar_wait_fast(sb + B_SB + 8 * (s & 1), ph);
            float sv[5][2];
#pragma unroll
            for (int j = 0; j < 5; j++) lds64f(sv[j][0], sv[j][1], l8 + SM_S + j * 256);
            if (!C) {
#pragma unroll
                for (int j = 0; j < 5; j++) { sv[j][0] *= EC; sv[j][1] *= EC; asm volatile("" : "+f"(sv[j][0]), "+f"(sv[j][1])); }
                mbar_wait_fast(sb + B_SB + 8 * (s & 1), ph);
            }
            FS(6, 0);
            uint32_t p[5];
            {
                float sr[5][2];
#pragma unroll
                for (int j = 0; j < 5; j++) lds64f(sr[j][0], sr[j][1], l8 + SM_S + 1280 + j * 256);
                if (!C && VFP == 1) load_vf();
                lds64(vm[0][0], vm[0][1], l8 + SM_VM + wq * 512);
                lds64(vm[1][0], vm[1][1], l8 + SM_VM + wq * 512 + 256);
#pragma unroll
                for (int j = 0; j < 5; j++) {
                    sv[j][0] = C ? sv[j][0] + sr[j][0] : fmaf(sr[j][0], EC, sv[j][0]);
                    sv[j][1] = C ? sv[j][1] + sr[j][1] : fmaf(sr[j][1], EC, sv[j][1]);
                }
                float mx = fmaxf(fmaxf(fmaxf(sv[0][0], sv[0][1]), fmaxf(sv[1][0], sv[1][1])), fmaxf(fmaxf(sv[2][0], sv[2][1]), fmaxf(sv[3][0], sv[3][1])));
                mx = fmaxf(mx, fmaxf(sv[4][0], sv[4][1]));
                {
                    const float m1 = __shfl_xor_sync(0xffffffffu, mx, 1), m2 = __shfl_xor_sync(0xffffffffu, mx, 2), m3 = __shfl_xor_sync(0xffffffffu, mx, 3);
                    if (!C && VFP == 2) { va += __float_as_uint(mx) & l16 & 3u; load_vf(); }
                    if (C) {
#pragma unroll
                        for (int j = 0; j < 5; j++) { sv[j][0] *= EC; sv[j][1] *= EC; }
                        mx = fmaxf(fmaxf(mx * EC, m1 * EC), fmaxf(m2 * EC, m3 * EC));
                    } else mx = fmaxf(fmaxf(mx, m1), fmaxf(m2, m3));
                }
#pragma unroll
                for (int jj = 0; jj < 5; jj++) {
                    const int j = (jj + 1) % 5;
                    asm("ex2.approx.ftz.f32 %0, %1;" : "=f"(sv[j][0]) : "f"(sv[j][0] - mx));
                    asm("ex2.approx.ftz.f32 %0, %1;" : "=f"(sv[j][1]) : "f"(sv[j][1] - mx));
                    p[j] = pack_bf16(sv[j][0], sv[j][1]);
                }
            }
            FS(0, p[0]);
            uint32_t b[4][4];
            float zs[4];
            {
                float o0[2][4], o1[2][4];
                mma_z(o0[0], vf[0][0], p[1], p[2]);
                mma_z(o0[1], vf[1][0], p[1], p[2]);
                mma_z(o1[0], vf[0][1], p[3], p[4]);
                mma_z(o1[1], vf[1][1], p[3], p[4]);
                mma_k8(o0[0], vm[0][0], vm[0][1], p[0]);
                mma_k8(o0[1], vm[1][0], vm[1][1], p[0]);
                const uint32_t one4[4] = {0x3f803f80u, 0x3f803f80u, 0x3f803f80u, 0x3f803f80u};
                mma_z(zs, one4, p[1], p[2]);
                mma_bf16(zs, one4, p[3], p[4]);
                mma_k8(zs, one4[0], one4[1], p[0]);
                uint32_t ow[4];
#pragma unroll
                for (int m = 0; m < 2; m++) {
                    ow[2 * m] = pack_bf16(o0[m][0] + o1[m][0], o0[m][1] + o1[m][1]);
                    ow[2 * m + 1] = pack_bf16(o0[m][2] + o1[m][2], o0[m][3] + o1[m][3]);
                }
                stsm_x4(oa + SM_O, ow[0], ow[1], ow[2], ow[3]);
                FS(2, 0);
#pragma unroll
                for (int i = 0; i < 4; i++) b[0][i] = movm(ow[i]);
            }
            float acc[3][2][4];
            named_bar(3, 128);
#pragma unroll
            for (int i = 1; i < 4; i++) ldsm_x4_t(b[i], l16 + SM_O + ((wq + i) & 3) * 512);
#pragma unroll
            for (int c = 0; c < 2; c++)
#pragma unroll
                for (int t = 0; t < 3; t++) mma_z(acc[t][c], wo[t][c], b[0][2 * c], b[0][2 * c + 1]);
            float z0, z1;
            asm volatile("rcp.approx.ftz.f32 %0, %1;" : "=f"(z0) : "f"(zs[0]));
            asm volatile("rcp.approx.ftz.f32 %0, %1;" : "=f"(z1) : "f"(zs[1]));
            asm volatile("{\n.reg .pred p;\nsetp.eq.s32 p, %1, 0;\n@p bar.sync 12, 160;\n@p ld.shared.f32 %0, [%2];\n}" : "+f"(scale) : "r"(s), "r"(sb + SM_SC) : "memory");
            z0 *= scale; z1 *= scale;
            FS(3, b[1][0]);
#pragma unroll
            for (int i = 1; i < 4; i++)
#pragma unroll
                for (int c = 0; c < 2; c++)
#pragma unroll
                    for (int t = 0; t < 3; t++) mma_bf16(acc[t][c], wo[t][2 * i + c], b[i][2 * c], b[i][2 * c + 1]);
            {
                uint32_t w[6];
#pragma unroll
                for (int t = 0; t < 3; t++) {
                    w[2 * t] = pack_f16(fmaf(acc[t][1][0], z0, acc[t][0][0] * z0), fmaf(acc[t][1][1], z1, acc[t][0][1] * z1));
                    w[2 * t + 1] = pack_f16(fmaf(acc[t][1][2], z0, acc[t][0][2] * z0), fmaf(acc[t][1][3], z1, acc[t][0][3] * z1));
                }
                FS(8, w[5]);
                asm volatile("red.relaxed.gpu.global.add.noftz.v4.f16x2 [%0], {%1,%2,%3,%4};" :: "l"(dst), "r"(w[0]), "r"(w[1]), "r"(w[2]), "r"(0x3c00u) : "memory");
                asm volatile("red.relaxed.gpu.global.add.noftz.v4.f16x2 [%0], {%1,%2,%3,%4};" :: "l"(dst + 4096), "r"(w[3]), "r"(w[4]), "r"(w[5]), "r"(0x3c00u) : "memory");
            }
            FS(9, 0);
            if (s == 0) TSQ(5);
            bar_arrive(4, 384);
            const uint32_t t0 = clock32();
            minv = __uint_as_float(0x7f000000u - __float_as_uint(scale));
            if (lane_o == 0) {
                if (wq == 0) sts32(sb + SM_SC + 8, __float_as_uint(minv));
                if (s + 3 < NSEG) {
                    if (wq == 0) mbar_expect(sb + B_SB + 8 * (s & 1), C ? 2560 : 1280 + 2048);
                    if (wq == 1 && s > 0 && s + 5 < NSEG) mbar_expect(sb + B_XT + ((s & 1) ? 0 : 16) + 4 * ((s + 1) & 2), (s & 1) ? 32768 : 40960);
                    if (wq == 3 && !C) mbar_expect(sb + B_VX + 8 * (s & 1), 8192);
                }
            }
            __syncwarp();
            if (RARE(s == 1)) {
                if (!C) pad_code<PADC>();
                int lane = lane_o;
                asm volatile("" : "+r"(lane));
                if (wq == 3) xmax_gather(lane, sb);
                __syncwarp();
            }
            if (!C) load_kf(kf, (s + 1) & 3);
            const uint4* src = reinterpret_cast<const uint4*>(dst + (wq * 16 - role * 32) * 1024);
            dst += n3 == 0 ? -256 : 128;
            asm volatile("" : "+l"(dst));
            const int xp = (s + 5) >> 1, kb = wq + ((s & 1) ? 2 * role : 4 + 3 * role);
            const bool xl = !C && xp < NSEG / 2 && wq < ((s & 1) ? 2 : 3 - role);
            const uint32_t xs = wq == 3 && (s & 1) == 0 && xp < NSEG / 2;
            const uint32_t xd = sb + SM_X + (rx + kb >= 13 ? rx + kb - 13 : rx + kb) * 8192;
            mx2 = poll_mem(src, l16 + SM_M + wq * 2304, t0, [&]() {
                if (xs && lane_o < 2) asm volatile("mbarrier.arrive.relaxed.cluster.shared::cluster.b64 _, [%0];" :: "r"(mapa(sb + B_XF, lane_o)) : "memory");
                if (!C && (xl || s == 0) && (s & 1) == 0) mbar_wait(sb + B_XF, (uint32_t)(s >> 1) & 1u);
                if (lane_o == 0) {
                    if (xl) tma_2d_mc(xd, &tmx2, ((s & 1) ? kb + 5 : kb - 4) * 64, xp * 64, sb + B_XT + ((s & 1) ? 0 : 16) + 8 * (xp & 1));
                    if (!C && s == 0 && role == 1) tma_2d_mc(sb + SM_X + (9 + wq) * 8192, &tmx2, (wq + 5) * 64, 128, sb + B_XT);
                }
                __syncwarp();
            });
            if ((s & 1) == 0) rx = rx >= 4 ? rx - 4 : rx + 9;
            if (s == 0) TSQ(6);
            b3 = n3;
        }
        if (!C) bar_arrive(2, 384);
        };
        if (role == 2) helper_loop(Flag<true>()); else helper_loop(Flag<false>());
    }
    TS3C(1);
    if (role == 2 && warp >= 4) last_rows(1);
    cluster_sync_all();
}

extern "C" void kernel_launch(void* const* d_in, const int* in_sizes, int n_in, void* d_out, int out_size) {
    const bf16* x = (const bf16*)d_in[0];
    const bf16* mem0 = (const bf16*)d_in[1];
    const bf16* Wq = (const bf16*)d_in[2];
    const bf16* Wk = (const bf16*)d_in[3];
    const bf16* Wv = (const bf16*)d_in[4];
    const bf16* Wo = (const bf16*)d_in[5];
    const bf16* logA = (const bf16*)d_in[8];
    const bf16* Aim = (const bf16*)d_in[9];
    const bf16* Cre = (const bf16*)d_in[10];
    const bf16* Cim = (const bf16*)d_in[11];
    const bf16* logdt = (const bf16*)d_in[12];
    const bf16* dskip = (const bf16*)d_in[13];
    const bf16* gw = (const bf16*)d_in[14];
    bf16* out = (bf16*)d_out;
    static bool attr_done = false;
    typedef CUresult (*EncFn)(CUtensorMap*, CUtensorMapDataType, cuuint32_t, void*, const cuuint64_t*, const cuuint64_t*, const cuuint32_t*,
                              const cuuint32_t*, CUtensorMapInterleave, CUtensorMapSwizzle, CUtensorMapL2promotion, CUtensorMapFloatOOBfill);
    static EncFn enc = nullptr;
    if (!attr_done) {
        void* fn = nullptr;
        cudaDriverEntryPointQueryResult qr;
        cudaGetDriverEntryPoint("cuTensorMapEncodeTiled", &fn, cudaEnableDefault, &qr);
        enc = (EncFn)fn;
        cudaFuncSetAttribute(k_chain, cudaFuncAttributeMaxDynamicSharedMemorySize, 232448);
        cudaFuncSetAttribute(k_side, cudaFuncAttributeMaxDynamicSharedMemorySize, SIDE_SMEM);
        attr_done = true;
    }
    CUtensorMap tmw[3];
    for (int i = 0; i < 3; i++) {
        const cuuint64_t dims[2] = {(cuuint64_t)HD, (cuuint64_t)DM};
        const cuuint64_t strides[1] = {(cuuint64_t)HD * 2};
        const cuuint32_t box[2] = {64, 64};
        const cuuint32_t es[2] = {1, 1};
        enc(&tmw[i], CU_TENSOR_MAP_DATA_TYPE_BFLOAT16, 2, (void*)(i == 0 ? Wq : (i == 1 ? Wk : Wv)), dims, strides, box, es, CU_TENSOR_MAP_INTERLEAVE_NONE,
            CU_TENSOR_MAP_SWIZZLE_128B, CU_TENSOR_MAP_L2_PROMOTION_L2_256B, CU_TENSOR_MAP_FLOAT_OOB_FILL_NONE);
    }
    CUtensorMap tmo;
    {
        const cuuint64_t dims[2] = {(cuuint64_t)DM, (cuuint64_t)HD};
        const cuuint64_t strides[1] = {(cuuint64_t)DM * 2};
        const cuuint32_t box[2] = {64, 128};
        const cuuint32_t es[2] = {1, 1};
        enc(&tmo, CU_TENSOR_MAP_DATA_TYPE_BFLOAT16, 2, (void*)Wo, dims, strides, box, es, CU_TENSOR_MAP_INTERLEAVE_NONE,
            CU_TENSOR_MAP_SWIZZLE_128B, CU_TENSOR_MAP_L2_PROMOTION_L2_128B, CU_TENSOR_MAP_FLOAT_OOB_FILL_NONE);
    }
    CUtensorMap tmx2;
    {
        const cuuint64_t dims[2] = {(cuuint64_t)DM, (cuuint64_t)S_LEN};
        const cuuint64_t strides[1] = {(cuuint64_t)DM * 2};
        const cuuint32_t box[2] = {64, 64};
        const cuuint32_t es[2] = {1, 1};
        enc(&tmx2, CU_TENSOR_MAP_DATA_TYPE_BFLOAT16, 2, (void*)x, dims, strides, box, es, CU_TENSOR_MAP_INTERLEAVE_NONE,
            CU_TENSOR_MAP_SWIZZLE_128B, CU_TENSOR_MAP_L2_PROMOTION_L2_128B, CU_TENSOR_MAP_FLOAT_OOB_FILL_NONE);
    }
    CUtensorMap tmm;
    {
        const cuuint64_t dims[2] = {(cuuint64_t)DM, (cuuint64_t)MEMT};
        const cuuint64_t strides[1] = {(cuuint64_t)DM * 2};
        const cuuint32_t box[2] = {64, (cuuint32_t)MEMT};
        const cuuint32_t es[2] = {1, 1};
        enc(&tmm, CU_TENSOR_MAP_DATA_TYPE_BFLOAT16, 2, (void*)mem0, dims, strides, box, es, CU_TENSOR_MAP_INTERLEAVE_NONE,
            CU_TENSOR_MAP_SWIZZLE_128B, CU_TENSOR_MAP_L2_PROMOTION_L2_128B, CU_TENSOR_MAP_FLOAT_OOB_FILL_NONE);
    }
    k_chain<<<NCTA, 384, 232448>>>(tmw[0], tmw[1], tmw[2], tmx2, tmo, tmm, x);
    {
        cudaLaunchConfig_t cfg = {};
        cfg.gridDim = dim3(SD_NCTA); cfg.blockDim = dim3(512); cfg.dynamicSmemBytes = SIDE_SMEM; cfg.stream = cudaStreamPerThread;
        cudaLaunchAttribute at[1];
        at[0].id = cudaLaunchAttributeProgrammaticStreamSerialization;
        at[0].val.programmaticStreamSerializationAllowed = 1;
        cfg.attrs = at; cfg.numAttrs = 1;
        cudaLaunchKernelEx(&cfg, k_side, tmo, x, logA, Aim, Cre, Cim, logdt, Wo, dskip, gw, out);
    }
}
```

```cpp
#include <cuda_runtime.h>
#include <cuda.h>
#include <cuda_bf16.h>
#include <stdint.h>

typedef __nv_bfloat16 bf16;
#define LDV4 "ld.volatile.global.v4.u32 {%0,%1,%2,%3}, [%4];"
#define STV4 "st.volatile.global.v4.u32 [%0], {%1,%2,%3,%4};"
#define STV2 "st.volatile.global.v2.u32 [%0], {%1,%2};"

constexpr int S_LEN = 2048, DM = 576, NH = 32, DH = 128, HD = 4096, MEMT = 8, SEG = 32, NSEG = 64, NST = 128;

__device__ __align__(128) bf16 g_gate[S_LEN];
constexpr int NCTA = NH * 3;
__device__ __align__(1024) unsigned char g_acc[96 * 1024];
__device__ __align__(128) uint2 g_norm[NCTA];
__device__ __align__(128) uint4 g_wv[NH][2];
__device__ __align__(128) uint4 g_rx[NSEG][2];
__device__ __align__(128) unsigned char g_qkv[NSEG][NH][3][10240];
__device__ __align__(128) bf16 g_ox[S_LEN * HD];
__device__ __align__(128) uint4 g_fp[8][36][6][128];
__device__ __align__(128) unsigned g_flag[NH * NSEG];
__device__ unsigned g_prog[NSEG / 2 * 8];
__device__ unsigned g_gcnt[64];
__device__ unsigned g_epoch;
__device__ __align__(128) uint2 g_tick;
__device__ __align__(128) bf16 g_y[DM * S_LEN];

#define TS3(slot) do {} while (0)
#define TS3P(slot) do {} while (0)
#define TSQ(slot) do {} while (0)
#define TS3W(slot) do {} while (0)
#define TSS(row, slot) do {} while (0)
#define TS3C(slot) do {} while (0)
#define TST(slot) do {} while (0)
#define TSA(seg, slot) do {} while (0)
#define TSG(i) do {} while (0)
#define FS(i, dep) do {} while (0)
__device__ __forceinline__ uint32_t smem_u32(const void* p) { return (uint32_t)__cvta_generic_to_shared(p); }
__device__ __forceinline__ float bf16r(float x) { return __bfloat162float(__float2bfloat16_rn(x)); }
__device__ __forceinline__ uint32_t pack_bf16(float lo, float hi) {
    __nv_bfloat162 v = __floats2bfloat162_rn(lo, hi);
    return *reinterpret_cast<uint32_t*>(&v);
}
__device__ __forceinline__ void ldsm_x4(uint32_t (&r)[4], uint32_t addr) {
    asm volatile("ldmatrix.sync.aligned.m8n8.x4.shared.b16 {%0,%1,%2,%3}, [%4];"
                 : "=r"(r[0]), "=r"(r[1]), "=r"(r[2]), "=r"(r[3]) : "r"(addr));
}
__device__ __forceinline__ void ldsm_x4_t(uint32_t (&r)[4], uint32_t addr) {
    asm volatile("ldmatrix.sync.aligned.m8n8.x4.trans.shared.b16 {%0,%1,%2,%3}, [%4];"
                 : "=r"(r[0]), "=r"(r[1]), "=r"(r[2]), "=r"(r[3]) : "r"(addr));
}
__device__ __forceinline__ void mma_bf16(float (&d)[4], const uint32_t (&a)[4], uint32_t b0, uint32_t b1) {
    asm volatile("mma.sync.aligned.m16n8k16.row.col.f32.bf16.bf16.f32 {%0,%1,%2,%3}, {%4,%5,%6,%7}, {%8,%9}, {%0,%1,%2,%3};"
                 : "+f"(d[0]), "+f"(d[1]), "+f"(d[2]), "+f"(d[3])
                 : "r"(a[0]), "r"(a[1]), "r"(a[2]), "r"(a[3]), "r"(b0), "r"(b1));
}
__device__ __forceinline__ uint2 ld_vol_u2(const uint2* p) {
    uint2 v; asm volatile("ld.volatile.global.v2.u32 {%0,%1}, [%2];" : "=r"(v.x), "=r"(v.y) : "l"(p) : "memory"); return v;
}
__device__ __forceinline__ void st_vol_u2(uint2* p, uint2 v) {
    asm volatile(STV2 :: "l"(p), "r"(v.x), "r"(v.y) : "memory");
}
__device__ __forceinline__ unsigned ld_acq(const unsigned* p) {
    unsigned v; asm volatile("ld.acquire.gpu.global.u32 %0, [%1];" : "=r"(v) : "l"(p) : "memory"); return v;
}
#define NS 10
#define NP 4
#define X_OXSZ 16384
#define GATE_A 1050
#define GATE_B 300
#define GATE_P 1880u
#define STAGGER 0
#define RLX_SLEEP 300
#define VX_DELAY 100
#define EARLY4 0
#define SPEC_M 1
#define SPEC_H 1
#define C2_DELAY 0
#define SS_POS 10
#define UNGATE_G 3
#define GATE_Y 0
#define GATE_S 0
#define GATE_F 1
#define W14_SLEEP 60
#define TURN31 1
#define GL_A 1150
#define GL_B 480
#define GS_A 1400
#define GS_B 480
#define GATE_POLL 0
#define GP_A 900
#define GP_B 200
#define NUP 3
#define SIDE_WAIT 0
#define FASTW 0
#define NC1 3
#define NC1C 5
#define C1_DELAY 0
#define XSKIP 0
#define LATEW 1
#define VFP 0
#define CC_DELAY 0
#define KPRE 34
#define P0A 1
#define P0B 1
#define P0C 0
#define P0D 0
#define GPRED 1
#define P0W 3
#define XRARE 1
#define RARE(c) __builtin_expect(!!(c), 0)
#define PADB 0
#define PADC 0
#define PADD 0
#define PADE 0
#define PAD1 0
#define PAD2 0
#define PAD3 0
#define PAD4 0
#define B4P 1
#define XPF 0
#define NC0 4
#define KG1 20
#define ZSM 5
#define SMR 0
#define TL_DELAY 600
#define POLL_DELAY 590
#define UNGATE 6
constexpr unsigned SPIN_LIMIT = 1u << 20;
constexpr int NATT = NSEG - 2;

constexpr int SD_CH = 16;
constexpr int SD_NCTA = DM / SD_CH;
constexpr int SD_ROW = 528;
constexpr int SD_U = 8 * SD_ROW;
constexpr int SD_TAP = 5888;
constexpr int SD_CPY = 1376 * 2;
constexpr int SD_WSTR = SD_TAP + 2 * SD_CPY;
constexpr int SD_SMEM = SD_CH * SD_U + 8 * SD_WSTR;
constexpr int O_U = 79, O_U3 = 911, O_U4 = 1055, O_W79 = 1023, O_W35 = 1151, O_W610 = 1279, O_W511 = 1487;

__device__ __forceinline__ uint32_t lds32(uint32_t a) { uint32_t v; asm volatile("ld.shared.u32 %0, [%1];" : "=r"(v) : "r"(a)); return v; }
__device__ __forceinline__ void sts32(uint32_t a, uint32_t v) { asm volatile("st.shared.u32 [%0], %1;" :: "r"(a), "r"(v) : "memory"); }
__device__ __forceinline__ uint4 lds128(uint32_t a) {
    uint4 v; asm volatile("ld.shared.v4.u32 {%0,%1,%2,%3}, [%4];" : "=r"(v.x), "=r"(v.y), "=r"(v.z), "=r"(v.w) : "r"(a) : "memory"); return v;
}
__device__ __forceinline__ void tap_tile(uint32_t (&t)[4], uint32_t a) {
    asm volatile("ld.volatile.shared.u32 %0, [%4];\nld.volatile.shared.u32 %1, [%4+-16];\nld.volatile.shared.u32 %2, [%4+16];\nld.volatile.shared.u32 %3, [%4];"
                 : "=r"(t[0]), "=r"(t[1]), "=r"(t[2]), "=r"(t[3]) : "r"(a));
}
constexpr uint32_t sd_pass(int type, int dl, int o, int d0, int d1) { return (uint32_t)(type | dl << 2 | d0 << 8 | d1 << 12 | o << 17); }
__constant__ uint32_t SD_PASS[14] = {sd_pass(0, 0, O_U, 0, 2), sd_pass(0, 1, O_U + 96, 0, 2), sd_pass(0, 2, O_U + 192, 0, 4), sd_pass(0, 3, O_U + 288, 0, 2), sd_pass(1, 0, O_U3, 8, 8),
                                     sd_pass(0, 4, O_U + 384, 0, 2), sd_pass(1, 0, O_U4, 8, 15), sd_pass(0, 5, O_U + 480, 0, 2), sd_pass(0, 6, O_U + 576, 0, 4), sd_pass(0, 7, O_U + 672, 0, 2),
                                     sd_pass(2, 0, O_W35, 2, 8), sd_pass(3, 0, O_W79, 2, 4), sd_pass(2, 1, O_W610, 4, 8), sd_pass(3, 0, O_W511, 8, 15)};
__device__ __forceinline__ uint32_t band2(int x, int lo, int hi) { return (x >= lo && x <= hi ? 0x3f80u : 0u) | (x + 1 >= lo && x + 1 <= hi ? 0x3f800000u : 0u); }
__device__ __forceinline__ void mma_z(float (&d)[4], const uint32_t (&a)[4], uint32_t b0, uint32_t b1);
__device__ __forceinline__ void put_tap(uint32_t a, float v) {
    asm volatile("{\n.reg .b16 h;\ncvt.rn.bf16.f32 h, %1;\nst.shared.b16 [%0], h;\nst.shared.b16 [%0+%2], h;\n}" :: "r"(a), "f"(v), "n"(SD_CPY - 2) : "memory");
}

__device__ __forceinline__ void named_bar(int id, int n) { asm volatile("bar.sync %0, %1;" :: "r"(id), "r"(n) : "memory"); }
__device__ __forceinline__ uint32_t pack_f16(float lo, float hi) {
    uint32_t r; asm("cvt.rn.f16x2.f32 %0, %1, %2;" : "=r"(r) : "f"(hi), "f"(lo)); return r;
}
__device__ __forceinline__ void cexp_t(float lr, float turns, float& re, float& im) {
    float m;
    asm("ex2.approx.ftz.f32 %0, %1;" : "=f"(m) : "f"(lr));
    const float a = (turns - rintf(turns)) * 6.283185307179586f;
    re = m * __cosf(a); im = m * __sinf(a);
}
__device__ __forceinline__ void csq(float& re, float& im) { const float r = re * re - im * im; im = 2.f * re * im; re = r; }
__device__ __forceinline__ void kb_state(const float* tp, float gf, uint32_t (&a)[4][2], uint32_t (&b)[5]) {
    const float4 p0 = *reinterpret_cast<const float4*>(tp), p1 = *reinterpret_cast<const float4*>(tp + 4);
    float wr, wi;
    cexp_t(p0.x * gf, p0.y * gf, wr, wi);
    float vr = wr * p1.x - wi * p1.y, vi = wr * p1.y + wi * p1.x;
#pragma unroll
    for (int c = 0; c < 4; c++) {
        a[c][0] = pack_f16(wr, wi); a[c][1] = pack_f16(vr, vi);
        csq(wr, wi);
        if (c < 3) csq(vr, vi);
    }
    b[0] = pack_f16(p0.z * wr - p0.w * wi, -p0.z * wi - p0.w * wr);
    float er = wr * p1.z - wi * p1.w, ei = wr * p1.w + wi * p1.z;
#pragma unroll
    for (int c = 0; c < 4; c++) {
        b[1 + c] = pack_f16(p0.z * er - p0.w * ei, -p0.z * ei - p0.w * er);
        if (c < 3) csq(er, ei);
    }
}
__device__ __forceinline__ uint32_t bf2_mul(uint32_t a, uint32_t b) { uint32_t r; asm("mul.rn.bf16x2 %0, %1, %2;" : "=r"(r) : "r"(a), "r"(b)); return r; }
__device__ __forceinline__ uint32_t bf2_add(uint32_t a, uint32_t b) { uint32_t r; asm("add.rn.bf16x2 %0, %1, %2;" : "=r"(r) : "r"(a), "r"(b)); return r; }
__device__ __forceinline__ uint32_t bf2_sub(uint32_t a, uint32_t b) { uint32_t r; asm("sub.rn.bf16x2 %0, %1, %2;" : "=r"(r) : "r"(a), "r"(b)); return r; }
__device__ __forceinline__ void wait_cnt(const unsigned* p, unsigned target) {
    unsigned it = 0;
    while ((int)(ld_acq(p) - target) < 0 && ++it < SPIN_LIMIT) __nanosleep(64);
}
__device__ __forceinline__ uint32_t gtime32() { uint32_t t; asm volatile("mov.u32 %0, %%globaltimer_lo;" : "=r"(t) :: "memory"); return t; }
__device__ __forceinline__ void gate(uint32_t tick_addr, uint32_t ga = GATE_A, uint32_t gb = GATE_B) {
    uint32_t t1, p;
    asm volatile("ld.volatile.shared.v2.u32 {%0,%1}, [%2];" : "=r"(t1), "=r"(p) : "r"(tick_addr) : "memory");
    uint32_t d = gtime32() - t1;
    if (d < 4u * p) {
        d -= d >= 2u * p ? 2u * p : 0u;
        d -= d >= p ? p : 0u;
        if (d + ga >= p && d + gb < p) {
            const uint32_t t2 = gtime32() + (p - gb - d);
            while ((int)(gtime32() - t2) < 0) {}
        }
    }
}

__device__ __forceinline__ void read_tick(uint32_t tick_addr) {
    const uint2 tk = ld_vol_u2(&g_tick);
    uint32_t p = tk.x - tk.y;
    p = p > GATE_P + 100u ? GATE_P + 100u : p;
    asm volatile("st.volatile.shared.v2.u32 [%0], {%1,%2};" :: "r"(tick_addr), "r"(tk.x), "r"(p) : "memory");
}

__device__ __forceinline__ void s4d_phase(unsigned char* smem_raw, const bf16* __restrict__ x, const bf16* __restrict__ logA,
                                          const bf16* __restrict__ Aim, const bf16* __restrict__ Cre, const bf16* __restrict__ Cim,
                                          const bf16* __restrict__ logdt, const bf16* __restrict__ dskip, const bf16* __restrict__ wslice, unsigned ep, uint32_t tick) {
    const int tid = threadIdx.x, warp = __shfl_sync(0xffffffffu, tid >> 5, 0), lane = tid & 31;
    const int d0 = blockIdx.x * SD_CH;
    float* tab = reinterpret_cast<float*>(smem_raw + SD_CH * SD_U + warp * SD_WSTR);
    const uint32_t wb = smem_u32(tab);
    const int g = lane >> 2, tq = lane & 3;
    uint2 prm[4];
    float ldt;
    auto load_prm = [&](int d) {
        prm[0] = __ldg(reinterpret_cast<const uint2*>(logA + d * NST) + lane); prm[1] = __ldg(reinterpret_cast<const uint2*>(Aim + d * NST) + lane);
        prm[2] = __ldg(reinterpret_cast<const uint2*>(Cre + d * NST) + lane); prm[3] = __ldg(reinterpret_cast<const uint2*>(Cim + d * NST) + lane);
        ldt = __bfloat162float(logdt[d]);
    };
    load_prm(d0 + warp);
    for (int i = lane; i < 2 * SD_CPY / 16; i += 32) reinterpret_cast<uint4*>(tab + SD_TAP / 4)[i] = make_uint4(0u, 0u, 0u, 0u);
    TS3(20);
#pragma unroll 1
    for (int ch = 0; ch < 2; ch++) {
        const int d = d0 + 8 * ch + warp;
        const uint32_t ub = smem_u32(smem_raw) + (8 * ch + warp) * SD_U;
        float k2048 = 0.f, sinv;
        {
            const float dt = bf16r(expf(ldt));
            uint32_t cm = __vmaxu2(__vmaxu2(prm[2].x & 0x7fff7fffu, prm[2].y & 0x7fff7fffu), __vmaxu2(prm[3].x & 0x7fff7fffu, prm[3].y & 0x7fff7fffu));
            cm = __reduce_max_sync(0xffffffffu, max(cm << 16, cm & 0xffff0000u));
            int e = 134 - (int)(__float_as_uint(__uint_as_float(cm) * dt) >> 23);
            e = e > 100 ? 100 : (e < -100 ? -100 : e);
            const float s2 = __uint_as_float((uint32_t)(128 + e) << 23);
            sinv = __uint_as_float((uint32_t)(127 - e) << 23);
#pragma unroll
            for (int j = 0; j < 4; j++) {
                float q[4];
#pragma unroll
                for (int i = 0; i < 4; i++) { const uint32_t w = j < 2 ? prm[i].x : prm[i].y; q[i] = __uint_as_float((j & 1) ? w & 0xffff0000u : w << 16); }
                const float zl = -bf16r(expf(q[0])) * dt * 1.4426950408889634f;
                const float zt = q[1] * dt * 0.15915494309189535f;
                const float cr = s2 * (q[2] * dt), ci = s2 * (q[3] * dt);
                float ar, ai, br, bi, er, ei;
                cexp_t(zl * 8.f, zt * 8.f, ar, ai);
                cexp_t(zl * 128.f, zt * 128.f, br, bi);
                cexp_t(zl * 2048.f, zt * 2048.f, er, ei);
                k2048 += cr * er - ci * ei;
                *reinterpret_cast<float4*>(tab + (lane + 32 * j) * 8) = make_float4(zl, zt, cr, ci);
                *reinterpret_cast<float4*>(tab + (lane + 32 * j) * 8 + 4) = make_float4(ar, ai, br, bi);
            }
#pragma unroll
            for (int o = 16; o; o >>= 1) k2048 += __shfl_xor_sync(0xffffffffu, k2048, o);
        }
        __syncwarp();
        {
            float kc[5][4];
#pragma unroll
            for (int i = 0; i < 5; i++) { kc[i][0] = kc[i][1] = kc[i][2] = kc[i][3] = 0.f; }
            const float gf = (float)g;
#pragma unroll 2
            for (int ks = 0; ks < 16; ks++) {
                uint32_t a0[4][2], a1[4][2], b0[5], b1[5];
                kb_state(tab + (8 * ks + tq) * 8, gf, a0, b0);
                kb_state(tab + (8 * ks + 4 + tq) * 8, gf, a1, b1);
#pragma unroll
                for (int i = 0; i < 5; i++) {
                    const int c = i > 0 ? i - 1 : 0;
                    asm volatile("mma.sync.aligned.m16n8k16.row.col.f32.f16.f16.f32 {%0,%1,%2,%3}, {%4,%5,%6,%7}, {%8,%9}, {%0,%1,%2,%3};"
                                 : "+f"(kc[i][0]), "+f"(kc[i][1]), "+f"(kc[i][2]), "+f"(kc[i][3])
                                 : "r"(a0[c][0]), "r"(a0[c][1]), "r"(a1[c][0]), "r"(a1[c][1]), "r"(b0[i]), "r"(b1[i]));
                }
            }
            const uint32_t tp = wb + SD_TAP;
            const uint32_t a0 = tp + 2 * (O_U + 96 * g - 4 * tq);
            const uint32_t a2 = tp + 2 * (((g & 1) ? O_U + 96 * (2 * (g & 3)) : ((g & 2) ? O_W35 : O_W79 + 1)) - 32 - 8 * tq - (g >> 2));
            const uint32_t a3 = tp + 2 * (((g & 1) ? O_W35 : O_W610 + 1) - 64 - 16 * tq - (g >> 1));
            const uint32_t a4 = tp + 2 * (-128 - 32 * tq - g);
#pragma unroll
            for (int c = 0; c < 4; c++) {
                const int e = (c & 1) * 16 + (c >> 1) * 8;
                const bool first = c == 0 && lane == 0;
                put_tap(a0 - e / 4, kc[0][c] * sinv);
                put_tap(a0 - 32 - e / 4, kc[1][c] * sinv);
                put_tap(first ? tp + 2 * (O_U - 32) : a2 - e / 2, kc[2][c] * sinv);
                put_tap(first ? tp + 2 * (O_W79 - 63) : a3 - e, kc[3][c] * sinv);
                put_tap(first ? tp + 2 * (O_W610 - 127) : a4 + 2 * (O_W511 + 1 - e), kc[4][c] * sinv);
                if ((g & 1) == 0) {
                    put_tap(a4 + 2 * (O_U4 - e), kc[4][c] * sinv);
                    put_tap(first ? tp + 2 * (O_U3 - 128) : a4 + 2 * (O_U4 + 1 - e), kc[4][c] * sinv);
                }
            }
            if (lane == 0) {
                put_tap(tp + 2 * (O_U + 96 - 32), kc[2][0] * sinv);
                put_tap(tp + 2 * (O_U + 192 - 64), kc[3][0] * sinv);
                put_tap(tp + 2 * (O_W511 - 255), k2048 * sinv);
                put_tap(tp + 2 * (O_U4 - 255), k2048 * sinv);
            }
        }
        TS3(21 + 2 * ch);
        if (ch == 0) { if (!STAGGER || warp < 4) named_bar(1, 384); }
        else {
#pragma unroll
            for (int i = 0; i < 4; i++) asm volatile("prefetch.global.L2 [%0];" :: "l"(wslice + (size_t)((tid & 127) + 128 * i) * DM));
        }
        __syncwarp();
        if (tid == 0) TSS(18, 4 * ch);
        const uint32_t sh = wb + 80 + 11 * SD_ROW;
#pragma unroll
        for (int p = 0; p < 8; p++) {
            uint4 v;
            asm volatile("ld.shared.v4.u32 {%0,%1,%2,%3}, [%4];" : "=r"(v.x), "=r"(v.y), "=r"(v.z), "=r"(v.w) : "r"(ub + p * SD_ROW + lane * 16) : "memory");
            uint32_t pv = __shfl_up_sync(0xffffffffu, v.w, 1);
            pv = lane == 0 ? 0u : pv;
            asm volatile("st.shared.v4.u32 [%0], {%1,%2,%3,%4};" :: "r"(sh + (p - 8) * SD_ROW + lane * 16), "r"(__byte_perm(pv, v.x, 0x5432)), "r"(__byte_perm(v.x, v.y, 0x5432)),
                         "r"(__byte_perm(v.y, v.z, 0x5432)), "r"(__byte_perm(v.z, v.w, 0x5432)) : "memory");
            if (p >= 5) asm volatile("st.shared.v4.u32 [%0], {%1,%2,%3,%4};" :: "r"(sh + (p - 16) * SD_ROW + lane * 16), "r"(pv), "r"(v.x), "r"(v.y), "r"(v.z) : "memory");
        }
        __syncwarp();
        if (tid == 0) TSS(18, 4 * ch + 1);
        float acc[16][4];
#pragma unroll
        for (int i = 0; i < 16; i++) { acc[i][0] = acc[i][1] = acc[i][2] = acc[i][3] = 0.f; }
        {
            const uint32_t ka = wb + SD_TAP + ((g & 1) ? 0 : SD_CPY - 2) + 2 * (2 * tq - g);
            uint32_t b[16][2], b2[14][2];
#pragma unroll
            for (int k = 0; k < 16; k++) { b[k][0] = b[k][1] = 0u; if (k < 14) b2[k][0] = b2[k][1] = 0u; }
#pragma unroll 1
            for (int ps = 0; ps < 14; ps++) {
                const uint32_t pw = __shfl_sync(0xffffffffu, SD_PASS[ps], 0), type = pw & 3u, kp = ka + (pw >> 16);
                const int dl = (pw >> 2) & 7, d0 = (pw >> 8) & 15, d1 = (pw >> 12) & 15;
                uint32_t t[2][4];
                tap_tile(t[0], kp - 32 * d0);
                if (type == 0) {
                    const int p = (lane & 7) - dl;
                    const uint32_t ra = (p < 0 ? sh : ub) + p * SD_ROW + (lane >> 3) * 16;
#pragma unroll
                    for (int k = 0; k < 8; k++)
                        asm volatile("ldmatrix.sync.aligned.m8n8.x4.shared.b16 {%0,%1,%2,%3}, [%4];"
                                     : "=r"(b[2 * k][0]), "=r"(b[2 * k][1]), "=r"(b[2 * k + 1][0]), "=r"(b[2 * k + 1][1]) : "r"(ra + k * 64));
                } else if (type == 2) {
                    const int p = (lane & 15) - 11, xo = 2 * tq - g;
                    const uint32_t qa = (p < 0 ? sh : ub) + p * SD_ROW + (lane >> 4) * 16;
                    const int lx = 6 - 5 * dl, hx = 8 - 3 * dl, ly = 2 - 2 * dl, hy = 4 + 2 * dl;
                    const uint32_t sel[4] = {band2(xo, lx, hx), band2(xo, ly, hy), band2(xo + 8, lx, hx), band2(xo + 8, ly, hy)};
#pragma unroll
                    for (int k = 0; k < 14; k++) {
                        uint32_t q[4];
                        ldsm_x4_t(q, qa + k * 32);
#pragma unroll
                        for (int i = 0; i < 2; i++) {
                            float w[4];
                            mma_z(w, sel, q[2 * i], q[2 * i + 1]);
                            b[k][i] = pack_bf16(w[0], w[1]);
                            b2[k][i] = pack_bf16(w[2], w[3]);
                        }
                    }
                } else if (type == 3) {
#pragma unroll
                    for (int k = 0; k < 14; k++) { b[k][0] = b2[k][0]; b[k][1] = b2[k][1]; }
                }
#pragma unroll
                for (int d = 0; d < 16; d += 2) {
                    if (d >= 8 || d >= d0) {
                        tap_tile(t[1], kp - 32 * (d + 1));
#pragma unroll
                        for (int k = 0; k + d < 16; k++) mma_bf16(acc[k + d], t[0], b[k][0], b[k][1]);
                        if ((d == 2 || d == 4 || d == 8) && d == d1) break;
                        if (d < 14) tap_tile(t[0], kp - 32 * (d + 2));
#pragma unroll
                        for (int k = 0; k + d + 1 < 16; k++) mma_bf16(acc[k + d + 1], t[1], b[k][0], b[k][1]);
                    }
                }
            }
        }
        __syncwarp();
        if (tid == 0) TSS(18, 4 * ch + 2);
        load_prm(d0 + 8 + warp);
        if (ch == 0) { if (lane == 0) wait_cnt(&g_gcnt[0], SD_NCTA * ep); __syncwarp(); }
        if (tid == 0) TSS(18, 4 * ch + 3);
        uint4 gv[8];
#pragma unroll
        for (int i = 0; i < 8; i++) gv[i] = __ldcg(reinterpret_cast<const uint4*>(g_gate) + lane + 32 * i);
        const uint32_t dd = __byte_perm(*reinterpret_cast<const unsigned short*>(dskip + d), 0u, 0x1010);
#pragma unroll
        for (int i = 0; i < 8; i++) {
            uint32_t u[4];
            ldsm_x4_t(u, ub + (lane & 7) * SD_ROW + (lane >> 3) * 16 + i * 64);
            asm volatile("stmatrix.sync.aligned.m8n8.x4.shared.b16 [%0], {%1,%2,%3,%4};"
                         :: "r"(wb + (lane + 32 * i) * 16),
                            "r"(bf2_add(pack_bf16(acc[2 * i][0], acc[2 * i][1]), bf2_mul(u[0], dd))), "r"(bf2_add(pack_bf16(acc[2 * i][2], acc[2 * i][3]), bf2_mul(u[1], dd))),
                            "r"(bf2_add(pack_bf16(acc[2 * i + 1][0], acc[2 * i + 1][1]), bf2_mul(u[2], dd))), "r"(bf2_add(pack_bf16(acc[2 * i + 1][2], acc[2 * i + 1][3]), bf2_mul(u[3], dd))) : "memory");
        }
        if (GATE_Y) gate(tick);
        __syncwarp();
#pragma unroll
        for (int i = 0; i < 8; i++) {
            const uint4 y = *reinterpret_cast<const uint4*>(tab + (lane + 32 * i) * 4);
            *reinterpret_cast<uint4*>(g_y + (((lane >> 1) + 16 * i) * DM + d) * 16 + (lane & 1) * 8) =
                make_uint4(bf2_mul(bf2_sub(0x3f803f80u, gv[i].x), y.x), bf2_mul(bf2_sub(0x3f803f80u, gv[i].y), y.y),
                           bf2_mul(bf2_sub(0x3f803f80u, gv[i].z), y.z), bf2_mul(bf2_sub(0x3f803f80u, gv[i].w), y.w));
        }
        __syncwarp();
        TS3(22 + 2 * ch);
    }
}
__device__ __forceinline__ void s4d_stage_u(unsigned char* smem_raw, const bf16* __restrict__ x, int pt) {
    const int p = pt & 7, w0 = pt >> 3;
    const uint4* src = reinterpret_cast<const uint4*>(x + (size_t)(16 * w0 + p) * DM + blockIdx.x * SD_CH);
    uint32_t* dst = reinterpret_cast<uint32_t*>(smem_raw + p * SD_ROW) + w0;
#pragma unroll 1
    for (int b = 0; b < 4; b++) {
        uint4 v[2][2][2];
#pragma unroll
        for (int i = 0; i < 8; i++) v[i >> 2][(i >> 1) & 1][i & 1] = src[((b * 2 + (i >> 2)) * 256 + ((i >> 1) & 1) * 8) * (DM / 8) + (i & 1)];
#pragma unroll
        for (int i = 0; i < 4; i++) {
            const uint32_t* lo = reinterpret_cast<const uint32_t*>(&v[i >> 1][0][i & 1]);
            const uint32_t* hi = reinterpret_cast<const uint32_t*>(&v[i >> 1][1][i & 1]);
#pragma unroll
            for (int c = 0; c < 8; c++) dst[((i & 1) * 8 + c) * (SD_U / 4) + (b * 2 + (i >> 1)) * 16] = __byte_perm(lo[c >> 1], hi[c >> 1], (c & 1) ? 0x7632 : 0x5410);
        }
    }
    asm volatile("bar.arrive 1, 384;" ::: "memory");
}

constexpr int WOC = DM / 3;
constexpr int TBUF = 5 * DH * 16;
constexpr int XBUF = SEG * DM * 2;
constexpr int SM_BAR = 0;
constexpr int B_SB = 0, B_VX = 16, B_XT = 32, B_XF = 144, B_W = 64, B_E = 136;
constexpr int SM_SC = 256;
constexpr int SM_F = SM_SC + 1280;
constexpr int SM_VM = SM_F + 2048;
constexpr int SM_S = SM_VM + 2048;
constexpr int SM_O = SM_S + 2560;
constexpr int SM_M = SM_O + 2048;
constexpr int SM_WS = 19456;
constexpr int SM_T = SM_WS + 49152;
constexpr int SM_VX = SM_T + 4 * TBUF;
constexpr int SM_X = SM_VX + 2 * 8192;
constexpr int SM_X01 = SM_WS + DM * DH * 2;
__host__ __device__ constexpr int x01_off(int b) { return b < 2 ? 1024 + b * 9216 : SM_X01 + (b == 2 ? 6 : b - 3) * 9216; }
__host__ __device__ constexpr int x23_off(int b) { return b < 3 ? SM_WS + 7 * 16384 + b * 8192 : x01_off(b - 3); }
constexpr int CH_SMEM = SM_X01 + 8 * 8192;
static_assert(SM_M + DM * 16 <= SM_WS && SM_X + 13 * 8192 <= CH_SMEM && NS <= 10 && CH_SMEM <= 232448 && SM_X % 1024 == 0 && SM_X01 % 1024 == 0 && 1024 + 2 * 9216 <= SM_WS, "smem");
__device__ __forceinline__ uint32_t clock32() { uint32_t t; asm volatile("mov.u32 %0, %%clock;" : "=r"(t) :: "memory"); return t; }

__device__ __forceinline__ uint32_t mapa(uint32_t a, uint32_t rank) {
    uint32_t r; asm volatile("mapa.shared::cluster.u32 %0, %1, %2;" : "=r"(r) : "r"(a), "r"(rank)); return r;
}
__device__ __forceinline__ void st_async32(uint32_t addr, uint32_t v, uint32_t mbar) {
    asm volatile("st.async.weak.shared::cluster.mbarrier::complete_tx::bytes.b32 [%0], %1, [%2];" :: "r"(addr), "r"(v), "r"(mbar) : "memory");
}
__device__ __forceinline__ void mbar_init(uint32_t bar, uint32_t cnt) {
    asm volatile("mbarrier.init.shared::cta.b64 [%0], %1;" :: "r"(bar), "r"(cnt) : "memory");
}
__device__ __forceinline__ void mbar_expect(uint32_t bar, uint32_t bytes) {
    asm volatile("mbarrier.arrive.expect_tx.shared::cta.b64 _, [%0], %1;" :: "r"(bar), "r"(bytes) : "memory");
}
__device__ __forceinline__ void mbar_wait(uint32_t bar, uint32_t parity) {
    unsigned it = 0;
    uint32_t ok;
    do {
        ++it;
        asm volatile("{\n.reg .pred p;\nmbarrier.try_wait.parity.shared::cta.b64 p, [%1], %2;\nselp.u32 %0, 1, 0, p;\n}" : "=r"(ok) : "r"(bar), "r"(parity) : "memory");
    } while ((ok == 0u) & (it < SPIN_LIMIT));
}
__device__ __forceinline__ void mbar_wait_fast(uint32_t bar, uint32_t parity) {
    mbar_wait(bar, parity);
}
__device__ __forceinline__ void mbar_wait_long(uint32_t bar, uint32_t parity) {
    unsigned it = 0;
    while (true) {
        uint32_t ok;
        asm volatile("{\n.reg .pred p;\nmbarrier.try_wait.parity.shared::cta.b64 p, [%1], %2, %3;\nselp.u32 %0, 1, 0, p;\n}"
                     : "=r"(ok) : "r"(bar), "r"(parity), "r"(20000u) : "memory");
        if (ok || ++it >= SPIN_LIMIT) break;
    }
}
__device__ __forceinline__ bool mbar_test(uint32_t bar, uint32_t parity) {
    uint32_t ok;
    asm volatile("{\n.reg .pred p;\nmbarrier.test_wait.parity.shared::cta.b64 p, [%1], %2;\nselp.u32 %0, 1, 0, p;\n}" : "=r"(ok) : "r"(bar), "r"(parity) : "memory");
    return ok != 0u;
}
__device__ __forceinline__ uint64_t policy_evict_first() {
    uint64_t pol; asm volatile("createpolicy.fractional.L2::evict_first.b64 %0, 1.0;" : "=l"(pol)); return pol;
}
__device__ __forceinline__ void cluster_sync_all() {
    asm volatile("barrier.cluster.arrive.release.aligned;\nbarrier.cluster.wait.acquire.aligned;" ::: "memory");
}
__device__ __forceinline__ uint4 ld_vol_u4(const uint4* p) {
    uint4 v; asm volatile(LDV4 : "=r"(v.x), "=r"(v.y), "=r"(v.z), "=r"(v.w) : "l"(p) : "memory"); return v;
}
__device__ __forceinline__ void ld_vol_u4_p(uint4& v, const uint4* p, uint32_t pred) {
    asm volatile("{\n.reg .pred p;\nsetp.ne.u32 p, %5, 0;\n@p " LDV4 "\n}"
                 : "+r"(v.x), "+r"(v.y), "+r"(v.z), "+r"(v.w) : "l"(p), "r"(pred) : "memory");
}
__device__ __forceinline__ void st_vol_u4(uint4* p, uint4 v) {
    asm volatile(STV4 :: "l"(p), "r"(v.x), "r"(v.y), "r"(v.z), "r"(v.w) : "memory");
}
__device__ __forceinline__ void mma_bf16_r(float (&d)[4], uint32_t a0, uint32_t a1, uint32_t a2, uint32_t a3, uint32_t b0, uint32_t b1) {
    asm volatile("mma.sync.aligned.m16n8k16.row.col.f32.bf16.bf16.f32 {%0,%1,%2,%3}, {%4,%5,%6,%7}, {%8,%9}, {%0,%1,%2,%3};"
                 : "+f"(d[0]), "+f"(d[1]), "+f"(d[2]), "+f"(d[3])
                 : "r"(a0), "r"(a1), "r"(a2), "r"(a3), "r"(b0), "r"(b1));
}

__device__ __forceinline__ uint64_t smem_desc(uint32_t addr, uint32_t lbo, uint32_t sbo) {
    return (uint64_t)((addr & 0x3FFFF) >> 4) | ((uint64_t)(lbo >> 4) << 16) | ((uint64_t)(sbo >> 4) << 32);
}
__device__ __forceinline__ void wg_fence() { asm volatile("wgmma.fence.sync.aligned;" ::: "memory"); }
__device__ __forceinline__ void wg_commit() { asm volatile("wgmma.commit_group.sync.aligned;" ::: "memory"); }
__device__ __forceinline__ void wg_wait0() { asm volatile("wgmma.wait_group.sync.aligned 0;" ::: "memory"); }
__device__ __forceinline__ void fence_async() { asm volatile("fence.proxy.async.shared::cta;" ::: "memory"); }
__device__ __forceinline__ void wgmma_n64_ss(float (&d)[32], uint64_t adesc, uint64_t bdesc) {
    asm volatile("{\n.reg .pred p;\nsetp.eq.b32 p, 0, 0;\n"
                 "wgmma.mma_async.sync.aligned.m64n64k16.f32.bf16.bf16 {%0,%1,%2,%3,%4,%5,%6,%7,%8,%9,%10,%11,%12,%13,%14,%15,%16,%17,%18,%19,%20,%21,%22,%23,%24,%25,%26,%27,%28,%29,%30,%31}, %32, %33, p, 1, 1, 1, 0;\n}"
                 : "+f"(d[0]), "+f"(d[1]), "+f"(d[2]), "+f"(d[3]), "+f"(d[4]), "+f"(d[5]), "+f"(d[6]), "+f"(d[7]), "+f"(d[8]), "+f"(d[9]), "+f"(d[10]), "+f"(d[11]), "+f"(d[12]), "+f"(d[13]), "+f"(d[14]), "+f"(d[15]), "+f"(d[16]), "+f"(d[17]), "+f"(d[18]), "+f"(d[19]), "+f"(d[20]), "+f"(d[21]), "+f"(d[22]), "+f"(d[23]), "+f"(d[24]), "+f"(d[25]), "+f"(d[26]), "+f"(d[27]), "+f"(d[28]), "+f"(d[29]), "+f"(d[30]), "+f"(d[31])
                 : "l"(adesc), "l"(bdesc));
}
__device__ __forceinline__ void wgmma_n72_ss(float (&d)[36], uint64_t adesc, uint64_t bdesc) {
    asm volatile("{\n.reg .pred p;\nsetp.eq.b32 p, 0, 0;\n"
                 "wgmma.mma_async.sync.aligned.m64n72k16.f32.bf16.bf16 {%0,%1,%2,%3,%4,%5,%6,%7,%8,%9,%10,%11,%12,%13,%14,%15,%16,%17,%18,%19,%20,%21,%22,%23,%24,%25,%26,%27,%28,%29,%30,%31,%32,%33,%34,%35}, %36, %37, p, 1, 1, 1, 0;\n}"
                 : "+f"(d[0]), "+f"(d[1]), "+f"(d[2]), "+f"(d[3]), "+f"(d[4]), "+f"(d[5]), "+f"(d[6]), "+f"(d[7]), "+f"(d[8]), "+f"(d[9]), "+f"(d[10]), "+f"(d[11]), "+f"(d[12]), "+f"(d[13]), "+f"(d[14]), "+f"(d[15]), "+f"(d[16]), "+f"(d[17]), "+f"(d[18]), "+f"(d[19]), "+f"(d[20]), "+f"(d[21]), "+f"(d[22]), "+f"(d[23]), "+f"(d[24]), "+f"(d[25]), "+f"(d[26]), "+f"(d[27]), "+f"(d[28]), "+f"(d[29]), "+f"(d[30]), "+f"(d[31]), "+f"(d[32]), "+f"(d[33]), "+f"(d[34]), "+f"(d[35])
                 : "l"(adesc), "l"(bdesc));
}
__device__ __forceinline__ void tma_2d(uint32_t dst, const CUtensorMap* tm, int c0, int c1, uint32_t mbar) {
    asm volatile("cp.async.bulk.tensor.2d.shared::cluster.global.tile.mbarrier::complete_tx::bytes [%0], [%1, {%2, %3}], [%4];"
                 :: "r"(dst), "l"(tm), "r"(c0), "r"(c1), "r"(mbar) : "memory");
}

__device__ __forceinline__ void bulk_g2s(uint32_t dst, const void* src, uint32_t bytes, uint32_t mbar) {
    asm volatile("cp.async.bulk.shared::cluster.global.mbarrier::complete_tx::bytes [%0], [%1], %2, [%3];"
                 :: "r"(dst), "l"(src), "r"(bytes), "r"(mbar) : "memory");
}
__device__ __forceinline__ void bulk_g2s_h(uint32_t dst, const void* src, uint32_t bytes, uint32_t mbar, uint64_t pol) {
    asm volatile("cp.async.bulk.shared::cluster.global.mbarrier::complete_tx::bytes.L2::cache_hint [%0], [%1], %2, [%3], %4;"
                 :: "r"(dst), "l"(src), "r"(bytes), "r"(mbar), "l"(pol) : "memory");
}
__device__ __forceinline__ void tma_2d_mc(uint32_t dst, const CUtensorMap* tm, int c0, int c1, uint32_t mbar) {
    asm volatile("cp.async.bulk.tensor.2d.shared::cluster.global.tile.mbarrier::complete_tx::bytes.multicast::cluster [%0], [%1, {%2, %3}], [%4], %5;"
                 :: "r"(dst), "l"(tm), "r"(c0), "r"(c1), "r"(mbar), "h"((unsigned short)7) : "memory");
}
__device__ __forceinline__ void bulk_s2s(uint32_t dst, uint32_t src, uint32_t bytes, uint32_t mbar) {
    asm volatile("cp.async.bulk.shared::cluster.shared::cta.mbarrier::complete_tx::bytes [%0], [%1], %2, [%3];"
                 :: "r"(dst), "r"(src), "r"(bytes), "r"(mbar) : "memory");
}
__device__ __forceinline__ void wgmma_n40_ss(float (&d)[20], uint64_t adesc, uint64_t bdesc, int scale_d) {
    asm volatile("{\n.reg .pred p;\nsetp.ne.b32 p, %22, 0;\n"
                 "wgmma.mma_async.sync.aligned.m64n40k16.f32.bf16.bf16 {%0,%1,%2,%3,%4,%5,%6,%7,%8,%9,%10,%11,%12,%13,%14,%15,%16,%17,%18,%19}, %20, %21, p, 1, 1, 1, 1;\n}"
                 : "+f"(d[0]), "+f"(d[1]), "+f"(d[2]), "+f"(d[3]), "+f"(d[4]), "+f"(d[5]), "+f"(d[6]), "+f"(d[7]),
                   "+f"(d[8]), "+f"(d[9]), "+f"(d[10]), "+f"(d[11]), "+f"(d[12]), "+f"(d[13]), "+f"(d[14]), "+f"(d[15]),
                   "+f"(d[16]), "+f"(d[17]), "+f"(d[18]), "+f"(d[19])
                 : "l"(adesc), "l"(bdesc), "r"(scale_d));
}
__device__ __forceinline__ void wgmma_n64_z(float (&d)[32], const uint32_t (&a)[4], uint64_t bdesc) {
    asm volatile("{\n.reg .pred p;\nsetp.ne.b32 p, 0, 0;\n"
                 "wgmma.mma_async.sync.aligned.m64n64k16.f32.bf16.bf16 {%0,%1,%2,%3,%4,%5,%6,%7,%8,%9,%10,%11,%12,%13,%14,%15,%16,%17,%18,%19,%20,%21,%22,%23,%24,%25,%26,%27,%28,%29,%30,%31}, {%32,%33,%34,%35}, %36, p, 1, 1, 0;\n}"
                 : "=f"(d[0]), "=f"(d[1]), "=f"(d[2]), "=f"(d[3]), "=f"(d[4]), "=f"(d[5]), "=f"(d[6]), "=f"(d[7]),
                   "=f"(d[8]), "=f"(d[9]), "=f"(d[10]), "=f"(d[11]), "=f"(d[12]), "=f"(d[13]), "=f"(d[14]), "=f"(d[15]),
                   "=f"(d[16]), "=f"(d[17]), "=f"(d[18]), "=f"(d[19]), "=f"(d[20]), "=f"(d[21]), "=f"(d[22]), "=f"(d[23]),
                   "=f"(d[24]), "=f"(d[25]), "=f"(d[26]), "=f"(d[27]), "=f"(d[28]), "=f"(d[29]), "=f"(d[30]), "=f"(d[31])
                 : "r"(a[0]), "r"(a[1]), "r"(a[2]), "r"(a[3]), "l"(bdesc));
}
__device__ __forceinline__ void wgmma_n64(float (&d)[32], const uint32_t (&a)[4], uint64_t bdesc, int scale_d) {
    asm volatile("{\n.reg .pred p;\nsetp.ne.b32 p, %37, 0;\n"
                 "wgmma.mma_async.sync.aligned.m64n64k16.f32.bf16.bf16 {%0,%1,%2,%3,%4,%5,%6,%7,%8,%9,%10,%11,%12,%13,%14,%15,%16,%17,%18,%19,%20,%21,%22,%23,%24,%25,%26,%27,%28,%29,%30,%31}, {%32,%33,%34,%35}, %36, p, 1, 1, 0;\n}"
                 : "+f"(d[0]), "+f"(d[1]), "+f"(d[2]), "+f"(d[3]), "+f"(d[4]), "+f"(d[5]), "+f"(d[6]), "+f"(d[7]),
                   "+f"(d[8]), "+f"(d[9]), "+f"(d[10]), "+f"(d[11]), "+f"(d[12]), "+f"(d[13]), "+f"(d[14]), "+f"(d[15]),
                   "+f"(d[16]), "+f"(d[17]), "+f"(d[18]), "+f"(d[19]), "+f"(d[20]), "+f"(d[21]), "+f"(d[22]), "+f"(d[23]),
                   "+f"(d[24]), "+f"(d[25]), "+f"(d[26]), "+f"(d[27]), "+f"(d[28]), "+f"(d[29]), "+f"(d[30]), "+f"(d[31])
                 : "r"(a[0]), "r"(a[1]), "r"(a[2]), "r"(a[3]), "l"(bdesc), "r"(scale_d));
}

constexpr int SB_FULL = 0, SB_EMPTY = 64, SB_QKF = 128, SB_VF = 144, SB_QKE = 160, SB_VE = 176, SB_OF = 192, SB_WO = 208, SB_TICK = 216, SB_SEEN = 224, SB_FI = 232, SB_REQ = 240;
constexpr int AT_0 = 256, AT_ST = 10240 + 2 * 9216;
constexpr int FS_A = 58368;
constexpr int FS_P = FS_A + 131072;
constexpr int FS_I = FS_P + 16384;
constexpr int FS_O = FS_I + 12288;
constexpr int FS_Z = FS_O + 12288, FS_G = AT_0 + 2 * AT_ST;
constexpr int SIDE_SMEM = FS_Z + 2048;
static_assert(SIDE_SMEM <= 232448 && FS_G + 128 <= FS_A && FS_A + SD_SMEM <= SIDE_SMEM, "smem");

__device__ __forceinline__ void wg_wait1() { asm volatile("wgmma.wait_group.sync.aligned 1;" ::: "memory"); }
__device__ __forceinline__ void mbar_arrive(uint32_t bar) { asm volatile("mbarrier.arrive.shared::cta.b64 _, [%0];" :: "r"(bar) : "memory"); }
__device__ __forceinline__ void wait_cnt_rlx(const unsigned* p, unsigned target, bool urgent) {
    unsigned it = 0, v;
    while (true) {
        asm volatile("ld.relaxed.gpu.global.u32 %0, [%1];" : "=r"(v) : "l"(p) : "memory");
        if ((int)(v - target) >= 0 || ++it >= SPIN_LIMIT) break;
        if (!urgent) __nanosleep(RLX_SLEEP);
    }
}

__device__ __forceinline__ float xrow_softmax(float (&sc)[20], uint32_t (&p)[5], int wq, int lane) {
    constexpr float EC = (float)(1.4426950408889634 * 0.08838834764831845);
    const int lim = 8 * wq + (lane >> 2) - 2 * (lane & 3);
    float mx = fmaxf(sc[0], sc[1]);
#pragma unroll
    for (int j = 1; j < 5; j++) {
        sc[4 * j] = 8 * j - 8 > lim ? -INFINITY : sc[4 * j];
        sc[4 * j + 1] = 8 * j - 7 > lim ? -INFINITY : sc[4 * j + 1];
    }
    mx = fmaxf(fmaxf(mx, fmaxf(fmaxf(sc[4], sc[5]), fmaxf(sc[8], sc[9]))), fmaxf(fmaxf(sc[12], sc[13]), fmaxf(sc[16], sc[17])));
    {
        const float m1 = __shfl_xor_sync(0xffffffffu, mx, 1), m2 = __shfl_xor_sync(0xffffffffu, mx, 2), m3 = __shfl_xor_sync(0xffffffffu, mx, 3);
        mx = fmaxf(fmaxf(mx, m1), fmaxf(m2, m3)) * EC;
    }
    float sum = 0.f;
#pragma unroll
    for (int j = 0; j < 5; j++) {
        float e0, e1;
        asm("ex2.approx.ftz.f32 %0, %1;" : "=f"(e0) : "f"(fmaf(sc[4 * j], EC, -mx)));
        asm("ex2.approx.ftz.f32 %0, %1;" : "=f"(e1) : "f"(fmaf(sc[4 * j + 1], EC, -mx)));
        p[j] = pack_bf16(e0, e1);
        sum += e0 + e1;
    }
    return sum;
}
__device__ __forceinline__ float xrow_inv(float sum) {
    sum += __shfl_xor_sync(0xffffffffu, sum, 1);
    sum += __shfl_xor_sync(0xffffffffu, sum, 2);
    float r;
    asm("rcp.approx.ftz.f32 %0, %1;" : "=f"(r) : "f"(sum));
    return r;
}

__device__ __forceinline__ void stsm_x4(uint32_t addr, uint32_t r0, uint32_t r1, uint32_t r2, uint32_t r3) {
    asm volatile("stmatrix.sync.aligned.m8n8.x4.shared.b16 [%0], {%1,%2,%3,%4};" :: "r"(addr), "r"(r0), "r"(r1), "r"(r2), "r"(r3) : "memory");
}
__device__ __forceinline__ void xrow_pv(uint32_t (&ob)[16], const uint32_t (&p)[5], float psum, uint32_t vt) {
    float o[32];
    const uint64_t dv = smem_desc(vt, 2048, 128);
    uint32_t pa[6][4];
#pragma unroll
    for (int i = 0; i < 6; i++) {
        const int ks = i >> 1, hf = i & 1;
        pa[i][hf] = p[2 * ks]; pa[i][hf ^ 1] = 0u;
        pa[i][2 + hf] = ks < 2 ? p[ks < 2 ? 2 * ks + 1 : 0] : 0u; pa[i][3 - hf] = 0u;
    }
    wg_fence();
#pragma unroll
    for (int i = 0; i < 6; i++) { if (i == 0) wgmma_n64_z(o, pa[0], dv); else wgmma_n64(o, pa[i], dv + (uint64_t)((i & 1) * 64 + (i >> 1) * 256), 1); }
    wg_commit();
    const float inv = xrow_inv(psum);
    wg_wait0();
#pragma unroll
    for (int i = 0; i < 8; i++) { ob[i] = pack_bf16(o[4 * i] * inv, o[4 * i + 1] * inv); ob[8 + i] = pack_bf16(o[4 * i + 2] * inv, o[4 * i + 3] * inv); }
}
__device__ __forceinline__ uint32_t h2_to_bf2(uint32_t h) {
    uint32_t r;
    asm("{\n.reg .f16 l, h;\n.reg .f32 a, b;\nmov.b32 {l, h}, %1;\ncvt.f32.f16 a, l;\ncvt.f32.f16 b, h;\ncvt.rn.bf16x2.f32 %0, b, a;\n}" : "=r"(r) : "r"(h));
    return r;
}
__device__ __forceinline__ uint32_t max_abs2(uint32_t a, uint32_t b) { uint32_t r; asm("max.NaN.xorsign.abs.bf16x2 %0, %1, %2;" : "=r"(r) : "r"(a), "r"(b)); return r; }
__device__ __forceinline__ uint32_t movm(uint32_t v) {
    uint32_t r; asm volatile("movmatrix.sync.aligned.m8n8.trans.b16 %0, %1;" : "=r"(r) : "r"(v)); return r;
}
__device__ __forceinline__ void bar_arrive(int id, int n) { asm volatile("bar.arrive %0, %1;" :: "r"(id), "r"(n) : "memory"); }
__device__ __forceinline__ void lds64(uint32_t& a, uint32_t& b, uint32_t addr) {
    asm volatile("ld.shared.v2.u32 {%0,%1}, [%2];" : "=r"(a), "=r"(b) : "r"(addr) : "memory");
}
__device__ __forceinline__ void lds64f(float& a, float& b, uint32_t addr) {
    asm volatile("ld.shared.v2.f32 {%0,%1}, [%2];" : "=f"(a), "=f"(b) : "r"(addr) : "memory");
}
__device__ __forceinline__ void st_async64(uint32_t addr, uint32_t a, uint32_t b, uint32_t mbar) {
    asm volatile("st.async.weak.shared::cluster.mbarrier::complete_tx::bytes.v2.b32 [%0], {%1,%2}, [%3];" :: "r"(addr), "r"(a), "r"(b), "r"(mbar) : "memory");
}
__device__ __forceinline__ void mma_z(float (&d)[4], const uint32_t (&a)[4], uint32_t b0, uint32_t b1) {
    asm volatile("mma.sync.aligned.m16n8k16.row.col.f32.bf16.bf16.f32 {%0,%1,%2,%3}, {%4,%5,%6,%7}, {%8,%9}, {%10,%10,%10,%10};"
                 : "=f"(d[0]), "=f"(d[1]), "=f"(d[2]), "=f"(d[3])
                 : "r"(a[0]), "r"(a[1]), "r"(a[2]), "r"(a[3]), "r"(b0), "r"(b1), "f"(0.f));
}
__device__ __forceinline__ void mma_k8(float (&d)[4], uint32_t a0, uint32_t a1, uint32_t b) {
    asm volatile("mma.sync.aligned.m16n8k8.row.col.f32.bf16.bf16.f32 {%0,%1,%2,%3}, {%4,%5}, {%6}, {%0,%1,%2,%3};"
                 : "+f"(d[0]), "+f"(d[1]), "+f"(d[2]), "+f"(d[3]) : "r"(a0), "r"(a1), "r"(b));
}
__global__ void __launch_bounds__(512, 1) k_side(const __grid_constant__ CUtensorMap tmo, const bf16* __restrict__ x, const bf16* __restrict__ logA, const bf16* __restrict__ Aim,
                                                 const bf16* __restrict__ Cre, const bf16* __restrict__ Cim, const bf16* __restrict__ logdt,
                                                 const bf16* __restrict__ Wo, const bf16* __restrict__ dskip, const bf16* __restrict__ gw,
                                                 bf16* __restrict__ out) {
    extern __shared__ __align__(1024) unsigned char smem_raw[];
    const uint32_t sbase = smem_u32(smem_raw);
    const int tid = threadIdx.x, warp = __shfl_sync(0xffffffffu, tid >> 5, 0), lane = tid & 31, cta = blockIdx.x;
    const int cb = cta >> 2, kq = cta & 3;
    if (tid == 0) {
        for (int i = 0; i < 8; i++) { mbar_init(sbase + SB_FULL + 8 * i, 1); mbar_init(sbase + SB_EMPTY + 8 * i, 4); }
        for (int i = 0; i < 2; i++) {
            mbar_init(sbase + SB_QKF + 8 * i, 1); mbar_init(sbase + SB_VF + 8 * i, 1); mbar_init(sbase + SB_QKE + 8 * i, 4);
            mbar_init(sbase + SB_VE + 8 * i, 1); mbar_init(sbase + SB_OF + 8 * i, 4);
        }
        mbar_init(sbase + SB_WO, 1);
        mbar_init(sbase + SB_FI, 1);
        mbar_init(sbase + SB_REQ, 4);
        *reinterpret_cast<uint2*>(smem_raw + SB_TICK) = make_uint2(0u, 0u);
        *reinterpret_cast<uint32_t*>(smem_raw + SB_SEEN) = 0u;
        asm volatile("fence.mbarrier_init.release.cluster;" ::: "memory");
    }
    TS3(0);
    unsigned ep;
    asm volatile("ld.volatile.global.u32 %0, [%1];" : "=r"(ep) : "l"(&g_epoch) : "memory");
    ep += 1u;
    asm volatile("fence.proxy.async;" ::: "memory");
    __syncthreads();
    if (warp >= 12) {
      asm volatile("setmaxnreg.dec.sync.aligned.u32 40;");
      if (SIDE_WAIT > 0) __nanosleep(SIDE_WAIT);
      {
        uint32_t gwv[9];
#pragma unroll
        for (int i = 0; i < 9; i++) gwv[i] = reinterpret_cast<const uint32_t*>(gw)[lane + 32 * i];
#pragma unroll 1
        for (int i = 0; i < 8; i++) {
            uint32_t xv[2][9];
            float sm[2];
#pragma unroll
            for (int j = 0; j < 2; j++) {
                const int t = min(cta * 57 + 8 * i + 4 * j + warp - 12, S_LEN - 1);
#pragma unroll
                for (int k = 0; k < 9; k++) xv[j][k] = reinterpret_cast<const uint32_t*>(x + t * DM)[lane + 32 * k];
            }
#pragma unroll
            for (int j = 0; j < 2; j++) {
                sm[j] = 0.f;
#pragma unroll
                for (int k = 0; k < 9; k++) {
                    const uint32_t pr = bf2_mul(xv[j][k], gwv[k]);
                    sm[j] += __uint_as_float(pr << 16) + __uint_as_float(pr & 0xffff0000u);
                }
            }
            float v = (lane < 16 ? sm[0] : sm[1]) + __shfl_xor_sync(0xffffffffu, lane < 16 ? sm[1] : sm[0], 16);
#pragma unroll
            for (int o = 8; o; o >>= 1) v += __shfl_xor_sync(0xffffffffu, v, o);
            const float gv = 1.f / (1.f + expf(-bf16r(v)));
            const int tt = 8 * i + 4 * (lane >> 4) + warp - 12;
            if ((lane & 15) == 0 && tt < 57 && cta * 57 + tt < S_LEN) g_gate[cta * 57 + tt] = __float2bfloat16_rn(gv);
        }
        named_bar(2, 128);
        if (tid == 480) {
            __threadfence();
            asm volatile("red.relaxed.gpu.global.add.u32 [%0], 1;" :: "l"(&g_gcnt[0]) : "memory");
        }
        __syncwarp();
      }
      if (warp == 12 || warp == 15) {
        named_bar(3, 320);
        if (tid == 384) {
            fence_async();
            mbar_expect(sbase + SB_WO, 131072);
#pragma unroll 1
            for (int i = 0; i < 8; i++) {
                gate(sbase + SB_TICK);
                tma_2d(sbase + FS_A + i * 16384, &tmo, cb * 64, kq * 1024 + i * 128, sbase + SB_WO);
                __nanosleep(150);
            }
            TSS(17, 2);
        }
        if (tid == 480) {
            __threadfence();
            asm volatile("red.relaxed.gpu.global.add.u32 [%0], 1;" :: "l"(&g_gcnt[32]) : "memory");
            TSS(17, 3);
        }
        __syncwarp();
        named_bar(7, 320);
        if (lane == 0) {
            const int pi = warp == 12 ? 0 : 1, kb = 2 * kq + pi;
            fence_async();
            for (int pr = 0; pr < NSEG / 2; pr++) {
                const bool gon = pr < NSEG / 2 - UNGATE_G;
                wait_cnt_rlx(&g_prog[pr * 8 + kb], 8u * ep, pr >= NSEG / 2 - 2);
                if (pi == 0) asm volatile("st.volatile.shared.u32 [%0], %1;" :: "r"(sbase + SB_SEEN), "r"(pr + 1) : "memory");
                if (pr >= 30 && pi == 0) TSS(4 + pr - 30, 0);
                if (pr == 31) TS3P(26);
                if (pr == 30) TS3P(1);
#pragma unroll
                for (int j = 0; j < 4; j++) {
                    const int st = 4 * pi + j;
                    mbar_wait_long(sbase + SB_EMPTY + 8 * st, ((uint32_t)pr & 1u) ^ 1u);
                    mbar_expect(sbase + SB_FULL + 8 * st, X_OXSZ);
                    if (gon) gate(sbase + SB_TICK);
                    bulk_g2s(sbase + FS_A + st * 16384, g_ox + ((size_t)(pr * NH + 4 * kb + j)) * 8192, X_OXSZ, sbase + SB_FULL + 8 * st);
                }
            }
        }
        __syncwarp();
      } else if (warp == 13) {
        if (lane == 0) {
            const uint64_t pol = policy_evict_first();
            bool next_ok = false;
            for (int seg = 0; seg < NATT; seg++) {
                const uint32_t st = seg & 1, ph = (uint32_t)(seg >> 1) & 1u, ab = sbase + AT_0 + st * AT_ST;
                if (!next_ok) {
                    const unsigned* fp = &g_flag[(cta & (NH - 1)) * NSEG + seg];
                    unsigned it = 0, v0, v1;
                    while (true) {
                        asm volatile("ld.relaxed.gpu.global.u32 %0, [%1];" : "=r"(v0) : "l"(fp) : "memory");
                        asm volatile("ld.relaxed.gpu.global.u32 %0, [%1+4];" : "=r"(v1) : "l"(fp) : "memory");
                        read_tick(sbase + SB_TICK);
                        if ((int)(v0 - 3u * ep) >= 0 || ++it >= SPIN_LIMIT) break;
                        if (seg < NSEG - UNGATE || cta >= NH) { __nanosleep(RLX_SLEEP); if (GATE_POLL) gate(sbase + SB_TICK, GP_A, GP_B); }
                    }
                    next_ok = (int)(v1 - 3u * ep) >= 0;
                } else next_ok = false;
                if (cta < NH) {
                    TSA(seg, 0);
                    mbar_wait_long(sbase + SB_QKE + 8 * st, ph ^ 1u);
                    TSA(seg, 1);
                    mbar_expect(sbase + SB_QKF + 8 * st, 2 * 9216);
                    if (seg < NSEG - UNGATE) gate(sbase + SB_TICK, GL_A, GL_B);
                    TSA(seg, 2);
                    bulk_g2s_h(ab + 10240, &g_qkv[seg][cta][0][1024], 9216, sbase + SB_QKF + 8 * st, pol);
                    bulk_g2s_h(ab + 10240 + 9216, &g_qkv[seg][cta][1][1024], 9216, sbase + SB_QKF + 8 * st, pol);
                    mbar_wait_long(sbase + SB_VE + 8 * st, ph ^ 1u);
                    mbar_expect(sbase + SB_VF + 8 * st, 10240);
                    if (seg < NSEG - UNGATE) gate(sbase + SB_TICK, GL_A, GL_B);
                    TSA(seg, 3);
                    bulk_g2s_h(ab, &g_qkv[seg][cta][2][0], 10240, sbase + SB_VF + 8 * st, pol);
                }
            }
        }
        __syncwarp();
      } else if (warp == 14) {
        if (lane == 0) {
            int seg = cta < NH ? 0 : NATT, p = 0;
            unsigned it = 0;
            while ((seg < NATT || p < NSEG / 2 - 1) && ++it < 16 * SPIN_LIMIT) {
                if (p < NSEG / 2 - 1 && mbar_test(sbase + SB_REQ, (uint32_t)p & 1u)) {
                    if (p == 0) { wait_cnt(&g_gcnt[32], SD_NCTA * ep); asm volatile("fence.proxy.async;" ::: "memory"); }
                    mbar_expect(sbase + SB_FI, (p < NSEG / 2 - 2 ? 12288 : 2048 + 32) + 2048 + 32);
                    if (GATE_F && p < NSEG / 2 - UNGATE_G - 1) gate(sbase + SB_TICK);
                    if (p < NSEG / 2 - 2) bulk_g2s(sbase + FS_I, &g_fp[p & 7][cta][0][0], 12288, sbase + SB_FI);
                    else {
                        bulk_g2s(sbase + FS_I, g_y + ((p * 4 + 4 + kq) * DM + cb * 64) * 16, 2048, sbase + SB_FI);
                        bulk_g2s(sbase + FS_G + 32, g_gate + p * 64 + 64 + kq * 16, 32, sbase + SB_FI);
                    }
                    bulk_g2s(sbase + FS_Z, g_y + ((p * 4 + kq) * DM + cb * 64) * 16, 2048, sbase + SB_FI);
                    bulk_g2s(sbase + FS_G, g_gate + p * 64 + kq * 16, 32, sbase + SB_FI);
                    p++;
                } else if (seg < NATT && mbar_test(sbase + SB_OF + 8 * (seg & 1), (uint32_t)(seg >> 1) & 1u)) {
                    const uint32_t st = seg & 1, ab = sbase + AT_0 + st * AT_ST;
                    TSA(seg, 5);
                    if (seg < NSEG - UNGATE) gate(sbase + SB_TICK, GS_A, GS_B);
                    TSA(seg, 6);
                    unsigned char* dst = reinterpret_cast<unsigned char*>(g_ox) + ((size_t)((seg >> 1) * NH + cta)) * 16384 + (seg & 1) * 4096;
                    asm volatile("cp.async.bulk.global.shared::cta.bulk_group [%0], [%1], 4096;" :: "l"(dst), "r"(ab) : "memory");
                    asm volatile("cp.async.bulk.global.shared::cta.bulk_group [%0], [%1], 4096;" :: "l"(dst + 8192), "r"(ab + 4096) : "memory");
                    asm volatile("cp.async.bulk.commit_group;" ::: "memory");
                    asm volatile("cp.async.bulk.wait_group.read 0;" ::: "memory");
                    mbar_arrive(sbase + SB_VE + 8 * st);
                    asm volatile("cp.async.bulk.wait_group 0;" ::: "memory");
                    asm volatile("red.relaxed.gpu.global.add.u32 [%0], 1;" :: "l"(&g_prog[(seg >> 1) * 8 + (cta >> 2)]) : "memory");
                    TSA(seg, 7);
                    seg++;
                } else if (seg < NSEG - UNGATE) __nanosleep(W14_SLEEP);
            }
        }
        __syncwarp();
      }
    } else if (warp >= 8) {
        asm volatile("setmaxnreg.dec.sync.aligned.u32 88;");
        if (SIDE_WAIT > 0) __nanosleep(SIDE_WAIT);
        s4d_stage_u(smem_raw + FS_A, x, tid - 256);
        const int wq = warp - 8;
        for (int seg = 0; seg < (cta < NH ? NATT : 0); seg++) {
            const uint32_t st = seg & 1, ph = (uint32_t)(seg >> 1) & 1u, ab = sbase + AT_0 + st * AT_ST;
            float sc[20];
            if (seg < NSEG - UNGATE) mbar_wait_long(sbase + SB_QKF + 8 * st, ph); else mbar_wait(sbase + SB_QKF + 8 * st, ph);
            if (tid == 256) TSA(seg, 4);
            {
                const uint64_t da = smem_desc(ab + 10240 + 1024, 128, 1024), db = smem_desc(ab + 10240, 128, 2048);
                wg_fence();
#pragma unroll
                for (int ks = 0; ks < 8; ks++) wgmma_n40_ss(sc, da + (uint64_t)((ks >> 2) * 576 + (ks & 3) * 16), db + (uint64_t)((ks >> 2) * 576 + (ks & 3) * 16), ks > 0);
                wg_commit();
                wg_wait0();
            }
            if (lane == 0) mbar_arrive(sbase + SB_QKE + 8 * st);
            uint32_t p[5], ob[16];
            const float psum = xrow_softmax(sc, p, wq, lane);
            mbar_wait(sbase + SB_VF + 8 * st, ph);
            xrow_pv(ob, p, psum, ab);
            named_bar(6, 128);
#pragma unroll
            for (int i = 0; i < 4; i++) stsm_x4(ab + (i >> 1) * 4096 + wq * 1024 + (i & 1) * 512 + lane * 16, ob[4 * i], ob[4 * i + 1], ob[4 * i + 2], ob[4 * i + 3]);
            fence_async();
            __syncwarp();
            if (lane == 0) mbar_arrive(sbase + SB_OF + 8 * st);
        }
    } else {
        asm volatile("setmaxnreg.inc.sync.aligned.u32 192;");
        const int wg = warp >> 2, wq = warp & 3;
        s4d_phase(smem_raw + FS_A, x, logA, Aim, Cre, Cim, logdt, dskip, Wo + (size_t)((2 * kq + wg) * 512) * DM + cb * 64, ep, sbase + SB_TICK);
        TS3(2);
        if (lane == 0) TSS(16, warp);
        named_bar(3, 320);
        if (tid == 0) TSS(17, 0);
        uint32_t wa[32][4];
        mbar_wait_long(sbase + SB_WO, 0);
        if (tid == 0) TSS(17, 1);
        {
            const uint32_t a = sbase + FS_A + wg * 65536 + ((lane >> 4) * 8 + (lane & 7)) * 128 + (((wq * 2 + ((lane >> 3) & 1)) ^ (lane & 7)) << 4);
#pragma unroll
            for (int ks = 0; ks < 32; ks++) ldsm_x4_t(wa[ks], a + ks * 2048);
        }
        named_bar(7, 320);
        TS3(3);
        if (tid == 0) TSS(17, 4);
        auto product = [&](float (&acc)[32], int pr, const int wg) {
                if (pr + wg > 0 && (TURN31 || pr + wg < NSEG / 2)) named_bar(4 + wg, 256);
                const uint64_t db = smem_desc(sbase + FS_A + wg * 65536, 128, 1024);
                TSG(0);
#pragma unroll
                for (int j = 0; j < 4; j++) {
                    mbar_wait(sbase + SB_FULL + 8 * (4 * wg + j), (uint32_t)pr & 1u);
                    if (j == 0) TSG(1);
                    if (j == 3) TSG(2);
                    wg_fence();
#pragma unroll
                    for (int ks = 0; ks < 8; ks++) {
                        if ((j | ks) == 0) wgmma_n64_z(acc, wa[0], db);
                        else wgmma_n64(acc, wa[8 * j + ks], db + (uint64_t)(j * 1024 + (ks >> 2) * 512 + (ks & 3) * 16), 1);
                    }
                    wg_commit();
                    if (j == 3 && pr + (TURN31 ? wg : 1) < NSEG / 2) bar_arrive(4 + (wg ^ 1), 256);
                    if (j > 0) { wg_wait1(); if (lane == 0) mbar_arrive(sbase + SB_EMPTY + 8 * (4 * wg + j - 1)); }
                }
                wg_wait0();
                if (pr == 31) TS3W(27);
                TSG(3);
                if (lane == 0) mbar_arrive(sbase + SB_EMPTY + 8 * (4 * wg + 3));
        };
        if (wg == 1) {
            for (int pr = 0; pr < NSEG / 2; pr++) {
                uint32_t t16 = (uint32_t)(wq * 32 + lane) * 16u;
                asm volatile("" : "+r"(t16));
                float acc[32];
                product(acc, pr, 1);
                    uint32_t tag = ((uint32_t)(pr >> 3) & 1u) ^ 1u;
                    tag = __shfl_sync(0xffffffffu, tag, lane);
                    if (GATE_S && pr < NSEG / 2 - UNGATE_G) gate(sbase + SB_TICK);
                    named_bar(8, 256);
                    unsigned char* dst = reinterpret_cast<unsigned char*>(&g_fp[pr & 7][4 * cb][2 * kq - 2][0]) + t16;
                    const uint32_t own = sbase + FS_O + (pr % 3) * 4096 + t16;
#pragma unroll
                    for (int q = 0; q < 8; q++) {
                        float4 p;
                        asm volatile("ld.shared.v4.f32 {%0,%1,%2,%3}, [%4];" : "=f"(p.x), "=f"(p.y), "=f"(p.z), "=f"(p.w) : "r"(sbase + FS_P + t16 + q * 2048) : "memory");
                        acc[4 * q] = __uint_as_float((__float_as_uint(acc[4 * q] + p.x) & ~1u) | tag); acc[4 * q + 1] = __uint_as_float((__float_as_uint(acc[4 * q + 1] + p.y) & ~1u) | tag);
                        acc[4 * q + 2] = __uint_as_float((__float_as_uint(acc[4 * q + 2] + p.z) & ~1u) | tag); acc[4 * q + 3] = __uint_as_float((__float_as_uint(acc[4 * q + 3] + p.w) & ~1u) | tag);
                    }
#pragma unroll
                    for (int q = 0; q < 8; q++) {
                        asm volatile("{\n.reg .pred p;\nsetp.ne.s32 p, %5, %6;\n@p st.volatile.global.v4.f32 [%0], {%1,%2,%3,%4};\n@!p st.shared.v4.f32 [%7], {%1,%2,%3,%4};\n}"
                                     :: "l"(dst + (q & 1) * 2048), "f"(acc[4 * q]), "f"(acc[4 * q + 1]), "f"(acc[4 * q + 2]), "f"(acc[4 * q + 3]), "r"(q >> 1), "r"(kq),
                                        "r"(own + (q & 1) * 2048) : "memory");
                        if (q & 1) dst += (q >> 1) == kq ? 12288 + 4096 : 12288;
                    }
                    bar_arrive(9, 256);
                    if (pr == 31) TS3W(28);
                TSG(4);
            }
        } else {
          int nsync = 0;
          int np = 1, nf = 0, pr = 0, pf = -1;
          while (true) {
            uint32_t t16 = (uint32_t)(wq * 32 + lane) * 16u;
            asm volatile("" : "+r"(t16));
            if (pr < 0) {
                if (nsync <= pf) { named_bar(9, 256); nsync++; }
                if (lane == 0 && pf < NSEG / 2 - 1) mbar_arrive(sbase + SB_REQ);
            } else {
                float acc[32];
                product(acc, pr, 0);
                if (nsync < pr) { named_bar(9, 256); nsync++; }
#pragma unroll
                for (int q = 0; q < 8; q++)
                    asm volatile("st.shared.v4.f32 [%0], {%1,%2,%3,%4};" :: "r"(sbase + FS_P + t16 + q * 2048), "f"(acc[4 * q]), "f"(acc[4 * q + 1]), "f"(acc[4 * q + 2]), "f"(acc[4 * q + 3]) : "memory");
                bar_arrive(8, 256);
                TSG(4);
            }
            uint32_t w[4] = {0u, 0u, 0u, 0u};
            const int pc = pf;
            if (pf >= 0) {
                const uint32_t tag = ((uint32_t)(pf >> 3) & 1u) ^ 1u;
                uint4 v[8];
                unsigned n = 0;
                const bool last = pf == NSEG / 2 - 1;
                const uint4* src = reinterpret_cast<const uint4*>(reinterpret_cast<const unsigned char*>(&g_fp[pf & 7][cta][0][0]) + t16);
                if (pf >= NSEG / 2 - 2) {
#pragma unroll
                    for (int r = 0; r < 6; r++) v[r] = ld_vol_u4(src + r * 128);
                    mbar_wait(sbase + SB_FI, 0u);
                } else {
                    mbar_wait(sbase + SB_FI, (uint32_t)pf & 1u);
#pragma unroll
                    for (int r = 0; r < 6; r++)
                        asm volatile("ld.shared.v4.u32 {%0,%1,%2,%3}, [%4];" : "=r"(v[r].x), "=r"(v[r].y), "=r"(v[r].z), "=r"(v[r].w) : "r"(sbase + t16 + FS_I + r * 2048) : "memory");
                }
                while (true) {
                    uint32_t any = 0u;
#pragma unroll
                    for (int r = 0; r < 6; r++) {
                        uint32_t c0_, c1_;
                        asm("lop3.b32 %0, %1, %2, %3, 0x7e;" : "=r"(c0_) : "r"(v[r].x), "r"(v[r].y), "r"(tag));
                        asm("lop3.b32 %0, %1, %2, %3, 0x7e;" : "=r"(c1_) : "r"(v[r].z), "r"(v[r].w), "r"(tag));
                        asm("lop3.b32 %0, %1, %2, %3, 0xfe;" : "=r"(any) : "r"(any), "r"(c0_), "r"(c1_));
                    }
                    if (!__any_sync(0xffffffffu, (any & 1u) != 0u) || ++n >= SPIN_LIMIT) break;
                    if (pf < NSEG / 2 - 2) __nanosleep(200);
#pragma unroll
                    for (int r = 0; r < 6; r++) v[r] = ld_vol_u4(src + r * 128);
                }
                if (pf == 31) TS3(29);
                TSG(5);
#pragma unroll
                for (int r = 6; r < 8; r++)
                    asm volatile("ld.shared.v4.u32 {%0,%1,%2,%3}, [%4];" : "=r"(v[r].x), "=r"(v[r].y), "=r"(v[r].z), "=r"(v[r].w)
                                 : "r"(sbase + t16 + FS_O + (pf % 3) * 4096 + (r - 6) * 2048) : "memory");
                uint32_t zv[4], gg[2];
                ldsm_x4_t(zv, sbase + (last ? FS_I : FS_Z) + (wq * 16 + (lane & 15)) * 32 + (lane >> 4) * 16);
#pragma unroll
                for (int k = 0; k < 2; k++) gg[k] = __byte_perm(*reinterpret_cast<const volatile unsigned short*>(smem_raw + FS_G + (last ? 32 : 0) + k * 16 + (lane >> 2) * 2), 0u, 0x1010);
#define PQS(k, f) (((__uint_as_float(v[k].f) + __uint_as_float(v[2 + k].f)) + __uint_as_float(v[4 + k].f)) + __uint_as_float(v[6 + k].f))
#pragma unroll
                for (int k = 0; k < 2; k++) {
                    w[2 * k] = bf2_add(bf2_mul(gg[k], movm(pack_bf16(PQS(k, x), PQS(k, y)))), zv[2 * k]);
                    w[2 * k + 1] = bf2_add(bf2_mul(gg[k], movm(pack_bf16(PQS(k, z), PQS(k, w)))), zv[2 * k + 1]);
                }
#undef PQS
            }
            const bool more = nf < NSEG / 2;
            if (more) {
                uint32_t r;
                asm volatile("{\n.reg .pred p, q;\n.reg .b32 v;\nld.volatile.shared.u32 v, [%1];\nsetp.gt.s32 p, v, %2;\nbar.red.or.pred q, 10, 128, p;\nselp.u32 %0, 1, 0, q;\n}"
                             : "=r"(r) : "r"(sbase + SB_SEEN), "r"(np) : "memory");
                const bool dop = np < NSEG / 2 && (__shfl_sync(0xffffffffu, r, 0) != 0u || nf == np || nf >= NSEG / 2 - 2);
                TSG(6);
                pr = dop ? np++ : -1;
                pf = !dop || nf + (pr == NSEG / 2 - 1 ? 1 : 2) <= pr ? nf++ : -1;
                if (dop && pf >= 0 && lane == 0) mbar_arrive(sbase + SB_REQ);
            }
            if (pc >= 0) {
                unsigned char* op = reinterpret_cast<unsigned char*>(out) + (uint32_t)((pc * 64 + kq * 16 + (lane >> 2)) * DM + cb * 64 + wq * 16 + 2 * (lane & 3)) * 2u;
#pragma unroll
                for (int k = 0; k < 4; k++) *reinterpret_cast<uint32_t*>(op + (k >> 1) * (16 * DM) + (k & 1) * 16) = w[k];
                if ((pc & 1) == 0) TS3(4 + pc / 2);
                if (pc == 31) TS3(25);
            }
            if (!more) break;
          }
        }
        if (cta == 0 && tid == 0) asm volatile("red.relaxed.gpu.global.add.u32 [%0], 1;" :: "l"(&g_epoch) : "memory");
    }
    asm volatile("griddepcontrol.wait;" ::: "memory");
}

template <class F>
__device__ __forceinline__ uint32_t poll_mem(const uint4* src, uint32_t dst, uint32_t t0, F next) {
    uint4 v[6];
    unsigned it = 0;
#pragma unroll
    for (int j = 0; j < 6; j++) v[j] = make_uint4(0u, 0u, 0u, 0u);
    while (clock32() - t0 < POLL_DELAY) {}
    FS(12, 0);
    bool more;
#pragma unroll 1
    do {
        asm volatile("{\n.reg .pred p<6>;\n"
                     "setp.ne.u32 p0, %3, 0x5000;\nsetp.ne.u32 p1, %7, 0x5000;\nsetp.ne.u32 p2, %11, 0x5000;\n"
                     "setp.ne.u32 p3, %15, 0x5000;\nsetp.ne.u32 p4, %19, 0x5000;\nsetp.ne.u32 p5, %23, 0x5000;\n"
                     "@p0 ld.volatile.global.v4.u32 {%0,%1,%2,%3}, [%24];\n@p1 ld.volatile.global.v4.u32 {%4,%5,%6,%7}, [%24+4096];\n"
                     "@p2 ld.volatile.global.v4.u32 {%8,%9,%10,%11}, [%24+8192];\n@p3 ld.volatile.global.v4.u32 {%12,%13,%14,%15}, [%24+12288];\n"
                     "@p4 ld.volatile.global.v4.u32 {%16,%17,%18,%19}, [%24+16384];\n@p5 ld.volatile.global.v4.u32 {%20,%21,%22,%23}, [%24+20480];\n}"
                     : "+r"(v[0].x), "+r"(v[0].y), "+r"(v[0].z), "+r"(v[0].w), "+r"(v[1].x), "+r"(v[1].y), "+r"(v[1].z), "+r"(v[1].w),
                       "+r"(v[2].x), "+r"(v[2].y), "+r"(v[2].z), "+r"(v[2].w), "+r"(v[3].x), "+r"(v[3].y), "+r"(v[3].z), "+r"(v[3].w),
                       "+r"(v[4].x), "+r"(v[4].y), "+r"(v[4].z), "+r"(v[4].w), "+r"(v[5].x), "+r"(v[5].y), "+r"(v[5].z), "+r"(v[5].w)
                     : "l"(src) : "memory");
        stsm_x4(dst, h2_to_bf2(v[0].x), h2_to_bf2(v[0].y), h2_to_bf2(v[0].z), h2_to_bf2(v[1].x));
        stsm_x4(dst + 512, h2_to_bf2(v[1].y), h2_to_bf2(v[1].z), h2_to_bf2(v[2].x), h2_to_bf2(v[2].y));
        const uint32_t all = ((v[0].w & v[1].w) & (v[2].w & v[3].w)) & (v[4].w & v[5].w);
        more = __any_sync(0xffffffffu, (all & 0x5000u) != 0x5000u && ++it < SPIN_LIMIT);
        stsm_x4(dst + 1024, h2_to_bf2(v[2].z), h2_to_bf2(v[3].x), h2_to_bf2(v[3].y), h2_to_bf2(v[3].z));
        asm volatile("stmatrix.sync.aligned.m8n8.x2.shared.b16 [%0], {%1,%2};" :: "r"(dst + 1536), "r"(h2_to_bf2(v[4].x)), "r"(h2_to_bf2(v[4].y)) : "memory");
        stsm_x4(dst + 1792, h2_to_bf2(v[4].z), h2_to_bf2(v[5].x), h2_to_bf2(v[5].y), h2_to_bf2(v[5].z));
        asm volatile("{\n.reg .pred p;\nsetp.eq.u32 p, %0, 0;\n@p bar.sync 1, 384;\n}" :: "r"((uint32_t)more) : "memory");
    } while (more);
    next();
    FS(13, it);
    FS(14, 0);
    uint32_t m = v[0].x, m1 = v[0].y, m2 = v[0].z;
#pragma unroll
    for (int j = 1; j < 6; j++) {
        asm volatile("max.NaN.xorsign.abs.f16x2 %0, %0, %1;" : "+r"(m) : "r"(v[j].x));
        asm volatile("max.NaN.xorsign.abs.f16x2 %0, %0, %1;" : "+r"(m1) : "r"(v[j].y));
        asm volatile("max.NaN.xorsign.abs.f16x2 %0, %0, %1;" : "+r"(m2) : "r"(v[j].z));
    }
    asm volatile("max.NaN.xorsign.abs.f16x2 %0, %0, %1;" : "+r"(m) : "r"(m1));
    asm volatile("max.NaN.xorsign.abs.f16x2 %0, %0, %1;" : "+r"(m) : "r"(m2));
    return h2_to_bf2(m) & 0x7fff7fffu;
}

template <int N> __device__ __forceinline__ void pad_code() {
#pragma unroll
    for (int i = 0; i < N; i++) asm volatile("pmevent 7;" ::: "memory");
}
template <bool V> struct Flag { static constexpr bool value = V; };
struct RFlag { bool value; };
__device__ __forceinline__ void score_group(const uint32_t (&a)[2][4], const uint32_t (&kf)[2][4], uint32_t d0, uint32_t d1, uint32_t m1, uint32_t d2, uint32_t m2) {
    FS(4, a[1][0]);
    float sc[4][4];
    mma_z(sc[0], a[0], kf[0][0], kf[0][1]);
    mma_z(sc[1], a[0], kf[0][2], kf[0][3]);
    mma_z(sc[2], a[1], kf[1][0], kf[1][1]);
    mma_z(sc[3], a[1], kf[1][2], kf[1][3]);
    constexpr float EC = (float)(1.4426950408889634 * 0.08838834764831845);
    const uint32_t v0 = __float_as_uint(fmaf(sc[3][2], EC, ((sc[0][0] + sc[1][2]) + sc[2][0]) * EC)), v1 = __float_as_uint(fmaf(sc[3][3], EC, ((sc[0][1] + sc[1][3]) + sc[2][1]) * EC));
    FS(5, v0);
    st_async64(d2, v0, v1, m2);
    st_async64(d1, v0, v1, m1);
    asm volatile("st.shared.v2.u32 [%0], {%1,%2};" :: "r"(d0), "r"(v0), "r"(v1) : "memory");
}
__device__ __forceinline__ void store_tile(int s, int h, int role, uint32_t tile, uint32_t b0, uint32_t b1) {
    asm volatile("cp.async.bulk.global.shared::cta.bulk_group.L2::cache_hint [%0], [%1], %2, %3;"
                 :: "l"(&g_qkv[s][h][role][b0]), "r"(tile + b0), "r"(b1 - b0), "l"(policy_evict_first()) : "memory");
}
__device__ __forceinline__ uint32_t w_addr(uint32_t sbase, int warp, int lane) {
    return sbase + SM_WS + (warp >> 2) * 8192 + ((lane & 7) + ((lane >> 4) & 1) * 8) * 128 + ((((warp & 3) * 2 + ((lane >> 3) & 1)) ^ (lane & 7)) << 4);
}
__device__ __forceinline__ void vx_copy(uint32_t sbase, int j, int r) {
    bulk_s2s(mapa(sbase + SM_VX + (j & 1) * 8192, r), sbase + SM_T + (j & 3) * TBUF + DH * 16, 8192, mapa(sbase + B_VX + 8 * (j & 1), r));
}
__device__ __forceinline__ float to_scale(float bound) {
    int e = 141 - (int)((__float_as_uint(bound) >> 23) & 255u);
    e = e > 100 ? 100 : e;
    return __uint_as_float((uint32_t)(127 + e) << 23);
}
__device__ __forceinline__ void norms_gather(int lane, uint32_t sbase) {
    uint2 v[3];
    uint4 w[2];
    unsigned it = 0;
#pragma unroll
    for (int i = 0; i < 3; i++) v[i] = make_uint2(0u, 0u);
    w[0] = w[1] = make_uint4(0u, 0u, 0u, 0u);
    bool more;
    do {
#pragma unroll
        for (int i = 0; i < 3; i++) if (!GPRED || (v[i].x & 1u) == 0u) v[i] = ld_vol_u2(&g_norm[3 * lane + i]);
#pragma unroll
        for (int i = 0; i < 2; i++) if (!GPRED || (w[i].x & w[i].y & w[i].z & w[i].w & 1u) == 0u) w[i] = ld_vol_u4(&g_wv[lane][i]);
        more = __any_sync(0xffffffffu, (v[0].x & v[1].x & v[2].x & w[0].x & w[0].y & w[0].z & w[0].w & w[1].x & w[1].y & w[1].z & w[1].w & 1u) == 0u);
    } while (more && ++it < SPIN_LIMIT);
    float c;
    asm("sqrt.approx.f32 %0, %1;" : "=f"(c) : "f"(__uint_as_float(max(max(v[0].x, v[1].x), v[2].x))));
    c *= __uint_as_float(max(max(max(w[0].x, w[0].y), max(w[0].z, w[0].w)), max(max(w[1].x, w[1].y), max(w[1].z, w[1].w)))) * 272.f;
#pragma unroll
    for (int o = 16; o; o >>= 1) c += __shfl_xor_sync(0xffffffffu, c, o);
    const uint32_t r = __reduce_max_sync(0xffffffffu, v[0].y);
    if (lane < 3) {
        const uint32_t rb = mapa(sbase, lane);
        c *= 1.1f * 24.f;
        st_async64(rb + SM_SC, __float_as_uint(to_scale(__uint_as_float(r) * c)), __float_as_uint(c), rb + B_W + 8);
        st_async32(rb + SM_SC + 68, r, rb + B_W + 8);
    }
    __syncwarp();
}
__device__ __forceinline__ void xmax_gather(int lane, uint32_t sb) {
    uint4 v[4];
    unsigned it = 0;
    uint32_t ok;
    do {
#pragma unroll
        for (int i = 0; i < 4; i++) v[i] = ld_vol_u4(&g_rx[lane + 32 * (i >> 1)][i & 1]);
        ok = 1u;
#pragma unroll
        for (int i = 0; i < 4; i++) ok &= (v[i].x & v[i].y) & (v[i].z & v[i].w);
    } while (__any_sync(0xffffffffu, ok == 0u) && ++it < SPIN_LIMIT);
#pragma unroll
    for (int i = 0; i < 2; i++)
        sts32(sb + SM_SC + 64 + 4 * lane + 128 * i, max(max(max(v[2 * i].x, v[2 * i].y), max(v[2 * i].z, v[2 * i].w)), max(max(v[2 * i + 1].x, v[2 * i + 1].y), max(v[2 * i + 1].z, v[2 * i + 1].w))));
}
__device__ __forceinline__ uint32_t max_abs8(uint32_t m, uint32_t a, uint32_t b, uint32_t c, uint32_t d) { return max_abs2(max_abs2(m, max_abs2(a, b)), max_abs2(c, d)); }
__device__ __forceinline__ uint32_t warp_max_abs(uint32_t m) { return __reduce_max_sync(0xffffffffu, max((m << 16) & 0x7fff0000u, m & 0x7fff0000u)); }

__device__ __forceinline__ void last_rows(int pass) {
    extern __shared__ __align__(1024) unsigned char smem_raw[];
    const uint32_t sbase = smem_u32(smem_raw);
    const int tid = threadIdx.x, warp = __shfl_sync(0xffffffffu, tid >> 5, 0), h = blockIdx.x / 3;
    {
        const int sg = warp < 8, wq = warp & 3, lane = tid & 31;
        const uint32_t qk = sbase + SM_X + XBUF + sg * (2 * 9216), ob = sbase + SM_X + 2 * XBUF + sg * 8192;
        TST(0);
        if (pass) mbar_wait(sbase + B_VX + 8 * sg, 0);
        fence_async();
        TST(1);
        float sc[20];
#pragma unroll
        for (int i = 0; i < 20; i++) sc[i] = 0.f;
        {
            const uint64_t da = smem_desc(qk + 1024, 128, 1024), db = smem_desc(qk, 128, 2048);
            wg_fence();
#pragma unroll
            for (int ks = 0; ks < 8; ks++) wgmma_n40_ss(sc, da + (uint64_t)((ks >> 2) * 576 + (ks & 3) * 16), db + (uint64_t)((ks >> 2) * 576 + (ks & 3) * 16), ks > 0);
            wg_commit();
            wg_wait0();
        }
        uint32_t p[5], o[16];
        const float psum = xrow_softmax(sc, p, wq, lane);
        xrow_pv(o, p, psum, sbase + SM_T + ((NSEG - 2 + sg) & 3) * TBUF);
        if (pass) {
#pragma unroll
            for (int i = 0; i < 4; i++) stsm_x4(ob + (i >> 1) * 4096 + wq * 1024 + (i & 1) * 512 + lane * 16, o[4 * i], o[4 * i + 1], o[4 * i + 2], o[4 * i + 3]);
        }
        fence_async();
        named_bar(11 + sg, 128);
        TST(2);
        if ((tid & 127) == 0 && pass) {
            unsigned char* dst = reinterpret_cast<unsigned char*>(g_ox) + ((size_t)((NSEG / 2 - 1) * NH + h)) * 16384 + sg * 4096;
            asm volatile("cp.async.bulk.global.shared::cta.bulk_group [%0], [%1], 4096;" :: "l"(dst), "r"(ob) : "memory");
            asm volatile("cp.async.bulk.global.shared::cta.bulk_group [%0], [%1], 4096;" :: "l"(dst + 8192), "r"(ob + 4096) : "memory");
            asm volatile("cp.async.bulk.commit_group;" ::: "memory");
            asm volatile("cp.async.bulk.wait_group 0;" ::: "memory");
            asm volatile("red.relaxed.gpu.global.add.u32 [%0], 1;" :: "l"(&g_prog[(NSEG / 2 - 1) * 8 + (h >> 2)]) : "memory");
        }
        TST(3);
    }
    __syncwarp();
}

__global__ void __cluster_dims__(3, 1, 1) __launch_bounds__(384, 1)
k_chain(const __grid_constant__ CUtensorMap tmq, const __grid_constant__ CUtensorMap tmk,
        const __grid_constant__ CUtensorMap tmv, const __grid_constant__ CUtensorMap tmx2, const __grid_constant__ CUtensorMap tmo,
        const __grid_constant__ CUtensorMap tmm, const bf16* __restrict__ xg) {
    extern __shared__ __align__(1024) unsigned char smem_raw[];
    const uint32_t sbase = smem_u32(smem_raw);
    const int cta = blockIdx.x, h = cta / 3, role = cta - 3 * h;
    const int tid = threadIdx.x, warp = __shfl_sync(0xffffffffu, tid >> 5, 0), lane_o = tid & 31;
    TS3C(0);
    asm volatile("griddepcontrol.launch_dependents;" ::: "memory");
    auto stage_w = [&](int i) {
        tma_2d(sbase + SM_WS + i * 16384, role == 2 ? &tmv : &tmq, h * DH + (role == 1 ? 64 : 0), i * 64, sbase + B_W + 8 * i);
        tma_2d(sbase + SM_WS + i * 16384 + 8192, role == 2 ? &tmv : &tmk, h * DH + (role == 0 ? 0 : 64), i * 64, sbase + B_W + 8 * i);
    };
    auto stage_x = [&](int i) {
        tma_2d(sbase + x01_off(i), &tmx2, i * 64, 0, sbase + B_W + 8 * i);
        tma_2d(sbase + x01_off(i) + 8192, &tmm, i * 64, 0, sbase + B_W + 8 * i);
        if (i < 3) tma_2d(sbase + x23_off(i), &tmx2, i * 64, 64, sbase + B_W + 8 * i);
    };
    if (tid == 0) {
#pragma unroll
        for (int i = 0; i < 10; i++) mbar_init(sbase + B_W + 8 * i, 1);
        fence_async();
        TSQ(10);
#pragma unroll
        for (int i = 0; i < 3; i++) tma_2d(sbase + SM_X01 + i * 16384, &tmo, role * WOC + i * 64, h * DH, sbase + B_E);
        stage_x(0); stage_w(0);
        TSQ(11);
        mbar_expect(sbase + B_E, 49152);
#pragma unroll
        for (int i = 0; i < 9; i++) mbar_expect(sbase + B_W + 8 * i, 16384 + 9216 + (i < 3 ? 8192 : 0));
    } else if (tid == 32) {
#pragma unroll
        for (int i = 0; i < 8; i++) mbar_init(sbase + SM_BAR + 8 * i, 1);
        mbar_init(sbase + B_XF, 3);
        asm volatile("fence.mbarrier_init.release.cluster;" ::: "memory");
        for (int i = 0; i < 2; i++) {
            mbar_expect(sbase + B_SB + 8 * i, role == 2 ? 2560 : 1280 + 2048);
            mbar_expect(sbase + B_VX + 8 * i, role != 2 ? 8192 : 2 * 9216);
            mbar_expect(sbase + B_XT + 8 * i, 32768);
            mbar_expect(sbase + B_XT + 16 + 8 * i, i == 0 ? 40960 : 0);
        }
    }
    __syncthreads();
    TS3C(8);
    if (tid == 0) {
#pragma unroll 1
        for (int i = 1; i < NUP; i++) { if (i < 3) stage_x(i); stage_w(i); }
        TSQ(12);
    }
    __syncwarp();
    if (warp < 8) {
        uint32_t wreg[36 - NS][4];
        uint32_t v0, v1;
        {
            const int lane = lane_o;
            const uint32_t a = w_addr(sbase, warp, lane);
            const uint64_t da = smem_desc(sbase + SM_WS + (warp >> 2) * 8192, 1024, 1024) | (1ull << 62);
            float acc[36], acc1[32];
            uint32_t m = 0u;
#pragma unroll
            for (int i = 0; i < 36; i++) acc[i] = 0.f;
#pragma unroll
            for (int i = 0; i < 32; i++) acc1[i] = 0.f;
#pragma unroll 1
            for (int b = 0; b < 7; b++) {
                if (b == 0) TSQ(0);
                mbar_wait(sbase + B_W + 8 * b, 0);
                TSQ(1 + b);
                const uint64_t db = smem_desc(sbase + x01_off(b), 16, 1024) | (1ull << 62);
                wg_fence();
#pragma unroll
                for (int k = 0; k < 4; k++) wgmma_n72_ss(acc, da + (uint64_t)(b * 1024 + k * 128), db + (uint64_t)(k * 2));
                wg_commit();
                if (b < 3) {
                    const uint64_t d1 = smem_desc(sbase + x23_off(b), 16, 1024) | (1ull << 62);
                    wg_fence();
#pragma unroll
                    for (int k = 0; k < 4; k++) wgmma_n64_ss(acc1, da + (uint64_t)(b * 1024 + k * 128), d1 + (uint64_t)(k * 2));
                    wg_commit();
                }
                if (b == 2) {
                    wg_wait0();
                    bar_arrive(10, 384);
                }
                if (b == 3) {
                    if (tid == 0) mbar_expect(sbase + B_W + 8, 12);
                    __syncwarp();
                    if (role == 2) {
#pragma unroll
                        for (int ks = 0; ks < NS; ks++) {
                            uint32_t t[4];
                            ldsm_x4_t(t, a + (ks >> 2) * 16384 + (ks & 3) * 2048);
                            m = max_abs8(m, t[0], t[1], t[2], t[3]);
                        }
                    }
#pragma unroll
                    for (int ks = NS; ks < 16; ks++) ldsm_x4_t(wreg[ks - NS], a + (ks >> 2) * 16384 + (ks & 3) * 2048);
                }
                if (b == 5) {
#pragma unroll
                    for (int ks = 16; ks < 24; ks++) ldsm_x4_t(wreg[ks - NS], a + (ks >> 2) * 16384 + (ks & 3) * 2048);
                    if (role == 2) {
#pragma unroll
                        for (int ks = NS; ks < 24; ks++) m = max_abs8(m, wreg[ks - NS][0], wreg[ks - NS][1], wreg[ks - NS][2], wreg[ks - NS][3]);
                    }
                }
            }
            mbar_wait(sbase + B_W + 16, 1);
            TSQ(13);
            wg_fence();
#pragma unroll
            for (int k = 12; k < 20; k++)
                wgmma_n64_ss(acc1, da + (uint64_t)((k >> 2) * 1024 + (k & 3) * 128), (smem_desc(sbase + x23_off(k >> 2), 16, 1024) | (1ull << 62)) + (uint64_t)((k & 3) * 2));
            wg_commit();
            wg_wait0();
            named_bar(11, 384);
#pragma unroll
            for (int i = 0; i < 8; i++)
                asm volatile("st.shared.v4.f32 [%0], {%1,%2,%3,%4};" :: "r"(sbase + SM_X + 5 * 8192 + i * 4096 + tid * 16),
                             "f"(acc1[4 * i]), "f"(acc1[4 * i + 1]), "f"(acc1[4 * i + 2]), "f"(acc1[4 * i + 3]) : "memory");
#pragma unroll
            for (int b = 7; b < 9; b++) {
#pragma unroll
                for (int ks = 4 * b - 4; ks < 4 * b; ks++) ldsm_x4_t(wreg[ks - NS], a + (ks >> 2) * 16384 + (ks & 3) * 2048);
                if (role == 2) {
#pragma unroll
                    for (int ks = 4 * b - 4; ks < 4 * b; ks++) m = max_abs8(m, wreg[ks - NS][0], wreg[ks - NS][1], wreg[ks - NS][2], wreg[ks - NS][3]);
                }
                const uint64_t db = smem_desc(sbase + x01_off(b), 16, 1024) | (1ull << 62);
                mbar_wait(sbase + B_W + 8 * b, 0);
                TSQ(1 + b);
                if (b == 8) TS3C(2);
                wg_fence();
#pragma unroll
                for (int k = 0; k < 4; k++) wgmma_n72_ss(acc, da + (uint64_t)(b * 1024 + k * 128), db + (uint64_t)(k * 2));
                wg_commit();
            }
#pragma unroll
            for (int ks = 32; ks < KPRE; ks++) ldsm_x4_t(wreg[ks - NS], a + (ks >> 2) * 16384 + (ks & 3) * 2048);
            if (role == 2) {
#pragma unroll
                for (int ks = KPRE; ks < 36; ks++) {
                    uint32_t t[4];
                    ldsm_x4_t(t, a + (ks >> 2) * 16384 + (ks & 3) * 2048);
                    m = max_abs8(m, t[0], t[1], t[2], t[3]);
                }
#pragma unroll
                for (int ks = 32; ks < KPRE; ks++) m = max_abs8(m, wreg[ks - NS][0], wreg[ks - NS][1], wreg[ks - NS][2], wreg[ks - NS][3]);
                m = warp_max_abs(m);
                if (lane == 0) asm volatile("st.volatile.global.u32 [%0], %1;" :: "l"(reinterpret_cast<uint32_t*>(&g_wv[h][0]) + warp), "r"(m | 1u) : "memory");
                __syncwarp();
            }
            wg_wait0();
            named_bar(9, 256);
            const uint32_t off = sbase + SM_T + (DH + warp * 16 + (lane & 15)) * 16 + (lane >> 4) * (DH * 16);
#pragma unroll
            for (int i = 0; i < 4; i++)
                stsm_x4(off + (i >> 1) * TBUF + (i & 1) * (2 * DH * 16), pack_bf16(acc[8 * i], acc[8 * i + 1]), pack_bf16(acc[8 * i + 2], acc[8 * i + 3]),
                        pack_bf16(acc[8 * i + 4], acc[8 * i + 5]), pack_bf16(acc[8 * i + 6], acc[8 * i + 7]));
            v0 = pack_bf16(acc[32], acc[33]);
            v1 = pack_bf16(acc[34], acc[35]);
#pragma unroll
            for (int ks = KPRE; ks < 36; ks++) ldsm_x4_t(wreg[ks - NS], a + (ks >> 2) * 16384 + (ks & 3) * 2048);
            if (role == 2) fence_async();
            bar_arrive(8, 384);
            named_bar(7, 256);
            asm volatile("barrier.cluster.arrive.relaxed.aligned;" ::: "memory");
        }
        TS3C(3);
        uint32_t ws[NS][4];
#pragma unroll
        for (int ks = NS - NP; ks < NS; ks++) ldsm_x4_t(ws[ks], w_addr(sbase, warp, lane_o) + (ks >> 2) * 16384 + (ks & 3) * 2048);
        asm volatile("barrier.cluster.wait.aligned;" ::: "memory");
        if (lane_o == 0 && role != 2 && warp < 2) tma_2d_mc(sbase + SM_X + (2 * role + warp) * 8192, &tmx2, (2 * role + warp + 5) * 64, 64, sbase + B_XT + 8);
        __syncwarp();
        TS3C(4);
        auto main_loop = [&](auto is_c) {
            constexpr bool C = decltype(is_c)::value;
            if (C) pad_code<PAD4>(); else pad_code<PAD3>();
            const uint32_t l16 = __shfl_sync(0xffffffffu, sbase + lane_o * 16, lane_o);
            const uint32_t ka = __shfl_sync(0xffffffffu, sbase + SM_T + (64 + (lane_o & 7) + ((lane_o >> 3) & 1) * 16 + (lane_o >> 4) * 8) * 16, lane_o);
            const uint32_t wa = __shfl_sync(0xffffffffu, w_addr(sbase, warp, lane_o), lane_o);
            auto post = [&](bool act, int s, uint32_t to, uint32_t ta, int scw, uint32_t v0, uint32_t v1) {
                int lane = lane_o;
                asm volatile("" : "+r"(lane));
                asm volatile("stmatrix.sync.aligned.m8n8.x2.shared.b16 [%0], {%1,%2};" :: "r"(l16 + ta), "r"(v0), "r"(v1) : "memory");
                if (C) {
                    if (act || s + 1 < NSEG) {
                        const uint32_t fo = (uint32_t)(warp * 256 + lane * 8);
                        const uint32_t rb0 = mapa(sbase, 0), rb1 = mapa(sbase, 1);
                        st_async64(rb0 + SM_VM + fo, v0, v1, rb0 + B_SB + 8 * (s & 1));
                        st_async64(rb1 + SM_VM + fo, v0, v1, rb1 + B_SB + 8 * (s & 1));
                        asm volatile("st.shared.v2.u32 [%0], {%1,%2};" :: "r"(sbase + SM_VM + fo), "r"(v0), "r"(v1) : "memory");
                        bar_arrive(2, 384);
                    }
                } else if (act) bar_arrive(2, 384);
                else {
                    named_bar(2, 384);
                    if (scw == 0) {
                        uint32_t kf[2][4], qf[2][4];
#pragma unroll
                        for (int k2 = 0; k2 < 2; k2++) { ldsm_x4_t(kf[k2], ka + to + k2 * 512); ldsm_x4_t(qf[k2], l16 + SM_T + to + k2 * 512); }
                        const uint32_t d0 = sbase + SM_S + lane * 8, bo = sbase + B_SB + 8 * (s & 1);
                        const uint32_t d1 = mapa(d0 + 1280, role ^ 1), m1 = mapa(bo, role ^ 1), d2 = mapa(d0 + role * 1280, 2), m2 = mapa(bo, 2);
                        score_group(qf, kf, d0, d1, m1, d2, m2);
                        bar_arrive(6, 160);
                        bar_arrive(5, 384);
                    }
                    if (RARE(scw == 8)) {
                        const uint32_t dk = mapa(sbase + SM_X + XBUF + (2 + role) * 9216 + (warp - 4) * 256 + lane * 4, 2), mb = mapa(sbase + B_VX + 8, 2);
                        st_async32(dk, v0, mb);
                        st_async32(dk + 128, v1, mb);
                    }
                }
                FS(11, 0);
            };
            post(false, 0, 0, SM_T + warp * 256, warp ^ 7, v0, v1);
            if (tid == 128 && cta < NSEG) {
                fence_async();
                mbar_expect(sbase + B_E, XBUF);
                bulk_g2s(sbase + SM_X + 9 * 8192, xg + (size_t)cta * SEG * DM, 32768, sbase + B_E);
                bulk_g2s(sbase + SM_WS + 32768 + 4096, xg + (size_t)cta * SEG * DM + 16384, 4096, sbase + B_E);
            }
            __syncwarp();
            if (C) {
                named_bar(7, 256);
                if (warp == 1) norms_gather(lane_o, sbase);
            }
            auto chores = [&](int s, bool idle) {
                int lane = lane_o;
                asm volatile("" : "+r"(lane));
                const int hw = (s & 1) ? warp : warp - 4;
                const uint32_t tb = sbase + SM_T + (s & 3) * TBUF;
                if (idle) { if (hw != 2) named_bar(4, 384); else bar_arrive(4, 384); }
                if (hw == 2) {
                    if (lane == 0) {
                        if (C || !idle) fence_async();
                        if (C) {
                            store_tile(s + 1, h, 2, sbase + SM_T + ((s + 1) & 3) * TBUF, 2048, 10240);
                            store_tile(s, h, 2, tb, 0, idle ? 2048 : 10240);
                        } else store_tile(s, h, role, tb, 1024, 10240);
                        asm volatile("cp.async.bulk.commit_group;" ::: "memory");
                        asm volatile("cp.async.bulk.wait_group 0;" ::: "memory");
                        if (C) {
                            asm volatile("cp.async.bulk.shared::cluster.global.mbarrier::complete_tx::bytes.multicast::cluster [%0], [%1], 8192, [%2], %3;"
                                         :: "r"(sbase + SM_VX + ((s + 1) & 1) * 8192), "l"(&g_qkv[s + 1][h][2][2048]), "r"(sbase + B_VX + 8 * ((s + 1) & 1)), "h"((unsigned short)3) : "memory");
                        }
                        asm volatile("red.relaxed.gpu.global.add.u32 [%0], 1;" :: "l"(&g_flag[h * NSEG + s]) : "memory");
                    }
                    __syncwarp();
                    if (!C && (s & 1) && s + 4 < NSEG) bar_arrive(13, 160);
                }
                __syncwarp();
            };
            auto put_tiles = [&](const float (&acc)[32], uint32_t off) {
#pragma unroll
                for (int i = 0; i < 4; i++)
                    stsm_x4(off + (i >> 1) * TBUF + (i & 1) * (2 * DH * 16), pack_bf16(acc[8 * i], acc[8 * i + 1]), pack_bf16(acc[8 * i + 2], acc[8 * i + 3]),
                            pack_bf16(acc[8 * i + 4], acc[8 * i + 5]), pack_bf16(acc[8 * i + 6], acc[8 * i + 7]));
            };
            auto tile_off = [&](int p) {
                int lane = lane_o;
                asm volatile("" : "+r"(lane));
                return sbase + SM_T + (p & 1) * (2 * TBUF) + (DH + warp * 16 + (lane & 15)) * 16 + (lane >> 4) * (DH * 16);
            };
            {
                auto db = [&](int ks) { return (smem_desc(sbase + SM_X, 16, 1024) | (1ull << 62)) + (uint64_t)(((ks >> 2) - 5) * 512 + (ks & 3) * 2); };
                float acc[32];
#pragma unroll
                for (int i = 0; i < 8; i++)
                    asm volatile("ld.shared.v4.f32 {%0,%1,%2,%3}, [%4];" : "=f"(acc[4 * i]), "=f"(acc[4 * i + 1]), "=f"(acc[4 * i + 2]), "=f"(acc[4 * i + 3])
                                 : "r"(l16 + warp * 512 + SM_X + 5 * 8192 + i * 4096) : "memory");
                mbar_wait(sbase + B_XT + 8, 0);
                if (C) { if (warp < 4) named_bar(4, 384); } else if (warp != 7) named_bar(5, 384);
                wg_fence();
#pragma unroll
                for (int ks = 35; ks > 35 - NC0; ks--) wgmma_n64(acc, wreg[ks - NS], db(ks), 1);
                wg_commit();
                wg_wait0();
                if (warp == 5) {
                    mbar_wait(sbase + B_W + 8, 1);
                    bar_arrive(12, 160);
                }
                chores(0, false);
                if (!C || warp >= 4) named_bar(4, 384);
                wg_fence();
#pragma unroll
                for (int ks = 35 - NC0; ks >= 20; ks--) wgmma_n64(acc, wreg[ks - NS], db(ks), 1);
                wg_commit();
                if (cta < NSEG) {
                    uint32_t m = 0u;
                    mbar_wait(sbase + B_E, 1);
#pragma unroll 1
                    for (int j = 0; j < 9; j++) {
                        const uint4 xv = lds128(l16 + warp * 512 + (j < 8 ? SM_X + 9 * 8192 + j * 4096 : SM_WS + 32768 + 4096));
                        m = max_abs8(m, xv.x, xv.y, xv.z, xv.w);
                    }
                    m = warp_max_abs(m);
                    if (lane_o == 0) asm volatile("st.volatile.global.u32 [%0], %1;" :: "l"(reinterpret_cast<uint32_t*>(&g_rx[cta][0]) + warp), "r"(m | 1u) : "memory");
                    __syncwarp();
                }
                wg_wait0();
                put_tiles(acc, tile_off(1));
            }
            auto mem_proj = [&](uint32_t& u0, uint32_t& u1) {
#pragma unroll
                for (int ks = 0; ks < NS - NP; ks++) ldsm_x4_t(ws[ks], wa + (ks >> 2) * 16384 + (ks & 3) * 2048);
                FS(0, ws[0][0]);
                named_bar(1, 384);
                float acc[2][4], minv;
                uint32_t b[3][4];
#pragma unroll
                for (int kk = 0; kk < 3; kk++) ldsm_x4_t(b[kk], l16 + SM_M + kk * 512);
                FS(1, b[0][0]);
#pragma unroll
                for (int kk = 0; kk < 18; kk++) {
#pragma unroll
                    for (int i = 0; i < 2; i++) {
                        const int ks = 2 * kk + i;
                        if (ks < 2) mma_z(acc[i], ws[ks], b[kk % 3][2 * i], b[kk % 3][2 * i + 1]);
                        else if (ks < NS) mma_bf16(acc[i], ws[ks < NS ? ks : 0], b[kk % 3][2 * i], b[kk % 3][2 * i + 1]);
                        else mma_bf16(acc[i], wreg[ks >= NS ? ks - NS : 0], b[kk % 3][2 * i], b[kk % 3][2 * i + 1]);
                    }
                    if (kk + 3 < 18) ldsm_x4_t(b[kk % 3], l16 + SM_M + (kk + 3) * 512);
                    if (kk + 3 == 17) asm volatile("ld.shared.f32 %0, [%1];" : "=f"(minv) : "r"(sbase + SM_SC + 8) : "memory");
                }
                u0 = pack_bf16(fmaf(acc[1][0], minv, acc[0][0] * minv), fmaf(acc[1][1], minv, acc[0][1] * minv));
                u1 = pack_bf16(fmaf(acc[1][2], minv, acc[0][2] * minv), fmaf(acc[1][3], minv, acc[0][3] * minv));
                FS(2, u0);
            };
            int s = 0, rc = 9;
            bool act = warp >= 4;
            uint32_t to = TBUF, ta = SM_T + warp * 256 + TBUF;
            auto next_slot = [&]() {
                const uint32_t d = (s & 3) == 3 ? -3 * TBUF : TBUF;
                to += d; ta += d;
                asm volatile("" : "+r"(to), "+r"(ta));
            };
#pragma unroll 1
            for (;;) {
                uint32_t u0, u1;
                if (act) {
                    mem_proj(u0, u1);
                    s++;
                    post(true, s, to, ta, 1, u0, u1);
                    const int p = (s + 3) >> 1;
                    const uint32_t dlo = (uint32_t)smem_desc(sbase + SM_X, 16, 1024) + rc * 512;
                    const uint64_t da = smem_desc(sbase + SM_WS + (warp >> 2) * 8192, 1024, 1024) | (1ull << 62);
                    auto db = [&](int ks) {
                        const int j = ((ks >> 2) + 4) % 9;
                        return ((uint64_t)0x40000040u << 32) | (uint64_t)(dlo + (uint32_t)((j - (rc + j >= 13 ? 13 : 0)) * 512 + (ks & 3) * 2));
                    };
                    const uint32_t xph = (uint32_t)((p - 1) >> 1) & 1u;
                    float acc[32];
                    mbar_wait(sbase + B_XT + 8 * (p & 1), xph);
                    if (C) named_bar(7, 256); else named_bar(5, 384);
                    if ((C ? CC_DELAY : C1_DELAY) > 0) { const uint32_t t1 = clock32(); while (clock32() - t1 < (C ? CC_DELAY : C1_DELAY)) {} }
                    constexpr int N1 = C ? NC1C : NC1;
                    wg_fence();
#pragma unroll
                    for (int ks = 35; ks > 35 - N1; ks--) { if (ks == 35) wgmma_n64_z(acc, wreg[ks - NS], db(ks)); else wgmma_n64(acc, wreg[ks - NS], db(ks), 1); }
                    wg_commit();
                    wg_wait0();
                    FS(9, __float_as_uint(acc[0]));
                    next_slot();
                    FS(8, 0);
                    if (B4P) asm volatile("{\n.reg .pred p;\nsetp.ge.s32 p, %0, 0;\n@p bar.sync 4, 384;\n}" :: "r"(s) : "memory");
                    else named_bar(4, 384);
                    FS(3, 0);
                    wg_fence();
#pragma unroll
                    for (int ks = 35 - N1; ks >= KG1; ks--) wgmma_n64(acc, wreg[ks - NS], db(ks), 1);
                    wg_commit();
                    mbar_wait(sbase + B_XT + 16 + 8 * (p & 1), xph);
                    wg_fence();
#pragma unroll
                    for (int ks = 0; ks < NS; ks++) wgmma_n64_ss(acc, da + (uint64_t)((ks >> 2) * 1024 + (ks & 3) * 128), db(ks));
#pragma unroll
                    for (int ks = NS; ks < KG1; ks++) wgmma_n64(acc, wreg[ks - NS], db(ks), 1);
                    wg_commit();
                    if (!C && warp >= 4) named_bar(13, 160);
                    uint32_t off = tile_off(p);
                    rc = rc >= 4 ? rc - 4 : rc + 9;
                    asm volatile("" : "+r"(off), "+r"(rc));
                    wg_wait0();
                    put_tiles(acc, off);
                    FS(7, __float_as_uint(acc[0]));
                }
                int scw = s + 2 < NSEG ? warp ^ ((s & 1) ? 7 : 3) : (warp & 4) + 4;
                asm volatile("" : "+r"(scw));
                mem_proj(u0, u1);
                s++;
                post(false, s, to, ta, scw, u0, u1);
                if (s + 1 == NSEG) break;
                if (s + 2 < NSEG) {
                    if (!C && (warp & 3) == 2) fence_async();
                    if (C) named_bar(7, 256); else if (scw != 0) named_bar(5, 384);
                    chores(s, true);
                } else {
                    const uint32_t t0 = clock32();
                    const uint32_t dq = mapa(sbase + SM_X + XBUF + role * 9216, 2), mb = mapa(sbase + B_VX, 2);
                    if (!C) {
                        if (scw != 0) named_bar(5, 384);
                        if (tid == 64) { fence_async(); while (clock32() - t0 < TL_DELAY) {} bulk_s2s(dq, sbase + SM_T + 2 * TBUF + 1024, 9216, mb); }
                        __syncwarp();
                    }
                    named_bar(4, 384);
                    if (!C && tid == 64) { const uint32_t t1 = clock32(); while (clock32() - t1 < VX_DELAY) {} bulk_s2s(dq + 2 * 9216 + 1024, sbase + SM_T + 3 * TBUF + 2048, 8192, mb + 8); }
                    __syncwarp();
                }
                next_slot();
                act = s + 4 < NSEG;
            }
            if (C) named_bar(7, 256);
        };
        if (role == 2) main_loop(Flag<true>()); else main_loop(Flag<false>());
    } else {
        uint32_t wo[3][8][4];
        uint32_t mx2 = 0u;
        {
            const int pt = tid - 256, lane = lane_o, wq = warp - 8, g = lane >> 2, tq = lane & 3;
            TSQ(7);
            if (XPF && cta < 9) asm volatile("prefetch.global.L2 [%0];" :: "l"(xg + 64 * DM + (cta * 128 + pt) * 64));
            mbar_wait(sbase + B_E, 0);
            TSQ(8);
#pragma unroll
            for (int t = 0; t < 3; t++) {
                const int T = 3 * wq + t;
                const uint32_t a = sbase + SM_X01 + (T >> 2) * 16384 + ((lane >> 4) * 8 + (lane & 7)) * 128 + ((((T & 3) * 2 + ((lane >> 3) & 1)) ^ (lane & 7)) << 4);
#pragma unroll
                for (int kk = 0; kk < 8; kk++) ldsm_x4_t(wo[t][kk], a + ((2 * wq + kk) & 7) * 2048);
            }
            named_bar(3, 128);
            if (pt == 64) {
                fence_async();
#pragma unroll 1
                for (int i = 3; i < 9; i++) { stage_x(i); if (i < 7) stage_w(i); }
            }
            if (pt >= 96 && pt < 120) {
                *reinterpret_cast<uint4*>(g_acc + cta * 1024 + (pt - 96) * 16) = make_uint4(0u, 0u, 0u, 0u);
                __threadfence();
            }
            __syncwarp();
            TSQ(9);
            float c0 = 0.f;
#pragma unroll
            for (int t = 0; t < 3; t++) {
                float n[4][4];
#pragma unroll
                for (int i = 0; i < 4; i++) { n[i][0] = n[i][1] = n[i][2] = n[i][3] = 0.f; }
#pragma unroll
                for (int kk = 0; kk < 8; kk++)
#pragma unroll
                    for (int i = 0; i < 4; i++) mma_k8(n[i], wo[t][kk][i & 2], wo[t][kk][(i & 2) + 1], wo[t][kk][i]);
                if ((g >> 1) == tq) c0 = fmaxf(c0, (g & 1) ? fmaxf(n[0][1] + n[2][1], n[1][3] + n[3][3]) : fmaxf(n[0][0] + n[2][0], n[1][2] + n[3][2]));
            }
            c0 = __uint_as_float(__reduce_max_sync(0xffffffffu, __float_as_uint(c0)));
            uint32_t m = 0u;
            const int xb = role == 0 ? h % 9 : 9;
            auto x_max = [&]() {
                mbar_wait(sbase + B_W + 8 * xb, 0);
#pragma unroll
                for (int j = 0; j < 5; j++) {
                    uint4 xv;
                    asm volatile("ld.shared.v4.u32 {%0,%1,%2,%3}, [%4];" : "=r"(xv.x), "=r"(xv.y), "=r"(xv.z), "=r"(xv.w)
                                 : "r"(sbase + x01_off(xb) + (j < 4 ? pt + 128 * j : 512 + (pt & 63)) * 16) : "memory");
                    m = max_abs8(m, xv.x, xv.y, xv.z, xv.w);
                }
            };
            if (xb < 3) x_max();
            named_bar(10, 384);
            TSQ(10);
            if (pt == 64) {
                fence_async();
                mbar_expect(sbase + B_W + 16, 16384);
#pragma unroll
                for (int i = 3; i < 5; i++) tma_2d(sbase + x23_off(i), &tmx2, i * 64, 64, sbase + B_W + 16);
#pragma unroll 1
                for (int i = 7; i < 9; i++) stage_w(i);
            }
            __syncwarp();
            if (xb >= 3 && xb < 7) x_max();
            bar_arrive(11, 384);
            if (xb == 7 || xb == 8) x_max();
            asm volatile("barrier.cluster.arrive.relaxed.aligned;" ::: "memory");
            m = warp_max_abs(m);
            if (lane == 0) { sts32(sbase + SM_SC + 320 + 4 * wq, __float_as_uint(c0)); sts32(sbase + SM_SC + 336 + 4 * wq, m); }
            TSQ(1);
            named_bar(3, 128);
            if (pt == 0) {
                const uint4 a = lds128(sbase + SM_SC + 320), b = lds128(sbase + SM_SC + 336);
                st_vol_u2(&g_norm[cta], make_uint2(max(max(a.x, a.y), max(a.z, a.w)) | 1u, max(max(b.x, b.y), max(b.z, b.w)) | 1u));
            }
            __syncwarp();
            named_bar(8, 384);
            TSQ(2);
            asm volatile("barrier.cluster.wait.aligned;" ::: "memory");
            if (role == 2 && lane == 0 && wq < 2) vx_copy(sbase, 0, wq);
            __syncwarp();
        }
        const int wq = warp - 8;
        auto helper_loop = [&](auto is_c) {
        const bool C = is_c.value;
        if (C) pad_code<PAD2>(); else pad_code<PAD1>();
        const uint32_t sb = sbase;
        const uint32_t l8_o = __shfl_sync(0xffffffffu, sb + lane_o * 8, lane_o), l16_o = __shfl_sync(0xffffffffu, sb + lane_o * 16, lane_o);
        unsigned char* dst = g_acc + (role * 32 + wq * 8 + (lane_o >> 3)) * 1024 + (lane_o & 7) * 16;
        auto load_kf = [&](uint32_t (&kf)[2][4], int slot) {
            int lane = lane_o;
            asm volatile("" : "+r"(lane));
            const uint32_t ka = sb + SM_T + slot * TBUF + ((wq + 1) * DH + 64 + (lane & 7) + ((lane >> 3) & 1) * 16 + (lane >> 4) * 8) * 16;
#pragma unroll
            for (int k2 = 0; k2 < 2; k2++) ldsm_x4_t(kf[k2], ka + k2 * 512);
        };
        float minv = 1.f;
        uint32_t kf[2][4];
        if (!C) load_kf(kf, 0);
        int b3 = 0;
        int rx = 9;
        for (int s = 0; s + 1 < NSEG; s++) {
            const int n3 = b3 == 2 ? 0 : b3 + 1;
            uint32_t l8 = l8_o, l16 = l16_o;
            asm volatile("" : "+r"(l8), "+r"(l16));
            {
                int lane = lane_o;
                asm volatile("" : "+r"(lane));
                if (C) {
                    if (lane == 0) {
                        if (wq == 3 && h == 0) {
                            const uint32_t t = gtime32();
                            st_vol_u2(&g_tick, make_uint2(t, lds32(sb + SM_SC + 12)));
                            sts32(sb + SM_SC + 12, t);
                        }
                    }
                    __syncwarp();
                    if (wq == 2 && s > 1 && lane < 24) {
                        *reinterpret_cast<uint4*>(g_acc + n3 * 128 + (3 * h + (lane >> 3)) * 1024 + (lane & 7) * 16) = make_uint4(0u, 0u, 0u, 0u);
                    }
                    if (RARE(wq == 1 && s == 3 && lane < 3)) {
                        const int c = 3 * h + lane;
                        st_vol_u2(&g_norm[c], make_uint2(0u, 0u));
                        uint4* z = c < NSEG ? g_rx[c] : g_wv[c - NSEG];
                        st_vol_u4(z, make_uint4(0u, 0u, 0u, 0u)); st_vol_u4(z + 1, make_uint4(0u, 0u, 0u, 0u));
                    }
                    __syncwarp();
                }
                const uint32_t mw = __reduce_max_sync(0xffffffffu, max(mx2 << 16, mx2 & 0xffff0000u));
                if (lane == 0) sts32(sb + SM_SC + 16 + 4 * wq, mw);
            }
            const uint32_t to = SM_T + (s & 3) * TBUF;
            const uint32_t ph = (uint32_t)(s >> 1) & 1u;
            if (!C) {
                const uint32_t bo = sb + B_SB + 8 * (s & 1);
                uint32_t d0 = l8 + SM_S + (wq + 1) * 256, qa = l16 + to;
                const uint32_t d1 = mapa(d0 + 1280, role ^ 1), m1 = mapa(bo, role ^ 1), d2 = mapa(d0 + role * 1280, 2), m2 = mapa(bo, 2);
                asm volatile("" : "+r"(d0), "+r"(qa));
                mbar_wait(sb + (s > 0 ? B_VX + 8 * (s & 1) : B_W), ph);
                FS(1, 0);
                named_bar(2, 384);
                uint32_t qf[2][4];
#pragma unroll
                for (int k2 = 0; k2 < 2; k2++) ldsm_x4_t(qf[k2], qa + k2 * 512);
                score_group(qf, kf, d0, d1, m1, d2, m2);
                bar_arrive(5, 384);
            } else named_bar(2, 384);
            if (!C && s == 0) {
                TSQ(3);
                mbar_wait(sb + B_VX, 0);
                TSQ(4);
            }
            float4 m4;
            asm volatile("ld.shared.v4.f32 {%0,%1,%2,%3}, [%4];" : "=f"(m4.x), "=f"(m4.y), "=f"(m4.z), "=f"(m4.w) : "r"(sb + SM_SC + 16) : "memory");
            const float c24 = __uint_as_float(lds32(sb + SM_SC + 4)), xb = __uint_as_float(lds32(sb + SM_SC + 64 + 4 * s));
            uint32_t vf[2][2][4], vm[2][2];
            uint32_t va = l16 + ((l16 >> 8) & 1) * 1792 + wq * 512 + (C ? to + DH * 16 : SM_VX + (s & 1) * 8192);
            auto load_vf = [&]() {
#pragma unroll
                for (int i = 0; i < 4; i++) ldsm_x4(vf[i & 1][i >> 1], va + (i & 1) * 256 + (i >> 1) * 4096);
            };
            load_vf();
            float scale = to_scale(fmaxf(fmaxf(fmaxf(m4.x, m4.y), fmaxf(m4.z, m4.w)) * minv, xb) * c24);
            uint32_t oa = l16 + wq * 512;
            asm volatile("" : "+f"(scale), "+r"(oa), "+r"(va));
            FS(7, __float_as_uint(scale));
            if (!C) named_bar(6, 160);
            if (C) mbar_wait_fast(sb + B_SB + 8 * (s & 1), ph);
            float sv[5][2];
#pragma unroll
            for (int j = 0; j < 5; j++) lds64f(sv[j][0], sv[j][1], l8 + SM_S + j * 256);
            if (!C) mbar_wait_fast(sb + B_SB + 8 * (s & 1), ph);
            FS(6, 0);
            uint32_t p[5];
            {
                float sr[5][2];
#pragma unroll
                for (int j = 0; j < 5; j++) lds64f(sr[j][0], sr[j][1], l8 + SM_S + 1280 + j * 256);
                lds64(vm[0][0], vm[0][1], l8 + SM_VM + wq * 512);
                lds64(vm[1][0], vm[1][1], l8 + SM_VM + wq * 512 + 256);
#pragma unroll
                for (int j = 0; j < 5; j++) {
                    sv[j][0] += sr[j][0];
                    sv[j][1] += sr[j][1];
                }
                float mx = fmaxf(fmaxf(fmaxf(sv[0][0], sv[0][1]), fmaxf(sv[1][0], sv[1][1])), fmaxf(fmaxf(sv[2][0], sv[2][1]), fmaxf(sv[3][0], sv[3][1])));
                mx = fmaxf(mx, fmaxf(sv[4][0], sv[4][1]));
                {
                    const float m1 = __shfl_xor_sync(0xffffffffu, mx, 1), m2 = __shfl_xor_sync(0xffffffffu, mx, 2), m3 = __shfl_xor_sync(0xffffffffu, mx, 3);
                    mx = fmaxf(fmaxf(mx, m1), fmaxf(m2, m3));
                }
#pragma unroll
                for (int jj = 0; jj < 5; jj++) {
                    const int j = (jj + 1) % 5;
                    asm("ex2.approx.ftz.f32 %0, %1;" : "=f"(sv[j][0]) : "f"(sv[j][0] - mx));
                    asm("ex2.approx.ftz.f32 %0, %1;" : "=f"(sv[j][1]) : "f"(sv[j][1] - mx));
                    p[j] = pack_bf16(sv[j][0], sv[j][1]);
                }
            }
            FS(0, p[0]);
            uint32_t b[4][4];
            const uint32_t one4[4] = {0x3f803f80u, 0x3f803f80u, 0x3f803f80u, 0x3f803f80u};
            float zs[4];
            {
                float o0[2][4], o1[2][4];
                mma_z(o0[0], vf[0][0], p[1], p[2]);
                mma_z(o0[1], vf[1][0], p[1], p[2]);
                mma_z(o1[0], vf[0][1], p[3], p[4]);
                mma_z(o1[1], vf[1][1], p[3], p[4]);
                mma_k8(o0[0], vm[0][0], vm[0][1], p[0]);
                mma_k8(o0[1], vm[1][0], vm[1][1], p[0]);
                if ((ZSM & 1) == 0) {
                    mma_z(zs, one4, p[1], p[2]);
                    mma_bf16(zs, one4, p[3], p[4]);
                    mma_k8(zs, one4[0], one4[1], p[0]);
                } else {
                    float z2[4];
                    mma_z(zs, one4, p[1], p[2]);
                    mma_z(z2, one4, p[3], p[4]);
                    mma_k8(zs, one4[0], one4[1], p[0]);
                    zs[0] += z2[0]; zs[1] += z2[1];
                }
                uint32_t ow[4];
#pragma unroll
                for (int m = 0; m < 2; m++) {
                    ow[2 * m] = pack_bf16(o0[m][0] + o1[m][0], o0[m][1] + o1[m][1]);
                    ow[2 * m + 1] = pack_bf16(o0[m][2] + o1[m][2], o0[m][3] + o1[m][3]);
                }
                stsm_x4(oa + SM_O, ow[0], ow[1], ow[2], ow[3]);
                FS(2, 0);
                if (ZSM & 2) {
                    __syncwarp();
                    ldsm_x4_t(b[0], oa + SM_O);
                } else if (ZSM & 4) {
                    b[0][0] = movm(ow[0]); b[0][1] = movm(ow[1]);
                    __syncwarp();
                    asm volatile("ldmatrix.sync.aligned.m8n8.x2.trans.shared.b16 {%0,%1}, [%2];" : "=r"(b[0][2]), "=r"(b[0][3]) : "r"(oa + SM_O + 256));
                } else {
#pragma unroll
                    for (int i = 0; i < 4; i++) b[0][i] = movm(ow[i]);
                }
            }
            float acc[3][2][4];
            named_bar(3, 128);
#pragma unroll
            for (int i = 1; i < 4; i++) ldsm_x4_t(b[i], l16 + SM_O + ((wq + i) & 3) * 512);
#pragma unroll
            for (int c = 0; c < 2; c++)
#pragma unroll
                for (int t = 0; t < 3; t++) mma_z(acc[t][c], wo[t][c], b[0][2 * c], b[0][2 * c + 1]);
            float z0, z1;
            asm volatile("rcp.approx.ftz.f32 %0, %1;" : "=f"(z0) : "f"(zs[0]));
            asm volatile("rcp.approx.ftz.f32 %0, %1;" : "=f"(z1) : "f"(zs[1]));
            asm volatile("{\n.reg .pred p;\nsetp.eq.s32 p, %1, 0;\n@p bar.sync 12, 160;\n@p ld.shared.f32 %0, [%2];\n}" : "+f"(scale) : "r"(s), "r"(sb + SM_SC) : "memory");
            z0 *= scale; z1 *= scale;
            FS(3, b[1][0]);
#pragma unroll
            for (int i = 1; i < 4; i++)
#pragma unroll
                for (int c = 0; c < 2; c++)
#pragma unroll
                    for (int t = 0; t < 3; t++) mma_bf16(acc[t][c], wo[t][2 * i + c], b[i][2 * c], b[i][2 * c + 1]);
            {
                uint32_t w[6];
#pragma unroll
                for (int t = 0; t < 3; t++) {
                    w[2 * t] = pack_f16(fmaf(acc[t][1][0], z0, acc[t][0][0] * z0), fmaf(acc[t][1][1], z1, acc[t][0][1] * z1));
                    w[2 * t + 1] = pack_f16(fmaf(acc[t][1][2], z0, acc[t][0][2] * z0), fmaf(acc[t][1][3], z1, acc[t][0][3] * z1));
                }
                FS(8, w[5]);
                asm volatile("red.relaxed.gpu.global.add.noftz.v4.f16x2 [%0], {%1,%2,%3,%4};" :: "l"(dst), "r"(w[0]), "r"(w[1]), "r"(w[2]), "r"(0x3c00u) : "memory");
                asm volatile("red.relaxed.gpu.global.add.noftz.v4.f16x2 [%0], {%1,%2,%3,%4};" :: "l"(dst + 4096), "r"(w[3]), "r"(w[4]), "r"(w[5]), "r"(0x3c00u) : "memory");
            }
            FS(9, 0);
            if (s == 0) TSQ(5);
            bar_arrive(4, 384);
            const uint32_t t0 = clock32();
            minv = __uint_as_float(0x7f000000u - __float_as_uint(scale));
            if (lane_o == 0) {
                if (wq == 0) sts32(sb + SM_SC + 8, __float_as_uint(minv));
                if (s + 3 < NSEG) {
                    if (wq == 0) mbar_expect(sb + B_SB + 8 * (s & 1), C ? 2560 : 1280 + 2048);
                    if (wq == 1 && s > 0 && s + 5 < NSEG) mbar_expect(sb + B_XT + ((s & 1) ? 0 : 16) + 4 * ((s + 1) & 2), (s & 1) ? 32768 : 40960);
                    if (wq == 3 && !C) mbar_expect(sb + B_VX + 8 * (s & 1), 8192);
                }
            }
            __syncwarp();
            if (RARE(s == 1)) {
                if (!C) pad_code<PADC>();
                int lane = lane_o;
                asm volatile("" : "+r"(lane));
                if (wq == 3) xmax_gather(lane, sb);
                __syncwarp();
            }
            if (!C) load_kf(kf, (s + 1) & 3);
            const uint4* src = reinterpret_cast<const uint4*>(dst + (wq * 16 - role * 32) * 1024);
            dst += n3 == 0 ? -256 : 128;
            asm volatile("" : "+l"(dst));
            const int xp = (s + 5) >> 1, kb = wq + ((s & 1) ? 2 * role : 4 + 3 * role);
            const bool xl = !C && xp < NSEG / 2 && wq < ((s & 1) ? 2 : 3 - role);
            const uint32_t xs = wq == 3 && (s & 1) == 0 && xp < NSEG / 2;
            const uint32_t xd = sb + SM_X + (rx + kb >= 13 ? rx + kb - 13 : rx + kb) * 8192;
            mx2 = poll_mem(src, l16 + SM_M + wq * 2304, t0, [&]() {
                if (xs && lane_o < 2) asm volatile("mbarrier.arrive.relaxed.cluster.shared::cluster.b64 _, [%0];" :: "r"(mapa(sb + B_XF, lane_o)) : "memory");
                if (!C && (xl || s == 0) && (s & 1) == 0) mbar_wait(sb + B_XF, (uint32_t)(s >> 1) & 1u);
                if (lane_o == 0) {
                    if (xl) tma_2d_mc(xd, &tmx2, ((s & 1) ? kb + 5 : kb - 4) * 64, xp * 64, sb + B_XT + ((s & 1) ? 0 : 16) + 8 * (xp & 1));
                    if (!C && s == 0 && role == 1) tma_2d_mc(sb + SM_X + (9 + wq) * 8192, &tmx2, (wq + 5) * 64, 128, sb + B_XT);
                }
                __syncwarp();
            });
            if ((s & 1) == 0) rx = rx >= 4 ? rx - 4 : rx + 9;
            if (s == 0) TSQ(6);
            b3 = n3;
        }
        if (!C) bar_arrive(2, 384);
        };
        if (role == 2) helper_loop(Flag<true>()); else helper_loop(Flag<false>());
    }
    TS3C(1);
    if (role == 2 && warp >= 4) last_rows(1);
    cluster_sync_all();
}

extern "C" void kernel_launch(void* const* d_in, const int* in_sizes, int n_in, void* d_out, int out_size) {
    const bf16* x = (const bf16*)d_in[0];
    const bf16* mem0 = (const bf16*)d_in[1];
    const bf16* Wq = (const bf16*)d_in[2];
    const bf16* Wk = (const bf16*)d_in[3];
    const bf16* Wv = (const bf16*)d_in[4];
    const bf16* Wo = (const bf16*)d_in[5];
    const bf16* logA = (const bf16*)d_in[8];
    const bf16* Aim = (const bf16*)d_in[9];
    const bf16* Cre = (const bf16*)d_in[10];
    const bf16* Cim = (const bf16*)d_in[11];
    const bf16* logdt = (const bf16*)d_in[12];
    const bf16* dskip = (const bf16*)d_in[13];
    const bf16* gw = (const bf16*)d_in[14];
    bf16* out = (bf16*)d_out;
    static bool attr_done = false;
    typedef CUresult (*EncFn)(CUtensorMap*, CUtensorMapDataType, cuuint32_t, void*, const cuuint64_t*, const cuuint64_t*, const cuuint32_t*,
                              const cuuint32_t*, CUtensorMapInterleave, CUtensorMapSwizzle, CUtensorMapL2promotion, CUtensorMapFloatOOBfill);
    static EncFn enc = nullptr;
    if (!attr_done) {
        void* fn = nullptr;
        cudaDriverEntryPointQueryResult qr;
        cudaGetDriverEntryPoint("cuTensorMapEncodeTiled", &fn, cudaEnableDefault, &qr);
        enc = (EncFn)fn;
        cudaFuncSetAttribute(k_chain, cudaFuncAttributeMaxDynamicSharedMemorySize, 232448);
        cudaFuncSetAttribute(k_side, cudaFuncAttributeMaxDynamicSharedMemorySize, SIDE_SMEM);
        attr_done = true;
    }
    CUtensorMap tmw[3];
    for (int i = 0; i < 3; i++) {
        const cuuint64_t dims[2] = {(cuuint64_t)HD, (cuuint64_t)DM};
        const cuuint64_t strides[1] = {(cuuint64_t)HD * 2};
        const cuuint32_t box[2] = {64, 64};
        const cuuint32_t es[2] = {1, 1};
        enc(&tmw[i], CU_TENSOR_MAP_DATA_TYPE_BFLOAT16, 2, (void*)(i == 0 ? Wq : (i == 1 ? Wk : Wv)), dims, strides, box, es, CU_TENSOR_MAP_INTERLEAVE_NONE,
            CU_TENSOR_MAP_SWIZZLE_128B, CU_TENSOR_MAP_L2_PROMOTION_L2_256B, CU_TENSOR_MAP_FLOAT_OOB_FILL_NONE);
    }
    CUtensorMap tmo;
    {
        const cuuint64_t dims[2] = {(cuuint64_t)DM, (cuuint64_t)HD};
        const cuuint64_t strides[1] = {(cuuint64_t)DM * 2};
        const cuuint32_t box[2] = {64, 128};
        const cuuint32_t es[2] = {1, 1};
        enc(&tmo, CU_TENSOR_MAP_DATA_TYPE_BFLOAT16, 2, (void*)Wo, dims, strides, box, es, CU_TENSOR_MAP_INTERLEAVE_NONE,
            CU_TENSOR_MAP_SWIZZLE_128B, CU_TENSOR_MAP_L2_PROMOTION_L2_128B, CU_TENSOR_MAP_FLOAT_OOB_FILL_NONE);
    }
    CUtensorMap tmx2;
    {
        const cuuint64_t dims[2] = {(cuuint64_t)DM, (cuuint64_t)S_LEN};
        const cuuint64_t strides[1] = {(cuuint64_t)DM * 2};
        const cuuint32_t box[2] = {64, 64};
        const cuuint32_t es[2] = {1, 1};
        enc(&tmx2, CU_TENSOR_MAP_DATA_TYPE_BFLOAT16, 2, (void*)x, dims, strides, box, es, CU_TENSOR_MAP_INTERLEAVE_NONE,
            CU_TENSOR_MAP_SWIZZLE_128B, CU_TENSOR_MAP_L2_PROMOTION_L2_128B, CU_TENSOR_MAP_FLOAT_OOB_FILL_NONE);
    }
    CUtensorMap tmm;
    {
        const cuuint64_t dims[2] = {(cuuint64_t)DM, (cuuint64_t)MEMT};
        const cuuint64_t strides[1] = {(cuuint64_t)DM * 2};
        const cuuint32_t box[2] = {64, (cuuint32_t)MEMT};
        const cuuint32_t es[2] = {1, 1};
        enc(&tmm, CU_TENSOR_MAP_DATA_TYPE_BFLOAT16, 2, (void*)mem0, dims, strides, box, es, CU_TENSOR_MAP_INTERLEAVE_NONE,
            CU_TENSOR_MAP_SWIZZLE_128B, CU_TENSOR_MAP_L2_PROMOTION_L2_128B, CU_TENSOR_MAP_FLOAT_OOB_FILL_NONE);
    }
    k_chain<<<NCTA, 384, 232448>>>(tmw[0], tmw[1], tmw[2], tmx2, tmo, tmm, x);
    {
        cudaLaunchConfig_t cfg = {};
        cfg.gridDim = dim3(SD_NCTA); cfg.blockDim = dim3(512); cfg.dynamicSmemBytes = SIDE_SMEM; cfg.stream = cudaStreamPerThread;
        cudaLaunchAttribute at[1];
        at[0].id = cudaLaunchAttributeProgrammaticStreamSerialization;
        at[0].val.programmaticStreamSerializationAllowed = 1;
        cfg.attrs = at; cfg.numAttrs = 1;
        cudaLaunchKernelEx(&cfg, k_side, tmo, x, logA, Aim, Cre, Cim, logdt, Wo, dskip, gw, out);
    }
}
```

```cpp
#include <cuda_runtime.h>
#include <cuda.h>
#include <cuda_bf16.h>
#include <stdint.h>

typedef __nv_bfloat16 bf16;
#define LDV4 "ld.volatile.global.v4.u32 {%0,%1,%2,%3}, [%4];"
#define STV4 "st.volatile.global.v4.u32 [%0], {%1,%2,%3,%4};"
#define STV2 "st.volatile.global.v2.u32 [%0], {%1,%2};"

constexpr int S_LEN = 2048, DM = 576, NH = 32, DH = 128, HD = 4096, MEMT = 8, SEG = 32, NSEG = 64, NST = 128;

__device__ __align__(128) bf16 g_gate[S_LEN];
constexpr int NCTA = NH * 3;
__device__ __align__(1024) unsigned char g_acc[96 * 1024];
__device__ __align__(128) uint2 g_norm[NCTA];
__device__ __align__(128) uint4 g_wv[NH][2];
__device__ __align__(128) uint4 g_rx[NSEG][2];
__device__ __align__(128) unsigned char g_qkv[NSEG][NH][3][10240];
__device__ __align__(128) bf16 g_ox[S_LEN * HD];
__device__ __align__(128) uint4 g_fp[8][36][6][128];
__device__ __align__(128) unsigned g_flag[NH * NSEG];
__device__ unsigned g_prog[NSEG / 2 * 8];
__device__ unsigned g_gcnt[64];
__device__ unsigned g_epoch;
__device__ __align__(128) uint2 g_tick;
__device__ __align__(128) bf16 g_y[DM * S_LEN];

#define TS3(slot) do {} while (0)
#define TS3P(slot) do {} while (0)
#define TSQ(slot) do {} while (0)
#define TS3W(slot) do {} while (0)
#define TSS(row, slot) do {} while (0)
#define TS3C(slot) do {} while (0)
#define TST(slot) do {} while (0)
#define TSA(seg, slot) do {} while (0)
#define TSG(i) do {} while (0)
#define FS(i, dep) do {} while (0)
__device__ __forceinline__ uint32_t smem_u32(const void* p) { return (uint32_t)__cvta_generic_to_shared(p); }
__device__ __forceinline__ float bf16r(float x) { return __bfloat162float(__float2bfloat16_rn(x)); }
__device__ __forceinline__ uint32_t pack_bf16(float lo, float hi) {
    __nv_bfloat162 v = __floats2bfloat162_rn(lo, hi);
    return *reinterpret_cast<uint32_t*>(&v);
}
__device__ __forceinline__ void ldsm_x4(uint32_t (&r)[4], uint32_t addr) {
    asm volatile("ldmatrix.sync.aligned.m8n8.x4.shared.b16 {%0,%1,%2,%3}, [%4];"
                 : "=r"(r[0]), "=r"(r[1]), "=r"(r[2]), "=r"(r[3]) : "r"(addr));
}
__device__ __forceinline__ void ldsm_x4_t(uint32_t (&r)[4], uint32_t addr) {
    asm volatile("ldmatrix.sync.aligned.m8n8.x4.trans.shared.b16 {%0,%1,%2,%3}, [%4];"
                 : "=r"(r[0]), "=r"(r[1]), "=r"(r[2]), "=r"(r[3]) : "r"(addr));
}
__device__ __forceinline__ void mma_bf16(float (&d)[4], const uint32_t (&a)[4], uint32_t b0, uint32_t b1) {
    asm volatile("mma.sync.aligned.m16n8k16.row.col.f32.bf16.bf16.f32 {%0,%1,%2,%3}, {%4,%5,%6,%7}, {%8,%9}, {%0,%1,%2,%3};"
                 : "+f"(d[0]), "+f"(d[1]), "+f"(d[2]), "+f"(d[3])
                 : "r"(a[0]), "r"(a[1]), "r"(a[2]), "r"(a[3]), "r"(b0), "r"(b1));
}
__device__ __forceinline__ uint2 ld_vol_u2(const uint2* p) {
    uint2 v; asm volatile("ld.volatile.global.v2.u32 {%0,%1}, [%2];" : "=r"(v.x), "=r"(v.y) : "l"(p) : "memory"); return v;
}
__device__ __forceinline__ void st_vol_u2(uint2* p, uint2 v) {
    asm volatile(STV2 :: "l"(p), "r"(v.x), "r"(v.y) : "memory");
}
__device__ __forceinline__ unsigned ld_acq(const unsigned* p) {
    unsigned v; asm volatile("ld.acquire.gpu.global.u32 %0, [%1];" : "=r"(v) : "l"(p) : "memory"); return v;
}
#define NS 10
#define NP 4
#define X_OXSZ 16384
#define GATE_A 970
#define GATE_B 380
#define GATE_P 1880u
#define STAGGER 0
#define RLX_SLEEP 300
#define VX_DELAY 100
#define EARLY4 0
#define SPEC_M 1
#define SPEC_H 1
#define C2_DELAY 0
#define SS_POS 10
#define UNGATE_G 3
#define GATE_Y 0
#define GATE_S 0
#define GATE_F 1
#define W14_SLEEP 60
#define TURN31 1
#define GL_A 1150
#define GL_B 530
#define GS_A 1300
#define GS_B 480
#define GATE_POLL 0
#define GP_A 900
#define GP_B 200
#define NUP 3
#define SIDE_WAIT 0
#define FASTW 0
#define NC1 3
#define NC1C 5
#define C1_DELAY 0
#define XSKIP 0
#define LATEW 1
#define VFP 0
#define CC_DELAY 0
#define KPRE 34
#define P0A 1
#define P0B 1
#define P0C 0
#define P0D 0
#define GPRED 1
#define P0W 3
#define XRARE 1
#define RARE(c) __builtin_expect(!!(c), 0)
#define PADB 0
#define PADC 0
#define PADD 0
#define PADE 0
#define PAD1 0
#define PAD2 0
#define PAD3 0
#define PAD4 0
#define B4P 1
#define XPF 0
#define NC0 4
#define KG1 20
#define ZSM 5
#define SMR 0
#define TL_DELAY 600
#define POLL_DELAY 590
#define UNGATE 6
constexpr unsigned SPIN_LIMIT = 1u << 20;
constexpr int NATT = NSEG - 2;

constexpr int SD_CH = 16;
constexpr int SD_NCTA = DM / SD_CH;
constexpr int SD_ROW = 528;
constexpr int SD_U = 8 * SD_ROW;
constexpr int SD_TAP = 5888;
constexpr int SD_CPY = 1376 * 2;
constexpr int SD_WSTR = SD_TAP + 2 * SD_CPY;
constexpr int SD_SMEM = SD_CH * SD_U + 8 * SD_WSTR;
constexpr int O_U = 79, O_U3 = 911, O_U4 = 1055, O_W79 = 1023, O_W35 = 1151, O_W610 = 1279, O_W511 = 1487;

__device__ __forceinline__ uint32_t lds32(uint32_t a) { uint32_t v; asm volatile("ld.shared.u32 %0, [%1];" : "=r"(v) : "r"(a)); return v; }
__device__ __forceinline__ void sts32(uint32_t a, uint32_t v) { asm volatile("st.shared.u32 [%0], %1;" :: "r"(a), "r"(v) : "memory"); }
__device__ __forceinline__ uint4 lds128(uint32_t a) {
    uint4 v; asm volatile("ld.shared.v4.u32 {%0,%1,%2,%3}, [%4];" : "=r"(v.x), "=r"(v.y), "=r"(v.z), "=r"(v.w) : "r"(a) : "memory"); return v;
}
__device__ __forceinline__ void tap_tile(uint32_t (&t)[4], uint32_t a) {
    asm volatile("ld.volatile.shared.u32 %0, [%4];\nld.volatile.shared.u32 %1, [%4+-16];\nld.volatile.shared.u32 %2, [%4+16];\nld.volatile.shared.u32 %3, [%4];"
                 : "=r"(t[0]), "=r"(t[1]), "=r"(t[2]), "=r"(t[3]) : "r"(a));
}
constexpr uint32_t sd_pass(int type, int dl, int o, int d0, int d1) { return (uint32_t)(type | dl << 2 | d0 << 8 | d1 << 12 | o << 17); }
__constant__ uint32_t SD_PASS[14] = {sd_pass(0, 0, O_U, 0, 2), sd_pass(0, 1, O_U + 96, 0, 2), sd_pass(0, 2, O_U + 192, 0, 4), sd_pass(0, 3, O_U + 288, 0, 2), sd_pass(1, 0, O_U3, 8, 8),
                                     sd_pass(0, 4, O_U + 384, 0, 2), sd_pass(1, 0, O_U4, 8, 15), sd_pass(0, 5, O_U + 480, 0, 2), sd_pass(0, 6, O_U + 576, 0, 4), sd_pass(0, 7, O_U + 672, 0, 2),
                                     sd_pass(2, 0, O_W35, 2, 8), sd_pass(3, 0, O_W79, 2, 4), sd_pass(2, 1, O_W610, 4, 8), sd_pass(3, 0, O_W511, 8, 15)};
__device__ __forceinline__ uint32_t band2(int x, int lo, int hi) { return (x >= lo && x <= hi ? 0x3f80u : 0u) | (x + 1 >= lo && x + 1 <= hi ? 0x3f800000u : 0u); }
__device__ __forceinline__ void mma_z(float (&d)[4], const uint32_t (&a)[4], uint32_t b0, uint32_t b1);
__device__ __forceinline__ void put_tap(uint32_t a, float v) {
    asm volatile("{\n.reg .b16 h;\ncvt.rn.bf16.f32 h, %1;\nst.shared.b16 [%0], h;\nst.shared.b16 [%0+%2], h;\n}" :: "r"(a), "f"(v), "n"(SD_CPY - 2) : "memory");
}

__device__ __forceinline__ void named_bar(int id, int n) { asm volatile("bar.sync %0, %1;" :: "r"(id), "r"(n) : "memory"); }
__device__ __forceinline__ uint32_t pack_f16(float lo, float hi) {
    uint32_t r; asm("cvt.rn.f16x2.f32 %0, %1, %2;" : "=r"(r) : "f"(hi), "f"(lo)); return r;
}
__device__ __forceinline__ void cexp_t(float lr, float turns, float& re, float& im) {
    float m;
    asm("ex2.approx.ftz.f32 %0, %1;" : "=f"(m) : "f"(lr));
    const float a = (turns - rintf(turns)) * 6.283185307179586f;
    re = m * __cosf(a); im = m * __sinf(a);
}
__device__ __forceinline__ void csq(float& re, float& im) { const float r = re * re - im * im; im = 2.f * re * im; re = r; }
__device__ __forceinline__ void kb_state(const float* tp, float gf, uint32_t (&a)[4][2], uint32_t (&b)[5]) {
    const float4 p0 = *reinterpret_cast<const float4*>(tp), p1 = *reinterpret_cast<const float4*>(tp + 4);
    float wr, wi;
    cexp_t(p0.x * gf, p0.y * gf, wr, wi);
    float vr = wr * p1.x - wi * p1.y, vi = wr * p1.y + wi * p1.x;
#pragma unroll
    for (int c = 0; c < 4; c++) {
        a[c][0] = pack_f16(wr, wi); a[c][1] = pack_f16(vr, vi);
        csq(wr, wi);
        if (c < 3) csq(vr, vi);
    }
    b[0] = pack_f16(p0.z * wr - p0.w * wi, -p0.z * wi - p0.w * wr);
    float er = wr * p1.z - wi * p1.w, ei = wr * p1.w + wi * p1.z;
#pragma unroll
    for (int c = 0; c < 4; c++) {
        b[1 + c] = pack_f16(p0.z * er - p0.w * ei, -p0.z * ei - p0.w * er);
        if (c < 3) csq(er, ei);
    }
}
__device__ __forceinline__ uint32_t bf2_mul(uint32_t a, uint32_t b) { uint32_t r; asm("mul.rn.bf16x2 %0, %1, %2;" : "=r"(r) : "r"(a), "r"(b)); return r; }
__device__ __forceinline__ uint32_t bf2_add(uint32_t a, uint32_t b) { uint32_t r; asm("add.rn.bf16x2 %0, %1, %2;" : "=r"(r) : "r"(a), "r"(b)); return r; }
__device__ __forceinline__ uint32_t bf2_sub(uint32_t a, uint32_t b) { uint32_t r; asm("sub.rn.bf16x2 %0, %1, %2;" : "=r"(r) : "r"(a), "r"(b)); return r; }
__device__ __forceinline__ void wait_cnt(const unsigned* p, unsigned target) {
    unsigned it = 0;
    while ((int)(ld_acq(p) - target) < 0 && ++it < SPIN_LIMIT) __nanosleep(64);
}
__device__ __forceinline__ uint32_t gtime32() { uint32_t t; asm volatile("mov.u32 %0, %%globaltimer_lo;" : "=r"(t) :: "memory"); return t; }
__device__ __forceinline__ void gate(uint32_t tick_addr, uint32_t ga = GATE_A, uint32_t gb = GATE_B) {
    uint32_t t1, p;
    asm volatile("ld.volatile.shared.v2.u32 {%0,%1}, [%2];" : "=r"(t1), "=r"(p) : "r"(tick_addr) : "memory");
    uint32_t d = gtime32() - t1;
    if (d < 4u * p) {
        d -= d >= 2u * p ? 2u * p : 0u;
        d -= d >= p ? p : 0u;
        if (d + ga >= p && d + gb < p) {
            const uint32_t t2 = gtime32() + (p - gb - d);
            while ((int)(gtime32() - t2) < 0) {}
        }
    }
}

__device__ __forceinline__ void read_tick(uint32_t tick_addr) {
    const uint2 tk = ld_vol_u2(&g_tick);
    uint32_t p = tk.x - tk.y;
    p = p > GATE_P + 100u ? GATE_P + 100u : p;
    asm volatile("st.volatile.shared.v2.u32 [%0], {%1,%2};" :: "r"(tick_addr), "r"(tk.x), "r"(p) : "memory");
}

__device__ __forceinline__ void s4d_phase(unsigned char* smem_raw, const bf16* __restrict__ x, const bf16* __restrict__ logA,
                                          const bf16* __restrict__ Aim, const bf16* __restrict__ Cre, const bf16* __restrict__ Cim,
                                          const bf16* __restrict__ logdt, const bf16* __restrict__ dskip, const bf16* __restrict__ wslice, unsigned ep, uint32_t tick) {
    const int tid = threadIdx.x, warp = __shfl_sync(0xffffffffu, tid >> 5, 0), lane = tid & 31;
    const int d0 = blockIdx.x * SD_CH;
    float* tab = reinterpret_cast<float*>(smem_raw + SD_CH * SD_U + warp * SD_WSTR);
    const uint32_t wb = smem_u32(tab);
    const int g = lane >> 2, tq = lane & 3;
    uint2 prm[4];
    float ldt;
    auto load_prm = [&](int d) {
        prm[0] = __ldg(reinterpret_cast<const uint2*>(logA + d * NST) + lane); prm[1] = __ldg(reinterpret_cast<const uint2*>(Aim + d * NST) + lane);
        prm[2] = __ldg(reinterpret_cast<const uint2*>(Cre + d * NST) + lane); prm[3] = __ldg(reinterpret_cast<const uint2*>(Cim + d * NST) + lane);
        ldt = __bfloat162float(logdt[d]);
    };
    load_prm(d0 + warp);
    for (int i = lane; i < 2 * SD_CPY / 16; i += 32) reinterpret_cast<uint4*>(tab + SD_TAP / 4)[i] = make_uint4(0u, 0u, 0u, 0u);
    TS3(20);
#pragma unroll 1
    for (int ch = 0; ch < 2; ch++) {
        const int d = d0 + 8 * ch + warp;
        const uint32_t ub = smem_u32(smem_raw) + (8 * ch + warp) * SD_U;
        float k2048 = 0.f, sinv;
        {
            const float dt = bf16r(expf(ldt));
            uint32_t cm = __vmaxu2(__vmaxu2(prm[2].x & 0x7fff7fffu, prm[2].y & 0x7fff7fffu), __vmaxu2(prm[3].x & 0x7fff7fffu, prm[3].y & 0x7fff7fffu));
            cm = __reduce_max_sync(0xffffffffu, max(cm << 16, cm & 0xffff0000u));
            int e = 134 - (int)(__float_as_uint(__uint_as_float(cm) * dt) >> 23);
            e = e > 100 ? 100 : (e < -100 ? -100 : e);
            const float s2 = __uint_as_float((uint32_t)(128 + e) << 23);
            sinv = __uint_as_float((uint32_t)(127 - e) << 23);
#pragma unroll
            for (int j = 0; j < 4; j++) {
                float q[4];
#pragma unroll
                for (int i = 0; i < 4; i++) { const uint32_t w = j < 2 ? prm[i].x : prm[i].y; q[i] = __uint_as_float((j & 1) ? w & 0xffff0000u : w << 16); }
                const float zl = -bf16r(expf(q[0])) * dt * 1.4426950408889634f;
                const float zt = q[1] * dt * 0.15915494309189535f;
                const float cr = s2 * (q[2] * dt), ci = s2 * (q[3] * dt);
                float ar, ai, br, bi, er, ei;
                cexp_t(zl * 8.f, zt * 8.f, ar, ai);
                cexp_t(zl * 128.f, zt * 128.f, br, bi);
                cexp_t(zl * 2048.f, zt * 2048.f, er, ei);
                k2048 += cr * er - ci * ei;
                *reinterpret_cast<float4*>(tab + (lane + 32 * j) * 8) = make_float4(zl, zt, cr, ci);
                *reinterpret_cast<float4*>(tab + (lane + 32 * j) * 8 + 4) = make_float4(ar, ai, br, bi);
            }
#pragma unroll
            for (int o = 16; o; o >>= 1) k2048 += __shfl_xor_sync(0xffffffffu, k2048, o);
        }
        __syncwarp();
        {
            float kc[5][4];
#pragma unroll
            for (int i = 0; i < 5; i++) { kc[i][0] = kc[i][1] = kc[i][2] = kc[i][3] = 0.f; }
            const float gf = (float)g;
#pragma unroll 2
            for (int ks = 0; ks < 16; ks++) {
                uint32_t a0[4][2], a1[4][2], b0[5], b1[5];
                kb_state(tab + (8 * ks + tq) * 8, gf, a0, b0);
                kb_state(tab + (8 * ks + 4 + tq) * 8, gf, a1, b1);
#pragma unroll
                for (int i = 0; i < 5; i++) {
                    const int c = i > 0 ? i - 1 : 0;
                    asm volatile("mma.sync.aligned.m16n8k16.row.col.f32.f16.f16.f32 {%0,%1,%2,%3}, {%4,%5,%6,%7}, {%8,%9}, {%0,%1,%2,%3};"
                                 : "+f"(kc[i][0]), "+f"(kc[i][1]), "+f"(kc[i][2]), "+f"(kc[i][3])
                                 : "r"(a0[c][0]), "r"(a0[c][1]), "r"(a1[c][0]), "r"(a1[c][1]), "r"(b0[i]), "r"(b1[i]));
                }
            }
            const uint32_t tp = wb + SD_TAP;
            const uint32_t a0 = tp + 2 * (O_U + 96 * g - 4 * tq);
            const uint32_t a2 = tp + 2 * (((g & 1) ? O_U + 96 * (2 * (g & 3)) : ((g & 2) ? O_W35 : O_W79 + 1)) - 32 - 8 * tq - (g >> 2));
            const uint32_t a3 = tp + 2 * (((g & 1) ? O_W35 : O_W610 + 1) - 64 - 16 * tq - (g >> 1));
            const uint32_t a4 = tp + 2 * (-128 - 32 * tq - g);
#pragma unroll
            for (int c = 0; c < 4; c++) {
                const int e = (c & 1) * 16 + (c >> 1) * 8;
                const bool first = c == 0 && lane == 0;
                put_tap(a0 - e / 4, kc[0][c] * sinv);
                put_tap(a0 - 32 - e / 4, kc[1][c] * sinv);
                put_tap(first ? tp + 2 * (O_U - 32) : a2 - e / 2, kc[2][c] * sinv);
                put_tap(first ? tp + 2 * (O_W79 - 63) : a3 - e, kc[3][c] * sinv);
                put_tap(first ? tp + 2 * (O_W610 - 127) : a4 + 2 * (O_W511 + 1 - e), kc[4][c] * sinv);
                if ((g & 1) == 0) {
                    put_tap(a4 + 2 * (O_U4 - e), kc[4][c] * sinv);
                    put_tap(first ? tp + 2 * (O_U3 - 128) : a4 + 2 * (O_U4 + 1 - e), kc[4][c] * sinv);
                }
            }
            if (lane == 0) {
                put_tap(tp + 2 * (O_U + 96 - 32), kc[2][0] * sinv);
                put_tap(tp + 2 * (O_U + 192 - 64), kc[3][0] * sinv);
                put_tap(tp + 2 * (O_W511 - 255), k2048 * sinv);
                put_tap(tp + 2 * (O_U4 - 255), k2048 * sinv);
            }
        }
        TS3(21 + 2 * ch);
        if (ch == 0) { if (!STAGGER || warp < 4) named_bar(1, 384); }
        else {
#pragma unroll
            for (int i = 0; i < 4; i++) asm volatile("prefetch.global.L2 [%0];" :: "l"(wslice + (size_t)((tid & 127) + 128 * i) * DM));
        }
        __syncwarp();
        if (tid == 0) TSS(18, 4 * ch);
        const uint32_t sh = wb + 80 + 11 * SD_ROW;
#pragma unroll
        for (int p = 0; p < 8; p++) {
            uint4 v;
            asm volatile("ld.shared.v4.u32 {%0,%1,%2,%3}, [%4];" : "=r"(v.x), "=r"(v.y), "=r"(v.z), "=r"(v.w) : "r"(ub + p * SD_ROW + lane * 16) : "memory");
            uint32_t pv = __shfl_up_sync(0xffffffffu, v.w, 1);
            pv = lane == 0 ? 0u : pv;
            asm volatile("st.shared.v4.u32 [%0], {%1,%2,%3,%4};" :: "r"(sh + (p - 8) * SD_ROW + lane * 16), "r"(__byte_perm(pv, v.x, 0x5432)), "r"(__byte_perm(v.x, v.y, 0x5432)),
                         "r"(__byte_perm(v.y, v.z, 0x5432)), "r"(__byte_perm(v.z, v.w, 0x5432)) : "memory");
            if (p >= 5) asm volatile("st.shared.v4.u32 [%0], {%1,%2,%3,%4};" :: "r"(sh + (p - 16) * SD_ROW + lane * 16), "r"(pv), "r"(v.x), "r"(v.y), "r"(v.z) : "memory");
        }
        __syncwarp();
        if (tid == 0) TSS(18, 4 * ch + 1);
        float acc[16][4];
#pragma unroll
        for (int i = 0; i < 16; i++) { acc[i][0] = acc[i][1] = acc[i][2] = acc[i][3] = 0.f; }
        {
            const uint32_t ka = wb + SD_TAP + ((g & 1) ? 0 : SD_CPY - 2) + 2 * (2 * tq - g);
            uint32_t b[16][2], b2[14][2];
#pragma unroll
            for (int k = 0; k < 16; k++) { b[k][0] = b[k][1] = 0u; if (k < 14) b2[k][0] = b2[k][1] = 0u; }
#pragma unroll 1
            for (int ps = 0; ps < 14; ps++) {
                const uint32_t pw = __shfl_sync(0xffffffffu, SD_PASS[ps], 0), type = pw & 3u, kp = ka + (pw >> 16);
                const int dl = (pw >> 2) & 7, d0 = (pw >> 8) & 15, d1 = (pw >> 12) & 15;
                uint32_t t[2][4];
                tap_tile(t[0], kp - 32 * d0);
                if (type == 0) {
                    const int p = (lane & 7) - dl;
                    const uint32_t ra = (p < 0 ? sh : ub) + p * SD_ROW + (lane >> 3) * 16;
#pragma unroll
                    for (int k = 0; k < 8; k++)
                        asm volatile("ldmatrix.sync.aligned.m8n8.x4.shared.b16 {%0,%1,%2,%3}, [%4];"
                                     : "=r"(b[2 * k][0]), "=r"(b[2 * k][1]), "=r"(b[2 * k + 1][0]), "=r"(b[2 * k + 1][1]) : "r"(ra + k * 64));
                } else if (type == 2) {
                    const int p = (lane & 15) - 11, xo = 2 * tq - g;
                    const uint32_t qa = (p < 0 ? sh : ub) + p * SD_ROW + (lane >> 4) * 16;
                    const int lx = 6 - 5 * dl, hx = 8 - 3 * dl, ly = 2 - 2 * dl, hy = 4 + 2 * dl;
                    const uint32_t sel[4] = {band2(xo, lx, hx), band2(xo, ly, hy), band2(xo + 8, lx, hx), band2(xo + 8, ly, hy)};
#pragma unroll
                    for (int k = 0; k < 14; k++) {
                        uint32_t q[4];
                        ldsm_x4_t(q, qa + k * 32);
#pragma unroll
                        for (int i = 0; i < 2; i++) {
                            float w[4];
                            mma_z(w, sel, q[2 * i], q[2 * i + 1]);
                            b[k][i] = pack_bf16(w[0], w[1]);
                            b2[k][i] = pack_bf16(w[2], w[3]);
                        }
                    }
                } else if (type == 3) {
#pragma unroll
                    for (int k = 0; k < 14; k++) { b[k][0] = b2[k][0]; b[k][1] = b2[k][1]; }
                }
#pragma unroll
                for (int d = 0; d < 16; d += 2) {
                    if (d >= 8 || d >= d0) {
                        tap_tile(t[1], kp - 32 * (d + 1));
#pragma unroll
                        for (int k = 0; k + d < 16; k++) mma_bf16(acc[k + d], t[0], b[k][0], b[k][1]);
                        if ((d == 2 || d == 4 || d == 8) && d == d1) break;
                        if (d < 14) tap_tile(t[0], kp - 32 * (d + 2));
#pragma unroll
                        for (int k = 0; k + d + 1 < 16; k++) mma_bf16(acc[k + d + 1], t[1], b[k][0], b[k][1]);
                    }
                }
            }
        }
        __syncwarp();
        if (tid == 0) TSS(18, 4 * ch + 2);
        load_prm(d0 + 8 + warp);
        if (ch == 0) { if (lane == 0) wait_cnt(&g_gcnt[0], SD_NCTA * ep); __syncwarp(); }
        if (tid == 0) TSS(18, 4 * ch + 3);
        uint4 gv[8];
#pragma unroll
        for (int i = 0; i < 8; i++) gv[i] = __ldcg(reinterpret_cast<const uint4*>(g_gate) + lane + 32 * i);
        const uint32_t dd = __byte_perm(*reinterpret_cast<const unsigned short*>(dskip + d), 0u, 0x1010);
#pragma unroll
        for (int i = 0; i < 8; i++) {
            uint32_t u[4];
            ldsm_x4_t(u, ub + (lane & 7) * SD_ROW + (lane >> 3) * 16 + i * 64);
            asm volatile("stmatrix.sync.aligned.m8n8.x4.shared.b16 [%0], {%1,%2,%3,%4};"
                         :: "r"(wb + (lane + 32 * i) * 16),
                            "r"(bf2_add(pack_bf16(acc[2 * i][0], acc[2 * i][1]), bf2_mul(u[0], dd))), "r"(bf2_add(pack_bf16(acc[2 * i][2], acc[2 * i][3]), bf2_mul(u[1], dd))),
                            "r"(bf2_add(pack_bf16(acc[2 * i + 1][0], acc[2 * i + 1][1]), bf2_mul(u[2], dd))), "r"(bf2_add(pack_bf16(acc[2 * i + 1][2], acc[2 * i + 1][3]), bf2_mul(u[3], dd))) : "memory");
        }
        if (GATE_Y) gate(tick);
        __syncwarp();
#pragma unroll
        for (int i = 0; i < 8; i++) {
            const uint4 y = *reinterpret_cast<const uint4*>(tab + (lane + 32 * i) * 4);
            *reinterpret_cast<uint4*>(g_y + (((lane >> 1) + 16 * i) * DM + d) * 16 + (lane & 1) * 8) =
                make_uint4(bf2_mul(bf2_sub(0x3f803f80u, gv[i].x), y.x), bf2_mul(bf2_sub(0x3f803f80u, gv[i].y), y.y),
                           bf2_mul(bf2_sub(0x3f803f80u, gv[i].z), y.z), bf2_mul(bf2_sub(0x3f803f80u, gv[i].w), y.w));
        }
        __syncwarp();
        TS3(22 + 2 * ch);
    }
}
__device__ __forceinline__ void s4d_stage_u(unsigned char* smem_raw, const bf16* __restrict__ x, int pt) {
    const int p = pt & 7, w0 = pt >> 3;
    const uint4* src = reinterpret_cast<const uint4*>(x + (size_t)(16 * w0 + p) * DM + blockIdx.x * SD_CH);
    uint32_t* dst = reinterpret_cast<uint32_t*>(smem_raw + p * SD_ROW) + w0;
#pragma unroll 1
    for (int b = 0; b < 4; b++) {
        uint4 v[2][2][2];
#pragma unroll
        for (int i = 0; i < 8; i++) v[i >> 2][(i >> 1) & 1][i & 1] = src[((b * 2 + (i >> 2)) * 256 + ((i >> 1) & 1) * 8) * (DM / 8) + (i & 1)];
#pragma unroll
        for (int i = 0; i < 4; i++) {
            const uint32_t* lo = reinterpret_cast<const uint32_t*>(&v[i >> 1][0][i & 1]);
            const uint32_t* hi = reinterpret_cast<const uint32_t*>(&v[i >> 1][1][i & 1]);
#pragma unroll
            for (int c = 0; c < 8; c++) dst[((i & 1) * 8 + c) * (SD_U / 4) + (b * 2 + (i >> 1)) * 16] = __byte_perm(lo[c >> 1], hi[c >> 1], (c & 1) ? 0x7632 : 0x5410);
        }
    }
    asm volatile("bar.arrive 1, 384;" ::: "memory");
}

constexpr int WOC = DM / 3;
constexpr int TBUF = 5 * DH * 16;
constexpr int XBUF = SEG * DM * 2;
constexpr int SM_BAR = 0;
constexpr int B_SB = 0, B_VX = 16, B_XT = 32, B_XF = 144, B_W = 64, B_E = 136;
constexpr int SM_SC = 256;
constexpr int SM_F = SM_SC + 1280;
constexpr int SM_VM = SM_F + 2048;
constexpr int SM_S = SM_VM + 2048;
constexpr int SM_O = SM_S + 2560;
constexpr int SM_M = SM_O + 2048;
constexpr int SM_WS = 19456;
constexpr int SM_T = SM_WS + 49152;
constexpr int SM_VX = SM_T + 4 * TBUF;
constexpr int SM_X = SM_VX + 2 * 8192;
constexpr int SM_X01 = SM_WS + DM * DH * 2;
__host__ __device__ constexpr int x01_off(int b) { return b < 2 ? 1024 + b * 9216 : SM_X01 + (b == 2 ? 6 : b - 3) * 9216; }
__host__ __device__ constexpr int x23_off(int b) { return b < 3 ? SM_WS + 7 * 16384 + b * 8192 : x01_off(b - 3); }
constexpr int CH_SMEM = SM_X01 + 8 * 8192;
static_assert(SM_M + DM * 16 <= SM_WS && SM_X + 13 * 8192 <= CH_SMEM && NS <= 10 && CH_SMEM <= 232448 && SM_X % 1024 == 0 && SM_X01 % 1024 == 0 && 1024 + 2 * 9216 <= SM_WS, "smem");
__device__ __forceinline__ uint32_t clock32() { uint32_t t; asm volatile("mov.u32 %0, %%clock;" : "=r"(t) :: "memory"); return t; }

__device__ __forceinline__ uint32_t mapa(uint32_t a, uint32_t rank) {
    uint32_t r; asm volatile("mapa.shared::cluster.u32 %0, %1, %2;" : "=r"(r) : "r"(a), "r"(rank)); return r;
}
__device__ __forceinline__ void st_async32(uint32_t addr, uint32_t v, uint32_t mbar) {
    asm volatile("st.async.weak.shared::cluster.mbarrier::complete_tx::bytes.b32 [%0], %1, [%2];" :: "r"(addr), "r"(v), "r"(mbar) : "memory");
}
__device__ __forceinline__ void mbar_init(uint32_t bar, uint32_t cnt) {
    asm volatile("mbarrier.init.shared::cta.b64 [%0], %1;" :: "r"(bar), "r"(cnt) : "memory");
}
__device__ __forceinline__ void mbar_expect(uint32_t bar, uint32_t bytes) {
    asm volatile("mbarrier.arrive.expect_tx.shared::cta.b64 _, [%0], %1;" :: "r"(bar), "r"(bytes) : "memory");
}
__device__ __forceinline__ void mbar_wait(uint32_t bar, uint32_t parity) {
    unsigned it = 0;
    uint32_t ok;
    do {
        ++it;
        asm volatile("{\n.reg .pred p;\nmbarrier.try_wait.parity.shared::cta.b64 p, [%1], %2;\nselp.u32 %0, 1, 0, p;\n}" : "=r"(ok) : "r"(bar), "r"(parity) : "memory");
    } while ((ok == 0u) & (it < SPIN_LIMIT));
}
__device__ __forceinline__ void mbar_wait_fast(uint32_t bar, uint32_t parity) {
    mbar_wait(bar, parity);
}
__device__ __forceinline__ void mbar_wait_long(uint32_t bar, uint32_t parity) {
    unsigned it = 0;
    while (true) {
        uint32_t ok;
        asm volatile("{\n.reg .pred p;\nmbarrier.try_wait.parity.shared::cta.b64 p, [%1], %2, %3;\nselp.u32 %0, 1, 0, p;\n}"
                     : "=r"(ok) : "r"(bar), "r"(parity), "r"(20000u) : "memory");
        if (ok || ++it >= SPIN_LIMIT) break;
    }
}
__device__ __forceinline__ bool mbar_test(uint32_t bar, uint32_t parity) {
    uint32_t ok;
    asm volatile("{\n.reg .pred p;\nmbarrier.test_wait.parity.shared::cta.b64 p, [%1], %2;\nselp.u32 %0, 1, 0, p;\n}" : "=r"(ok) : "r"(bar), "r"(parity) : "memory");
    return ok != 0u;
}
__device__ __forceinline__ uint64_t policy_evict_first() {
    uint64_t pol; asm volatile("createpolicy.fractional.L2::evict_first.b64 %0, 1.0;" : "=l"(pol)); return pol;
}
__device__ __forceinline__ void cluster_sync_all() {
    asm volatile("barrier.cluster.arrive.release.aligned;\nbarrier.cluster.wait.acquire.aligned;" ::: "memory");
}
__device__ __forceinline__ uint4 ld_vol_u4(const uint4* p) {
    uint4 v; asm volatile(LDV4 : "=r"(v.x), "=r"(v.y), "=r"(v.z), "=r"(v.w) : "l"(p) : "memory"); return v;
}
__device__ __forceinline__ void ld_vol_u4_p(uint4& v, const uint4* p, uint32_t pred) {
    asm volatile("{\n.reg .pred p;\nsetp.ne.u32 p, %5, 0;\n@p " LDV4 "\n}"
                 : "+r"(v.x), "+r"(v.y), "+r"(v.z), "+r"(v.w) : "l"(p), "r"(pred) : "memory");
}
__device__ __forceinline__ void st_vol_u4(uint4* p, uint4 v) {
    asm volatile(STV4 :: "l"(p), "r"(v.x), "r"(v.y), "r"(v.z), "r"(v.w) : "memory");
}
__device__ __forceinline__ void mma_bf16_r(float (&d)[4], uint32_t a0, uint32_t a1, uint32_t a2, uint32_t a3, uint32_t b0, uint32_t b1) {
    asm volatile("mma.sync.aligned.m16n8k16.row.col.f32.bf16.bf16.f32 {%0,%1,%2,%3}, {%4,%5,%6,%7}, {%8,%9}, {%0,%1,%2,%3};"
                 : "+f"(d[0]), "+f"(d[1]), "+f"(d[2]), "+f"(d[3])
                 : "r"(a0), "r"(a1), "r"(a2), "r"(a3), "r"(b0), "r"(b1));
}

__device__ __forceinline__ uint64_t smem_desc(uint32_t addr, uint32_t lbo, uint32_t sbo) {
    return (uint64_t)((addr & 0x3FFFF) >> 4) | ((uint64_t)(lbo >> 4) << 16) | ((uint64_t)(sbo >> 4) << 32);
}
__device__ __forceinline__ void wg_fence() { asm volatile("wgmma.fence.sync.aligned;" ::: "memory"); }
__device__ __forceinline__ void wg_commit() { asm volatile("wgmma.commit_group.sync.aligned;" ::: "memory"); }
__device__ __forceinline__ void wg_wait0() { asm volatile("wgmma.wait_group.sync.aligned 0;" ::: "memory"); }
__device__ __forceinline__ void fence_async() { asm volatile("fence.proxy.async.shared::cta;" ::: "memory"); }
__device__ __forceinline__ void wgmma_n64_ss(float (&d)[32], uint64_t adesc, uint64_t bdesc) {
    asm volatile("{\n.reg .pred p;\nsetp.eq.b32 p, 0, 0;\n"
                 "wgmma.mma_async.sync.aligned.m64n64k16.f32.bf16.bf16 {%0,%1,%2,%3,%4,%5,%6,%7,%8,%9,%10,%11,%12,%13,%14,%15,%16,%17,%18,%19,%20,%21,%22,%23,%24,%25,%26,%27,%28,%29,%30,%31}, %32, %33, p, 1, 1, 1, 0;\n}"
                 : "+f"(d[0]), "+f"(d[1]), "+f"(d[2]), "+f"(d[3]), "+f"(d[4]), "+f"(d[5]), "+f"(d[6]), "+f"(d[7]), "+f"(d[8]), "+f"(d[9]), "+f"(d[10]), "+f"(d[11]), "+f"(d[12]), "+f"(d[13]), "+f"(d[14]), "+f"(d[15]), "+f"(d[16]), "+f"(d[17]), "+f"(d[18]), "+f"(d[19]), "+f"(d[20]), "+f"(d[21]), "+f"(d[22]), "+f"(d[23]), "+f"(d[24]), "+f"(d[25]), "+f"(d[26]), "+f"(d[27]), "+f"(d[28]), "+f"(d[29]), "+f"(d[30]), "+f"(d[31])
                 : "l"(adesc), "l"(bdesc));
}
__device__ __forceinline__ void wgmma_n72_ss(float (&d)[36], uint64_t adesc, uint64_t bdesc) {
    asm volatile("{\n.reg .pred p;\nsetp.eq.b32 p, 0, 0;\n"
                 "wgmma.mma_async.sync.aligned.m64n72k16.f32.bf16.bf16 {%0,%1,%2,%3,%4,%5,%6,%7,%8,%9,%10,%11,%12,%13,%14,%15,%16,%17,%18,%19,%20,%21,%22,%23,%24,%25,%26,%27,%28,%29,%30,%31,%32,%33,%34,%35}, %36, %37, p, 1, 1, 1, 0;\n}"
                 : "+f"(d[0]), "+f"(d[1]), "+f"(d[2]), "+f"(d[3]), "+f"(d[4]), "+f"(d[5]), "+f"(d[6]), "+f"(d[7]), "+f"(d[8]), "+f"(d[9]), "+f"(d[10]), "+f"(d[11]), "+f"(d[12]), "+f"(d[13]), "+f"(d[14]), "+f"(d[15]), "+f"(d[16]), "+f"(d[17]), "+f"(d[18]), "+f"(d[19]), "+f"(d[20]), "+f"(d[21]), "+f"(d[22]), "+f"(d[23]), "+f"(d[24]), "+f"(d[25]), "+f"(d[26]), "+f"(d[27]), "+f"(d[28]), "+f"(d[29]), "+f"(d[30]), "+f"(d[31]), "+f"(d[32]), "+f"(d[33]), "+f"(d[34]), "+f"(d[35])
                 : "l"(adesc), "l"(bdesc));
}
__device__ __forceinline__ void tma_2d(uint32_t dst, const CUtensorMap* tm, int c0, int c1, uint32_t mbar) {
    asm volatile("cp.async.bulk.tensor.2d.shared::cluster.global.tile.mbarrier::complete_tx::bytes [%0], [%1, {%2, %3}], [%4];"
                 :: "r"(dst), "l"(tm), "r"(c0), "r"(c1), "r"(mbar) : "memory");
}

__device__ __forceinline__ void bulk_g2s(uint32_t dst, const void* src, uint32_t bytes, uint32_t mbar) {
    asm volatile("cp.async.bulk.shared::cluster.global.mbarrier::complete_tx::bytes [%0], [%1], %2, [%3];"
                 :: "r"(dst), "l"(src), "r"(bytes), "r"(mbar) : "memory");
}
__device__ __forceinline__ void bulk_g2s_h(uint32_t dst, const void* src, uint32_t bytes, uint32_t mbar, uint64_t pol) {
    asm volatile("cp.async.bulk.shared::cluster.global.mbarrier::complete_tx::bytes.L2::cache_hint [%0], [%1], %2, [%3], %4;"
                 :: "r"(dst), "l"(src), "r"(bytes), "r"(mbar), "l"(pol) : "memory");
}
__device__ __forceinline__ void tma_2d_mc(uint32_t dst, const CUtensorMap* tm, int c0, int c1, uint32_t mbar) {
    asm volatile("cp.async.bulk.tensor.2d.shared::cluster.global.tile.mbarrier::complete_tx::bytes.multicast::cluster [%0], [%1, {%2, %3}], [%4], %5;"
                 :: "r"(dst), "l"(tm), "r"(c0), "r"(c1), "r"(mbar), "h"((unsigned short)7) : "memory");
}
__device__ __forceinline__ void bulk_s2s(uint32_t dst, uint32_t src, uint32_t bytes, uint32_t mbar) {
    asm volatile("cp.async.bulk.shared::cluster.shared::cta.mbarrier::complete_tx::bytes [%0], [%1], %2, [%3];"
                 :: "r"(dst), "r"(src), "r"(bytes), "r"(mbar) : "memory");
}
__device__ __forceinline__ void wgmma_n40_ss(float (&d)[20], uint64_t adesc, uint64_t bdesc, int scale_d) {
    asm volatile("{\n.reg .pred p;\nsetp.ne.b32 p, %22, 0;\n"
                 "wgmma.mma_async.sync.aligned.m64n40k16.f32.bf16.bf16 {%0,%1,%2,%3,%4,%5,%6,%7,%8,%9,%10,%11,%12,%13,%14,%15,%16,%17,%18,%19}, %20, %21, p, 1, 1, 1, 1;\n}"
                 : "+f"(d[0]), "+f"(d[1]), "+f"(d[2]), "+f"(d[3]), "+f"(d[4]), "+f"(d[5]), "+f"(d[6]), "+f"(d[7]),
                   "+f"(d[8]), "+f"(d[9]), "+f"(d[10]), "+f"(d[11]), "+f"(d[12]), "+f"(d[13]), "+f"(d[14]), "+f"(d[15]),
                   "+f"(d[16]), "+f"(d[17]), "+f"(d[18]), "+f"(d[19])
                 : "l"(adesc), "l"(bdesc), "r"(scale_d));
}
__device__ __forceinline__ void wgmma_n64_z(float (&d)[32], const uint32_t (&a)[4], uint64_t bdesc) {
    asm volatile("{\n.reg .pred p;\nsetp.ne.b32 p, 0, 0;\n"
                 "wgmma.mma_async.sync.aligned.m64n64k16.f32.bf16.bf16 {%0,%1,%2,%3,%4,%5,%6,%7,%8,%9,%10,%11,%12,%13,%14,%15,%16,%17,%18,%19,%20,%21,%22,%23,%24,%25,%26,%27,%28,%29,%30,%31}, {%32,%33,%34,%35}, %36, p, 1, 1, 0;\n}"
                 : "=f"(d[0]), "=f"(d[1]), "=f"(d[2]), "=f"(d[3]), "=f"(d[4]), "=f"(d[5]), "=f"(d[6]), "=f"(d[7]),
                   "=f"(d[8]), "=f"(d[9]), "=f"(d[10]), "=f"(d[11]), "=f"(d[12]), "=f"(d[13]), "=f"(d[14]), "=f"(d[15]),
                   "=f"(d[16]), "=f"(d[17]), "=f"(d[18]), "=f"(d[19]), "=f"(d[20]), "=f"(d[21]), "=f"(d[22]), "=f"(d[23]),
                   "=f"(d[24]), "=f"(d[25]), "=f"(d[26]), "=f"(d[27]), "=f"(d[28]), "=f"(d[29]), "=f"(d[30]), "=f"(d[31])
                 : "r"(a[0]), "r"(a[1]), "r"(a[2]), "r"(a[3]), "l"(bdesc));
}
__device__ __forceinline__ void wgmma_n64(float (&d)[32], const uint32_t (&a)[4], uint64_t bdesc, int scale_d) {
    asm volatile("{\n.reg .pred p;\nsetp.ne.b32 p, %37, 0;\n"
                 "wgmma.mma_async.sync.aligned.m64n64k16.f32.bf16.bf16 {%0,%1,%2,%3,%4,%5,%6,%7,%8,%9,%10,%11,%12,%13,%14,%15,%16,%17,%18,%19,%20,%21,%22,%23,%24,%25,%26,%27,%28,%29,%30,%31}, {%32,%33,%34,%35}, %36, p, 1, 1, 0;\n}"
                 : "+f"(d[0]), "+f"(d[1]), "+f"(d[2]), "+f"(d[3]), "+f"(d[4]), "+f"(d[5]), "+f"(d[6]), "+f"(d[7]),
                   "+f"(d[8]), "+f"(d[9]), "+f"(d[10]), "+f"(d[11]), "+f"(d[12]), "+f"(d[13]), "+f"(d[14]), "+f"(d[15]),
                   "+f"(d[16]), "+f"(d[17]), "+f"(d[18]), "+f"(d[19]), "+f"(d[20]), "+f"(d[21]), "+f"(d[22]), "+f"(d[23]),
                   "+f"(d[24]), "+f"(d[25]), "+f"(d[26]), "+f"(d[27]), "+f"(d[28]), "+f"(d[29]), "+f"(d[30]), "+f"(d[31])
                 : "r"(a[0]), "r"(a[1]), "r"(a[2]), "r"(a[3]), "l"(bdesc), "r"(scale_d));
}

constexpr int SB_FULL = 0, SB_EMPTY = 64, SB_QKF = 128, SB_VF = 144, SB_QKE = 160, SB_VE = 176, SB_OF = 192, SB_WO = 208, SB_TICK = 216, SB_SEEN = 224, SB_FI = 232, SB_REQ = 240;
constexpr int AT_0 = 256, AT_ST = 10240 + 2 * 9216;
constexpr int FS_A = 58368;
constexpr int FS_P = FS_A + 131072;
constexpr int FS_I = FS_P + 16384;
constexpr int FS_O = FS_I + 12288;
constexpr int FS_Z = FS_O + 12288, FS_G = AT_0 + 2 * AT_ST;
constexpr int SIDE_SMEM = FS_Z + 2048;
static_assert(SIDE_SMEM <= 232448 && FS_G + 128 <= FS_A && FS_A + SD_SMEM <= SIDE_SMEM, "smem");

__device__ __forceinline__ void wg_wait1() { asm volatile("wgmma.wait_group.sync.aligned 1;" ::: "memory"); }
__device__ __forceinline__ void mbar_arrive(uint32_t bar) { asm volatile("mbarrier.arrive.shared::cta.b64 _, [%0];" :: "r"(bar) : "memory"); }
__device__ __forceinline__ void wait_cnt_rlx(const unsigned* p, unsigned target, bool urgent) {
    unsigned it = 0, v;
    while (true) {
        asm volatile("ld.relaxed.gpu.global.u32 %0, [%1];" : "=r"(v) : "l"(p) : "memory");
        if ((int)(v - target) >= 0 || ++it >= SPIN_LIMIT) break;
        if (!urgent) __nanosleep(RLX_SLEEP);
    }
}

__device__ __forceinline__ float xrow_softmax(float (&sc)[20], uint32_t (&p)[5], int wq, int lane) {
    constexpr float EC = (float)(1.4426950408889634 * 0.08838834764831845);
    const int lim = 8 * wq + (lane >> 2) - 2 * (lane & 3);
    float mx = fmaxf(sc[0], sc[1]);
#pragma unroll
    for (int j = 1; j < 5; j++) {
        sc[4 * j] = 8 * j - 8 > lim ? -INFINITY : sc[4 * j];
        sc[4 * j + 1] = 8 * j - 7 > lim ? -INFINITY : sc[4 * j + 1];
    }
    mx = fmaxf(fmaxf(mx, fmaxf(fmaxf(sc[4], sc[5]), fmaxf(sc[8], sc[9]))), fmaxf(fmaxf(sc[12], sc[13]), fmaxf(sc[16], sc[17])));
    {
        const float m1 = __shfl_xor_sync(0xffffffffu, mx, 1), m2 = __shfl_xor_sync(0xffffffffu, mx, 2), m3 = __shfl_xor_sync(0xffffffffu, mx, 3);
        mx = fmaxf(fmaxf(mx, m1), fmaxf(m2, m3)) * EC;
    }
    float sum = 0.f;
#pragma unroll
    for (int j = 0; j < 5; j++) {
        float e0, e1;
        asm("ex2.approx.ftz.f32 %0, %1;" : "=f"(e0) : "f"(fmaf(sc[4 * j], EC, -mx)));
        asm("ex2.approx.ftz.f32 %0, %1;" : "=f"(e1) : "f"(fmaf(sc[4 * j + 1], EC, -mx)));
        p[j] = pack_bf16(e0, e1);
        sum += e0 + e1;
    }
    return sum;
}
__device__ __forceinline__ float xrow_inv(float sum) {
    sum += __shfl_xor_sync(0xffffffffu, sum, 1);
    sum += __shfl_xor_sync(0xffffffffu, sum, 2);
    float r;
    asm("rcp.approx.ftz.f32 %0, %1;" : "=f"(r) : "f"(sum));
    return r;
}

__device__ __forceinline__ void stsm_x4(uint32_t addr, uint32_t r0, uint32_t r1, uint32_t r2, uint32_t r3) {
    asm volatile("stmatrix.sync.aligned.m8n8.x4.shared.b16 [%0], {%1,%2,%3,%4};" :: "r"(addr), "r"(r0), "r"(r1), "r"(r2), "r"(r3) : "memory");
}
__device__ __forceinline__ void xrow_pv(uint32_t (&ob)[16], const uint32_t (&p)[5], float psum, uint32_t vt) {
    float o[32];
    const uint64_t dv = smem_desc(vt, 2048, 128);
    uint32_t pa[6][4];
#pragma unroll
    for (int i = 0; i < 6; i++) {
        const int ks = i >> 1, hf = i & 1;
        pa[i][hf] = p[2 * ks]; pa[i][hf ^ 1] = 0u;
        pa[i][2 + hf] = ks < 2 ? p[ks < 2 ? 2 * ks + 1 : 0] : 0u; pa[i][3 - hf] = 0u;
    }
    wg_fence();
#pragma unroll
    for (int i = 0; i < 6; i++) { if (i == 0) wgmma_n64_z(o, pa[0], dv); else wgmma_n64(o, pa[i], dv + (uint64_t)((i & 1) * 64 + (i >> 1) * 256), 1); }
    wg_commit();
    const float inv = xrow_inv(psum);
    wg_wait0();
#pragma unroll
    for (int i = 0; i < 8; i++) { ob[i] = pack_bf16(o[4 * i] * inv, o[4 * i + 1] * inv); ob[8 + i] = pack_bf16(o[4 * i + 2] * inv, o[4 * i + 3] * inv); }
}
__device__ __forceinline__ uint32_t h2_to_bf2(uint32_t h) {
    uint32_t r;
    asm("{\n.reg .f16 l, h;\n.reg .f32 a, b;\nmov.b32 {l, h}, %1;\ncvt.f32.f16 a, l;\ncvt.f32.f16 b, h;\ncvt.rn.bf16x2.f32 %0, b, a;\n}" : "=r"(r) : "r"(h));
    return r;
}
__device__ __forceinline__ uint32_t max_abs2(uint32_t a, uint32_t b) { uint32_t r; asm("max.NaN.xorsign.abs.bf16x2 %0, %1, %2;" : "=r"(r) : "r"(a), "r"(b)); return r; }
__device__ __forceinline__ uint32_t movm(uint32_t v) {
    uint32_t r; asm volatile("movmatrix.sync.aligned.m8n8.trans.b16 %0, %1;" : "=r"(r) : "r"(v)); return r;
}
__device__ __forceinline__ void bar_arrive(int id, int n) { asm volatile("bar.arrive %0, %1;" :: "r"(id), "r"(n) : "memory"); }
__device__ __forceinline__ void lds64(uint32_t& a, uint32_t& b, uint32_t addr) {
    asm volatile("ld.shared.v2.u32 {%0,%1}, [%2];" : "=r"(a), "=r"(b) : "r"(addr) : "memory");
}
__device__ __forceinline__ void lds64f(float& a, float& b, uint32_t addr) {
    asm volatile("ld.shared.v2.f32 {%0,%1}, [%2];" : "=f"(a), "=f"(b) : "r"(addr) : "memory");
}
__device__ __forceinline__ void st_async64(uint32_t addr, uint32_t a, uint32_t b, uint32_t mbar) {
    asm volatile("st.async.weak.shared::cluster.mbarrier::complete_tx::bytes.v2.b32 [%0], {%1,%2}, [%3];" :: "r"(addr), "r"(a), "r"(b), "r"(mbar) : "memory");
}
__device__ __forceinline__ void mma_z(float (&d)[4], const uint32_t (&a)[4], uint32_t b0, uint32_t b1) {
    asm volatile("mma.sync.aligned.m16n8k16.row.col.f32.bf16.bf16.f32 {%0,%1,%2,%3}, {%4,%5,%6,%7}, {%8,%9}, {%10,%10,%10,%10};"
                 : "=f"(d[0]), "=f"(d[1]), "=f"(d[2]), "=f"(d[3])
                 : "r"(a[0]), "r"(a[1]), "r"(a[2]), "r"(a[3]), "r"(b0), "r"(b1), "f"(0.f));
}
__device__ __forceinline__ void mma_k8(float (&d)[4], uint32_t a0, uint32_t a1, uint32_t b) {
    asm volatile("mma.sync.aligned.m16n8k8.row.col.f32.bf16.bf16.f32 {%0,%1,%2,%3}, {%4,%5}, {%6}, {%0,%1,%2,%3};"
                 : "+f"(d[0]), "+f"(d[1]), "+f"(d[2]), "+f"(d[3]) : "r"(a0), "r"(a1), "r"(b));
}
__global__ void __launch_bounds__(512, 1) k_side(const __grid_constant__ CUtensorMap tmo, const bf16* __restrict__ x, const bf16* __restrict__ logA, const bf16* __restrict__ Aim,
                                                 const bf16* __restrict__ Cre, const bf16* __restrict__ Cim, const bf16* __restrict__ logdt,
                                                 const bf16* __restrict__ Wo, const bf16* __restrict__ dskip, const bf16* __restrict__ gw,
                                                 bf16* __restrict__ out) {
    extern __shared__ __align__(1024) unsigned char smem_raw[];
    const uint32_t sbase = smem_u32(smem_raw);
    const int tid = threadIdx.x, warp = __shfl_sync(0xffffffffu, tid >> 5, 0), lane = tid & 31, cta = blockIdx.x;
    const int cb = cta >> 2, kq = cta & 3;
    if (tid == 0) {
        for (int i = 0; i < 8; i++) { mbar_init(sbase + SB_FULL + 8 * i, 1); mbar_init(sbase + SB_EMPTY + 8 * i, 4); }
        for (int i = 0; i < 2; i++) {
            mbar_init(sbase + SB_QKF + 8 * i, 1); mbar_init(sbase + SB_VF + 8 * i, 1); mbar_init(sbase + SB_QKE + 8 * i, 4);
            mbar_init(sbase + SB_VE + 8 * i, 1); mbar_init(sbase + SB_OF + 8 * i, 4);
        }
        mbar_init(sbase + SB_WO, 1);
        mbar_init(sbase + SB_FI, 1);
        mbar_init(sbase + SB_REQ, 4);
        *reinterpret_cast<uint2*>(smem_raw + SB_TICK) = make_uint2(0u, 0u);
        *reinterpret_cast<uint32_t*>(smem_raw + SB_SEEN) = 0u;
        asm volatile("fence.mbarrier_init.release.cluster;" ::: "memory");
    }
    TS3(0);
    unsigned ep;
    asm volatile("ld.volatile.global.u32 %0, [%1];" : "=r"(ep) : "l"(&g_epoch) : "memory");
    ep += 1u;
    asm volatile("fence.proxy.async;" ::: "memory");
    __syncthreads();
    if (warp >= 12) {
      asm volatile("setmaxnreg.dec.sync.aligned.u32 40;");
      if (SIDE_WAIT > 0) __nanosleep(SIDE_WAIT);
      {
        uint32_t gwv[9];
#pragma unroll
        for (int i = 0; i < 9; i++) gwv[i] = reinterpret_cast<const uint32_t*>(gw)[lane + 32 * i];
#pragma unroll 1
        for (int i = 0; i < 8; i++) {
            uint32_t xv[2][9];
            float sm[2];
#pragma unroll
            for (int j = 0; j < 2; j++) {
                const int t = min(cta * 57 + 8 * i + 4 * j + warp - 12, S_LEN - 1);
#pragma unroll
                for (int k = 0; k < 9; k++) xv[j][k] = reinterpret_cast<const uint32_t*>(x + t * DM)[lane + 32 * k];
            }
#pragma unroll
            for (int j = 0; j < 2; j++) {
                sm[j] = 0.f;
#pragma unroll
                for (int k = 0; k < 9; k++) {
                    const uint32_t pr = bf2_mul(xv[j][k], gwv[k]);
                    sm[j] += __uint_as_float(pr << 16) + __uint_as_float(pr & 0xffff0000u);
                }
            }
            float v = (lane < 16 ? sm[0] : sm[1]) + __shfl_xor_sync(0xffffffffu, lane < 16 ? sm[1] : sm[0], 16);
#pragma unroll
            for (int o = 8; o; o >>= 1) v += __shfl_xor_sync(0xffffffffu, v, o);
            const float gv = 1.f / (1.f + expf(-bf16r(v)));
            const int tt = 8 * i + 4 * (lane >> 4) + warp - 12;
            if ((lane & 15) == 0 && tt < 57 && cta * 57 + tt < S_LEN) g_gate[cta * 57 + tt] = __float2bfloat16_rn(gv);
        }
        named_bar(2, 128);
        if (tid == 480) {
            __threadfence();
            asm volatile("red.relaxed.gpu.global.add.u32 [%0], 1;" :: "l"(&g_gcnt[0]) : "memory");
        }
        __syncwarp();
      }
      if (warp == 12 || warp == 15) {
        named_bar(3, 320);
        if (tid == 384) {
            fence_async();
            mbar_expect(sbase + SB_WO, 131072);
#pragma unroll 1
            for (int i = 0; i < 8; i++) {
                gate(sbase + SB_TICK);
                tma_2d(sbase + FS_A + i * 16384, &tmo, cb * 64, kq * 1024 + i * 128, sbase + SB_WO);
                __nanosleep(150);
            }
            TSS(17, 2);
        }
        if (tid == 480) {
            __threadfence();
            asm volatile("red.relaxed.gpu.global.add.u32 [%0], 1;" :: "l"(&g_gcnt[32]) : "memory");
            TSS(17, 3);
        }
        __syncwarp();
        named_bar(7, 320);
        if (lane == 0) {
            const int pi = warp == 12 ? 0 : 1, kb = 2 * kq + pi;
            fence_async();
            for (int pr = 0; pr < NSEG / 2; pr++) {
                const bool gon = pr < NSEG / 2 - UNGATE_G;
                wait_cnt_rlx(&g_prog[pr * 8 + kb], 8u * ep, pr >= NSEG / 2 - 2);
                if (pi == 0) asm volatile("st.volatile.shared.u32 [%0], %1;" :: "r"(sbase + SB_SEEN), "r"(pr + 1) : "memory");
                if (pr >= 30 && pi == 0) TSS(4 + pr - 30, 0);
                if (pr == 31) TS3P(26);
                if (pr == 30) TS3P(1);
#pragma unroll
                for (int j = 0; j < 4; j++) {
                    const int st = 4 * pi + j;
                    mbar_wait_long(sbase + SB_EMPTY + 8 * st, ((uint32_t)pr & 1u) ^ 1u);
                    mbar_expect(sbase + SB_FULL + 8 * st, X_OXSZ);
                    if (gon) gate(sbase + SB_TICK);
                    bulk_g2s(sbase + FS_A + st * 16384, g_ox + ((size_t)(pr * NH + 4 * kb + j)) * 8192, X_OXSZ, sbase + SB_FULL + 8 * st);
                }
            }
        }
        __syncwarp();
      } else if (warp == 13) {
        if (lane == 0) {
            const uint64_t pol = policy_evict_first();
            bool next_ok = false;
            for (int seg = 0; seg < NATT; seg++) {
                const uint32_t st = seg & 1, ph = (uint32_t)(seg >> 1) & 1u, ab = sbase + AT_0 + st * AT_ST;
                if (!next_ok) {
                    const unsigned* fp = &g_flag[(cta & (NH - 1)) * NSEG + seg];
                    unsigned it = 0, v0, v1;
                    while (true) {
                        asm volatile("ld.relaxed.gpu.global.u32 %0, [%1];" : "=r"(v0) : "l"(fp) : "memory");
                        asm volatile("ld.relaxed.gpu.global.u32 %0, [%1+4];" : "=r"(v1) : "l"(fp) : "memory");
                        read_tick(sbase + SB_TICK);
                        if ((int)(v0 - 3u * ep) >= 0 || ++it >= SPIN_LIMIT) break;
                        if (seg < NSEG - UNGATE || cta >= NH) { __nanosleep(RLX_SLEEP); if (GATE_POLL) gate(sbase + SB_TICK, GP_A, GP_B); }
                    }
                    next_ok = (int)(v1 - 3u * ep) >= 0;
                } else next_ok = false;
                if (cta < NH) {
                    TSA(seg, 0);
                    mbar_wait_long(sbase + SB_QKE + 8 * st, ph ^ 1u);
                    TSA(seg, 1);
                    mbar_expect(sbase + SB_QKF + 8 * st, 2 * 9216);
                    if (seg < NSEG - UNGATE) gate(sbase + SB_TICK, GL_A, GL_B);
                    TSA(seg, 2);
                    bulk_g2s_h(ab + 10240, &g_qkv[seg][cta][0][1024], 9216, sbase + SB_QKF + 8 * st, pol);
                    bulk_g2s_h(ab + 10240 + 9216, &g_qkv[seg][cta][1][1024], 9216, sbase + SB_QKF + 8 * st, pol);
                    mbar_wait_long(sbase + SB_VE + 8 * st, ph ^ 1u);
                    mbar_expect(sbase + SB_VF + 8 * st, 10240);
                    if (seg < NSEG - UNGATE) gate(sbase + SB_TICK, GL_A, GL_B);
                    TSA(seg, 3);
                    bulk_g2s_h(ab, &g_qkv[seg][cta][2][0], 10240, sbase + SB_VF + 8 * st, pol);
                }
            }
        }
        __syncwarp();
      } else if (warp == 14) {
        if (lane == 0) {
            int seg = cta < NH ? 0 : NATT, p = 0;
            unsigned it = 0;
            while ((seg < NATT || p < NSEG / 2 - 1) && ++it < 16 * SPIN_LIMIT) {
                if (p < NSEG / 2 - 1 && mbar_test(sbase + SB_REQ, (uint32_t)p & 1u)) {
                    if (p == 0) { wait_cnt(&g_gcnt[32], SD_NCTA * ep); asm volatile("fence.proxy.async;" ::: "memory"); }
                    mbar_expect(sbase + SB_FI, (p < NSEG / 2 - 2 ? 12288 : 2048 + 32) + 2048 + 32);
                    if (GATE_F && p < NSEG / 2 - UNGATE_G - 1) gate(sbase + SB_TICK);
                    if (p < NSEG / 2 - 2) bulk_g2s(sbase + FS_I, &g_fp[p & 7][cta][0][0], 12288, sbase + SB_FI);
                    else {
                        bulk_g2s(sbase + FS_I, g_y + ((p * 4 + 4 + kq) * DM + cb * 64) * 16, 2048, sbase + SB_FI);
                        bulk_g2s(sbase + FS_G + 32, g_gate + p * 64 + 64 + kq * 16, 32, sbase + SB_FI);
                    }
                    bulk_g2s(sbase + FS_Z, g_y + ((p * 4 + kq) * DM + cb * 64) * 16, 2048, sbase + SB_FI);
                    bulk_g2s(sbase + FS_G, g_gate + p * 64 + kq * 16, 32, sbase + SB_FI);
                    p++;
                } else if (seg < NATT && mbar_test(sbase + SB_OF + 8 * (seg & 1), (uint32_t)(seg >> 1) & 1u)) {
                    const uint32_t st = seg & 1, ab = sbase + AT_0 + st * AT_ST;
                    TSA(seg, 5);
                    if (seg < NSEG - UNGATE) gate(sbase + SB_TICK, GS_A, GS_B);
                    TSA(seg, 6);
                    unsigned char* dst = reinterpret_cast<unsigned char*>(g_ox) + ((size_t)((seg >> 1) * NH + cta)) * 16384 + (seg & 1) * 4096;
                    asm volatile("cp.async.bulk.global.shared::cta.bulk_group [%0], [%1], 4096;" :: "l"(dst), "r"(ab) : "memory");
                    asm volatile("cp.async.bulk.global.shared::cta.bulk_group [%0], [%1], 4096;" :: "l"(dst + 8192), "r"(ab + 4096) : "memory");
                    asm volatile("cp.async.bulk.commit_group;" ::: "memory");
                    asm volatile("cp.async.bulk.wait_group.read 0;" ::: "memory");
                    mbar_arrive(sbase + SB_VE + 8 * st);
                    asm volatile("cp.async.bulk.wait_group 0;" ::: "memory");
                    asm volatile("red.relaxed.gpu.global.add.u32 [%0], 1;" :: "l"(&g_prog[(seg >> 1) * 8 + (cta >> 2)]) : "memory");
                    TSA(seg, 7);
                    seg++;
                } else if (seg < NSEG - UNGATE) __nanosleep(W14_SLEEP);
            }
        }
        __syncwarp();
      }
    } else if (warp >= 8) {
        asm volatile("setmaxnreg.dec.sync.aligned.u32 88;");
        if (SIDE_WAIT > 0) __nanosleep(SIDE_WAIT);
        s4d_stage_u(smem_raw + FS_A, x, tid - 256);
        const int wq = warp - 8;
        for (int seg = 0; seg < (cta < NH ? NATT : 0); seg++) {
            const uint32_t st = seg & 1, ph = (uint32_t)(seg >> 1) & 1u, ab = sbase + AT_0 + st * AT_ST;
            float sc[20];
            if (seg < NSEG - UNGATE) mbar_wait_long(sbase + SB_QKF + 8 * st, ph); else mbar_wait(sbase + SB_QKF + 8 * st, ph);
            if (tid == 256) TSA(seg, 4);
            {
                const uint64_t da = smem_desc(ab + 10240 + 1024, 128, 1024), db = smem_desc(ab + 10240, 128, 2048);
                wg_fence();
#pragma unroll
                for (int ks = 0; ks < 8; ks++) wgmma_n40_ss(sc, da + (uint64_t)((ks >> 2) * 576 + (ks & 3) * 16), db + (uint64_t)((ks >> 2) * 576 + (ks & 3) * 16), ks > 0);
                wg_commit();
                wg_wait0();
            }
            if (lane == 0) mbar_arrive(sbase + SB_QKE + 8 * st);
            uint32_t p[5], ob[16];
            const float psum = xrow_softmax(sc, p, wq, lane);
            mbar_wait(sbase + SB_VF + 8 * st, ph);
            xrow_pv(ob, p, psum, ab);
            named_bar(6, 128);
#pragma unroll
            for (int i = 0; i < 4; i++) stsm_x4(ab + (i >> 1) * 4096 + wq * 1024 + (i & 1) * 512 + lane * 16, ob[4 * i], ob[4 * i + 1], ob[4 * i + 2], ob[4 * i + 3]);
            fence_async();
            __syncwarp();
            if (lane == 0) mbar_arrive(sbase + SB_OF + 8 * st);
        }
    } else {
        asm volatile("setmaxnreg.inc.sync.aligned.u32 192;");
        const int wg = warp >> 2, wq = warp & 3;
        s4d_phase(smem_raw + FS_A, x, logA, Aim, Cre, Cim, logdt, dskip, Wo + (size_t)((2 * kq + wg) * 512) * DM + cb * 64, ep, sbase + SB_TICK);
        TS3(2);
        if (lane == 0) TSS(16, warp);
        named_bar(3, 320);
        if (tid == 0) TSS(17, 0);
        uint32_t wa[32][4];
        mbar_wait_long(sbase + SB_WO, 0);
        if (tid == 0) TSS(17, 1);
        {
            const uint32_t a = sbase + FS_A + wg * 65536 + ((lane >> 4) * 8 + (lane & 7)) * 128 + (((wq * 2 + ((lane >> 3) & 1)) ^ (lane & 7)) << 4);
#pragma unroll
            for (int ks = 0; ks < 32; ks++) ldsm_x4_t(wa[ks], a + ks * 2048);
        }
        named_bar(7, 320);
        TS3(3);
        if (tid == 0) TSS(17, 4);
        auto product = [&](float (&acc)[32], int pr, const int wg) {
                if (pr + wg > 0 && (TURN31 || pr + wg < NSEG / 2)) named_bar(4 + wg, 256);
                const uint64_t db = smem_desc(sbase + FS_A + wg * 65536, 128, 1024);
                TSG(0);
#pragma unroll
                for (int j = 0; j < 4; j++) {
                    mbar_wait(sbase + SB_FULL + 8 * (4 * wg + j), (uint32_t)pr & 1u);
                    if (j == 0) TSG(1);
                    if (j == 3) TSG(2);
                    wg_fence();
#pragma unroll
                    for (int ks = 0; ks < 8; ks++) {
                        if ((j | ks) == 0) wgmma_n64_z(acc, wa[0], db);
                        else wgmma_n64(acc, wa[8 * j + ks], db + (uint64_t)(j * 1024 + (ks >> 2) * 512 + (ks & 3) * 16), 1);
                    }
                    wg_commit();
                    if (j == 3 && pr + (TURN31 ? wg : 1) < NSEG / 2) bar_arrive(4 + (wg ^ 1), 256);
                    if (j > 0) { wg_wait1(); if (lane == 0) mbar_arrive(sbase + SB_EMPTY + 8 * (4 * wg + j - 1)); }
                }
                wg_wait0();
                if (pr == 31) TS3W(27);
                TSG(3);
                if (lane == 0) mbar_arrive(sbase + SB_EMPTY + 8 * (4 * wg + 3));
        };
        if (wg == 1) {
            for (int pr = 0; pr < NSEG / 2; pr++) {
                uint32_t t16 = (uint32_t)(wq * 32 + lane) * 16u;
                asm volatile("" : "+r"(t16));
                float acc[32];
                product(acc, pr, 1);
                    uint32_t tag = ((uint32_t)(pr >> 3) & 1u) ^ 1u;
                    tag = __shfl_sync(0xffffffffu, tag, lane);
                    if (GATE_S && pr < NSEG / 2 - UNGATE_G) gate(sbase + SB_TICK);
                    named_bar(8, 256);
                    unsigned char* dst = reinterpret_cast<unsigned char*>(&g_fp[pr & 7][4 * cb][2 * kq - 2][0]) + t16;
                    const uint32_t own = sbase + FS_O + (pr % 3) * 4096 + t16;
#pragma unroll
                    for (int q = 0; q < 8; q++) {
                        float4 p;
                        asm volatile("ld.shared.v4.f32 {%0,%1,%2,%3}, [%4];" : "=f"(p.x), "=f"(p.y), "=f"(p.z), "=f"(p.w) : "r"(sbase + FS_P + t16 + q * 2048) : "memory");
                        acc[4 * q] = __uint_as_float((__float_as_uint(acc[4 * q] + p.x) & ~1u) | tag); acc[4 * q + 1] = __uint_as_float((__float_as_uint(acc[4 * q + 1] + p.y) & ~1u) | tag);
                        acc[4 * q + 2] = __uint_as_float((__float_as_uint(acc[4 * q + 2] + p.z) & ~1u) | tag); acc[4 * q + 3] = __uint_as_float((__float_as_uint(acc[4 * q + 3] + p.w) & ~1u) | tag);
                    }
#pragma unroll
                    for (int q = 0; q < 8; q++) {
                        asm volatile("{\n.reg .pred p;\nsetp.ne.s32 p, %5, %6;\n@p st.volatile.global.v4.f32 [%0], {%1,%2,%3,%4};\n@!p st.shared.v4.f32 [%7], {%1,%2,%3,%4};\n}"
                                     :: "l"(dst + (q & 1) * 2048), "f"(acc[4 * q]), "f"(acc[4 * q + 1]), "f"(acc[4 * q + 2]), "f"(acc[4 * q + 3]), "r"(q >> 1), "r"(kq),
                                        "r"(own + (q & 1) * 2048) : "memory");
                        if (q & 1) dst += (q >> 1) == kq ? 12288 + 4096 : 12288;
                    }
                    bar_arrive(9, 256);
                    if (pr == 31) TS3W(28);
                TSG(4);
            }
        } else {
          int nsync = 0;
          int np = 1, nf = 0, pr = 0, pf = -1;
          while (true) {
            uint32_t t16 = (uint32_t)(wq * 32 + lane) * 16u;
            asm volatile("" : "+r"(t16));
            if (pr < 0) {
                if (nsync <= pf) { named_bar(9, 256); nsync++; }
                if (lane == 0 && pf < NSEG / 2 - 1) mbar_arrive(sbase + SB_REQ);
            } else {
                float acc[32];
                product(acc, pr, 0);
                if (nsync < pr) { named_bar(9, 256); nsync++; }
#pragma unroll
                for (int q = 0; q < 8; q++)
                    asm volatile("st.shared.v4.f32 [%0], {%1,%2,%3,%4};" :: "r"(sbase + FS_P + t16 + q * 2048), "f"(acc[4 * q]), "f"(acc[4 * q + 1]), "f"(acc[4 * q + 2]), "f"(acc[4 * q + 3]) : "memory");
                bar_arrive(8, 256);
                TSG(4);
            }
            uint32_t w[4] = {0u, 0u, 0u, 0u};
            const int pc = pf;
            if (pf >= 0) {
                const uint32_t tag = ((uint32_t)(pf >> 3) & 1u) ^ 1u;
                uint4 v[8];
                unsigned n = 0;
                const bool last = pf == NSEG / 2 - 1;
                const uint4* src = reinterpret_cast<const uint4*>(reinterpret_cast<const unsigned char*>(&g_fp[pf & 7][cta][0][0]) + t16);
                if (pf >= NSEG / 2 - 2) {
#pragma unroll
                    for (int r = 0; r < 6; r++) v[r] = ld_vol_u4(src + r * 128);
                    mbar_wait(sbase + SB_FI, 0u);
                } else {
                    mbar_wait(sbase + SB_FI, (uint32_t)pf & 1u);
#pragma unroll
                    for (int r = 0; r < 6; r++)
                        asm volatile("ld.shared.v4.u32 {%0,%1,%2,%3}, [%4];" : "=r"(v[r].x), "=r"(v[r].y), "=r"(v[r].z), "=r"(v[r].w) : "r"(sbase + t16 + FS_I + r * 2048) : "memory");
                }
                while (true) {
                    uint32_t any = 0u;
#pragma unroll
                    for (int r = 0; r < 6; r++) {
                        uint32_t c0_, c1_;
                        asm("lop3.b32 %0, %1, %2, %3, 0x7e;" : "=r"(c0_) : "r"(v[r].x), "r"(v[r].y), "r"(tag));
                        asm("lop3.b32 %0, %1, %2, %3, 0x7e;" : "=r"(c1_) : "r"(v[r].z), "r"(v[r].w), "r"(tag));
                        asm("lop3.b32 %0, %1, %2, %3, 0xfe;" : "=r"(any) : "r"(any), "r"(c0_), "r"(c1_));
                    }
                    if (!__any_sync(0xffffffffu, (any & 1u) != 0u) || ++n >= SPIN_LIMIT) break;
                    if (pf < NSEG / 2 - 2) __nanosleep(200);
#pragma unroll
                    for (int r = 0; r < 6; r++) v[r] = ld_vol_u4(src + r * 128);
                }
                if (pf == 31) TS3(29);
                TSG(5);
#pragma unroll
                for (int r = 6; r < 8; r++)
                    asm volatile("ld.shared.v4.u32 {%0,%1,%2,%3}, [%4];" : "=r"(v[r].x), "=r"(v[r].y), "=r"(v[r].z), "=r"(v[r].w)
                                 : "r"(sbase + t16 + FS_O + (pf % 3) * 4096 + (r - 6) * 2048) : "memory");
                uint32_t zv[4], gg[2];
                ldsm_x4_t(zv, sbase + (last ? FS_I : FS_Z) + (wq * 16 + (lane & 15)) * 32 + (lane >> 4) * 16);
#pragma unroll
                for (int k = 0; k < 2; k++) gg[k] = __byte_perm(*reinterpret_cast<const volatile unsigned short*>(smem_raw + FS_G + (last ? 32 : 0) + k * 16 + (lane >> 2) * 2), 0u, 0x1010);
#define PQS(k, f) (((__uint_as_float(v[k].f) + __uint_as_float(v[2 + k].f)) + __uint_as_float(v[4 + k].f)) + __uint_as_float(v[6 + k].f))
#pragma unroll
                for (int k = 0; k < 2; k++) {
                    w[2 * k] = bf2_add(bf2_mul(gg[k], movm(pack_bf16(PQS(k, x), PQS(k, y)))), zv[2 * k]);
                    w[2 * k + 1] = bf2_add(bf2_mul(gg[k], movm(pack_bf16(PQS(k, z), PQS(k, w)))), zv[2 * k + 1]);
                }
#undef PQS
            }
            const bool more = nf < NSEG / 2;
            if (more) {
                uint32_t r;
                asm volatile("{\n.reg .pred p, q;\n.reg .b32 v;\nld.volatile.shared.u32 v, [%1];\nsetp.gt.s32 p, v, %2;\nbar.red.or.pred q, 10, 128, p;\nselp.u32 %0, 1, 0, q;\n}"
                             : "=r"(r) : "r"(sbase + SB_SEEN), "r"(np) : "memory");
                const bool dop = np < NSEG / 2 && (__shfl_sync(0xffffffffu, r, 0) != 0u || nf == np || nf >= NSEG / 2 - 2);
                TSG(6);
                pr = dop ? np++ : -1;
                pf = !dop || nf + (pr == NSEG / 2 - 1 ? 1 : 2) <= pr ? nf++ : -1;
                if (dop && pf >= 0 && lane == 0) mbar_arrive(sbase + SB_REQ);
            }
            if (pc >= 0) {
                unsigned char* op = reinterpret_cast<unsigned char*>(out) + (uint32_t)((pc * 64 + kq * 16 + (lane >> 2)) * DM + cb * 64 + wq * 16 + 2 * (lane & 3)) * 2u;
#pragma unroll
                for (int k = 0; k < 4; k++) *reinterpret_cast<uint32_t*>(op + (k >> 1) * (16 * DM) + (k & 1) * 16) = w[k];
                if ((pc & 1) == 0) TS3(4 + pc / 2);
                if (pc == 31) TS3(25);
            }
            if (!more) break;
          }
        }
        if (cta == 0 && tid == 0) asm volatile("red.relaxed.gpu.global.add.u32 [%0], 1;" :: "l"(&g_epoch) : "memory");
    }
    asm volatile("griddepcontrol.wait;" ::: "memory");
}

template <class F>
__device__ __forceinline__ uint32_t poll_mem(const uint4* src, uint32_t dst, uint32_t t0, F next) {
    uint4 v[6];
    unsigned it = 0;
#pragma unroll
    for (int j = 0; j < 6; j++) v[j] = make_uint4(0u, 0u, 0u, 0u);
    while (clock32() - t0 < POLL_DELAY) {}
    FS(12, 0);
    bool more;
#pragma unroll 1
    do {
        asm volatile("{\n.reg .pred p<6>;\n"
                     "setp.ne.u32 p0, %3, 0x5000;\nsetp.ne.u32 p1, %7, 0x5000;\nsetp.ne.u32 p2, %11, 0x5000;\n"
                     "setp.ne.u32 p3, %15, 0x5000;\nsetp.ne.u32 p4, %19, 0x5000;\nsetp.ne.u32 p5, %23, 0x5000;\n"
                     "@p0 ld.volatile.global.v4.u32 {%0,%1,%2,%3}, [%24];\n@p1 ld.volatile.global.v4.u32 {%4,%5,%6,%7}, [%24+4096];\n"
                     "@p2 ld.volatile.global.v4.u32 {%8,%9,%10,%11}, [%24+8192];\n@p3 ld.volatile.global.v4.u32 {%12,%13,%14,%15}, [%24+12288];\n"
                     "@p4 ld.volatile.global.v4.u32 {%16,%17,%18,%19}, [%24+16384];\n@p5 ld.volatile.global.v4.u32 {%20,%21,%22,%23}, [%24+20480];\n}"
                     : "+r"(v[0].x), "+r"(v[0].y), "+r"(v[0].z), "+r"(v[0].w), "+r"(v[1].x), "+r"(v[1].y), "+r"(v[1].z), "+r"(v[1].w),
                       "+r"(v[2].x), "+r"(v[2].y), "+r"(v[2].z), "+r"(v[2].w), "+r"(v[3].x), "+r"(v[3].y), "+r"(v[3].z), "+r"(v[3].w),
                       "+r"(v[4].x), "+r"(v[4].y), "+r"(v[4].z), "+r"(v[4].w), "+r"(v[5].x), "+r"(v[5].y), "+r"(v[5].z), "+r"(v[5].w)
                     : "l"(src) : "memory");
        stsm_x4(dst, h2_to_bf2(v[0].x), h2_to_bf2(v[0].y), h2_to_bf2(v[0].z), h2_to_bf2(v[1].x));
        stsm_x4(dst + 512, h2_to_bf2(v[1].y), h2_to_bf2(v[1].z), h2_to_bf2(v[2].x), h2_to_bf2(v[2].y));
        const uint32_t all = ((v[0].w & v[1].w) & (v[2].w & v[3].w)) & (v[4].w & v[5].w);
        more = __any_sync(0xffffffffu, (all & 0x5000u) != 0x5000u && ++it < SPIN_LIMIT);
        stsm_x4(dst + 1024, h2_to_bf2(v[2].z), h2_to_bf2(v[3].x), h2_to_bf2(v[3].y), h2_to_bf2(v[3].z));
        asm volatile("stmatrix.sync.aligned.m8n8.x2.shared.b16 [%0], {%1,%2};" :: "r"(dst + 1536), "r"(h2_to_bf2(v[4].x)), "r"(h2_to_bf2(v[4].y)) : "memory");
        stsm_x4(dst + 1792, h2_to_bf2(v[4].z), h2_to_bf2(v[5].x), h2_to_bf2(v[5].y), h2_to_bf2(v[5].z));
        asm volatile("{\n.reg .pred p;\nsetp.eq.u32 p, %0, 0;\n@p bar.sync 1, 384;\n}" :: "r"((uint32_t)more) : "memory");
    } while (more);
    next();
    FS(13, it);
    FS(14, 0);
    uint32_t m = v[0].x, m1 = v[0].y, m2 = v[0].z;
#pragma unroll
    for (int j = 1; j < 6; j++) {
        asm volatile("max.NaN.xorsign.abs.f16x2 %0, %0, %1;" : "+r"(m) : "r"(v[j].x));
        asm volatile("max.NaN.xorsign.abs.f16x2 %0, %0, %1;" : "+r"(m1) : "r"(v[j].y));
        asm volatile("max.NaN.xorsign.abs.f16x2 %0, %0, %1;" : "+r"(m2) : "r"(v[j].z));
    }
    asm volatile("max.NaN.xorsign.abs.f16x2 %0, %0, %1;" : "+r"(m) : "r"(m1));
    asm volatile("max.NaN.xorsign.abs.f16x2 %0, %0, %1;" : "+r"(m) : "r"(m2));
    return h2_to_bf2(m) & 0x7fff7fffu;
}

template <int N> __device__ __forceinline__ void pad_code() {
#pragma unroll
    for (int i = 0; i < N; i++) asm volatile("pmevent 7;" ::: "memory");
}
template <bool V> struct Flag { static constexpr bool value = V; };
struct RFlag { bool value; };
__device__ __forceinline__ void score_group(const uint32_t (&a)[2][4], const uint32_t (&kf)[2][4], uint32_t d0, uint32_t d1, uint32_t m1, uint32_t d2, uint32_t m2) {
    FS(4, a[1][0]);
    float sc[4][4];
    mma_z(sc[0], a[0], kf[0][0], kf[0][1]);
    mma_z(sc[1], a[0], kf[0][2], kf[0][3]);
    mma_z(sc[2], a[1], kf[1][0], kf[1][1]);
    mma_z(sc[3], a[1], kf[1][2], kf[1][3]);
    constexpr float EC = (float)(1.4426950408889634 * 0.08838834764831845);
    const uint32_t v0 = __float_as_uint(fmaf(sc[3][2], EC, ((sc[0][0] + sc[1][2]) + sc[2][0]) * EC)), v1 = __float_as_uint(fmaf(sc[3][3], EC, ((sc[0][1] + sc[1][3]) + sc[2][1]) * EC));
    FS(5, v0);
    st_async64(d2, v0, v1, m2);
    st_async64(d1, v0, v1, m1);
    asm volatile("st.shared.v2.u32 [%0], {%1,%2};" :: "r"(d0), "r"(v0), "r"(v1) : "memory");
}
__device__ __forceinline__ void store_tile(int s, int h, int role, uint32_t tile, uint32_t b0, uint32_t b1) {
    asm volatile("cp.async.bulk.global.shared::cta.bulk_group.L2::cache_hint [%0], [%1], %2, %3;"
                 :: "l"(&g_qkv[s][h][role][b0]), "r"(tile + b0), "r"(b1 - b0), "l"(policy_evict_first()) : "memory");
}
__device__ __forceinline__ uint32_t w_addr(uint32_t sbase, int warp, int lane) {
    return sbase + SM_WS + (warp >> 2) * 8192 + ((lane & 7) + ((lane >> 4) & 1) * 8) * 128 + ((((warp & 3) * 2 + ((lane >> 3) & 1)) ^ (lane & 7)) << 4);
}
__device__ __forceinline__ void vx_copy(uint32_t sbase, int j, int r) {
    bulk_s2s(mapa(sbase + SM_VX + (j & 1) * 8192, r), sbase + SM_T + (j & 3) * TBUF + DH * 16, 8192, mapa(sbase + B_VX + 8 * (j & 1), r));
}
__device__ __forceinline__ float to_scale(float bound) {
    int e = 141 - (int)((__float_as_uint(bound) >> 23) & 255u);
    e = e > 100 ? 100 : e;
    return __uint_as_float((uint32_t)(127 + e) << 23);
}
__device__ __forceinline__ void norms_gather(int lane, uint32_t sbase) {
    uint2 v[3];
    uint4 w[2];
    unsigned it = 0;
#pragma unroll
    for (int i = 0; i < 3; i++) v[i] = make_uint2(0u, 0u);
    w[0] = w[1] = make_uint4(0u, 0u, 0u, 0u);
    bool more;
    do {
#pragma unroll
        for (int i = 0; i < 3; i++) if (!GPRED || (v[i].x & 1u) == 0u) v[i] = ld_vol_u2(&g_norm[3 * lane + i]);
#pragma unroll
        for (int i = 0; i < 2; i++) if (!GPRED || (w[i].x & w[i].y & w[i].z & w[i].w & 1u) == 0u) w[i] = ld_vol_u4(&g_wv[lane][i]);
        more = __any_sync(0xffffffffu, (v[0].x & v[1].x & v[2].x & w[0].x & w[0].y & w[0].z & w[0].w & w[1].x & w[1].y & w[1].z & w[1].w & 1u) == 0u);
    } while (more && ++it < SPIN_LIMIT);
    float c;
    asm("sqrt.approx.f32 %0, %1;" : "=f"(c) : "f"(__uint_as_float(max(max(v[0].x, v[1].x), v[2].x))));
    c *= __uint_as_float(max(max(max(w[0].x, w[0].y), max(w[0].z, w[0].w)), max(max(w[1].x, w[1].y), max(w[1].z, w[1].w)))) * 272.f;
#pragma unroll
    for (int o = 16; o; o >>= 1) c += __shfl_xor_sync(0xffffffffu, c, o);
    const uint32_t r = __reduce_max_sync(0xffffffffu, v[0].y);
    if (lane < 3) {
        const uint32_t rb = mapa(sbase, lane);
        c *= 1.1f * 24.f;
        st_async64(rb + SM_SC, __float_as_uint(to_scale(__uint_as_float(r) * c)), __float_as_uint(c), rb + B_W + 8);
        st_async32(rb + SM_SC + 68, r, rb + B_W + 8);
    }
    __syncwarp();
}
__device__ __forceinline__ void xmax_gather(int lane, uint32_t sb) {
    uint4 v[4];
    unsigned it = 0;
    uint32_t ok;
    do {
#pragma unroll
        for (int i = 0; i < 4; i++) v[i] = ld_vol_u4(&g_rx[lane + 32 * (i >> 1)][i & 1]);
        ok = 1u;
#pragma unroll
        for (int i = 0; i < 4; i++) ok &= (v[i].x & v[i].y) & (v[i].z & v[i].w);
    } while (__any_sync(0xffffffffu, ok == 0u) && ++it < SPIN_LIMIT);
#pragma unroll
    for (int i = 0; i < 2; i++)
        sts32(sb + SM_SC + 64 + 4 * lane + 128 * i, max(max(max(v[2 * i].x, v[2 * i].y), max(v[2 * i].z, v[2 * i].w)), max(max(v[2 * i + 1].x, v[2 * i + 1].y), max(v[2 * i + 1].z, v[2 * i + 1].w))));
}
__device__ __forceinline__ uint32_t max_abs8(uint32_t m, uint32_t a, uint32_t b, uint32_t c, uint32_t d) { return max_abs2(max_abs2(m, max_abs2(a, b)), max_abs2(c, d)); }
__device__ __forceinline__ uint32_t warp_max_abs(uint32_t m) { return __reduce_max_sync(0xffffffffu, max((m << 16) & 0x7fff0000u, m & 0x7fff0000u)); }

__device__ __forceinline__ void last_rows(int pass) {
    extern __shared__ __align__(1024) unsigned char smem_raw[];
    const uint32_t sbase = smem_u32(smem_raw);
    const int tid = threadIdx.x, warp = __shfl_sync(0xffffffffu, tid >> 5, 0), h = blockIdx.x / 3;
    {
        const int sg = warp < 8, wq = warp & 3, lane = tid & 31;
        const uint32_t qk = sbase + SM_X + XBUF + sg * (2 * 9216), ob = sbase + SM_X + 2 * XBUF + sg * 8192;
        TST(0);
        if (pass) mbar_wait(sbase + B_VX + 8 * sg, 0);
        fence_async();
        TST(1);
        float sc[20];
#pragma unroll
        for (int i = 0; i < 20; i++) sc[i] = 0.f;
        {
            const uint64_t da = smem_desc(qk + 1024, 128, 1024), db = smem_desc(qk, 128, 2048);
            wg_fence();
#pragma unroll
            for (int ks = 0; ks < 8; ks++) wgmma_n40_ss(sc, da + (uint64_t)((ks >> 2) * 576 + (ks & 3) * 16), db + (uint64_t)((ks >> 2) * 576 + (ks & 3) * 16), ks > 0);
            wg_commit();
            wg_wait0();
        }
        uint32_t p[5], o[16];
        const float psum = xrow_softmax(sc, p, wq, lane);
        xrow_pv(o, p, psum, sbase + SM_T + ((NSEG - 2 + sg) & 3) * TBUF);
        if (pass) {
#pragma unroll
            for (int i = 0; i < 4; i++) stsm_x4(ob + (i >> 1) * 4096 + wq * 1024 + (i & 1) * 512 + lane * 16, o[4 * i], o[4 * i + 1], o[4 * i + 2], o[4 * i + 3]);
        }
        fence_async();
        named_bar(11 + sg, 128);
        TST(2);
        if ((tid & 127) == 0 && pass) {
            unsigned char* dst = reinterpret_cast<unsigned char*>(g_ox) + ((size_t)((NSEG / 2 - 1) * NH + h)) * 16384 + sg * 4096;
            asm volatile("cp.async.bulk.global.shared::cta.bulk_group [%0], [%1], 4096;" :: "l"(dst), "r"(ob) : "memory");
            asm volatile("cp.async.bulk.global.shared::cta.bulk_group [%0], [%1], 4096;" :: "l"(dst + 8192), "r"(ob + 4096) : "memory");
            asm volatile("cp.async.bulk.commit_group;" ::: "memory");
            asm volatile("cp.async.bulk.wait_group 0;" ::: "memory");
            asm volatile("red.relaxed.gpu.global.add.u32 [%0], 1;" :: "l"(&g_prog[(NSEG / 2 - 1) * 8 + (h >> 2)]) : "memory");
        }
        TST(3);
    }
    __syncwarp();
}

__global__ void __cluster_dims__(3, 1, 1) __launch_bounds__(384, 1)
k_chain(const __grid_constant__ CUtensorMap tmq, const __grid_constant__ CUtensorMap tmk,
        const __grid_constant__ CUtensorMap tmv, const __grid_constant__ CUtensorMap tmx2, const __grid_constant__ CUtensorMap tmo,
        const __grid_constant__ CUtensorMap tmm, const bf16* __restrict__ xg) {
    extern __shared__ __align__(1024) unsigned char smem_raw[];
    const uint32_t sbase = smem_u32(smem_raw);
    const int cta = blockIdx.x, h = cta / 3, role = cta - 3 * h;
    const int tid = threadIdx.x, warp = __shfl_sync(0xffffffffu, tid >> 5, 0), lane_o = tid & 31;
    TS3C(0);
    asm volatile("griddepcontrol.launch_dependents;" ::: "memory");
    auto stage_w = [&](int i) {
        tma_2d(sbase + SM_WS + i * 16384, role == 2 ? &tmv : &tmq, h * DH + (role == 1 ? 64 : 0), i * 64, sbase + B_W + 8 * i);
        tma_2d(sbase + SM_WS + i * 16384 + 8192, role == 2 ? &tmv : &tmk, h * DH + (role == 0 ? 0 : 64), i * 64, sbase + B_W + 8 * i);
    };
    auto stage_x = [&](int i) {
        tma_2d(sbase + x01_off(i), &tmx2, i * 64, 0, sbase + B_W + 8 * i);
        tma_2d(sbase + x01_off(i) + 8192, &tmm, i * 64, 0, sbase + B_W + 8 * i);
        if (i < 3) tma_2d(sbase + x23_off(i), &tmx2, i * 64, 64, sbase + B_W + 8 * i);
    };
    if (tid == 0) {
#pragma unroll
        for (int i = 0; i < 10; i++) mbar_init(sbase + B_W + 8 * i, 1);
        fence_async();
        TSQ(10);
#pragma unroll
        for (int i = 0; i < 3; i++) tma_2d(sbase + SM_X01 + i * 16384, &tmo, role * WOC + i * 64, h * DH, sbase + B_E);
        stage_x(0); stage_w(0);
        TSQ(11);
        mbar_expect(sbase + B_E, 49152);
#pragma unroll
        for (int i = 0; i < 9; i++) mbar_expect(sbase + B_W + 8 * i, 16384 + 9216 + (i < 3 ? 8192 : 0));
    } else if (tid == 32) {
#pragma unroll
        for (int i = 0; i < 8; i++) mbar_init(sbase + SM_BAR + 8 * i, 1);
        mbar_init(sbase + B_XF, 3);
        asm volatile("fence.mbarrier_init.release.cluster;" ::: "memory");
        for (int i = 0; i < 2; i++) {
            mbar_expect(sbase + B_SB + 8 * i, role == 2 ? 2560 : 1280 + 2048);
            mbar_expect(sbase + B_VX + 8 * i, role != 2 ? 8192 : 2 * 9216);
            mbar_expect(sbase + B_XT + 8 * i, 32768);
            mbar_expect(sbase + B_XT + 16 + 8 * i, i == 0 ? 40960 : 0);
        }
    }
    __syncthreads();
    TS3C(8);
    if (tid == 0) {
#pragma unroll 1
        for (int i = 1; i < NUP; i++) { if (i < 3) stage_x(i); stage_w(i); }
        TSQ(12);
    }
    __syncwarp();
    if (warp < 8) {
        uint32_t wreg[36 - NS][4];
        uint32_t v0, v1;
        {
            const int lane = lane_o;
            const uint32_t a = w_addr(sbase, warp, lane);
            const uint64_t da = smem_desc(sbase + SM_WS + (warp >> 2) * 8192, 1024, 1024) | (1ull << 62);
            float acc[36], acc1[32];
            uint32_t m = 0u;
#pragma unroll
            for (int i = 0; i < 36; i++) acc[i] = 0.f;
#pragma unroll
            for (int i = 0; i < 32; i++) acc1[i] = 0.f;
#pragma unroll 1
            for (int b = 0; b < 7; b++) {
                if (b == 0) TSQ(0);
                mbar_wait(sbase + B_W + 8 * b, 0);
                TSQ(1 + b);
                const uint64_t db = smem_desc(sbase + x01_off(b), 16, 1024) | (1ull << 62);
                wg_fence();
#pragma unroll
                for (int k = 0; k < 4; k++) wgmma_n72_ss(acc, da + (uint64_t)(b * 1024 + k * 128), db + (uint64_t)(k * 2));
                wg_commit();
                if (b < 3) {
                    const uint64_t d1 = smem_desc(sbase + x23_off(b), 16, 1024) | (1ull << 62);
                    wg_fence();
#pragma unroll
                    for (int k = 0; k < 4; k++) wgmma_n64_ss(acc1, da + (uint64_t)(b * 1024 + k * 128), d1 + (uint64_t)(k * 2));
                    wg_commit();
                }
                if (b == 2) {
                    wg_wait0();
                    bar_arrive(10, 384);
                }
                if (b == 3) {
                    if (tid == 0) mbar_expect(sbase + B_W + 8, 12);
                    __syncwarp();
                    if (role == 2) {
#pragma unroll
                        for (int ks = 0; ks < NS; ks++) {
                            uint32_t t[4];
                            ldsm_x4_t(t, a + (ks >> 2) * 16384 + (ks & 3) * 2048);
                            m = max_abs8(m, t[0], t[1], t[2], t[3]);
                        }
                    }
#pragma unroll
                    for (int ks = NS; ks < 16; ks++) ldsm_x4_t(wreg[ks - NS], a + (ks >> 2) * 16384 + (ks & 3) * 2048);
                }
                if (b == 5) {
#pragma unroll
                    for (int ks = 16; ks < 24; ks++) ldsm_x4_t(wreg[ks - NS], a + (ks >> 2) * 16384 + (ks & 3) * 2048);
                    if (role == 2) {
#pragma unroll
                        for (int ks = NS; ks < 24; ks++) m = max_abs8(m, wreg[ks - NS][0], wreg[ks - NS][1], wreg[ks - NS][2], wreg[ks - NS][3]);
                    }
                }
            }
            mbar_wait(sbase + B_W + 16, 1);
            TSQ(13);
            wg_fence();
#pragma unroll
            for (int k = 12; k < 20; k++)
                wgmma_n64_ss(acc1, da + (uint64_t)((k >> 2) * 1024 + (k & 3) * 128), (smem_desc(sbase + x23_off(k >> 2), 16, 1024) | (1ull << 62)) + (uint64_t)((k & 3) * 2));
            wg_commit();
            wg_wait0();
            named_bar(11, 384);
#pragma unroll
            for (int i = 0; i < 8; i++)
                asm volatile("st.shared.v4.f32 [%0], {%1,%2,%3,%4};" :: "r"(sbase + SM_X + 5 * 8192 + i * 4096 + tid * 16),
                             "f"(acc1[4 * i]), "f"(acc1[4 * i + 1]), "f"(acc1[4 * i + 2]), "f"(acc1[4 * i + 3]) : "memory");
#pragma unroll
            for (int b = 7; b < 9; b++) {
#pragma unroll
                for (int ks = 4 * b - 4; ks < 4 * b; ks++) ldsm_x4_t(wreg[ks - NS], a + (ks >> 2) * 16384 + (ks & 3) * 2048);
                if (role == 2) {
#pragma unroll
                    for (int ks = 4 * b - 4; ks < 4 * b; ks++) m = max_abs8(m, wreg[ks - NS][0], wreg[ks - NS][1], wreg[ks - NS][2], wreg[ks - NS][3]);
                }
                const uint64_t db = smem_desc(sbase + x01_off(b), 16, 1024) | (1ull << 62);
                mbar_wait(sbase + B_W + 8 * b, 0);
                TSQ(1 + b);
                if (b == 8) TS3C(2);
                wg_fence();
#pragma unroll
                for (int k = 0; k < 4; k++) wgmma_n72_ss(acc, da + (uint64_t)(b * 1024 + k * 128), db + (uint64_t)(k * 2));
                wg_commit();
            }
#pragma unroll
            for (int ks = 32; ks < KPRE; ks++) ldsm_x4_t(wreg[ks - NS], a + (ks >> 2) * 16384 + (ks & 3) * 2048);
            if (role == 2) {
#pragma unroll
                for (int ks = KPRE; ks < 36; ks++) {
                    uint32_t t[4];
                    ldsm_x4_t(t, a + (ks >> 2) * 16384 + (ks & 3) * 2048);
                    m = max_abs8(m, t[0], t[1], t[2], t[3]);
                }
#pragma unroll
                for (int ks = 32; ks < KPRE; ks++) m = max_abs8(m, wreg[ks - NS][0], wreg[ks - NS][1], wreg[ks - NS][2], wreg[ks - NS][3]);
                m = warp_max_abs(m);
                if (lane == 0) asm volatile("st.volatile.global.u32 [%0], %1;" :: "l"(reinterpret_cast<uint32_t*>(&g_wv[h][0]) + warp), "r"(m | 1u) : "memory");
                __syncwarp();
            }
            wg_wait0();
            named_bar(9, 256);
            const uint32_t off = sbase + SM_T + (DH + warp * 16 + (lane & 15)) * 16 + (lane >> 4) * (DH * 16);
#pragma unroll
            for (int i = 0; i < 4; i++)
                stsm_x4(off + (i >> 1) * TBUF + (i & 1) * (2 * DH * 16), pack_bf16(acc[8 * i], acc[8 * i + 1]), pack_bf16(acc[8 * i + 2], acc[8 * i + 3]),
                        pack_bf16(acc[8 * i + 4], acc[8 * i + 5]), pack_bf16(acc[8 * i + 6], acc[8 * i + 7]));
            v0 = pack_bf16(acc[32], acc[33]);
            v1 = pack_bf16(acc[34], acc[35]);
#pragma unroll
            for (int ks = KPRE; ks < 36; ks++) ldsm_x4_t(wreg[ks - NS], a + (ks >> 2) * 16384 + (ks & 3) * 2048);
            if (role == 2) fence_async();
            bar_arrive(8, 384);
            named_bar(7, 256);
            asm volatile("barrier.cluster.arrive.relaxed.aligned;" ::: "memory");
        }
        TS3C(3);
        uint32_t ws[NS][4];
#pragma unroll
        for (int ks = NS - NP; ks < NS; ks++) ldsm_x4_t(ws[ks], w_addr(sbase, warp, lane_o) + (ks >> 2) * 16384 + (ks & 3) * 2048);
        asm volatile("barrier.cluster.wait.aligned;" ::: "memory");
        if (lane_o == 0 && role != 2 && warp < 2) tma_2d_mc(sbase + SM_X + (2 * role + warp) * 8192, &tmx2, (2 * role + warp + 5) * 64, 64, sbase + B_XT + 8);
        __syncwarp();
        TS3C(4);
        auto main_loop = [&](auto is_c) {
            constexpr bool C = decltype(is_c)::value;
            if (C) pad_code<PAD4>(); else pad_code<PAD3>();
            const uint32_t l16 = __shfl_sync(0xffffffffu, sbase + lane_o * 16, lane_o);
            const uint32_t ka = __shfl_sync(0xffffffffu, sbase + SM_T + (64 + (lane_o & 7) + ((lane_o >> 3) & 1) * 16 + (lane_o >> 4) * 8) * 16, lane_o);
            const uint32_t wa = __shfl_sync(0xffffffffu, w_addr(sbase, warp, lane_o), lane_o);
            auto post = [&](bool act, int s, uint32_t to, uint32_t ta, int scw, uint32_t v0, uint32_t v1) {
                int lane = lane_o;
                asm volatile("" : "+r"(lane));
                asm volatile("stmatrix.sync.aligned.m8n8.x2.shared.b16 [%0], {%1,%2};" :: "r"(l16 + ta), "r"(v0), "r"(v1) : "memory");
                if (C) {
                    if (act || s + 1 < NSEG) {
                        const uint32_t fo = (uint32_t)(warp * 256 + lane * 8);
                        const uint32_t rb0 = mapa(sbase, 0), rb1 = mapa(sbase, 1);
                        st_async64(rb0 + SM_VM + fo, v0, v1, rb0 + B_SB + 8 * (s & 1));
                        st_async64(rb1 + SM_VM + fo, v0, v1, rb1 + B_SB + 8 * (s & 1));
                        asm volatile("st.shared.v2.u32 [%0], {%1,%2};" :: "r"(sbase + SM_VM + fo), "r"(v0), "r"(v1) : "memory");
                        bar_arrive(2, 384);
                    }
                } else if (act) bar_arrive(2, 384);
                else {
                    named_bar(2, 384);
                    if (scw == 0) {
                        uint32_t kf[2][4], qf[2][4];
#pragma unroll
                        for (int k2 = 0; k2 < 2; k2++) { ldsm_x4_t(kf[k2], ka + to + k2 * 512); ldsm_x4_t(qf[k2], l16 + SM_T + to + k2 * 512); }
                        const uint32_t d0 = sbase + SM_S + lane * 8, bo = sbase + B_SB + 8 * (s & 1);
                        const uint32_t d1 = mapa(d0 + 1280, role ^ 1), m1 = mapa(bo, role ^ 1), d2 = mapa(d0 + role * 1280, 2), m2 = mapa(bo, 2);
                        score_group(qf, kf, d0, d1, m1, d2, m2);
                        bar_arrive(6, 160);
                        bar_arrive(5, 384);
                    }
                    if (RARE(scw == 8)) {
                        const uint32_t dk = mapa(sbase + SM_X + XBUF + (2 + role) * 9216 + (warp - 4) * 256 + lane * 4, 2), mb = mapa(sbase + B_VX + 8, 2);
                        st_async32(dk, v0, mb);
                        st_async32(dk + 128, v1, mb);
                    }
                }
                FS(11, 0);
            };
            post(false, 0, 0, SM_T + warp * 256, warp ^ 7, v0, v1);
            if (tid == 128 && cta < NSEG) {
                fence_async();
                mbar_expect(sbase + B_E, XBUF);
                bulk_g2s(sbase + SM_X + 9 * 8192, xg + (size_t)cta * SEG * DM, 32768, sbase + B_E);
                bulk_g2s(sbase + SM_WS + 32768 + 4096, xg + (size_t)cta * SEG * DM + 16384, 4096, sbase + B_E);
            }
            __syncwarp();
            if (C) {
                named_bar(7, 256);
                if (warp == 1) norms_gather(lane_o, sbase);
            }
            auto chores = [&](int s, bool idle) {
                int lane = lane_o;
                asm volatile("" : "+r"(lane));
                const int hw = (s & 1) ? warp : warp - 4;
                const uint32_t tb = sbase + SM_T + (s & 3) * TBUF;
                if (idle) { if (hw != 2) named_bar(4, 384); else bar_arrive(4, 384); }
                if (hw == 2) {
                    if (lane == 0) {
                        if (C || !idle) fence_async();
                        if (C) {
                            store_tile(s + 1, h, 2, sbase + SM_T + ((s + 1) & 3) * TBUF, 2048, 10240);
                            store_tile(s, h, 2, tb, 0, idle ? 2048 : 10240);
                        } else store_tile(s, h, role, tb, 1024, 10240);
                        asm volatile("cp.async.bulk.commit_group;" ::: "memory");
                        asm volatile("cp.async.bulk.wait_group 0;" ::: "memory");
                        if (C) {
                            asm volatile("cp.async.bulk.shared::cluster.global.mbarrier::complete_tx::bytes.multicast::cluster [%0], [%1], 8192, [%2], %3;"
                                         :: "r"(sbase + SM_VX + ((s + 1) & 1) * 8192), "l"(&g_qkv[s + 1][h][2][2048]), "r"(sbase + B_VX + 8 * ((s + 1) & 1)), "h"((unsigned short)3) : "memory");
                        }
                        asm volatile("red.relaxed.gpu.global.add.u32 [%0], 1;" :: "l"(&g_flag[h * NSEG + s]) : "memory");
                    }
                    __syncwarp();
                    if (!C && (s & 1) && s + 4 < NSEG) bar_arrive(13, 160);
                }
                __syncwarp();
            };
            auto put_tiles = [&](const float (&acc)[32], uint32_t off) {
#pragma unroll
                for (int i = 0; i < 4; i++)
                    stsm_x4(off + (i >> 1) * TBUF + (i & 1) * (2 * DH * 16), pack_bf16(acc[8 * i], acc[8 * i + 1]), pack_bf16(acc[8 * i + 2], acc[8 * i + 3]),
                            pack_bf16(acc[8 * i + 4], acc[8 * i + 5]), pack_bf16(acc[8 * i + 6], acc[8 * i + 7]));
            };
            auto tile_off = [&](int p) {
                int lane = lane_o;
                asm volatile("" : "+r"(lane));
                return sbase + SM_T + (p & 1) * (2 * TBUF) + (DH + warp * 16 + (lane & 15)) * 16 + (lane >> 4) * (DH * 16);
            };
            {
                auto db = [&](int ks) { return (smem_desc(sbase + SM_X, 16, 1024) | (1ull << 62)) + (uint64_t)(((ks >> 2) - 5) * 512 + (ks & 3) * 2); };
                float acc[32];
#pragma unroll
                for (int i = 0; i < 8; i++)
                    asm volatile("ld.shared.v4.f32 {%0,%1,%2,%3}, [%4];" : "=f"(acc[4 * i]), "=f"(acc[4 * i + 1]), "=f"(acc[4 * i + 2]), "=f"(acc[4 * i + 3])
                                 : "r"(l16 + warp * 512 + SM_X + 5 * 8192 + i * 4096) : "memory");
                mbar_wait(sbase + B_XT + 8, 0);
                if (C) { if (warp < 4) named_bar(4, 384); } else if (warp != 7) named_bar(5, 384);
                wg_fence();
#pragma unroll
                for (int ks = 35; ks > 35 - NC0; ks--) wgmma_n64(acc, wreg[ks - NS], db(ks), 1);
                wg_commit();
                wg_wait0();
                if (warp == 5) {
                    mbar_wait(sbase + B_W + 8, 1);
                    bar_arrive(12, 160);
                }
                chores(0, false);
                if (!C || warp >= 4) named_bar(4, 384);
                wg_fence();
#pragma unroll
                for (int ks = 35 - NC0; ks >= 20; ks--) wgmma_n64(acc, wreg[ks - NS], db(ks), 1);
                wg_commit();
                if (cta < NSEG) {
                    uint32_t m = 0u;
                    mbar_wait(sbase + B_E, 1);
#pragma unroll 1
                    for (int j = 0; j < 9; j++) {
                        const uint4 xv = lds128(l16 + warp * 512 + (j < 8 ? SM_X + 9 * 8192 + j * 4096 : SM_WS + 32768 + 4096));
                        m = max_abs8(m, xv.x, xv.y, xv.z, xv.w);
                    }
                    m = warp_max_abs(m);
                    if (lane_o == 0) asm volatile("st.volatile.global.u32 [%0], %1;" :: "l"(reinterpret_cast<uint32_t*>(&g_rx[cta][0]) + warp), "r"(m | 1u) : "memory");
                    __syncwarp();
                }
                wg_wait0();
                put_tiles(acc, tile_off(1));
            }
            auto mem_proj = [&](uint32_t& u0, uint32_t& u1) {
#pragma unroll
                for (int ks = 0; ks < NS - NP; ks++) ldsm_x4_t(ws[ks], wa + (ks >> 2) * 16384 + (ks & 3) * 2048);
                FS(0, ws[0][0]);
                named_bar(1, 384);
                float acc[2][4], minv;
                uint32_t b[3][4];
#pragma unroll
                for (int kk = 0; kk < 3; kk++) ldsm_x4_t(b[kk], l16 + SM_M + kk * 512);
                FS(1, b[0][0]);
#pragma unroll
                for (int kk = 0; kk < 18; kk++) {
#pragma unroll
                    for (int i = 0; i < 2; i++) {
                        const int ks = 2 * kk + i;
                        if (ks < 2) mma_z(acc[i], ws[ks], b[kk % 3][2 * i], b[kk % 3][2 * i + 1]);
                        else if (ks < NS) mma_bf16(acc[i], ws[ks < NS ? ks : 0], b[kk % 3][2 * i], b[kk % 3][2 * i + 1]);
                        else mma_bf16(acc[i], wreg[ks >= NS ? ks - NS : 0], b[kk % 3][2 * i], b[kk % 3][2 * i + 1]);
                    }
                    if (kk + 3 < 18) ldsm_x4_t(b[kk % 3], l16 + SM_M + (kk + 3) * 512);
                    if (kk + 3 == 17) asm volatile("ld.shared.f32 %0, [%1];" : "=f"(minv) : "r"(sbase + SM_SC + 8) : "memory");
                }
                u0 = pack_bf16(fmaf(acc[1][0], minv, acc[0][0] * minv), fmaf(acc[1][1], minv, acc[0][1] * minv));
                u1 = pack_bf16(fmaf(acc[1][2], minv, acc[0][2] * minv), fmaf(acc[1][3], minv, acc[0][3] * minv));
                FS(2, u0);
            };
            int s = 0, rc = 9;
            bool act = warp >= 4;
            uint32_t to = TBUF, ta = SM_T + warp * 256 + TBUF;
            auto next_slot = [&]() {
                const uint32_t d = (s & 3) == 3 ? -3 * TBUF : TBUF;
                to += d; ta += d;
                asm volatile("" : "+r"(to), "+r"(ta));
            };
#pragma unroll 1
            for (;;) {
                uint32_t u0, u1;
                if (act) {
                    mem_proj(u0, u1);
                    s++;
                    post(true, s, to, ta, 1, u0, u1);
                    const int p = (s + 3) >> 1;
                    const uint32_t dlo = (uint32_t)smem_desc(sbase + SM_X, 16, 1024) + rc * 512;
                    const uint64_t da = smem_desc(sbase + SM_WS + (warp >> 2) * 8192, 1024, 1024) | (1ull << 62);
                    auto db = [&](int ks) {
                        const int j = ((ks >> 2) + 4) % 9;
                        return ((uint64_t)0x40000040u << 32) | (uint64_t)(dlo + (uint32_t)((j - (rc + j >= 13 ? 13 : 0)) * 512 + (ks & 3) * 2));
                    };
                    const uint32_t xph = (uint32_t)((p - 1) >> 1) & 1u;
                    float acc[32];
                    mbar_wait(sbase + B_XT + 8 * (p & 1), xph);
                    if (C) named_bar(7, 256); else named_bar(5, 384);
                    if ((C ? CC_DELAY : C1_DELAY) > 0) { const uint32_t t1 = clock32(); while (clock32() - t1 < (C ? CC_DELAY : C1_DELAY)) {} }
                    constexpr int N1 = C ? NC1C : NC1;
                    wg_fence();
#pragma unroll
                    for (int ks = 35; ks > 35 - N1; ks--) { if (ks == 35) wgmma_n64_z(acc, wreg[ks - NS], db(ks)); else wgmma_n64(acc, wreg[ks - NS], db(ks), 1); }
                    wg_commit();
                    wg_wait0();
                    FS(9, __float_as_uint(acc[0]));
                    next_slot();
                    FS(8, 0);
                    if (B4P) asm volatile("{\n.reg .pred p;\nsetp.ge.s32 p, %0, 0;\n@p bar.sync 4, 384;\n}" :: "r"(s) : "memory");
                    else named_bar(4, 384);
                    FS(3, 0);
                    wg_fence();
#pragma unroll
                    for (int ks = 35 - N1; ks >= KG1; ks--) wgmma_n64(acc, wreg[ks - NS], db(ks), 1);
                    wg_commit();
                    mbar_wait(sbase + B_XT + 16 + 8 * (p & 1), xph);
                    wg_fence();
#pragma unroll
                    for (int ks = 0; ks < NS; ks++) wgmma_n64_ss(acc, da + (uint64_t)((ks >> 2) * 1024 + (ks & 3) * 128), db(ks));
#pragma unroll
                    for (int ks = NS; ks < KG1; ks++) wgmma_n64(acc, wreg[ks - NS], db(ks), 1);
                    wg_commit();
                    if (!C && warp >= 4) named_bar(13, 160);
                    uint32_t off = tile_off(p);
                    rc = rc >= 4 ? rc - 4 : rc + 9;
                    asm volatile("" : "+r"(off), "+r"(rc));
                    wg_wait0();
                    put_tiles(acc, off);
                    FS(7, __float_as_uint(acc[0]));
                }
                int scw = s + 2 < NSEG ? warp ^ ((s & 1) ? 7 : 3) : (warp & 4) + 4;
                asm volatile("" : "+r"(scw));
                mem_proj(u0, u1);
                s++;
                post(false, s, to, ta, scw, u0, u1);
                if (s + 1 == NSEG) break;
                if (s + 2 < NSEG) {
                    if (!C && (warp & 3) == 2) fence_async();
                    if (C) named_bar(7, 256); else if (scw != 0) named_bar(5, 384);
                    chores(s, true);
                } else {
                    const uint32_t t0 = clock32();
                    const uint32_t dq = mapa(sbase + SM_X + XBUF + role * 9216, 2), mb = mapa(sbase + B_VX, 2);
                    if (!C) {
                        if (scw != 0) named_bar(5, 384);
                        if (tid == 64) { fence_async(); while (clock32() - t0 < TL_DELAY) {} bulk_s2s(dq, sbase + SM_T + 2 * TBUF + 1024, 9216, mb); }
                        __syncwarp();
                    }
                    named_bar(4, 384);
                    if (!C && tid == 64) { const uint32_t t1 = clock32(); while (clock32() - t1 < VX_DELAY) {} bulk_s2s(dq + 2 * 9216 + 1024, sbase + SM_T + 3 * TBUF + 2048, 8192, mb + 8); }
                    __syncwarp();
                }
                next_slot();
                act = s + 4 < NSEG;
            }
            if (C) named_bar(7, 256);
        };
        if (role == 2) main_loop(Flag<true>()); else main_loop(Flag<false>());
    } else {
        uint32_t wo[3][8][4];
        uint32_t mx2 = 0u;
        {
            const int pt = tid - 256, lane = lane_o, wq = warp - 8, g = lane >> 2, tq = lane & 3;
            TSQ(7);
            if (XPF && cta < 9) asm volatile("prefetch.global.L2 [%0];" :: "l"(xg + 64 * DM + (cta * 128 + pt) * 64));
            mbar_wait(sbase + B_E, 0);
            TSQ(8);
#pragma unroll
            for (int t = 0; t < 3; t++) {
                const int T = 3 * wq + t;
                const uint32_t a = sbase + SM_X01 + (T >> 2) * 16384 + ((lane >> 4) * 8 + (lane & 7)) * 128 + ((((T & 3) * 2 + ((lane >> 3) & 1)) ^ (lane & 7)) << 4);
#pragma unroll
                for (int kk = 0; kk < 8; kk++) ldsm_x4_t(wo[t][kk], a + ((2 * wq + kk) & 7) * 2048);
            }
            named_bar(3, 128);
            if (pt == 64) {
                fence_async();
#pragma unroll 1
                for (int i = 3; i < 9; i++) { stage_x(i); if (i < 7) stage_w(i); }
            }
            if (pt >= 96 && pt < 120) {
                *reinterpret_cast<uint4*>(g_acc + cta * 1024 + (pt - 96) * 16) = make_uint4(0u, 0u, 0u, 0u);
                __threadfence();
            }
            __syncwarp();
            TSQ(9);
            float c0 = 0.f;
#pragma unroll
            for (int t = 0; t < 3; t++) {
                float n[4][4];
#pragma unroll
                for (int i = 0; i < 4; i++) { n[i][0] = n[i][1] = n[i][2] = n[i][3] = 0.f; }
#pragma unroll
                for (int kk = 0; kk < 8; kk++)
#pragma unroll
                    for (int i = 0; i < 4; i++) mma_k8(n[i], wo[t][kk][i & 2], wo[t][kk][(i & 2) + 1], wo[t][kk][i]);
                if ((g >> 1) == tq) c0 = fmaxf(c0, (g & 1) ? fmaxf(n[0][1] + n[2][1], n[1][3] + n[3][3]) : fmaxf(n[0][0] + n[2][0], n[1][2] + n[3][2]));
            }
            c0 = __uint_as_float(__reduce_max_sync(0xffffffffu, __float_as_uint(c0)));
            uint32_t m = 0u;
            const int xb = role == 0 ? h % 9 : 9;
            auto x_max = [&]() {
                mbar_wait(sbase + B_W + 8 * xb, 0);
#pragma unroll
                for (int j = 0; j < 5; j++) {
                    uint4 xv;
                    asm volatile("ld.shared.v4.u32 {%0,%1,%2,%3}, [%4];" : "=r"(xv.x), "=r"(xv.y), "=r"(xv.z), "=r"(xv.w)
                                 : "r"(sbase + x01_off(xb) + (j < 4 ? pt + 128 * j : 512 + (pt & 63)) * 16) : "memory");
                    m = max_abs8(m, xv.x, xv.y, xv.z, xv.w);
                }
            };
            if (xb < 3) x_max();
            named_bar(10, 384);
            TSQ(10);
            if (pt == 64) {
                fence_async();
                mbar_expect(sbase + B_W + 16, 16384);
#pragma unroll
                for (int i = 3; i < 5; i++) tma_2d(sbase + x23_off(i), &tmx2, i * 64, 64, sbase + B_W + 16);
#pragma unroll 1
                for (int i = 7; i < 9; i++) stage_w(i);
            }
            __syncwarp();
            if (xb >= 3 && xb < 7) x_max();
            bar_arrive(11, 384);
            if (xb == 7 || xb == 8) x_max();
            asm volatile("barrier.cluster.arrive.relaxed.aligned;" ::: "memory");
            m = warp_max_abs(m);
            if (lane == 0) { sts32(sbase + SM_SC + 320 + 4 * wq, __float_as_uint(c0)); sts32(sbase + SM_SC + 336 + 4 * wq, m); }
            TSQ(1);
            named_bar(3, 128);
            if (pt == 0) {
                const uint4 a = lds128(sbase + SM_SC + 320), b = lds128(sbase + SM_SC + 336);
                st_vol_u2(&g_norm[cta], make_uint2(max(max(a.x, a.y), max(a.z, a.w)) | 1u, max(max(b.x, b.y), max(b.z, b.w)) | 1u));
            }
            __syncwarp();
            named_bar(8, 384);
            TSQ(2);
            asm volatile("barrier.cluster.wait.aligned;" ::: "memory");
            if (role == 2 && lane == 0 && wq < 2) vx_copy(sbase, 0, wq);
            __syncwarp();
        }
        const int wq = warp - 8;
        auto helper_loop = [&](auto is_c) {
        const bool C = is_c.value;
        if (C) pad_code<PAD2>(); else pad_code<PAD1>();
        const uint32_t sb = sbase;
        const uint32_t l8_o = __shfl_sync(0xffffffffu, sb + lane_o * 8, lane_o), l16_o = __shfl_sync(0xffffffffu, sb + lane_o * 16, lane_o);
        unsigned char* dst = g_acc + (role * 32 + wq * 8 + (lane_o >> 3)) * 1024 + (lane_o & 7) * 16;
        auto load_kf = [&](uint32_t (&kf)[2][4], int slot) {
            int lane = lane_o;
            asm volatile("" : "+r"(lane));
            const uint32_t ka = sb + SM_T + slot * TBUF + ((wq + 1) * DH + 64 + (lane & 7) + ((lane >> 3) & 1) * 16 + (lane >> 4) * 8) * 16;
#pragma unroll
            for (int k2 = 0; k2 < 2; k2++) ldsm_x4_t(kf[k2], ka + k2 * 512);
        };
        float minv = 1.f;
        uint32_t kf[2][4];
        if (!C) load_kf(kf, 0);
        int b3 = 0;
        int rx = 9;
        for (int s = 0; s + 1 < NSEG; s++) {
            const int n3 = b3 == 2 ? 0 : b3 + 1;
            uint32_t l8 = l8_o, l16 = l16_o;
            asm volatile("" : "+r"(l8), "+r"(l16));
            {
                int lane = lane_o;
                asm volatile("" : "+r"(lane));
                if (C) {
                    if (lane == 0) {
                        if (wq == 3 && h == 0) {
                            const uint32_t t = gtime32();
                            st_vol_u2(&g_tick, make_uint2(t, lds32(sb + SM_SC + 12)));
                            sts32(sb + SM_SC + 12, t);
                        }
                    }
                    __syncwarp();
                    if (wq == 2 && s > 1 && lane < 24) {
                        *reinterpret_cast<uint4*>(g_acc + n3 * 128 + (3 * h + (lane >> 3)) * 1024 + (lane & 7) * 16) = make_uint4(0u, 0u, 0u, 0u);
                    }
                    if (RARE(wq == 1 && s == 3 && lane < 3)) {
                        const int c = 3 * h + lane;
                        st_vol_u2(&g_norm[c], make_uint2(0u, 0u));
                        uint4* z = c < NSEG ? g_rx[c] : g_wv[c - NSEG];
                        st_vol_u4(z, make_uint4(0u, 0u, 0u, 0u)); st_vol_u4(z + 1, make_uint4(0u, 0u, 0u, 0u));
                    }
                    __syncwarp();
                }
                const uint32_t mw = __reduce_max_sync(0xffffffffu, max(mx2 << 16, mx2 & 0xffff0000u));
                if (lane == 0) sts32(sb + SM_SC + 16 + 4 * wq, mw);
            }
            const uint32_t to = SM_T + (s & 3) * TBUF;
            const uint32_t ph = (uint32_t)(s >> 1) & 1u;
            if (!C) {
                const uint32_t bo = sb + B_SB + 8 * (s & 1);
                uint32_t d0 = l8 + SM_S + (wq + 1) * 256, qa = l16 + to;
                const uint32_t d1 = mapa(d0 + 1280, role ^ 1), m1 = mapa(bo, role ^ 1), d2 = mapa(d0 + role * 1280, 2), m2 = mapa(bo, 2);
                asm volatile("" : "+r"(d0), "+r"(qa));
                mbar_wait(sb + (s > 0 ? B_VX + 8 * (s & 1) : B_W), ph);
                FS(1, 0);
                named_bar(2, 384);
                uint32_t qf[2][4];
#pragma unroll
                for (int k2 = 0; k2 < 2; k2++) ldsm_x4_t(qf[k2], qa + k2 * 512);
                score_group(qf, kf, d0, d1, m1, d2, m2);
                bar_arrive(5, 384);
            } else named_bar(2, 384);
            if (!C && s == 0) {
                TSQ(3);
                mbar_wait(sb + B_VX, 0);
                TSQ(4);
            }
            float4 m4;
            asm volatile("ld.shared.v4.f32 {%0,%1,%2,%3}, [%4];" : "=f"(m4.x), "=f"(m4.y), "=f"(m4.z), "=f"(m4.w) : "r"(sb + SM_SC + 16) : "memory");
            const float c24 = __uint_as_float(lds32(sb + SM_SC + 4)), xb = __uint_as_float(lds32(sb + SM_SC + 64 + 4 * s));
            uint32_t vf[2][2][4], vm[2][2];
            uint32_t va = l16 + ((l16 >> 8) & 1) * 1792 + wq * 512 + (C ? to + DH * 16 : SM_VX + (s & 1) * 8192);
            auto load_vf = [&]() {
#pragma unroll
                for (int i = 0; i < 4; i++) ldsm_x4(vf[i & 1][i >> 1], va + (i & 1) * 256 + (i >> 1) * 4096);
            };
            load_vf();
            float scale = to_scale(fmaxf(fmaxf(fmaxf(m4.x, m4.y), fmaxf(m4.z, m4.w)) * minv, xb) * c24);
            uint32_t oa = l16 + wq * 512;
            asm volatile("" : "+f"(scale), "+r"(oa), "+r"(va));
            FS(7, __float_as_uint(scale));
            if (!C) named_bar(6, 160);
            if (C) mbar_wait_fast(sb + B_SB + 8 * (s & 1), ph);
            float sv[5][2];
#pragma unroll
            for (int j = 0; j < 5; j++) lds64f(sv[j][0], sv[j][1], l8 + SM_S + j * 256);
            if (!C) mbar_wait_fast(sb + B_SB + 8 * (s & 1), ph);
            FS(6, 0);
            uint32_t p[5];
            {
                float sr[5][2];
#pragma unroll
                for (int j = 0; j < 5; j++) lds64f(sr[j][0], sr[j][1], l8 + SM_S + 1280 + j * 256);
                lds64(vm[0][0], vm[0][1], l8 + SM_VM + wq * 512);
                lds64(vm[1][0], vm[1][1], l8 + SM_VM + wq * 512 + 256);
#pragma unroll
                for (int j = 0; j < 5; j++) {
                    sv[j][0] += sr[j][0];
                    sv[j][1] += sr[j][1];
                }
                float mx = fmaxf(fmaxf(fmaxf(sv[0][0], sv[0][1]), fmaxf(sv[1][0], sv[1][1])), fmaxf(fmaxf(sv[2][0], sv[2][1]), fmaxf(sv[3][0], sv[3][1])));
                mx = fmaxf(mx, fmaxf(sv[4][0], sv[4][1]));
                {
                    const float m1 = __shfl_xor_sync(0xffffffffu, mx, 1), m2 = __shfl_xor_sync(0xffffffffu, mx, 2), m3 = __shfl_xor_sync(0xffffffffu, mx, 3);
                    mx = fmaxf(fmaxf(mx, m1), fmaxf(m2, m3));
                }
#pragma unroll
                for (int jj = 0; jj < 5; jj++) {
                    const int j = (jj + 1) % 5;
                    asm("ex2.approx.ftz.f32 %0, %1;" : "=f"(sv[j][0]) : "f"(sv[j][0] - mx));
                    asm("ex2.approx.ftz.f32 %0, %1;" : "=f"(sv[j][1]) : "f"(sv[j][1] - mx));
                    p[j] = pack_bf16(sv[j][0], sv[j][1]);
                }
            }
            FS(0, p[0]);
            uint32_t b[4][4];
            const uint32_t one4[4] = {0x3f803f80u, 0x3f803f80u, 0x3f803f80u, 0x3f803f80u};
            float zs[4];
            {
                float o0[2][4], o1[2][4];
                mma_z(o0[0], vf[0][0], p[1], p[2]);
                mma_z(o0[1], vf[1][0], p[1], p[2]);
                mma_z(o1[0], vf[0][1], p[3], p[4]);
                mma_z(o1[1], vf[1][1], p[3], p[4]);
                mma_k8(o0[0], vm[0][0], vm[0][1], p[0]);
                mma_k8(o0[1], vm[1][0], vm[1][1], p[0]);
                if ((ZSM & 1) == 0) {
                    mma_z(zs, one4, p[1], p[2]);
                    mma_bf16(zs, one4, p[3], p[4]);
                    mma_k8(zs, one4[0], one4[1], p[0]);
                } else {
                    float z2[4];
                    mma_z(zs, one4, p[1], p[2]);
                    mma_z(z2, one4, p[3], p[4]);
                    mma_k8(zs, one4[0], one4[1], p[0]);
                    zs[0] += z2[0]; zs[1] += z2[1];
                }
                uint32_t ow[4];
#pragma unroll
                for (int m = 0; m < 2; m++) {
                    ow[2 * m] = pack_bf16(o0[m][0] + o1[m][0], o0[m][1] + o1[m][1]);
                    ow[2 * m + 1] = pack_bf16(o0[m][2] + o1[m][2], o0[m][3] + o1[m][3]);
                }
                stsm_x4(oa + SM_O, ow[0], ow[1], ow[2], ow[3]);
                FS(2, 0);
                if (ZSM & 2) {
                    __syncwarp();
                    ldsm_x4_t(b[0], oa + SM_O);
                } else if (ZSM & 4) {
                    b[0][0] = movm(ow[0]); b[0][1] = movm(ow[1]);
                    __syncwarp();
                    asm volatile("ldmatrix.sync.aligned.m8n8.x2.trans.shared.b16 {%0,%1}, [%2];" : "=r"(b[0][2]), "=r"(b[0][3]) : "r"(oa + SM_O + 256));
                } else {
#pragma unroll
                    for (int i = 0; i < 4; i++) b[0][i] = movm(ow[i]);
                }
            }
            float acc[3][2][4];
            named_bar(3, 128);
#pragma unroll
            for (int i = 1; i < 4; i++) ldsm_x4_t(b[i], l16 + SM_O + ((wq + i) & 3) * 512);
#pragma unroll
            for (int c = 0; c < 2; c++)
#pragma unroll
                for (int t = 0; t < 3; t++) mma_z(acc[t][c], wo[t][c], b[0][2 * c], b[0][2 * c + 1]);
            float z0, z1;
            asm volatile("rcp.approx.ftz.f32 %0, %1;" : "=f"(z0) : "f"(zs[0]));
            asm volatile("rcp.approx.ftz.f32 %0, %1;" : "=f"(z1) : "f"(zs[1]));
            asm volatile("{\n.reg .pred p;\nsetp.eq.s32 p, %1, 0;\n@p bar.sync 12, 160;\n@p ld.shared.f32 %0, [%2];\n}" : "+f"(scale) : "r"(s), "r"(sb + SM_SC) : "memory");
            z0 *= scale; z1 *= scale;
            FS(3, b[1][0]);
#pragma unroll
            for (int i = 1; i < 4; i++)
#pragma unroll
                for (int c = 0; c < 2; c++)
#pragma unroll
                    for (int t = 0; t < 3; t++) mma_bf16(acc[t][c], wo[t][2 * i + c], b[i][2 * c], b[i][2 * c + 1]);
            {
                uint32_t w[6];
#pragma unroll
                for (int t = 0; t < 3; t++) {
                    w[2 * t] = pack_f16(fmaf(acc[t][1][0], z0, acc[t][0][0] * z0), fmaf(acc[t][1][1], z1, acc[t][0][1] * z1));
                    w[2 * t + 1] = pack_f16(fmaf(acc[t][1][2], z0, acc[t][0][2] * z0), fmaf(acc[t][1][3], z1, acc[t][0][3] * z1));
                }
                FS(8, w[5]);
                asm volatile("red.relaxed.gpu.global.add.noftz.v4.f16x2 [%0], {%1,%2,%3,%4};" :: "l"(dst), "r"(w[0]), "r"(w[1]), "r"(w[2]), "r"(0x3c00u) : "memory");
                asm volatile("red.relaxed.gpu.global.add.noftz.v4.f16x2 [%0], {%1,%2,%3,%4};" :: "l"(dst + 4096), "r"(w[3]), "r"(w[4]), "r"(w[5]), "r"(0x3c00u) : "memory");
            }
            FS(9, 0);
            if (s == 0) TSQ(5);
            bar_arrive(4, 384);
            const uint32_t t0 = clock32();
            minv = __uint_as_float(0x7f000000u - __float_as_uint(scale));
            if (lane_o == 0) {
                if (wq == 0) sts32(sb + SM_SC + 8, __float_as_uint(minv));
                if (s + 3 < NSEG) {
                    if (wq == 0) mbar_expect(sb + B_SB + 8 * (s & 1), C ? 2560 : 1280 + 2048);
                    if (wq == 1 && s > 0 && s + 5 < NSEG) mbar_expect(sb + B_XT + ((s & 1) ? 0 : 16) + 4 * ((s + 1) & 2), (s & 1) ? 32768 : 40960);
                    if (wq == 3 && !C) mbar_expect(sb + B_VX + 8 * (s & 1), 8192);
                }
            }
            __syncwarp();
            if (RARE(s == 1)) {
                if (!C) pad_code<PADC>();
                int lane = lane_o;
                asm volatile("" : "+r"(lane));
                if (wq == 3) xmax_gather(lane, sb);
                __syncwarp();
            }
            if (!C) load_kf(kf, (s + 1) & 3);
            const uint4* src = reinterpret_cast<const uint4*>(dst + (wq * 16 - role * 32) * 1024);
            dst += n3 == 0 ? -256 : 128;
            asm volatile("" : "+l"(dst));
            const int xp = (s + 5) >> 1, kb = wq + ((s & 1) ? 2 * role : 4 + 3 * role);
            const bool xl = !C && xp < NSEG / 2 && wq < ((s & 1) ? 2 : 3 - role);
            const uint32_t xs = wq == 3 && (s & 1) == 0 && xp < NSEG / 2;
            const uint32_t xd = sb + SM_X + (rx + kb >= 13 ? rx + kb - 13 : rx + kb) * 8192;
            mx2 = poll_mem(src, l16 + SM_M + wq * 2304, t0, [&]() {
                if (xs && lane_o < 2) asm volatile("mbarrier.arrive.relaxed.cluster.shared::cluster.b64 _, [%0];" :: "r"(mapa(sb + B_XF, lane_o)) : "memory");
                if (!C && (xl || s == 0) && (s & 1) == 0) mbar_wait(sb + B_XF, (uint32_t)(s >> 1) & 1u);
                if (lane_o == 0) {
                    if (xl) tma_2d_mc(xd, &tmx2, ((s & 1) ? kb + 5 : kb - 4) * 64, xp * 64, sb + B_XT + ((s & 1) ? 0 : 16) + 8 * (xp & 1));
                    if (!C && s == 0 && role == 1) tma_2d_mc(sb + SM_X + (9 + wq) * 8192, &tmx2, (wq + 5) * 64, 128, sb + B_XT);
                }
                __syncwarp();
            });
            if ((s & 1) == 0) rx = rx >= 4 ? rx - 4 : rx + 9;
            if (s == 0) TSQ(6);
            b3 = n3;
        }
        if (!C) bar_arrive(2, 384);
        };
        if (role == 2) helper_loop(Flag<true>()); else helper_loop(Flag<false>());
    }
    TS3C(1);
    if (role == 2 && warp >= 4) last_rows(1);
    cluster_sync_all();
}

extern "C" void kernel_launch(void* const* d_in, const int* in_sizes, int n_in, void* d_out, int out_size) {
    const bf16* x = (const bf16*)d_in[0];
    const bf16* mem0 = (const bf16*)d_in[1];
    const bf16* Wq = (const bf16*)d_in[2];
    const bf16* Wk = (const bf16*)d_in[3];
    const bf16* Wv = (const bf16*)d_in[4];
    const bf16* Wo = (const bf16*)d_in[5];
    const bf16* logA = (const bf16*)d_in[8];
    const bf16* Aim = (const bf16*)d_in[9];
    const bf16* Cre = (const bf16*)d_in[10];
    const bf16* Cim = (const bf16*)d_in[11];
    const bf16* logdt = (const bf16*)d_in[12];
    const bf16* dskip = (const bf16*)d_in[13];
    const bf16* gw = (const bf16*)d_in[14];
    bf16* out = (bf16*)d_out;
    static bool attr_done = false;
    typedef CUresult (*EncFn)(CUtensorMap*, CUtensorMapDataType, cuuint32_t, void*, const cuuint64_t*, const cuuint64_t*, const cuuint32_t*,
                              const cuuint32_t*, CUtensorMapInterleave, CUtensorMapSwizzle, CUtensorMapL2promotion, CUtensorMapFloatOOBfill);
    static EncFn enc = nullptr;
    if (!attr_done) {
        void* fn = nullptr;
        cudaDriverEntryPointQueryResult qr;
        cudaGetDriverEntryPoint("cuTensorMapEncodeTiled", &fn, cudaEnableDefault, &qr);
        enc = (EncFn)fn;
        cudaFuncSetAttribute(k_chain, cudaFuncAttributeMaxDynamicSharedMemorySize, 232448);
        cudaFuncSetAttribute(k_side, cudaFuncAttributeMaxDynamicSharedMemorySize, SIDE_SMEM);
        attr_done = true;
    }
    CUtensorMap tmw[3];
    for (int i = 0; i < 3; i++) {
        const cuuint64_t dims[2] = {(cuuint64_t)HD, (cuuint64_t)DM};
        const cuuint64_t strides[1] = {(cuuint64_t)HD * 2};
        const cuuint32_t box[2] = {64, 64};
        const cuuint32_t es[2] = {1, 1};
        enc(&tmw[i], CU_TENSOR_MAP_DATA_TYPE_BFLOAT16, 2, (void*)(i == 0 ? Wq : (i == 1 ? Wk : Wv)), dims, strides, box, es, CU_TENSOR_MAP_INTERLEAVE_NONE,
            CU_TENSOR_MAP_SWIZZLE_128B, CU_TENSOR_MAP_L2_PROMOTION_L2_256B, CU_TENSOR_MAP_FLOAT_OOB_FILL_NONE);
    }
    CUtensorMap tmo;
    {
        const cuuint64_t dims[2] = {(cuuint64_t)DM, (cuuint64_t)HD};
        const cuuint64_t strides[1] = {(cuuint64_t)DM * 2};
        const cuuint32_t box[2] = {64, 128};
        const cuuint32_t es[2] = {1, 1};
        enc(&tmo, CU_TENSOR_MAP_DATA_TYPE_BFLOAT16, 2, (void*)Wo, dims, strides, box, es, CU_TENSOR_MAP_INTERLEAVE_NONE,
            CU_TENSOR_MAP_SWIZZLE_128B, CU_TENSOR_MAP_L2_PROMOTION_L2_128B, CU_TENSOR_MAP_FLOAT_OOB_FILL_NONE);
    }
    CUtensorMap tmx2;
    {
        const cuuint64_t dims[2] = {(cuuint64_t)DM, (cuuint64_t)S_LEN};
        const cuuint64_t strides[1] = {(cuuint64_t)DM * 2};
        const cuuint32_t box[2] = {64, 64};
        const cuuint32_t es[2] = {1, 1};
        enc(&tmx2, CU_TENSOR_MAP_DATA_TYPE_BFLOAT16, 2, (void*)x, dims, strides, box, es, CU_TENSOR_MAP_INTERLEAVE_NONE,
            CU_TENSOR_MAP_SWIZZLE_128B, CU_TENSOR_MAP_L2_PROMOTION_L2_128B, CU_TENSOR_MAP_FLOAT_OOB_FILL_NONE);
    }
    CUtensorMap tmm;
    {
        const cuuint64_t dims[2] = {(cuuint64_t)DM, (cuuint64_t)MEMT};
        const cuuint64_t strides[1] = {(cuuint64_t)DM * 2};
        const cuuint32_t box[2] = {64, (cuuint32_t)MEMT};
        const cuuint32_t es[2] = {1, 1};
        enc(&tmm, CU_TENSOR_MAP_DATA_TYPE_BFLOAT16, 2, (void*)mem0, dims, strides, box, es, CU_TENSOR_MAP_INTERLEAVE_NONE,
            CU_TENSOR_MAP_SWIZZLE_128B, CU_TENSOR_MAP_L2_PROMOTION_L2_128B, CU_TENSOR_MAP_FLOAT_OOB_FILL_NONE);
    }
    k_chain<<<NCTA, 384, 232448>>>(tmw[0], tmw[1], tmw[2], tmx2, tmo, tmm, x);
    {
        cudaLaunchConfig_t cfg = {};
        cfg.gridDim = dim3(SD_NCTA); cfg.blockDim = dim3(512); cfg.dynamicSmemBytes = SIDE_SMEM; cfg.stream = cudaStreamPerThread;
        cudaLaunchAttribute at[1];
        at[0].id = cudaLaunchAttributeProgrammaticStreamSerialization;
        at[0].val.programmaticStreamSerializationAllowed = 1;
        cfg.attrs = at; cfg.numAttrs = 1;
        cudaLaunchKernelEx(&cfg, k_side, tmo, x, logA, Aim, Cre, Cim, logdt, Wo, dskip, gw, out);
    }
}
```

```cpp
#include <cuda_runtime.h>
#include <cuda.h>
#include <cuda_bf16.h>
#include <stdint.h>

typedef __nv_bfloat16 bf16;
#define LDV4 "ld.volatile.global.v4.u32 {%0,%1,%2,%3}, [%4];"
#define STV4 "st.volatile.global.v4.u32 [%0], {%1,%2,%3,%4};"
#define STV2 "st.volatile.global.v2.u32 [%0], {%1,%2};"

constexpr int S_LEN = 2048, DM = 576, NH = 32, DH = 128, HD = 4096, MEMT = 8, SEG = 32, NSEG = 64, NST = 128;

__device__ __align__(128) bf16 g_gate[S_LEN];
constexpr int NCTA = NH * 3;
__device__ __align__(1024) unsigned char g_acc[96 * 1024];
__device__ __align__(128) uint2 g_norm[NCTA];
__device__ __align__(128) uint4 g_wv[NH][2];
__device__ __align__(128) uint4 g_rx[NSEG][2];
__device__ __align__(128) unsigned char g_qkv[NSEG][NH][3][10240];
__device__ __align__(128) bf16 g_ox[S_LEN * HD];
__device__ __align__(128) uint4 g_fp[8][36][6][128];
__device__ __align__(128) unsigned g_flag[NH * NSEG];
__device__ __align__(128) unsigned g_prog[8 * 64];
__device__ unsigned g_gcnt[64];
__device__ unsigned g_epoch;
__device__ __align__(128) uint2 g_tick;
__device__ __align__(128) bf16 g_y[DM * S_LEN];

#define TS3(slot) do {} while (0)
#define TS3P(slot) do {} while (0)
#define TSQ(slot) do {} while (0)
#define TS3W(slot) do {} while (0)
#define TSS(row, slot) do {} while (0)
#define TS3C(slot) do {} while (0)
#define TST(slot) do {} while (0)
#define TSA(seg, slot) do {} while (0)
#define TSG(i) do {} while (0)
#define FS(i, dep) do {} while (0)
__device__ __forceinline__ uint32_t smem_u32(const void* p) { return (uint32_t)__cvta_generic_to_shared(p); }
__device__ __forceinline__ float bf16r(float x) { return __bfloat162float(__float2bfloat16_rn(x)); }
__device__ __forceinline__ uint32_t pack_bf16(float lo, float hi) {
    __nv_bfloat162 v = __floats2bfloat162_rn(lo, hi);
    return *reinterpret_cast<uint32_t*>(&v);
}
__device__ __forceinline__ void ldsm_x4(uint32_t (&r)[4], uint32_t addr) {
    asm volatile("ldmatrix.sync.aligned.m8n8.x4.shared.b16 {%0,%1,%2,%3}, [%4];"
                 : "=r"(r[0]), "=r"(r[1]), "=r"(r[2]), "=r"(r[3]) : "r"(addr));
}
__device__ __forceinline__ void ldsm_x4_t(uint32_t (&r)[4], uint32_t addr) {
    asm volatile("ldmatrix.sync.aligned.m8n8.x4.trans.shared.b16 {%0,%1,%2,%3}, [%4];"
                 : "=r"(r[0]), "=r"(r[1]), "=r"(r[2]), "=r"(r[3]) : "r"(addr));
}
__device__ __forceinline__ void mma_bf16(float (&d)[4], const uint32_t (&a)[4], uint32_t b0, uint32_t b1) {
    asm volatile("mma.sync.aligned.m16n8k16.row.col.f32.bf16.bf16.f32 {%0,%1,%2,%3}, {%4,%5,%6,%7}, {%8,%9}, {%0,%1,%2,%3};"
                 : "+f"(d[0]), "+f"(d[1]), "+f"(d[2]), "+f"(d[3])
                 : "r"(a[0]), "r"(a[1]), "r"(a[2]), "r"(a[3]), "r"(b0), "r"(b1));
}
__device__ __forceinline__ uint2 ld_vol_u2(const uint2* p) {
    uint2 v; asm volatile("ld.volatile.global.v2.u32 {%0,%1}, [%2];" : "=r"(v.x), "=r"(v.y) : "l"(p) : "memory"); return v;
}
__device__ __forceinline__ void st_vol_u2(uint2* p, uint2 v) {
    asm volatile(STV2 :: "l"(p), "r"(v.x), "r"(v.y) : "memory");
}
__device__ __forceinline__ unsigned ld_acq(const unsigned* p) {
    unsigned v; asm volatile("ld.acquire.gpu.global.u32 %0, [%1];" : "=r"(v) : "l"(p) : "memory"); return v;
}
#define NS 10
#define NP 4
#define X_OXSZ 16384
#define GATE_A 970
#define GATE_B 380
#define GATE_P 1880u
#define STAGGER 0
#define RLX_SLEEP 300
#define VX_DELAY 100
#define EARLY4 0
#define SPEC_M 1
#define SPEC_H 1
#define C2_DELAY 0
#define SS_POS 10
#define UNGATE_G 3
#define GATE_Y 0
#define GATE_S 0
#define GATE_F 1
#define W14_SLEEP 60
#define TURN31 1
#define GL_A 1150
#define GL_B 530
#define GS_A 1300
#define GS_B 480
#define GATE_POLL 0
#define GP_A 900
#define GP_B 200
#define NUP 3
#define SIDE_WAIT 0
#define FASTW 0
#define NC1 3
#define NC1C 5
#define C1_DELAY 0
#define XSKIP 0
#define LATEW 1
#define VFP 0
#define CC_DELAY 0
#define KPRE 34
#define P0A 1
#define P0B 1
#define P0C 0
#define P0D 0
#define GPRED 1
#define P0W 3
#define XRARE 1
#define RARE(c) __builtin_expect(!!(c), 0)
#define PADB 0
#define PADC 0
#define PADD 0
#define PADE 0
#define PAD1 0
#define PAD2 0
#define PAD3 0
#define PAD4 0
#define B4P 1
#define XPF 0
#define NC0 4
#define KG1 20
#define ZSM 5
#define LB4 1
#define SPL 0
#define LBE (NATT + 1)
#define TIGHT 1
#define WO_SLEEP 0
#define WO_LAG 200
#define EXS 0
#define TM 29
#define TM2 (TM - 1)
#define SMR 0
#define TL_DELAY 600
#define POLL_DELAY 590
#define UNGATE 6
constexpr unsigned SPIN_LIMIT = 1u << 20;
constexpr int NATT = NSEG - 2;

constexpr int SD_CH = 16;
constexpr int SD_NCTA = DM / SD_CH;
constexpr int SD_ROW = 528;
constexpr int SD_U = 8 * SD_ROW;
constexpr int SD_TAP = 5888;
constexpr int SD_CPY = 1376 * 2;
constexpr int SD_WSTR = SD_TAP + 2 * SD_CPY;
constexpr int SD_SMEM = SD_CH * SD_U + 8 * SD_WSTR;
constexpr int O_U = 79, O_U3 = 911, O_U4 = 1055, O_W79 = 1023, O_W35 = 1151, O_W610 = 1279, O_W511 = 1487;

__device__ __forceinline__ uint32_t lds32(uint32_t a) { uint32_t v; asm volatile("ld.shared.u32 %0, [%1];" : "=r"(v) : "r"(a)); return v; }
__device__ __forceinline__ void sts32(uint32_t a, uint32_t v) { asm volatile("st.shared.u32 [%0], %1;" :: "r"(a), "r"(v) : "memory"); }
__device__ __forceinline__ uint4 lds128(uint32_t a) {
    uint4 v; asm volatile("ld.shared.v4.u32 {%0,%1,%2,%3}, [%4];" : "=r"(v.x), "=r"(v.y), "=r"(v.z), "=r"(v.w) : "r"(a) : "memory"); return v;
}
__device__ __forceinline__ void tap_tile(uint32_t (&t)[4], uint32_t a) {
    asm volatile("ld.volatile.shared.u32 %0, [%4];\nld.volatile.shared.u32 %1, [%4+-16];\nld.volatile.shared.u32 %2, [%4+16];\nld.volatile.shared.u32 %3, [%4];"
                 : "=r"(t[0]), "=r"(t[1]), "=r"(t[2]), "=r"(t[3]) : "r"(a));
}
constexpr uint32_t sd_pass(int type, int dl, int o, int d0, int d1) { return (uint32_t)(type | dl << 2 | d0 << 8 | d1 << 12 | o << 17); }
__constant__ uint32_t SD_PASS[14] = {sd_pass(0, 0, O_U, 0, 2), sd_pass(0, 1, O_U + 96, 0, 2), sd_pass(0, 2, O_U + 192, 0, 4), sd_pass(0, 3, O_U + 288, 0, 2), sd_pass(1, 0, O_U3, 8, 8),
                                     sd_pass(0, 4, O_U + 384, 0, 2), sd_pass(1, 0, O_U4, 8, 15), sd_pass(0, 5, O_U + 480, 0, 2), sd_pass(0, 6, O_U + 576, 0, 4), sd_pass(0, 7, O_U + 672, 0, 2),
                                     sd_pass(2, 0, O_W35, 2, 8), sd_pass(3, 0, O_W79, 2, 4), sd_pass(2, 1, O_W610, 4, 8), sd_pass(3, 0, O_W511, 8, 15)};
__device__ __forceinline__ uint32_t band2(int x, int lo, int hi) { return (x >= lo && x <= hi ? 0x3f80u : 0u) | (x + 1 >= lo && x + 1 <= hi ? 0x3f800000u : 0u); }
__device__ __forceinline__ void mma_z(float (&d)[4], const uint32_t (&a)[4], uint32_t b0, uint32_t b1);
__device__ __forceinline__ void put_tap(uint32_t a, float v) {
    asm volatile("{\n.reg .b16 h;\ncvt.rn.bf16.f32 h, %1;\nst.shared.b16 [%0], h;\nst.shared.b16 [%0+%2], h;\n}" :: "r"(a), "f"(v), "n"(SD_CPY - 2) : "memory");
}

__device__ __forceinline__ void named_bar(int id, int n) { asm volatile("bar.sync %0, %1;" :: "r"(id), "r"(n) : "memory"); }
__device__ __forceinline__ uint32_t pack_f16(float lo, float hi) {
    uint32_t r; asm("cvt.rn.f16x2.f32 %0, %1, %2;" : "=r"(r) : "f"(hi), "f"(lo)); return r;
}
__device__ __forceinline__ void cexp_t(float lr, float turns, float& re, float& im) {
    float m;
    asm("ex2.approx.ftz.f32 %0, %1;" : "=f"(m) : "f"(lr));
    const float a = (turns - rintf(turns)) * 6.283185307179586f;
    re = m * __cosf(a); im = m * __sinf(a);
}
__device__ __forceinline__ void csq(float& re, float& im) { const float r = re * re - im * im; im = 2.f * re * im; re = r; }
__device__ __forceinline__ void kb_state(const float* tp, float gf, uint32_t (&a)[4][2], uint32_t (&b)[5]) {
    const float4 p0 = *reinterpret_cast<const float4*>(tp), p1 = *reinterpret_cast<const float4*>(tp + 4);
    float wr, wi;
    cexp_t(p0.x * gf, p0.y * gf, wr, wi);
    float vr = wr * p1.x - wi * p1.y, vi = wr * p1.y + wi * p1.x;
#pragma unroll
    for (int c = 0; c < 4; c++) {
        a[c][0] = pack_f16(wr, wi); a[c][1] = pack_f16(vr, vi);
        csq(wr, wi);
        if (c < 3) csq(vr, vi);
    }
    b[0] = pack_f16(p0.z * wr - p0.w * wi, -p0.z * wi - p0.w * wr);
    float er = wr * p1.z - wi * p1.w, ei = wr * p1.w + wi * p1.z;
#pragma unroll
    for (int c = 0; c < 4; c++) {
        b[1 + c] = pack_f16(p0.z * er - p0.w * ei, -p0.z * ei - p0.w * er);
        if (c < 3) csq(er, ei);
    }
}
__device__ __forceinline__ uint32_t bf2_mul(uint32_t a, uint32_t b) { uint32_t r; asm("mul.rn.bf16x2 %0, %1, %2;" : "=r"(r) : "r"(a), "r"(b)); return r; }
__device__ __forceinline__ uint32_t bf2_add(uint32_t a, uint32_t b) { uint32_t r; asm("add.rn.bf16x2 %0, %1, %2;" : "=r"(r) : "r"(a), "r"(b)); return r; }
__device__ __forceinline__ uint32_t bf2_sub(uint32_t a, uint32_t b) { uint32_t r; asm("sub.rn.bf16x2 %0, %1, %2;" : "=r"(r) : "r"(a), "r"(b)); return r; }
__device__ __forceinline__ void wait_cnt(const unsigned* p, unsigned target) {
    unsigned it = 0;
    while ((int)(ld_acq(p) - target) < 0 && ++it < SPIN_LIMIT) __nanosleep(64);
}
__device__ __forceinline__ uint32_t gtime32() { uint32_t t; asm volatile("mov.u32 %0, %%globaltimer_lo;" : "=r"(t) :: "memory"); return t; }
__device__ __forceinline__ void gate(uint32_t tick_addr, uint32_t ga = GATE_A, uint32_t gb = GATE_B) {
    uint32_t t1, p;
    asm volatile("ld.volatile.shared.v2.u32 {%0,%1}, [%2];" : "=r"(t1), "=r"(p) : "r"(tick_addr) : "memory");
    uint32_t d = gtime32() - t1;
    if (d < 4u * p) {
        d -= d >= 2u * p ? 2u * p : 0u;
        d -= d >= p ? p : 0u;
        if (d + ga >= p && d + gb < p) {
            const uint32_t t2 = gtime32() + (p - gb - d);
            while ((int)(gtime32() - t2) < 0) {}
        }
    }
}

__device__ __forceinline__ void read_tick(uint32_t tick_addr) {
    const uint2 tk = ld_vol_u2(&g_tick);
    uint32_t p = tk.x - tk.y;
    p = p > GATE_P + 100u ? GATE_P + 100u : p;
    asm volatile("st.volatile.shared.v2.u32 [%0], {%1,%2};" :: "r"(tick_addr), "r"(tk.x), "r"(p) : "memory");
}

__device__ __forceinline__ void s4d_phase(unsigned char* smem_raw, const bf16* __restrict__ x, const bf16* __restrict__ logA,
                                          const bf16* __restrict__ Aim, const bf16* __restrict__ Cre, const bf16* __restrict__ Cim,
                                          const bf16* __restrict__ logdt, const bf16* __restrict__ dskip, const bf16* __restrict__ wslice, uint32_t tick) {
    const int tid = threadIdx.x, warp = __shfl_sync(0xffffffffu, tid >> 5, 0), lane = tid & 31;
    const int d0 = blockIdx.x * SD_CH;
    float* tab = reinterpret_cast<float*>(smem_raw + SD_CH * SD_U + warp * SD_WSTR);
    const uint32_t wb = smem_u32(tab);
    const int g = lane >> 2, tq = lane & 3;
    uint2 prm[4];
    float ldt;
    auto load_prm = [&](int d) {
        prm[0] = __ldg(reinterpret_cast<const uint2*>(logA + d * NST) + lane); prm[1] = __ldg(reinterpret_cast<const uint2*>(Aim + d * NST) + lane);
        prm[2] = __ldg(reinterpret_cast<const uint2*>(Cre + d * NST) + lane); prm[3] = __ldg(reinterpret_cast<const uint2*>(Cim + d * NST) + lane);
        ldt = __bfloat162float(logdt[d]);
    };
    load_prm(d0 + warp);
    for (int i = lane; i < 2 * SD_CPY / 16; i += 32) reinterpret_cast<uint4*>(tab + SD_TAP / 4)[i] = make_uint4(0u, 0u, 0u, 0u);
    TS3(20);
#pragma unroll 1
    for (int ch = 0; ch < 2; ch++) {
        const int d = d0 + 8 * ch + warp;
        const uint32_t ub = smem_u32(smem_raw) + (8 * ch + warp) * SD_U;
        float k2048 = 0.f, sinv;
        {
            const float dt = bf16r(expf(ldt));
            uint32_t cm = __vmaxu2(__vmaxu2(prm[2].x & 0x7fff7fffu, prm[2].y & 0x7fff7fffu), __vmaxu2(prm[3].x & 0x7fff7fffu, prm[3].y & 0x7fff7fffu));
            cm = __reduce_max_sync(0xffffffffu, max(cm << 16, cm & 0xffff0000u));
            int e = 134 - (int)(__float_as_uint(__uint_as_float(cm) * dt) >> 23);
            e = e > 100 ? 100 : (e < -100 ? -100 : e);
            const float s2 = __uint_as_float((uint32_t)(128 + e) << 23);
            sinv = __uint_as_float((uint32_t)(127 - e) << 23);
#pragma unroll
            for (int j = 0; j < 4; j++) {
                float q[4];
#pragma unroll
                for (int i = 0; i < 4; i++) { const uint32_t w = j < 2 ? prm[i].x : prm[i].y; q[i] = __uint_as_float((j & 1) ? w & 0xffff0000u : w << 16); }
                const float zl = -bf16r(expf(q[0])) * dt * 1.4426950408889634f;
                const float zt = q[1] * dt * 0.15915494309189535f;
                const float cr = s2 * (q[2] * dt), ci = s2 * (q[3] * dt);
                float ar, ai, br, bi, er, ei;
                cexp_t(zl * 8.f, zt * 8.f, ar, ai);
                cexp_t(zl * 128.f, zt * 128.f, br, bi);
                cexp_t(zl * 2048.f, zt * 2048.f, er, ei);
                k2048 += cr * er - ci * ei;
                *reinterpret_cast<float4*>(tab + (lane + 32 * j) * 8) = make_float4(zl, zt, cr, ci);
                *reinterpret_cast<float4*>(tab + (lane + 32 * j) * 8 + 4) = make_float4(ar, ai, br, bi);
            }
#pragma unroll
            for (int o = 16; o; o >>= 1) k2048 += __shfl_xor_sync(0xffffffffu, k2048, o);
        }
        __syncwarp();
        {
            float kc[5][4];
#pragma unroll
            for (int i = 0; i < 5; i++) { kc[i][0] = kc[i][1] = kc[i][2] = kc[i][3] = 0.f; }
            const float gf = (float)g;
#pragma unroll 2
            for (int ks = 0; ks < 16; ks++) {
                uint32_t a0[4][2], a1[4][2], b0[5], b1[5];
                kb_state(tab + (8 * ks + tq) * 8, gf, a0, b0);
                kb_state(tab + (8 * ks + 4 + tq) * 8, gf, a1, b1);
#pragma unroll
                for (int i = 0; i < 5; i++) {
                    const int c = i > 0 ? i - 1 : 0;
                    asm volatile("mma.sync.aligned.m16n8k16.row.col.f32.f16.f16.f32 {%0,%1,%2,%3}, {%4,%5,%6,%7}, {%8,%9}, {%0,%1,%2,%3};"
                                 : "+f"(kc[i][0]), "+f"(kc[i][1]), "+f"(kc[i][2]), "+f"(kc[i][3])
                                 : "r"(a0[c][0]), "r"(a0[c][1]), "r"(a1[c][0]), "r"(a1[c][1]), "r"(b0[i]), "r"(b1[i]));
                }
            }
            const uint32_t tp = wb + SD_TAP;
            const uint32_t a0 = tp + 2 * (O_U + 96 * g - 4 * tq);
            const uint32_t a2 = tp + 2 * (((g & 1) ? O_U + 96 * (2 * (g & 3)) : ((g & 2) ? O_W35 : O_W79 + 1)) - 32 - 8 * tq - (g >> 2));
            const uint32_t a3 = tp + 2 * (((g & 1) ? O_W35 : O_W610 + 1) - 64 - 16 * tq - (g >> 1));
            const uint32_t a4 = tp + 2 * (-128 - 32 * tq - g);
#pragma unroll
            for (int c = 0; c < 4; c++) {
                const int e = (c & 1) * 16 + (c >> 1) * 8;
                const bool first = c == 0 && lane == 0;
                put_tap(a0 - e / 4, kc[0][c] * sinv);
                put_tap(a0 - 32 - e / 4, kc[1][c] * sinv);
                put_tap(first ? tp + 2 * (O_U - 32) : a2 - e / 2, kc[2][c] * sinv);
                put_tap(first ? tp + 2 * (O_W79 - 63) : a3 - e, kc[3][c] * sinv);
                put_tap(first ? tp + 2 * (O_W610 - 127) : a4 + 2 * (O_W511 + 1 - e), kc[4][c] * sinv);
                if ((g & 1) == 0) {
                    put_tap(a4 + 2 * (O_U4 - e), kc[4][c] * sinv);
                    put_tap(first ? tp + 2 * (O_U3 - 128) : a4 + 2 * (O_U4 + 1 - e), kc[4][c] * sinv);
                }
            }
            if (lane == 0) {
                put_tap(tp + 2 * (O_U + 96 - 32), kc[2][0] * sinv);
                put_tap(tp + 2 * (O_U + 192 - 64), kc[3][0] * sinv);
                put_tap(tp + 2 * (O_W511 - 255), k2048 * sinv);
                put_tap(tp + 2 * (O_U4 - 255), k2048 * sinv);
            }
        }
        TS3(21 + 2 * ch);
        if (ch == 0) { if (!STAGGER || warp < 4) named_bar(1, 384); }
        else {
#pragma unroll
            for (int i = 0; i < 4; i++) asm volatile("prefetch.global.L2 [%0];" :: "l"(wslice + (size_t)((tid & 127) + 128 * i) * DM));
        }
        __syncwarp();
        if (tid == 0) TSS(18, 4 * ch);
        const uint32_t sh = wb + 80 + 11 * SD_ROW;
#pragma unroll
        for (int p = 0; p < 8; p++) {
            uint4 v;
            asm volatile("ld.shared.v4.u32 {%0,%1,%2,%3}, [%4];" : "=r"(v.x), "=r"(v.y), "=r"(v.z), "=r"(v.w) : "r"(ub + p * SD_ROW + lane * 16) : "memory");
            uint32_t pv = __shfl_up_sync(0xffffffffu, v.w, 1);
            pv = lane == 0 ? 0u : pv;
            asm volatile("st.shared.v4.u32 [%0], {%1,%2,%3,%4};" :: "r"(sh + (p - 8) * SD_ROW + lane * 16), "r"(__byte_perm(pv, v.x, 0x5432)), "r"(__byte_perm(v.x, v.y, 0x5432)),
                         "r"(__byte_perm(v.y, v.z, 0x5432)), "r"(__byte_perm(v.z, v.w, 0x5432)) : "memory");
            if (p >= 5) asm volatile("st.shared.v4.u32 [%0], {%1,%2,%3,%4};" :: "r"(sh + (p - 16) * SD_ROW + lane * 16), "r"(pv), "r"(v.x), "r"(v.y), "r"(v.z) : "memory");
        }
        __syncwarp();
        if (tid == 0) TSS(18, 4 * ch + 1);
        float acc[16][4];
#pragma unroll
        for (int i = 0; i < 16; i++) { acc[i][0] = acc[i][1] = acc[i][2] = acc[i][3] = 0.f; }
        {
            const uint32_t ka = wb + SD_TAP + ((g & 1) ? 0 : SD_CPY - 2) + 2 * (2 * tq - g);
            uint32_t b[16][2], b2[14][2];
#pragma unroll
            for (int k = 0; k < 16; k++) { b[k][0] = b[k][1] = 0u; if (k < 14) b2[k][0] = b2[k][1] = 0u; }
#pragma unroll 1
            for (int ps = 0; ps < 14; ps++) {
                const uint32_t pw = __shfl_sync(0xffffffffu, SD_PASS[ps], 0), type = pw & 3u, kp = ka + (pw >> 16);
                const int dl = (pw >> 2) & 7, d0 = (pw >> 8) & 15, d1 = (pw >> 12) & 15;
                uint32_t t[2][4];
                tap_tile(t[0], kp - 32 * d0);
                if (type == 0) {
                    const int p = (lane & 7) - dl;
                    const uint32_t ra = (p < 0 ? sh : ub) + p * SD_ROW + (lane >> 3) * 16;
#pragma unroll
                    for (int k = 0; k < 8; k++)
                        asm volatile("ldmatrix.sync.aligned.m8n8.x4.shared.b16 {%0,%1,%2,%3}, [%4];"
                                     : "=r"(b[2 * k][0]), "=r"(b[2 * k][1]), "=r"(b[2 * k + 1][0]), "=r"(b[2 * k + 1][1]) : "r"(ra + k * 64));
                } else if (type == 2) {
                    const int p = (lane & 15) - 11, xo = 2 * tq - g;
                    const uint32_t qa = (p < 0 ? sh : ub) + p * SD_ROW + (lane >> 4) * 16;
                    const int lx = 6 - 5 * dl, hx = 8 - 3 * dl, ly = 2 - 2 * dl, hy = 4 + 2 * dl;
                    const uint32_t sel[4] = {band2(xo, lx, hx), band2(xo, ly, hy), band2(xo + 8, lx, hx), band2(xo + 8, ly, hy)};
#pragma unroll
                    for (int k = 0; k < 14; k++) {
                        uint32_t q[4];
                        ldsm_x4_t(q, qa + k * 32);
#pragma unroll
                        for (int i = 0; i < 2; i++) {
                            float w[4];
                            mma_z(w, sel, q[2 * i], q[2 * i + 1]);
                            b[k][i] = pack_bf16(w[0], w[1]);
                            b2[k][i] = pack_bf16(w[2], w[3]);
                        }
                    }
                } else if (type == 3) {
#pragma unroll
                    for (int k = 0; k < 14; k++) { b[k][0] = b2[k][0]; b[k][1] = b2[k][1]; }
                }
#pragma unroll
                for (int d = 0; d < 16; d += 2) {
                    if (d >= 8 || d >= d0) {
                        tap_tile(t[1], kp - 32 * (d + 1));
#pragma unroll
                        for (int k = 0; k + d < 16; k++) mma_bf16(acc[k + d], t[0], b[k][0], b[k][1]);
                        if ((d == 2 || d == 4 || d == 8) && d == d1) break;
                        if (d < 14) tap_tile(t[0], kp - 32 * (d + 2));
#pragma unroll
                        for (int k = 0; k + d + 1 < 16; k++) mma_bf16(acc[k + d + 1], t[1], b[k][0], b[k][1]);
                    }
                }
            }
        }
        __syncwarp();
        if (tid == 0) TSS(18, 4 * ch + 2);
        load_prm(d0 + 8 + warp);
        if (ch == 0) {
            if (lane == 0) {
                unsigned ep;
                asm volatile("ld.volatile.global.u32 %0, [%1];" : "=r"(ep) : "l"(&g_epoch) : "memory");
                wait_cnt(&g_gcnt[0], SD_NCTA * (ep + 1u));
            }
            __syncwarp();
        }
        if (tid == 0) TSS(18, 4 * ch + 3);
        uint4 gv[8];
#pragma unroll
        for (int i = 0; i < 8; i++) gv[i] = __ldcg(reinterpret_cast<const uint4*>(g_gate) + lane + 32 * i);
        const uint32_t dd = __byte_perm(*reinterpret_cast<const unsigned short*>(dskip + d), 0u, 0x1010);
#pragma unroll
        for (int i = 0; i < 8; i++) {
            uint32_t u[4];
            ldsm_x4_t(u, ub + (lane & 7) * SD_ROW + (lane >> 3) * 16 + i * 64);
            asm volatile("stmatrix.sync.aligned.m8n8.x4.shared.b16 [%0], {%1,%2,%3,%4};"
                         :: "r"(wb + (lane + 32 * i) * 16),
                            "r"(bf2_add(pack_bf16(acc[2 * i][0], acc[2 * i][1]), bf2_mul(u[0], dd))), "r"(bf2_add(pack_bf16(acc[2 * i][2], acc[2 * i][3]), bf2_mul(u[1], dd))),
                            "r"(bf2_add(pack_bf16(acc[2 * i + 1][0], acc[2 * i + 1][1]), bf2_mul(u[2], dd))), "r"(bf2_add(pack_bf16(acc[2 * i + 1][2], acc[2 * i + 1][3]), bf2_mul(u[3], dd))) : "memory");
        }
        if (GATE_Y) gate(tick);
        __syncwarp();
#pragma unroll
        for (int i = 0; i < 8; i++) {
            const uint4 y = *reinterpret_cast<const uint4*>(tab + (lane + 32 * i) * 4);
            *reinterpret_cast<uint4*>(g_y + (((lane >> 1) + 16 * i) * DM + d) * 16 + (lane & 1) * 8) =
                make_uint4(bf2_mul(bf2_sub(0x3f803f80u, gv[i].x), y.x), bf2_mul(bf2_sub(0x3f803f80u, gv[i].y), y.y),
                           bf2_mul(bf2_sub(0x3f803f80u, gv[i].z), y.z), bf2_mul(bf2_sub(0x3f803f80u, gv[i].w), y.w));
        }
        __syncwarp();
        if (ch == 0) asm volatile("bar.arrive 11, 288;" ::: "memory");
        TS3(22 + 2 * ch);
    }
}
__device__ __forceinline__ void s4d_stage_u(unsigned char* smem_raw, const bf16* __restrict__ x, int pt) {
    const int p = pt & 7, w0 = pt >> 3;
    const uint4* src = reinterpret_cast<const uint4*>(x + (size_t)(16 * w0 + p) * DM + blockIdx.x * SD_CH);
    uint32_t* dst = reinterpret_cast<uint32_t*>(smem_raw + p * SD_ROW) + w0;
#pragma unroll 1
    for (int b = 0; b < 4; b++) {
        uint4 v[2][2][2];
#pragma unroll
        for (int i = 0; i < 8; i++) v[i >> 2][(i >> 1) & 1][i & 1] = src[((b * 2 + (i >> 2)) * 256 + ((i >> 1) & 1) * 8) * (DM / 8) + (i & 1)];
#pragma unroll
        for (int i = 0; i < 4; i++) {
            const uint32_t* lo = reinterpret_cast<const uint32_t*>(&v[i >> 1][0][i & 1]);
            const uint32_t* hi = reinterpret_cast<const uint32_t*>(&v[i >> 1][1][i & 1]);
#pragma unroll
            for (int c = 0; c < 8; c++) dst[((i & 1) * 8 + c) * (SD_U / 4) + (b * 2 + (i >> 1)) * 16] = __byte_perm(lo[c >> 1], hi[c >> 1], (c & 1) ? 0x7632 : 0x5410);
        }
    }
    asm volatile("bar.arrive 1, 384;" ::: "memory");
}

constexpr int WOC = DM / 3;
constexpr int TBUF = 5 * DH * 16;
constexpr int XBUF = SEG * DM * 2;
constexpr int SM_BAR = 0;
constexpr int B_SB = 0, B_VX = 16, B_XT = 32, B_XF = 144, B_W = 64, B_E = 136;
constexpr int SM_SC = 256;
constexpr int SM_F = SM_SC + 1280;
constexpr int SM_VM = SM_F + 2048;
constexpr int SM_S = SM_VM + 2048;
constexpr int SM_O = SM_S + 2560;
constexpr int SM_M = SM_O + 2048;
constexpr int SM_WS = 19456;
constexpr int SM_T = SM_WS + 49152;
constexpr int SM_VX = SM_T + 4 * TBUF;
constexpr int SM_X = SM_VX + 2 * 8192;
constexpr int SM_X01 = SM_WS + DM * DH * 2;
__host__ __device__ constexpr int x01_off(int b) { return b < 2 ? 1024 + b * 9216 : SM_X01 + (b == 2 ? 6 : b - 3) * 9216; }
__host__ __device__ constexpr int x23_off(int b) { return b < 3 ? SM_WS + 7 * 16384 + b * 8192 : x01_off(b - 3); }
constexpr int CH_SMEM = SM_X01 + 8 * 8192;
static_assert(SM_M + DM * 16 <= SM_WS && SM_X + 13 * 8192 <= CH_SMEM && NS <= 10 && CH_SMEM <= 232448 && SM_X % 1024 == 0 && SM_X01 % 1024 == 0 && 1024 + 2 * 9216 <= SM_WS, "smem");
__device__ __forceinline__ uint32_t clock32() { uint32_t t; asm volatile("mov.u32 %0, %%clock;" : "=r"(t) :: "memory"); return t; }

__device__ __forceinline__ uint32_t mapa(uint32_t a, uint32_t rank) {
    uint32_t r; asm volatile("mapa.shared::cluster.u32 %0, %1, %2;" : "=r"(r) : "r"(a), "r"(rank)); return r;
}
__device__ __forceinline__ void st_async32(uint32_t addr, uint32_t v, uint32_t mbar) {
    asm volatile("st.async.weak.shared::cluster.mbarrier::complete_tx::bytes.b32 [%0], %1, [%2];" :: "r"(addr), "r"(v), "r"(mbar) : "memory");
}
__device__ __forceinline__ void mbar_init(uint32_t bar, uint32_t cnt) {
    asm volatile("mbarrier.init.shared::cta.b64 [%0], %1;" :: "r"(bar), "r"(cnt) : "memory");
}
__device__ __forceinline__ void mbar_expect(uint32_t bar, uint32_t bytes) {
    asm volatile("mbarrier.arrive.expect_tx.shared::cta.b64 _, [%0], %1;" :: "r"(bar), "r"(bytes) : "memory");
}
__device__ __forceinline__ void mbar_wait(uint32_t bar, uint32_t parity) {
    unsigned it = 0;
    uint32_t ok;
    do {
        ++it;
        asm volatile("{\n.reg .pred p;\nmbarrier.try_wait.parity.shared::cta.b64 p, [%1], %2;\nselp.u32 %0, 1, 0, p;\n}" : "=r"(ok) : "r"(bar), "r"(parity) : "memory");
    } while ((ok == 0u) & (it < SPIN_LIMIT));
}
__device__ __forceinline__ void mbar_wait_fast(uint32_t bar, uint32_t parity) {
    mbar_wait(bar, parity);
}
__device__ __forceinline__ void mbar_wait_long(uint32_t bar, uint32_t parity) {
    unsigned it = 0;
    while (true) {
        uint32_t ok;
        asm volatile("{\n.reg .pred p;\nmbarrier.try_wait.parity.shared::cta.b64 p, [%1], %2, %3;\nselp.u32 %0, 1, 0, p;\n}"
                     : "=r"(ok) : "r"(bar), "r"(parity), "r"(20000u) : "memory");
        if (ok || ++it >= SPIN_LIMIT) break;
    }
}
__device__ __forceinline__ bool mbar_test(uint32_t bar, uint32_t parity) {
    uint32_t ok;
    asm volatile("{\n.reg .pred p;\nmbarrier.test_wait.parity.shared::cta.b64 p, [%1], %2;\nselp.u32 %0, 1, 0, p;\n}" : "=r"(ok) : "r"(bar), "r"(parity) : "memory");
    return ok != 0u;
}
__device__ __forceinline__ uint64_t policy_evict_first() {
    uint64_t pol; asm volatile("createpolicy.fractional.L2::evict_first.b64 %0, 1.0;" : "=l"(pol)); return pol;
}
__device__ __forceinline__ void cluster_sync_all() {
    asm volatile("barrier.cluster.arrive.release.aligned;\nbarrier.cluster.wait.acquire.aligned;" ::: "memory");
}
__device__ __forceinline__ uint4 ld_vol_u4(const uint4* p) {
    uint4 v; asm volatile(LDV4 : "=r"(v.x), "=r"(v.y), "=r"(v.z), "=r"(v.w) : "l"(p) : "memory"); return v;
}
__device__ __forceinline__ void ld_vol_u4_p(uint4& v, const uint4* p, uint32_t pred) {
    asm volatile("{\n.reg .pred p;\nsetp.ne.u32 p, %5, 0;\n@p " LDV4 "\n}"
                 : "+r"(v.x), "+r"(v.y), "+r"(v.z), "+r"(v.w) : "l"(p), "r"(pred) : "memory");
}
__device__ __forceinline__ void st_vol_u4(uint4* p, uint4 v) {
    asm volatile(STV4 :: "l"(p), "r"(v.x), "r"(v.y), "r"(v.z), "r"(v.w) : "memory");
}
__device__ __forceinline__ void mma_bf16_r(float (&d)[4], uint32_t a0, uint32_t a1, uint32_t a2, uint32_t a3, uint32_t b0, uint32_t b1) {
    asm volatile("mma.sync.aligned.m16n8k16.row.col.f32.bf16.bf16.f32 {%0,%1,%2,%3}, {%4,%5,%6,%7}, {%8,%9}, {%0,%1,%2,%3};"
                 : "+f"(d[0]), "+f"(d[1]), "+f"(d[2]), "+f"(d[3])
                 : "r"(a0), "r"(a1), "r"(a2), "r"(a3), "r"(b0), "r"(b1));
}

__device__ __forceinline__ uint64_t smem_desc(uint32_t addr, uint32_t lbo, uint32_t sbo) {
    return (uint64_t)((addr & 0x3FFFF) >> 4) | ((uint64_t)(lbo >> 4) << 16) | ((uint64_t)(sbo >> 4) << 32);
}
__device__ __forceinline__ void wg_fence() { asm volatile("wgmma.fence.sync.aligned;" ::: "memory"); }
__device__ __forceinline__ void wg_commit() { asm volatile("wgmma.commit_group.sync.aligned;" ::: "memory"); }
__device__ __forceinline__ void wg_wait0() { asm volatile("wgmma.wait_group.sync.aligned 0;" ::: "memory"); }
__device__ __forceinline__ void fence_async() { asm volatile("fence.proxy.async.shared::cta;" ::: "memory"); }
__device__ __forceinline__ void wgmma_n64_ss(float (&d)[32], uint64_t adesc, uint64_t bdesc) {
    asm volatile("{\n.reg .pred p;\nsetp.eq.b32 p, 0, 0;\n"
                 "wgmma.mma_async.sync.aligned.m64n64k16.f32.bf16.bf16 {%0,%1,%2,%3,%4,%5,%6,%7,%8,%9,%10,%11,%12,%13,%14,%15,%16,%17,%18,%19,%20,%21,%22,%23,%24,%25,%26,%27,%28,%29,%30,%31}, %32, %33, p, 1, 1, 1, 0;\n}"
                 : "+f"(d[0]), "+f"(d[1]), "+f"(d[2]), "+f"(d[3]), "+f"(d[4]), "+f"(d[5]), "+f"(d[6]), "+f"(d[7]), "+f"(d[8]), "+f"(d[9]), "+f"(d[10]), "+f"(d[11]), "+f"(d[12]), "+f"(d[13]), "+f"(d[14]), "+f"(d[15]), "+f"(d[16]), "+f"(d[17]), "+f"(d[18]), "+f"(d[19]), "+f"(d[20]), "+f"(d[21]), "+f"(d[22]), "+f"(d[23]), "+f"(d[24]), "+f"(d[25]), "+f"(d[26]), "+f"(d[27]), "+f"(d[28]), "+f"(d[29]), "+f"(d[30]), "+f"(d[31])
                 : "l"(adesc), "l"(bdesc));
}
__device__ __forceinline__ void wgmma_n72_ss(float (&d)[36], uint64_t adesc, uint64_t bdesc) {
    asm volatile("{\n.reg .pred p;\nsetp.eq.b32 p, 0, 0;\n"
                 "wgmma.mma_async.sync.aligned.m64n72k16.f32.bf16.bf16 {%0,%1,%2,%3,%4,%5,%6,%7,%8,%9,%10,%11,%12,%13,%14,%15,%16,%17,%18,%19,%20,%21,%22,%23,%24,%25,%26,%27,%28,%29,%30,%31,%32,%33,%34,%35}, %36, %37, p, 1, 1, 1, 0;\n}"
                 : "+f"(d[0]), "+f"(d[1]), "+f"(d[2]), "+f"(d[3]), "+f"(d[4]), "+f"(d[5]), "+f"(d[6]), "+f"(d[7]), "+f"(d[8]), "+f"(d[9]), "+f"(d[10]), "+f"(d[11]), "+f"(d[12]), "+f"(d[13]), "+f"(d[14]), "+f"(d[15]), "+f"(d[16]), "+f"(d[17]), "+f"(d[18]), "+f"(d[19]), "+f"(d[20]), "+f"(d[21]), "+f"(d[22]), "+f"(d[23]), "+f"(d[24]), "+f"(d[25]), "+f"(d[26]), "+f"(d[27]), "+f"(d[28]), "+f"(d[29]), "+f"(d[30]), "+f"(d[31]), "+f"(d[32]), "+f"(d[33]), "+f"(d[34]), "+f"(d[35])
                 : "l"(adesc), "l"(bdesc));
}
__device__ __forceinline__ void tma_2d(uint32_t dst, const CUtensorMap* tm, int c0, int c1, uint32_t mbar) {
    asm volatile("cp.async.bulk.tensor.2d.shared::cluster.global.tile.mbarrier::complete_tx::bytes [%0], [%1, {%2, %3}], [%4];"
                 :: "r"(dst), "l"(tm), "r"(c0), "r"(c1), "r"(mbar) : "memory");
}

__device__ __forceinline__ void bulk_g2s(uint32_t dst, const void* src, uint32_t bytes, uint32_t mbar) {
    asm volatile("cp.async.bulk.shared::cluster.global.mbarrier::complete_tx::bytes [%0], [%1], %2, [%3];"
                 :: "r"(dst), "l"(src), "r"(bytes), "r"(mbar) : "memory");
}
__device__ __forceinline__ void bulk_g2s_h(uint32_t dst, const void* src, uint32_t bytes, uint32_t mbar, uint64_t pol) {
    asm volatile("cp.async.bulk.shared::cluster.global.mbarrier::complete_tx::bytes.L2::cache_hint [%0], [%1], %2, [%3], %4;"
                 :: "r"(dst), "l"(src), "r"(bytes), "r"(mbar), "l"(pol) : "memory");
}
__device__ __forceinline__ void tma_2d_mc(uint32_t dst, const CUtensorMap* tm, int c0, int c1, uint32_t mbar) {
    asm volatile("cp.async.bulk.tensor.2d.shared::cluster.global.tile.mbarrier::complete_tx::bytes.multicast::cluster [%0], [%1, {%2, %3}], [%4], %5;"
                 :: "r"(dst), "l"(tm), "r"(c0), "r"(c1), "r"(mbar), "h"((unsigned short)7) : "memory");
}
__device__ __forceinline__ void bulk_s2s(uint32_t dst, uint32_t src, uint32_t bytes, uint32_t mbar) {
    asm volatile("cp.async.bulk.shared::cluster.shared::cta.mbarrier::complete_tx::bytes [%0], [%1], %2, [%3];"
                 :: "r"(dst), "r"(src), "r"(bytes), "r"(mbar) : "memory");
}
__device__ __forceinline__ void wgmma_n40_ss(float (&d)[20], uint64_t adesc, uint64_t bdesc, int scale_d) {
    asm volatile("{\n.reg .pred p;\nsetp.ne.b32 p, %22, 0;\n"
                 "wgmma.mma_async.sync.aligned.m64n40k16.f32.bf16.bf16 {%0,%1,%2,%3,%4,%5,%6,%7,%8,%9,%10,%11,%12,%13,%14,%15,%16,%17,%18,%19}, %20, %21, p, 1, 1, 1, 1;\n}"
                 : "+f"(d[0]), "+f"(d[1]), "+f"(d[2]), "+f"(d[3]), "+f"(d[4]), "+f"(d[5]), "+f"(d[6]), "+f"(d[7]),
                   "+f"(d[8]), "+f"(d[9]), "+f"(d[10]), "+f"(d[11]), "+f"(d[12]), "+f"(d[13]), "+f"(d[14]), "+f"(d[15]),
                   "+f"(d[16]), "+f"(d[17]), "+f"(d[18]), "+f"(d[19])
                 : "l"(adesc), "l"(bdesc), "r"(scale_d));
}
__device__ __forceinline__ void wgmma_n64_z(float (&d)[32], const uint32_t (&a)[4], uint64_t bdesc) {
    asm volatile("{\n.reg .pred p;\nsetp.ne.b32 p, 0, 0;\n"
                 "wgmma.mma_async.sync.aligned.m64n64k16.f32.bf16.bf16 {%0,%1,%2,%3,%4,%5,%6,%7,%8,%9,%10,%11,%12,%13,%14,%15,%16,%17,%18,%19,%20,%21,%22,%23,%24,%25,%26,%27,%28,%29,%30,%31}, {%32,%33,%34,%35}, %36, p, 1, 1, 0;\n}"
                 : "=f"(d[0]), "=f"(d[1]), "=f"(d[2]), "=f"(d[3]), "=f"(d[4]), "=f"(d[5]), "=f"(d[6]), "=f"(d[7]),
                   "=f"(d[8]), "=f"(d[9]), "=f"(d[10]), "=f"(d[11]), "=f"(d[12]), "=f"(d[13]), "=f"(d[14]), "=f"(d[15]),
                   "=f"(d[16]), "=f"(d[17]), "=f"(d[18]), "=f"(d[19]), "=f"(d[20]), "=f"(d[21]), "=f"(d[22]), "=f"(d[23]),
                   "=f"(d[24]), "=f"(d[25]), "=f"(d[26]), "=f"(d[27]), "=f"(d[28]), "=f"(d[29]), "=f"(d[30]), "=f"(d[31])
                 : "r"(a[0]), "r"(a[1]), "r"(a[2]), "r"(a[3]), "l"(bdesc));
}
__device__ __forceinline__ void wgmma_n64(float (&d)[32], const uint32_t (&a)[4], uint64_t bdesc, int scale_d) {
    asm volatile("{\n.reg .pred p;\nsetp.ne.b32 p, %37, 0;\n"
                 "wgmma.mma_async.sync.aligned.m64n64k16.f32.bf16.bf16 {%0,%1,%2,%3,%4,%5,%6,%7,%8,%9,%10,%11,%12,%13,%14,%15,%16,%17,%18,%19,%20,%21,%22,%23,%24,%25,%26,%27,%28,%29,%30,%31}, {%32,%33,%34,%35}, %36, p, 1, 1, 0;\n}"
                 : "+f"(d[0]), "+f"(d[1]), "+f"(d[2]), "+f"(d[3]), "+f"(d[4]), "+f"(d[5]), "+f"(d[6]), "+f"(d[7]),
                   "+f"(d[8]), "+f"(d[9]), "+f"(d[10]), "+f"(d[11]), "+f"(d[12]), "+f"(d[13]), "+f"(d[14]), "+f"(d[15]),
                   "+f"(d[16]), "+f"(d[17]), "+f"(d[18]), "+f"(d[19]), "+f"(d[20]), "+f"(d[21]), "+f"(d[22]), "+f"(d[23]),
                   "+f"(d[24]), "+f"(d[25]), "+f"(d[26]), "+f"(d[27]), "+f"(d[28]), "+f"(d[29]), "+f"(d[30]), "+f"(d[31])
                 : "r"(a[0]), "r"(a[1]), "r"(a[2]), "r"(a[3]), "l"(bdesc), "r"(scale_d));
}

constexpr int SB_FULL = 0, SB_EMPTY = 64, SB_QKF = 128, SB_VF = 144, SB_QKE = 160, SB_VE = 176, SB_OF = 192, SB_WO = 208  , SB_TICK = 216, SB_SEEN = 224, SB_FI = 232, SB_REQ = 240;
constexpr int AT_0 = 256, AT_ST = 10240 + 2 * 9216;
constexpr int FS_A = 58368;
constexpr int FS_P = FS_A + 131072;
constexpr int FS_I = FS_P + 16384;
constexpr int FS_O = FS_I + 12288;
constexpr int FS_Z = FS_O + 12288, FS_G = AT_0 + 2 * AT_ST;
constexpr int SIDE_SMEM = FS_Z + 2048;
static_assert(SIDE_SMEM <= 232448 && FS_G + 128 <= FS_A && FS_A + SD_SMEM <= SIDE_SMEM, "smem");

__device__ __forceinline__ void wg_wait1() { asm volatile("wgmma.wait_group.sync.aligned 1;" ::: "memory"); }
__device__ __forceinline__ void mbar_arrive(uint32_t bar) { asm volatile("mbarrier.arrive.shared::cta.b64 _, [%0];" :: "r"(bar) : "memory"); }
__device__ __forceinline__ void wait_cnt_rlx(const unsigned* p, unsigned target, bool urgent) {
    unsigned it = 0, v;
    while (true) {
        asm volatile("ld.relaxed.gpu.global.u32 %0, [%1];" : "=r"(v) : "l"(p) : "memory");
        if ((int)(v - target) >= 0 || ++it >= SPIN_LIMIT) break;
        if (!urgent) __nanosleep(RLX_SLEEP);
    }
}

__device__ __forceinline__ float xrow_softmax(float (&sc)[20], uint32_t (&p)[5], int wq, int lane) {
    constexpr float EC = (float)(1.4426950408889634 * 0.08838834764831845);
    const int lim = 8 * wq + (lane >> 2) - 2 * (lane & 3);
    float mx = fmaxf(sc[0], sc[1]);
#pragma unroll
    for (int j = 1; j < 5; j++) {
        sc[4 * j] = 8 * j - 8 > lim ? -INFINITY : sc[4 * j];
        sc[4 * j + 1] = 8 * j - 7 > lim ? -INFINITY : sc[4 * j + 1];
    }
    mx = fmaxf(fmaxf(mx, fmaxf(fmaxf(sc[4], sc[5]), fmaxf(sc[8], sc[9]))), fmaxf(fmaxf(sc[12], sc[13]), fmaxf(sc[16], sc[17])));
    {
        const float m1 = __shfl_xor_sync(0xffffffffu, mx, 1), m2 = __shfl_xor_sync(0xffffffffu, mx, 2), m3 = __shfl_xor_sync(0xffffffffu, mx, 3);
        mx = fmaxf(fmaxf(mx, m1), fmaxf(m2, m3)) * EC;
    }
    float sum = 0.f;
#pragma unroll
    for (int j = 0; j < 5; j++) {
        float e0, e1;
        asm("ex2.approx.ftz.f32 %0, %1;" : "=f"(e0) : "f"(fmaf(sc[4 * j], EC, -mx)));
        asm("ex2.approx.ftz.f32 %0, %1;" : "=f"(e1) : "f"(fmaf(sc[4 * j + 1], EC, -mx)));
        p[j] = pack_bf16(e0, e1);
        sum += e0 + e1;
    }
    return sum;
}
__device__ __forceinline__ float xrow_inv(float sum) {
    sum += __shfl_xor_sync(0xffffffffu, sum, 1);
    sum += __shfl_xor_sync(0xffffffffu, sum, 2);
    float r;
    asm("rcp.approx.ftz.f32 %0, %1;" : "=f"(r) : "f"(sum));
    return r;
}

__device__ __forceinline__ void stsm_x4(uint32_t addr, uint32_t r0, uint32_t r1, uint32_t r2, uint32_t r3) {
    asm volatile("stmatrix.sync.aligned.m8n8.x4.shared.b16 [%0], {%1,%2,%3,%4};" :: "r"(addr), "r"(r0), "r"(r1), "r"(r2), "r"(r3) : "memory");
}
__device__ __forceinline__ void xrow_pv(uint32_t (&ob)[16], const uint32_t (&p)[5], float psum, uint32_t vt) {
    float o[32];
    const uint64_t dv = smem_desc(vt, 2048, 128);
    uint32_t pa[6][4];
#pragma unroll
    for (int i = 0; i < 6; i++) {
        const int ks = i >> 1, hf = i & 1;
        pa[i][hf] = p[2 * ks]; pa[i][hf ^ 1] = 0u;
        pa[i][2 + hf] = ks < 2 ? p[ks < 2 ? 2 * ks + 1 : 0] : 0u; pa[i][3 - hf] = 0u;
    }
    wg_fence();
#pragma unroll
    for (int i = 0; i < 6; i++) { if (i == 0) wgmma_n64_z(o, pa[0], dv); else wgmma_n64(o, pa[i], dv + (uint64_t)((i & 1) * 64 + (i >> 1) * 256), 1); }
    wg_commit();
    const float inv = xrow_inv(psum);
    wg_wait0();
#pragma unroll
    for (int i = 0; i < 8; i++) { ob[i] = pack_bf16(o[4 * i] * inv, o[4 * i + 1] * inv); ob[8 + i] = pack_bf16(o[4 * i + 2] * inv, o[4 * i + 3] * inv); }
}
__device__ __forceinline__ uint32_t h2_to_bf2(uint32_t h) {
    uint32_t r;
    asm("{\n.reg .f16 l, h;\n.reg .f32 a, b;\nmov.b32 {l, h}, %1;\ncvt.f32.f16 a, l;\ncvt.f32.f16 b, h;\ncvt.rn.bf16x2.f32 %0, b, a;\n}" : "=r"(r) : "r"(h));
    return r;
}
__device__ __forceinline__ uint32_t max_abs2(uint32_t a, uint32_t b) { uint32_t r; asm("max.NaN.xorsign.abs.bf16x2 %0, %1, %2;" : "=r"(r) : "r"(a), "r"(b)); return r; }
__device__ __forceinline__ uint32_t movm(uint32_t v) {
    uint32_t r; asm volatile("movmatrix.sync.aligned.m8n8.trans.b16 %0, %1;" : "=r"(r) : "r"(v)); return r;
}
__device__ __forceinline__ void bar_arrive(int id, int n) { asm volatile("bar.arrive %0, %1;" :: "r"(id), "r"(n) : "memory"); }
__device__ __forceinline__ void lds64(uint32_t& a, uint32_t& b, uint32_t addr) {
    asm volatile("ld.shared.v2.u32 {%0,%1}, [%2];" : "=r"(a), "=r"(b) : "r"(addr) : "memory");
}
__device__ __forceinline__ void lds64f(float& a, float& b, uint32_t addr) {
    asm volatile("ld.shared.v2.f32 {%0,%1}, [%2];" : "=f"(a), "=f"(b) : "r"(addr) : "memory");
}
__device__ __forceinline__ void st_async64(uint32_t addr, uint32_t a, uint32_t b, uint32_t mbar) {
    asm volatile("st.async.weak.shared::cluster.mbarrier::complete_tx::bytes.v2.b32 [%0], {%1,%2}, [%3];" :: "r"(addr), "r"(a), "r"(b), "r"(mbar) : "memory");
}
__device__ __forceinline__ void mma_z(float (&d)[4], const uint32_t (&a)[4], uint32_t b0, uint32_t b1) {
    asm volatile("mma.sync.aligned.m16n8k16.row.col.f32.bf16.bf16.f32 {%0,%1,%2,%3}, {%4,%5,%6,%7}, {%8,%9}, {%10,%10,%10,%10};"
                 : "=f"(d[0]), "=f"(d[1]), "=f"(d[2]), "=f"(d[3])
                 : "r"(a[0]), "r"(a[1]), "r"(a[2]), "r"(a[3]), "r"(b0), "r"(b1), "f"(0.f));
}
__device__ __forceinline__ void mma_k8(float (&d)[4], uint32_t a0, uint32_t a1, uint32_t b) {
    asm volatile("mma.sync.aligned.m16n8k8.row.col.f32.bf16.bf16.f32 {%0,%1,%2,%3}, {%4,%5}, {%6}, {%0,%1,%2,%3};"
                 : "+f"(d[0]), "+f"(d[1]), "+f"(d[2]), "+f"(d[3]) : "r"(a0), "r"(a1), "r"(b));
}
__global__ void __launch_bounds__(512, 1) k_side(const __grid_constant__ CUtensorMap tmo, const bf16* __restrict__ x, const bf16* __restrict__ logA, const bf16* __restrict__ Aim,
                                                 const bf16* __restrict__ Cre, const bf16* __restrict__ Cim, const bf16* __restrict__ logdt,
                                                 const bf16* __restrict__ Wo, const bf16* __restrict__ dskip, const bf16* __restrict__ gw,
                                                 bf16* __restrict__ out) {
    extern __shared__ __align__(1024) unsigned char smem_raw[];
    const uint32_t sbase = smem_u32(smem_raw);
    const int tid = threadIdx.x, warp = __shfl_sync(0xffffffffu, tid >> 5, 0), lane = tid & 31, cta = blockIdx.x;
    const int cb = cta >> 2, kq = cta & 3;
    if (tid == 0) {
        for (int i = 0; i < 8; i++) { mbar_init(sbase + SB_FULL + 8 * i, 1); mbar_init(sbase + SB_EMPTY + 8 * i, 4); }
        for (int i = 0; i < 2; i++) {
            mbar_init(sbase + SB_QKF + 8 * i, 1); mbar_init(sbase + SB_VF + 8 * i, 1); mbar_init(sbase + SB_QKE + 8 * i, 4);
            mbar_init(sbase + SB_VE + 8 * i, 1); mbar_init(sbase + SB_OF + 8 * i, 4);
        }
        mbar_init(sbase + SB_WO, 1);
        mbar_init(sbase + SB_WO + 40, 1);
        mbar_init(sbase + SB_FI, 1);
        mbar_init(sbase + SB_REQ, 4);
        *reinterpret_cast<uint2*>(smem_raw + SB_TICK) = make_uint2(0u, 0u);
        *reinterpret_cast<uint32_t*>(smem_raw + SB_SEEN) = 0u;
        asm volatile("fence.mbarrier_init.release.cluster;" ::: "memory");
    }
    TS3(0);
    asm volatile("fence.proxy.async;" ::: "memory");
    __syncthreads();
    auto epoch = []() {
        unsigned ep;
        asm volatile("ld.volatile.global.u32 %0, [%1];" : "=r"(ep) : "l"(&g_epoch) : "memory");
        return ep + 1u;
    };
    if (warp >= 12) {
      asm volatile("setmaxnreg.dec.sync.aligned.u32 40;");
      if (SIDE_WAIT > 0) __nanosleep(SIDE_WAIT);
      {
        uint32_t gwv[9];
#pragma unroll
        for (int i = 0; i < 9; i++) gwv[i] = reinterpret_cast<const uint32_t*>(gw)[lane + 32 * i];
#pragma unroll 1
        for (int i = 0; i < 8; i++) {
            uint32_t xv[2][9];
            float sm[2];
#pragma unroll
            for (int j = 0; j < 2; j++) {
                const int t = min(cta * 57 + 8 * i + 4 * j + warp - 12, S_LEN - 1);
#pragma unroll
                for (int k = 0; k < 9; k++) xv[j][k] = reinterpret_cast<const uint32_t*>(x + t * DM)[lane + 32 * k];
            }
#pragma unroll
            for (int j = 0; j < 2; j++) {
                sm[j] = 0.f;
#pragma unroll
                for (int k = 0; k < 9; k++) {
                    const uint32_t pr = bf2_mul(xv[j][k], gwv[k]);
                    sm[j] += __uint_as_float(pr << 16) + __uint_as_float(pr & 0xffff0000u);
                }
            }
            float v = (lane < 16 ? sm[0] : sm[1]) + __shfl_xor_sync(0xffffffffu, lane < 16 ? sm[1] : sm[0], 16);
#pragma unroll
            for (int o = 8; o; o >>= 1) v += __shfl_xor_sync(0xffffffffu, v, o);
            const float gv = 1.f / (1.f + expf(-bf16r(v)));
            const int tt = 8 * i + 4 * (lane >> 4) + warp - 12;
            if ((lane & 15) == 0 && tt < 57 && cta * 57 + tt < S_LEN) g_gate[cta * 57 + tt] = __float2bfloat16_rn(gv);
        }
        named_bar(2, 128);
        if (tid == 480) {
            __threadfence();
            asm volatile("red.relaxed.gpu.global.add.u32 [%0], 1;" :: "l"(&g_gcnt[0]) : "memory");
        }
        __syncwarp();
      }
      const unsigned ep = epoch();
      if (warp == 12 || warp == 15) {
        const int pi = warp == 12 ? 0 : 1;
        auto stage_wo = [&](int i0, int i1) {
            if (lane == 0) {
                fence_async();
#pragma unroll 1
                for (int i = i0; i < i1; i++) {
                    gate(sbase + SB_TICK);
                    tma_2d(sbase + FS_A + i * 16384, &tmo, cb * 64, kq * 1024 + i * 128, sbase + SB_WO + (i >> 2) * 40);
                    if (WO_SLEEP > 0) __nanosleep(WO_SLEEP);
                }
            }
            __syncwarp();
        };
        if (lane == 0) mbar_expect(sbase + SB_WO + pi * 40, 65536);
        if (pi == 0) {
            named_bar(11, 288);
            stage_wo(0, 2);
        }
        named_bar(3, 320);
        if (pi == 0) stage_wo(2, 4);
        else {
            if (WO_LAG > 0) __nanosleep(WO_LAG);
            stage_wo(4, 8);
        }
        if (lane == 0) TSS(17, 2 + pi);
        if (tid == 480) {
            __threadfence();
            asm volatile("red.relaxed.gpu.global.add.u32 [%0], 1;" :: "l"(&g_gcnt[32]) : "memory");
        }
        __syncwarp();
        named_bar(12 + pi, 160);
        if (lane == 0) {
            const int kb = 2 * kq + pi;
            fence_async();
            for (int pq = 0; pq < NSEG / 2 + SPL; pq++) {
                const bool one = pq >= NSEG / 2 - SPL, sec = one && ((pq + SPL) & 1);
                const int pr = one ? (pq + NSEG / 2 - SPL) >> 1 : pq;
                const bool gon = pr < NSEG / 2 - UNGATE_G;
                wait_cnt_rlx(&g_prog[kb * 64 + pq], (one ? 4u : 8u) * ep, pr >= NSEG / 2 - 2);
                if (pi == 0 && one == sec) asm volatile("st.volatile.shared.u32 [%0], %1;" :: "r"(sbase + SB_SEEN), "r"(pr + 1) : "memory");
                if (pr >= 30 && pi == 0) TSS(4 + pr - 30, 0);
                if (pr == 31) TS3P(26);
                if (pr == 30) TS3P(1);
                const uint32_t o = sec ? 8192u : 0u, n = one ? 8192u : 16384u;
#pragma unroll
                for (int j = 0; j < 4; j++) {
                    const int st = 4 * pi + j;
                    if (!sec) {
                        if (one && TIGHT) mbar_wait(sbase + SB_EMPTY + 8 * st, ((uint32_t)pr & 1u) ^ 1u); else mbar_wait_long(sbase + SB_EMPTY + 8 * st, ((uint32_t)pr & 1u) ^ 1u);
                        mbar_expect(sbase + SB_FULL + 8 * st, 16384);
                    }
                    if (gon) gate(sbase + SB_TICK);
                    bulk_g2s(sbase + FS_A + st * 16384 + o, reinterpret_cast<const unsigned char*>(g_ox) + ((size_t)(pr * NH + 4 * kb + j)) * 16384 + o, n, sbase + SB_FULL + 8 * st);
                }
            }
        }
        __syncwarp();
      } else if (warp == 13) {
        if (lane == 0) {
            const uint64_t pol = policy_evict_first();
            bool next_ok = false;
            for (int seg = 0; seg < NATT; seg++) {
                const uint32_t st = seg & 1, ph = (uint32_t)(seg >> 1) & 1u, ab = sbase + AT_0 + st * AT_ST;
                if (!next_ok) {
                    const unsigned* fp = &g_flag[(cta & (NH - 1)) * NSEG + seg];
                    unsigned it = 0, v0, v1;
                    while (true) {
                        asm volatile("ld.relaxed.gpu.global.u32 %0, [%1];" : "=r"(v0) : "l"(fp) : "memory");
                        asm volatile("ld.relaxed.gpu.global.u32 %0, [%1+4];" : "=r"(v1) : "l"(fp) : "memory");
                        read_tick(sbase + SB_TICK);
                        if ((int)(v0 - 3u * ep) >= 0 || ++it >= SPIN_LIMIT) break;
                        if (seg < NSEG - UNGATE || cta >= NH) { __nanosleep(RLX_SLEEP); if (GATE_POLL) gate(sbase + SB_TICK, GP_A, GP_B); }
                    }
                    next_ok = (int)(v1 - 3u * ep) >= 0;
                } else next_ok = false;
                if (cta < NH) {
                    TSA(seg, 0);
                    mbar_wait_long(sbase + SB_QKE + 8 * st, ph ^ 1u);
                    TSA(seg, 1);
                    mbar_expect(sbase + SB_QKF + 8 * st, 2 * 9216);
                    if (seg < NSEG - UNGATE) gate(sbase + SB_TICK, GL_A, GL_B);
                    TSA(seg, 2);
                    bulk_g2s_h(ab + 10240, &g_qkv[seg][cta][0][1024], 9216, sbase + SB_QKF + 8 * st, pol);
                    bulk_g2s_h(ab + 10240 + 9216, &g_qkv[seg][cta][1][1024], 9216, sbase + SB_QKF + 8 * st, pol);
                    mbar_wait_long(sbase + SB_VE + 8 * st, ph ^ 1u);
                    mbar_expect(sbase + SB_VF + 8 * st, 10240);
                    if (seg < NSEG - UNGATE) gate(sbase + SB_TICK, GL_A, GL_B);
                    TSA(seg, 3);
                    bulk_g2s_h(ab, &g_qkv[seg][cta][2][0], 10240, sbase + SB_VF + 8 * st, pol);
                }
            }
        }
        __syncwarp();
      } else if (warp == 14) {
        if (lane == 0) {
            int seg = cta < NH ? 0 : NATT, p = 0;
            unsigned it = 0;
            while ((seg < NATT || p < NSEG / 2 - 1) && ++it < 16 * SPIN_LIMIT) {
                if (p < NSEG / 2 - 1 && mbar_test(sbase + SB_REQ, (uint32_t)p & 1u)) {
                    if (p == 0) { wait_cnt(&g_gcnt[32], SD_NCTA * ep); asm volatile("fence.proxy.async;" ::: "memory"); }
                    mbar_expect(sbase + SB_FI, (p < NSEG / 2 - 2 ? 12288 : 2048 + 32) + 2048 + 32);
                    if (GATE_F && p < NSEG / 2 - UNGATE_G - 1) gate(sbase + SB_TICK);
                    if (p < NSEG / 2 - 2) bulk_g2s(sbase + FS_I, &g_fp[p & 7][cta][0][0], 12288, sbase + SB_FI);
                    else {
                        bulk_g2s(sbase + FS_I, g_y + ((p * 4 + 4 + kq) * DM + cb * 64) * 16, 2048, sbase + SB_FI);
                        bulk_g2s(sbase + FS_G + 32, g_gate + p * 64 + 64 + kq * 16, 32, sbase + SB_FI);
                    }
                    bulk_g2s(sbase + FS_Z, g_y + ((p * 4 + kq) * DM + cb * 64) * 16, 2048, sbase + SB_FI);
                    bulk_g2s(sbase + FS_G, g_gate + p * 64 + kq * 16, 32, sbase + SB_FI);
                    p++;
                } else if (seg < NATT && mbar_test(sbase + SB_OF + 8 * (seg & 1), (uint32_t)(seg >> 1) & 1u)) {
                    const uint32_t st = seg & 1, ab = sbase + AT_0 + st * AT_ST;
                    TSA(seg, 5);
                    if (seg < NSEG - UNGATE) gate(sbase + SB_TICK, GS_A, GS_B);
                    TSA(seg, 6);
                    unsigned char* dst = reinterpret_cast<unsigned char*>(g_ox) + ((size_t)((seg >> 1) * NH + cta)) * 16384 + (seg & 1) * 8192;
                    asm volatile("cp.async.bulk.global.shared::cta.bulk_group [%0], [%1], 8192;" :: "l"(dst), "r"(ab) : "memory");
                    asm volatile("cp.async.bulk.commit_group;" ::: "memory");
                    asm volatile("cp.async.bulk.wait_group.read 0;" ::: "memory");
                    mbar_arrive(sbase + SB_VE + 8 * st);
                    asm volatile("cp.async.bulk.wait_group 0;" ::: "memory");
                    asm volatile("red.relaxed.gpu.global.add.u32 [%0], 1;" :: "l"(&g_prog[(cta >> 2) * 64 + (seg >> 1)]) : "memory");
                    TSA(seg, 7);
                    seg++;
                } else if (seg < NSEG - UNGATE) __nanosleep(W14_SLEEP);
            }
        }
        __syncwarp();
      }
    } else if (warp >= 8) {
        asm volatile("setmaxnreg.dec.sync.aligned.u32 88;");
        if (SIDE_WAIT > 0) __nanosleep(SIDE_WAIT);
        s4d_stage_u(smem_raw + FS_A, x, tid - 256);
        const int wq = warp - 8;
        for (int seg = 0; seg < (cta < NH ? NATT : 0); seg++) {
            const uint32_t st = seg & 1, ph = (uint32_t)(seg >> 1) & 1u, ab = sbase + AT_0 + st * AT_ST;
            float sc[20];
            if (seg < NSEG - UNGATE) mbar_wait_long(sbase + SB_QKF + 8 * st, ph); else mbar_wait(sbase + SB_QKF + 8 * st, ph);
            if (tid == 256) TSA(seg, 4);
            {
                const uint64_t da = smem_desc(ab + 10240 + 1024, 128, 1024), db = smem_desc(ab + 10240, 128, 2048);
                wg_fence();
#pragma unroll
                for (int ks = 0; ks < 8; ks++) wgmma_n40_ss(sc, da + (uint64_t)((ks >> 2) * 576 + (ks & 3) * 16), db + (uint64_t)((ks >> 2) * 576 + (ks & 3) * 16), ks > 0);
                wg_commit();
                wg_wait0();
            }
            if (lane == 0) mbar_arrive(sbase + SB_QKE + 8 * st);
            uint32_t p[5], ob[16];
            const float psum = xrow_softmax(sc, p, wq, lane);
            mbar_wait(sbase + SB_VF + 8 * st, ph);
            xrow_pv(ob, p, psum, ab);
            named_bar(6, 128);
#pragma unroll
            for (int i = 0; i < 4; i++) stsm_x4(ab + wq * 2048 + i * 512 + lane * 16, ob[4 * i], ob[4 * i + 1], ob[4 * i + 2], ob[4 * i + 3]);
            fence_async();
            __syncwarp();
            if (lane == 0) mbar_arrive(sbase + SB_OF + 8 * st);
        }
    } else {
        asm volatile("setmaxnreg.inc.sync.aligned.u32 192;");
        const int wg = warp >> 2, wq = warp & 3;
        s4d_phase(smem_raw + FS_A, x, logA, Aim, Cre, Cim, logdt, dskip, Wo + (size_t)((2 * kq + wg) * 512) * DM + cb * 64, sbase + SB_TICK);
        TS3(2);
        if (lane == 0) TSS(16, warp);
        named_bar(3, 320);
        if (tid == 0) TSS(17, 0);
        uint32_t wa[32][4];
        mbar_wait_long(sbase + SB_WO + wg * 40, 0);
        if (tid == 0) TSS(17, 1);
        {
            const uint32_t a = sbase + FS_A + wg * 65536 + ((lane >> 4) * 8 + (lane & 7)) * 128 + (((wq * 2 + ((lane >> 3) & 1)) ^ (lane & 7)) << 4);
#pragma unroll
            for (int ks = 0; ks < 32; ks++) ldsm_x4_t(wa[ks], a + ks * 2048);
        }
        named_bar(12 + wg, 160);
        TS3(3);
        if (tid == 0) TSS(17, 4);
        auto product = [&](float (&acc)[32], int pr, const int wg) {
                if (pr + wg > 0 && (TURN31 || pr + wg < NSEG / 2)) named_bar(4 + wg, 256);
                const uint64_t db = smem_desc(sbase + FS_A + wg * 65536, 128, 2048);
                TSG(0);
#pragma unroll
                for (int j = 0; j < 4; j++) {
                    mbar_wait(sbase + SB_FULL + 8 * (4 * wg + j), (uint32_t)pr & 1u);
                    if (j == 0) TSG(1);
                    if (j == 3) TSG(2);
                    wg_fence();
#pragma unroll
                    for (int ks = 0; ks < 8; ks++) {
                        if ((j | ks) == 0) wgmma_n64_z(acc, wa[0], db);
                        else wgmma_n64(acc, wa[8 * j + ks], db + (uint64_t)(j * 1024 + ks * 16), 1);
                    }
                    wg_commit();
                    if (j == 3 && pr + (TURN31 ? wg : 1) < NSEG / 2) bar_arrive(4 + (wg ^ 1), 256);
                    if (j > 0) { wg_wait1(); if (lane == 0) mbar_arrive(sbase + SB_EMPTY + 8 * (4 * wg + j - 1)); }
                }
                wg_wait0();
                if (pr == 31) TS3W(27);
                TSG(3);
                if (lane == 0) mbar_arrive(sbase + SB_EMPTY + 8 * (4 * wg + 3));
        };
        if (wg == 1) {
            for (int pr = 0; pr < NSEG / 2; pr++) {
                uint32_t t16 = (uint32_t)(wq * 32 + lane) * 16u;
                asm volatile("" : "+r"(t16));
                float acc[32];
                product(acc, pr, 1);
                    uint32_t tag = ((uint32_t)(pr >> 3) & 1u) ^ 1u;
                    tag = __shfl_sync(0xffffffffu, tag, lane);
                    if (GATE_S && pr < NSEG / 2 - UNGATE_G) gate(sbase + SB_TICK);
                    named_bar(8, 256);
                    unsigned char* dst = reinterpret_cast<unsigned char*>(&g_fp[pr & 7][4 * cb][2 * kq - 2][0]) + t16;
                    const uint32_t own = sbase + FS_O + (pr % 3) * 4096 + t16;
#pragma unroll
                    for (int q = 0; q < 8; q++) {
                        float4 p;
                        asm volatile("ld.shared.v4.f32 {%0,%1,%2,%3}, [%4];" : "=f"(p.x), "=f"(p.y), "=f"(p.z), "=f"(p.w) : "r"(sbase + FS_P + t16 + q * 2048) : "memory");
                        acc[4 * q] = __uint_as_float((__float_as_uint(acc[4 * q] + p.x) & ~1u) | tag); acc[4 * q + 1] = __uint_as_float((__float_as_uint(acc[4 * q + 1] + p.y) & ~1u) | tag);
                        acc[4 * q + 2] = __uint_as_float((__float_as_uint(acc[4 * q + 2] + p.z) & ~1u) | tag); acc[4 * q + 3] = __uint_as_float((__float_as_uint(acc[4 * q + 3] + p.w) & ~1u) | tag);
                    }
#pragma unroll
                    for (int q = 0; q < 8; q++) {
                        asm volatile("{\n.reg .pred p;\nsetp.ne.s32 p, %5, %6;\n@p st.volatile.global.v4.f32 [%0], {%1,%2,%3,%4};\n@!p st.shared.v4.f32 [%7], {%1,%2,%3,%4};\n}"
                                     :: "l"(dst + (q & 1) * 2048), "f"(acc[4 * q]), "f"(acc[4 * q + 1]), "f"(acc[4 * q + 2]), "f"(acc[4 * q + 3]), "r"(q >> 1), "r"(kq),
                                        "r"(own + (q & 1) * 2048) : "memory");
                        if (q & 1) dst += (q >> 1) == kq ? 12288 + 4096 : 12288;
                    }
                    bar_arrive(9, 256);
                    if (pr == 31) TS3W(28);
                TSG(4);
            }
        } else {
          int nsync = 0;
          int np = 1, nf = 0, pr = 0, pf = -1;
          while (true) {
            uint32_t t16 = (uint32_t)(wq * 32 + lane) * 16u;
            asm volatile("" : "+r"(t16));
            if (pr < 0) {
                if (nsync <= pf) { named_bar(9, 256); nsync++; }
                if (lane == 0 && pf < NSEG / 2 - 1) mbar_arrive(sbase + SB_REQ);
            } else {
                float acc[32];
                product(acc, pr, 0);
                if (nsync < pr) { named_bar(9, 256); nsync++; }
#pragma unroll
                for (int q = 0; q < 8; q++)
                    asm volatile("st.shared.v4.f32 [%0], {%1,%2,%3,%4};" :: "r"(sbase + FS_P + t16 + q * 2048), "f"(acc[4 * q]), "f"(acc[4 * q + 1]), "f"(acc[4 * q + 2]), "f"(acc[4 * q + 3]) : "memory");
                bar_arrive(8, 256);
                TSG(4);
            }
            uint32_t w[4] = {0u, 0u, 0u, 0u};
            const int pc = pf;
            if (pf >= 0) {
                const uint32_t tag = ((uint32_t)(pf >> 3) & 1u) ^ 1u;
                uint4 v[8];
                unsigned n = 0;
                const bool last = pf == NSEG / 2 - 1;
                const uint4* src = reinterpret_cast<const uint4*>(reinterpret_cast<const unsigned char*>(&g_fp[pf & 7][cta][0][0]) + t16);
                if (pf >= NSEG / 2 - 2) {
#pragma unroll
                    for (int r = 0; r < 6; r++) v[r] = ld_vol_u4(src + r * 128);
                    mbar_wait(sbase + SB_FI, 0u);
                } else {
                    mbar_wait(sbase + SB_FI, (uint32_t)pf & 1u);
#pragma unroll
                    for (int r = 0; r < 6; r++)
                        asm volatile("ld.shared.v4.u32 {%0,%1,%2,%3}, [%4];" : "=r"(v[r].x), "=r"(v[r].y), "=r"(v[r].z), "=r"(v[r].w) : "r"(sbase + t16 + FS_I + r * 2048) : "memory");
                }
                while (true) {
                    uint32_t any = 0u;
#pragma unroll
                    for (int r = 0; r < 6; r++) {
                        uint32_t c0_, c1_;
                        asm("lop3.b32 %0, %1, %2, %3, 0x7e;" : "=r"(c0_) : "r"(v[r].x), "r"(v[r].y), "r"(tag));
                        asm("lop3.b32 %0, %1, %2, %3, 0x7e;" : "=r"(c1_) : "r"(v[r].z), "r"(v[r].w), "r"(tag));
                        asm("lop3.b32 %0, %1, %2, %3, 0xfe;" : "=r"(any) : "r"(any), "r"(c0_), "r"(c1_));
                    }
                    if (!__any_sync(0xffffffffu, (any & 1u) != 0u) || ++n >= SPIN_LIMIT) break;
                    if (pf < NSEG / 2 - 2) __nanosleep(200);
#pragma unroll
                    for (int r = 0; r < 6; r++) v[r] = ld_vol_u4(src + r * 128);
                }
                if (pf == 31) TS3(29);
                TSG(5);
#pragma unroll
                for (int r = 6; r < 8; r++)
                    asm volatile("ld.shared.v4.u32 {%0,%1,%2,%3}, [%4];" : "=r"(v[r].x), "=r"(v[r].y), "=r"(v[r].z), "=r"(v[r].w)
                                 : "r"(sbase + t16 + FS_O + (pf % 3) * 4096 + (r - 6) * 2048) : "memory");
                uint32_t zv[4], gg[2];
                ldsm_x4_t(zv, sbase + (last ? FS_I : FS_Z) + (wq * 16 + (lane & 15)) * 32 + (lane >> 4) * 16);
#pragma unroll
                for (int k = 0; k < 2; k++) gg[k] = __byte_perm(*reinterpret_cast<const volatile unsigned short*>(smem_raw + FS_G + (last ? 32 : 0) + k * 16 + (lane >> 2) * 2), 0u, 0x1010);
#define PQS(k, f) (((__uint_as_float(v[k].f) + __uint_as_float(v[2 + k].f)) + __uint_as_float(v[4 + k].f)) + __uint_as_float(v[6 + k].f))
#pragma unroll
                for (int k = 0; k < 2; k++) {
                    w[2 * k] = bf2_add(bf2_mul(gg[k], movm(pack_bf16(PQS(k, x), PQS(k, y)))), zv[2 * k]);
                    w[2 * k + 1] = bf2_add(bf2_mul(gg[k], movm(pack_bf16(PQS(k, z), PQS(k, w)))), zv[2 * k + 1]);
                }
#undef PQS
            }
            const bool more = nf < NSEG / 2;
            if (more) {
                uint32_t r;
                asm volatile("{\n.reg .pred p, q;\n.reg .b32 v;\nld.volatile.shared.u32 v, [%1];\nsetp.gt.s32 p, v, %2;\nbar.red.or.pred q, 10, 128, p;\nselp.u32 %0, 1, 0, q;\n}"
                             : "=r"(r) : "r"(sbase + SB_SEEN), "r"(np) : "memory");
                const bool dop = np < NSEG / 2 && (__shfl_sync(0xffffffffu, r, 0) != 0u || nf == np || (np >= TM && nf + 1 >= np));
                TSG(6);
                pr = dop ? np++ : -1;
                pf = !dop || nf + (pr >= TM2 ? 1 : 2) <= pr ? nf++ : -1;
                if (dop && pf >= 0 && lane == 0) mbar_arrive(sbase + SB_REQ);
            }
            if (pc >= 0) {
                unsigned char* op = reinterpret_cast<unsigned char*>(out) + (uint32_t)((pc * 64 + kq * 16 + (lane >> 2)) * DM + cb * 64 + wq * 16 + 2 * (lane & 3)) * 2u;
#pragma unroll
                for (int k = 0; k < 4; k++) *reinterpret_cast<uint32_t*>(op + (k >> 1) * (16 * DM) + (k & 1) * 16) = w[k];
                if ((pc & 1) == 0) TS3(4 + pc / 2);
                if (pc == 31) TS3(25);
            }
            if (!more) break;
          }
        }
        if (cta == 0 && tid == 0) asm volatile("red.relaxed.gpu.global.add.u32 [%0], 1;" :: "l"(&g_epoch) : "memory");
    }
    asm volatile("griddepcontrol.wait;" ::: "memory");
}

template <class F>
__device__ __forceinline__ uint32_t poll_mem(const uint4* src, uint32_t dst, uint32_t t0, F next) {
    uint4 v[6];
    unsigned it = 0;
#pragma unroll
    for (int j = 0; j < 6; j++) v[j] = make_uint4(0u, 0u, 0u, 0u);
    while (clock32() - t0 < POLL_DELAY) {}
    FS(12, 0);
    bool more;
#pragma unroll 1
    do {
        asm volatile("{\n.reg .pred p<6>;\n"
                     "setp.ne.u32 p0, %3, 0x5000;\nsetp.ne.u32 p1, %7, 0x5000;\nsetp.ne.u32 p2, %11, 0x5000;\n"
                     "setp.ne.u32 p3, %15, 0x5000;\nsetp.ne.u32 p4, %19, 0x5000;\nsetp.ne.u32 p5, %23, 0x5000;\n"
                     "@p0 ld.volatile.global.v4.u32 {%0,%1,%2,%3}, [%24];\n@p1 ld.volatile.global.v4.u32 {%4,%5,%6,%7}, [%24+4096];\n"
                     "@p2 ld.volatile.global.v4.u32 {%8,%9,%10,%11}, [%24+8192];\n@p3 ld.volatile.global.v4.u32 {%12,%13,%14,%15}, [%24+12288];\n"
                     "@p4 ld.volatile.global.v4.u32 {%16,%17,%18,%19}, [%24+16384];\n@p5 ld.volatile.global.v4.u32 {%20,%21,%22,%23}, [%24+20480];\n}"
                     : "+r"(v[0].x), "+r"(v[0].y), "+r"(v[0].z), "+r"(v[0].w), "+r"(v[1].x), "+r"(v[1].y), "+r"(v[1].z), "+r"(v[1].w),
                       "+r"(v[2].x), "+r"(v[2].y), "+r"(v[2].z), "+r"(v[2].w), "+r"(v[3].x), "+r"(v[3].y), "+r"(v[3].z), "+r"(v[3].w),
                       "+r"(v[4].x), "+r"(v[4].y), "+r"(v[4].z), "+r"(v[4].w), "+r"(v[5].x), "+r"(v[5].y), "+r"(v[5].z), "+r"(v[5].w)
                     : "l"(src) : "memory");
        stsm_x4(dst, h2_to_bf2(v[0].x), h2_to_bf2(v[0].y), h2_to_bf2(v[0].z), h2_to_bf2(v[1].x));
        stsm_x4(dst + 512, h2_to_bf2(v[1].y), h2_to_bf2(v[1].z), h2_to_bf2(v[2].x), h2_to_bf2(v[2].y));
        const uint32_t all = ((v[0].w & v[1].w) & (v[2].w & v[3].w)) & (v[4].w & v[5].w);
        more = __any_sync(0xffffffffu, (all & 0x5000u) != 0x5000u && ++it < SPIN_LIMIT);
        stsm_x4(dst + 1024, h2_to_bf2(v[2].z), h2_to_bf2(v[3].x), h2_to_bf2(v[3].y), h2_to_bf2(v[3].z));
        asm volatile("stmatrix.sync.aligned.m8n8.x2.shared.b16 [%0], {%1,%2};" :: "r"(dst + 1536), "r"(h2_to_bf2(v[4].x)), "r"(h2_to_bf2(v[4].y)) : "memory");
        stsm_x4(dst + 1792, h2_to_bf2(v[4].z), h2_to_bf2(v[5].x), h2_to_bf2(v[5].y), h2_to_bf2(v[5].z));
        asm volatile("{\n.reg .pred p;\nsetp.eq.u32 p, %0, 0;\n@p bar.sync 1, 384;\n}" :: "r"((uint32_t)more) : "memory");
    } while (more);
    next();
    FS(13, it);
    FS(14, 0);
    uint32_t m = v[0].x, m1 = v[0].y, m2 = v[0].z;
#pragma unroll
    for (int j = 1; j < 6; j++) {
        asm volatile("max.NaN.xorsign.abs.f16x2 %0, %0, %1;" : "+r"(m) : "r"(v[j].x));
        asm volatile("max.NaN.xorsign.abs.f16x2 %0, %0, %1;" : "+r"(m1) : "r"(v[j].y));
        asm volatile("max.NaN.xorsign.abs.f16x2 %0, %0, %1;" : "+r"(m2) : "r"(v[j].z));
    }
    asm volatile("max.NaN.xorsign.abs.f16x2 %0, %0, %1;" : "+r"(m) : "r"(m1));
    asm volatile("max.NaN.xorsign.abs.f16x2 %0, %0, %1;" : "+r"(m) : "r"(m2));
    return h2_to_bf2(m) & 0x7fff7fffu;
}

template <int N> __device__ __forceinline__ void pad_code() {
#pragma unroll
    for (int i = 0; i < N; i++) asm volatile("pmevent 7;" ::: "memory");
}
template <bool V> struct Flag { static constexpr bool value = V; };
struct RFlag { bool value; };
__device__ __forceinline__ void score_group(const uint32_t (&a)[2][4], const uint32_t (&kf)[2][4], uint32_t d0, uint32_t d1, uint32_t m1, uint32_t d2, uint32_t m2) {
    FS(4, a[1][0]);
    float sc[4][4];
    mma_z(sc[0], a[0], kf[0][0], kf[0][1]);
    mma_z(sc[1], a[0], kf[0][2], kf[0][3]);
    mma_z(sc[2], a[1], kf[1][0], kf[1][1]);
    mma_z(sc[3], a[1], kf[1][2], kf[1][3]);
    constexpr float EC = (float)(1.4426950408889634 * 0.08838834764831845);
    const uint32_t v0 = __float_as_uint(fmaf(sc[3][2], EC, ((sc[0][0] + sc[1][2]) + sc[2][0]) * EC)), v1 = __float_as_uint(fmaf(sc[3][3], EC, ((sc[0][1] + sc[1][3]) + sc[2][1]) * EC));
    FS(5, v0);
    st_async64(d2, v0, v1, m2);
    st_async64(d1, v0, v1, m1);
    asm volatile("st.shared.v2.u32 [%0], {%1,%2};" :: "r"(d0), "r"(v0), "r"(v1) : "memory");
}
__device__ __forceinline__ void store_tile(int s, int h, int role, uint32_t tile, uint32_t b0, uint32_t b1) {
    asm volatile("cp.async.bulk.global.shared::cta.bulk_group.L2::cache_hint [%0], [%1], %2, %3;"
                 :: "l"(&g_qkv[s][h][role][b0]), "r"(tile + b0), "r"(b1 - b0), "l"(policy_evict_first()) : "memory");
}
__device__ __forceinline__ uint32_t w_addr(uint32_t sbase, int warp, int lane) {
    return sbase + SM_WS + (warp >> 2) * 8192 + ((lane & 7) + ((lane >> 4) & 1) * 8) * 128 + ((((warp & 3) * 2 + ((lane >> 3) & 1)) ^ (lane & 7)) << 4);
}
__device__ __forceinline__ void vx_copy(uint32_t sbase, int j, int r) {
    bulk_s2s(mapa(sbase + SM_VX + (j & 1) * 8192, r), sbase + SM_T + (j & 3) * TBUF + DH * 16, 8192, mapa(sbase + B_VX + 8 * (j & 1), r));
}
__device__ __forceinline__ float to_scale(float bound) {
    int e = 141 - (int)((__float_as_uint(bound) >> 23) & 255u);
    e = e > 100 ? 100 : e;
    return __uint_as_float((uint32_t)(127 + e) << 23);
}
__device__ __forceinline__ void norms_gather(int lane, uint32_t sbase) {
    uint2 v[3];
    uint4 w[2];
    unsigned it = 0;
#pragma unroll
    for (int i = 0; i < 3; i++) v[i] = make_uint2(0u, 0u);
    w[0] = w[1] = make_uint4(0u, 0u, 0u, 0u);
    bool more;
    do {
#pragma unroll
        for (int i = 0; i < 3; i++) if (!GPRED || (v[i].x & 1u) == 0u) v[i] = ld_vol_u2(&g_norm[3 * lane + i]);
#pragma unroll
        for (int i = 0; i < 2; i++) if (!GPRED || (w[i].x & w[i].y & w[i].z & w[i].w & 1u) == 0u) w[i] = ld_vol_u4(&g_wv[lane][i]);
        more = __any_sync(0xffffffffu, (v[0].x & v[1].x & v[2].x & w[0].x & w[0].y & w[0].z & w[0].w & w[1].x & w[1].y & w[1].z & w[1].w & 1u) == 0u);
    } while (more && ++it < SPIN_LIMIT);
    float c;
    asm("sqrt.approx.f32 %0, %1;" : "=f"(c) : "f"(__uint_as_float(max(max(v[0].x, v[1].x), v[2].x))));
    c *= __uint_as_float(max(max(max(w[0].x, w[0].y), max(w[0].z, w[0].w)), max(max(w[1].x, w[1].y), max(w[1].z, w[1].w)))) * 272.f;
#pragma unroll
    for (int o = 16; o; o >>= 1) c += __shfl_xor_sync(0xffffffffu, c, o);
    const uint32_t r = __reduce_max_sync(0xffffffffu, v[0].y);
    if (lane < 3) {
        const uint32_t rb = mapa(sbase, lane);
        c *= 1.1f * 24.f;
        st_async64(rb + SM_SC, __float_as_uint(to_scale(__uint_as_float(r) * c)), __float_as_uint(c), rb + B_W + 8);
        st_async32(rb + SM_SC + 68, r, rb + B_W + 8);
    }
    __syncwarp();
}
__device__ __forceinline__ void xmax_gather(int lane, uint32_t sb) {
    uint4 v[4];
    unsigned it = 0;
    uint32_t ok;
    do {
#pragma unroll
        for (int i = 0; i < 4; i++) v[i] = ld_vol_u4(&g_rx[lane + 32 * (i >> 1)][i & 1]);
        ok = 1u;
#pragma unroll
        for (int i = 0; i < 4; i++) ok &= (v[i].x & v[i].y) & (v[i].z & v[i].w);
    } while (__any_sync(0xffffffffu, ok == 0u) && ++it < SPIN_LIMIT);
#pragma unroll
    for (int i = 0; i < 2; i++)
        sts32(sb + SM_SC + 64 + 4 * lane + 128 * i, max(max(max(v[2 * i].x, v[2 * i].y), max(v[2 * i].z, v[2 * i].w)), max(max(v[2 * i + 1].x, v[2 * i + 1].y), max(v[2 * i + 1].z, v[2 * i + 1].w))));
}
__device__ __forceinline__ uint32_t max_abs8(uint32_t m, uint32_t a, uint32_t b, uint32_t c, uint32_t d) { return max_abs2(max_abs2(m, max_abs2(a, b)), max_abs2(c, d)); }
__device__ __forceinline__ uint32_t warp_max_abs(uint32_t m) { return __reduce_max_sync(0xffffffffu, max((m << 16) & 0x7fff0000u, m & 0x7fff0000u)); }

__device__ __forceinline__ void last_rows(int pass) {
    extern __shared__ __align__(1024) unsigned char smem_raw[];
    const uint32_t sbase = smem_u32(smem_raw);
    const int tid = threadIdx.x, warp = __shfl_sync(0xffffffffu, tid >> 5, 0), h = blockIdx.x / 3;
    {
        const int sg = warp < 8, wq = warp & 3, lane = tid & 31;
        const uint32_t qk = sbase + SM_X + XBUF + sg * (2 * 9216), ob = sbase + SM_X + 2 * XBUF + sg * 8192;
        TST(0);
        if (pass) mbar_wait(sbase + B_VX + 8 * sg, 0);
        fence_async();
        TST(1);
        float sc[20];
#pragma unroll
        for (int i = 0; i < 20; i++) sc[i] = 0.f;
        {
            const uint64_t da = smem_desc(qk + 1024, 128, 1024), db = smem_desc(qk, 128, 2048);
            wg_fence();
#pragma unroll
            for (int ks = 0; ks < 8; ks++) wgmma_n40_ss(sc, da + (uint64_t)((ks >> 2) * 576 + (ks & 3) * 16), db + (uint64_t)((ks >> 2) * 576 + (ks & 3) * 16), ks > 0);
            wg_commit();
            wg_wait0();
        }
        uint32_t p[5], o[16];
        const float psum = xrow_softmax(sc, p, wq, lane);
        xrow_pv(o, p, psum, sbase + SM_T + ((NSEG - 2 + sg) & 3) * TBUF);
        if (pass) {
#pragma unroll
            for (int i = 0; i < 4; i++) stsm_x4(ob + wq * 2048 + i * 512 + lane * 16, o[4 * i], o[4 * i + 1], o[4 * i + 2], o[4 * i + 3]);
        }
        fence_async();
        named_bar(11 + sg, 128);
        TST(2);
        if ((tid & 127) == 0 && pass) {
            unsigned char* dst = reinterpret_cast<unsigned char*>(g_ox) + ((size_t)((NSEG / 2 - 1) * NH + h)) * 16384 + sg * 8192;
            asm volatile("cp.async.bulk.global.shared::cta.bulk_group [%0], [%1], 8192;" :: "l"(dst), "r"(ob) : "memory");
            asm volatile("cp.async.bulk.commit_group;" ::: "memory");
            asm volatile("cp.async.bulk.wait_group 0;" ::: "memory");
            asm volatile("red.relaxed.gpu.global.add.u32 [%0], 1;" :: "l"(&g_prog[(h >> 2) * 64 + NSEG / 2 - 1]) : "memory");
        }
        TST(3);
    }
    __syncwarp();
}

__global__ void __cluster_dims__(3, 1, 1) __launch_bounds__(384, 1)
k_chain(const __grid_constant__ CUtensorMap tmq, const __grid_constant__ CUtensorMap tmk,
        const __grid_constant__ CUtensorMap tmv, const __grid_constant__ CUtensorMap tmx2, const __grid_constant__ CUtensorMap tmo,
        const __grid_constant__ CUtensorMap tmm, const bf16* __restrict__ xg) {
    extern __shared__ __align__(1024) unsigned char smem_raw[];
    const uint32_t sbase = smem_u32(smem_raw);
    const int cta = blockIdx.x, h = cta / 3, role = cta - 3 * h;
    const int tid = threadIdx.x, warp = __shfl_sync(0xffffffffu, tid >> 5, 0), lane_o = tid & 31;
    TS3C(0);
    asm volatile("griddepcontrol.launch_dependents;" ::: "memory");
    auto stage_w = [&](int i) {
        tma_2d(sbase + SM_WS + i * 16384, role == 2 ? &tmv : &tmq, h * DH + (role == 1 ? 64 : 0), i * 64, sbase + B_W + 8 * i);
        tma_2d(sbase + SM_WS + i * 16384 + 8192, role == 2 ? &tmv : &tmk, h * DH + (role == 0 ? 0 : 64), i * 64, sbase + B_W + 8 * i);
    };
    auto stage_x = [&](int i) {
        tma_2d(sbase + x01_off(i), &tmx2, i * 64, 0, sbase + B_W + 8 * i);
        tma_2d(sbase + x01_off(i) + 8192, &tmm, i * 64, 0, sbase + B_W + 8 * i);
        if (i < 3) tma_2d(sbase + x23_off(i), &tmx2, i * 64, 64, sbase + B_W + 8 * i);
    };
    if (tid == 0) {
#pragma unroll
        for (int i = 0; i < 10; i++) mbar_init(sbase + B_W + 8 * i, 1);
        fence_async();
        TSQ(10);
#pragma unroll
        for (int i = 0; i < 3; i++) tma_2d(sbase + SM_X01 + i * 16384, &tmo, role * WOC + i * 64, h * DH, sbase + B_E);
        stage_x(0); stage_w(0);
        TSQ(11);
        mbar_expect(sbase + B_E, 49152);
#pragma unroll
        for (int i = 0; i < 9; i++) mbar_expect(sbase + B_W + 8 * i, 16384 + 9216 + (i < 3 ? 8192 : 0));
    } else if (tid == 32) {
#pragma unroll
        for (int i = 0; i < 8; i++) mbar_init(sbase + SM_BAR + 8 * i, 1);
        mbar_init(sbase + B_XF, 3);
        asm volatile("fence.mbarrier_init.release.cluster;" ::: "memory");
        for (int i = 0; i < 2; i++) {
            mbar_expect(sbase + B_SB + 8 * i, role == 2 ? 2560 : 1280 + 2048);
            mbar_expect(sbase + B_VX + 8 * i, role != 2 ? 8192 : 2 * 9216);
            mbar_expect(sbase + B_XT + 8 * i, 32768);
            mbar_expect(sbase + B_XT + 16 + 8 * i, i == 0 ? 40960 : 0);
        }
    }
    __syncthreads();
    TS3C(8);
    if (tid == 0) {
#pragma unroll 1
        for (int i = 1; i < NUP; i++) { if (i < 3) stage_x(i); stage_w(i); }
        TSQ(12);
    }
    __syncwarp();
    if (warp < 8) {
        uint32_t wreg[36 - NS][4];
        uint32_t v0, v1;
        {
            const int lane = lane_o;
            const uint32_t a = w_addr(sbase, warp, lane);
            const uint64_t da = smem_desc(sbase + SM_WS + (warp >> 2) * 8192, 1024, 1024) | (1ull << 62);
            float acc[36], acc1[32];
            uint32_t m = 0u;
#pragma unroll
            for (int i = 0; i < 36; i++) acc[i] = 0.f;
#pragma unroll
            for (int i = 0; i < 32; i++) acc1[i] = 0.f;
#pragma unroll 1
            for (int b = 0; b < 7; b++) {
                if (b == 0) TSQ(0);
                mbar_wait(sbase + B_W + 8 * b, 0);
                TSQ(1 + b);
                const uint64_t db = smem_desc(sbase + x01_off(b), 16, 1024) | (1ull << 62);
                wg_fence();
#pragma unroll
                for (int k = 0; k < 4; k++) wgmma_n72_ss(acc, da + (uint64_t)(b * 1024 + k * 128), db + (uint64_t)(k * 2));
                wg_commit();
                if (b < 3) {
                    const uint64_t d1 = smem_desc(sbase + x23_off(b), 16, 1024) | (1ull << 62);
                    wg_fence();
#pragma unroll
                    for (int k = 0; k < 4; k++) wgmma_n64_ss(acc1, da + (uint64_t)(b * 1024 + k * 128), d1 + (uint64_t)(k * 2));
                    wg_commit();
                }
                if (b == 2) {
                    wg_wait0();
                    bar_arrive(10, 384);
                }
                if (b == 3) {
                    if (tid == 0) mbar_expect(sbase + B_W + 8, 12);
                    __syncwarp();
                    if (role == 2) {
#pragma unroll
                        for (int ks = 0; ks < NS; ks++) {
                            uint32_t t[4];
                            ldsm_x4_t(t, a + (ks >> 2) * 16384 + (ks & 3) * 2048);
                            m = max_abs8(m, t[0], t[1], t[2], t[3]);
                        }
                    }
#pragma unroll
                    for (int ks = NS; ks < 16; ks++) ldsm_x4_t(wreg[ks - NS], a + (ks >> 2) * 16384 + (ks & 3) * 2048);
                }
                if (b == 5) {
#pragma unroll
                    for (int ks = 16; ks < 24; ks++) ldsm_x4_t(wreg[ks - NS], a + (ks >> 2) * 16384 + (ks & 3) * 2048);
                    if (role == 2) {
#pragma unroll
                        for (int ks = NS; ks < 24; ks++) m = max_abs8(m, wreg[ks - NS][0], wreg[ks - NS][1], wreg[ks - NS][2], wreg[ks - NS][3]);
                    }
                }
            }
            mbar_wait(sbase + B_W + 16, 1);
            TSQ(13);
            wg_fence();
#pragma unroll
            for (int k = 12; k < 20; k++)
                wgmma_n64_ss(acc1, da + (uint64_t)((k >> 2) * 1024 + (k & 3) * 128), (smem_desc(sbase + x23_off(k >> 2), 16, 1024) | (1ull << 62)) + (uint64_t)((k & 3) * 2));
            wg_commit();
            wg_wait0();
            named_bar(11, 384);
#pragma unroll
            for (int i = 0; i < 8; i++)
                asm volatile("st.shared.v4.f32 [%0], {%1,%2,%3,%4};" :: "r"(sbase + SM_X + 5 * 8192 + i * 4096 + tid * 16),
                             "f"(acc1[4 * i]), "f"(acc1[4 * i + 1]), "f"(acc1[4 * i + 2]), "f"(acc1[4 * i + 3]) : "memory");
#pragma unroll
            for (int b = 7; b < 9; b++) {
#pragma unroll
                for (int ks = 4 * b - 4; ks < 4 * b; ks++) ldsm_x4_t(wreg[ks - NS], a + (ks >> 2) * 16384 + (ks & 3) * 2048);
                if (role == 2) {
#pragma unroll
                    for (int ks = 4 * b - 4; ks < 4 * b; ks++) m = max_abs8(m, wreg[ks - NS][0], wreg[ks - NS][1], wreg[ks - NS][2], wreg[ks - NS][3]);
                }
                const uint64_t db = smem_desc(sbase + x01_off(b), 16, 1024) | (1ull << 62);
                mbar_wait(sbase + B_W + 8 * b, 0);
                TSQ(1 + b);
                if (b == 8) TS3C(2);
                wg_fence();
#pragma unroll
                for (int k = 0; k < 4; k++) wgmma_n72_ss(acc, da + (uint64_t)(b * 1024 + k * 128), db + (uint64_t)(k * 2));
                wg_commit();
            }
#pragma unroll
            for (int ks = 32; ks < KPRE; ks++) ldsm_x4_t(wreg[ks - NS], a + (ks >> 2) * 16384 + (ks & 3) * 2048);
            if (role == 2) {
#pragma unroll
                for (int ks = KPRE; ks < 36; ks++) {
                    uint32_t t[4];
                    ldsm_x4_t(t, a + (ks >> 2) * 16384 + (ks & 3) * 2048);
                    m = max_abs8(m, t[0], t[1], t[2], t[3]);
                }
#pragma unroll
                for (int ks = 32; ks < KPRE; ks++) m = max_abs8(m, wreg[ks - NS][0], wreg[ks - NS][1], wreg[ks - NS][2], wreg[ks - NS][3]);
                m = warp_max_abs(m);
                if (lane == 0) asm volatile("st.volatile.global.u32 [%0], %1;" :: "l"(reinterpret_cast<uint32_t*>(&g_wv[h][0]) + warp), "r"(m | 1u) : "memory");
                __syncwarp();
            }
            wg_wait0();
            named_bar(9, 256);
            const uint32_t off = sbase + SM_T + (DH + warp * 16 + (lane & 15)) * 16 + (lane >> 4) * (DH * 16);
#pragma unroll
            for (int i = 0; i < 4; i++)
                stsm_x4(off + (i >> 1) * TBUF + (i & 1) * (2 * DH * 16), pack_bf16(acc[8 * i], acc[8 * i + 1]), pack_bf16(acc[8 * i + 2], acc[8 * i + 3]),
                        pack_bf16(acc[8 * i + 4], acc[8 * i + 5]), pack_bf16(acc[8 * i + 6], acc[8 * i + 7]));
            v0 = pack_bf16(acc[32], acc[33]);
            v1 = pack_bf16(acc[34], acc[35]);
#pragma unroll
            for (int ks = KPRE; ks < 36; ks++) ldsm_x4_t(wreg[ks - NS], a + (ks >> 2) * 16384 + (ks & 3) * 2048);
            if (role == 2) fence_async();
            bar_arrive(8, 384);
            named_bar(7, 256);
            asm volatile("barrier.cluster.arrive.relaxed.aligned;" ::: "memory");
        }
        TS3C(3);
        uint32_t ws[NS][4];
#pragma unroll
        for (int ks = NS - NP; ks < NS; ks++) ldsm_x4_t(ws[ks], w_addr(sbase, warp, lane_o) + (ks >> 2) * 16384 + (ks & 3) * 2048);
        asm volatile("barrier.cluster.wait.aligned;" ::: "memory");
        if (lane_o == 0 && role != 2 && warp < 2) tma_2d_mc(sbase + SM_X + (2 * role + warp) * 8192, &tmx2, (2 * role + warp + 5) * 64, 64, sbase + B_XT + 8);
        __syncwarp();
        TS3C(4);
        auto main_loop = [&](auto is_c) {
            constexpr bool C = decltype(is_c)::value;
            if (C) pad_code<PAD4>(); else pad_code<PAD3>();
            const uint32_t l16 = __shfl_sync(0xffffffffu, sbase + lane_o * 16, lane_o);
            const uint32_t ka = __shfl_sync(0xffffffffu, sbase + SM_T + (64 + (lane_o & 7) + ((lane_o >> 3) & 1) * 16 + (lane_o >> 4) * 8) * 16, lane_o);
            const uint32_t wa = __shfl_sync(0xffffffffu, w_addr(sbase, warp, lane_o), lane_o);
            auto post = [&](bool act, int s, uint32_t to, uint32_t ta, int scw, uint32_t v0, uint32_t v1) {
                int lane = lane_o;
                asm volatile("" : "+r"(lane));
                asm volatile("stmatrix.sync.aligned.m8n8.x2.shared.b16 [%0], {%1,%2};" :: "r"(l16 + ta), "r"(v0), "r"(v1) : "memory");
                if (C) {
                    if (act || s + 1 < NSEG) {
                        const uint32_t fo = (uint32_t)(warp * 256 + lane * 8);
                        const uint32_t rb0 = mapa(sbase, 0), rb1 = mapa(sbase, 1);
                        st_async64(rb0 + SM_VM + fo, v0, v1, rb0 + B_SB + 8 * (s & 1));
                        st_async64(rb1 + SM_VM + fo, v0, v1, rb1 + B_SB + 8 * (s & 1));
                        asm volatile("st.shared.v2.u32 [%0], {%1,%2};" :: "r"(sbase + SM_VM + fo), "r"(v0), "r"(v1) : "memory");
                        bar_arrive(2, 384);
                    }
                } else if (act) bar_arrive(2, 384);
                else {
                    named_bar(2, 384);
                    if (scw == 0) {
                        uint32_t kf[2][4], qf[2][4];
#pragma unroll
                        for (int k2 = 0; k2 < 2; k2++) { ldsm_x4_t(kf[k2], ka + to + k2 * 512); ldsm_x4_t(qf[k2], l16 + SM_T + to + k2 * 512); }
                        const uint32_t d0 = sbase + SM_S + lane * 8, bo = sbase + B_SB + 8 * (s & 1);
                        const uint32_t d1 = mapa(d0 + 1280, role ^ 1), m1 = mapa(bo, role ^ 1), d2 = mapa(d0 + role * 1280, 2), m2 = mapa(bo, 2);
                        score_group(qf, kf, d0, d1, m1, d2, m2);
                        bar_arrive(6, 160);
                        bar_arrive(5, 384);
                    }
                    if (RARE(scw == 8)) {
                        const uint32_t dk = mapa(sbase + SM_X + XBUF + (2 + role) * 9216 + (warp - 4) * 256 + lane * 4, 2), mb = mapa(sbase + B_VX + 8, 2);
                        st_async32(dk, v0, mb);
                        st_async32(dk + 128, v1, mb);
                    }
                }
                FS(11, 0);
            };
            post(false, 0, 0, SM_T + warp * 256, warp ^ 7, v0, v1);
            if (tid == 128 && cta < NSEG) {
                fence_async();
                mbar_expect(sbase + B_E, XBUF);
                bulk_g2s(sbase + SM_X + 9 * 8192, xg + (size_t)cta * SEG * DM, 32768, sbase + B_E);
                bulk_g2s(sbase + SM_WS + 32768 + 4096, xg + (size_t)cta * SEG * DM + 16384, 4096, sbase + B_E);
            }
            __syncwarp();
            if (C) {
                named_bar(7, 256);
                if (warp == 1) norms_gather(lane_o, sbase);
            }
            auto chores = [&](int s, bool idle) {
                int lane = lane_o;
                asm volatile("" : "+r"(lane));
                const int hw = (s & 1) ? warp : warp - 4;
                const uint32_t tb = sbase + SM_T + (s & 3) * TBUF;
                if (idle) { if (hw != 2) named_bar(4, 384); else bar_arrive(4, 384); }
                if (hw == 2) {
                    if (lane == 0) {
                        if (C || !idle) fence_async();
                        if (C) {
                            store_tile(s + 1, h, 2, sbase + SM_T + ((s + 1) & 3) * TBUF, 2048, 10240);
                            store_tile(s, h, 2, tb, 0, idle ? 2048 : 10240);
                        } else if (EXS) {
                            store_tile(s + 1, h, role, sbase + SM_T + ((s + 1) & 3) * TBUF, 2048, 10240);
                            store_tile(s, h, role, tb, 1024, idle ? 2048 : 10240);
                        } else store_tile(s, h, role, tb, 1024, 10240);
                        asm volatile("cp.async.bulk.commit_group;" ::: "memory");
                        asm volatile("cp.async.bulk.wait_group 0;" ::: "memory");
                        if (C) {
                            asm volatile("cp.async.bulk.shared::cluster.global.mbarrier::complete_tx::bytes.multicast::cluster [%0], [%1], 8192, [%2], %3;"
                                         :: "r"(sbase + SM_VX + ((s + 1) & 1) * 8192), "l"(&g_qkv[s + 1][h][2][2048]), "r"(sbase + B_VX + 8 * ((s + 1) & 1)), "h"((unsigned short)3) : "memory");
                        }
                        asm volatile("red.relaxed.gpu.global.add.u32 [%0], 1;" :: "l"(&g_flag[h * NSEG + s]) : "memory");
                    }
                    __syncwarp();
                    if (!EXS && !C && (s & 1) && s + 4 < NSEG) bar_arrive(13, 160);
                }
                __syncwarp();
            };
            auto put_tiles = [&](const float (&acc)[32], uint32_t off) {
#pragma unroll
                for (int i = 0; i < 4; i++)
                    stsm_x4(off + (i >> 1) * TBUF + (i & 1) * (2 * DH * 16), pack_bf16(acc[8 * i], acc[8 * i + 1]), pack_bf16(acc[8 * i + 2], acc[8 * i + 3]),
                            pack_bf16(acc[8 * i + 4], acc[8 * i + 5]), pack_bf16(acc[8 * i + 6], acc[8 * i + 7]));
            };
            auto tile_off = [&](int p) {
                int lane = lane_o;
                asm volatile("" : "+r"(lane));
                return sbase + SM_T + (p & 1) * (2 * TBUF) + (DH + warp * 16 + (lane & 15)) * 16 + (lane >> 4) * (DH * 16);
            };
            {
                auto db = [&](int ks) { return (smem_desc(sbase + SM_X, 16, 1024) | (1ull << 62)) + (uint64_t)(((ks >> 2) - 5) * 512 + (ks & 3) * 2); };
                float acc[32];
#pragma unroll
                for (int i = 0; i < 8; i++)
                    asm volatile("ld.shared.v4.f32 {%0,%1,%2,%3}, [%4];" : "=f"(acc[4 * i]), "=f"(acc[4 * i + 1]), "=f"(acc[4 * i + 2]), "=f"(acc[4 * i + 3])
                                 : "r"(l16 + warp * 512 + SM_X + 5 * 8192 + i * 4096) : "memory");
                mbar_wait(sbase + B_XT + 8, 0);
                if (C) { if (warp < 4) named_bar(4, 384); } else if (warp != 7) named_bar(5, 384);
                wg_fence();
#pragma unroll
                for (int ks = 35; ks > 35 - NC0; ks--) wgmma_n64(acc, wreg[ks - NS], db(ks), 1);
                wg_commit();
                wg_wait0();
                if (warp == 5) {
                    mbar_wait(sbase + B_W + 8, 1);
                    bar_arrive(12, 160);
                }
                chores(0, false);
                if (!C || warp >= 4) named_bar(4, 384);
                wg_fence();
#pragma unroll
                for (int ks = 35 - NC0; ks >= 20; ks--) wgmma_n64(acc, wreg[ks - NS], db(ks), 1);
                wg_commit();
                if (cta < NSEG) {
                    uint32_t m = 0u;
                    mbar_wait(sbase + B_E, 1);
#pragma unroll 1
                    for (int j = 0; j < 9; j++) {
                        const uint4 xv = lds128(l16 + warp * 512 + (j < 8 ? SM_X + 9 * 8192 + j * 4096 : SM_WS + 32768 + 4096));
                        m = max_abs8(m, xv.x, xv.y, xv.z, xv.w);
                    }
                    m = warp_max_abs(m);
                    if (lane_o == 0) asm volatile("st.volatile.global.u32 [%0], %1;" :: "l"(reinterpret_cast<uint32_t*>(&g_rx[cta][0]) + warp), "r"(m | 1u) : "memory");
                    __syncwarp();
                }
                wg_wait0();
                put_tiles(acc, tile_off(1));
            }
            auto mem_proj = [&](uint32_t& u0, uint32_t& u1) {
#pragma unroll
                for (int ks = 0; ks < NS - NP; ks++) ldsm_x4_t(ws[ks], wa + (ks >> 2) * 16384 + (ks & 3) * 2048);
                FS(0, ws[0][0]);
                named_bar(1, 384);
                float acc[2][4], minv;
                uint32_t b[3][4];
#pragma unroll
                for (int kk = 0; kk < 3; kk++) ldsm_x4_t(b[kk], l16 + SM_M + kk * 512);
                FS(1, b[0][0]);
#pragma unroll
                for (int kk = 0; kk < 18; kk++) {
#pragma unroll
                    for (int i = 0; i < 2; i++) {
                        const int ks = 2 * kk + i;
                        if (ks < 2) mma_z(acc[i], ws[ks], b[kk % 3][2 * i], b[kk % 3][2 * i + 1]);
                        else if (ks < NS) mma_bf16(acc[i], ws[ks < NS ? ks : 0], b[kk % 3][2 * i], b[kk % 3][2 * i + 1]);
                        else mma_bf16(acc[i], wreg[ks >= NS ? ks - NS : 0], b[kk % 3][2 * i], b[kk % 3][2 * i + 1]);
                    }
                    if (kk + 3 < 18) ldsm_x4_t(b[kk % 3], l16 + SM_M + (kk + 3) * 512);
                    if (kk + 3 == 17) asm volatile("ld.shared.f32 %0, [%1];" : "=f"(minv) : "r"(sbase + SM_SC + 8) : "memory");
                }
                u0 = pack_bf16(fmaf(acc[1][0], minv, acc[0][0] * minv), fmaf(acc[1][1], minv, acc[0][1] * minv));
                u1 = pack_bf16(fmaf(acc[1][2], minv, acc[0][2] * minv), fmaf(acc[1][3], minv, acc[0][3] * minv));
                FS(2, u0);
            };
            int s = 0, rc = 9;
            bool act = warp >= 4;
            uint32_t to = TBUF, ta = SM_T + warp * 256 + TBUF;
            auto next_slot = [&]() {
                const uint32_t d = (s & 3) == 3 ? -3 * TBUF : TBUF;
                to += d; ta += d;
                asm volatile("" : "+r"(to), "+r"(ta));
            };
#pragma unroll 1
            for (;;) {
                uint32_t u0, u1;
                if (act) {
                    mem_proj(u0, u1);
                    s++;
                    post(true, s, to, ta, 1, u0, u1);
                    const int p = (s + 3) >> 1;
                    const uint32_t dlo = (uint32_t)smem_desc(sbase + SM_X, 16, 1024) + rc * 512;
                    const uint64_t da = smem_desc(sbase + SM_WS + (warp >> 2) * 8192, 1024, 1024) | (1ull << 62);
                    auto db = [&](int ks) {
                        const int j = ((ks >> 2) + 4) % 9;
                        return ((uint64_t)0x40000040u << 32) | (uint64_t)(dlo + (uint32_t)((j - (rc + j >= 13 ? 13 : 0)) * 512 + (ks & 3) * 2));
                    };
                    const uint32_t xph = (uint32_t)((p - 1) >> 1) & 1u;
                    float acc[32];
                    mbar_wait(sbase + B_XT + 8 * (p & 1), xph);
                    if (C) named_bar(7, 256); else named_bar(5, 384);
                    if ((C ? CC_DELAY : C1_DELAY) > 0) { const uint32_t t1 = clock32(); while (clock32() - t1 < (C ? CC_DELAY : C1_DELAY)) {} }
                    constexpr int N1 = C ? NC1C : NC1;
                    wg_fence();
#pragma unroll
                    for (int ks = 35; ks > 35 - N1; ks--) { if (ks == 35) wgmma_n64_z(acc, wreg[ks - NS], db(ks)); else wgmma_n64(acc, wreg[ks - NS], db(ks), 1); }
                    wg_commit();
                    wg_wait0();
                    FS(9, __float_as_uint(acc[0]));
                    next_slot();
                    FS(8, 0);
                    if (B4P) asm volatile("{\n.reg .pred p;\nsetp.ge.s32 p, %0, 0;\n@p bar.sync 4, 384;\n}" :: "r"(s) : "memory");
                    else named_bar(4, 384);
                    FS(3, 0);
                    wg_fence();
#pragma unroll
                    for (int ks = 35 - N1; ks >= KG1; ks--) wgmma_n64(acc, wreg[ks - NS], db(ks), 1);
                    wg_commit();
                    mbar_wait(sbase + B_XT + 16 + 8 * (p & 1), xph);
                    wg_fence();
#pragma unroll
                    for (int ks = 0; ks < NS; ks++) wgmma_n64_ss(acc, da + (uint64_t)((ks >> 2) * 1024 + (ks & 3) * 128), db(ks));
#pragma unroll
                    for (int ks = NS; ks < KG1; ks++) wgmma_n64(acc, wreg[ks - NS], db(ks), 1);
                    wg_commit();
                    if (!EXS && !C && warp >= 4) named_bar(13, 160);
                    uint32_t off = tile_off(p);
                    rc = rc >= 4 ? rc - 4 : rc + 9;
                    asm volatile("" : "+r"(off), "+r"(rc));
                    wg_wait0();
                    put_tiles(acc, off);
                    FS(7, __float_as_uint(acc[0]));
                }
                int scw = s + 2 < NSEG ? warp ^ ((s & 1) ? 7 : 3) : (warp & 4) + 4;
                asm volatile("" : "+r"(scw));
                mem_proj(u0, u1);
                s++;
                post(false, s, to, ta, scw, u0, u1);
                if (s + 1 == NSEG) break;
                if (s + 2 < NSEG) {
                    if (!C && (warp & 3) == 2) fence_async();
                    if (C) named_bar(7, 256); else if (scw != 0) named_bar(5, 384);
                    chores(s, true);
                } else {
                    const uint32_t t0 = clock32();
                    const uint32_t dq = mapa(sbase + SM_X + XBUF + role * 9216, 2), mb = mapa(sbase + B_VX, 2);
                    if (!C) {
                        if (scw != 0) named_bar(5, 384);
                        if (tid == 64) { fence_async(); while (clock32() - t0 < TL_DELAY) {} bulk_s2s(dq, sbase + SM_T + 2 * TBUF + 1024, 9216, mb); }
                        __syncwarp();
                    }
                    named_bar(4, 384);
                    if (!C && tid == 64) { const uint32_t t1 = clock32(); while (clock32() - t1 < VX_DELAY) {} bulk_s2s(dq + 2 * 9216 + 1024, sbase + SM_T + 3 * TBUF + 2048, 8192, mb + 8); }
                    __syncwarp();
                }
                next_slot();
                act = s + 4 < NSEG;
            }
            if (C) named_bar(7, 256);
        };
        if (role == 2) main_loop(Flag<true>()); else main_loop(Flag<false>());
    } else {
        uint32_t wo[3][8][4];
        uint32_t mx2 = 0u;
        {
            const int pt = tid - 256, lane = lane_o, wq = warp - 8, g = lane >> 2, tq = lane & 3;
            TSQ(7);
            if (XPF && cta < 9) asm volatile("prefetch.global.L2 [%0];" :: "l"(xg + 64 * DM + (cta * 128 + pt) * 64));
            mbar_wait(sbase + B_E, 0);
            TSQ(8);
#pragma unroll
            for (int t = 0; t < 3; t++) {
                const int T = 3 * wq + t;
                const uint32_t a = sbase + SM_X01 + (T >> 2) * 16384 + ((lane >> 4) * 8 + (lane & 7)) * 128 + ((((T & 3) * 2 + ((lane >> 3) & 1)) ^ (lane & 7)) << 4);
#pragma unroll
                for (int kk = 0; kk < 8; kk++) ldsm_x4_t(wo[t][kk], a + ((2 * wq + kk) & 7) * 2048);
            }
            named_bar(3, 128);
            if (pt == 64) {
                fence_async();
#pragma unroll 1
                for (int i = 3; i < 9; i++) { stage_x(i); if (i < 7) stage_w(i); }
            }
            if (pt >= 96 && pt < 120) {
                *reinterpret_cast<uint4*>(g_acc + cta * 1024 + (pt - 96) * 16) = make_uint4(0u, 0u, 0u, 0u);
                __threadfence();
            }
            __syncwarp();
            TSQ(9);
            float c0 = 0.f;
#pragma unroll
            for (int t = 0; t < 3; t++) {
                float n[4][4];
#pragma unroll
                for (int i = 0; i < 4; i++) { n[i][0] = n[i][1] = n[i][2] = n[i][3] = 0.f; }
#pragma unroll
                for (int kk = 0; kk < 8; kk++)
#pragma unroll
                    for (int i = 0; i < 4; i++) mma_k8(n[i], wo[t][kk][i & 2], wo[t][kk][(i & 2) + 1], wo[t][kk][i]);
                if ((g >> 1) == tq) c0 = fmaxf(c0, (g & 1) ? fmaxf(n[0][1] + n[2][1], n[1][3] + n[3][3]) : fmaxf(n[0][0] + n[2][0], n[1][2] + n[3][2]));
            }
            c0 = __uint_as_float(__reduce_max_sync(0xffffffffu, __float_as_uint(c0)));
            uint32_t m = 0u;
            const int xb = role == 0 ? h % 9 : 9;
            auto x_max = [&]() {
                mbar_wait(sbase + B_W + 8 * xb, 0);
#pragma unroll
                for (int j = 0; j < 5; j++) {
                    uint4 xv;
                    asm volatile("ld.shared.v4.u32 {%0,%1,%2,%3}, [%4];" : "=r"(xv.x), "=r"(xv.y), "=r"(xv.z), "=r"(xv.w)
                                 : "r"(sbase + x01_off(xb) + (j < 4 ? pt + 128 * j : 512 + (pt & 63)) * 16) : "memory");
                    m = max_abs8(m, xv.x, xv.y, xv.z, xv.w);
                }
            };
            if (xb < 3) x_max();
            named_bar(10, 384);
            TSQ(10);
            if (pt == 64) {
                fence_async();
                mbar_expect(sbase + B_W + 16, 16384);
#pragma unroll
                for (int i = 3; i < 5; i++) tma_2d(sbase + x23_off(i), &tmx2, i * 64, 64, sbase + B_W + 16);
#pragma unroll 1
                for (int i = 7; i < 9; i++) stage_w(i);
            }
            __syncwarp();
            if (xb >= 3 && xb < 7) x_max();
            bar_arrive(11, 384);
            if (xb == 7 || xb == 8) x_max();
            asm volatile("barrier.cluster.arrive.relaxed.aligned;" ::: "memory");
            m = warp_max_abs(m);
            if (lane == 0) { sts32(sbase + SM_SC + 320 + 4 * wq, __float_as_uint(c0)); sts32(sbase + SM_SC + 336 + 4 * wq, m); }
            TSQ(1);
            named_bar(3, 128);
            if (pt == 0) {
                const uint4 a = lds128(sbase + SM_SC + 320), b = lds128(sbase + SM_SC + 336);
                st_vol_u2(&g_norm[cta], make_uint2(max(max(a.x, a.y), max(a.z, a.w)) | 1u, max(max(b.x, b.y), max(b.z, b.w)) | 1u));
            }
            __syncwarp();
            named_bar(8, 384);
            TSQ(2);
            asm volatile("barrier.cluster.wait.aligned;" ::: "memory");
            if (role == 2 && lane == 0 && wq < 2) vx_copy(sbase, 0, wq);
            __syncwarp();
        }
        const int wq = warp - 8;
        auto helper_loop = [&](auto is_c) {
        const bool C = is_c.value;
        if (C) pad_code<PAD2>(); else pad_code<PAD1>();
        const uint32_t sb = sbase;
        const uint32_t l8_o = __shfl_sync(0xffffffffu, sb + lane_o * 8, lane_o), l16_o = __shfl_sync(0xffffffffu, sb + lane_o * 16, lane_o);
        unsigned char* dst = g_acc + (role * 32 + wq * 8 + (lane_o >> 3)) * 1024 + (lane_o & 7) * 16;
        auto load_kf = [&](uint32_t (&kf)[2][4], int slot) {
            int lane = lane_o;
            asm volatile("" : "+r"(lane));
            const uint32_t ka = sb + SM_T + slot * TBUF + ((wq + 1) * DH + 64 + (lane & 7) + ((lane >> 3) & 1) * 16 + (lane >> 4) * 8) * 16;
#pragma unroll
            for (int k2 = 0; k2 < 2; k2++) ldsm_x4_t(kf[k2], ka + k2 * 512);
        };
        float minv = 1.f;
        uint32_t kf[2][4];
        if (!C) load_kf(kf, 0);
        int b3 = 0;
        int rx = 9;
        for (int s = 0; s + 1 < NSEG; s++) {
            const int n3 = b3 == 2 ? 0 : b3 + 1;
            uint32_t l8 = l8_o, l16 = l16_o;
            asm volatile("" : "+r"(l8), "+r"(l16));
            {
                int lane = lane_o;
                asm volatile("" : "+r"(lane));
                if (C) {
                    if (lane == 0) {
                        if (wq == 3 && h == 0) {
                            const uint32_t t = gtime32();
                            st_vol_u2(&g_tick, make_uint2(t, lds32(sb + SM_SC + 12)));
                            sts32(sb + SM_SC + 12, t);
                        }
                    }
                    __syncwarp();
                    if (wq == 2 && s > 1 && lane < 24) {
                        *reinterpret_cast<uint4*>(g_acc + n3 * 128 + (3 * h + (lane >> 3)) * 1024 + (lane & 7) * 16) = make_uint4(0u, 0u, 0u, 0u);
                    }
                    if (RARE(wq == 1 && s == 3 && lane < 3)) {
                        const int c = 3 * h + lane;
                        st_vol_u2(&g_norm[c], make_uint2(0u, 0u));
                        uint4* z = c < NSEG ? g_rx[c] : g_wv[c - NSEG];
                        st_vol_u4(z, make_uint4(0u, 0u, 0u, 0u)); st_vol_u4(z + 1, make_uint4(0u, 0u, 0u, 0u));
                    }
                    __syncwarp();
                }
                const uint32_t mw = __reduce_max_sync(0xffffffffu, max(mx2 << 16, mx2 & 0xffff0000u));
                if (lane == 0) sts32(sb + SM_SC + 16 + 4 * wq, mw);
            }
            const uint32_t to = SM_T + (s & 3) * TBUF;
            const uint32_t ph = (uint32_t)(s >> 1) & 1u;
            if (!C) {
                const uint32_t bo = sb + B_SB + 8 * (s & 1);
                uint32_t d0 = l8 + SM_S + (wq + 1) * 256, qa = l16 + to;
                const uint32_t d1 = mapa(d0 + 1280, role ^ 1), m1 = mapa(bo, role ^ 1), d2 = mapa(d0 + role * 1280, 2), m2 = mapa(bo, 2);
                asm volatile("" : "+r"(d0), "+r"(qa));
                mbar_wait(sb + (s > 0 ? B_VX + 8 * (s & 1) : B_W), ph);
                FS(1, 0);
                named_bar(2, 384);
                uint32_t qf[2][4];
#pragma unroll
                for (int k2 = 0; k2 < 2; k2++) ldsm_x4_t(qf[k2], qa + k2 * 512);
                score_group(qf, kf, d0, d1, m1, d2, m2);
                bar_arrive(5, 384);
            } else named_bar(2, 384);
            if (!C && s == 0) {
                TSQ(3);
                mbar_wait(sb + B_VX, 0);
                TSQ(4);
            }
            float4 m4;
            asm volatile("ld.shared.v4.f32 {%0,%1,%2,%3}, [%4];" : "=f"(m4.x), "=f"(m4.y), "=f"(m4.z), "=f"(m4.w) : "r"(sb + SM_SC + 16) : "memory");
            const float c24 = __uint_as_float(lds32(sb + SM_SC + 4)), xb = __uint_as_float(lds32(sb + SM_SC + 64 + 4 * s));
            uint32_t vf[2][2][4], vm[2][2];
            uint32_t va = l16 + ((l16 >> 8) & 1) * 1792 + wq * 512 + (C ? to + DH * 16 : SM_VX + (s & 1) * 8192);
            auto load_vf = [&]() {
#pragma unroll
                for (int i = 0; i < 4; i++) ldsm_x4(vf[i & 1][i >> 1], va + (i & 1) * 256 + (i >> 1) * 4096);
            };
            load_vf();
            float scale = to_scale(fmaxf(fmaxf(fmaxf(m4.x, m4.y), fmaxf(m4.z, m4.w)) * minv, xb) * c24);
            uint32_t oa = l16 + wq * 512;
            asm volatile("" : "+f"(scale), "+r"(oa), "+r"(va));
            FS(7, __float_as_uint(scale));
            if (!C) named_bar(6, 160);
            if (C) mbar_wait_fast(sb + B_SB + 8 * (s & 1), ph);
            float sv[5][2];
#pragma unroll
            for (int j = 0; j < 5; j++) lds64f(sv[j][0], sv[j][1], l8 + SM_S + j * 256);
            if (!C) mbar_wait_fast(sb + B_SB + 8 * (s & 1), ph);
            FS(6, 0);
            uint32_t p[5];
            {
                float sr[5][2];
#pragma unroll
                for (int j = 0; j < 5; j++) lds64f(sr[j][0], sr[j][1], l8 + SM_S + 1280 + j * 256);
                lds64(vm[0][0], vm[0][1], l8 + SM_VM + wq * 512);
                lds64(vm[1][0], vm[1][1], l8 + SM_VM + wq * 512 + 256);
#pragma unroll
                for (int j = 0; j < 5; j++) {
                    sv[j][0] += sr[j][0];
                    sv[j][1] += sr[j][1];
                }
                float mx = fmaxf(fmaxf(fmaxf(sv[0][0], sv[0][1]), fmaxf(sv[1][0], sv[1][1])), fmaxf(fmaxf(sv[2][0], sv[2][1]), fmaxf(sv[3][0], sv[3][1])));
                mx = fmaxf(mx, fmaxf(sv[4][0], sv[4][1]));
                {
                    const float m1 = __shfl_xor_sync(0xffffffffu, mx, 1), m2 = __shfl_xor_sync(0xffffffffu, mx, 2), m3 = __shfl_xor_sync(0xffffffffu, mx, 3);
                    mx = fmaxf(fmaxf(mx, m1), fmaxf(m2, m3));
                }
#pragma unroll
                for (int jj = 0; jj < 5; jj++) {
                    const int j = (jj + 1) % 5;
                    asm("ex2.approx.ftz.f32 %0, %1;" : "=f"(sv[j][0]) : "f"(sv[j][0] - mx));
                    asm("ex2.approx.ftz.f32 %0, %1;" : "=f"(sv[j][1]) : "f"(sv[j][1] - mx));
                    p[j] = pack_bf16(sv[j][0], sv[j][1]);
                }
            }
            FS(0, p[0]);
            uint32_t b[4][4];
            const uint32_t one4[4] = {0x3f803f80u, 0x3f803f80u, 0x3f803f80u, 0x3f803f80u};
            float zs[4];
            {
                float o0[2][4], o1[2][4];
                mma_z(o0[0], vf[0][0], p[1], p[2]);
                mma_z(o0[1], vf[1][0], p[1], p[2]);
                mma_z(o1[0], vf[0][1], p[3], p[4]);
                mma_z(o1[1], vf[1][1], p[3], p[4]);
                mma_k8(o0[0], vm[0][0], vm[0][1], p[0]);
                mma_k8(o0[1], vm[1][0], vm[1][1], p[0]);
                if ((ZSM & 1) == 0) {
                    mma_z(zs, one4, p[1], p[2]);
                    mma_bf16(zs, one4, p[3], p[4]);
                    mma_k8(zs, one4[0], one4[1], p[0]);
                } else {
                    float z2[4];
                    mma_z(zs, one4, p[1], p[2]);
                    mma_z(z2, one4, p[3], p[4]);
                    mma_k8(zs, one4[0], one4[1], p[0]);
                    zs[0] += z2[0]; zs[1] += z2[1];
                }
                uint32_t ow[4];
#pragma unroll
                for (int m = 0; m < 2; m++) {
                    ow[2 * m] = pack_bf16(o0[m][0] + o1[m][0], o0[m][1] + o1[m][1]);
                    ow[2 * m + 1] = pack_bf16(o0[m][2] + o1[m][2], o0[m][3] + o1[m][3]);
                }
                stsm_x4(oa + SM_O, ow[0], ow[1], ow[2], ow[3]);
                FS(2, 0);
                if (ZSM & 2) {
                    __syncwarp();
                    ldsm_x4_t(b[0], oa + SM_O);
                } else if (ZSM & 4) {
                    b[0][0] = movm(ow[0]); b[0][1] = movm(ow[1]);
                    __syncwarp();
                    asm volatile("ldmatrix.sync.aligned.m8n8.x2.trans.shared.b16 {%0,%1}, [%2];" : "=r"(b[0][2]), "=r"(b[0][3]) : "r"(oa + SM_O + 256));
                } else {
#pragma unroll
                    for (int i = 0; i < 4; i++) b[0][i] = movm(ow[i]);
                }
            }
            float acc[3][2][4];
            named_bar(3, 128);
#pragma unroll
            for (int i = 1; i < 4; i++) ldsm_x4_t(b[i], l16 + SM_O + ((wq + i) & 3) * 512);
#pragma unroll
            for (int c = 0; c < 2; c++)
#pragma unroll
                for (int t = 0; t < 3; t++) mma_z(acc[t][c], wo[t][c], b[0][2 * c], b[0][2 * c + 1]);
            float z0, z1;
            asm volatile("rcp.approx.ftz.f32 %0, %1;" : "=f"(z0) : "f"(zs[0]));
            asm volatile("rcp.approx.ftz.f32 %0, %1;" : "=f"(z1) : "f"(zs[1]));
            asm volatile("{\n.reg .pred p;\nsetp.eq.s32 p, %1, 0;\n@p bar.sync 12, 160;\n@p ld.shared.f32 %0, [%2];\n}" : "+f"(scale) : "r"(s), "r"(sb + SM_SC) : "memory");
            z0 *= scale; z1 *= scale;
            FS(3, b[1][0]);
#pragma unroll
            for (int i = 1; i < 4; i++)
#pragma unroll
                for (int c = 0; c < 2; c++)
#pragma unroll
                    for (int t = 0; t < 3; t++) mma_bf16(acc[t][c], wo[t][2 * i + c], b[i][2 * c], b[i][2 * c + 1]);
            {
                uint32_t w[6];
#pragma unroll
                for (int t = 0; t < 3; t++) {
                    w[2 * t] = pack_f16(fmaf(acc[t][1][0], z0, acc[t][0][0] * z0), fmaf(acc[t][1][1], z1, acc[t][0][1] * z1));
                    w[2 * t + 1] = pack_f16(fmaf(acc[t][1][2], z0, acc[t][0][2] * z0), fmaf(acc[t][1][3], z1, acc[t][0][3] * z1));
                }
                FS(8, w[5]);
                asm volatile("red.relaxed.gpu.global.add.noftz.v4.f16x2 [%0], {%1,%2,%3,%4};" :: "l"(dst), "r"(w[0]), "r"(w[1]), "r"(w[2]), "r"(0x3c00u) : "memory");
                asm volatile("red.relaxed.gpu.global.add.noftz.v4.f16x2 [%0], {%1,%2,%3,%4};" :: "l"(dst + 4096), "r"(w[3]), "r"(w[4]), "r"(w[5]), "r"(0x3c00u) : "memory");
            }
            FS(9, 0);
            if (s == 0) TSQ(5);
            bar_arrive(4, 384);
            const uint32_t t0 = clock32();
            minv = __uint_as_float(0x7f000000u - __float_as_uint(scale));
            if (lane_o == 0) {
                if (wq == 0) sts32(sb + SM_SC + 8, __float_as_uint(minv));
                if (s + 3 < NSEG) {
                    if (wq == 0) mbar_expect(sb + B_SB + 8 * (s & 1), C ? 2560 : 1280 + 2048);
                    if (wq == 1 && s > 0 && s + 5 < NSEG) mbar_expect(sb + B_XT + ((s & 1) ? 0 : 16) + 4 * ((s + 1) & 2), (s & 1) ? 32768 : 40960);
                    if (wq == 3 && !C) mbar_expect(sb + B_VX + 8 * (s & 1), 8192);
                }
            }
            __syncwarp();
            if (RARE(s == 1)) {
                if (!C) pad_code<PADC>();
                int lane = lane_o;
                asm volatile("" : "+r"(lane));
                if (wq == 3) xmax_gather(lane, sb);
                __syncwarp();
            }
            if (!C) load_kf(kf, (s + 1) & 3);
            const uint4* src = reinterpret_cast<const uint4*>(dst + (wq * 16 - role * 32) * 1024);
            dst += n3 == 0 ? -256 : 128;
            asm volatile("" : "+l"(dst));
            const int xp = (s + 5) >> 1, kb = wq + ((s & 1) ? 2 * role : 4 + 3 * role);
            const bool xl = !C && xp < NSEG / 2 && wq < ((s & 1) ? 2 : 3 - role);
            const uint32_t xs = wq == 3 && (s & 1) == 0 && xp < NSEG / 2;
            const uint32_t xd = sb + SM_X + (rx + kb >= 13 ? rx + kb - 13 : rx + kb) * 8192;
            mx2 = poll_mem(src, l16 + SM_M + wq * 2304, t0, [&]() {
                if (xs && lane_o < 2) asm volatile("mbarrier.arrive.relaxed.cluster.shared::cluster.b64 _, [%0];" :: "r"(mapa(sb + B_XF, lane_o)) : "memory");
                if (!C && (xl || s == 0) && (s & 1) == 0) mbar_wait(sb + B_XF, (uint32_t)(s >> 1) & 1u);
                if (lane_o == 0) {
                    if (xl) tma_2d_mc(xd, &tmx2, ((s & 1) ? kb + 5 : kb - 4) * 64, xp * 64, sb + B_XT + ((s & 1) ? 0 : 16) + 8 * (xp & 1));
                    if (!C && s == 0 && role == 1) tma_2d_mc(sb + SM_X + (9 + wq) * 8192, &tmx2, (wq + 5) * 64, 128, sb + B_XT);
                }
                __syncwarp();
            });
            if ((s & 1) == 0) rx = rx >= 4 ? rx - 4 : rx + 9;
            if (s == 0) TSQ(6);
            b3 = n3;
        }
        if (!C) bar_arrive(2, 384);
        };
        if (role == 2) helper_loop(Flag<true>()); else helper_loop(Flag<false>());
    }
    TS3C(1);
    if (role == 2 && warp >= 4) last_rows(1);
    cluster_sync_all();
}

extern "C" void kernel_launch(void* const* d_in, const int* in_sizes, int n_in, void* d_out, int out_size) {
    const bf16* x = (const bf16*)d_in[0];
    const bf16* mem0 = (const bf16*)d_in[1];
    const bf16* Wq = (const bf16*)d_in[2];
    const bf16* Wk = (const bf16*)d_in[3];
    const bf16* Wv = (const bf16*)d_in[4];
    const bf16* Wo = (const bf16*)d_in[5];
    const bf16* logA = (const bf16*)d_in[8];
    const bf16* Aim = (const bf16*)d_in[9];
    const bf16* Cre = (const bf16*)d_in[10];
    const bf16* Cim = (const bf16*)d_in[11];
    const bf16* logdt = (const bf16*)d_in[12];
    const bf16* dskip = (const bf16*)d_in[13];
    const bf16* gw = (const bf16*)d_in[14];
    bf16* out = (bf16*)d_out;
    static bool attr_done = false;
    typedef CUresult (*EncFn)(CUtensorMap*, CUtensorMapDataType, cuuint32_t, void*, const cuuint64_t*, const cuuint64_t*, const cuuint32_t*,
                              const cuuint32_t*, CUtensorMapInterleave, CUtensorMapSwizzle, CUtensorMapL2promotion, CUtensorMapFloatOOBfill);
    static EncFn enc = nullptr;
    if (!attr_done) {
        void* fn = nullptr;
        cudaDriverEntryPointQueryResult qr;
        cudaGetDriverEntryPoint("cuTensorMapEncodeTiled", &fn, cudaEnableDefault, &qr);
        enc = (EncFn)fn;
        cudaFuncSetAttribute(k_chain, cudaFuncAttributeMaxDynamicSharedMemorySize, 232448);
        cudaFuncSetAttribute(k_side, cudaFuncAttributeMaxDynamicSharedMemorySize, SIDE_SMEM);
        attr_done = true;
    }
    CUtensorMap tmw[3];
    for (int i = 0; i < 3; i++) {
        const cuuint64_t dims[2] = {(cuuint64_t)HD, (cuuint64_t)DM};
        const cuuint64_t strides[1] = {(cuuint64_t)HD * 2};
        const cuuint32_t box[2] = {64, 64};
        const cuuint32_t es[2] = {1, 1};
        enc(&tmw[i], CU_TENSOR_MAP_DATA_TYPE_BFLOAT16, 2, (void*)(i == 0 ? Wq : (i == 1 ? Wk : Wv)), dims, strides, box, es, CU_TENSOR_MAP_INTERLEAVE_NONE,
            CU_TENSOR_MAP_SWIZZLE_128B, CU_TENSOR_MAP_L2_PROMOTION_L2_256B, CU_TENSOR_MAP_FLOAT_OOB_FILL_NONE);
    }
    CUtensorMap tmo;
    {
        const cuuint64_t dims[2] = {(cuuint64_t)DM, (cuuint64_t)HD};
        const cuuint64_t strides[1] = {(cuuint64_t)DM * 2};
        const cuuint32_t box[2] = {64, 128};
        const cuuint32_t es[2] = {1, 1};
        enc(&tmo, CU_TENSOR_MAP_DATA_TYPE_BFLOAT16, 2, (void*)Wo, dims, strides, box, es, CU_TENSOR_MAP_INTERLEAVE_NONE,
            CU_TENSOR_MAP_SWIZZLE_128B, CU_TENSOR_MAP_L2_PROMOTION_L2_128B, CU_TENSOR_MAP_FLOAT_OOB_FILL_NONE);
    }
    CUtensorMap tmx2;
    {
        const cuuint64_t dims[2] = {(cuuint64_t)DM, (cuuint64_t)S_LEN};
        const cuuint64_t strides[1] = {(cuuint64_t)DM * 2};
        const cuuint32_t box[2] = {64, 64};
        const cuuint32_t es[2] = {1, 1};
        enc(&tmx2, CU_TENSOR_MAP_DATA_TYPE_BFLOAT16, 2, (void*)x, dims, strides, box, es, CU_TENSOR_MAP_INTERLEAVE_NONE,
            CU_TENSOR_MAP_SWIZZLE_128B, CU_TENSOR_MAP_L2_PROMOTION_L2_128B, CU_TENSOR_MAP_FLOAT_OOB_FILL_NONE);
    }
    CUtensorMap tmm;
    {
        const cuuint64_t dims[2] = {(cuuint64_t)DM, (cuuint64_t)MEMT};
        const cuuint64_t strides[1] = {(cuuint64_t)DM * 2};
        const cuuint32_t box[2] = {64, (cuuint32_t)MEMT};
        const cuuint32_t es[2] = {1, 1};
        enc(&tmm, CU_TENSOR_MAP_DATA_TYPE_BFLOAT16, 2, (void*)mem0, dims, strides, box, es, CU_TENSOR_MAP_INTERLEAVE_NONE,
            CU_TENSOR_MAP_SWIZZLE_128B, CU_TENSOR_MAP_L2_PROMOTION_L2_128B, CU_TENSOR_MAP_FLOAT_OOB_FILL_NONE);
    }
    k_chain<<<NCTA, 384, 232448>>>(tmw[0], tmw[1], tmw[2], tmx2, tmo, tmm, x);
    {
        cudaLaunchConfig_t cfg = {};
        cfg.gridDim = dim3(SD_NCTA); cfg.blockDim = dim3(512); cfg.dynamicSmemBytes = SIDE_SMEM; cfg.stream = cudaStreamPerThread;
        cudaLaunchAttribute at[1];
        at[0].id = cudaLaunchAttributeProgrammaticStreamSerialization;
        at[0].val.programmaticStreamSerializationAllowed = 1;
        cfg.attrs = at; cfg.numAttrs = 1;
        cudaLaunchKernelEx(&cfg, k_side, tmo, x, logA, Aim, Cre, Cim, logdt, Wo, dskip, gw, out);
    }
}
```

```cpp
#include <cuda_runtime.h>
#include <cuda.h>
#include <cuda_bf16.h>
#include <stdint.h>

typedef __nv_bfloat16 bf16;
#define LDV4 "ld.volatile.global.v4.u32 {%0,%1,%2,%3}, [%4];"
#define STV4 "st.volatile.global.v4.u32 [%0], {%1,%2,%3,%4};"
#define STV2 "st.volatile.global.v2.u32 [%0], {%1,%2};"

constexpr int S_LEN = 2048, DM = 576, NH = 32, DH = 128, HD = 4096, MEMT = 8, SEG = 32, NSEG = 64, NST = 128;

__device__ __align__(128) bf16 g_gate[S_LEN];
constexpr int NCTA = NH * 3;
__device__ __align__(1024) unsigned char g_acc[96 * 1024];
__device__ __align__(128) uint2 g_norm[NCTA];
__device__ __align__(128) uint4 g_wv[NH][2];
__device__ __align__(128) uint4 g_rx[NSEG][2];
__device__ __align__(128) unsigned char g_qkv[NSEG][NH][3][10240];
__device__ __align__(128) bf16 g_ox[S_LEN * HD];
__device__ __align__(128) uint4 g_fp[8][36][6][128];
__device__ __align__(128) unsigned g_flag[NH * NSEG];
__device__ __align__(128) unsigned g_prog[8 * 64];
__device__ unsigned g_gcnt[64];
__device__ unsigned g_epoch;
__device__ __align__(128) uint2 g_tick;
__device__ __align__(128) bf16 g_y[DM * S_LEN];

#define TS3(slot) do {} while (0)
#define TS3P(slot) do {} while (0)
#define TSQ(slot) do {} while (0)
#define TS3W(slot) do {} while (0)
#define TSS(row, slot) do {} while (0)
#define TS3C(slot) do {} while (0)
#define TST(slot) do {} while (0)
#define TSA(seg, slot) do {} while (0)
#define TSG(i) do {} while (0)
#define FS(i, dep) do {} while (0)
__device__ __forceinline__ uint32_t smem_u32(const void* p) { return (uint32_t)__cvta_generic_to_shared(p); }
__device__ __forceinline__ float bf16r(float x) { return __bfloat162float(__float2bfloat16_rn(x)); }
__device__ __forceinline__ uint32_t pack_bf16(float lo, float hi) {
    __nv_bfloat162 v = __floats2bfloat162_rn(lo, hi);
    return *reinterpret_cast<uint32_t*>(&v);
}
__device__ __forceinline__ void ldsm_x4(uint32_t (&r)[4], uint32_t addr) {
    asm volatile("ldmatrix.sync.aligned.m8n8.x4.shared.b16 {%0,%1,%2,%3}, [%4];"
                 : "=r"(r[0]), "=r"(r[1]), "=r"(r[2]), "=r"(r[3]) : "r"(addr));
}
__device__ __forceinline__ void ldsm_x4_t(uint32_t (&r)[4], uint32_t addr) {
    asm volatile("ldmatrix.sync.aligned.m8n8.x4.trans.shared.b16 {%0,%1,%2,%3}, [%4];"
                 : "=r"(r[0]), "=r"(r[1]), "=r"(r[2]), "=r"(r[3]) : "r"(addr));
}
__device__ __forceinline__ void mma_bf16(float (&d)[4], const uint32_t (&a)[4], uint32_t b0, uint32_t b1) {
    asm volatile("mma.sync.aligned.m16n8k16.row.col.f32.bf16.bf16.f32 {%0,%1,%2,%3}, {%4,%5,%6,%7}, {%8,%9}, {%0,%1,%2,%3};"
                 : "+f"(d[0]), "+f"(d[1]), "+f"(d[2]), "+f"(d[3])
                 : "r"(a[0]), "r"(a[1]), "r"(a[2]), "r"(a[3]), "r"(b0), "r"(b1));
}
__device__ __forceinline__ uint2 ld_vol_u2(const uint2* p) {
    uint2 v; asm volatile("ld.volatile.global.v2.u32 {%0,%1}, [%2];" : "=r"(v.x), "=r"(v.y) : "l"(p) : "memory"); return v;
}
__device__ __forceinline__ void st_vol_u2(uint2* p, uint2 v) {
    asm volatile(STV2 :: "l"(p), "r"(v.x), "r"(v.y) : "memory");
}
__device__ __forceinline__ unsigned ld_acq(const unsigned* p) {
    unsigned v; asm volatile("ld.acquire.gpu.global.u32 %0, [%1];" : "=r"(v) : "l"(p) : "memory"); return v;
}
#define NS 10
#define NP 4
#define GATE_A 1030
#define GATE_B 380
#define GATE_P 1880u
#define RLX_SLEEP 300
#define VX_DELAY 100
#define UNGATE_G 3
#define W14_SLEEP 60
#define GL_A 1150
#define GL_B 530
#define GS_A 1300
#define GS_B 480
#define NC1 3
#define NC1C 5
#define KPRE 34
#define PADC 0
#define PAD1 0
#define PAD2 0
#define PAD3 0
#define PAD4 0
#define KG1 20
#define WO_SLEEP 300
#define WO_LAG 700
#define TM 29
#define TM2 (TM - 1)
#define TL_DELAY 600
#define POLL_DELAY 590
#define UNGATE 6
constexpr unsigned SPIN_LIMIT = 1u << 20;
constexpr int NATT = NSEG - 2;

constexpr int SD_CH = 16;
constexpr int SD_NCTA = DM / SD_CH;
constexpr int SD_ROW = 528;
constexpr int SD_U = 8 * SD_ROW;
constexpr int SD_TAP = 5888;
constexpr int SD_CPY = 1376 * 2;
constexpr int SD_WSTR = SD_TAP + 2 * SD_CPY;
constexpr int SD_SMEM = SD_CH * SD_U + 8 * SD_WSTR;
constexpr int O_U = 79, O_U3 = 911, O_U4 = 1055, O_W79 = 1023, O_W35 = 1151, O_W610 = 1279, O_W511 = 1487;

__device__ __forceinline__ uint32_t lds32(uint32_t a) { uint32_t v; asm volatile("ld.shared.u32 %0, [%1];" : "=r"(v) : "r"(a)); return v; }
__device__ __forceinline__ void sts32(uint32_t a, uint32_t v) { asm volatile("st.shared.u32 [%0], %1;" :: "r"(a), "r"(v) : "memory"); }
__device__ __forceinline__ uint4 lds128(uint32_t a) {
    uint4 v; asm volatile("ld.shared.v4.u32 {%0,%1,%2,%3}, [%4];" : "=r"(v.x), "=r"(v.y), "=r"(v.z), "=r"(v.w) : "r"(a) : "memory"); return v;
}
__device__ __forceinline__ void tap_tile(uint32_t (&t)[4], uint32_t a) {
    asm volatile("ld.volatile.shared.u32 %0, [%4];\nld.volatile.shared.u32 %1, [%4+-16];\nld.volatile.shared.u32 %2, [%4+16];\nld.volatile.shared.u32 %3, [%4];"
                 : "=r"(t[0]), "=r"(t[1]), "=r"(t[2]), "=r"(t[3]) : "r"(a));
}
constexpr uint32_t sd_pass(int type, int dl, int o, int d0, int d1) { return (uint32_t)(type | dl << 2 | d0 << 8 | d1 << 12 | o << 17); }
__constant__ uint32_t SD_PASS[14] = {sd_pass(0, 0, O_U, 0, 2), sd_pass(0, 1, O_U + 96, 0, 2), sd_pass(0, 2, O_U + 192, 0, 4), sd_pass(0, 3, O_U + 288, 0, 2), sd_pass(1, 0, O_U3, 8, 8),
                                     sd_pass(0, 4, O_U + 384, 0, 2), sd_pass(1, 0, O_U4, 8, 15), sd_pass(0, 5, O_U + 480, 0, 2), sd_pass(0, 6, O_U + 576, 0, 4), sd_pass(0, 7, O_U + 672, 0, 2),
                                     sd_pass(2, 0, O_W35, 2, 8), sd_pass(3, 0, O_W79, 2, 4), sd_pass(2, 1, O_W610, 4, 8), sd_pass(3, 0, O_W511, 8, 15)};
__device__ __forceinline__ uint32_t band2(int x, int lo, int hi) { return (x >= lo && x <= hi ? 0x3f80u : 0u) | (x + 1 >= lo && x + 1 <= hi ? 0x3f800000u : 0u); }
__device__ __forceinline__ void mma_z(float (&d)[4], const uint32_t (&a)[4], uint32_t b0, uint32_t b1);
__device__ __forceinline__ void put_tap(uint32_t a, float v) {
    asm volatile("{\n.reg .b16 h;\ncvt.rn.bf16.f32 h, %1;\nst.shared.b16 [%0], h;\nst.shared.b16 [%0+%2], h;\n}" :: "r"(a), "f"(v), "n"(SD_CPY - 2) : "memory");
}

__device__ __forceinline__ void named_bar(int id, int n) { asm volatile("bar.sync %0, %1;" :: "r"(id), "r"(n) : "memory"); }
__device__ __forceinline__ uint32_t pack_f16(float lo, float hi) {
    uint32_t r; asm("cvt.rn.f16x2.f32 %0, %1, %2;" : "=r"(r) : "f"(hi), "f"(lo)); return r;
}
__device__ __forceinline__ void cexp_t(float lr, float turns, float& re, float& im) {
    float m;
    asm("ex2.approx.ftz.f32 %0, %1;" : "=f"(m) : "f"(lr));
    const float a = (turns - rintf(turns)) * 6.283185307179586f;
    re = m * __cosf(a); im = m * __sinf(a);
}
__device__ __forceinline__ void csq(float& re, float& im) { const float r = re * re - im * im; im = 2.f * re * im; re = r; }
__device__ __forceinline__ void kb_state(const float* tp, float gf, uint32_t (&a)[4][2], uint32_t (&b)[5]) {
    const float4 p0 = *reinterpret_cast<const float4*>(tp), p1 = *reinterpret_cast<const float4*>(tp + 4);
    float wr, wi;
    cexp_t(p0.x * gf, p0.y * gf, wr, wi);
    float vr = wr * p1.x - wi * p1.y, vi = wr * p1.y + wi * p1.x;
#pragma unroll
    for (int c = 0; c < 4; c++) {
        a[c][0] = pack_f16(wr, wi); a[c][1] = pack_f16(vr, vi);
        csq(wr, wi);
        if (c < 3) csq(vr, vi);
    }
    b[0] = pack_f16(p0.z * wr - p0.w * wi, -p0.z * wi - p0.w * wr);
    float er = wr * p1.z - wi * p1.w, ei = wr * p1.w + wi * p1.z;
#pragma unroll
    for (int c = 0; c < 4; c++) {
        b[1 + c] = pack_f16(p0.z * er - p0.w * ei, -p0.z * ei - p0.w * er);
        if (c < 3) csq(er, ei);
    }
}
__device__ __forceinline__ uint32_t bf2_mul(uint32_t a, uint32_t b) { uint32_t r; asm("mul.rn.bf16x2 %0, %1, %2;" : "=r"(r) : "r"(a), "r"(b)); return r; }
__device__ __forceinline__ uint32_t bf2_add(uint32_t a, uint32_t b) { uint32_t r; asm("add.rn.bf16x2 %0, %1, %2;" : "=r"(r) : "r"(a), "r"(b)); return r; }
__device__ __forceinline__ uint32_t bf2_sub(uint32_t a, uint32_t b) { uint32_t r; asm("sub.rn.bf16x2 %0, %1, %2;" : "=r"(r) : "r"(a), "r"(b)); return r; }
__device__ __forceinline__ void wait_cnt(const unsigned* p, unsigned target) {
    unsigned it = 0;
    while ((int)(ld_acq(p) - target) < 0 && ++it < SPIN_LIMIT) __nanosleep(64);
}
__device__ __forceinline__ uint32_t gtime32() { uint32_t t; asm volatile("mov.u32 %0, %%globaltimer_lo;" : "=r"(t) :: "memory"); return t; }
__device__ __forceinline__ void gate(uint32_t tick_addr, uint32_t ga = GATE_A, uint32_t gb = GATE_B) {
    uint32_t t1, p;
    asm volatile("ld.volatile.shared.v2.u32 {%0,%1}, [%2];" : "=r"(t1), "=r"(p) : "r"(tick_addr) : "memory");
    uint32_t d = gtime32() - t1;
    if (d < 4u * p) {
        d -= d >= 2u * p ? 2u * p : 0u;
        d -= d >= p ? p : 0u;
        if (d + ga >= p && d + gb < p) {
            const uint32_t t2 = gtime32() + (p - gb - d);
            while ((int)(gtime32() - t2) < 0) {}
        }
    }
}

__device__ __forceinline__ void read_tick(uint32_t tick_addr) {
    const uint2 tk = ld_vol_u2(&g_tick);
    uint32_t p = tk.x - tk.y;
    p = p > GATE_P + 100u ? GATE_P + 100u : p;
    asm volatile("st.volatile.shared.v2.u32 [%0], {%1,%2};" :: "r"(tick_addr), "r"(tk.x), "r"(p) : "memory");
}

__device__ __forceinline__ void s4d_phase(unsigned char* smem_raw, const bf16* __restrict__ x, const bf16* __restrict__ logA,
                                          const bf16* __restrict__ Aim, const bf16* __restrict__ Cre, const bf16* __restrict__ Cim,
                                          const bf16* __restrict__ logdt, const bf16* __restrict__ dskip, const bf16* __restrict__ wslice) {
    const int tid = threadIdx.x, warp = __shfl_sync(0xffffffffu, tid >> 5, 0), lane = tid & 31;
    const int d0 = blockIdx.x * SD_CH;
    float* tab = reinterpret_cast<float*>(smem_raw + SD_CH * SD_U + warp * SD_WSTR);
    const uint32_t wb = smem_u32(tab);
    const int g = lane >> 2, tq = lane & 3;
    uint2 prm[4];
    float ldt;
    auto load_prm = [&](int d) {
        prm[0] = __ldg(reinterpret_cast<const uint2*>(logA + d * NST) + lane); prm[1] = __ldg(reinterpret_cast<const uint2*>(Aim + d * NST) + lane);
        prm[2] = __ldg(reinterpret_cast<const uint2*>(Cre + d * NST) + lane); prm[3] = __ldg(reinterpret_cast<const uint2*>(Cim + d * NST) + lane);
        ldt = __bfloat162float(logdt[d]);
    };
    load_prm(d0 + warp);
    for (int i = lane; i < 2 * SD_CPY / 16; i += 32) reinterpret_cast<uint4*>(tab + SD_TAP / 4)[i] = make_uint4(0u, 0u, 0u, 0u);
    TS3(20);
#pragma unroll 1
    for (int ch = 0; ch < 2; ch++) {
        const int d = d0 + 8 * ch + warp;
        const uint32_t ub = smem_u32(smem_raw) + (8 * ch + warp) * SD_U;
        float k2048 = 0.f, sinv;
        {
            const float dt = bf16r(expf(ldt));
            uint32_t cm = __vmaxu2(__vmaxu2(prm[2].x & 0x7fff7fffu, prm[2].y & 0x7fff7fffu), __vmaxu2(prm[3].x & 0x7fff7fffu, prm[3].y & 0x7fff7fffu));
            cm = __reduce_max_sync(0xffffffffu, max(cm << 16, cm & 0xffff0000u));
            int e = 134 - (int)(__float_as_uint(__uint_as_float(cm) * dt) >> 23);
            e = e > 100 ? 100 : (e < -100 ? -100 : e);
            const float s2 = __uint_as_float((uint32_t)(128 + e) << 23);
            sinv = __uint_as_float((uint32_t)(127 - e) << 23);
#pragma unroll
            for (int j = 0; j < 4; j++) {
                float q[4];
#pragma unroll
                for (int i = 0; i < 4; i++) { const uint32_t w = j < 2 ? prm[i].x : prm[i].y; q[i] = __uint_as_float((j & 1) ? w & 0xffff0000u : w << 16); }
                const float zl = -bf16r(expf(q[0])) * dt * 1.4426950408889634f;
                const float zt = q[1] * dt * 0.15915494309189535f;
                const float cr = s2 * (q[2] * dt), ci = s2 * (q[3] * dt);
                float ar, ai, br, bi, er, ei;
                cexp_t(zl * 8.f, zt * 8.f, ar, ai);
                cexp_t(zl * 128.f, zt * 128.f, br, bi);
                cexp_t(zl * 2048.f, zt * 2048.f, er, ei);
                k2048 += cr * er - ci * ei;
                *reinterpret_cast<float4*>(tab + (lane + 32 * j) * 8) = make_float4(zl, zt, cr, ci);
                *reinterpret_cast<float4*>(tab + (lane + 32 * j) * 8 + 4) = make_float4(ar, ai, br, bi);
            }
#pragma unroll
            for (int o = 16; o; o >>= 1) k2048 += __shfl_xor_sync(0xffffffffu, k2048, o);
        }
        __syncwarp();
        {
            float kc[5][4];
#pragma unroll
            for (int i = 0; i < 5; i++) { kc[i][0] = kc[i][1] = kc[i][2] = kc[i][3] = 0.f; }
            const float gf = (float)g;
#pragma unroll 2
            for (int ks = 0; ks < 16; ks++) {
                uint32_t a0[4][2], a1[4][2], b0[5], b1[5];
                kb_state(tab + (8 * ks + tq) * 8, gf, a0, b0);
                kb_state(tab + (8 * ks + 4 + tq) * 8, gf, a1, b1);
#pragma unroll
                for (int i = 0; i < 5; i++) {
                    const int c = i > 0 ? i - 1 : 0;
                    asm volatile("mma.sync.aligned.m16n8k16.row.col.f32.f16.f16.f32 {%0,%1,%2,%3}, {%4,%5,%6,%7}, {%8,%9}, {%0,%1,%2,%3};"
                                 : "+f"(kc[i][0]), "+f"(kc[i][1]), "+f"(kc[i][2]), "+f"(kc[i][3])
                                 : "r"(a0[c][0]), "r"(a0[c][1]), "r"(a1[c][0]), "r"(a1[c][1]), "r"(b0[i]), "r"(b1[i]));
                }
            }
            const uint32_t tp = wb + SD_TAP;
            const uint32_t a0 = tp + 2 * (O_U + 96 * g - 4 * tq);
            const uint32_t a2 = tp + 2 * (((g & 1) ? O_U + 96 * (2 * (g & 3)) : ((g & 2) ? O_W35 : O_W79 + 1)) - 32 - 8 * tq - (g >> 2));
            const uint32_t a3 = tp + 2 * (((g & 1) ? O_W35 : O_W610 + 1) - 64 - 16 * tq - (g >> 1));
            const uint32_t a4 = tp + 2 * (-128 - 32 * tq - g);
#pragma unroll
            for (int c = 0; c < 4; c++) {
                const int e = (c & 1) * 16 + (c >> 1) * 8;
                const bool first = c == 0 && lane == 0;
                put_tap(a0 - e / 4, kc[0][c] * sinv);
                put_tap(a0 - 32 - e / 4, kc[1][c] * sinv);
                put_tap(first ? tp + 2 * (O_U - 32) : a2 - e / 2, kc[2][c] * sinv);
                put_tap(first ? tp + 2 * (O_W79 - 63) : a3 - e, kc[3][c] * sinv);
                put_tap(first ? tp + 2 * (O_W610 - 127) : a4 + 2 * (O_W511 + 1 - e), kc[4][c] * sinv);
                if ((g & 1) == 0) {
                    put_tap(a4 + 2 * (O_U4 - e), kc[4][c] * sinv);
                    put_tap(first ? tp + 2 * (O_U3 - 128) : a4 + 2 * (O_U4 + 1 - e), kc[4][c] * sinv);
                }
            }
            if (lane == 0) {
                put_tap(tp + 2 * (O_U + 96 - 32), kc[2][0] * sinv);
                put_tap(tp + 2 * (O_U + 192 - 64), kc[3][0] * sinv);
                put_tap(tp + 2 * (O_W511 - 255), k2048 * sinv);
                put_tap(tp + 2 * (O_U4 - 255), k2048 * sinv);
            }
        }
        TS3(21 + 2 * ch);
        if (ch == 0) named_bar(1, 384);
        else {
#pragma unroll
            for (int i = 0; i < 4; i++) asm volatile("prefetch.global.L2 [%0];" :: "l"(wslice + (size_t)((tid & 127) + 128 * i) * DM));
        }
        __syncwarp();
        if (tid == 0) TSS(18, 4 * ch);
        const uint32_t sh = wb + 80 + 11 * SD_ROW;
#pragma unroll
        for (int p = 0; p < 8; p++) {
            uint4 v;
            asm volatile("ld.shared.v4.u32 {%0,%1,%2,%3}, [%4];" : "=r"(v.x), "=r"(v.y), "=r"(v.z), "=r"(v.w) : "r"(ub + p * SD_ROW + lane * 16) : "memory");
            uint32_t pv = __shfl_up_sync(0xffffffffu, v.w, 1);
            pv = lane == 0 ? 0u : pv;
            asm volatile("st.shared.v4.u32 [%0], {%1,%2,%3,%4};" :: "r"(sh + (p - 8) * SD_ROW + lane * 16), "r"(__byte_perm(pv, v.x, 0x5432)), "r"(__byte_perm(v.x, v.y, 0x5432)),
                         "r"(__byte_perm(v.y, v.z, 0x5432)), "r"(__byte_perm(v.z, v.w, 0x5432)) : "memory");
            if (p >= 5) asm volatile("st.shared.v4.u32 [%0], {%1,%2,%3,%4};" :: "r"(sh + (p - 16) * SD_ROW + lane * 16), "r"(pv), "r"(v.x), "r"(v.y), "r"(v.z) : "memory");
        }
        __syncwarp();
        if (tid == 0) TSS(18, 4 * ch + 1);
        float acc[16][4];
#pragma unroll
        for (int i = 0; i < 16; i++) { acc[i][0] = acc[i][1] = acc[i][2] = acc[i][3] = 0.f; }
        {
            const uint32_t ka = wb + SD_TAP + ((g & 1) ? 0 : SD_CPY - 2) + 2 * (2 * tq - g);
            uint32_t b[16][2], b2[14][2];
#pragma unroll
            for (int k = 0; k < 16; k++) { b[k][0] = b[k][1] = 0u; if (k < 14) b2[k][0] = b2[k][1] = 0u; }
#pragma unroll 1
            for (int ps = 0; ps < 14; ps++) {
                const uint32_t pw = __shfl_sync(0xffffffffu, SD_PASS[ps], 0), type = pw & 3u, kp = ka + (pw >> 16);
                const int dl = (pw >> 2) & 7, d0 = (pw >> 8) & 15, d1 = (pw >> 12) & 15;
                uint32_t t[2][4];
                tap_tile(t[0], kp - 32 * d0);
                if (type == 0) {
                    const int p = (lane & 7) - dl;
                    const uint32_t ra = (p < 0 ? sh : ub) + p * SD_ROW + (lane >> 3) * 16;
#pragma unroll
                    for (int k = 0; k < 8; k++)
                        asm volatile("ldmatrix.sync.aligned.m8n8.x4.shared.b16 {%0,%1,%2,%3}, [%4];"
                                     : "=r"(b[2 * k][0]), "=r"(b[2 * k][1]), "=r"(b[2 * k + 1][0]), "=r"(b[2 * k + 1][1]) : "r"(ra + k * 64));
                } else if (type == 2) {
                    const int p = (lane & 15) - 11, xo = 2 * tq - g;
                    const uint32_t qa = (p < 0 ? sh : ub) + p * SD_ROW + (lane >> 4) * 16;
                    const int lx = 6 - 5 * dl, hx = 8 - 3 * dl, ly = 2 - 2 * dl, hy = 4 + 2 * dl;
                    const uint32_t sel[4] = {band2(xo, lx, hx), band2(xo, ly, hy), band2(xo + 8, lx, hx), band2(xo + 8, ly, hy)};
#pragma unroll
                    for (int k = 0; k < 14; k++) {
                        uint32_t q[4];
                        ldsm_x4_t(q, qa + k * 32);
#pragma unroll
                        for (int i = 0; i < 2; i++) {
                            float w[4];
                            mma_z(w, sel, q[2 * i], q[2 * i + 1]);
                            b[k][i] = pack_bf16(w[0], w[1]);
                            b2[k][i] = pack_bf16(w[2], w[3]);
                        }
                    }
                } else if (type == 3) {
#pragma unroll
                    for (int k = 0; k < 14; k++) { b[k][0] = b2[k][0]; b[k][1] = b2[k][1]; }
                }
#pragma unroll
                for (int d = 0; d < 16; d += 2) {
                    if (d >= 8 || d >= d0) {
                        tap_tile(t[1], kp - 32 * (d + 1));
#pragma unroll
                        for (int k = 0; k + d < 16; k++) mma_bf16(acc[k + d], t[0], b[k][0], b[k][1]);
                        if ((d == 2 || d == 4 || d == 8) && d == d1) break;
                        if (d < 14) tap_tile(t[0], kp - 32 * (d + 2));
#pragma unroll
                        for (int k = 0; k + d + 1 < 16; k++) mma_bf16(acc[k + d + 1], t[1], b[k][0], b[k][1]);
                    }
                }
            }
        }
        __syncwarp();
        if (tid == 0) TSS(18, 4 * ch + 2);
        load_prm(d0 + 8 + warp);
        if (ch == 0) {
            if (lane == 0) {
                unsigned ep;
                asm volatile("ld.volatile.global.u32 %0, [%1];" : "=r"(ep) : "l"(&g_epoch) : "memory");
                wait_cnt(&g_gcnt[0], SD_NCTA * (ep + 1u));
            }
            __syncwarp();
        }
        if (tid == 0) TSS(18, 4 * ch + 3);
        uint4 gv[8];
#pragma unroll
        for (int i = 0; i < 8; i++) gv[i] = __ldcg(reinterpret_cast<const uint4*>(g_gate) + lane + 32 * i);
        const uint32_t dd = __byte_perm(*reinterpret_cast<const unsigned short*>(dskip + d), 0u, 0x1010);
#pragma unroll
        for (int i = 0; i < 8; i++) {
            uint32_t u[4];
            ldsm_x4_t(u, ub + (lane & 7) * SD_ROW + (lane >> 3) * 16 + i * 64);
            asm volatile("stmatrix.sync.aligned.m8n8.x4.shared.b16 [%0], {%1,%2,%3,%4};"
                         :: "r"(wb + (lane + 32 * i) * 16),
                            "r"(bf2_add(pack_bf16(acc[2 * i][0], acc[2 * i][1]), bf2_mul(u[0], dd))), "r"(bf2_add(pack_bf16(acc[2 * i][2], acc[2 * i][3]), bf2_mul(u[1], dd))),
                            "r"(bf2_add(pack_bf16(acc[2 * i + 1][0], acc[2 * i + 1][1]), bf2_mul(u[2], dd))), "r"(bf2_add(pack_bf16(acc[2 * i + 1][2], acc[2 * i + 1][3]), bf2_mul(u[3], dd))) : "memory");
        }
        __syncwarp();
#pragma unroll
        for (int i = 0; i < 8; i++) {
            const uint4 y = *reinterpret_cast<const uint4*>(tab + (lane + 32 * i) * 4);
            *reinterpret_cast<uint4*>(g_y + (((lane >> 1) + 16 * i) * DM + d) * 16 + (lane & 1) * 8) =
                make_uint4(bf2_mul(bf2_sub(0x3f803f80u, gv[i].x), y.x), bf2_mul(bf2_sub(0x3f803f80u, gv[i].y), y.y),
                           bf2_mul(bf2_sub(0x3f803f80u, gv[i].z), y.z), bf2_mul(bf2_sub(0x3f803f80u, gv[i].w), y.w));
        }
        __syncwarp();
        if (ch == 0) asm volatile("bar.arrive 11, 288;" ::: "memory");
        TS3(22 + 2 * ch);
    }
}
__device__ __forceinline__ void s4d_stage_u(unsigned char* smem_raw, const bf16* __restrict__ x, int pt) {
    const int p = pt & 7, w0 = pt >> 3;
    const uint4* src = reinterpret_cast<const uint4*>(x + (size_t)(16 * w0 + p) * DM + blockIdx.x * SD_CH);
    uint32_t* dst = reinterpret_cast<uint32_t*>(smem_raw + p * SD_ROW) + w0;
#pragma unroll 1
    for (int b = 0; b < 4; b++) {
        uint4 v[2][2][2];
#pragma unroll
        for (int i = 0; i < 8; i++) v[i >> 2][(i >> 1) & 1][i & 1] = src[((b * 2 + (i >> 2)) * 256 + ((i >> 1) & 1) * 8) * (DM / 8) + (i & 1)];
#pragma unroll
        for (int i = 0; i < 4; i++) {
            const uint32_t* lo = reinterpret_cast<const uint32_t*>(&v[i >> 1][0][i & 1]);
            const uint32_t* hi = reinterpret_cast<const uint32_t*>(&v[i >> 1][1][i & 1]);
#pragma unroll
            for (int c = 0; c < 8; c++) dst[((i & 1) * 8 + c) * (SD_U / 4) + (b * 2 + (i >> 1)) * 16] = __byte_perm(lo[c >> 1], hi[c >> 1], (c & 1) ? 0x7632 : 0x5410);
        }
    }
    asm volatile("bar.arrive 1, 384;" ::: "memory");
}

constexpr int WOC = DM / 3;
constexpr int TBUF = 5 * DH * 16;
constexpr int XBUF = SEG * DM * 2;
constexpr int SM_BAR = 0;
constexpr int B_SB = 0, B_VX = 16, B_XT = 32, B_XF = 144, B_W = 64, B_E = 136;
constexpr int SM_SC = 256;
constexpr int SM_F = SM_SC + 1280;
constexpr int SM_VM = SM_F + 2048;
constexpr int SM_S = SM_VM + 2048;
constexpr int SM_O = SM_S + 2560;
constexpr int SM_M = SM_O + 2048;
constexpr int SM_WS = 19456;
constexpr int SM_T = SM_WS + 49152;
constexpr int SM_VX = SM_T + 4 * TBUF;
constexpr int SM_X = SM_VX + 2 * 8192;
constexpr int SM_X01 = SM_WS + DM * DH * 2;
__host__ __device__ constexpr int x01_off(int b) { return b < 2 ? 1024 + b * 9216 : SM_X01 + (b == 2 ? 6 : b - 3) * 9216; }
__host__ __device__ constexpr int x23_off(int b) { return b < 3 ? SM_WS + 7 * 16384 + b * 8192 : x01_off(b - 3); }
constexpr int CH_SMEM = SM_X01 + 8 * 8192;
static_assert(SM_M + DM * 16 <= SM_WS && SM_X + 13 * 8192 <= CH_SMEM && NS <= 10 && CH_SMEM <= 232448 && SM_X % 1024 == 0 && SM_X01 % 1024 == 0 && 1024 + 2 * 9216 <= SM_WS, "smem");
__device__ __forceinline__ uint32_t clock32() { uint32_t t; asm volatile("mov.u32 %0, %%clock;" : "=r"(t) :: "memory"); return t; }

__device__ __forceinline__ uint32_t mapa(uint32_t a, uint32_t rank) {
    uint32_t r; asm volatile("mapa.shared::cluster.u32 %0, %1, %2;" : "=r"(r) : "r"(a), "r"(rank)); return r;
}
__device__ __forceinline__ void st_async32(uint32_t addr, uint32_t v, uint32_t mbar) {
    asm volatile("st.async.weak.shared::cluster.mbarrier::complete_tx::bytes.b32 [%0], %1, [%2];" :: "r"(addr), "r"(v), "r"(mbar) : "memory");
}
__device__ __forceinline__ void mbar_init(uint32_t bar, uint32_t cnt) {
    asm volatile("mbarrier.init.shared::cta.b64 [%0], %1;" :: "r"(bar), "r"(cnt) : "memory");
}
__device__ __forceinline__ void mbar_expect(uint32_t bar, uint32_t bytes) {
    asm volatile("mbarrier.arrive.expect_tx.shared::cta.b64 _, [%0], %1;" :: "r"(bar), "r"(bytes) : "memory");
}
__device__ __forceinline__ void mbar_wait(uint32_t bar, uint32_t parity) {
    unsigned it = 0;
    uint32_t ok;
    do {
        ++it;
        asm volatile("{\n.reg .pred p;\nmbarrier.try_wait.parity.shared::cta.b64 p, [%1], %2;\nselp.u32 %0, 1, 0, p;\n}" : "=r"(ok) : "r"(bar), "r"(parity) : "memory");
    } while ((ok == 0u) & (it < SPIN_LIMIT));
}
__device__ __forceinline__ void mbar_wait_long(uint32_t bar, uint32_t parity) {
    unsigned it = 0;
    while (true) {
        uint32_t ok;
        asm volatile("{\n.reg .pred p;\nmbarrier.try_wait.parity.shared::cta.b64 p, [%1], %2, %3;\nselp.u32 %0, 1, 0, p;\n}"
                     : "=r"(ok) : "r"(bar), "r"(parity), "r"(20000u) : "memory");
        if (ok || ++it >= SPIN_LIMIT) break;
    }
}
__device__ __forceinline__ bool mbar_test(uint32_t bar, uint32_t parity) {
    uint32_t ok;
    asm volatile("{\n.reg .pred p;\nmbarrier.test_wait.parity.shared::cta.b64 p, [%1], %2;\nselp.u32 %0, 1, 0, p;\n}" : "=r"(ok) : "r"(bar), "r"(parity) : "memory");
    return ok != 0u;
}
__device__ __forceinline__ uint64_t policy_evict_first() {
    uint64_t pol; asm volatile("createpolicy.fractional.L2::evict_first.b64 %0, 1.0;" : "=l"(pol)); return pol;
}
__device__ __forceinline__ void cluster_sync_all() {
    asm volatile("barrier.cluster.arrive.release.aligned;\nbarrier.cluster.wait.acquire.aligned;" ::: "memory");
}
__device__ __forceinline__ uint4 ld_vol_u4(const uint4* p) {
    uint4 v; asm volatile(LDV4 : "=r"(v.x), "=r"(v.y), "=r"(v.z), "=r"(v.w) : "l"(p) : "memory"); return v;
}
__device__ __forceinline__ void ld_vol_u4_p(uint4& v, const uint4* p, uint32_t pred) {
    asm volatile("{\n.reg .pred p;\nsetp.ne.u32 p, %5, 0;\n@p " LDV4 "\n}"
                 : "+r"(v.x), "+r"(v.y), "+r"(v.z), "+r"(v.w) : "l"(p), "r"(pred) : "memory");
}
__device__ __forceinline__ void st_vol_u4(uint4* p, uint4 v) {
    asm volatile(STV4 :: "l"(p), "r"(v.x), "r"(v.y), "r"(v.z), "r"(v.w) : "memory");
}
__device__ __forceinline__ void mma_bf16_r(float (&d)[4], uint32_t a0, uint32_t a1, uint32_t a2, uint32_t a3, uint32_t b0, uint32_t b1) {
    asm volatile("mma.sync.aligned.m16n8k16.row.col.f32.bf16.bf16.f32 {%0,%1,%2,%3}, {%4,%5,%6,%7}, {%8,%9}, {%0,%1,%2,%3};"
                 : "+f"(d[0]), "+f"(d[1]), "+f"(d[2]), "+f"(d[3])
                 : "r"(a0), "r"(a1), "r"(a2), "r"(a3), "r"(b0), "r"(b1));
}

__device__ __forceinline__ uint64_t smem_desc(uint32_t addr, uint32_t lbo, uint32_t sbo) {
    return (uint64_t)((addr & 0x3FFFF) >> 4) | ((uint64_t)(lbo >> 4) << 16) | ((uint64_t)(sbo >> 4) << 32);
}
__device__ __forceinline__ void wg_fence() { asm volatile("wgmma.fence.sync.aligned;" ::: "memory"); }
__device__ __forceinline__ void wg_commit() { asm volatile("wgmma.commit_group.sync.aligned;" ::: "memory"); }
__device__ __forceinline__ void wg_wait0() { asm volatile("wgmma.wait_group.sync.aligned 0;" ::: "memory"); }
__device__ __forceinline__ void fence_async() { asm volatile("fence.proxy.async.shared::cta;" ::: "memory"); }
__device__ __forceinline__ void wgmma_n64_ss(float (&d)[32], uint64_t adesc, uint64_t bdesc) {
    asm volatile("{\n.reg .pred p;\nsetp.eq.b32 p, 0, 0;\n"
                 "wgmma.mma_async.sync.aligned.m64n64k16.f32.bf16.bf16 {%0,%1,%2,%3,%4,%5,%6,%7,%8,%9,%10,%11,%12,%13,%14,%15,%16,%17,%18,%19,%20,%21,%22,%23,%24,%25,%26,%27,%28,%29,%30,%31}, %32, %33, p, 1, 1, 1, 0;\n}"
                 : "+f"(d[0]), "+f"(d[1]), "+f"(d[2]), "+f"(d[3]), "+f"(d[4]), "+f"(d[5]), "+f"(d[6]), "+f"(d[7]), "+f"(d[8]), "+f"(d[9]), "+f"(d[10]), "+f"(d[11]), "+f"(d[12]), "+f"(d[13]), "+f"(d[14]), "+f"(d[15]), "+f"(d[16]), "+f"(d[17]), "+f"(d[18]), "+f"(d[19]), "+f"(d[20]), "+f"(d[21]), "+f"(d[22]), "+f"(d[23]), "+f"(d[24]), "+f"(d[25]), "+f"(d[26]), "+f"(d[27]), "+f"(d[28]), "+f"(d[29]), "+f"(d[30]), "+f"(d[31])
                 : "l"(adesc), "l"(bdesc));
}
__device__ __forceinline__ void wgmma_n72_ss(float (&d)[36], uint64_t adesc, uint64_t bdesc) {
    asm volatile("{\n.reg .pred p;\nsetp.eq.b32 p, 0, 0;\n"
                 "wgmma.mma_async.sync.aligned.m64n72k16.f32.bf16.bf16 {%0,%1,%2,%3,%4,%5,%6,%7,%8,%9,%10,%11,%12,%13,%14,%15,%16,%17,%18,%19,%20,%21,%22,%23,%24,%25,%26,%27,%28,%29,%30,%31,%32,%33,%34,%35}, %36, %37, p, 1, 1, 1, 0;\n}"
                 : "+f"(d[0]), "+f"(d[1]), "+f"(d[2]), "+f"(d[3]), "+f"(d[4]), "+f"(d[5]), "+f"(d[6]), "+f"(d[7]), "+f"(d[8]), "+f"(d[9]), "+f"(d[10]), "+f"(d[11]), "+f"(d[12]), "+f"(d[13]), "+f"(d[14]), "+f"(d[15]), "+f"(d[16]), "+f"(d[17]), "+f"(d[18]), "+f"(d[19]), "+f"(d[20]), "+f"(d[21]), "+f"(d[22]), "+f"(d[23]), "+f"(d[24]), "+f"(d[25]), "+f"(d[26]), "+f"(d[27]), "+f"(d[28]), "+f"(d[29]), "+f"(d[30]), "+f"(d[31]), "+f"(d[32]), "+f"(d[33]), "+f"(d[34]), "+f"(d[35])
                 : "l"(adesc), "l"(bdesc));
}
__device__ __forceinline__ void tma_2d(uint32_t dst, const CUtensorMap* tm, int c0, int c1, uint32_t mbar) {
    asm volatile("cp.async.bulk.tensor.2d.shared::cluster.global.tile.mbarrier::complete_tx::bytes [%0], [%1, {%2, %3}], [%4];"
                 :: "r"(dst), "l"(tm), "r"(c0), "r"(c1), "r"(mbar) : "memory");
}

__device__ __forceinline__ void bulk_g2s(uint32_t dst, const void* src, uint32_t bytes, uint32_t mbar) {
    asm volatile("cp.async.bulk.shared::cluster.global.mbarrier::complete_tx::bytes [%0], [%1], %2, [%3];"
                 :: "r"(dst), "l"(src), "r"(bytes), "r"(mbar) : "memory");
}
__device__ __forceinline__ void bulk_g2s_h(uint32_t dst, const void* src, uint32_t bytes, uint32_t mbar, uint64_t pol) {
    asm volatile("cp.async.bulk.shared::cluster.global.mbarrier::complete_tx::bytes.L2::cache_hint [%0], [%1], %2, [%3], %4;"
                 :: "r"(dst), "l"(src), "r"(bytes), "r"(mbar), "l"(pol) : "memory");
}
__device__ __forceinline__ void tma_2d_mc(uint32_t dst, const CUtensorMap* tm, int c0, int c1, uint32_t mbar) {
    asm volatile("cp.async.bulk.tensor.2d.shared::cluster.global.tile.mbarrier::complete_tx::bytes.multicast::cluster [%0], [%1, {%2, %3}], [%4], %5;"
                 :: "r"(dst), "l"(tm), "r"(c0), "r"(c1), "r"(mbar), "h"((unsigned short)7) : "memory");
}
__device__ __forceinline__ void bulk_s2s(uint32_t dst, uint32_t src, uint32_t bytes, uint32_t mbar) {
    asm volatile("cp.async.bulk.shared::cluster.shared::cta.mbarrier::complete_tx::bytes [%0], [%1], %2, [%3];"
                 :: "r"(dst), "r"(src), "r"(bytes), "r"(mbar) : "memory");
}
__device__ __forceinline__ void wgmma_n40_ss(float (&d)[20], uint64_t adesc, uint64_t bdesc, int scale_d) {
    asm volatile("{\n.reg .pred p;\nsetp.ne.b32 p, %22, 0;\n"
                 "wgmma.mma_async.sync.aligned.m64n40k16.f32.bf16.bf16 {%0,%1,%2,%3,%4,%5,%6,%7,%8,%9,%10,%11,%12,%13,%14,%15,%16,%17,%18,%19}, %20, %21, p, 1, 1, 1, 1;\n}"
                 : "+f"(d[0]), "+f"(d[1]), "+f"(d[2]), "+f"(d[3]), "+f"(d[4]), "+f"(d[5]), "+f"(d[6]), "+f"(d[7]),
                   "+f"(d[8]), "+f"(d[9]), "+f"(d[10]), "+f"(d[11]), "+f"(d[12]), "+f"(d[13]), "+f"(d[14]), "+f"(d[15]),
                   "+f"(d[16]), "+f"(d[17]), "+f"(d[18]), "+f"(d[19])
                 : "l"(adesc), "l"(bdesc), "r"(scale_d));
}
__device__ __forceinline__ void wgmma_n64_z(float (&d)[32], const uint32_t (&a)[4], uint64_t bdesc) {
    asm volatile("{\n.reg .pred p;\nsetp.ne.b32 p, 0, 0;\n"
                 "wgmma.mma_async.sync.aligned.m64n64k16.f32.bf16.bf16 {%0,%1,%2,%3,%4,%5,%6,%7,%8,%9,%10,%11,%12,%13,%14,%15,%16,%17,%18,%19,%20,%21,%22,%23,%24,%25,%26,%27,%28,%29,%30,%31}, {%32,%33,%34,%35}, %36, p, 1, 1, 0;\n}"
                 : "=f"(d[0]), "=f"(d[1]), "=f"(d[2]), "=f"(d[3]), "=f"(d[4]), "=f"(d[5]), "=f"(d[6]), "=f"(d[7]),
                   "=f"(d[8]), "=f"(d[9]), "=f"(d[10]), "=f"(d[11]), "=f"(d[12]), "=f"(d[13]), "=f"(d[14]), "=f"(d[15]),
                   "=f"(d[16]), "=f"(d[17]), "=f"(d[18]), "=f"(d[19]), "=f"(d[20]), "=f"(d[21]), "=f"(d[22]), "=f"(d[23]),
                   "=f"(d[24]), "=f"(d[25]), "=f"(d[26]), "=f"(d[27]), "=f"(d[28]), "=f"(d[29]), "=f"(d[30]), "=f"(d[31])
                 : "r"(a[0]), "r"(a[1]), "r"(a[2]), "r"(a[3]), "l"(bdesc));
}
__device__ __forceinline__ void wgmma_n64(float (&d)[32], const uint32_t (&a)[4], uint64_t bdesc, int scale_d) {
    asm volatile("{\n.reg .pred p;\nsetp.ne.b32 p, %37, 0;\n"
                 "wgmma.mma_async.sync.aligned.m64n64k16.f32.bf16.bf16 {%0,%1,%2,%3,%4,%5,%6,%7,%8,%9,%10,%11,%12,%13,%14,%15,%16,%17,%18,%19,%20,%21,%22,%23,%24,%25,%26,%27,%28,%29,%30,%31}, {%32,%33,%34,%35}, %36, p, 1, 1, 0;\n}"
                 : "+f"(d[0]), "+f"(d[1]), "+f"(d[2]), "+f"(d[3]), "+f"(d[4]), "+f"(d[5]), "+f"(d[6]), "+f"(d[7]),
                   "+f"(d[8]), "+f"(d[9]), "+f"(d[10]), "+f"(d[11]), "+f"(d[12]), "+f"(d[13]), "+f"(d[14]), "+f"(d[15]),
                   "+f"(d[16]), "+f"(d[17]), "+f"(d[18]), "+f"(d[19]), "+f"(d[20]), "+f"(d[21]), "+f"(d[22]), "+f"(d[23]),
                   "+f"(d[24]), "+f"(d[25]), "+f"(d[26]), "+f"(d[27]), "+f"(d[28]), "+f"(d[29]), "+f"(d[30]), "+f"(d[31])
                 : "r"(a[0]), "r"(a[1]), "r"(a[2]), "r"(a[3]), "l"(bdesc), "r"(scale_d));
}

constexpr int SB_FULL = 0, SB_EMPTY = 64, SB_QKF = 128, SB_VF = 144, SB_QKE = 160, SB_VE = 176, SB_OF = 192, SB_WO = 208  , SB_TICK = 216, SB_SEEN = 224, SB_FI = 232, SB_REQ = 240;
constexpr int AT_0 = 256, AT_ST = 10240 + 2 * 9216;
constexpr int FS_A = 58368;
constexpr int FS_P = FS_A + 131072;
constexpr int FS_I = FS_P + 16384;
constexpr int FS_O = FS_I + 12288;
constexpr int FS_Z = FS_O + 12288, FS_G = AT_0 + 2 * AT_ST;
constexpr int SIDE_SMEM = FS_Z + 2048;
static_assert(SIDE_SMEM <= 232448 && FS_G + 128 <= FS_A && FS_A + SD_SMEM <= SIDE_SMEM, "smem");

__device__ __forceinline__ void wg_wait1() { asm volatile("wgmma.wait_group.sync.aligned 1;" ::: "memory"); }
__device__ __forceinline__ void mbar_arrive(uint32_t bar) { asm volatile("mbarrier.arrive.shared::cta.b64 _, [%0];" :: "r"(bar) : "memory"); }
__device__ __forceinline__ void wait_cnt_rlx(const unsigned* p, unsigned target, bool urgent) {
    unsigned it = 0, v;
    while (true) {
        asm volatile("ld.relaxed.gpu.global.u32 %0, [%1];" : "=r"(v) : "l"(p) : "memory");
        if ((int)(v - target) >= 0 || ++it >= SPIN_LIMIT) break;
        if (!urgent) __nanosleep(RLX_SLEEP);
    }
}

__device__ __forceinline__ float xrow_softmax(float (&sc)[20], uint32_t (&p)[5], int wq, int lane) {
    constexpr float EC = (float)(1.4426950408889634 * 0.08838834764831845);
    const int lim = 8 * wq + (lane >> 2) - 2 * (lane & 3);
    float mx = fmaxf(sc[0], sc[1]);
#pragma unroll
    for (int j = 1; j < 5; j++) {
        sc[4 * j] = 8 * j - 8 > lim ? -INFINITY : sc[4 * j];
        sc[4 * j + 1] = 8 * j - 7 > lim ? -INFINITY : sc[4 * j + 1];
    }
    mx = fmaxf(fmaxf(mx, fmaxf(fmaxf(sc[4], sc[5]), fmaxf(sc[8], sc[9]))), fmaxf(fmaxf(sc[12], sc[13]), fmaxf(sc[16], sc[17])));
    {
        const float m1 = __shfl_xor_sync(0xffffffffu, mx, 1), m2 = __shfl_xor_sync(0xffffffffu, mx, 2), m3 = __shfl_xor_sync(0xffffffffu, mx, 3);
        mx = fmaxf(fmaxf(mx, m1), fmaxf(m2, m3));
    }
    float sum = 0.f;
#pragma unroll
    for (int j = 0; j < 5; j++) {
        float e0, e1;
        asm("ex2.approx.ftz.f32 %0, %1;" : "=f"(e0) : "f"((sc[4 * j] - mx) * EC));
        asm("ex2.approx.ftz.f32 %0, %1;" : "=f"(e1) : "f"((sc[4 * j + 1] - mx) * EC));
        p[j] = pack_bf16(e0, e1);
        sum += e0 + e1;
    }
    return sum;
}
__device__ __forceinline__ float xrow_inv(float sum) {
    sum += __shfl_xor_sync(0xffffffffu, sum, 1);
    sum += __shfl_xor_sync(0xffffffffu, sum, 2);
    float r;
    asm("rcp.approx.ftz.f32 %0, %1;" : "=f"(r) : "f"(sum));
    return r;
}

__device__ __forceinline__ void stsm_x4(uint32_t addr, uint32_t r0, uint32_t r1, uint32_t r2, uint32_t r3) {
    asm volatile("stmatrix.sync.aligned.m8n8.x4.shared.b16 [%0], {%1,%2,%3,%4};" :: "r"(addr), "r"(r0), "r"(r1), "r"(r2), "r"(r3) : "memory");
}
__device__ __forceinline__ void xrow_pv(uint32_t (&ob)[16], const uint32_t (&p)[5], float psum, uint32_t vt) {
    float o[32];
    const uint64_t dv = smem_desc(vt, 2048, 128);
    uint32_t pa[6][4];
#pragma unroll
    for (int i = 0; i < 6; i++) {
        const int ks = i >> 1, hf = i & 1;
        pa[i][hf] = p[2 * ks]; pa[i][hf ^ 1] = 0u;
        pa[i][2 + hf] = ks < 2 ? p[ks < 2 ? 2 * ks + 1 : 0] : 0u; pa[i][3 - hf] = 0u;
    }
    wg_fence();
#pragma unroll
    for (int i = 0; i < 6; i++) { if (i == 0) wgmma_n64_z(o, pa[0], dv); else wgmma_n64(o, pa[i], dv + (uint64_t)((i & 1) * 64 + (i >> 1) * 256), 1); }
    wg_commit();
    const float inv = xrow_inv(psum);
    wg_wait0();
#pragma unroll
    for (int i = 0; i < 8; i++) { ob[i] = pack_bf16(o[4 * i] * inv, o[4 * i + 1] * inv); ob[8 + i] = pack_bf16(o[4 * i + 2] * inv, o[4 * i + 3] * inv); }
}
__device__ __forceinline__ uint32_t h2_to_bf2(uint32_t h) {
    uint32_t r;
    asm("{\n.reg .f16 l, h;\n.reg .f32 a, b;\nmov.b32 {l, h}, %1;\ncvt.f32.f16 a, l;\ncvt.f32.f16 b, h;\ncvt.rn.bf16x2.f32 %0, b, a;\n}" : "=r"(r) : "r"(h));
    return r;
}
__device__ __forceinline__ uint32_t max_abs2(uint32_t a, uint32_t b) { uint32_t r; asm("max.NaN.xorsign.abs.bf16x2 %0, %1, %2;" : "=r"(r) : "r"(a), "r"(b)); return r; }
__device__ __forceinline__ uint32_t movm(uint32_t v) {
    uint32_t r; asm volatile("movmatrix.sync.aligned.m8n8.trans.b16 %0, %1;" : "=r"(r) : "r"(v)); return r;
}
__device__ __forceinline__ void bar_arrive(int id, int n) { asm volatile("bar.arrive %0, %1;" :: "r"(id), "r"(n) : "memory"); }
__device__ __forceinline__ void lds64(uint32_t& a, uint32_t& b, uint32_t addr) {
    asm volatile("ld.shared.v2.u32 {%0,%1}, [%2];" : "=r"(a), "=r"(b) : "r"(addr) : "memory");
}
__device__ __forceinline__ void lds64f(float& a, float& b, uint32_t addr) {
    asm volatile("ld.shared.v2.f32 {%0,%1}, [%2];" : "=f"(a), "=f"(b) : "r"(addr) : "memory");
}
__device__ __forceinline__ void st_async64(uint32_t addr, uint32_t a, uint32_t b, uint32_t mbar) {
    asm volatile("st.async.weak.shared::cluster.mbarrier::complete_tx::bytes.v2.b32 [%0], {%1,%2}, [%3];" :: "r"(addr), "r"(a), "r"(b), "r"(mbar) : "memory");
}
__device__ __forceinline__ void mma_z(float (&d)[4], const uint32_t (&a)[4], uint32_t b0, uint32_t b1) {
    asm volatile("mma.sync.aligned.m16n8k16.row.col.f32.bf16.bf16.f32 {%0,%1,%2,%3}, {%4,%5,%6,%7}, {%8,%9}, {%10,%10,%10,%10};"
                 : "=f"(d[0]), "=f"(d[1]), "=f"(d[2]), "=f"(d[3])
                 : "r"(a[0]), "r"(a[1]), "r"(a[2]), "r"(a[3]), "r"(b0), "r"(b1), "f"(0.f));
}
__device__ __forceinline__ void mma_k8(float (&d)[4], uint32_t a0, uint32_t a1, uint32_t b) {
    asm volatile("mma.sync.aligned.m16n8k8.row.col.f32.bf16.bf16.f32 {%0,%1,%2,%3}, {%4,%5}, {%6}, {%0,%1,%2,%3};"
                 : "+f"(d[0]), "+f"(d[1]), "+f"(d[2]), "+f"(d[3]) : "r"(a0), "r"(a1), "r"(b));
}
__global__ void __launch_bounds__(512, 1) k_side(const __grid_constant__ CUtensorMap tmo, const bf16* __restrict__ x, const bf16* __restrict__ logA, const bf16* __restrict__ Aim,
                                                 const bf16* __restrict__ Cre, const bf16* __restrict__ Cim, const bf16* __restrict__ logdt,
                                                 const bf16* __restrict__ Wo, const bf16* __restrict__ dskip, const bf16* __restrict__ gw,
                                                 bf16* __restrict__ out) {
    extern __shared__ __align__(1024) unsigned char smem_raw[];
    const uint32_t sbase = smem_u32(smem_raw);
    const int tid = threadIdx.x, warp = __shfl_sync(0xffffffffu, tid >> 5, 0), lane = tid & 31, cta = blockIdx.x;
    const int cb = cta >> 2, kq = cta & 3;
    if (tid == 0) {
        for (int i = 0; i < 8; i++) { mbar_init(sbase + SB_FULL + 8 * i, 1); mbar_init(sbase + SB_EMPTY + 8 * i, 4); }
        for (int i = 0; i < 2; i++) {
            mbar_init(sbase + SB_QKF + 8 * i, 1); mbar_init(sbase + SB_VF + 8 * i, 1); mbar_init(sbase + SB_QKE + 8 * i, 4);
            mbar_init(sbase + SB_VE + 8 * i, 1); mbar_init(sbase + SB_OF + 8 * i, 4);
        }
        mbar_init(sbase + SB_WO, 1);
        mbar_init(sbase + SB_WO + 40, 1);
        mbar_init(sbase + SB_FI, 1);
        mbar_init(sbase + SB_REQ, 4);
        *reinterpret_cast<uint2*>(smem_raw + SB_TICK) = make_uint2(0u, 0u);
        *reinterpret_cast<uint32_t*>(smem_raw + SB_SEEN) = 0u;
        asm volatile("fence.mbarrier_init.release.cluster;" ::: "memory");
    }
    TS3(0);
    asm volatile("fence.proxy.async;" ::: "memory");
    __syncthreads();
    auto epoch = []() {
        unsigned ep;
        asm volatile("ld.volatile.global.u32 %0, [%1];" : "=r"(ep) : "l"(&g_epoch) : "memory");
        return ep + 1u;
    };
    if (warp >= 12) {
      asm volatile("setmaxnreg.dec.sync.aligned.u32 40;");
      {
        uint32_t gwv[9];
#pragma unroll
        for (int i = 0; i < 9; i++) gwv[i] = reinterpret_cast<const uint32_t*>(gw)[lane + 32 * i];
#pragma unroll 1
        for (int i = 0; i < 8; i++) {
            uint32_t xv[2][9];
            float sm[2];
#pragma unroll
            for (int j = 0; j < 2; j++) {
                const int t = min(cta * 57 + 8 * i + 4 * j + warp - 12, S_LEN - 1);
#pragma unroll
                for (int k = 0; k < 9; k++) xv[j][k] = reinterpret_cast<const uint32_t*>(x + t * DM)[lane + 32 * k];
            }
#pragma unroll
            for (int j = 0; j < 2; j++) {
                sm[j] = 0.f;
#pragma unroll
                for (int k = 0; k < 9; k++) {
                    const uint32_t pr = bf2_mul(xv[j][k], gwv[k]);
                    sm[j] += __uint_as_float(pr << 16) + __uint_as_float(pr & 0xffff0000u);
                }
            }
            float v = (lane < 16 ? sm[0] : sm[1]) + __shfl_xor_sync(0xffffffffu, lane < 16 ? sm[1] : sm[0], 16);
#pragma unroll
            for (int o = 8; o; o >>= 1) v += __shfl_xor_sync(0xffffffffu, v, o);
            const float gv = 1.f / (1.f + expf(-bf16r(v)));
            const int tt = 8 * i + 4 * (lane >> 4) + warp - 12;
            if ((lane & 15) == 0 && tt < 57 && cta * 57 + tt < S_LEN) g_gate[cta * 57 + tt] = __float2bfloat16_rn(gv);
        }
        named_bar(2, 128);
        if (tid == 480) {
            __threadfence();
            asm volatile("red.relaxed.gpu.global.add.u32 [%0], 1;" :: "l"(&g_gcnt[0]) : "memory");
        }
        __syncwarp();
      }
      const unsigned ep = epoch();
      if (warp == 12 || warp == 15) {
        const int pi = warp == 12 ? 0 : 1;
        auto stage_wo = [&](int i0, int i1) {
            if (lane == 0) {
                fence_async();
#pragma unroll 1
                for (int i = i0; i < i1; i++) {
                    gate(sbase + SB_TICK);
                    tma_2d(sbase + FS_A + i * 16384, &tmo, cb * 64, kq * 1024 + i * 128, sbase + SB_WO + (i >> 2) * 40);
                    if (WO_SLEEP > 0) __nanosleep(WO_SLEEP);
                }
            }
            __syncwarp();
        };
        if (lane == 0) mbar_expect(sbase + SB_WO + pi * 40, 65536);
        if (pi == 0) {
            named_bar(11, 288);
            stage_wo(0, 2);
        }
        named_bar(3, 320);
        if (pi == 0) stage_wo(2, 4);
        else {
            if (WO_LAG > 0) __nanosleep(WO_LAG);
            stage_wo(4, 8);
        }
        if (lane == 0) TSS(17, 2 + pi);
        if (tid == 480) {
            __threadfence();
            asm volatile("red.relaxed.gpu.global.add.u32 [%0], 1;" :: "l"(&g_gcnt[32]) : "memory");
        }
        __syncwarp();
        named_bar(12 + pi, 160);
        if (lane == 0) {
            const int kb = 2 * kq + pi;
            fence_async();
            for (int pr = 0; pr < NSEG / 2; pr++) {
                const bool gon = pr < NSEG / 2 - UNGATE_G;
                wait_cnt_rlx(&g_prog[kb * 64 + pr], 8u * ep, pr >= NSEG / 2 - 2);
                if (pi == 0) asm volatile("st.volatile.shared.u32 [%0], %1;" :: "r"(sbase + SB_SEEN), "r"(pr + 1) : "memory");
                if (pr >= 30 && pi == 0) TSS(4 + pr - 30, 0);
                if (pr == 31) TS3P(26);
                if (pr == 30) TS3P(1);
#pragma unroll
                for (int j = 0; j < 4; j++) {
                    const int st = 4 * pi + j;
                    mbar_wait_long(sbase + SB_EMPTY + 8 * st, ((uint32_t)pr & 1u) ^ 1u);
                    mbar_expect(sbase + SB_FULL + 8 * st, 16384);
                    if (gon) gate(sbase + SB_TICK);
                    bulk_g2s(sbase + FS_A + st * 16384, g_ox + ((size_t)(pr * NH + 4 * kb + j)) * 8192, 16384, sbase + SB_FULL + 8 * st);
                }
            }
        }
        __syncwarp();
      } else if (warp == 13) {
        if (lane == 0) {
            const uint64_t pol = policy_evict_first();
            bool next_ok = false;
            for (int seg = 0; seg < NATT; seg++) {
                const uint32_t st = seg & 1, ph = (uint32_t)(seg >> 1) & 1u, ab = sbase + AT_0 + st * AT_ST;
                if (!next_ok) {
                    const unsigned* fp = &g_flag[(cta & (NH - 1)) * NSEG + seg];
                    unsigned it = 0, v0, v1;
                    while (true) {
                        asm volatile("ld.relaxed.gpu.global.u32 %0, [%1];" : "=r"(v0) : "l"(fp) : "memory");
                        asm volatile("ld.relaxed.gpu.global.u32 %0, [%1+4];" : "=r"(v1) : "l"(fp) : "memory");
                        read_tick(sbase + SB_TICK);
                        if ((int)(v0 - 3u * ep) >= 0 || ++it >= SPIN_LIMIT) break;
                        if (seg < NSEG - UNGATE || cta >= NH) __nanosleep(RLX_SLEEP);
                    }
                    next_ok = (int)(v1 - 3u * ep) >= 0;
                } else next_ok = false;
                if (cta < NH) {
                    TSA(seg, 0);
                    mbar_wait_long(sbase + SB_QKE + 8 * st, ph ^ 1u);
                    TSA(seg, 1);
                    mbar_expect(sbase + SB_QKF + 8 * st, 2 * 9216);
                    if (seg < NSEG - UNGATE) gate(sbase + SB_TICK, GL_A, GL_B);
                    TSA(seg, 2);
                    bulk_g2s_h(ab + 10240, &g_qkv[seg][cta][0][1024], 9216, sbase + SB_QKF + 8 * st, pol);
                    bulk_g2s_h(ab + 10240 + 9216, &g_qkv[seg][cta][1][1024], 9216, sbase + SB_QKF + 8 * st, pol);
                    mbar_wait_long(sbase + SB_VE + 8 * st, ph ^ 1u);
                    mbar_expect(sbase + SB_VF + 8 * st, 10240);
                    if (seg < NSEG - UNGATE) gate(sbase + SB_TICK, GL_A, GL_B);
                    TSA(seg, 3);
                    bulk_g2s_h(ab, &g_qkv[seg][cta][2][0], 10240, sbase + SB_VF + 8 * st, pol);
                }
            }
        }
        __syncwarp();
      } else if (warp == 14) {
        if (lane == 0) {
            int seg = cta < NH ? 0 : NATT, p = 0;
            unsigned it = 0;
            while ((seg < NATT || p < NSEG / 2 - 1) && ++it < 16 * SPIN_LIMIT) {
                if (p < NSEG / 2 - 1 && mbar_test(sbase + SB_REQ, (uint32_t)p & 1u)) {
                    if (p == 0) { wait_cnt(&g_gcnt[32], SD_NCTA * ep); asm volatile("fence.proxy.async;" ::: "memory"); }
                    mbar_expect(sbase + SB_FI, (p < NSEG / 2 - 2 ? 12288 : 2048 + 32) + 2048 + 32);
                    if (p < NSEG / 2 - UNGATE_G - 1) gate(sbase + SB_TICK);
                    if (p < NSEG / 2 - 2) bulk_g2s(sbase + FS_I, &g_fp[p & 7][cta][0][0], 12288, sbase + SB_FI);
                    else {
                        bulk_g2s(sbase + FS_I, g_y + ((p * 4 + 4 + kq) * DM + cb * 64) * 16, 2048, sbase + SB_FI);
                        bulk_g2s(sbase + FS_G + 32, g_gate + p * 64 + 64 + kq * 16, 32, sbase + SB_FI);
                    }
                    bulk_g2s(sbase + FS_Z, g_y + ((p * 4 + kq) * DM + cb * 64) * 16, 2048, sbase + SB_FI);
                    bulk_g2s(sbase + FS_G, g_gate + p * 64 + kq * 16, 32, sbase + SB_FI);
                    p++;
                } else if (seg < NATT && mbar_test(sbase + SB_OF + 8 * (seg & 1), (uint32_t)(seg >> 1) & 1u)) {
                    const uint32_t st = seg & 1, ab = sbase + AT_0 + st * AT_ST;
                    TSA(seg, 5);
                    if (seg < NSEG - UNGATE) gate(sbase + SB_TICK, GS_A, GS_B);
                    TSA(seg, 6);
                    unsigned char* dst = reinterpret_cast<unsigned char*>(g_ox) + ((size_t)((seg >> 1) * NH + cta)) * 16384 + (seg & 1) * 8192;
                    asm volatile("cp.async.bulk.global.shared::cta.bulk_group [%0], [%1], 8192;" :: "l"(dst), "r"(ab) : "memory");
                    asm volatile("cp.async.bulk.commit_group;" ::: "memory");
                    asm volatile("cp.async.bulk.wait_group.read 0;" ::: "memory");
                    mbar_arrive(sbase + SB_VE + 8 * st);
                    asm volatile("cp.async.bulk.wait_group 0;" ::: "memory");
                    asm volatile("red.relaxed.gpu.global.add.u32 [%0], 1;" :: "l"(&g_prog[(cta >> 2) * 64 + (seg >> 1)]) : "memory");
                    TSA(seg, 7);
                    seg++;
                } else if (seg < NSEG - UNGATE) __nanosleep(W14_SLEEP);
            }
        }
        __syncwarp();
      }
    } else if (warp >= 8) {
        asm volatile("setmaxnreg.dec.sync.aligned.u32 88;");
          s4d_stage_u(smem_raw + FS_A, x, tid - 256);
        const int wq = warp - 8;
        for (int seg = 0; seg < (cta < NH ? NATT : 0); seg++) {
            const uint32_t st = seg & 1, ph = (uint32_t)(seg >> 1) & 1u, ab = sbase + AT_0 + st * AT_ST;
            float sc[20];
            if (seg < NSEG - UNGATE) mbar_wait_long(sbase + SB_QKF + 8 * st, ph); else mbar_wait(sbase + SB_QKF + 8 * st, ph);
            if (tid == 256) TSA(seg, 4);
            {
                const uint64_t da = smem_desc(ab + 10240 + 1024, 128, 1024), db = smem_desc(ab + 10240, 128, 2048);
                wg_fence();
#pragma unroll
                for (int ks = 0; ks < 8; ks++) wgmma_n40_ss(sc, da + (uint64_t)((ks >> 2) * 576 + (ks & 3) * 16), db + (uint64_t)((ks >> 2) * 576 + (ks & 3) * 16), ks > 0);
                wg_commit();
                wg_wait0();
            }
            if (lane == 0) mbar_arrive(sbase + SB_QKE + 8 * st);
            uint32_t p[5], ob[16];
            const float psum = xrow_softmax(sc, p, wq, lane);
            mbar_wait(sbase + SB_VF + 8 * st, ph);
            xrow_pv(ob, p, psum, ab);
            named_bar(6, 128);
#pragma unroll
            for (int i = 0; i < 4; i++) stsm_x4(ab + wq * 2048 + i * 512 + lane * 16, ob[4 * i], ob[4 * i + 1], ob[4 * i + 2], ob[4 * i + 3]);
            fence_async();
            __syncwarp();
            if (lane == 0) mbar_arrive(sbase + SB_OF + 8 * st);
        }
    } else {
        asm volatile("setmaxnreg.inc.sync.aligned.u32 192;");
        const int wg = warp >> 2, wq = warp & 3;
        s4d_phase(smem_raw + FS_A, x, logA, Aim, Cre, Cim, logdt, dskip, Wo + (size_t)((2 * kq + wg) * 512) * DM + cb * 64);
        TS3(2);
        if (lane == 0) TSS(16, warp);
        named_bar(3, 320);
        if (tid == 0) TSS(17, 0);
        uint32_t wa[32][4];
        mbar_wait_long(sbase + SB_WO + wg * 40, 0);
        if (tid == 0) TSS(17, 1);
        {
            const uint32_t a = sbase + FS_A + wg * 65536 + ((lane >> 4) * 8 + (lane & 7)) * 128 + (((wq * 2 + ((lane >> 3) & 1)) ^ (lane & 7)) << 4);
#pragma unroll
            for (int ks = 0; ks < 32; ks++) ldsm_x4_t(wa[ks], a + ks * 2048);
        }
        named_bar(12 + wg, 160);
        TS3(3);
        if (tid == 0) TSS(17, 4);
        auto product = [&](float (&acc)[32], int pr, const int wg) {
                if (pr + wg > 0) named_bar(4 + wg, 256);
                const uint64_t db = smem_desc(sbase + FS_A + wg * 65536, 128, 2048);
                TSG(0);
#pragma unroll
                for (int j = 0; j < 4; j++) {
                    mbar_wait(sbase + SB_FULL + 8 * (4 * wg + j), (uint32_t)pr & 1u);
                    if (j == 0) TSG(1);
                    if (j == 3) TSG(2);
                    wg_fence();
#pragma unroll
                    for (int ks = 0; ks < 8; ks++) {
                        if ((j | ks) == 0) wgmma_n64_z(acc, wa[0], db);
                        else wgmma_n64(acc, wa[8 * j + ks], db + (uint64_t)(j * 1024 + ks * 16), 1);
                    }
                    wg_commit();
                    if (j == 3 && pr + wg < NSEG / 2) bar_arrive(4 + (wg ^ 1), 256);
                    if (j > 0) { wg_wait1(); if (lane == 0) mbar_arrive(sbase + SB_EMPTY + 8 * (4 * wg + j - 1)); }
                }
                wg_wait0();
                if (pr == 31) TS3W(27);
                TSG(3);
                if (lane == 0) mbar_arrive(sbase + SB_EMPTY + 8 * (4 * wg + 3));
        };
        if (wg == 1) {
            for (int pr = 0; pr < NSEG / 2; pr++) {
                uint32_t t16 = (uint32_t)(wq * 32 + lane) * 16u;
                asm volatile("" : "+r"(t16));
                float acc[32];
                product(acc, pr, 1);
                    uint32_t tag = ((uint32_t)(pr >> 3) & 1u) ^ 1u;
                    tag = __shfl_sync(0xffffffffu, tag, lane);
                    named_bar(8, 256);
                    unsigned char* dst = reinterpret_cast<unsigned char*>(&g_fp[pr & 7][4 * cb][2 * kq - 2][0]) + t16;
                    const uint32_t own = sbase + FS_O + (pr % 3) * 4096 + t16;
#pragma unroll
                    for (int q = 0; q < 8; q++) {
                        float4 p;
                        asm volatile("ld.shared.v4.f32 {%0,%1,%2,%3}, [%4];" : "=f"(p.x), "=f"(p.y), "=f"(p.z), "=f"(p.w) : "r"(sbase + FS_P + t16 + q * 2048) : "memory");
                        acc[4 * q] = __uint_as_float((__float_as_uint(acc[4 * q] + p.x) & ~1u) | tag); acc[4 * q + 1] = __uint_as_float((__float_as_uint(acc[4 * q + 1] + p.y) & ~1u) | tag);
                        acc[4 * q + 2] = __uint_as_float((__float_as_uint(acc[4 * q + 2] + p.z) & ~1u) | tag); acc[4 * q + 3] = __uint_as_float((__float_as_uint(acc[4 * q + 3] + p.w) & ~1u) | tag);
                    }
#pragma unroll
                    for (int q = 0; q < 8; q++) {
                        asm volatile("{\n.reg .pred p;\nsetp.ne.s32 p, %5, %6;\n@p st.volatile.global.v4.f32 [%0], {%1,%2,%3,%4};\n@!p st.shared.v4.f32 [%7], {%1,%2,%3,%4};\n}"
                                     :: "l"(dst + (q & 1) * 2048), "f"(acc[4 * q]), "f"(acc[4 * q + 1]), "f"(acc[4 * q + 2]), "f"(acc[4 * q + 3]), "r"(q >> 1), "r"(kq),
                                        "r"(own + (q & 1) * 2048) : "memory");
                        if (q & 1) dst += (q >> 1) == kq ? 12288 + 4096 : 12288;
                    }
                    bar_arrive(9, 256);
                    if (pr == 31) TS3W(28);
                TSG(4);
            }
        } else {
          int nsync = 0;
          int np = 1, nf = 0, pr = 0, pf = -1;
          while (true) {
            uint32_t t16 = (uint32_t)(wq * 32 + lane) * 16u;
            asm volatile("" : "+r"(t16));
            if (pr < 0) {
                if (nsync <= pf) { named_bar(9, 256); nsync++; }
                if (lane == 0 && pf < NSEG / 2 - 1) mbar_arrive(sbase + SB_REQ);
            } else {
                float acc[32];
                product(acc, pr, 0);
                if (nsync < pr) { named_bar(9, 256); nsync++; }
#pragma unroll
                for (int q = 0; q < 8; q++)
                    asm volatile("st.shared.v4.f32 [%0], {%1,%2,%3,%4};" :: "r"(sbase + FS_P + t16 + q * 2048), "f"(acc[4 * q]), "f"(acc[4 * q + 1]), "f"(acc[4 * q + 2]), "f"(acc[4 * q + 3]) : "memory");
                bar_arrive(8, 256);
                TSG(4);
            }
            uint32_t w[4] = {0u, 0u, 0u, 0u};
            const int pc = pf;
            if (pf >= 0) {
                const uint32_t tag = ((uint32_t)(pf >> 3) & 1u) ^ 1u;
                uint4 v[8];
                unsigned n = 0;
                const bool last = pf == NSEG / 2 - 1;
                const uint4* src = reinterpret_cast<const uint4*>(reinterpret_cast<const unsigned char*>(&g_fp[pf & 7][cta][0][0]) + t16);
                if (pf >= NSEG / 2 - 2) {
#pragma unroll
                    for (int r = 0; r < 6; r++) v[r] = ld_vol_u4(src + r * 128);
                    mbar_wait(sbase + SB_FI, 0u);
                } else {
                    mbar_wait(sbase + SB_FI, (uint32_t)pf & 1u);
#pragma unroll
                    for (int r = 0; r < 6; r++)
                        asm volatile("ld.shared.v4.u32 {%0,%1,%2,%3}, [%4];" : "=r"(v[r].x), "=r"(v[r].y), "=r"(v[r].z), "=r"(v[r].w) : "r"(sbase + t16 + FS_I + r * 2048) : "memory");
                }
                while (true) {
                    uint32_t any = 0u;
#pragma unroll
                    for (int r = 0; r < 6; r++) {
                        uint32_t c0_, c1_;
                        asm("lop3.b32 %0, %1, %2, %3, 0x7e;" : "=r"(c0_) : "r"(v[r].x), "r"(v[r].y), "r"(tag));
                        asm("lop3.b32 %0, %1, %2, %3, 0x7e;" : "=r"(c1_) : "r"(v[r].z), "r"(v[r].w), "r"(tag));
                        asm("lop3.b32 %0, %1, %2, %3, 0xfe;" : "=r"(any) : "r"(any), "r"(c0_), "r"(c1_));
                    }
                    if (!__any_sync(0xffffffffu, (any & 1u) != 0u) || ++n >= SPIN_LIMIT) break;
                    if (pf < NSEG / 2 - 2) __nanosleep(200);
#pragma unroll
                    for (int r = 0; r < 6; r++) v[r] = ld_vol_u4(src + r * 128);
                }
                if (pf == 31) TS3(29);
                TSG(5);
#pragma unroll
                for (int r = 6; r < 8; r++)
                    asm volatile("ld.shared.v4.u32 {%0,%1,%2,%3}, [%4];" : "=r"(v[r].x), "=r"(v[r].y), "=r"(v[r].z), "=r"(v[r].w)
                                 : "r"(sbase + t16 + FS_O + (pf % 3) * 4096 + (r - 6) * 2048) : "memory");
                uint32_t zv[4], gg[2];
                ldsm_x4_t(zv, sbase + (last ? FS_I : FS_Z) + (wq * 16 + (lane & 15)) * 32 + (lane >> 4) * 16);
#pragma unroll
                for (int k = 0; k < 2; k++) gg[k] = __byte_perm(*reinterpret_cast<const volatile unsigned short*>(smem_raw + FS_G + (last ? 32 : 0) + k * 16 + (lane >> 2) * 2), 0u, 0x1010);
#define PQS(k, f) (((__uint_as_float(v[k].f) + __uint_as_float(v[2 + k].f)) + __uint_as_float(v[4 + k].f)) + __uint_as_float(v[6 + k].f))
#pragma unroll
                for (int k = 0; k < 2; k++) {
                    w[2 * k] = bf2_add(bf2_mul(gg[k], movm(pack_bf16(PQS(k, x), PQS(k, y)))), zv[2 * k]);
                    w[2 * k + 1] = bf2_add(bf2_mul(gg[k], movm(pack_bf16(PQS(k, z), PQS(k, w)))), zv[2 * k + 1]);
                }
#undef PQS
            }
            const bool more = nf < NSEG / 2;
            if (more) {
                uint32_t r;
                asm volatile("{\n.reg .pred p, q;\n.reg .b32 v;\nld.volatile.shared.u32 v, [%1];\nsetp.gt.s32 p, v, %2;\nbar.red.or.pred q, 10, 128, p;\nselp.u32 %0, 1, 0, q;\n}"
                             : "=r"(r) : "r"(sbase + SB_SEEN), "r"(np) : "memory");
                const bool dop = np < NSEG / 2 && (__shfl_sync(0xffffffffu, r, 0) != 0u || nf == np || (np >= TM && nf + 1 >= np));
                TSG(6);
                pr = dop ? np++ : -1;
                pf = !dop || nf + (pr >= TM2 ? 1 : 2) <= pr ? nf++ : -1;
                if (dop && pf >= 0 && lane == 0) mbar_arrive(sbase + SB_REQ);
            }
            if (pc >= 0) {
                unsigned char* op = reinterpret_cast<unsigned char*>(out) + (uint32_t)((pc * 64 + kq * 16 + (lane >> 2)) * DM + cb * 64 + wq * 16 + 2 * (lane & 3)) * 2u;
#pragma unroll
                for (int k = 0; k < 4; k++) *reinterpret_cast<uint32_t*>(op + (k >> 1) * (16 * DM) + (k & 1) * 16) = w[k];
                if ((pc & 1) == 0) TS3(4 + pc / 2);
                if (pc == 31) TS3(25);
            }
            if (!more) break;
          }
        }
        if (cta == 0 && tid == 0) asm volatile("red.relaxed.gpu.global.add.u32 [%0], 1;" :: "l"(&g_epoch) : "memory");
    }
    asm volatile("griddepcontrol.wait;" ::: "memory");
}

template <class F>
__device__ __forceinline__ uint32_t poll_mem(const uint4* src, uint32_t dst, uint32_t t0, F next) {
    uint4 v[6];
    unsigned it = 0;
#pragma unroll
    for (int j = 0; j < 6; j++) v[j] = make_uint4(0u, 0u, 0u, 0u);
    while (clock32() - t0 < POLL_DELAY) {}
    FS(12, 0);
    bool more;
#pragma unroll 1
    do {
        asm volatile("{\n.reg .pred p<6>;\n"
                     "setp.ne.u32 p0, %3, 0x5000;\nsetp.ne.u32 p1, %7, 0x5000;\nsetp.ne.u32 p2, %11, 0x5000;\n"
                     "setp.ne.u32 p3, %15, 0x5000;\nsetp.ne.u32 p4, %19, 0x5000;\nsetp.ne.u32 p5, %23, 0x5000;\n"
                     "@p0 ld.volatile.global.v4.u32 {%0,%1,%2,%3}, [%24];\n@p1 ld.volatile.global.v4.u32 {%4,%5,%6,%7}, [%24+4096];\n"
                     "@p2 ld.volatile.global.v4.u32 {%8,%9,%10,%11}, [%24+8192];\n@p3 ld.volatile.global.v4.u32 {%12,%13,%14,%15}, [%24+12288];\n"
                     "@p4 ld.volatile.global.v4.u32 {%16,%17,%18,%19}, [%24+16384];\n@p5 ld.volatile.global.v4.u32 {%20,%21,%22,%23}, [%24+20480];\n}"
                     : "+r"(v[0].x), "+r"(v[0].y), "+r"(v[0].z), "+r"(v[0].w), "+r"(v[1].x), "+r"(v[1].y), "+r"(v[1].z), "+r"(v[1].w),
                       "+r"(v[2].x), "+r"(v[2].y), "+r"(v[2].z), "+r"(v[2].w), "+r"(v[3].x), "+r"(v[3].y), "+r"(v[3].z), "+r"(v[3].w),
                       "+r"(v[4].x), "+r"(v[4].y), "+r"(v[4].z), "+r"(v[4].w), "+r"(v[5].x), "+r"(v[5].y), "+r"(v[5].z), "+r"(v[5].w)
                     : "l"(src) : "memory");
        stsm_x4(dst, h2_to_bf2(v[0].x), h2_to_bf2(v[0].y), h2_to_bf2(v[0].z), h2_to_bf2(v[1].x));
        stsm_x4(dst + 512, h2_to_bf2(v[1].y), h2_to_bf2(v[1].z), h2_to_bf2(v[2].x), h2_to_bf2(v[2].y));
        const uint32_t all = ((v[0].w & v[1].w) & (v[2].w & v[3].w)) & (v[4].w & v[5].w);
        more = __any_sync(0xffffffffu, (all & 0x5000u) != 0x5000u && ++it < SPIN_LIMIT);
        stsm_x4(dst + 1024, h2_to_bf2(v[2].z), h2_to_bf2(v[3].x), h2_to_bf2(v[3].y), h2_to_bf2(v[3].z));
        asm volatile("stmatrix.sync.aligned.m8n8.x2.shared.b16 [%0], {%1,%2};" :: "r"(dst + 1536), "r"(h2_to_bf2(v[4].x)), "r"(h2_to_bf2(v[4].y)) : "memory");
        stsm_x4(dst + 1792, h2_to_bf2(v[4].z), h2_to_bf2(v[5].x), h2_to_bf2(v[5].y), h2_to_bf2(v[5].z));
        asm volatile("{\n.reg .pred p;\nsetp.eq.u32 p, %0, 0;\n@p bar.sync 1, 384;\n}" :: "r"((uint32_t)more) : "memory");
    } while (more);
    next();
    FS(13, it);
    FS(14, 0);
    uint32_t m = v[0].x, m1 = v[0].y, m2 = v[0].z;
#pragma unroll
    for (int j = 1; j < 6; j++) {
        asm volatile("max.NaN.xorsign.abs.f16x2 %0, %0, %1;" : "+r"(m) : "r"(v[j].x));
        asm volatile("max.NaN.xorsign.abs.f16x2 %0, %0, %1;" : "+r"(m1) : "r"(v[j].y));
        asm volatile("max.NaN.xorsign.abs.f16x2 %0, %0, %1;" : "+r"(m2) : "r"(v[j].z));
    }
    asm volatile("max.NaN.xorsign.abs.f16x2 %0, %0, %1;" : "+r"(m) : "r"(m1));
    asm volatile("max.NaN.xorsign.abs.f16x2 %0, %0, %1;" : "+r"(m) : "r"(m2));
    return h2_to_bf2(m) & 0x7fff7fffu;
}

template <int N> __device__ __forceinline__ void pad_code() {
#pragma unroll
    for (int i = 0; i < N; i++) asm volatile("pmevent 7;" ::: "memory");
}
template <bool V> struct Flag { static constexpr bool value = V; };
__device__ __forceinline__ void score_group(const uint32_t (&a)[2][4], const uint32_t (&kf)[2][4], uint32_t d0, uint32_t d1, uint32_t m1, uint32_t d2, uint32_t m2) {
    FS(4, a[1][0]);
    float sc[4][4];
    mma_z(sc[0], a[0], kf[0][0], kf[0][1]);
    mma_z(sc[1], a[0], kf[0][2], kf[0][3]);
    mma_z(sc[2], a[1], kf[1][0], kf[1][1]);
    mma_z(sc[3], a[1], kf[1][2], kf[1][3]);
    constexpr float EC = (float)(1.4426950408889634 * 0.08838834764831845);
    const uint32_t v0 = __float_as_uint(fmaf(sc[3][2], EC, ((sc[0][0] + sc[1][2]) + sc[2][0]) * EC)), v1 = __float_as_uint(fmaf(sc[3][3], EC, ((sc[0][1] + sc[1][3]) + sc[2][1]) * EC));
    FS(5, v0);
    st_async64(d2, v0, v1, m2);
    st_async64(d1, v0, v1, m1);
    asm volatile("st.shared.v2.u32 [%0], {%1,%2};" :: "r"(d0), "r"(v0), "r"(v1) : "memory");
}
__device__ __forceinline__ void store_tile(int s, int h, int role, uint32_t tile, uint32_t b0, uint32_t b1) {
    asm volatile("cp.async.bulk.global.shared::cta.bulk_group.L2::cache_hint [%0], [%1], %2, %3;"
                 :: "l"(&g_qkv[s][h][role][b0]), "r"(tile + b0), "r"(b1 - b0), "l"(policy_evict_first()) : "memory");
}
__device__ __forceinline__ uint32_t w_addr(uint32_t sbase, int warp, int lane) {
    return sbase + SM_WS + (warp >> 2) * 8192 + ((lane & 7) + ((lane >> 4) & 1) * 8) * 128 + ((((warp & 3) * 2 + ((lane >> 3) & 1)) ^ (lane & 7)) << 4);
}
__device__ __forceinline__ void vx_copy(uint32_t sbase, int j, int r) {
    bulk_s2s(mapa(sbase + SM_VX + (j & 1) * 8192, r), sbase + SM_T + (j & 3) * TBUF + DH * 16, 8192, mapa(sbase + B_VX + 8 * (j & 1), r));
}
__device__ __forceinline__ float to_scale(float bound) {
    int e = 141 - (int)((__float_as_uint(bound) >> 23) & 255u);
    e = e > 100 ? 100 : e;
    return __uint_as_float((uint32_t)(127 + e) << 23);
}
__device__ __forceinline__ void norms_gather(int lane, uint32_t sbase) {
    uint2 v[3];
    uint4 w[2];
    unsigned it = 0;
#pragma unroll
    for (int i = 0; i < 3; i++) v[i] = make_uint2(0u, 0u);
    w[0] = w[1] = make_uint4(0u, 0u, 0u, 0u);
    bool more;
    do {
#pragma unroll
        for (int i = 0; i < 3; i++) if ((v[i].x & 1u) == 0u) v[i] = ld_vol_u2(&g_norm[3 * lane + i]);
#pragma unroll
        for (int i = 0; i < 2; i++) if ((w[i].x & w[i].y & w[i].z & w[i].w & 1u) == 0u) w[i] = ld_vol_u4(&g_wv[lane][i]);
        more = __any_sync(0xffffffffu, (v[0].x & v[1].x & v[2].x & w[0].x & w[0].y & w[0].z & w[0].w & w[1].x & w[1].y & w[1].z & w[1].w & 1u) == 0u);
    } while (more && ++it < SPIN_LIMIT);
    float c;
    asm("sqrt.approx.f32 %0, %1;" : "=f"(c) : "f"(__uint_as_float(max(max(v[0].x, v[1].x), v[2].x))));
    c *= __uint_as_float(max(max(max(w[0].x, w[0].y), max(w[0].z, w[0].w)), max(max(w[1].x, w[1].y), max(w[1].z, w[1].w)))) * 272.f;
#pragma unroll
    for (int o = 16; o; o >>= 1) c += __shfl_xor_sync(0xffffffffu, c, o);
    const uint32_t r = __reduce_max_sync(0xffffffffu, v[0].y);
    if (lane < 3) {
        const uint32_t rb = mapa(sbase, lane);
        c *= 1.1f * 24.f;
        st_async64(rb + SM_SC, __float_as_uint(to_scale(__uint_as_float(r) * c)), __float_as_uint(c), rb + B_W + 8);
        st_async32(rb + SM_SC + 68, r, rb + B_W + 8);
    }
    __syncwarp();
}
__device__ __forceinline__ void xmax_gather(int lane, uint32_t sb) {
    uint4 v[4];
    unsigned it = 0;
    uint32_t ok;
    do {
#pragma unroll
        for (int i = 0; i < 4; i++) v[i] = ld_vol_u4(&g_rx[lane + 32 * (i >> 1)][i & 1]);
        ok = 1u;
#pragma unroll
        for (int i = 0; i < 4; i++) ok &= (v[i].x & v[i].y) & (v[i].z & v[i].w);
    } while (__any_sync(0xffffffffu, ok == 0u) && ++it < SPIN_LIMIT);
#pragma unroll
    for (int i = 0; i < 2; i++)
        sts32(sb + SM_SC + 64 + 4 * lane + 128 * i, max(max(max(v[2 * i].x, v[2 * i].y), max(v[2 * i].z, v[2 * i].w)), max(max(v[2 * i + 1].x, v[2 * i + 1].y), max(v[2 * i + 1].z, v[2 * i + 1].w))));
}
__device__ __forceinline__ uint32_t max_abs8(uint32_t m, uint32_t a, uint32_t b, uint32_t c, uint32_t d) { return max_abs2(max_abs2(m, max_abs2(a, b)), max_abs2(c, d)); }
__device__ __forceinline__ uint32_t warp_max_abs(uint32_t m) { return __reduce_max_sync(0xffffffffu, max((m << 16) & 0x7fff0000u, m & 0x7fff0000u)); }

__device__ __forceinline__ void last_rows() {
    extern __shared__ __align__(1024) unsigned char smem_raw[];
    const uint32_t sbase = smem_u32(smem_raw);
    const int tid = threadIdx.x, warp = __shfl_sync(0xffffffffu, tid >> 5, 0), h = blockIdx.x / 3;
    {
        const int sg = warp < 8, wq = warp & 3, lane = tid & 31;
        const uint32_t qk = sbase + SM_X + XBUF + sg * (2 * 9216), ob = sbase + SM_X + 2 * XBUF + sg * 8192;
        TST(0);
        mbar_wait(sbase + B_VX + 8 * sg, 0);
        fence_async();
        TST(1);
        float sc[20];
#pragma unroll
        for (int i = 0; i < 20; i++) sc[i] = 0.f;
        {
            const uint64_t da = smem_desc(qk + 1024, 128, 1024), db = smem_desc(qk, 128, 2048);
            wg_fence();
#pragma unroll
            for (int ks = 0; ks < 8; ks++) wgmma_n40_ss(sc, da + (uint64_t)((ks >> 2) * 576 + (ks & 3) * 16), db + (uint64_t)((ks >> 2) * 576 + (ks & 3) * 16), ks > 0);
            wg_commit();
            wg_wait0();
        }
        uint32_t p[5], o[16];
        const float psum = xrow_softmax(sc, p, wq, lane);
        xrow_pv(o, p, psum, sbase + SM_T + ((NSEG - 2 + sg) & 3) * TBUF);
        {
#pragma unroll
            for (int i = 0; i < 4; i++) stsm_x4(ob + wq * 2048 + i * 512 + lane * 16, o[4 * i], o[4 * i + 1], o[4 * i + 2], o[4 * i + 3]);
        }
        fence_async();
        named_bar(11 + sg, 128);
        TST(2);
        if ((tid & 127) == 0) {
            unsigned char* dst = reinterpret_cast<unsigned char*>(g_ox) + ((size_t)((NSEG / 2 - 1) * NH + h)) * 16384 + sg * 8192;
            asm volatile("cp.async.bulk.global.shared::cta.bulk_group [%0], [%1], 8192;" :: "l"(dst), "r"(ob) : "memory");
            asm volatile("cp.async.bulk.commit_group;" ::: "memory");
            asm volatile("cp.async.bulk.wait_group 0;" ::: "memory");
            asm volatile("red.relaxed.gpu.global.add.u32 [%0], 1;" :: "l"(&g_prog[(h >> 2) * 64 + NSEG / 2 - 1]) : "memory");
        }
        TST(3);
    }
    __syncwarp();
}

__global__ void __cluster_dims__(3, 1, 1) __launch_bounds__(384, 1)
k_chain(const __grid_constant__ CUtensorMap tmq, const __grid_constant__ CUtensorMap tmk,
        const __grid_constant__ CUtensorMap tmv, const __grid_constant__ CUtensorMap tmx2, const __grid_constant__ CUtensorMap tmo,
        const __grid_constant__ CUtensorMap tmm, const bf16* __restrict__ xg) {
    extern __shared__ __align__(1024) unsigned char smem_raw[];
    const uint32_t sbase = smem_u32(smem_raw);
    const int cta = blockIdx.x, h = cta / 3, role = cta - 3 * h;
    const int tid = threadIdx.x, warp = __shfl_sync(0xffffffffu, tid >> 5, 0), lane_o = tid & 31;
    TS3C(0);
    asm volatile("griddepcontrol.launch_dependents;" ::: "memory");
    auto stage_w = [&](int i) {
        tma_2d(sbase + SM_WS + i * 16384, role == 2 ? &tmv : &tmq, h * DH + (role == 1 ? 64 : 0), i * 64, sbase + B_W + 8 * i);
        tma_2d(sbase + SM_WS + i * 16384 + 8192, role == 2 ? &tmv : &tmk, h * DH + (role == 0 ? 0 : 64), i * 64, sbase + B_W + 8 * i);
    };
    auto stage_x = [&](int i) {
        tma_2d(sbase + x01_off(i), &tmx2, i * 64, 0, sbase + B_W + 8 * i);
        tma_2d(sbase + x01_off(i) + 8192, &tmm, i * 64, 0, sbase + B_W + 8 * i);
        if (i < 3) tma_2d(sbase + x23_off(i), &tmx2, i * 64, 64, sbase + B_W + 8 * i);
    };
    if (tid == 0) {
#pragma unroll
        for (int i = 0; i < 10; i++) mbar_init(sbase + B_W + 8 * i, 1);
        fence_async();
        TSQ(10);
#pragma unroll
        for (int i = 0; i < 3; i++) tma_2d(sbase + SM_X01 + i * 16384, &tmo, role * WOC + i * 64, h * DH, sbase + B_E);
        stage_x(0); stage_w(0);
        TSQ(11);
        mbar_expect(sbase + B_E, 49152);
#pragma unroll
        for (int i = 0; i < 9; i++) mbar_expect(sbase + B_W + 8 * i, 16384 + 9216 + (i < 3 ? 8192 : 0));
    } else if (tid == 32) {
#pragma unroll
        for (int i = 0; i < 8; i++) mbar_init(sbase + SM_BAR + 8 * i, 1);
        mbar_init(sbase + B_XF, 3);
        asm volatile("fence.mbarrier_init.release.cluster;" ::: "memory");
        for (int i = 0; i < 2; i++) {
            mbar_expect(sbase + B_SB + 8 * i, role == 2 ? 2560 : 1280 + 2048);
            mbar_expect(sbase + B_VX + 8 * i, role != 2 ? 8192 : 2 * 9216);
            mbar_expect(sbase + B_XT + 8 * i, 32768);
            mbar_expect(sbase + B_XT + 16 + 8 * i, i == 0 ? 40960 : 0);
        }
    }
    __syncthreads();
    TS3C(8);
    if (tid == 0) {
#pragma unroll 1
        for (int i = 1; i < 3; i++) { stage_x(i); stage_w(i); }
        TSQ(12);
    }
    __syncwarp();
    if (warp < 8) {
        uint32_t wreg[36 - NS][4];
        uint32_t v0, v1;
        {
            const int lane = lane_o;
            const uint32_t a = w_addr(sbase, warp, lane);
            const uint64_t da = smem_desc(sbase + SM_WS + (warp >> 2) * 8192, 1024, 1024) | (1ull << 62);
            float acc[36], acc1[32];
            uint32_t m = 0u;
#pragma unroll
            for (int i = 0; i < 36; i++) acc[i] = 0.f;
#pragma unroll
            for (int i = 0; i < 32; i++) acc1[i] = 0.f;
#pragma unroll 1
            for (int b = 0; b < 7; b++) {
                if (b == 0) TSQ(0);
                mbar_wait(sbase + B_W + 8 * b, 0);
                TSQ(1 + b);
                const uint64_t db = smem_desc(sbase + x01_off(b), 16, 1024) | (1ull << 62);
                wg_fence();
#pragma unroll
                for (int k = 0; k < 4; k++) wgmma_n72_ss(acc, da + (uint64_t)(b * 1024 + k * 128), db + (uint64_t)(k * 2));
                wg_commit();
                if (b < 3) {
                    const uint64_t d1 = smem_desc(sbase + x23_off(b), 16, 1024) | (1ull << 62);
                    wg_fence();
#pragma unroll
                    for (int k = 0; k < 4; k++) wgmma_n64_ss(acc1, da + (uint64_t)(b * 1024 + k * 128), d1 + (uint64_t)(k * 2));
                    wg_commit();
                }
                if (b == 2) {
                    wg_wait0();
                    bar_arrive(10, 384);
                }
                if (b == 3) {
                    if (tid == 0) mbar_expect(sbase + B_W + 8, 12);
                    __syncwarp();
                    if (role == 2) {
#pragma unroll
                        for (int ks = 0; ks < NS; ks++) {
                            uint32_t t[4];
                            ldsm_x4_t(t, a + (ks >> 2) * 16384 + (ks & 3) * 2048);
                            m = max_abs8(m, t[0], t[1], t[2], t[3]);
                        }
                    }
#pragma unroll
                    for (int ks = NS; ks < 16; ks++) ldsm_x4_t(wreg[ks - NS], a + (ks >> 2) * 16384 + (ks & 3) * 2048);
                }
                if (b == 5) {
#pragma unroll
                    for (int ks = 16; ks < 24; ks++) ldsm_x4_t(wreg[ks - NS], a + (ks >> 2) * 16384 + (ks & 3) * 2048);
                    if (role == 2) {
#pragma unroll
                        for (int ks = NS; ks < 24; ks++) m = max_abs8(m, wreg[ks - NS][0], wreg[ks - NS][1], wreg[ks - NS][2], wreg[ks - NS][3]);
                    }
                }
            }
            mbar_wait(sbase + B_W + 16, 1);
            TSQ(13);
            wg_fence();
#pragma unroll
            for (int k = 12; k < 20; k++)
                wgmma_n64_ss(acc1, da + (uint64_t)((k >> 2) * 1024 + (k & 3) * 128), (smem_desc(sbase + x23_off(k >> 2), 16, 1024) | (1ull << 62)) + (uint64_t)((k & 3) * 2));
            wg_commit();
            wg_wait0();
            named_bar(11, 384);
#pragma unroll
            for (int i = 0; i < 8; i++)
                asm volatile("st.shared.v4.f32 [%0], {%1,%2,%3,%4};" :: "r"(sbase + SM_X + 5 * 8192 + i * 4096 + tid * 16),
                             "f"(acc1[4 * i]), "f"(acc1[4 * i + 1]), "f"(acc1[4 * i + 2]), "f"(acc1[4 * i + 3]) : "memory");
#pragma unroll
            for (int b = 7; b < 9; b++) {
#pragma unroll
                for (int ks = 4 * b - 4; ks < 4 * b; ks++) ldsm_x4_t(wreg[ks - NS], a + (ks >> 2) * 16384 + (ks & 3) * 2048);
                if (role == 2) {
#pragma unroll
                    for (int ks = 4 * b - 4; ks < 4 * b; ks++) m = max_abs8(m, wreg[ks - NS][0], wreg[ks - NS][1], wreg[ks - NS][2], wreg[ks - NS][3]);
                }
                const uint64_t db = smem_desc(sbase + x01_off(b), 16, 1024) | (1ull << 62);
                mbar_wait(sbase + B_W + 8 * b, 0);
                TSQ(1 + b);
                if (b == 8) TS3C(2);
                wg_fence();
#pragma unroll
                for (int k = 0; k < 4; k++) wgmma_n72_ss(acc, da + (uint64_t)(b * 1024 + k * 128), db + (uint64_t)(k * 2));
                wg_commit();
            }
#pragma unroll
            for (int ks = 32; ks < KPRE; ks++) ldsm_x4_t(wreg[ks - NS], a + (ks >> 2) * 16384 + (ks & 3) * 2048);
            if (role == 2) {
#pragma unroll
                for (int ks = KPRE; ks < 36; ks++) {
                    uint32_t t[4];
                    ldsm_x4_t(t, a + (ks >> 2) * 16384 + (ks & 3) * 2048);
                    m = max_abs8(m, t[0], t[1], t[2], t[3]);
                }
#pragma unroll
                for (int ks = 32; ks < KPRE; ks++) m = max_abs8(m, wreg[ks - NS][0], wreg[ks - NS][1], wreg[ks - NS][2], wreg[ks - NS][3]);
                m = warp_max_abs(m);
                if (lane == 0) asm volatile("st.volatile.global.u32 [%0], %1;" :: "l"(reinterpret_cast<uint32_t*>(&g_wv[h][0]) + warp), "r"(m | 1u) : "memory");
                __syncwarp();
            }
            wg_wait0();
            named_bar(9, 256);
            const uint32_t off = sbase + SM_T + (DH + warp * 16 + (lane & 15)) * 16 + (lane >> 4) * (DH * 16);
#pragma unroll
            for (int i = 0; i < 4; i++)
                stsm_x4(off + (i >> 1) * TBUF + (i & 1) * (2 * DH * 16), pack_bf16(acc[8 * i], acc[8 * i + 1]), pack_bf16(acc[8 * i + 2], acc[8 * i + 3]),
                        pack_bf16(acc[8 * i + 4], acc[8 * i + 5]), pack_bf16(acc[8 * i + 6], acc[8 * i + 7]));
            v0 = pack_bf16(acc[32], acc[33]);
            v1 = pack_bf16(acc[34], acc[35]);
#pragma unroll
            for (int ks = KPRE; ks < 36; ks++) ldsm_x4_t(wreg[ks - NS], a + (ks >> 2) * 16384 + (ks & 3) * 2048);
            if (role == 2) fence_async();
            bar_arrive(8, 384);
            named_bar(7, 256);
            asm volatile("barrier.cluster.arrive.relaxed.aligned;" ::: "memory");
        }
        TS3C(3);
        uint32_t ws[NS][4];
#pragma unroll
        for (int ks = NS - NP; ks < NS; ks++) ldsm_x4_t(ws[ks], w_addr(sbase, warp, lane_o) + (ks >> 2) * 16384 + (ks & 3) * 2048);
        asm volatile("barrier.cluster.wait.aligned;" ::: "memory");
        if (lane_o == 0 && role != 2 && warp < 2) tma_2d_mc(sbase + SM_X + (2 * role + warp) * 8192, &tmx2, (2 * role + warp + 5) * 64, 64, sbase + B_XT + 8);
        __syncwarp();
        TS3C(4);
        auto main_loop = [&](auto is_c) {
            constexpr bool C = decltype(is_c)::value;
            if (C) pad_code<PAD4>(); else pad_code<PAD3>();
            const uint32_t l16 = __shfl_sync(0xffffffffu, sbase + lane_o * 16, lane_o);
            const uint32_t ka = __shfl_sync(0xffffffffu, sbase + SM_T + (64 + (lane_o & 7) + ((lane_o >> 3) & 1) * 16 + (lane_o >> 4) * 8) * 16, lane_o);
            const uint32_t wa = __shfl_sync(0xffffffffu, w_addr(sbase, warp, lane_o), lane_o);
            auto post = [&](bool act, int s, uint32_t to, uint32_t ta, int scw, uint32_t v0, uint32_t v1) {
                int lane = lane_o;
                asm volatile("" : "+r"(lane));
                asm volatile("stmatrix.sync.aligned.m8n8.x2.shared.b16 [%0], {%1,%2};" :: "r"(l16 + ta), "r"(v0), "r"(v1) : "memory");
                if (C) {
                    if (act || s + 1 < NSEG) {
                        const uint32_t fo = (uint32_t)(warp * 256 + lane * 8);
                        const uint32_t rb0 = mapa(sbase, 0), rb1 = mapa(sbase, 1);
                        st_async64(rb0 + SM_VM + fo, v0, v1, rb0 + B_SB + 8 * (s & 1));
                        st_async64(rb1 + SM_VM + fo, v0, v1, rb1 + B_SB + 8 * (s & 1));
                        asm volatile("st.shared.v2.u32 [%0], {%1,%2};" :: "r"(sbase + SM_VM + fo), "r"(v0), "r"(v1) : "memory");
                        bar_arrive(2, 384);
                    }
                } else if (act) bar_arrive(2, 384);
                else {
                    named_bar(2, 384);
                    if (scw == 0) {
                        uint32_t kf[2][4], qf[2][4];
#pragma unroll
                        for (int k2 = 0; k2 < 2; k2++) { ldsm_x4_t(kf[k2], ka + to + k2 * 512); ldsm_x4_t(qf[k2], l16 + SM_T + to + k2 * 512); }
                        const uint32_t d0 = sbase + SM_S + lane * 8, bo = sbase + B_SB + 8 * (s & 1);
                        const uint32_t d1 = mapa(d0 + 1280, role ^ 1), m1 = mapa(bo, role ^ 1), d2 = mapa(d0 + role * 1280, 2), m2 = mapa(bo, 2);
                        score_group(qf, kf, d0, d1, m1, d2, m2);
                        bar_arrive(6, 160);
                        bar_arrive(5, 384);
                    }
                    if (scw == 8) {
                        const uint32_t dk = mapa(sbase + SM_X + XBUF + (2 + role) * 9216 + (warp - 4) * 256 + lane * 4, 2), mb = mapa(sbase + B_VX + 8, 2);
                        st_async32(dk, v0, mb);
                        st_async32(dk + 128, v1, mb);
                    }
                }
                FS(11, 0);
            };
            post(false, 0, 0, SM_T + warp * 256, warp ^ 7, v0, v1);
            if (tid == 128 && cta < NSEG) {
                fence_async();
                mbar_expect(sbase + B_E, XBUF);
                bulk_g2s(sbase + SM_X + 9 * 8192, xg + (size_t)cta * SEG * DM, 32768, sbase + B_E);
                bulk_g2s(sbase + SM_WS + 32768 + 4096, xg + (size_t)cta * SEG * DM + 16384, 4096, sbase + B_E);
            }
            __syncwarp();
            if (C) {
                named_bar(7, 256);
                if (warp == 1) norms_gather(lane_o, sbase);
            }
            auto chores = [&](int s, bool idle) {
                int lane = lane_o;
                asm volatile("" : "+r"(lane));
                const int hw = (s & 1) ? warp : warp - 4;
                const uint32_t tb = sbase + SM_T + (s & 3) * TBUF;
                if (idle) { if (hw != 2) named_bar(4, 384); else bar_arrive(4, 384); }
                if (hw == 2) {
                    if (lane == 0) {
                        {
                            if (C || !idle) fence_async();
                            if (C) {
                                store_tile(s + 1, h, 2, sbase + SM_T + ((s + 1) & 3) * TBUF, 2048, 10240);
                                store_tile(s, h, 2, tb, 0, idle ? 2048 : 10240);
                            } else store_tile(s, h, role, tb, 1024, 10240);
                            asm volatile("cp.async.bulk.commit_group;" ::: "memory");
                        }
                        {
                            asm volatile("cp.async.bulk.wait_group 0;" ::: "memory");
                            if (C) {
                                asm volatile("cp.async.bulk.shared::cluster.global.mbarrier::complete_tx::bytes.multicast::cluster [%0], [%1], 8192, [%2], %3;"
                                             :: "r"(sbase + SM_VX + ((s + 1) & 1) * 8192), "l"(&g_qkv[s + 1][h][2][2048]), "r"(sbase + B_VX + 8 * ((s + 1) & 1)), "h"((unsigned short)3) : "memory");
                            }
                            asm volatile("red.relaxed.gpu.global.add.u32 [%0], 1;" :: "l"(&g_flag[h * NSEG + s]) : "memory");
                        }
                    }
                    __syncwarp();
                    if (!C && (s & 1) && s + 4 < NSEG) bar_arrive(13, 160);
                }
                __syncwarp();
            };
            auto put_tiles = [&](const float (&acc)[32], uint32_t off) {
#pragma unroll
                for (int i = 0; i < 4; i++)
                    stsm_x4(off + (i >> 1) * TBUF + (i & 1) * (2 * DH * 16), pack_bf16(acc[8 * i], acc[8 * i + 1]), pack_bf16(acc[8 * i + 2], acc[8 * i + 3]),
                            pack_bf16(acc[8 * i + 4], acc[8 * i + 5]), pack_bf16(acc[8 * i + 6], acc[8 * i + 7]));
            };
            auto tile_off = [&](int p) {
                int lane = lane_o;
                asm volatile("" : "+r"(lane));
                return sbase + SM_T + (p & 1) * (2 * TBUF) + (DH + warp * 16 + (lane & 15)) * 16 + (lane >> 4) * (DH * 16);
            };
            {
                auto db = [&](int ks) { return (smem_desc(sbase + SM_X, 16, 1024) | (1ull << 62)) + (uint64_t)(((ks >> 2) - 5) * 512 + (ks & 3) * 2); };
                if (!C && warp != 7) bar_arrive(5, 384);
                if (warp == 5) {
                    mbar_wait(sbase + B_W + 8, 1);
                    bar_arrive(12, 160);
                }
                chores(0, false);
                float acc[32];
#pragma unroll
                for (int i = 0; i < 8; i++)
                    asm volatile("ld.shared.v4.f32 {%0,%1,%2,%3}, [%4];" : "=f"(acc[4 * i]), "=f"(acc[4 * i + 1]), "=f"(acc[4 * i + 2]), "=f"(acc[4 * i + 3])
                                 : "r"(l16 + warp * 512 + SM_X + 5 * 8192 + i * 4096) : "memory");
                mbar_wait(sbase + B_XT + 8, 0);
                FS(8, 0);
                named_bar(4, 384);
                wg_fence();
#pragma unroll
                for (int ks = 35; ks >= 20; ks--) wgmma_n64(acc, wreg[ks - NS], db(ks), 1);
                wg_commit();
                if (cta < NSEG) {
                    uint32_t m = 0u;
                    mbar_wait(sbase + B_E, 1);
#pragma unroll
                    for (int j = 0; j < 9; j++) {
                        const uint4 xv = lds128(l16 + warp * 512 + (j < 8 ? SM_X + 9 * 8192 + j * 4096 : SM_WS + 32768 + 4096));
                        m = max_abs8(m, xv.x, xv.y, xv.z, xv.w);
                    }
                    m = warp_max_abs(m);
                    if (lane_o == 0) asm volatile("st.volatile.global.u32 [%0], %1;" :: "l"(reinterpret_cast<uint32_t*>(&g_rx[cta][0]) + warp), "r"(m | 1u) : "memory");
                    __syncwarp();
                }
                FS(3, 0);
                wg_wait0();
                put_tiles(acc, tile_off(1));
                FS(7, __float_as_uint(acc[0]));
            }
            auto mem_proj = [&](uint32_t& u0, uint32_t& u1) {
#pragma unroll
                for (int ks = 0; ks < NS - NP; ks++) ldsm_x4_t(ws[ks], wa + (ks >> 2) * 16384 + (ks & 3) * 2048);
                FS(0, ws[0][0]);
                named_bar(1, 384);
                float acc[2][4], minv;
                uint32_t b[3][4];
#pragma unroll
                for (int kk = 0; kk < 3; kk++) ldsm_x4_t(b[kk], l16 + SM_M + kk * 512);
                FS(1, b[0][0]);
#pragma unroll
                for (int kk = 0; kk < 18; kk++) {
#pragma unroll
                    for (int i = 0; i < 2; i++) {
                        const int ks = 2 * kk + i;
                        if (ks < 2) mma_z(acc[i], ws[ks], b[kk % 3][2 * i], b[kk % 3][2 * i + 1]);
                        else if (ks < NS) mma_bf16(acc[i], ws[ks < NS ? ks : 0], b[kk % 3][2 * i], b[kk % 3][2 * i + 1]);
                        else mma_bf16(acc[i], wreg[ks >= NS ? ks - NS : 0], b[kk % 3][2 * i], b[kk % 3][2 * i + 1]);
                    }
                    if (kk + 3 < 18) ldsm_x4_t(b[kk % 3], l16 + SM_M + (kk + 3) * 512);
                    if (kk + 3 == 17) asm volatile("ld.shared.f32 %0, [%1];" : "=f"(minv) : "r"(sbase + SM_SC + 8) : "memory");
                }
                u0 = pack_bf16(fmaf(acc[1][0], minv, acc[0][0] * minv), fmaf(acc[1][1], minv, acc[0][1] * minv));
                u1 = pack_bf16(fmaf(acc[1][2], minv, acc[0][2] * minv), fmaf(acc[1][3], minv, acc[0][3] * minv));
                FS(2, u0);
            };
            int s = 0, rc = 9;
            bool act = warp >= 4;
            uint32_t to = TBUF, ta = SM_T + warp * 256 + TBUF;
            auto next_slot = [&]() {
                const uint32_t d = (s & 3) == 3 ? -3 * TBUF : TBUF;
                to += d; ta += d;
                asm volatile("" : "+r"(to), "+r"(ta));
            };
#pragma unroll 1
            for (;;) {
                uint32_t u0, u1;
                if (act) {
                    mem_proj(u0, u1);
                    s++;
                    post(true, s, to, ta, 1, u0, u1);
                    const int p = (s + 3) >> 1;
                    const uint32_t dlo = (uint32_t)smem_desc(sbase + SM_X, 16, 1024) + rc * 512;
                    const uint64_t da = smem_desc(sbase + SM_WS + (warp >> 2) * 8192, 1024, 1024) | (1ull << 62);
                    auto db = [&](int ks) {
                        const int j = ((ks >> 2) + 4) % 9;
                        return ((uint64_t)0x40000040u << 32) | (uint64_t)(dlo + (uint32_t)((j - (rc + j >= 13 ? 13 : 0)) * 512 + (ks & 3) * 2));
                    };
                    const uint32_t xph = (uint32_t)((p - 1) >> 1) & 1u;
                    float acc[32];
                    mbar_wait(sbase + B_XT + 8 * (p & 1), xph);
                    if (C) named_bar(7, 256); else named_bar(5, 384);
                    constexpr int N1 = C ? NC1C : NC1;
                    wg_fence();
#pragma unroll
                    for (int ks = 35; ks > 35 - N1; ks--) { if (ks == 35) wgmma_n64_z(acc, wreg[ks - NS], db(ks)); else wgmma_n64(acc, wreg[ks - NS], db(ks), 1); }
                    wg_commit();
                    wg_wait0();
                    FS(9, __float_as_uint(acc[0]));
                    next_slot();
                    FS(8, 0);
                    asm volatile("{\n.reg .pred p;\nsetp.ge.s32 p, %0, 0;\n@p bar.sync 4, 384;\n}" :: "r"(s) : "memory");
                    FS(3, 0);
                    wg_fence();
#pragma unroll
                    for (int ks = 35 - N1; ks >= KG1; ks--) wgmma_n64(acc, wreg[ks - NS], db(ks), 1);
                    wg_commit();
                    mbar_wait(sbase + B_XT + 16 + 8 * (p & 1), xph);
                    wg_fence();
#pragma unroll
                    for (int ks = 0; ks < NS; ks++) wgmma_n64_ss(acc, da + (uint64_t)((ks >> 2) * 1024 + (ks & 3) * 128), db(ks));
#pragma unroll
                    for (int ks = NS; ks < KG1; ks++) wgmma_n64(acc, wreg[ks - NS], db(ks), 1);
                    wg_commit();
                    if (!C && warp >= 4) named_bar(13, 160);
                    uint32_t off = tile_off(p);
                    rc = rc >= 4 ? rc - 4 : rc + 9;
                    asm volatile("" : "+r"(off), "+r"(rc));
                    wg_wait0();
                    put_tiles(acc, off);
                    FS(7, __float_as_uint(acc[0]));
                }
                int scw = s + 2 < NSEG ? warp ^ ((s & 1) ? 7 : 3) : (warp & 4) + 4;
                asm volatile("" : "+r"(scw));
                mem_proj(u0, u1);
                s++;
                post(false, s, to, ta, scw, u0, u1);
                if (s + 1 == NSEG) break;
                if (s + 2 < NSEG) {
                    if (!C && (warp & 3) == 2) fence_async();
                    if (C) named_bar(7, 256); else if (scw != 0) named_bar(5, 384);
                    chores(s, true);
                } else {
                    const uint32_t t0 = clock32();
                    const uint32_t dq = mapa(sbase + SM_X + XBUF + role * 9216, 2), mb = mapa(sbase + B_VX, 2);
                    if (!C) {
                        if (scw != 0) named_bar(5, 384);
                        if (tid == 64) { fence_async(); while (clock32() - t0 < TL_DELAY) {} bulk_s2s(dq, sbase + SM_T + 2 * TBUF + 1024, 9216, mb); }
                        __syncwarp();
                    }
                    named_bar(4, 384);
                    if (!C && tid == 64) { const uint32_t t1 = clock32(); while (clock32() - t1 < VX_DELAY) {} bulk_s2s(dq + 2 * 9216 + 1024, sbase + SM_T + 3 * TBUF + 2048, 8192, mb + 8); }
                    __syncwarp();
                }
                next_slot();
                act = s + 4 < NSEG;
            }
            if (C) named_bar(7, 256);
        };
        if (role == 2) main_loop(Flag<true>()); else main_loop(Flag<false>());
    } else {
        uint32_t wo[3][8][4];
        uint32_t mx2 = 0u;
        {
            const int pt = tid - 256, lane = lane_o, wq = warp - 8, g = lane >> 2, tq = lane & 3;
            TSQ(7);
            mbar_wait(sbase + B_E, 0);
            TSQ(8);
#pragma unroll
            for (int t = 0; t < 3; t++) {
                const int T = 3 * wq + t;
                const uint32_t a = sbase + SM_X01 + (T >> 2) * 16384 + ((lane >> 4) * 8 + (lane & 7)) * 128 + ((((T & 3) * 2 + ((lane >> 3) & 1)) ^ (lane & 7)) << 4);
#pragma unroll
                for (int kk = 0; kk < 8; kk++) ldsm_x4_t(wo[t][kk], a + ((2 * wq + kk) & 7) * 2048);
            }
            named_bar(3, 128);
            if (pt == 64) {
                fence_async();
#pragma unroll 1
                for (int i = 3; i < 9; i++) { stage_x(i); if (i < 7) stage_w(i); }
            }
            if (pt >= 96 && pt < 120) {
                *reinterpret_cast<uint4*>(g_acc + cta * 1024 + (pt - 96) * 16) = make_uint4(0u, 0u, 0u, 0u);
                __threadfence();
            }
            __syncwarp();
            TSQ(9);
            float c0 = 0.f;
#pragma unroll
            for (int t = 0; t < 3; t++) {
                float n[4][4];
#pragma unroll
                for (int i = 0; i < 4; i++) { n[i][0] = n[i][1] = n[i][2] = n[i][3] = 0.f; }
#pragma unroll
                for (int kk = 0; kk < 8; kk++)
#pragma unroll
                    for (int i = 0; i < 4; i++) mma_k8(n[i], wo[t][kk][i & 2], wo[t][kk][(i & 2) + 1], wo[t][kk][i]);
                if ((g >> 1) == tq) c0 = fmaxf(c0, (g & 1) ? fmaxf(n[0][1] + n[2][1], n[1][3] + n[3][3]) : fmaxf(n[0][0] + n[2][0], n[1][2] + n[3][2]));
            }
            c0 = __uint_as_float(__reduce_max_sync(0xffffffffu, __float_as_uint(c0)));
            uint32_t m = 0u;
            const int xb = role == 0 ? h % 9 : 9;
            auto x_max = [&]() {
                mbar_wait(sbase + B_W + 8 * xb, 0);
#pragma unroll
                for (int j = 0; j < 5; j++) {
                    uint4 xv;
                    asm volatile("ld.shared.v4.u32 {%0,%1,%2,%3}, [%4];" : "=r"(xv.x), "=r"(xv.y), "=r"(xv.z), "=r"(xv.w)
                                 : "r"(sbase + x01_off(xb) + (j < 4 ? pt + 128 * j : 512 + (pt & 63)) * 16) : "memory");
                    m = max_abs8(m, xv.x, xv.y, xv.z, xv.w);
                }
            };
            if (xb < 3) x_max();
            named_bar(10, 384);
            TSQ(10);
            if (pt == 64) {
                fence_async();
                mbar_expect(sbase + B_W + 16, 16384);
#pragma unroll
                for (int i = 3; i < 5; i++) tma_2d(sbase + x23_off(i), &tmx2, i * 64, 64, sbase + B_W + 16);
#pragma unroll 1
                for (int i = 7; i < 9; i++) stage_w(i);
            }
            __syncwarp();
            if (xb >= 3 && xb < 7) x_max();
            bar_arrive(11, 384);
            if (xb == 7 || xb == 8) x_max();
            asm volatile("barrier.cluster.arrive.relaxed.aligned;" ::: "memory");
            m = warp_max_abs(m);
            if (lane == 0) { sts32(sbase + SM_SC + 320 + 4 * wq, __float_as_uint(c0)); sts32(sbase + SM_SC + 336 + 4 * wq, m); }
            TSQ(1);
            named_bar(3, 128);
            if (pt == 0) {
                const uint4 a = lds128(sbase + SM_SC + 320), b = lds128(sbase + SM_SC + 336);
                st_vol_u2(&g_norm[cta], make_uint2(max(max(a.x, a.y), max(a.z, a.w)) | 1u, max(max(b.x, b.y), max(b.z, b.w)) | 1u));
            }
            __syncwarp();
            named_bar(8, 384);
            TSQ(2);
            asm volatile("barrier.cluster.wait.aligned;" ::: "memory");
            if (role == 2 && lane == 0 && wq < 2) vx_copy(sbase, 0, wq);
            __syncwarp();
        }
        const int wq = warp - 8;
        auto helper_loop = [&](auto is_c) {
        const bool C = is_c.value;
        if (C) pad_code<PAD2>(); else pad_code<PAD1>();
        const uint32_t sb = sbase;
        const uint32_t l8_o = __shfl_sync(0xffffffffu, sb + lane_o * 8, lane_o), l16_o = __shfl_sync(0xffffffffu, sb + lane_o * 16, lane_o);
        unsigned char* dst = g_acc + (role * 32 + wq * 8 + (lane_o >> 3)) * 1024 + (lane_o & 7) * 16;
        auto load_kf = [&](uint32_t (&kf)[2][4], int slot) {
            int lane = lane_o;
            asm volatile("" : "+r"(lane));
            const uint32_t ka = sb + SM_T + slot * TBUF + ((wq + 1) * DH + 64 + (lane & 7) + ((lane >> 3) & 1) * 16 + (lane >> 4) * 8) * 16;
#pragma unroll
            for (int k2 = 0; k2 < 2; k2++) ldsm_x4_t(kf[k2], ka + k2 * 512);
        };
        float minv = 1.f;
        uint32_t kf[2][4];
        if (!C) load_kf(kf, 0);
        int b3 = 0;
        int rx = 9;
        for (int s = 0; s + 1 < NSEG; s++) {
            const int n3 = b3 == 2 ? 0 : b3 + 1;
            uint32_t l8 = l8_o, l16 = l16_o;
            asm volatile("" : "+r"(l8), "+r"(l16));
            {
                int lane = lane_o;
                asm volatile("" : "+r"(lane));
                if (C) {
                    if (lane == 0) {
                        if (wq == 3 && h == 0) {
                            const uint32_t t = gtime32();
                            st_vol_u2(&g_tick, make_uint2(t, lds32(sb + SM_SC + 12)));
                            sts32(sb + SM_SC + 12, t);
                        }
                    }
                    __syncwarp();
                    if (wq == 2 && s > 1 && lane < 24) {
                        *reinterpret_cast<uint4*>(g_acc + n3 * 128 + (3 * h + (lane >> 3)) * 1024 + (lane & 7) * 16) = make_uint4(0u, 0u, 0u, 0u);
                    }
                    if (wq == 1 && s == 3 && lane < 3) {
                        const int c = 3 * h + lane;
                        st_vol_u2(&g_norm[c], make_uint2(0u, 0u));
                        uint4* z = c < NSEG ? g_rx[c] : g_wv[c - NSEG];
                        st_vol_u4(z, make_uint4(0u, 0u, 0u, 0u)); st_vol_u4(z + 1, make_uint4(0u, 0u, 0u, 0u));
                    }
                    __syncwarp();
                }
                const uint32_t mw = __reduce_max_sync(0xffffffffu, max(mx2 << 16, mx2 & 0xffff0000u));
                if (lane == 0) sts32(sb + SM_SC + 16 + 4 * wq, mw);
            }
            const uint32_t to = SM_T + (s & 3) * TBUF;
            const uint32_t ph = (uint32_t)(s >> 1) & 1u;
            if (!C) {
                const uint32_t bo = sb + B_SB + 8 * (s & 1);
                uint32_t d0 = l8 + SM_S + (wq + 1) * 256, qa = l16 + to;
                const uint32_t d1 = mapa(d0 + 1280, role ^ 1), m1 = mapa(bo, role ^ 1), d2 = mapa(d0 + role * 1280, 2), m2 = mapa(bo, 2);
                asm volatile("" : "+r"(d0), "+r"(qa));
                mbar_wait(sb + (s > 0 ? B_VX + 8 * (s & 1) : B_W), ph);
                FS(1, 0);
                named_bar(2, 384);
                uint32_t qf[2][4];
#pragma unroll
                for (int k2 = 0; k2 < 2; k2++) ldsm_x4_t(qf[k2], qa + k2 * 512);
                score_group(qf, kf, d0, d1, m1, d2, m2);
                bar_arrive(5, 384);
            } else named_bar(2, 384);
            if (!C && s == 0) {
                TSQ(3);
                mbar_wait(sb + B_VX, 0);
                TSQ(4);
            }
            float4 m4;
            asm volatile("ld.shared.v4.f32 {%0,%1,%2,%3}, [%4];" : "=f"(m4.x), "=f"(m4.y), "=f"(m4.z), "=f"(m4.w) : "r"(sb + SM_SC + 16) : "memory");
            const float c24 = __uint_as_float(lds32(sb + SM_SC + 4)), xb = __uint_as_float(lds32(sb + SM_SC + 64 + 4 * s));
            uint32_t vf[2][2][4], vm[2][2];
            uint32_t va = l16 + ((l16 >> 8) & 1) * 1792 + wq * 512 + (C ? to + DH * 16 : SM_VX + (s & 1) * 8192);
            auto load_vf = [&]() {
#pragma unroll
                for (int i = 0; i < 4; i++) ldsm_x4(vf[i & 1][i >> 1], va + (i & 1) * 256 + (i >> 1) * 4096);
            };
            load_vf();
            float scale = to_scale(fmaxf(fmaxf(fmaxf(m4.x, m4.y), fmaxf(m4.z, m4.w)) * minv, xb) * c24);
            uint32_t oa = l16 + wq * 512;
            asm volatile("" : "+f"(scale), "+r"(oa), "+r"(va));
            FS(7, __float_as_uint(scale));
            if (!C) named_bar(6, 160);
            if (C) mbar_wait(sb + B_SB + 8 * (s & 1), ph);
            float sv[5][2];
#pragma unroll
            for (int j = 0; j < 5; j++) lds64f(sv[j][0], sv[j][1], l8 + SM_S + j * 256);
            if (!C) mbar_wait(sb + B_SB + 8 * (s & 1), ph);
            FS(6, 0);
            uint32_t p[5];
            {
                float sr[5][2];
#pragma unroll
                for (int j = 0; j < 5; j++) lds64f(sr[j][0], sr[j][1], l8 + SM_S + 1280 + j * 256);
                lds64(vm[0][0], vm[0][1], l8 + SM_VM + wq * 512);
                lds64(vm[1][0], vm[1][1], l8 + SM_VM + wq * 512 + 256);
#pragma unroll
                for (int j = 0; j < 5; j++) {
                    sv[j][0] += sr[j][0];
                    sv[j][1] += sr[j][1];
                }
                float mx = fmaxf(fmaxf(fmaxf(sv[0][0], sv[0][1]), fmaxf(sv[1][0], sv[1][1])), fmaxf(fmaxf(sv[2][0], sv[2][1]), fmaxf(sv[3][0], sv[3][1])));
                mx = fmaxf(mx, fmaxf(sv[4][0], sv[4][1]));
                {
                    const float m1 = __shfl_xor_sync(0xffffffffu, mx, 1), m2 = __shfl_xor_sync(0xffffffffu, mx, 2), m3 = __shfl_xor_sync(0xffffffffu, mx, 3);
                    mx = fmaxf(fmaxf(mx, m1), fmaxf(m2, m3));
                }
#pragma unroll
                for (int jj = 0; jj < 5; jj++) {
                    const int j = (jj + 1) % 5;
                    asm("ex2.approx.ftz.f32 %0, %1;" : "=f"(sv[j][0]) : "f"(sv[j][0] - mx));
                    asm("ex2.approx.ftz.f32 %0, %1;" : "=f"(sv[j][1]) : "f"(sv[j][1] - mx));
                    p[j] = pack_bf16(sv[j][0], sv[j][1]);
                }
            }
            FS(0, p[0]);
            uint32_t b[4][4];
            const uint32_t one4[4] = {0x3f803f80u, 0x3f803f80u, 0x3f803f80u, 0x3f803f80u};
            float zs[4];
            {
                float o0[2][4], o1[2][4];
                mma_z(o0[0], vf[0][0], p[1], p[2]);
                mma_z(o0[1], vf[1][0], p[1], p[2]);
                mma_z(o1[0], vf[0][1], p[3], p[4]);
                mma_z(o1[1], vf[1][1], p[3], p[4]);
                mma_k8(o0[0], vm[0][0], vm[0][1], p[0]);
                mma_k8(o0[1], vm[1][0], vm[1][1], p[0]);
                float z2[4];
                mma_z(zs, one4, p[1], p[2]);
                mma_z(z2, one4, p[3], p[4]);
                mma_k8(zs, one4[0], one4[1], p[0]);
                zs[0] += z2[0]; zs[1] += z2[1];
                uint32_t ow[4];
#pragma unroll
                for (int m = 0; m < 2; m++) {
                    ow[2 * m] = pack_bf16(o0[m][0] + o1[m][0], o0[m][1] + o1[m][1]);
                    ow[2 * m + 1] = pack_bf16(o0[m][2] + o1[m][2], o0[m][3] + o1[m][3]);
                }
                stsm_x4(oa + SM_O, ow[0], ow[1], ow[2], ow[3]);
                FS(2, 0);
                b[0][0] = movm(ow[0]); b[0][1] = movm(ow[1]);
                __syncwarp();
                asm volatile("ldmatrix.sync.aligned.m8n8.x2.trans.shared.b16 {%0,%1}, [%2];" : "=r"(b[0][2]), "=r"(b[0][3]) : "r"(oa + SM_O + 256));
            }
            float acc[3][2][4];
            named_bar(3, 128);
#pragma unroll
            for (int i = 1; i < 4; i++) ldsm_x4_t(b[i], l16 + SM_O + ((wq + i) & 3) * 512);
#pragma unroll
            for (int c = 0; c < 2; c++)
#pragma unroll
                for (int t = 0; t < 3; t++) mma_z(acc[t][c], wo[t][c], b[0][2 * c], b[0][2 * c + 1]);
            float z0, z1;
            asm volatile("rcp.approx.ftz.f32 %0, %1;" : "=f"(z0) : "f"(zs[0]));
            asm volatile("rcp.approx.ftz.f32 %0, %1;" : "=f"(z1) : "f"(zs[1]));
            asm volatile("{\n.reg .pred p;\nsetp.eq.s32 p, %1, 0;\n@p bar.sync 12, 160;\n@p ld.shared.f32 %0, [%2];\n}" : "+f"(scale) : "r"(s), "r"(sb + SM_SC) : "memory");
            z0 *= scale; z1 *= scale;
            FS(3, b[1][0]);
#pragma unroll
            for (int i = 1; i < 4; i++)
#pragma unroll
                for (int c = 0; c < 2; c++)
#pragma unroll
                    for (int t = 0; t < 3; t++) mma_bf16(acc[t][c], wo[t][2 * i + c], b[i][2 * c], b[i][2 * c + 1]);
            {
                uint32_t w[6];
#pragma unroll
                for (int t = 0; t < 3; t++) {
                    w[2 * t] = pack_f16(fmaf(acc[t][1][0], z0, acc[t][0][0] * z0), fmaf(acc[t][1][1], z1, acc[t][0][1] * z1));
                    w[2 * t + 1] = pack_f16(fmaf(acc[t][1][2], z0, acc[t][0][2] * z0), fmaf(acc[t][1][3], z1, acc[t][0][3] * z1));
                }
                FS(8, w[5]);
                asm volatile("red.relaxed.gpu.global.add.noftz.v4.f16x2 [%0], {%1,%2,%3,%4};" :: "l"(dst), "r"(w[0]), "r"(w[1]), "r"(w[2]), "r"(0x3c00u) : "memory");
                asm volatile("red.relaxed.gpu.global.add.noftz.v4.f16x2 [%0], {%1,%2,%3,%4};" :: "l"(dst + 4096), "r"(w[3]), "r"(w[4]), "r"(w[5]), "r"(0x3c00u) : "memory");
            }
            FS(9, 0);
            if (s == 0) TSQ(5);
            bar_arrive(4, 384);
            const uint32_t t0 = clock32();
            minv = __uint_as_float(0x7f000000u - __float_as_uint(scale));
            if (lane_o == 0) {
                if (wq == 0) sts32(sb + SM_SC + 8, __float_as_uint(minv));
                if (s + 3 < NSEG) {
                    if (wq == 0) mbar_expect(sb + B_SB + 8 * (s & 1), C ? 2560 : 1280 + 2048);
                    if (wq == 1 && s > 0 && s + 5 < NSEG) mbar_expect(sb + B_XT + ((s & 1) ? 0 : 16) + 4 * ((s + 1) & 2), (s & 1) ? 32768 : 40960);
                    if (wq == 3 && !C) mbar_expect(sb + B_VX + 8 * (s & 1), 8192);
                }
            }
            __syncwarp();
            if (s == 1) {
                if (!C) pad_code<PADC>();
                int lane = lane_o;
                asm volatile("" : "+r"(lane));
                if (wq == 3) xmax_gather(lane, sb);
                __syncwarp();
            }
            if (!C) load_kf(kf, (s + 1) & 3);
            const uint4* src = reinterpret_cast<const uint4*>(dst + (wq * 16 - role * 32) * 1024);
            dst += n3 == 0 ? -256 : 128;
            asm volatile("" : "+l"(dst));
            const int xp = (s + 5) >> 1, kb = wq + ((s & 1) ? 2 * role : 4 + 3 * role);
            const bool xl = !C && xp < NSEG / 2 && wq < ((s & 1) ? 2 : 3 - role);
            const uint32_t xs = wq == 3 && (s & 1) == 0 && xp < NSEG / 2;
            const uint32_t xd = sb + SM_X + (rx + kb >= 13 ? rx + kb - 13 : rx + kb) * 8192;
            mx2 = poll_mem(src, l16 + SM_M + wq * 2304, t0, [&]() {
                if (xs && lane_o < 2) asm volatile("mbarrier.arrive.relaxed.cluster.shared::cluster.b64 _, [%0];" :: "r"(mapa(sb + B_XF, lane_o)) : "memory");
                if (!C && (xl || s == 0) && (s & 1) == 0) mbar_wait(sb + B_XF, (uint32_t)(s >> 1) & 1u);
                if (lane_o == 0) {
                    if (xl) tma_2d_mc(xd, &tmx2, ((s & 1) ? kb + 5 : kb - 4) * 64, xp * 64, sb + B_XT + ((s & 1) ? 0 : 16) + 8 * (xp & 1));
                    if (!C && s == 0 && role == 1) tma_2d_mc(sb + SM_X + (9 + wq) * 8192, &tmx2, (wq + 5) * 64, 128, sb + B_XT);
                }
                __syncwarp();
            });
            if ((s & 1) == 0) rx = rx >= 4 ? rx - 4 : rx + 9;
            if (s == 0) TSQ(6);
            b3 = n3;
        }
        if (!C) bar_arrive(2, 384);
        };
        if (role == 2) helper_loop(Flag<true>()); else helper_loop(Flag<false>());
    }
    TS3C(1);
    if (role == 2 && warp >= 4) last_rows();
    cluster_sync_all();
}

extern "C" void kernel_launch(void* const* d_in, const int* in_sizes, int n_in, void* d_out, int out_size) {
    const bf16* x = (const bf16*)d_in[0];
    const bf16* mem0 = (const bf16*)d_in[1];
    const bf16* Wq = (const bf16*)d_in[2];
    const bf16* Wk = (const bf16*)d_in[3];
    const bf16* Wv = (const bf16*)d_in[4];
    const bf16* Wo = (const bf16*)d_in[5];
    const bf16* logA = (const bf16*)d_in[8];
    const bf16* Aim = (const bf16*)d_in[9];
    const bf16* Cre = (const bf16*)d_in[10];
    const bf16* Cim = (const bf16*)d_in[11];
    const bf16* logdt = (const bf16*)d_in[12];
    const bf16* dskip = (const bf16*)d_in[13];
    const bf16* gw = (const bf16*)d_in[14];
    bf16* out = (bf16*)d_out;
    static bool attr_done = false;
    typedef CUresult (*EncFn)(CUtensorMap*, CUtensorMapDataType, cuuint32_t, void*, const cuuint64_t*, const cuuint64_t*, const cuuint32_t*,
                              const cuuint32_t*, CUtensorMapInterleave, CUtensorMapSwizzle, CUtensorMapL2promotion, CUtensorMapFloatOOBfill);
    static EncFn enc = nullptr;
    if (!attr_done) {
        void* fn = nullptr;
        cudaDriverEntryPointQueryResult qr;
        cudaGetDriverEntryPoint("cuTensorMapEncodeTiled", &fn, cudaEnableDefault, &qr);
        enc = (EncFn)fn;
        cudaFuncSetAttribute(k_chain, cudaFuncAttributeMaxDynamicSharedMemorySize, 232448);
        cudaFuncSetAttribute(k_side, cudaFuncAttributeMaxDynamicSharedMemorySize, SIDE_SMEM);
        attr_done = true;
    }
    CUtensorMap tmw[3];
    for (int i = 0; i < 3; i++) {
        const cuuint64_t dims[2] = {(cuuint64_t)HD, (cuuint64_t)DM};
        const cuuint64_t strides[1] = {(cuuint64_t)HD * 2};
        const cuuint32_t box[2] = {64, 64};
        const cuuint32_t es[2] = {1, 1};
        enc(&tmw[i], CU_TENSOR_MAP_DATA_TYPE_BFLOAT16, 2, (void*)(i == 0 ? Wq : (i == 1 ? Wk : Wv)), dims, strides, box, es, CU_TENSOR_MAP_INTERLEAVE_NONE,
            CU_TENSOR_MAP_SWIZZLE_128B, CU_TENSOR_MAP_L2_PROMOTION_L2_256B, CU_TENSOR_MAP_FLOAT_OOB_FILL_NONE);
    }
    CUtensorMap tmo;
    {
        const cuuint64_t dims[2] = {(cuuint64_t)DM, (cuuint64_t)HD};
        const cuuint64_t strides[1] = {(cuuint64_t)DM * 2};
        const cuuint32_t box[2] = {64, 128};
        const cuuint32_t es[2] = {1, 1};
        enc(&tmo, CU_TENSOR_MAP_DATA_TYPE_BFLOAT16, 2, (void*)Wo, dims, strides, box, es, CU_TENSOR_MAP_INTERLEAVE_NONE,
            CU_TENSOR_MAP_SWIZZLE_128B, CU_TENSOR_MAP_L2_PROMOTION_L2_128B, CU_TENSOR_MAP_FLOAT_OOB_FILL_NONE);
    }
    CUtensorMap tmx2;
    {
        const cuuint64_t dims[2] = {(cuuint64_t)DM, (cuuint64_t)S_LEN};
        const cuuint64_t strides[1] = {(cuuint64_t)DM * 2};
        const cuuint32_t box[2] = {64, 64};
        const cuuint32_t es[2] = {1, 1};
        enc(&tmx2, CU_TENSOR_MAP_DATA_TYPE_BFLOAT16, 2, (void*)x, dims, strides, box, es, CU_TENSOR_MAP_INTERLEAVE_NONE,
            CU_TENSOR_MAP_SWIZZLE_128B, CU_TENSOR_MAP_L2_PROMOTION_L2_128B, CU_TENSOR_MAP_FLOAT_OOB_FILL_NONE);
    }
    CUtensorMap tmm;
    {
        const cuuint64_t dims[2] = {(cuuint64_t)DM, (cuuint64_t)MEMT};
        const cuuint64_t strides[1] = {(cuuint64_t)DM * 2};
        const cuuint32_t box[2] = {64, (cuuint32_t)MEMT};
        const cuuint32_t es[2] = {1, 1};
        enc(&tmm, CU_TENSOR_MAP_DATA_TYPE_BFLOAT16, 2, (void*)mem0, dims, strides, box, es, CU_TENSOR_MAP_INTERLEAVE_NONE,
            CU_TENSOR_MAP_SWIZZLE_128B, CU_TENSOR_MAP_L2_PROMOTION_L2_128B, CU_TENSOR_MAP_FLOAT_OOB_FILL_NONE);
    }
    k_chain<<<NCTA, 384, 232448>>>(tmw[0], tmw[1], tmw[2], tmx2, tmo, tmm, x);
    {
        cudaLaunchConfig_t cfg = {};
        cfg.gridDim = dim3(SD_NCTA); cfg.blockDim = dim3(512); cfg.dynamicSmemBytes = SIDE_SMEM; cfg.stream = cudaStreamPerThread;
        cudaLaunchAttribute at[1];
        at[0].id = cudaLaunchAttributeProgrammaticStreamSerialization;
        at[0].val.programmaticStreamSerializationAllowed = 1;
        cfg.attrs = at; cfg.numAttrs = 1;
        cudaLaunchKernelEx(&cfg, k_side, tmo, x, logA, Aim, Cre, Cim, logdt, Wo, dskip, gw, out);
    }
}
```

```cpp
#include <cuda_runtime.h>
#include <cuda.h>
#include <cuda_bf16.h>
#include <stdint.h>

typedef __nv_bfloat16 bf16;
#define LDV4 "ld.volatile.global.v4.u32 {%0,%1,%2,%3}, [%4];"
#define STV4 "st.volatile.global.v4.u32 [%0], {%1,%2,%3,%4};"
#define STV2 "st.volatile.global.v2.u32 [%0], {%1,%2};"

constexpr int S_LEN = 2048, DM = 576, NH = 32, DH = 128, HD = 4096, MEMT = 8, SEG = 32, NSEG = 64, NST = 128;

__device__ __align__(128) bf16 g_gate[S_LEN];
constexpr int NCTA = NH * 3;
__device__ __align__(1024) unsigned char g_acc[96 * 1024];
__device__ __align__(128) uint2 g_norm[NCTA];
__device__ __align__(128) uint4 g_wv[NH][2];
__device__ __align__(128) uint4 g_rx[NSEG][2];
__device__ __align__(128) unsigned char g_qkv[NSEG][NH][3][10240];
__device__ __align__(128) bf16 g_ox[S_LEN * HD];
__device__ __align__(128) uint4 g_fp[8][36][6][128];
__device__ __align__(128) unsigned g_flag[NH * NSEG];
__device__ __align__(128) unsigned g_prog[8 * 64];
__device__ unsigned g_gcnt[64];
__device__ unsigned g_epoch;
__device__ __align__(128) uint2 g_tick;
__device__ __align__(128) bf16 g_y[DM * S_LEN];

#define TS3(slot) do {} while (0)
#define TS3P(slot) do {} while (0)
#define TSQ(slot) do {} while (0)
#define TS3W(slot) do {} while (0)
#define TSS(row, slot) do {} while (0)
#define TS3C(slot) do {} while (0)
#define TST(slot) do {} while (0)
#define TSA(seg, slot) do {} while (0)
#define TSG(i) do {} while (0)
#define FS(i, dep) do {} while (0)
__device__ __forceinline__ uint32_t smem_u32(const void* p) { return (uint32_t)__cvta_generic_to_shared(p); }
__device__ __forceinline__ float bf16r(float x) { return __bfloat162float(__float2bfloat16_rn(x)); }
__device__ __forceinline__ uint32_t pack_bf16(float lo, float hi) {
    __nv_bfloat162 v = __floats2bfloat162_rn(lo, hi);
    return *reinterpret_cast<uint32_t*>(&v);
}
__device__ __forceinline__ void ldsm_x4(uint32_t (&r)[4], uint32_t addr) {
    asm volatile("ldmatrix.sync.aligned.m8n8.x4.shared.b16 {%0,%1,%2,%3}, [%4];"
                 : "=r"(r[0]), "=r"(r[1]), "=r"(r[2]), "=r"(r[3]) : "r"(addr));
}
__device__ __forceinline__ void ldsm_x4_t(uint32_t (&r)[4], uint32_t addr) {
    asm volatile("ldmatrix.sync.aligned.m8n8.x4.trans.shared.b16 {%0,%1,%2,%3}, [%4];"
                 : "=r"(r[0]), "=r"(r[1]), "=r"(r[2]), "=r"(r[3]) : "r"(addr));
}
__device__ __forceinline__ void mma_bf16(float (&d)[4], const uint32_t (&a)[4], uint32_t b0, uint32_t b1) {
    asm volatile("mma.sync.aligned.m16n8k16.row.col.f32.bf16.bf16.f32 {%0,%1,%2,%3}, {%4,%5,%6,%7}, {%8,%9}, {%0,%1,%2,%3};"
                 : "+f"(d[0]), "+f"(d[1]), "+f"(d[2]), "+f"(d[3])
                 : "r"(a[0]), "r"(a[1]), "r"(a[2]), "r"(a[3]), "r"(b0), "r"(b1));
}
__device__ __forceinline__ uint2 ld_vol_u2(const uint2* p) {
    uint2 v; asm volatile("ld.volatile.global.v2.u32 {%0,%1}, [%2];" : "=r"(v.x), "=r"(v.y) : "l"(p) : "memory"); return v;
}
__device__ __forceinline__ void st_vol_u2(uint2* p, uint2 v) {
    asm volatile(STV2 :: "l"(p), "r"(v.x), "r"(v.y) : "memory");
}
__device__ __forceinline__ unsigned ld_acq(const unsigned* p) {
    unsigned v; asm volatile("ld.acquire.gpu.global.u32 %0, [%1];" : "=r"(v) : "l"(p) : "memory"); return v;
}
#define NS 10
#define NP 4
#define GATE_A 950
#define GATE_B 450
#define GATE_P 1800u
#define RLX_SLEEP 300
#define VX_DELAY 100
#define UNGATE_G 3
#define W14_SLEEP 60
#define GL_A 1150
#define GL_B 530
#define GS_A 1300
#define GS_B 480
#define NC1 3
#define NC1C 5
#define KPRE 34
#define PADC 0
#define PAD1 0
#define PAD2 0
#define PAD3 0
#define PAD4 0
#define HS 1
#define PDC 0
#define PDS 0
#define KG1 20
#define WO_SLEEP 200
#define WO_LAG 500
#define TM 29
#define TM2 (TM - 1)
#define TL_DELAY 600
#define POLL_DELAY 590
#define UNGATE 6
constexpr unsigned SPIN_LIMIT = 1u << 20;
constexpr int NATT = NSEG - 2;

constexpr int SD_CH = 16;
constexpr int SD_NCTA = DM / SD_CH;
constexpr int SD_ROW = 528;
constexpr int SD_U = 8 * SD_ROW;
constexpr int SD_TAP = 5888;
constexpr int SD_CPY = 1376 * 2;
constexpr int SD_WSTR = SD_TAP + 2 * SD_CPY;
constexpr int SD_SMEM = SD_CH * SD_U + 8 * SD_WSTR;
constexpr int O_U = 79, O_U3 = 911, O_U4 = 1055, O_W79 = 1023, O_W35 = 1151, O_W610 = 1279, O_W511 = 1487;

__device__ __forceinline__ uint32_t lds32(uint32_t a) { uint32_t v; asm volatile("ld.shared.u32 %0, [%1];" : "=r"(v) : "r"(a)); return v; }
__device__ __forceinline__ void sts32(uint32_t a, uint32_t v) { asm volatile("st.shared.u32 [%0], %1;" :: "r"(a), "r"(v) : "memory"); }
__device__ __forceinline__ uint4 lds128(uint32_t a) {
    uint4 v; asm volatile("ld.shared.v4.u32 {%0,%1,%2,%3}, [%4];" : "=r"(v.x), "=r"(v.y), "=r"(v.z), "=r"(v.w) : "r"(a) : "memory"); return v;
}
__device__ __forceinline__ void tap_tile(uint32_t (&t)[4], uint32_t a) {
    asm volatile("ld.volatile.shared.u32 %0, [%4];\nld.volatile.shared.u32 %1, [%4+-16];\nld.volatile.shared.u32 %2, [%4+16];\nld.volatile.shared.u32 %3, [%4];"
                 : "=r"(t[0]), "=r"(t[1]), "=r"(t[2]), "=r"(t[3]) : "r"(a));
}
constexpr uint32_t sd_pass(int type, int dl, int o, int d0, int d1) { return (uint32_t)(type | dl << 2 | d0 << 8 | d1 << 12 | o << 17); }
__constant__ uint32_t SD_PASS[14] = {sd_pass(0, 0, O_U, 0, 2), sd_pass(0, 1, O_U + 96, 0, 2), sd_pass(0, 2, O_U + 192, 0, 4), sd_pass(0, 3, O_U + 288, 0, 2), sd_pass(1, 0, O_U3, 8, 8),
                                     sd_pass(0, 4, O_U + 384, 0, 2), sd_pass(1, 0, O_U4, 8, 15), sd_pass(0, 5, O_U + 480, 0, 2), sd_pass(0, 6, O_U + 576, 0, 4), sd_pass(0, 7, O_U + 672, 0, 2),
                                     sd_pass(2, 0, O_W35, 2, 8), sd_pass(3, 0, O_W79, 2, 4), sd_pass(2, 1, O_W610, 4, 8), sd_pass(3, 0, O_W511, 8, 15)};
__device__ __forceinline__ uint32_t band2(int x, int lo, int hi) { return (x >= lo && x <= hi ? 0x3f80u : 0u) | (x + 1 >= lo && x + 1 <= hi ? 0x3f800000u : 0u); }
__device__ __forceinline__ void mma_z(float (&d)[4], const uint32_t (&a)[4], uint32_t b0, uint32_t b1);
__device__ __forceinline__ void put_tap(uint32_t a, float v) {
    asm volatile("{\n.reg .b16 h;\ncvt.rn.bf16.f32 h, %1;\nst.shared.b16 [%0], h;\nst.shared.b16 [%0+%2], h;\n}" :: "r"(a), "f"(v), "n"(SD_CPY - 2) : "memory");
}

__device__ __forceinline__ void named_bar(int id, int n) { asm volatile("bar.sync %0, %1;" :: "r"(id), "r"(n) : "memory"); }
__device__ __forceinline__ uint32_t pack_f16(float lo, float hi) {
    uint32_t r; asm("cvt.rn.f16x2.f32 %0, %1, %2;" : "=r"(r) : "f"(hi), "f"(lo)); return r;
}
__device__ __forceinline__ void cexp_t(float lr, float turns, float& re, float& im) {
    float m;
    asm("ex2.approx.ftz.f32 %0, %1;" : "=f"(m) : "f"(lr));
    const float a = (turns - rintf(turns)) * 6.283185307179586f;
    re = m * __cosf(a); im = m * __sinf(a);
}
__device__ __forceinline__ void csq(float& re, float& im) { const float r = re * re - im * im; im = 2.f * re * im; re = r; }
__device__ __forceinline__ void kb_state(const float* tp, float gf, uint32_t (&a)[4][2], uint32_t (&b)[5]) {
    const float4 p0 = *reinterpret_cast<const float4*>(tp), p1 = *reinterpret_cast<const float4*>(tp + 4);
    float wr, wi;
    cexp_t(p0.x * gf, p0.y * gf, wr, wi);
    float vr = wr * p1.x - wi * p1.y, vi = wr * p1.y + wi * p1.x;
#pragma unroll
    for (int c = 0; c < 4; c++) {
        a[c][0] = pack_f16(wr, wi); a[c][1] = pack_f16(vr, vi);
        csq(wr, wi);
        if (c < 3) csq(vr, vi);
    }
    b[0] = pack_f16(p0.z * wr - p0.w * wi, -p0.z * wi - p0.w * wr);
    float er = wr * p1.z - wi * p1.w, ei = wr * p1.w + wi * p1.z;
#pragma unroll
    for (int c = 0; c < 4; c++) {
        b[1 + c] = pack_f16(p0.z * er - p0.w * ei, -p0.z * ei - p0.w * er);
        if (c < 3) csq(er, ei);
    }
}
__device__ __forceinline__ uint32_t bf2_mul(uint32_t a, uint32_t b) { uint32_t r; asm("mul.rn.bf16x2 %0, %1, %2;" : "=r"(r) : "r"(a), "r"(b)); return r; }
__device__ __forceinline__ uint32_t bf2_add(uint32_t a, uint32_t b) { uint32_t r; asm("add.rn.bf16x2 %0, %1, %2;" : "=r"(r) : "r"(a), "r"(b)); return r; }
__device__ __forceinline__ uint32_t bf2_sub(uint32_t a, uint32_t b) { uint32_t r; asm("sub.rn.bf16x2 %0, %1, %2;" : "=r"(r) : "r"(a), "r"(b)); return r; }
__device__ __forceinline__ void wait_cnt(const unsigned* p, unsigned target) {
    unsigned it = 0;
    while ((int)(ld_acq(p) - target) < 0 && ++it < SPIN_LIMIT) __nanosleep(64);
}
__device__ __forceinline__ uint32_t gtime32() { uint32_t t; asm volatile("mov.u32 %0, %%globaltimer_lo;" : "=r"(t) :: "memory"); return t; }
__device__ __forceinline__ void gate(uint32_t tick_addr, uint32_t ga = GATE_A, uint32_t gb = GATE_B) {
    uint32_t t1, p;
    asm volatile("ld.volatile.shared.v2.u32 {%0,%1}, [%2];" : "=r"(t1), "=r"(p) : "r"(tick_addr) : "memory");
    uint32_t d = gtime32() - t1;
    if (d < 4u * p) {
        d -= d >= 2u * p ? 2u * p : 0u;
        d -= d >= p ? p : 0u;
        if (d + ga >= p && d + gb < p) {
            const uint32_t t2 = gtime32() + (p - gb - d);
            while ((int)(gtime32() - t2) < 0) {}
        }
    }
}

__device__ __forceinline__ void read_tick(uint32_t tick_addr) {
    const uint2 tk = ld_vol_u2(&g_tick);
    uint32_t p = tk.x - tk.y;
    p = p > GATE_P + 100u ? GATE_P + 100u : p;
    asm volatile("st.volatile.shared.v2.u32 [%0], {%1,%2};" :: "r"(tick_addr), "r"(tk.x), "r"(p) : "memory");
}

__device__ __forceinline__ void s4d_phase(unsigned char* smem_raw, const bf16* __restrict__ x, const bf16* __restrict__ logA,
                                          const bf16* __restrict__ Aim, const bf16* __restrict__ Cre, const bf16* __restrict__ Cim,
                                          const bf16* __restrict__ logdt, const bf16* __restrict__ dskip, const bf16* __restrict__ wslice) {
    const int tid = threadIdx.x, warp = __shfl_sync(0xffffffffu, tid >> 5, 0), lane = tid & 31;
    const int d0 = blockIdx.x * SD_CH;
    float* tab = reinterpret_cast<float*>(smem_raw + SD_CH * SD_U + warp * SD_WSTR);
    const uint32_t wb = smem_u32(tab);
    const int g = lane >> 2, tq = lane & 3;
    uint2 prm[4];
    float ldt;
    auto load_prm = [&](int d) {
        prm[0] = __ldg(reinterpret_cast<const uint2*>(logA + d * NST) + lane); prm[1] = __ldg(reinterpret_cast<const uint2*>(Aim + d * NST) + lane);
        prm[2] = __ldg(reinterpret_cast<const uint2*>(Cre + d * NST) + lane); prm[3] = __ldg(reinterpret_cast<const uint2*>(Cim + d * NST) + lane);
        ldt = __bfloat162float(logdt[d]);
    };
    load_prm(d0 + warp);
    for (int i = lane; i < 2 * SD_CPY / 16; i += 32) reinterpret_cast<uint4*>(tab + SD_TAP / 4)[i] = make_uint4(0u, 0u, 0u, 0u);
    TS3(20);
#pragma unroll 1
    for (int ch = 0; ch < 2; ch++) {
        const int d = d0 + 8 * ch + warp;
        const uint32_t ub = smem_u32(smem_raw) + (8 * ch + warp) * SD_U;
        float k2048 = 0.f, sinv;
        {
            const float dt = bf16r(expf(ldt));
            uint32_t cm = __vmaxu2(__vmaxu2(prm[2].x & 0x7fff7fffu, prm[2].y & 0x7fff7fffu), __vmaxu2(prm[3].x & 0x7fff7fffu, prm[3].y & 0x7fff7fffu));
            cm = __reduce_max_sync(0xffffffffu, max(cm << 16, cm & 0xffff0000u));
            int e = 134 - (int)(__float_as_uint(__uint_as_float(cm) * dt) >> 23);
            e = e > 100 ? 100 : (e < -100 ? -100 : e);
            const float s2 = __uint_as_float((uint32_t)(128 + e) << 23);
            sinv = __uint_as_float((uint32_t)(127 - e) << 23);
#pragma unroll
            for (int j = 0; j < 4; j++) {
                float q[4];
#pragma unroll
                for (int i = 0; i < 4; i++) { const uint32_t w = j < 2 ? prm[i].x : prm[i].y; q[i] = __uint_as_float((j & 1) ? w & 0xffff0000u : w << 16); }
                const float zl = -bf16r(expf(q[0])) * dt * 1.4426950408889634f;
                const float zt = q[1] * dt * 0.15915494309189535f;
                const float cr = s2 * (q[2] * dt), ci = s2 * (q[3] * dt);
                float ar, ai, br, bi, er, ei;
                cexp_t(zl * 8.f, zt * 8.f, ar, ai);
                cexp_t(zl * 128.f, zt * 128.f, br, bi);
                cexp_t(zl * 2048.f, zt * 2048.f, er, ei);
                k2048 += cr * er - ci * ei;
                *reinterpret_cast<float4*>(tab + (lane + 32 * j) * 8) = make_float4(zl, zt, cr, ci);
                *reinterpret_cast<float4*>(tab + (lane + 32 * j) * 8 + 4) = make_float4(ar, ai, br, bi);
            }
#pragma unroll
            for (int o = 16; o; o >>= 1) k2048 += __shfl_xor_sync(0xffffffffu, k2048, o);
        }
        __syncwarp();
        {
            float kc[5][4];
#pragma unroll
            for (int i = 0; i < 5; i++) { kc[i][0] = kc[i][1] = kc[i][2] = kc[i][3] = 0.f; }
            const float gf = (float)g;
#pragma unroll 2
            for (int ks = 0; ks < 16; ks++) {
                uint32_t a0[4][2], a1[4][2], b0[5], b1[5];
                kb_state(tab + (8 * ks + tq) * 8, gf, a0, b0);
                kb_state(tab + (8 * ks + 4 + tq) * 8, gf, a1, b1);
#pragma unroll
                for (int i = 0; i < 5; i++) {
                    const int c = i > 0 ? i - 1 : 0;
                    asm volatile("mma.sync.aligned.m16n8k16.row.col.f32.f16.f16.f32 {%0,%1,%2,%3}, {%4,%5,%6,%7}, {%8,%9}, {%0,%1,%2,%3};"
                                 : "+f"(kc[i][0]), "+f"(kc[i][1]), "+f"(kc[i][2]), "+f"(kc[i][3])
                                 : "r"(a0[c][0]), "r"(a0[c][1]), "r"(a1[c][0]), "r"(a1[c][1]), "r"(b0[i]), "r"(b1[i]));
                }
            }
            const uint32_t tp = wb + SD_TAP;
            const uint32_t a0 = tp + 2 * (O_U + 96 * g - 4 * tq);
            const uint32_t a2 = tp + 2 * (((g & 1) ? O_U + 96 * (2 * (g & 3)) : ((g & 2) ? O_W35 : O_W79 + 1)) - 32 - 8 * tq - (g >> 2));
            const uint32_t a3 = tp + 2 * (((g & 1) ? O_W35 : O_W610 + 1) - 64 - 16 * tq - (g >> 1));
            const uint32_t a4 = tp + 2 * (-128 - 32 * tq - g);
#pragma unroll
            for (int c = 0; c < 4; c++) {
                const int e = (c & 1) * 16 + (c >> 1) * 8;
                const bool first = c == 0 && lane == 0;
                put_tap(a0 - e / 4, kc[0][c] * sinv);
                put_tap(a0 - 32 - e / 4, kc[1][c] * sinv);
                put_tap(first ? tp + 2 * (O_U - 32) : a2 - e / 2, kc[2][c] * sinv);
                put_tap(first ? tp + 2 * (O_W79 - 63) : a3 - e, kc[3][c] * sinv);
                put_tap(first ? tp + 2 * (O_W610 - 127) : a4 + 2 * (O_W511 + 1 - e), kc[4][c] * sinv);
                if ((g & 1) == 0) {
                    put_tap(a4 + 2 * (O_U4 - e), kc[4][c] * sinv);
                    put_tap(first ? tp + 2 * (O_U3 - 128) : a4 + 2 * (O_U4 + 1 - e), kc[4][c] * sinv);
                }
            }
            if (lane == 0) {
                put_tap(tp + 2 * (O_U + 96 - 32), kc[2][0] * sinv);
                put_tap(tp + 2 * (O_U + 192 - 64), kc[3][0] * sinv);
                put_tap(tp + 2 * (O_W511 - 255), k2048 * sinv);
                put_tap(tp + 2 * (O_U4 - 255), k2048 * sinv);
            }
        }
        TS3(21 + 2 * ch);
        if (ch == 0) named_bar(1, 384);
        else {
#pragma unroll
            for (int i = 0; i < 4; i++) asm volatile("prefetch.global.L2 [%0];" :: "l"(wslice + (size_t)((tid & 127) + 128 * i) * DM));
        }
        __syncwarp();
        if (tid == 0) TSS(18, 4 * ch);
        const uint32_t sh = wb + 80 + 11 * SD_ROW;
#pragma unroll
        for (int p = 0; p < 8; p++) {
            uint4 v;
            asm volatile("ld.shared.v4.u32 {%0,%1,%2,%3}, [%4];" : "=r"(v.x), "=r"(v.y), "=r"(v.z), "=r"(v.w) : "r"(ub + p * SD_ROW + lane * 16) : "memory");
            uint32_t pv = __shfl_up_sync(0xffffffffu, v.w, 1);
            pv = lane == 0 ? 0u : pv;
            asm volatile("st.shared.v4.u32 [%0], {%1,%2,%3,%4};" :: "r"(sh + (p - 8) * SD_ROW + lane * 16), "r"(__byte_perm(pv, v.x, 0x5432)), "r"(__byte_perm(v.x, v.y, 0x5432)),
                         "r"(__byte_perm(v.y, v.z, 0x5432)), "r"(__byte_perm(v.z, v.w, 0x5432)) : "memory");
            if (p >= 5) asm volatile("st.shared.v4.u32 [%0], {%1,%2,%3,%4};" :: "r"(sh + (p - 16) * SD_ROW + lane * 16), "r"(pv), "r"(v.x), "r"(v.y), "r"(v.z) : "memory");
        }
        __syncwarp();
        if (tid == 0) TSS(18, 4 * ch + 1);
        float acc[16][4];
#pragma unroll
        for (int i = 0; i < 16; i++) { acc[i][0] = acc[i][1] = acc[i][2] = acc[i][3] = 0.f; }
        {
            const uint32_t ka = wb + SD_TAP + ((g & 1) ? 0 : SD_CPY - 2) + 2 * (2 * tq - g);
            uint32_t b[16][2], b2[14][2];
#pragma unroll
            for (int k = 0; k < 16; k++) { b[k][0] = b[k][1] = 0u; if (k < 14) b2[k][0] = b2[k][1] = 0u; }
#pragma unroll 1
            for (int ps = 0; ps < 14; ps++) {
                const uint32_t pw = __shfl_sync(0xffffffffu, SD_PASS[ps], 0), type = pw & 3u, kp = ka + (pw >> 16);
                const int dl = (pw >> 2) & 7, d0 = (pw >> 8) & 15, d1 = (pw >> 12) & 15;
                uint32_t t[2][4];
                tap_tile(t[0], kp - 32 * d0);
                if (type == 0) {
                    const int p = (lane & 7) - dl;
                    const uint32_t ra = (p < 0 ? sh : ub) + p * SD_ROW + (lane >> 3) * 16;
#pragma unroll
                    for (int k = 0; k < 8; k++)
                        asm volatile("ldmatrix.sync.aligned.m8n8.x4.shared.b16 {%0,%1,%2,%3}, [%4];"
                                     : "=r"(b[2 * k][0]), "=r"(b[2 * k][1]), "=r"(b[2 * k + 1][0]), "=r"(b[2 * k + 1][1]) : "r"(ra + k * 64));
                } else if (type == 2) {
                    const int p = (lane & 15) - 11, xo = 2 * tq - g;
                    const uint32_t qa = (p < 0 ? sh : ub) + p * SD_ROW + (lane >> 4) * 16;
                    const int lx = 6 - 5 * dl, hx = 8 - 3 * dl, ly = 2 - 2 * dl, hy = 4 + 2 * dl;
                    const uint32_t sel[4] = {band2(xo, lx, hx), band2(xo, ly, hy), band2(xo + 8, lx, hx), band2(xo + 8, ly, hy)};
#pragma unroll
                    for (int k = 0; k < 14; k++) {
                        uint32_t q[4];
                        ldsm_x4_t(q, qa + k * 32);
#pragma unroll
                        for (int i = 0; i < 2; i++) {
                            float w[4];
                            mma_z(w, sel, q[2 * i], q[2 * i + 1]);
                            b[k][i] = pack_bf16(w[0], w[1]);
                            b2[k][i] = pack_bf16(w[2], w[3]);
                        }
                    }
                } else if (type == 3) {
#pragma unroll
                    for (int k = 0; k < 14; k++) { b[k][0] = b2[k][0]; b[k][1] = b2[k][1]; }
                }
#pragma unroll
                for (int d = 0; d < 16; d += 2) {
                    if (d >= 8 || d >= d0) {
                        tap_tile(t[1], kp - 32 * (d + 1));
#pragma unroll
                        for (int k = 0; k + d < 16; k++) mma_bf16(acc[k + d], t[0], b[k][0], b[k][1]);
                        if ((d == 2 || d == 4 || d == 8) && d == d1) break;
                        if (d < 14) tap_tile(t[0], kp - 32 * (d + 2));
#pragma unroll
                        for (int k = 0; k + d + 1 < 16; k++) mma_bf16(acc[k + d + 1], t[1], b[k][0], b[k][1]);
                    }
                }
            }
        }
        __syncwarp();
        if (tid == 0) TSS(18, 4 * ch + 2);
        load_prm(d0 + 8 + warp);
        if (ch == 0) {
            if (lane == 0) {
                unsigned ep;
                asm volatile("ld.volatile.global.u32 %0, [%1];" : "=r"(ep) : "l"(&g_epoch) : "memory");
                wait_cnt(&g_gcnt[0], SD_NCTA * (ep + 1u));
            }
            __syncwarp();
        }
        if (tid == 0) TSS(18, 4 * ch + 3);
        uint4 gv[8];
#pragma unroll
        for (int i = 0; i < 8; i++) gv[i] = __ldcg(reinterpret_cast<const uint4*>(g_gate) + lane + 32 * i);
        const uint32_t dd = __byte_perm(*reinterpret_cast<const unsigned short*>(dskip + d), 0u, 0x1010);
#pragma unroll
        for (int i = 0; i < 8; i++) {
            uint32_t u[4];
            ldsm_x4_t(u, ub + (lane & 7) * SD_ROW + (lane >> 3) * 16 + i * 64);
            asm volatile("stmatrix.sync.aligned.m8n8.x4.shared.b16 [%0], {%1,%2,%3,%4};"
                         :: "r"(wb + (lane + 32 * i) * 16),
                            "r"(bf2_add(pack_bf16(acc[2 * i][0], acc[2 * i][1]), bf2_mul(u[0], dd))), "r"(bf2_add(pack_bf16(acc[2 * i][2], acc[2 * i][3]), bf2_mul(u[1], dd))),
                            "r"(bf2_add(pack_bf16(acc[2 * i + 1][0], acc[2 * i + 1][1]), bf2_mul(u[2], dd))), "r"(bf2_add(pack_bf16(acc[2 * i + 1][2], acc[2 * i + 1][3]), bf2_mul(u[3], dd))) : "memory");
        }
        __syncwarp();
#pragma unroll
        for (int i = 0; i < 8; i++) {
            const uint4 y = *reinterpret_cast<const uint4*>(tab + (lane + 32 * i) * 4);
            *reinterpret_cast<uint4*>(g_y + (((lane >> 1) + 16 * i) * DM + d) * 16 + (lane & 1) * 8) =
                make_uint4(bf2_mul(bf2_sub(0x3f803f80u, gv[i].x), y.x), bf2_mul(bf2_sub(0x3f803f80u, gv[i].y), y.y),
                           bf2_mul(bf2_sub(0x3f803f80u, gv[i].z), y.z), bf2_mul(bf2_sub(0x3f803f80u, gv[i].w), y.w));
        }
        __syncwarp();
        if (ch == 0) asm volatile("bar.arrive 11, 288;" ::: "memory");
        TS3(22 + 2 * ch);
    }
}
__device__ __forceinline__ void s4d_stage_u(unsigned char* smem_raw, const bf16* __restrict__ x, int pt) {
    const int p = pt & 7, w0 = pt >> 3;
    const uint4* src = reinterpret_cast<const uint4*>(x + (size_t)(16 * w0 + p) * DM + blockIdx.x * SD_CH);
    uint32_t* dst = reinterpret_cast<uint32_t*>(smem_raw + p * SD_ROW) + w0;
#pragma unroll 1
    for (int b = 0; b < 4; b++) {
        uint4 v[2][2][2];
#pragma unroll
        for (int i = 0; i < 8; i++) v[i >> 2][(i >> 1) & 1][i & 1] = src[((b * 2 + (i >> 2)) * 256 + ((i >> 1) & 1) * 8) * (DM / 8) + (i & 1)];
#pragma unroll
        for (int i = 0; i < 4; i++) {
            const uint32_t* lo = reinterpret_cast<const uint32_t*>(&v[i >> 1][0][i & 1]);
            const uint32_t* hi = reinterpret_cast<const uint32_t*>(&v[i >> 1][1][i & 1]);
#pragma unroll
            for (int c = 0; c < 8; c++) dst[((i & 1) * 8 + c) * (SD_U / 4) + (b * 2 + (i >> 1)) * 16] = __byte_perm(lo[c >> 1], hi[c >> 1], (c & 1) ? 0x7632 : 0x5410);
        }
    }
    asm volatile("bar.arrive 1, 384;" ::: "memory");
}

constexpr int WOC = DM / 3;
constexpr int TBUF = 5 * DH * 16;
constexpr int XBUF = SEG * DM * 2;
constexpr int SM_BAR = 0;
constexpr int B_SB = 0, B_VX = 16, B_XT = 32, B_XF = 144, B_W = 64, B_E = 136;
constexpr int SM_SC = 256;
constexpr int SM_F = SM_SC + 1280;
constexpr int SM_VM = SM_F + 2048;
constexpr int SM_S = SM_VM + 2048;
constexpr int SM_O = SM_S + 2560;
constexpr int SM_M = SM_O + 2048;
constexpr int SM_WS = 19456;
constexpr int SM_T = SM_WS + 49152;
constexpr int SM_VX = SM_T + 4 * TBUF;
constexpr int SM_X = SM_VX + 2 * 8192;
constexpr int SM_X01 = SM_WS + DM * DH * 2;
__host__ __device__ constexpr int x01_off(int b) { return b < 2 ? 1024 + b * 9216 : SM_X01 + (b == 2 ? 6 : b - 3) * 9216; }
__host__ __device__ constexpr int x23_off(int b) { return b < 3 ? SM_WS + 7 * 16384 + b * 8192 : x01_off(b - 3); }
constexpr int CH_SMEM = SM_X01 + 8 * 8192;
static_assert(SM_M + DM * 16 <= SM_WS && SM_X + 13 * 8192 <= CH_SMEM && NS <= 10 && CH_SMEM <= 232448 && SM_X % 1024 == 0 && SM_X01 % 1024 == 0 && 1024 + 2 * 9216 <= SM_WS, "smem");
__device__ __forceinline__ uint32_t clock32() { uint32_t t; asm volatile("mov.u32 %0, %%clock;" : "=r"(t) :: "memory"); return t; }

__device__ __forceinline__ uint32_t mapa(uint32_t a, uint32_t rank) {
    uint32_t r; asm volatile("mapa.shared::cluster.u32 %0, %1, %2;" : "=r"(r) : "r"(a), "r"(rank)); return r;
}
__device__ __forceinline__ void st_async32(uint32_t addr, uint32_t v, uint32_t mbar) {
    asm volatile("st.async.weak.shared::cluster.mbarrier::complete_tx::bytes.b32 [%0], %1, [%2];" :: "r"(addr), "r"(v), "r"(mbar) : "memory");
}
__device__ __forceinline__ void mbar_init(uint32_t bar, uint32_t cnt) {
    asm volatile("mbarrier.init.shared::cta.b64 [%0], %1;" :: "r"(bar), "r"(cnt) : "memory");
}
__device__ __forceinline__ void mbar_expect(uint32_t bar, uint32_t bytes) {
    asm volatile("mbarrier.arrive.expect_tx.shared::cta.b64 _, [%0], %1;" :: "r"(bar), "r"(bytes) : "memory");
}
__device__ __forceinline__ void mbar_wait(uint32_t bar, uint32_t parity) {
    unsigned it = 0;
    uint32_t ok;
    do {
        ++it;
        asm volatile("{\n.reg .pred p;\nmbarrier.try_wait.parity.shared::cta.b64 p, [%1], %2;\nselp.u32 %0, 1, 0, p;\n}" : "=r"(ok) : "r"(bar), "r"(parity) : "memory");
    } while ((ok == 0u) & (it < SPIN_LIMIT));
}
__device__ __forceinline__ void mbar_wait_long(uint32_t bar, uint32_t parity) {
    unsigned it = 0;
    while (true) {
        uint32_t ok;
        asm volatile("{\n.reg .pred p;\nmbarrier.try_wait.parity.shared::cta.b64 p, [%1], %2, %3;\nselp.u32 %0, 1, 0, p;\n}"
                     : "=r"(ok) : "r"(bar), "r"(parity), "r"(20000u) : "memory");
        if (ok || ++it >= SPIN_LIMIT) break;
    }
}
__device__ __forceinline__ bool mbar_test(uint32_t bar, uint32_t parity) {
    uint32_t ok;
    asm volatile("{\n.reg .pred p;\nmbarrier.test_wait.parity.shared::cta.b64 p, [%1], %2;\nselp.u32 %0, 1, 0, p;\n}" : "=r"(ok) : "r"(bar), "r"(parity) : "memory");
    return ok != 0u;
}
__device__ __forceinline__ uint64_t policy_evict_first() {
    uint64_t pol; asm volatile("createpolicy.fractional.L2::evict_first.b64 %0, 1.0;" : "=l"(pol)); return pol;
}
__device__ __forceinline__ void cluster_sync_all() {
    asm volatile("barrier.cluster.arrive.release.aligned;\nbarrier.cluster.wait.acquire.aligned;" ::: "memory");
}
__device__ __forceinline__ uint4 ld_vol_u4(const uint4* p) {
    uint4 v; asm volatile(LDV4 : "=r"(v.x), "=r"(v.y), "=r"(v.z), "=r"(v.w) : "l"(p) : "memory"); return v;
}
__device__ __forceinline__ void ld_vol_u4_p(uint4& v, const uint4* p, uint32_t pred) {
    asm volatile("{\n.reg .pred p;\nsetp.ne.u32 p, %5, 0;\n@p " LDV4 "\n}"
                 : "+r"(v.x), "+r"(v.y), "+r"(v.z), "+r"(v.w) : "l"(p), "r"(pred) : "memory");
}
__device__ __forceinline__ void st_vol_u4(uint4* p, uint4 v) {
    asm volatile(STV4 :: "l"(p), "r"(v.x), "r"(v.y), "r"(v.z), "r"(v.w) : "memory");
}
__device__ __forceinline__ void mma_bf16_r(float (&d)[4], uint32_t a0, uint32_t a1, uint32_t a2, uint32_t a3, uint32_t b0, uint32_t b1) {
    asm volatile("mma.sync.aligned.m16n8k16.row.col.f32.bf16.bf16.f32 {%0,%1,%2,%3}, {%4,%5,%6,%7}, {%8,%9}, {%0,%1,%2,%3};"
                 : "+f"(d[0]), "+f"(d[1]), "+f"(d[2]), "+f"(d[3])
                 : "r"(a0), "r"(a1), "r"(a2), "r"(a3), "r"(b0), "r"(b1));
}

__device__ __forceinline__ uint64_t smem_desc(uint32_t addr, uint32_t lbo, uint32_t sbo) {
    return (uint64_t)((addr & 0x3FFFF) >> 4) | ((uint64_t)(lbo >> 4) << 16) | ((uint64_t)(sbo >> 4) << 32);
}
__device__ __forceinline__ void wg_fence() { asm volatile("wgmma.fence.sync.aligned;" ::: "memory"); }
__device__ __forceinline__ void wg_commit() { asm volatile("wgmma.commit_group.sync.aligned;" ::: "memory"); }
__device__ __forceinline__ void wg_wait0() { asm volatile("wgmma.wait_group.sync.aligned 0;" ::: "memory"); }
__device__ __forceinline__ void fence_async() { asm volatile("fence.proxy.async.shared::cta;" ::: "memory"); }
__device__ __forceinline__ void wgmma_n64_ss(float (&d)[32], uint64_t adesc, uint64_t bdesc) {
    asm volatile("{\n.reg .pred p;\nsetp.eq.b32 p, 0, 0;\n"
                 "wgmma.mma_async.sync.aligned.m64n64k16.f32.bf16.bf16 {%0,%1,%2,%3,%4,%5,%6,%7,%8,%9,%10,%11,%12,%13,%14,%15,%16,%17,%18,%19,%20,%21,%22,%23,%24,%25,%26,%27,%28,%29,%30,%31}, %32, %33, p, 1, 1, 1, 0;\n}"
                 : "+f"(d[0]), "+f"(d[1]), "+f"(d[2]), "+f"(d[3]), "+f"(d[4]), "+f"(d[5]), "+f"(d[6]), "+f"(d[7]), "+f"(d[8]), "+f"(d[9]), "+f"(d[10]), "+f"(d[11]), "+f"(d[12]), "+f"(d[13]), "+f"(d[14]), "+f"(d[15]), "+f"(d[16]), "+f"(d[17]), "+f"(d[18]), "+f"(d[19]), "+f"(d[20]), "+f"(d[21]), "+f"(d[22]), "+f"(d[23]), "+f"(d[24]), "+f"(d[25]), "+f"(d[26]), "+f"(d[27]), "+f"(d[28]), "+f"(d[29]), "+f"(d[30]), "+f"(d[31])
                 : "l"(adesc), "l"(bdesc));
}
__device__ __forceinline__ void wgmma_n72_ss(float (&d)[36], uint64_t adesc, uint64_t bdesc) {
    asm volatile("{\n.reg .pred p;\nsetp.eq.b32 p, 0, 0;\n"
                 "wgmma.mma_async.sync.aligned.m64n72k16.f32.bf16.bf16 {%0,%1,%2,%3,%4,%5,%6,%7,%8,%9,%10,%11,%12,%13,%14,%15,%16,%17,%18,%19,%20,%21,%22,%23,%24,%25,%26,%27,%28,%29,%30,%31,%32,%33,%34,%35}, %36, %37, p, 1, 1, 1, 0;\n}"
                 : "+f"(d[0]), "+f"(d[1]), "+f"(d[2]), "+f"(d[3]), "+f"(d[4]), "+f"(d[5]), "+f"(d[6]), "+f"(d[7]), "+f"(d[8]), "+f"(d[9]), "+f"(d[10]), "+f"(d[11]), "+f"(d[12]), "+f"(d[13]), "+f"(d[14]), "+f"(d[15]), "+f"(d[16]), "+f"(d[17]), "+f"(d[18]), "+f"(d[19]), "+f"(d[20]), "+f"(d[21]), "+f"(d[22]), "+f"(d[23]), "+f"(d[24]), "+f"(d[25]), "+f"(d[26]), "+f"(d[27]), "+f"(d[28]), "+f"(d[29]), "+f"(d[30]), "+f"(d[31]), "+f"(d[32]), "+f"(d[33]), "+f"(d[34]), "+f"(d[35])
                 : "l"(adesc), "l"(bdesc));
}
__device__ __forceinline__ void tma_2d(uint32_t dst, const CUtensorMap* tm, int c0, int c1, uint32_t mbar) {
    asm volatile("cp.async.bulk.tensor.2d.shared::cluster.global.tile.mbarrier::complete_tx::bytes [%0], [%1, {%2, %3}], [%4];"
                 :: "r"(dst), "l"(tm), "r"(c0), "r"(c1), "r"(mbar) : "memory");
}

__device__ __forceinline__ void bulk_g2s(uint32_t dst, const void* src, uint32_t bytes, uint32_t mbar) {
    asm volatile("cp.async.bulk.shared::cluster.global.mbarrier::complete_tx::bytes [%0], [%1], %2, [%3];"
                 :: "r"(dst), "l"(src), "r"(bytes), "r"(mbar) : "memory");
}
__device__ __forceinline__ void bulk_g2s_h(uint32_t dst, const void* src, uint32_t bytes, uint32_t mbar, uint64_t pol) {
    asm volatile("cp.async.bulk.shared::cluster.global.mbarrier::complete_tx::bytes.L2::cache_hint [%0], [%1], %2, [%3], %4;"
                 :: "r"(dst), "l"(src), "r"(bytes), "r"(mbar), "l"(pol) : "memory");
}
__device__ __forceinline__ void tma_2d_mc(uint32_t dst, const CUtensorMap* tm, int c0, int c1, uint32_t mbar) {
    asm volatile("cp.async.bulk.tensor.2d.shared::cluster.global.tile.mbarrier::complete_tx::bytes.multicast::cluster [%0], [%1, {%2, %3}], [%4], %5;"
                 :: "r"(dst), "l"(tm), "r"(c0), "r"(c1), "r"(mbar), "h"((unsigned short)7) : "memory");
}
__device__ __forceinline__ void bulk_s2s(uint32_t dst, uint32_t src, uint32_t bytes, uint32_t mbar) {
    asm volatile("cp.async.bulk.shared::cluster.shared::cta.mbarrier::complete_tx::bytes [%0], [%1], %2, [%3];"
                 :: "r"(dst), "r"(src), "r"(bytes), "r"(mbar) : "memory");
}
__device__ __forceinline__ void wgmma_n40_ss(float (&d)[20], uint64_t adesc, uint64_t bdesc, int scale_d) {
    asm volatile("{\n.reg .pred p;\nsetp.ne.b32 p, %22, 0;\n"
                 "wgmma.mma_async.sync.aligned.m64n40k16.f32.bf16.bf16 {%0,%1,%2,%3,%4,%5,%6,%7,%8,%9,%10,%11,%12,%13,%14,%15,%16,%17,%18,%19}, %20, %21, p, 1, 1, 1, 1;\n}"
                 : "+f"(d[0]), "+f"(d[1]), "+f"(d[2]), "+f"(d[3]), "+f"(d[4]), "+f"(d[5]), "+f"(d[6]), "+f"(d[7]),
                   "+f"(d[8]), "+f"(d[9]), "+f"(d[10]), "+f"(d[11]), "+f"(d[12]), "+f"(d[13]), "+f"(d[14]), "+f"(d[15]),
                   "+f"(d[16]), "+f"(d[17]), "+f"(d[18]), "+f"(d[19])
                 : "l"(adesc), "l"(bdesc), "r"(scale_d));
}
__device__ __forceinline__ void wgmma_n64_z(float (&d)[32], const uint32_t (&a)[4], uint64_t bdesc) {
    asm volatile("{\n.reg .pred p;\nsetp.ne.b32 p, 0, 0;\n"
                 "wgmma.mma_async.sync.aligned.m64n64k16.f32.bf16.bf16 {%0,%1,%2,%3,%4,%5,%6,%7,%8,%9,%10,%11,%12,%13,%14,%15,%16,%17,%18,%19,%20,%21,%22,%23,%24,%25,%26,%27,%28,%29,%30,%31}, {%32,%33,%34,%35}, %36, p, 1, 1, 0;\n}"
                 : "=f"(d[0]), "=f"(d[1]), "=f"(d[2]), "=f"(d[3]), "=f"(d[4]), "=f"(d[5]), "=f"(d[6]), "=f"(d[7]),
                   "=f"(d[8]), "=f"(d[9]), "=f"(d[10]), "=f"(d[11]), "=f"(d[12]), "=f"(d[13]), "=f"(d[14]), "=f"(d[15]),
                   "=f"(d[16]), "=f"(d[17]), "=f"(d[18]), "=f"(d[19]), "=f"(d[20]), "=f"(d[21]), "=f"(d[22]), "=f"(d[23]),
                   "=f"(d[24]), "=f"(d[25]), "=f"(d[26]), "=f"(d[27]), "=f"(d[28]), "=f"(d[29]), "=f"(d[30]), "=f"(d[31])
                 : "r"(a[0]), "r"(a[1]), "r"(a[2]), "r"(a[3]), "l"(bdesc));
}
__device__ __forceinline__ void wgmma_n64(float (&d)[32], const uint32_t (&a)[4], uint64_t bdesc, int scale_d) {
    asm volatile("{\n.reg .pred p;\nsetp.ne.b32 p, %37, 0;\n"
                 "wgmma.mma_async.sync.aligned.m64n64k16.f32.bf16.bf16 {%0,%1,%2,%3,%4,%5,%6,%7,%8,%9,%10,%11,%12,%13,%14,%15,%16,%17,%18,%19,%20,%21,%22,%23,%24,%25,%26,%27,%28,%29,%30,%31}, {%32,%33,%34,%35}, %36, p, 1, 1, 0;\n}"
                 : "+f"(d[0]), "+f"(d[1]), "+f"(d[2]), "+f"(d[3]), "+f"(d[4]), "+f"(d[5]), "+f"(d[6]), "+f"(d[7]),
                   "+f"(d[8]), "+f"(d[9]), "+f"(d[10]), "+f"(d[11]), "+f"(d[12]), "+f"(d[13]), "+f"(d[14]), "+f"(d[15]),
                   "+f"(d[16]), "+f"(d[17]), "+f"(d[18]), "+f"(d[19]), "+f"(d[20]), "+f"(d[21]), "+f"(d[22]), "+f"(d[23]),
                   "+f"(d[24]), "+f"(d[25]), "+f"(d[26]), "+f"(d[27]), "+f"(d[28]), "+f"(d[29]), "+f"(d[30]), "+f"(d[31])
                 : "r"(a[0]), "r"(a[1]), "r"(a[2]), "r"(a[3]), "l"(bdesc), "r"(scale_d));
}

constexpr int SB_FULL = 0, SB_EMPTY = 64, SB_QKF = 128, SB_VF = 144, SB_QKE = 160, SB_VE = 176, SB_OF = 192, SB_WO = 208  , SB_TICK = 216, SB_SEEN = 224, SB_FI = 232, SB_REQ = 240;
constexpr int AT_0 = 256, AT_ST = 10240 + 2 * 9216;
constexpr int FS_A = 58368;
constexpr int FS_P = FS_A + 131072;
constexpr int FS_I = FS_P + 16384;
constexpr int FS_O = FS_I + 12288;
constexpr int FS_Z = FS_O + 12288, FS_G = AT_0 + 2 * AT_ST;
constexpr int SIDE_SMEM = FS_Z + 2048;
static_assert(SIDE_SMEM <= 232448 && FS_G + 128 <= FS_A && FS_A + SD_SMEM <= SIDE_SMEM, "smem");

__device__ __forceinline__ void wg_wait1() { asm volatile("wgmma.wait_group.sync.aligned 1;" ::: "memory"); }
__device__ __forceinline__ void mbar_arrive(uint32_t bar) { asm volatile("mbarrier.arrive.shared::cta.b64 _, [%0];" :: "r"(bar) : "memory"); }
__device__ __forceinline__ void wait_cnt_rlx(const unsigned* p, unsigned target, bool urgent) {
    unsigned it = 0, v;
    while (true) {
        asm volatile("ld.relaxed.gpu.global.u32 %0, [%1];" : "=r"(v) : "l"(p) : "memory");
        if ((int)(v - target) >= 0 || ++it >= SPIN_LIMIT) break;
        if (!urgent) __nanosleep(RLX_SLEEP);
    }
}

__device__ __forceinline__ float xrow_softmax(float (&sc)[20], uint32_t (&p)[5], int wq, int lane) {
    constexpr float EC = (float)(1.4426950408889634 * 0.08838834764831845);
    const int lim = 8 * wq + (lane >> 2) - 2 * (lane & 3);
    float mx = fmaxf(sc[0], sc[1]);
#pragma unroll
    for (int j = 1; j < 5; j++) {
        sc[4 * j] = 8 * j - 8 > lim ? -INFINITY : sc[4 * j];
        sc[4 * j + 1] = 8 * j - 7 > lim ? -INFINITY : sc[4 * j + 1];
    }
    mx = fmaxf(fmaxf(mx, fmaxf(fmaxf(sc[4], sc[5]), fmaxf(sc[8], sc[9]))), fmaxf(fmaxf(sc[12], sc[13]), fmaxf(sc[16], sc[17])));
    {
        const float m1 = __shfl_xor_sync(0xffffffffu, mx, 1), m2 = __shfl_xor_sync(0xffffffffu, mx, 2), m3 = __shfl_xor_sync(0xffffffffu, mx, 3);
        mx = fmaxf(fmaxf(mx, m1), fmaxf(m2, m3));
    }
    float sum = 0.f;
#pragma unroll
    for (int j = 0; j < 5; j++) {
        float e0, e1;
        asm("ex2.approx.ftz.f32 %0, %1;" : "=f"(e0) : "f"((sc[4 * j] - mx) * EC));
        asm("ex2.approx.ftz.f32 %0, %1;" : "=f"(e1) : "f"((sc[4 * j + 1] - mx) * EC));
        p[j] = pack_bf16(e0, e1);
        sum += e0 + e1;
    }
    return sum;
}
__device__ __forceinline__ float xrow_inv(float sum) {
    sum += __shfl_xor_sync(0xffffffffu, sum, 1);
    sum += __shfl_xor_sync(0xffffffffu, sum, 2);
    float r;
    asm("rcp.approx.ftz.f32 %0, %1;" : "=f"(r) : "f"(sum));
    return r;
}

__device__ __forceinline__ void stsm_x4(uint32_t addr, uint32_t r0, uint32_t r1, uint32_t r2, uint32_t r3) {
    asm volatile("stmatrix.sync.aligned.m8n8.x4.shared.b16 [%0], {%1,%2,%3,%4};" :: "r"(addr), "r"(r0), "r"(r1), "r"(r2), "r"(r3) : "memory");
}
__device__ __forceinline__ void xrow_pv(uint32_t (&ob)[16], const uint32_t (&p)[5], float psum, uint32_t vt) {
    float o[32];
    const uint64_t dv = smem_desc(vt, 2048, 128);
    uint32_t pa[6][4];
#pragma unroll
    for (int i = 0; i < 6; i++) {
        const int ks = i >> 1, hf = i & 1;
        pa[i][hf] = p[2 * ks]; pa[i][hf ^ 1] = 0u;
        pa[i][2 + hf] = ks < 2 ? p[ks < 2 ? 2 * ks + 1 : 0] : 0u; pa[i][3 - hf] = 0u;
    }
    wg_fence();
#pragma unroll
    for (int i = 0; i < 6; i++) { if (i == 0) wgmma_n64_z(o, pa[0], dv); else wgmma_n64(o, pa[i], dv + (uint64_t)((i & 1) * 64 + (i >> 1) * 256), 1); }
    wg_commit();
    const float inv = xrow_inv(psum);
    wg_wait0();
#pragma unroll
    for (int i = 0; i < 8; i++) { ob[i] = pack_bf16(o[4 * i] * inv, o[4 * i + 1] * inv); ob[8 + i] = pack_bf16(o[4 * i + 2] * inv, o[4 * i + 3] * inv); }
}
__device__ __forceinline__ uint32_t h2_to_bf2(uint32_t h) {
    uint32_t r;
    asm("{\n.reg .f16 l, h;\n.reg .f32 a, b;\nmov.b32 {l, h}, %1;\ncvt.f32.f16 a, l;\ncvt.f32.f16 b, h;\ncvt.rn.bf16x2.f32 %0, b, a;\n}" : "=r"(r) : "r"(h));
    return r;
}
__device__ __forceinline__ uint32_t max_abs2(uint32_t a, uint32_t b) { uint32_t r; asm("max.NaN.xorsign.abs.bf16x2 %0, %1, %2;" : "=r"(r) : "r"(a), "r"(b)); return r; }
__device__ __forceinline__ uint32_t movm(uint32_t v) {
    uint32_t r; asm volatile("movmatrix.sync.aligned.m8n8.trans.b16 %0, %1;" : "=r"(r) : "r"(v)); return r;
}
__device__ __forceinline__ void bar_arrive(int id, int n) { asm volatile("bar.arrive %0, %1;" :: "r"(id), "r"(n) : "memory"); }
__device__ __forceinline__ void lds64(uint32_t& a, uint32_t& b, uint32_t addr) {
    asm volatile("ld.shared.v2.u32 {%0,%1}, [%2];" : "=r"(a), "=r"(b) : "r"(addr) : "memory");
}
__device__ __forceinline__ void lds64f(float& a, float& b, uint32_t addr) {
    asm volatile("ld.shared.v2.f32 {%0,%1}, [%2];" : "=f"(a), "=f"(b) : "r"(addr) : "memory");
}
__device__ __forceinline__ void st_async64(uint32_t addr, uint32_t a, uint32_t b, uint32_t mbar) {
    asm volatile("st.async.weak.shared::cluster.mbarrier::complete_tx::bytes.v2.b32 [%0], {%1,%2}, [%3];" :: "r"(addr), "r"(a), "r"(b), "r"(mbar) : "memory");
}
__device__ __forceinline__ void mma_z(float (&d)[4], const uint32_t (&a)[4], uint32_t b0, uint32_t b1) {
    asm volatile("mma.sync.aligned.m16n8k16.row.col.f32.bf16.bf16.f32 {%0,%1,%2,%3}, {%4,%5,%6,%7}, {%8,%9}, {%10,%10,%10,%10};"
                 : "=f"(d[0]), "=f"(d[1]), "=f"(d[2]), "=f"(d[3])
                 : "r"(a[0]), "r"(a[1]), "r"(a[2]), "r"(a[3]), "r"(b0), "r"(b1), "f"(0.f));
}
__device__ __forceinline__ void mma_k8(float (&d)[4], uint32_t a0, uint32_t a1, uint32_t b) {
    asm volatile("mma.sync.aligned.m16n8k8.row.col.f32.bf16.bf16.f32 {%0,%1,%2,%3}, {%4,%5}, {%6}, {%0,%1,%2,%3};"
                 : "+f"(d[0]), "+f"(d[1]), "+f"(d[2]), "+f"(d[3]) : "r"(a0), "r"(a1), "r"(b));
}
__global__ void __launch_bounds__(512, 1) k_side(const __grid_constant__ CUtensorMap tmo, const bf16* __restrict__ x, const bf16* __restrict__ logA, const bf16* __restrict__ Aim,
                                                 const bf16* __restrict__ Cre, const bf16* __restrict__ Cim, const bf16* __restrict__ logdt,
                                                 const bf16* __restrict__ Wo, const bf16* __restrict__ dskip, const bf16* __restrict__ gw,
                                                 bf16* __restrict__ out) {
    extern __shared__ __align__(1024) unsigned char smem_raw[];
    const uint32_t sbase = smem_u32(smem_raw);
    const int tid = threadIdx.x, warp = __shfl_sync(0xffffffffu, tid >> 5, 0), lane = tid & 31, cta = blockIdx.x;
    const int cb = cta >> 2, kq = cta & 3;
    if (tid == 0) {
        for (int i = 0; i < 8; i++) { mbar_init(sbase + SB_FULL + 8 * i, 1); mbar_init(sbase + SB_EMPTY + 8 * i, 4); }
        for (int i = 0; i < 2; i++) {
            mbar_init(sbase + SB_QKF + 8 * i, 1); mbar_init(sbase + SB_VF + 8 * i, 1); mbar_init(sbase + SB_QKE + 8 * i, 4);
            mbar_init(sbase + SB_VE + 8 * i, 1); mbar_init(sbase + SB_OF + 8 * i, 4);
        }
        mbar_init(sbase + SB_WO, 1);
        mbar_init(sbase + SB_WO + 40, 1);
        mbar_init(sbase + SB_FI, 1);
        mbar_init(sbase + SB_REQ, 4);
        *reinterpret_cast<uint2*>(smem_raw + SB_TICK) = make_uint2(0u, 0u);
        *reinterpret_cast<uint32_t*>(smem_raw + SB_SEEN) = 0u;
        asm volatile("fence.mbarrier_init.release.cluster;" ::: "memory");
    }
    TS3(0);
    asm volatile("fence.proxy.async;" ::: "memory");
    __syncthreads();
    auto epoch = []() {
        unsigned ep;
        asm volatile("ld.volatile.global.u32 %0, [%1];" : "=r"(ep) : "l"(&g_epoch) : "memory");
        return ep + 1u;
    };
    if (warp >= 12) {
      asm volatile("setmaxnreg.dec.sync.aligned.u32 40;");
      {
        uint32_t gwv[9];
#pragma unroll
        for (int i = 0; i < 9; i++) gwv[i] = reinterpret_cast<const uint32_t*>(gw)[lane + 32 * i];
#pragma unroll 1
        for (int i = 0; i < 8; i++) {
            uint32_t xv[2][9];
            float sm[2];
#pragma unroll
            for (int j = 0; j < 2; j++) {
                const int t = min(cta * 57 + 8 * i + 4 * j + warp - 12, S_LEN - 1);
#pragma unroll
                for (int k = 0; k < 9; k++) xv[j][k] = reinterpret_cast<const uint32_t*>(x + t * DM)[lane + 32 * k];
            }
#pragma unroll
            for (int j = 0; j < 2; j++) {
                sm[j] = 0.f;
#pragma unroll
                for (int k = 0; k < 9; k++) {
                    const uint32_t pr = bf2_mul(xv[j][k], gwv[k]);
                    sm[j] += __uint_as_float(pr << 16) + __uint_as_float(pr & 0xffff0000u);
                }
            }
            float v = (lane < 16 ? sm[0] : sm[1]) + __shfl_xor_sync(0xffffffffu, lane < 16 ? sm[1] : sm[0], 16);
#pragma unroll
            for (int o = 8; o; o >>= 1) v += __shfl_xor_sync(0xffffffffu, v, o);
            const float gv = 1.f / (1.f + expf(-bf16r(v)));
            const int tt = 8 * i + 4 * (lane >> 4) + warp - 12;
            if ((lane & 15) == 0 && tt < 57 && cta * 57 + tt < S_LEN) g_gate[cta * 57 + tt] = __float2bfloat16_rn(gv);
        }
        named_bar(2, 128);
        if (tid == 480) {
            __threadfence();
            asm volatile("red.relaxed.gpu.global.add.u32 [%0], 1;" :: "l"(&g_gcnt[0]) : "memory");
        }
        __syncwarp();
      }
      const unsigned ep = epoch();
      if (warp == 12 || warp == 15) {
        const int pi = warp == 12 ? 0 : 1;
        auto stage_wo = [&](int i0, int i1) {
            if (lane == 0) {
                fence_async();
#pragma unroll 1
                for (int i = i0; i < i1; i++) {
                    gate(sbase + SB_TICK);
                    tma_2d(sbase + FS_A + i * 16384, &tmo, cb * 64, kq * 1024 + i * 128, sbase + SB_WO + (i >> 2) * 40);
                    if (WO_SLEEP > 0) __nanosleep(WO_SLEEP);
                }
            }
            __syncwarp();
        };
        if (lane == 0) mbar_expect(sbase + SB_WO + pi * 40, 65536);
        if (pi == 0) {
            named_bar(11, 288);
            stage_wo(0, 2);
        }
        named_bar(3, 320);
        if (pi == 0) stage_wo(2, 4);
        else {
            if (WO_LAG > 0) __nanosleep(WO_LAG);
            stage_wo(4, 8);
        }
        if (lane == 0) TSS(17, 2 + pi);
        if (tid == 480) {
            __threadfence();
            asm volatile("red.relaxed.gpu.global.add.u32 [%0], 1;" :: "l"(&g_gcnt[32]) : "memory");
        }
        __syncwarp();
        named_bar(12 + pi, 160);
        if (lane == 0) {
            const int kb = 2 * kq + pi;
            fence_async();
            for (int pr = 0; pr < NSEG / 2; pr++) {
                const bool gon = pr < NSEG / 2 - UNGATE_G;
                wait_cnt_rlx(&g_prog[kb * 64 + pr], 8u * ep, pr >= NSEG / 2 - 2);
                if (pi == 0) asm volatile("st.volatile.shared.u32 [%0], %1;" :: "r"(sbase + SB_SEEN), "r"(pr + 1) : "memory");
                if (pr >= 30 && pi == 0) TSS(4 + pr - 30, 0);
                if (pr == 31) TS3P(26);
                if (pr == 30) TS3P(1);
#pragma unroll
                for (int j = 0; j < 4; j++) {
                    const int st = 4 * pi + j;
                    mbar_wait_long(sbase + SB_EMPTY + 8 * st, ((uint32_t)pr & 1u) ^ 1u);
                    mbar_expect(sbase + SB_FULL + 8 * st, 16384);
                    if (gon) gate(sbase + SB_TICK);
                    bulk_g2s(sbase + FS_A + st * 16384, g_ox + ((size_t)(pr * NH + 4 * kb + j)) * 8192, 16384, sbase + SB_FULL + 8 * st);
                }
            }
        }
        __syncwarp();
      } else if (warp == 13) {
        if (lane == 0) {
            const uint64_t pol = policy_evict_first();
            bool next_ok = false;
            for (int seg = 0; seg < NATT; seg++) {
                const uint32_t st = seg & 1, ph = (uint32_t)(seg >> 1) & 1u, ab = sbase + AT_0 + st * AT_ST;
                if (!next_ok) {
                    const unsigned* fp = &g_flag[(cta & (NH - 1)) * NSEG + seg];
                    unsigned it = 0, v0, v1;
                    while (true) {
                        asm volatile("ld.relaxed.gpu.global.u32 %0, [%1];" : "=r"(v0) : "l"(fp) : "memory");
                        asm volatile("ld.relaxed.gpu.global.u32 %0, [%1+4];" : "=r"(v1) : "l"(fp) : "memory");
                        read_tick(sbase + SB_TICK);
                        if ((int)(v0 - 3u * ep) >= 0 || ++it >= SPIN_LIMIT) break;
                        if (seg < NSEG - UNGATE || cta >= NH) __nanosleep(RLX_SLEEP);
                    }
                    next_ok = (int)(v1 - 3u * ep) >= 0;
                } else next_ok = false;
                if (cta < NH) {
                    TSA(seg, 0);
                    mbar_wait_long(sbase + SB_QKE + 8 * st, ph ^ 1u);
                    TSA(seg, 1);
                    mbar_expect(sbase + SB_QKF + 8 * st, 2 * 9216);
                    if (seg < NSEG - UNGATE) gate(sbase + SB_TICK, GL_A, GL_B);
                    TSA(seg, 2);
                    bulk_g2s_h(ab + 10240, &g_qkv[seg][cta][0][1024], 9216, sbase + SB_QKF + 8 * st, pol);
                    bulk_g2s_h(ab + 10240 + 9216, &g_qkv[seg][cta][1][1024], 9216, sbase + SB_QKF + 8 * st, pol);
                    mbar_wait_long(sbase + SB_VE + 8 * st, ph ^ 1u);
                    mbar_expect(sbase + SB_VF + 8 * st, 10240);
                    if (seg < NSEG - UNGATE) gate(sbase + SB_TICK, GL_A, GL_B);
                    TSA(seg, 3);
                    bulk_g2s_h(ab, &g_qkv[seg][cta][2][0], 10240, sbase + SB_VF + 8 * st, pol);
                }
            }
        }
        __syncwarp();
      } else if (warp == 14) {
        if (lane == 0) {
            int seg = cta < NH ? 0 : NATT, p = 0;
            unsigned it = 0;
            while ((seg < NATT || p < NSEG / 2 - 1) && ++it < 16 * SPIN_LIMIT) {
                if (p < NSEG / 2 - 1 && mbar_test(sbase + SB_REQ, (uint32_t)p & 1u)) {
                    if (p == 0) { wait_cnt(&g_gcnt[32], SD_NCTA * ep); asm volatile("fence.proxy.async;" ::: "memory"); }
                    mbar_expect(sbase + SB_FI, (p < NSEG / 2 - 2 ? 12288 : 2048 + 32) + 2048 + 32);
                    if (p < NSEG / 2 - UNGATE_G - 1) gate(sbase + SB_TICK);
                    if (p < NSEG / 2 - 2) bulk_g2s(sbase + FS_I, &g_fp[p & 7][cta][0][0], 12288, sbase + SB_FI);
                    else {
                        bulk_g2s(sbase + FS_I, g_y + ((p * 4 + 4 + kq) * DM + cb * 64) * 16, 2048, sbase + SB_FI);
                        bulk_g2s(sbase + FS_G + 32, g_gate + p * 64 + 64 + kq * 16, 32, sbase + SB_FI);
                    }
                    bulk_g2s(sbase + FS_Z, g_y + ((p * 4 + kq) * DM + cb * 64) * 16, 2048, sbase + SB_FI);
                    bulk_g2s(sbase + FS_G, g_gate + p * 64 + kq * 16, 32, sbase + SB_FI);
                    p++;
                } else if (seg < NATT && mbar_test(sbase + SB_OF + 8 * (seg & 1), (uint32_t)(seg >> 1) & 1u)) {
                    const uint32_t st = seg & 1, ab = sbase + AT_0 + st * AT_ST;
                    TSA(seg, 5);
                    if (seg < NSEG - UNGATE) gate(sbase + SB_TICK, GS_A, GS_B);
                    TSA(seg, 6);
                    unsigned char* dst = reinterpret_cast<unsigned char*>(g_ox) + ((size_t)((seg >> 1) * NH + cta)) * 16384 + (seg & 1) * 8192;
                    asm volatile("cp.async.bulk.global.shared::cta.bulk_group [%0], [%1], 8192;" :: "l"(dst), "r"(ab) : "memory");
                    asm volatile("cp.async.bulk.commit_group;" ::: "memory");
                    asm volatile("cp.async.bulk.wait_group.read 0;" ::: "memory");
                    mbar_arrive(sbase + SB_VE + 8 * st);
                    asm volatile("cp.async.bulk.wait_group 0;" ::: "memory");
                    asm volatile("red.relaxed.gpu.global.add.u32 [%0], 1;" :: "l"(&g_prog[(cta >> 2) * 64 + (seg >> 1)]) : "memory");
                    TSA(seg, 7);
                    seg++;
                } else if (seg < NSEG - UNGATE) __nanosleep(W14_SLEEP);
            }
        }
        __syncwarp();
      }
    } else if (warp >= 8) {
        asm volatile("setmaxnreg.dec.sync.aligned.u32 88;");
          s4d_stage_u(smem_raw + FS_A, x, tid - 256);
        const int wq = warp - 8;
        for (int seg = 0; seg < (cta < NH ? NATT : 0); seg++) {
            const uint32_t st = seg & 1, ph = (uint32_t)(seg >> 1) & 1u, ab = sbase + AT_0 + st * AT_ST;
            float sc[20];
            if (seg < NSEG - UNGATE) mbar_wait_long(sbase + SB_QKF + 8 * st, ph); else mbar_wait(sbase + SB_QKF + 8 * st, ph);
            if (tid == 256) TSA(seg, 4);
            {
                const uint64_t da = smem_desc(ab + 10240 + 1024, 128, 1024), db = smem_desc(ab + 10240, 128, 2048);
                wg_fence();
#pragma unroll
                for (int ks = 0; ks < 8; ks++) wgmma_n40_ss(sc, da + (uint64_t)((ks >> 2) * 576 + (ks & 3) * 16), db + (uint64_t)((ks >> 2) * 576 + (ks & 3) * 16), ks > 0);
                wg_commit();
                wg_wait0();
            }
            if (lane == 0) mbar_arrive(sbase + SB_QKE + 8 * st);
            uint32_t p[5], ob[16];
            const float psum = xrow_softmax(sc, p, wq, lane);
            mbar_wait(sbase + SB_VF + 8 * st, ph);
            xrow_pv(ob, p, psum, ab);
            named_bar(6, 128);
#pragma unroll
            for (int i = 0; i < 4; i++) stsm_x4(ab + wq * 2048 + i * 512 + lane * 16, ob[4 * i], ob[4 * i + 1], ob[4 * i + 2], ob[4 * i + 3]);
            fence_async();
            __syncwarp();
            if (lane == 0) mbar_arrive(sbase + SB_OF + 8 * st);
        }
    } else {
        asm volatile("setmaxnreg.inc.sync.aligned.u32 192;");
        const int wg = warp >> 2, wq = warp & 3;
        s4d_phase(smem_raw + FS_A, x, logA, Aim, Cre, Cim, logdt, dskip, Wo + (size_t)((2 * kq + wg) * 512) * DM + cb * 64);
        TS3(2);
        if (lane == 0) TSS(16, warp);
        named_bar(3, 320);
        if (tid == 0) TSS(17, 0);
        uint32_t wa[32][4];
        mbar_wait_long(sbase + SB_WO + wg * 40, 0);
        if (tid == 0) TSS(17, 1);
        {
            const uint32_t a = sbase + FS_A + wg * 65536 + ((lane >> 4) * 8 + (lane & 7)) * 128 + (((wq * 2 + ((lane >> 3) & 1)) ^ (lane & 7)) << 4);
#pragma unroll
            for (int ks = 0; ks < 32; ks++) ldsm_x4_t(wa[ks], a + ks * 2048);
        }
        named_bar(12 + wg, 160);
        TS3(3);
        if (tid == 0) TSS(17, 4);
        auto product = [&](float (&acc)[32], int pr, const int wg) {
                if (pr + wg > 0) named_bar(4 + wg, 256);
                const uint64_t db = smem_desc(sbase + FS_A + wg * 65536, 128, 2048);
                TSG(0);
#pragma unroll
                for (int j = 0; j < 4; j++) {
                    mbar_wait(sbase + SB_FULL + 8 * (4 * wg + j), (uint32_t)pr & 1u);
                    if (j == 0) TSG(1);
                    if (j == 3) TSG(2);
                    wg_fence();
#pragma unroll
                    for (int ks = 0; ks < 8; ks++) {
                        if ((j | ks) == 0) wgmma_n64_z(acc, wa[0], db);
                        else wgmma_n64(acc, wa[8 * j + ks], db + (uint64_t)(j * 1024 + ks * 16), 1);
                    }
                    wg_commit();
                    if (j == 3 && pr + wg < NSEG / 2) bar_arrive(4 + (wg ^ 1), 256);
                    if (j > 0) { wg_wait1(); if (lane == 0) mbar_arrive(sbase + SB_EMPTY + 8 * (4 * wg + j - 1)); }
                }
                wg_wait0();
                if (pr == 31) TS3W(27);
                TSG(3);
                if (lane == 0) mbar_arrive(sbase + SB_EMPTY + 8 * (4 * wg + 3));
        };
        if (wg == 1) {
            for (int pr = 0; pr < NSEG / 2; pr++) {
                uint32_t t16 = (uint32_t)(wq * 32 + lane) * 16u;
                asm volatile("" : "+r"(t16));
                float acc[32];
                product(acc, pr, 1);
                    uint32_t tag = ((uint32_t)(pr >> 3) & 1u) ^ 1u;
                    tag = __shfl_sync(0xffffffffu, tag, lane);
                    named_bar(8, 256);
                    unsigned char* dst = reinterpret_cast<unsigned char*>(&g_fp[pr & 7][4 * cb][2 * kq - 2][0]) + t16;
                    const uint32_t own = sbase + FS_O + (pr % 3) * 4096 + t16;
#pragma unroll
                    for (int q = 0; q < 8; q++) {
                        float4 p;
                        asm volatile("ld.shared.v4.f32 {%0,%1,%2,%3}, [%4];" : "=f"(p.x), "=f"(p.y), "=f"(p.z), "=f"(p.w) : "r"(sbase + FS_P + t16 + q * 2048) : "memory");
                        acc[4 * q] = __uint_as_float((__float_as_uint(acc[4 * q] + p.x) & ~1u) | tag); acc[4 * q + 1] = __uint_as_float((__float_as_uint(acc[4 * q + 1] + p.y) & ~1u) | tag);
                        acc[4 * q + 2] = __uint_as_float((__float_as_uint(acc[4 * q + 2] + p.z) & ~1u) | tag); acc[4 * q + 3] = __uint_as_float((__float_as_uint(acc[4 * q + 3] + p.w) & ~1u) | tag);
                    }
#pragma unroll
                    for (int q = 0; q < 8; q++) {
                        asm volatile("{\n.reg .pred p;\nsetp.ne.s32 p, %5, %6;\n@p st.volatile.global.v4.f32 [%0], {%1,%2,%3,%4};\n@!p st.shared.v4.f32 [%7], {%1,%2,%3,%4};\n}"
                                     :: "l"(dst + (q & 1) * 2048), "f"(acc[4 * q]), "f"(acc[4 * q + 1]), "f"(acc[4 * q + 2]), "f"(acc[4 * q + 3]), "r"(q >> 1), "r"(kq),
                                        "r"(own + (q & 1) * 2048) : "memory");
                        if (q & 1) dst += (q >> 1) == kq ? 12288 + 4096 : 12288;
                    }
                    bar_arrive(9, 256);
                    if (pr == 31) TS3W(28);
                TSG(4);
            }
        } else {
          int nsync = 0;
          int np = 1, nf = 0, pr = 0, pf = -1;
          while (true) {
            uint32_t t16 = (uint32_t)(wq * 32 + lane) * 16u;
            asm volatile("" : "+r"(t16));
            if (pr < 0) {
                if (nsync <= pf) { named_bar(9, 256); nsync++; }
                if (lane == 0 && pf < NSEG / 2 - 1) mbar_arrive(sbase + SB_REQ);
            } else {
                float acc[32];
                product(acc, pr, 0);
                if (nsync < pr) { named_bar(9, 256); nsync++; }
#pragma unroll
                for (int q = 0; q < 8; q++)
                    asm volatile("st.shared.v4.f32 [%0], {%1,%2,%3,%4};" :: "r"(sbase + FS_P + t16 + q * 2048), "f"(acc[4 * q]), "f"(acc[4 * q + 1]), "f"(acc[4 * q + 2]), "f"(acc[4 * q + 3]) : "memory");
                bar_arrive(8, 256);
                TSG(4);
            }
            uint32_t w[4] = {0u, 0u, 0u, 0u};
            const int pc = pf;
            if (pf >= 0) {
                const uint32_t tag = ((uint32_t)(pf >> 3) & 1u) ^ 1u;
                uint4 v[8];
                unsigned n = 0;
                const bool last = pf == NSEG / 2 - 1;
                const uint4* src = reinterpret_cast<const uint4*>(reinterpret_cast<const unsigned char*>(&g_fp[pf & 7][cta][0][0]) + t16);
                if (pf >= NSEG / 2 - 2) {
#pragma unroll
                    for (int r = 0; r < 6; r++) v[r] = ld_vol_u4(src + r * 128);
                    mbar_wait(sbase + SB_FI, 0u);
                } else {
                    mbar_wait(sbase + SB_FI, (uint32_t)pf & 1u);
#pragma unroll
                    for (int r = 0; r < 6; r++)
                        asm volatile("ld.shared.v4.u32 {%0,%1,%2,%3}, [%4];" : "=r"(v[r].x), "=r"(v[r].y), "=r"(v[r].z), "=r"(v[r].w) : "r"(sbase + t16 + FS_I + r * 2048) : "memory");
                }
                while (true) {
                    uint32_t any = 0u;
#pragma unroll
                    for (int r = 0; r < 6; r++) {
                        uint32_t c0_, c1_;
                        asm("lop3.b32 %0, %1, %2, %3, 0x7e;" : "=r"(c0_) : "r"(v[r].x), "r"(v[r].y), "r"(tag));
                        asm("lop3.b32 %0, %1, %2, %3, 0x7e;" : "=r"(c1_) : "r"(v[r].z), "r"(v[r].w), "r"(tag));
                        asm("lop3.b32 %0, %1, %2, %3, 0xfe;" : "=r"(any) : "r"(any), "r"(c0_), "r"(c1_));
                    }
                    if (!__any_sync(0xffffffffu, (any & 1u) != 0u) || ++n >= SPIN_LIMIT) break;
                    if (pf < NSEG / 2 - 2) __nanosleep(200);
#pragma unroll
                    for (int r = 0; r < 6; r++) v[r] = ld_vol_u4(src + r * 128);
                }
                if (pf == 31) TS3(29);
                TSG(5);
#pragma unroll
                for (int r = 6; r < 8; r++)
                    asm volatile("ld.shared.v4.u32 {%0,%1,%2,%3}, [%4];" : "=r"(v[r].x), "=r"(v[r].y), "=r"(v[r].z), "=r"(v[r].w)
                                 : "r"(sbase + t16 + FS_O + (pf % 3) * 4096 + (r - 6) * 2048) : "memory");
                uint32_t zv[4], gg[2];
                ldsm_x4_t(zv, sbase + (last ? FS_I : FS_Z) + (wq * 16 + (lane & 15)) * 32 + (lane >> 4) * 16);
#pragma unroll
                for (int k = 0; k < 2; k++) gg[k] = __byte_perm(*reinterpret_cast<const volatile unsigned short*>(smem_raw + FS_G + (last ? 32 : 0) + k * 16 + (lane >> 2) * 2), 0u, 0x1010);
#define PQS(k, f) (((__uint_as_float(v[k].f) + __uint_as_float(v[2 + k].f)) + __uint_as_float(v[4 + k].f)) + __uint_as_float(v[6 + k].f))
#pragma unroll
                for (int k = 0; k < 2; k++) {
                    w[2 * k] = bf2_add(bf2_mul(gg[k], movm(pack_bf16(PQS(k, x), PQS(k, y)))), zv[2 * k]);
                    w[2 * k + 1] = bf2_add(bf2_mul(gg[k], movm(pack_bf16(PQS(k, z), PQS(k, w)))), zv[2 * k + 1]);
                }
#undef PQS
            }
            const bool more = nf < NSEG / 2;
            if (more) {
                uint32_t r;
                asm volatile("{\n.reg .pred p, q;\n.reg .b32 v;\nld.volatile.shared.u32 v, [%1];\nsetp.gt.s32 p, v, %2;\nbar.red.or.pred q, 10, 128, p;\nselp.u32 %0, 1, 0, q;\n}"
                             : "=r"(r) : "r"(sbase + SB_SEEN), "r"(np) : "memory");
                const bool dop = np < NSEG / 2 && (__shfl_sync(0xffffffffu, r, 0) != 0u || nf == np || (np >= TM && nf + 1 >= np));
                TSG(6);
                pr = dop ? np++ : -1;
                pf = !dop || nf + (pr >= TM2 ? 1 : 2) <= pr ? nf++ : -1;
                if (dop && pf >= 0 && lane == 0) mbar_arrive(sbase + SB_REQ);
            }
            if (pc >= 0) {
                unsigned char* op = reinterpret_cast<unsigned char*>(out) + (uint32_t)((pc * 64 + kq * 16 + (lane >> 2)) * DM + cb * 64 + wq * 16 + 2 * (lane & 3)) * 2u;
#pragma unroll
                for (int k = 0; k < 4; k++) *reinterpret_cast<uint32_t*>(op + (k >> 1) * (16 * DM) + (k & 1) * 16) = w[k];
                if ((pc & 1) == 0) TS3(4 + pc / 2);
                if (pc == 31) TS3(25);
            }
            if (!more) break;
          }
        }
        if (cta == 0 && tid == 0) asm volatile("red.relaxed.gpu.global.add.u32 [%0], 1;" :: "l"(&g_epoch) : "memory");
    }
    asm volatile("griddepcontrol.wait;" ::: "memory");
}

template <class F>
__device__ __forceinline__ uint32_t poll_mem(const uint4* src, uint32_t dst, uint32_t t0, F next) {
    uint4 v[6];
    unsigned it = 0;
#pragma unroll
    for (int j = 0; j < 6; j++) v[j] = make_uint4(0u, 0u, 0u, 0u);
    if (PDC > 0) {
        float w = __uint_as_float((dst & 0xffffu) | 0x3f800000u);
#pragma unroll
        for (int i = 0; i < PDC; i++) asm volatile("rcp.approx.ftz.f32 %0, %0;" : "+f"(w));
        t0 += __float_as_uint(w) >> 31;
    }
    if (PDS > 0) __nanosleep(PDS);
    while (clock32() - t0 < POLL_DELAY) {}
    FS(12, 0);
    bool more;
#pragma unroll 1
    do {
        asm volatile("{\n.reg .pred p<6>;\n"
                     "setp.ne.u32 p0, %3, 0x5000;\nsetp.ne.u32 p1, %7, 0x5000;\nsetp.ne.u32 p2, %11, 0x5000;\n"
                     "setp.ne.u32 p3, %15, 0x5000;\nsetp.ne.u32 p4, %19, 0x5000;\nsetp.ne.u32 p5, %23, 0x5000;\n"
                     "@p0 ld.volatile.global.v4.u32 {%0,%1,%2,%3}, [%24];\n@p1 ld.volatile.global.v4.u32 {%4,%5,%6,%7}, [%24+4096];\n"
                     "@p2 ld.volatile.global.v4.u32 {%8,%9,%10,%11}, [%24+8192];\n@p3 ld.volatile.global.v4.u32 {%12,%13,%14,%15}, [%24+12288];\n"
                     "@p4 ld.volatile.global.v4.u32 {%16,%17,%18,%19}, [%24+16384];\n@p5 ld.volatile.global.v4.u32 {%20,%21,%22,%23}, [%24+20480];\n}"
                     : "+r"(v[0].x), "+r"(v[0].y), "+r"(v[0].z), "+r"(v[0].w), "+r"(v[1].x), "+r"(v[1].y), "+r"(v[1].z), "+r"(v[1].w),
                       "+r"(v[2].x), "+r"(v[2].y), "+r"(v[2].z), "+r"(v[2].w), "+r"(v[3].x), "+r"(v[3].y), "+r"(v[3].z), "+r"(v[3].w),
                       "+r"(v[4].x), "+r"(v[4].y), "+r"(v[4].z), "+r"(v[4].w), "+r"(v[5].x), "+r"(v[5].y), "+r"(v[5].z), "+r"(v[5].w)
                     : "l"(src) : "memory");
        stsm_x4(dst, h2_to_bf2(v[0].x), h2_to_bf2(v[0].y), h2_to_bf2(v[0].z), h2_to_bf2(v[1].x));
        stsm_x4(dst + 512, h2_to_bf2(v[1].y), h2_to_bf2(v[1].z), h2_to_bf2(v[2].x), h2_to_bf2(v[2].y));
        const uint32_t all = ((v[0].w & v[1].w) & (v[2].w & v[3].w)) & (v[4].w & v[5].w);
        more = __any_sync(0xffffffffu, (all & 0x5000u) != 0x5000u && ++it < SPIN_LIMIT);
        stsm_x4(dst + 1024, h2_to_bf2(v[2].z), h2_to_bf2(v[3].x), h2_to_bf2(v[3].y), h2_to_bf2(v[3].z));
        asm volatile("stmatrix.sync.aligned.m8n8.x2.shared.b16 [%0], {%1,%2};" :: "r"(dst + 1536), "r"(h2_to_bf2(v[4].x)), "r"(h2_to_bf2(v[4].y)) : "memory");
        stsm_x4(dst + 1792, h2_to_bf2(v[4].z), h2_to_bf2(v[5].x), h2_to_bf2(v[5].y), h2_to_bf2(v[5].z));
        asm volatile("{\n.reg .pred p;\nsetp.eq.u32 p, %0, 0;\n@p bar.sync 1, 384;\n}" :: "r"((uint32_t)more) : "memory");
    } while (more);
    next();
    FS(13, it);
    FS(14, 0);
    uint32_t m = v[0].x, m1 = v[0].y, m2 = v[0].z;
#pragma unroll
    for (int j = 1; j < 6; j++) {
        asm volatile("max.NaN.xorsign.abs.f16x2 %0, %0, %1;" : "+r"(m) : "r"(v[j].x));
        asm volatile("max.NaN.xorsign.abs.f16x2 %0, %0, %1;" : "+r"(m1) : "r"(v[j].y));
        asm volatile("max.NaN.xorsign.abs.f16x2 %0, %0, %1;" : "+r"(m2) : "r"(v[j].z));
    }
    asm volatile("max.NaN.xorsign.abs.f16x2 %0, %0, %1;" : "+r"(m) : "r"(m1));
    asm volatile("max.NaN.xorsign.abs.f16x2 %0, %0, %1;" : "+r"(m) : "r"(m2));
    return h2_to_bf2(m) & 0x7fff7fffu;
}

template <int N> __device__ __forceinline__ void pad_code() {
#pragma unroll
    for (int i = 0; i < N; i++) asm volatile("pmevent 7;" ::: "memory");
}
template <bool V> struct Flag { static constexpr bool value = V; };
__device__ __forceinline__ void score_group(const uint32_t (&a)[2][4], const uint32_t (&kf)[2][4], uint32_t d0, uint32_t d1, uint32_t m1, uint32_t d2, uint32_t m2) {
    FS(4, a[1][0]);
    float sc[4][4];
    mma_z(sc[0], a[0], kf[0][0], kf[0][1]);
    mma_z(sc[1], a[0], kf[0][2], kf[0][3]);
    mma_z(sc[2], a[1], kf[1][0], kf[1][1]);
    mma_z(sc[3], a[1], kf[1][2], kf[1][3]);
    constexpr float EC = (float)(1.4426950408889634 * 0.08838834764831845);
    const uint32_t v0 = __float_as_uint(fmaf(sc[3][2], EC, ((sc[0][0] + sc[1][2]) + sc[2][0]) * EC)), v1 = __float_as_uint(fmaf(sc[3][3], EC, ((sc[0][1] + sc[1][3]) + sc[2][1]) * EC));
    FS(5, v0);
    const uint32_t pk = pack_bf16(__uint_as_float(v0), __uint_as_float(v1));
    st_async32(d2, pk, m2);
    st_async32(d1, pk, m1);
    asm volatile("st.shared.v2.u32 [%0], {%1,%2};" :: "r"(d0), "r"(v0), "r"(v1) : "memory");
}
__device__ __forceinline__ void store_tile(int s, int h, int role, uint32_t tile, uint32_t b0, uint32_t b1) {
    asm volatile("cp.async.bulk.global.shared::cta.bulk_group.L2::cache_hint [%0], [%1], %2, %3;"
                 :: "l"(&g_qkv[s][h][role][b0]), "r"(tile + b0), "r"(b1 - b0), "l"(policy_evict_first()) : "memory");
}
__device__ __forceinline__ uint32_t w_addr(uint32_t sbase, int warp, int lane) {
    return sbase + SM_WS + (warp >> 2) * 8192 + ((lane & 7) + ((lane >> 4) & 1) * 8) * 128 + ((((warp & 3) * 2 + ((lane >> 3) & 1)) ^ (lane & 7)) << 4);
}
__device__ __forceinline__ void vx_copy(uint32_t sbase, int j, int r) {
    bulk_s2s(mapa(sbase + SM_VX + (j & 1) * 8192, r), sbase + SM_T + (j & 3) * TBUF + DH * 16, 8192, mapa(sbase + B_VX + 8 * (j & 1), r));
}
__device__ __forceinline__ float to_scale(float bound) {
    int e = 141 - (int)((__float_as_uint(bound) >> 23) & 255u);
    e = e > 100 ? 100 : e;
    return __uint_as_float((uint32_t)(127 + e) << 23);
}
__device__ __forceinline__ void norms_gather(int lane, uint32_t sbase) {
    uint2 v[3];
    uint4 w[2];
    unsigned it = 0;
#pragma unroll
    for (int i = 0; i < 3; i++) v[i] = make_uint2(0u, 0u);
    w[0] = w[1] = make_uint4(0u, 0u, 0u, 0u);
    bool more;
    do {
#pragma unroll
        for (int i = 0; i < 3; i++) if ((v[i].x & 1u) == 0u) v[i] = ld_vol_u2(&g_norm[3 * lane + i]);
#pragma unroll
        for (int i = 0; i < 2; i++) if ((w[i].x & w[i].y & w[i].z & w[i].w & 1u) == 0u) w[i] = ld_vol_u4(&g_wv[lane][i]);
        more = __any_sync(0xffffffffu, (v[0].x & v[1].x & v[2].x & w[0].x & w[0].y & w[0].z & w[0].w & w[1].x & w[1].y & w[1].z & w[1].w & 1u) == 0u);
    } while (more && ++it < SPIN_LIMIT);
    float c;
    asm("sqrt.approx.f32 %0, %1;" : "=f"(c) : "f"(__uint_as_float(max(max(v[0].x, v[1].x), v[2].x))));
    c *= __uint_as_float(max(max(max(w[0].x, w[0].y), max(w[0].z, w[0].w)), max(max(w[1].x, w[1].y), max(w[1].z, w[1].w)))) * 272.f;
#pragma unroll
    for (int o = 16; o; o >>= 1) c += __shfl_xor_sync(0xffffffffu, c, o);
    const uint32_t r = __reduce_max_sync(0xffffffffu, v[0].y);
    if (lane < 3) {
        const uint32_t rb = mapa(sbase, lane);
        c *= 1.1f * 24.f;
        st_async64(rb + SM_SC, __float_as_uint(to_scale(__uint_as_float(r) * c)), __float_as_uint(c), rb + B_W + 8);
        st_async32(rb + SM_SC + 68, r, rb + B_W + 8);
    }
    __syncwarp();
}
__device__ __forceinline__ void xmax_gather(int lane, uint32_t sb) {
    uint4 v[4];
    unsigned it = 0;
    uint32_t ok;
    do {
#pragma unroll
        for (int i = 0; i < 4; i++) v[i] = ld_vol_u4(&g_rx[lane + 32 * (i >> 1)][i & 1]);
        ok = 1u;
#pragma unroll
        for (int i = 0; i < 4; i++) ok &= (v[i].x & v[i].y) & (v[i].z & v[i].w);
    } while (__any_sync(0xffffffffu, ok == 0u) && ++it < SPIN_LIMIT);
#pragma unroll
    for (int i = 0; i < 2; i++)
        sts32(sb + SM_SC + 64 + 4 * lane + 128 * i, max(max(max(v[2 * i].x, v[2 * i].y), max(v[2 * i].z, v[2 * i].w)), max(max(v[2 * i + 1].x, v[2 * i + 1].y), max(v[2 * i + 1].z, v[2 * i + 1].w))));
}
__device__ __forceinline__ uint32_t max_abs8(uint32_t m, uint32_t a, uint32_t b, uint32_t c, uint32_t d) { return max_abs2(max_abs2(m, max_abs2(a, b)), max_abs2(c, d)); }
__device__ __forceinline__ uint32_t warp_max_abs(uint32_t m) { return __reduce_max_sync(0xffffffffu, max((m << 16) & 0x7fff0000u, m & 0x7fff0000u)); }

__device__ __forceinline__ void last_rows() {
    extern __shared__ __align__(1024) unsigned char smem_raw[];
    const uint32_t sbase = smem_u32(smem_raw);
    const int tid = threadIdx.x, warp = __shfl_sync(0xffffffffu, tid >> 5, 0), h = blockIdx.x / 3;
    {
        const int sg = warp < 8, wq = warp & 3, lane = tid & 31;
        const uint32_t qk = sbase + SM_X + XBUF + sg * (2 * 9216), ob = sbase + SM_X + 2 * XBUF + sg * 8192;
        TST(0);
        mbar_wait(sbase + B_VX + 8 * sg, 0);
        fence_async();
        TST(1);
        float sc[20];
#pragma unroll
        for (int i = 0; i < 20; i++) sc[i] = 0.f;
        {
            const uint64_t da = smem_desc(qk + 1024, 128, 1024), db = smem_desc(qk, 128, 2048);
            wg_fence();
#pragma unroll
            for (int ks = 0; ks < 8; ks++) wgmma_n40_ss(sc, da + (uint64_t)((ks >> 2) * 576 + (ks & 3) * 16), db + (uint64_t)((ks >> 2) * 576 + (ks & 3) * 16), ks > 0);
            wg_commit();
            wg_wait0();
        }
        uint32_t p[5], o[16];
        const float psum = xrow_softmax(sc, p, wq, lane);
        xrow_pv(o, p, psum, sbase + SM_T + ((NSEG - 2 + sg) & 3) * TBUF);
        {
#pragma unroll
            for (int i = 0; i < 4; i++) stsm_x4(ob + wq * 2048 + i * 512 + lane * 16, o[4 * i], o[4 * i + 1], o[4 * i + 2], o[4 * i + 3]);
        }
        fence_async();
        named_bar(11 + sg, 128);
        TST(2);
        if ((tid & 127) == 0) {
            unsigned char* dst = reinterpret_cast<unsigned char*>(g_ox) + ((size_t)((NSEG / 2 - 1) * NH + h)) * 16384 + sg * 8192;
            asm volatile("cp.async.bulk.global.shared::cta.bulk_group [%0], [%1], 8192;" :: "l"(dst), "r"(ob) : "memory");
            asm volatile("cp.async.bulk.commit_group;" ::: "memory");
            asm volatile("cp.async.bulk.wait_group 0;" ::: "memory");
            asm volatile("red.relaxed.gpu.global.add.u32 [%0], 1;" :: "l"(&g_prog[(h >> 2) * 64 + NSEG / 2 - 1]) : "memory");
        }
        TST(3);
    }
    __syncwarp();
}

__global__ void __cluster_dims__(3, 1, 1) __launch_bounds__(384, 1)
k_chain(const __grid_constant__ CUtensorMap tmq, const __grid_constant__ CUtensorMap tmk,
        const __grid_constant__ CUtensorMap tmv, const __grid_constant__ CUtensorMap tmx2, const __grid_constant__ CUtensorMap tmo,
        const __grid_constant__ CUtensorMap tmm, const bf16* __restrict__ xg) {
    extern __shared__ __align__(1024) unsigned char smem_raw[];
    const uint32_t sbase = smem_u32(smem_raw);
    const int cta = blockIdx.x, h = cta / 3, role = cta - 3 * h;
    const int tid = threadIdx.x, warp = __shfl_sync(0xffffffffu, tid >> 5, 0), lane_o = tid & 31;
    TS3C(0);
    asm volatile("griddepcontrol.launch_dependents;" ::: "memory");
    auto stage_w = [&](int i) {
        tma_2d(sbase + SM_WS + i * 16384, role == 2 ? &tmv : &tmq, h * DH + (role == 1 ? 64 : 0), i * 64, sbase + B_W + 8 * i);
        tma_2d(sbase + SM_WS + i * 16384 + 8192, role == 2 ? &tmv : &tmk, h * DH + (role == 0 ? 0 : 64), i * 64, sbase + B_W + 8 * i);
    };
    auto stage_x = [&](int i) {
        tma_2d(sbase + x01_off(i), &tmx2, i * 64, 0, sbase + B_W + 8 * i);
        tma_2d(sbase + x01_off(i) + 8192, &tmm, i * 64, 0, sbase + B_W + 8 * i);
        if (i < 3) tma_2d(sbase + x23_off(i), &tmx2, i * 64, 64, sbase + B_W + 8 * i);
    };
    if (tid == 0) {
#pragma unroll
        for (int i = 0; i < 10; i++) mbar_init(sbase + B_W + 8 * i, 1);
        fence_async();
        TSQ(10);
#pragma unroll
        for (int i = 0; i < 3; i++) tma_2d(sbase + SM_X01 + i * 16384, &tmo, role * WOC + i * 64, h * DH, sbase + B_E);
        stage_x(0); stage_w(0);
        TSQ(11);
        mbar_expect(sbase + B_E, 49152);
#pragma unroll
        for (int i = 0; i < 9; i++) mbar_expect(sbase + B_W + 8 * i, 16384 + 9216 + (i < 3 ? 8192 : 0));
    } else if (tid == 32) {
#pragma unroll
        for (int i = 0; i < 8; i++) mbar_init(sbase + SM_BAR + 8 * i, 1);
        mbar_init(sbase + B_XF, 3);
        asm volatile("fence.mbarrier_init.release.cluster;" ::: "memory");
        for (int i = 0; i < 2; i++) {
            mbar_expect(sbase + B_SB + 8 * i, role == 2 ? 2560 >> HS : (1280 >> HS) + 2048);
            mbar_expect(sbase + B_VX + 8 * i, role != 2 ? 8192 : 2 * 9216);
            mbar_expect(sbase + B_XT + 8 * i, 32768);
            mbar_expect(sbase + B_XT + 16 + 8 * i, i == 0 ? 40960 : 0);
        }
    }
    __syncthreads();
    TS3C(8);
    if (tid == 0) {
#pragma unroll 1
        for (int i = 1; i < 3; i++) { stage_x(i); stage_w(i); }
        TSQ(12);
    }
    __syncwarp();
    if (warp < 8) {
        uint32_t wreg[36 - NS][4];
        uint32_t v0, v1;
        {
            const int lane = lane_o;
            const uint32_t a = w_addr(sbase, warp, lane);
            const uint64_t da = smem_desc(sbase + SM_WS + (warp >> 2) * 8192, 1024, 1024) | (1ull << 62);
            float acc[36], acc1[32];
            uint32_t m = 0u;
#pragma unroll
            for (int i = 0; i < 36; i++) acc[i] = 0.f;
#pragma unroll
            for (int i = 0; i < 32; i++) acc1[i] = 0.f;
#pragma unroll 1
            for (int b = 0; b < 7; b++) {
                if (b == 0) TSQ(0);
                mbar_wait(sbase + B_W + 8 * b, 0);
                TSQ(1 + b);
                const uint64_t db = smem_desc(sbase + x01_off(b), 16, 1024) | (1ull << 62);
                wg_fence();
#pragma unroll
                for (int k = 0; k < 4; k++) wgmma_n72_ss(acc, da + (uint64_t)(b * 1024 + k * 128), db + (uint64_t)(k * 2));
                wg_commit();
                if (b < 3) {
                    const uint64_t d1 = smem_desc(sbase + x23_off(b), 16, 1024) | (1ull << 62);
                    wg_fence();
#pragma unroll
                    for (int k = 0; k < 4; k++) wgmma_n64_ss(acc1, da + (uint64_t)(b * 1024 + k * 128), d1 + (uint64_t)(k * 2));
                    wg_commit();
                }
                if (b == 2) {
                    wg_wait0();
                    bar_arrive(10, 384);
                }
                if (b == 3) {
                    if (tid == 0) mbar_expect(sbase + B_W + 8, 12);
                    __syncwarp();
                    if (role == 2) {
#pragma unroll
                        for (int ks = 0; ks < NS; ks++) {
                            uint32_t t[4];
                            ldsm_x4_t(t, a + (ks >> 2) * 16384 + (ks & 3) * 2048);
                            m = max_abs8(m, t[0], t[1], t[2], t[3]);
                        }
                    }
#pragma unroll
                    for (int ks = NS; ks < 16; ks++) ldsm_x4_t(wreg[ks - NS], a + (ks >> 2) * 16384 + (ks & 3) * 2048);
                }
                if (b == 5) {
#pragma unroll
                    for (int ks = 16; ks < 24; ks++) ldsm_x4_t(wreg[ks - NS], a + (ks >> 2) * 16384 + (ks & 3) * 2048);
                    if (role == 2) {
#pragma unroll
                        for (int ks = NS; ks < 24; ks++) m = max_abs8(m, wreg[ks - NS][0], wreg[ks - NS][1], wreg[ks - NS][2], wreg[ks - NS][3]);
                    }
                }
            }
            mbar_wait(sbase + B_W + 16, 1);
            TSQ(13);
            wg_fence();
#pragma unroll
            for (int k = 12; k < 20; k++)
                wgmma_n64_ss(acc1, da + (uint64_t)((k >> 2) * 1024 + (k & 3) * 128), (smem_desc(sbase + x23_off(k >> 2), 16, 1024) | (1ull << 62)) + (uint64_t)((k & 3) * 2));
            wg_commit();
            wg_wait0();
            named_bar(11, 384);
#pragma unroll
            for (int i = 0; i < 8; i++)
                asm volatile("st.shared.v4.f32 [%0], {%1,%2,%3,%4};" :: "r"(sbase + SM_X + 5 * 8192 + i * 4096 + tid * 16),
                             "f"(acc1[4 * i]), "f"(acc1[4 * i + 1]), "f"(acc1[4 * i + 2]), "f"(acc1[4 * i + 3]) : "memory");
#pragma unroll
            for (int b = 7; b < 9; b++) {
#pragma unroll
                for (int ks = 4 * b - 4; ks < 4 * b; ks++) ldsm_x4_t(wreg[ks - NS], a + (ks >> 2) * 16384 + (ks & 3) * 2048);
                if (role == 2) {
#pragma unroll
                    for (int ks = 4 * b - 4; ks < 4 * b; ks++) m = max_abs8(m, wreg[ks - NS][0], wreg[ks - NS][1], wreg[ks - NS][2], wreg[ks - NS][3]);
                }
                const uint64_t db = smem_desc(sbase + x01_off(b), 16, 1024) | (1ull << 62);
                mbar_wait(sbase + B_W + 8 * b, 0);
                TSQ(1 + b);
                if (b == 8) TS3C(2);
                wg_fence();
#pragma unroll
                for (int k = 0; k < 4; k++) wgmma_n72_ss(acc, da + (uint64_t)(b * 1024 + k * 128), db + (uint64_t)(k * 2));
                wg_commit();
            }
#pragma unroll
            for (int ks = 32; ks < KPRE; ks++) ldsm_x4_t(wreg[ks - NS], a + (ks >> 2) * 16384 + (ks & 3) * 2048);
            if (role == 2) {
#pragma unroll
                for (int ks = KPRE; ks < 36; ks++) {
                    uint32_t t[4];
                    ldsm_x4_t(t, a + (ks >> 2) * 16384 + (ks & 3) * 2048);
                    m = max_abs8(m, t[0], t[1], t[2], t[3]);
                }
#pragma unroll
                for (int ks = 32; ks < KPRE; ks++) m = max_abs8(m, wreg[ks - NS][0], wreg[ks - NS][1], wreg[ks - NS][2], wreg[ks - NS][3]);
                m = warp_max_abs(m);
                if (lane == 0) asm volatile("st.volatile.global.u32 [%0], %1;" :: "l"(reinterpret_cast<uint32_t*>(&g_wv[h][0]) + warp), "r"(m | 1u) : "memory");
                __syncwarp();
            }
            wg_wait0();
            named_bar(9, 256);
            const uint32_t off = sbase + SM_T + (DH + warp * 16 + (lane & 15)) * 16 + (lane >> 4) * (DH * 16);
#pragma unroll
            for (int i = 0; i < 4; i++)
                stsm_x4(off + (i >> 1) * TBUF + (i & 1) * (2 * DH * 16), pack_bf16(acc[8 * i], acc[8 * i + 1]), pack_bf16(acc[8 * i + 2], acc[8 * i + 3]),
                        pack_bf16(acc[8 * i + 4], acc[8 * i + 5]), pack_bf16(acc[8 * i + 6], acc[8 * i + 7]));
            v0 = pack_bf16(acc[32], acc[33]);
            v1 = pack_bf16(acc[34], acc[35]);
#pragma unroll
            for (int ks = KPRE; ks < 36; ks++) ldsm_x4_t(wreg[ks - NS], a + (ks >> 2) * 16384 + (ks & 3) * 2048);
            if (role == 2) fence_async();
            bar_arrive(8, 384);
            named_bar(7, 256);
            asm volatile("barrier.cluster.arrive.relaxed.aligned;" ::: "memory");
        }
        TS3C(3);
        uint32_t ws[NS][4];
#pragma unroll
        for (int ks = NS - NP; ks < NS; ks++) ldsm_x4_t(ws[ks], w_addr(sbase, warp, lane_o) + (ks >> 2) * 16384 + (ks & 3) * 2048);
        asm volatile("barrier.cluster.wait.aligned;" ::: "memory");
        if (lane_o == 0 && role != 2 && warp < 2) tma_2d_mc(sbase + SM_X + (2 * role + warp) * 8192, &tmx2, (2 * role + warp + 5) * 64, 64, sbase + B_XT + 8);
        __syncwarp();
        TS3C(4);
        auto main_loop = [&](auto is_c) {
            constexpr bool C = decltype(is_c)::value;
            if (C) pad_code<PAD4>(); else pad_code<PAD3>();
            const uint32_t l16 = __shfl_sync(0xffffffffu, sbase + lane_o * 16, lane_o);
            const uint32_t ka = __shfl_sync(0xffffffffu, sbase + SM_T + (64 + (lane_o & 7) + ((lane_o >> 3) & 1) * 16 + (lane_o >> 4) * 8) * 16, lane_o);
            const uint32_t wa = __shfl_sync(0xffffffffu, w_addr(sbase, warp, lane_o), lane_o);
            auto post = [&](bool act, int s, uint32_t to, uint32_t ta, int scw, uint32_t v0, uint32_t v1) {
                int lane = lane_o;
                asm volatile("" : "+r"(lane));
                asm volatile("stmatrix.sync.aligned.m8n8.x2.shared.b16 [%0], {%1,%2};" :: "r"(l16 + ta), "r"(v0), "r"(v1) : "memory");
                if (C) {
                    if (act || s + 1 < NSEG) {
                        const uint32_t fo = (uint32_t)(warp * 256 + lane * 8);
                        const uint32_t rb0 = mapa(sbase, 0), rb1 = mapa(sbase, 1);
                        st_async64(rb0 + SM_VM + fo, v0, v1, rb0 + B_SB + 8 * (s & 1));
                        st_async64(rb1 + SM_VM + fo, v0, v1, rb1 + B_SB + 8 * (s & 1));
                        asm volatile("st.shared.v2.u32 [%0], {%1,%2};" :: "r"(sbase + SM_VM + fo), "r"(v0), "r"(v1) : "memory");
                        bar_arrive(2, 384);
                    }
                } else if (act) bar_arrive(2, 384);
                else {
                    named_bar(2, 384);
                    if (scw == 0) {
                        uint32_t kf[2][4], qf[2][4];
#pragma unroll
                        for (int k2 = 0; k2 < 2; k2++) { ldsm_x4_t(kf[k2], ka + to + k2 * 512); ldsm_x4_t(qf[k2], l16 + SM_T + to + k2 * 512); }
                        const uint32_t d0 = sbase + SM_S + lane * 8, bo = sbase + B_SB + 8 * (s & 1);
                        const uint32_t dr = HS ? d0 - lane * 4 : d0;
                        const uint32_t d1 = mapa(dr + 1280, role ^ 1), m1 = mapa(bo, role ^ 1), d2 = mapa(dr + role * 1280, 2), m2 = mapa(bo, 2);
                        score_group(qf, kf, d0, d1, m1, d2, m2);
                        bar_arrive(6, 160);
                        bar_arrive(5, 384);
                    }
                    if (scw == 8) {
                        const uint32_t dk = mapa(sbase + SM_X + XBUF + (2 + role) * 9216 + (warp - 4) * 256 + lane * 4, 2), mb = mapa(sbase + B_VX + 8, 2);
                        st_async32(dk, v0, mb);
                        st_async32(dk + 128, v1, mb);
                    }
                }
                FS(11, 0);
            };
            post(false, 0, 0, SM_T + warp * 256, warp ^ 7, v0, v1);
            if (tid == 128 && cta < NSEG) {
                fence_async();
                mbar_expect(sbase + B_E, XBUF);
                bulk_g2s(sbase + SM_X + 9 * 8192, xg + (size_t)cta * SEG * DM, 32768, sbase + B_E);
                bulk_g2s(sbase + SM_WS + 32768 + 4096, xg + (size_t)cta * SEG * DM + 16384, 4096, sbase + B_E);
            }
            __syncwarp();
            if (C) {
                named_bar(7, 256);
                if (warp == 1) norms_gather(lane_o, sbase);
            }
            auto chores = [&](int s, bool idle) {
                int lane = lane_o;
                asm volatile("" : "+r"(lane));
                const int hw = (s & 1) ? warp : warp - 4;
                const uint32_t tb = sbase + SM_T + (s & 3) * TBUF;
                if (idle) { if (hw != 2) named_bar(4, 384); else bar_arrive(4, 384); }
                if (hw == 2) {
                    if (lane == 0) {
                        {
                            if (C || !idle) fence_async();
                            if (C) {
                                store_tile(s + 1, h, 2, sbase + SM_T + ((s + 1) & 3) * TBUF, 2048, 10240);
                                store_tile(s, h, 2, tb, 0, idle ? 2048 : 10240);
                            } else store_tile(s, h, role, tb, 1024, 10240);
                            asm volatile("cp.async.bulk.commit_group;" ::: "memory");
                        }
                        {
                            asm volatile("cp.async.bulk.wait_group 0;" ::: "memory");
                            if (C) {
                                asm volatile("cp.async.bulk.shared::cluster.global.mbarrier::complete_tx::bytes.multicast::cluster [%0], [%1], 8192, [%2], %3;"
                                             :: "r"(sbase + SM_VX + ((s + 1) & 1) * 8192), "l"(&g_qkv[s + 1][h][2][2048]), "r"(sbase + B_VX + 8 * ((s + 1) & 1)), "h"((unsigned short)3) : "memory");
                            }
                            asm volatile("red.relaxed.gpu.global.add.u32 [%0], 1;" :: "l"(&g_flag[h * NSEG + s]) : "memory");
                        }
                    }
                    __syncwarp();
                    if (!C && (s & 1) && s + 4 < NSEG) bar_arrive(13, 160);
                }
                __syncwarp();
            };
            auto put_tiles = [&](const float (&acc)[32], uint32_t off) {
#pragma unroll
                for (int i = 0; i < 4; i++)
                    stsm_x4(off + (i >> 1) * TBUF + (i & 1) * (2 * DH * 16), pack_bf16(acc[8 * i], acc[8 * i + 1]), pack_bf16(acc[8 * i + 2], acc[8 * i + 3]),
                            pack_bf16(acc[8 * i + 4], acc[8 * i + 5]), pack_bf16(acc[8 * i + 6], acc[8 * i + 7]));
            };
            auto tile_off = [&](int p) {
                int lane = lane_o;
                asm volatile("" : "+r"(lane));
                return sbase + SM_T + (p & 1) * (2 * TBUF) + (DH + warp * 16 + (lane & 15)) * 16 + (lane >> 4) * (DH * 16);
            };
            {
                auto db = [&](int ks) { return (smem_desc(sbase + SM_X, 16, 1024) | (1ull << 62)) + (uint64_t)(((ks >> 2) - 5) * 512 + (ks & 3) * 2); };
                if (!C && warp != 7) bar_arrive(5, 384);
                if (warp == 5) {
                    mbar_wait(sbase + B_W + 8, 1);
                    bar_arrive(12, 160);
                }
                chores(0, false);
                float acc[32];
#pragma unroll
                for (int i = 0; i < 8; i++)
                    asm volatile("ld.shared.v4.f32 {%0,%1,%2,%3}, [%4];" : "=f"(acc[4 * i]), "=f"(acc[4 * i + 1]), "=f"(acc[4 * i + 2]), "=f"(acc[4 * i + 3])
                                 : "r"(l16 + warp * 512 + SM_X + 5 * 8192 + i * 4096) : "memory");
                mbar_wait(sbase + B_XT + 8, 0);
                FS(8, 0);
                named_bar(4, 384);
                wg_fence();
#pragma unroll
                for (int ks = 35; ks >= 20; ks--) wgmma_n64(acc, wreg[ks - NS], db(ks), 1);
                wg_commit();
                if (cta < NSEG) {
                    uint32_t m = 0u;
                    mbar_wait(sbase + B_E, 1);
#pragma unroll
                    for (int j = 0; j < 9; j++) {
                        const uint4 xv = lds128(l16 + warp * 512 + (j < 8 ? SM_X + 9 * 8192 + j * 4096 : SM_WS + 32768 + 4096));
                        m = max_abs8(m, xv.x, xv.y, xv.z, xv.w);
                    }
                    m = warp_max_abs(m);
                    if (lane_o == 0) asm volatile("st.volatile.global.u32 [%0], %1;" :: "l"(reinterpret_cast<uint32_t*>(&g_rx[cta][0]) + warp), "r"(m | 1u) : "memory");
                    __syncwarp();
                }
                FS(3, 0);
                wg_wait0();
                put_tiles(acc, tile_off(1));
                FS(7, __float_as_uint(acc[0]));
            }
            auto mem_proj = [&](uint32_t& u0, uint32_t& u1) {
#pragma unroll
                for (int ks = 0; ks < NS - NP; ks++) ldsm_x4_t(ws[ks], wa + (ks >> 2) * 16384 + (ks & 3) * 2048);
                FS(0, ws[0][0]);
                named_bar(1, 384);
                float acc[2][4], minv;
                uint32_t b[3][4];
#pragma unroll
                for (int kk = 0; kk < 3; kk++) ldsm_x4_t(b[kk], l16 + SM_M + kk * 512);
                FS(1, b[0][0]);
#pragma unroll
                for (int kk = 0; kk < 18; kk++) {
#pragma unroll
                    for (int i = 0; i < 2; i++) {
                        const int ks = 2 * kk + i;
                        if (ks < 2) mma_z(acc[i], ws[ks], b[kk % 3][2 * i], b[kk % 3][2 * i + 1]);
                        else if (ks < NS) mma_bf16(acc[i], ws[ks < NS ? ks : 0], b[kk % 3][2 * i], b[kk % 3][2 * i + 1]);
                        else mma_bf16(acc[i], wreg[ks >= NS ? ks - NS : 0], b[kk % 3][2 * i], b[kk % 3][2 * i + 1]);
                    }
                    if (kk + 3 < 18) ldsm_x4_t(b[kk % 3], l16 + SM_M + (kk + 3) * 512);
                    if (kk + 3 == 17) asm volatile("ld.shared.f32 %0, [%1];" : "=f"(minv) : "r"(sbase + SM_SC + 8) : "memory");
                }
                u0 = pack_bf16(fmaf(acc[1][0], minv, acc[0][0] * minv), fmaf(acc[1][1], minv, acc[0][1] * minv));
                u1 = pack_bf16(fmaf(acc[1][2], minv, acc[0][2] * minv), fmaf(acc[1][3], minv, acc[0][3] * minv));
                FS(2, u0);
            };
            int s = 0, rc = 9;
            bool act = warp >= 4;
            uint32_t to = TBUF, ta = SM_T + warp * 256 + TBUF;
            auto next_slot = [&]() {
                const uint32_t d = (s & 3) == 3 ? -3 * TBUF : TBUF;
                to += d; ta += d;
                asm volatile("" : "+r"(to), "+r"(ta));
            };
#pragma unroll 1
            for (;;) {
                uint32_t u0, u1;
                if (act) {
                    mem_proj(u0, u1);
                    s++;
                    post(true, s, to, ta, 1, u0, u1);
                    const int p = (s + 3) >> 1;
                    const uint32_t dlo = (uint32_t)smem_desc(sbase + SM_X, 16, 1024) + rc * 512;
                    const uint64_t da = smem_desc(sbase + SM_WS + (warp >> 2) * 8192, 1024, 1024) | (1ull << 62);
                    auto db = [&](int ks) {
                        const int j = ((ks >> 2) + 4) % 9;
                        return ((uint64_t)0x40000040u << 32) | (uint64_t)(dlo + (uint32_t)((j - (rc + j >= 13 ? 13 : 0)) * 512 + (ks & 3) * 2));
                    };
                    const uint32_t xph = (uint32_t)((p - 1) >> 1) & 1u;
                    float acc[32];
                    mbar_wait(sbase + B_XT + 8 * (p & 1), xph);
                    if (C) named_bar(7, 256); else named_bar(5, 384);
                    constexpr int N1 = C ? NC1C : NC1;
                    wg_fence();
#pragma unroll
                    for (int ks = 35; ks > 35 - N1; ks--) { if (ks == 35) wgmma_n64_z(acc, wreg[ks - NS], db(ks)); else wgmma_n64(acc, wreg[ks - NS], db(ks), 1); }
                    wg_commit();
                    wg_wait0();
                    FS(9, __float_as_uint(acc[0]));
                    next_slot();
                    FS(8, 0);
                    asm volatile("{\n.reg .pred p;\nsetp.ge.s32 p, %0, 0;\n@p bar.sync 4, 384;\n}" :: "r"(s) : "memory");
                    FS(3, 0);
                    wg_fence();
#pragma unroll
                    for (int ks = 35 - N1; ks >= KG1; ks--) wgmma_n64(acc, wreg[ks - NS], db(ks), 1);
                    wg_commit();
                    mbar_wait(sbase + B_XT + 16 + 8 * (p & 1), xph);
                    wg_fence();
#pragma unroll
                    for (int ks = 0; ks < NS; ks++) wgmma_n64_ss(acc, da + (uint64_t)((ks >> 2) * 1024 + (ks & 3) * 128), db(ks));
#pragma unroll
                    for (int ks = NS; ks < KG1; ks++) wgmma_n64(acc, wreg[ks - NS], db(ks), 1);
                    wg_commit();
                    if (!C && warp >= 4) named_bar(13, 160);
                    uint32_t off = tile_off(p);
                    rc = rc >= 4 ? rc - 4 : rc + 9;
                    asm volatile("" : "+r"(off), "+r"(rc));
                    wg_wait0();
                    put_tiles(acc, off);
                    FS(7, __float_as_uint(acc[0]));
                }
                int scw = s + 2 < NSEG ? warp ^ ((s & 1) ? 7 : 3) : (warp & 4) + 4;
                asm volatile("" : "+r"(scw));
                mem_proj(u0, u1);
                s++;
                post(false, s, to, ta, scw, u0, u1);
                if (s + 1 == NSEG) break;
                if (s + 2 < NSEG) {
                    if (!C && (warp & 3) == 2) fence_async();
                    if (C) named_bar(7, 256); else if (scw != 0) named_bar(5, 384);
                    chores(s, true);
                } else {
                    const uint32_t t0 = clock32();
                    const uint32_t dq = mapa(sbase + SM_X + XBUF + role * 9216, 2), mb = mapa(sbase + B_VX, 2);
                    if (!C) {
                        if (scw != 0) named_bar(5, 384);
                        if (tid == 64) { fence_async(); while (clock32() - t0 < TL_DELAY) {} bulk_s2s(dq, sbase + SM_T + 2 * TBUF + 1024, 9216, mb); }
                        __syncwarp();
                    }
                    named_bar(4, 384);
                    if (!C && tid == 64) { const uint32_t t1 = clock32(); while (clock32() - t1 < VX_DELAY) {} bulk_s2s(dq + 2 * 9216 + 1024, sbase + SM_T + 3 * TBUF + 2048, 8192, mb + 8); }
                    __syncwarp();
                }
                next_slot();
                act = s + 4 < NSEG;
            }
            if (C) named_bar(7, 256);
        };
        if (role == 2) main_loop(Flag<true>()); else main_loop(Flag<false>());
    } else {
        uint32_t wo[3][8][4];
        uint32_t mx2 = 0u;
        {
            const int pt = tid - 256, lane = lane_o, wq = warp - 8, g = lane >> 2, tq = lane & 3;
            TSQ(7);
            mbar_wait(sbase + B_E, 0);
            TSQ(8);
#pragma unroll
            for (int t = 0; t < 3; t++) {
                const int T = 3 * wq + t;
                const uint32_t a = sbase + SM_X01 + (T >> 2) * 16384 + ((lane >> 4) * 8 + (lane & 7)) * 128 + ((((T & 3) * 2 + ((lane >> 3) & 1)) ^ (lane & 7)) << 4);
#pragma unroll
                for (int kk = 0; kk < 8; kk++) ldsm_x4_t(wo[t][kk], a + ((2 * wq + kk) & 7) * 2048);
            }
            named_bar(3, 128);
            if (pt == 64) {
                fence_async();
#pragma unroll 1
                for (int i = 3; i < 9; i++) { stage_x(i); if (i < 7) stage_w(i); }
            }
            if (pt >= 96 && pt < 120) {
                *reinterpret_cast<uint4*>(g_acc + cta * 1024 + (pt - 96) * 16) = make_uint4(0u, 0u, 0u, 0u);
                __threadfence();
            }
            __syncwarp();
            TSQ(9);
            float c0 = 0.f;
#pragma unroll
            for (int t = 0; t < 3; t++) {
                float n[4][4];
#pragma unroll
                for (int i = 0; i < 4; i++) { n[i][0] = n[i][1] = n[i][2] = n[i][3] = 0.f; }
#pragma unroll
                for (int kk = 0; kk < 8; kk++)
#pragma unroll
                    for (int i = 0; i < 4; i++) mma_k8(n[i], wo[t][kk][i & 2], wo[t][kk][(i & 2) + 1], wo[t][kk][i]);
                if ((g >> 1) == tq) c0 = fmaxf(c0, (g & 1) ? fmaxf(n[0][1] + n[2][1], n[1][3] + n[3][3]) : fmaxf(n[0][0] + n[2][0], n[1][2] + n[3][2]));
            }
            c0 = __uint_as_float(__reduce_max_sync(0xffffffffu, __float_as_uint(c0)));
            uint32_t m = 0u;
            const int xb = role == 0 ? h % 9 : 9;
            auto x_max = [&]() {
                mbar_wait(sbase + B_W + 8 * xb, 0);
#pragma unroll
                for (int j = 0; j < 5; j++) {
                    uint4 xv;
                    asm volatile("ld.shared.v4.u32 {%0,%1,%2,%3}, [%4];" : "=r"(xv.x), "=r"(xv.y), "=r"(xv.z), "=r"(xv.w)
                                 : "r"(sbase + x01_off(xb) + (j < 4 ? pt + 128 * j : 512 + (pt & 63)) * 16) : "memory");
                    m = max_abs8(m, xv.x, xv.y, xv.z, xv.w);
                }
            };
            if (xb < 3) x_max();
            named_bar(10, 384);
            TSQ(10);
            if (pt == 64) {
                fence_async();
                mbar_expect(sbase + B_W + 16, 16384);
#pragma unroll
                for (int i = 3; i < 5; i++) tma_2d(sbase + x23_off(i), &tmx2, i * 64, 64, sbase + B_W + 16);
#pragma unroll 1
                for (int i = 7; i < 9; i++) stage_w(i);
            }
            __syncwarp();
            if (xb >= 3 && xb < 7) x_max();
            bar_arrive(11, 384);
            if (xb == 7 || xb == 8) x_max();
            asm volatile("barrier.cluster.arrive.relaxed.aligned;" ::: "memory");
            m = warp_max_abs(m);
            if (lane == 0) { sts32(sbase + SM_SC + 320 + 4 * wq, __float_as_uint(c0)); sts32(sbase + SM_SC + 336 + 4 * wq, m); }
            TSQ(1);
            named_bar(3, 128);
            if (pt == 0) {
                const uint4 a = lds128(sbase + SM_SC + 320), b = lds128(sbase + SM_SC + 336);
                st_vol_u2(&g_norm[cta], make_uint2(max(max(a.x, a.y), max(a.z, a.w)) | 1u, max(max(b.x, b.y), max(b.z, b.w)) | 1u));
            }
            __syncwarp();
            named_bar(8, 384);
            TSQ(2);
            asm volatile("barrier.cluster.wait.aligned;" ::: "memory");
            if (role == 2 && lane == 0 && wq < 2) vx_copy(sbase, 0, wq);
            __syncwarp();
        }
        const int wq = warp - 8;
        auto helper_loop = [&](auto is_c) {
        const bool C = is_c.value;
        if (C) pad_code<PAD2>(); else pad_code<PAD1>();
        const uint32_t sb = sbase;
        const uint32_t l8_o = __shfl_sync(0xffffffffu, sb + lane_o * 8, lane_o), l16_o = __shfl_sync(0xffffffffu, sb + lane_o * 16, lane_o);
        unsigned char* dst = g_acc + (role * 32 + wq * 8 + (lane_o >> 3)) * 1024 + (lane_o & 7) * 16;
        auto load_kf = [&](uint32_t (&kf)[2][4], int slot) {
            int lane = lane_o;
            asm volatile("" : "+r"(lane));
            const uint32_t ka = sb + SM_T + slot * TBUF + ((wq + 1) * DH + 64 + (lane & 7) + ((lane >> 3) & 1) * 16 + (lane >> 4) * 8) * 16;
#pragma unroll
            for (int k2 = 0; k2 < 2; k2++) ldsm_x4_t(kf[k2], ka + k2 * 512);
        };
        float minv = 1.f;
        uint32_t kf[2][4];
        if (!C) load_kf(kf, 0);
        int b3 = 0;
        int rx = 9;
        for (int s = 0; s + 1 < NSEG; s++) {
            const int n3 = b3 == 2 ? 0 : b3 + 1;
            uint32_t l8 = l8_o, l16 = l16_o;
            asm volatile("" : "+r"(l8), "+r"(l16));
            const uint32_t l4 = sb + ((l8 - sb) >> 1);
            {
                int lane = lane_o;
                asm volatile("" : "+r"(lane));
                if (C) {
                    if (lane == 0) {
                        if (wq == 3 && h == 0) {
                            const uint32_t t = gtime32();
                            st_vol_u2(&g_tick, make_uint2(t, lds32(sb + SM_SC + 12)));
                            sts32(sb + SM_SC + 12, t);
                        }
                    }
                    __syncwarp();
                    if (wq == 2 && s > 1 && lane < 24) {
                        *reinterpret_cast<uint4*>(g_acc + n3 * 128 + (3 * h + (lane >> 3)) * 1024 + (lane & 7) * 16) = make_uint4(0u, 0u, 0u, 0u);
                    }
                    if (wq == 1 && s == 3 && lane < 3) {
                        const int c = 3 * h + lane;
                        st_vol_u2(&g_norm[c], make_uint2(0u, 0u));
                        uint4* z = c < NSEG ? g_rx[c] : g_wv[c - NSEG];
                        st_vol_u4(z, make_uint4(0u, 0u, 0u, 0u)); st_vol_u4(z + 1, make_uint4(0u, 0u, 0u, 0u));
                    }
                    __syncwarp();
                }
                const uint32_t mw = __reduce_max_sync(0xffffffffu, max(mx2 << 16, mx2 & 0xffff0000u));
                if (lane == 0) sts32(sb + SM_SC + 16 + 4 * wq, mw);
            }
            const uint32_t to = SM_T + (s & 3) * TBUF;
            const uint32_t ph = (uint32_t)(s >> 1) & 1u;
            if (!C) {
                const uint32_t bo = sb + B_SB + 8 * (s & 1);
                uint32_t d0 = l8 + SM_S + (wq + 1) * 256, qa = l16 + to;
                const uint32_t dr = HS ? l4 + SM_S + (wq + 1) * 256 : d0;
                const uint32_t d1 = mapa(dr + 1280, role ^ 1), m1 = mapa(bo, role ^ 1), d2 = mapa(dr + role * 1280, 2), m2 = mapa(bo, 2);
                asm volatile("" : "+r"(d0), "+r"(qa));
                mbar_wait(sb + (s > 0 ? B_VX + 8 * (s & 1) : B_W), ph);
                FS(1, 0);
                named_bar(2, 384);
                uint32_t qf[2][4];
#pragma unroll
                for (int k2 = 0; k2 < 2; k2++) ldsm_x4_t(qf[k2], qa + k2 * 512);
                score_group(qf, kf, d0, d1, m1, d2, m2);
                bar_arrive(5, 384);
            } else named_bar(2, 384);
            if (!C && s == 0) {
                TSQ(3);
                mbar_wait(sb + B_VX, 0);
                TSQ(4);
            }
            float4 m4;
            asm volatile("ld.shared.v4.f32 {%0,%1,%2,%3}, [%4];" : "=f"(m4.x), "=f"(m4.y), "=f"(m4.z), "=f"(m4.w) : "r"(sb + SM_SC + 16) : "memory");
            const float c24 = __uint_as_float(lds32(sb + SM_SC + 4)), xb = __uint_as_float(lds32(sb + SM_SC + 64 + 4 * s));
            uint32_t vf[2][2][4], vm[2][2];
            uint32_t va = l16 + ((l16 >> 8) & 1) * 1792 + wq * 512 + (C ? to + DH * 16 : SM_VX + (s & 1) * 8192);
            auto load_vf = [&]() {
#pragma unroll
                for (int i = 0; i < 4; i++) ldsm_x4(vf[i & 1][i >> 1], va + (i & 1) * 256 + (i >> 1) * 4096);
            };
            load_vf();
            float scale = to_scale(fmaxf(fmaxf(fmaxf(m4.x, m4.y), fmaxf(m4.z, m4.w)) * minv, xb) * c24);
            uint32_t oa = l16 + wq * 512;
            asm volatile("" : "+f"(scale), "+r"(oa), "+r"(va));
            FS(7, __float_as_uint(scale));
            if (!C) named_bar(6, 160);
            if (C) mbar_wait(sb + B_SB + 8 * (s & 1), ph);
            float sv[5][2];
#pragma unroll
            for (int j = 0; j < 5; j++) {
                if (HS && C) { const uint32_t w = lds32(l4 + SM_S + j * 256); sv[j][0] = __uint_as_float(w << 16); sv[j][1] = __uint_as_float(w & 0xffff0000u); }
                else lds64f(sv[j][0], sv[j][1], l8 + SM_S + j * 256);
            }
            if (!C) mbar_wait(sb + B_SB + 8 * (s & 1), ph);
            FS(6, 0);
            uint32_t p[5];
            {
                float sr[5][2];
#pragma unroll
                for (int j = 0; j < 5; j++) {
                    if (HS) { const uint32_t w = lds32(l4 + SM_S + 1280 + j * 256); sr[j][0] = __uint_as_float(w << 16); sr[j][1] = __uint_as_float(w & 0xffff0000u); }
                    else lds64f(sr[j][0], sr[j][1], l8 + SM_S + 1280 + j * 256);
                }
                lds64(vm[0][0], vm[0][1], l8 + SM_VM + wq * 512);
                lds64(vm[1][0], vm[1][1], l8 + SM_VM + wq * 512 + 256);
#pragma unroll
                for (int j = 0; j < 5; j++) {
                    sv[j][0] += sr[j][0];
                    sv[j][1] += sr[j][1];
                }
                float mx = fmaxf(fmaxf(fmaxf(sv[0][0], sv[0][1]), fmaxf(sv[1][0], sv[1][1])), fmaxf(fmaxf(sv[2][0], sv[2][1]), fmaxf(sv[3][0], sv[3][1])));
                mx = fmaxf(mx, fmaxf(sv[4][0], sv[4][1]));
                {
                    const float m1 = __shfl_xor_sync(0xffffffffu, mx, 1), m2 = __shfl_xor_sync(0xffffffffu, mx, 2), m3 = __shfl_xor_sync(0xffffffffu, mx, 3);
                    mx = fmaxf(fmaxf(mx, m1), fmaxf(m2, m3));
                }
#pragma unroll
                for (int jj = 0; jj < 5; jj++) {
                    const int j = (jj + 1) % 5;
                    asm("ex2.approx.ftz.f32 %0, %1;" : "=f"(sv[j][0]) : "f"(sv[j][0] - mx));
                    asm("ex2.approx.ftz.f32 %0, %1;" : "=f"(sv[j][1]) : "f"(sv[j][1] - mx));
                    p[j] = pack_bf16(sv[j][0], sv[j][1]);
                }
            }
            FS(0, p[0]);
            uint32_t b[4][4];
            const uint32_t one4[4] = {0x3f803f80u, 0x3f803f80u, 0x3f803f80u, 0x3f803f80u};
            float zs[4];
            {
                float o0[2][4], o1[2][4];
                mma_z(o0[0], vf[0][0], p[1], p[2]);
                mma_z(o0[1], vf[1][0], p[1], p[2]);
                mma_z(o1[0], vf[0][1], p[3], p[4]);
                mma_z(o1[1], vf[1][1], p[3], p[4]);
                mma_k8(o0[0], vm[0][0], vm[0][1], p[0]);
                mma_k8(o0[1], vm[1][0], vm[1][1], p[0]);
                float z2[4];
                mma_z(zs, one4, p[1], p[2]);
                mma_z(z2, one4, p[3], p[4]);
                mma_k8(zs, one4[0], one4[1], p[0]);
                zs[0] += z2[0]; zs[1] += z2[1];
                uint32_t ow[4];
#pragma unroll
                for (int m = 0; m < 2; m++) {
                    ow[2 * m] = pack_bf16(o0[m][0] + o1[m][0], o0[m][1] + o1[m][1]);
                    ow[2 * m + 1] = pack_bf16(o0[m][2] + o1[m][2], o0[m][3] + o1[m][3]);
                }
                stsm_x4(oa + SM_O, ow[0], ow[1], ow[2], ow[3]);
                FS(2, 0);
                b[0][0] = movm(ow[0]); b[0][1] = movm(ow[1]);
                __syncwarp();
                asm volatile("ldmatrix.sync.aligned.m8n8.x2.trans.shared.b16 {%0,%1}, [%2];" : "=r"(b[0][2]), "=r"(b[0][3]) : "r"(oa + SM_O + 256));
            }
            float acc[3][2][4];
            named_bar(3, 128);
#pragma unroll
            for (int i = 1; i < 4; i++) ldsm_x4_t(b[i], l16 + SM_O + ((wq + i) & 3) * 512);
#pragma unroll
            for (int c = 0; c < 2; c++)
#pragma unroll
                for (int t = 0; t < 3; t++) mma_z(acc[t][c], wo[t][c], b[0][2 * c], b[0][2 * c + 1]);
            float z0, z1;
            asm volatile("rcp.approx.ftz.f32 %0, %1;" : "=f"(z0) : "f"(zs[0]));
            asm volatile("rcp.approx.ftz.f32 %0, %1;" : "=f"(z1) : "f"(zs[1]));
            asm volatile("{\n.reg .pred p;\nsetp.eq.s32 p, %1, 0;\n@p bar.sync 12, 160;\n@p ld.shared.f32 %0, [%2];\n}" : "+f"(scale) : "r"(s), "r"(sb + SM_SC) : "memory");
            z0 *= scale; z1 *= scale;
            FS(3, b[1][0]);
#pragma unroll
            for (int i = 1; i < 4; i++)
#pragma unroll
                for (int c = 0; c < 2; c++)
#pragma unroll
                    for (int t = 0; t < 3; t++) mma_bf16(acc[t][c], wo[t][2 * i + c], b[i][2 * c], b[i][2 * c + 1]);
            {
                uint32_t w[6];
#pragma unroll
                for (int t = 0; t < 3; t++) {
                    w[2 * t] = pack_f16(fmaf(acc[t][1][0], z0, acc[t][0][0] * z0), fmaf(acc[t][1][1], z1, acc[t][0][1] * z1));
                    w[2 * t + 1] = pack_f16(fmaf(acc[t][1][2], z0, acc[t][0][2] * z0), fmaf(acc[t][1][3], z1, acc[t][0][3] * z1));
                }
                FS(8, w[5]);
                asm volatile("red.relaxed.gpu.global.add.noftz.v4.f16x2 [%0], {%1,%2,%3,%4};" :: "l"(dst), "r"(w[0]), "r"(w[1]), "r"(w[2]), "r"(0x3c00u) : "memory");
                asm volatile("red.relaxed.gpu.global.add.noftz.v4.f16x2 [%0], {%1,%2,%3,%4};" :: "l"(dst + 4096), "r"(w[3]), "r"(w[4]), "r"(w[5]), "r"(0x3c00u) : "memory");
            }
            FS(9, 0);
            if (s == 0) TSQ(5);
            bar_arrive(4, 384);
            const uint32_t t0 = clock32();
            minv = __uint_as_float(0x7f000000u - __float_as_uint(scale));
            if (lane_o == 0) {
                if (wq == 0) sts32(sb + SM_SC + 8, __float_as_uint(minv));
                if (s + 3 < NSEG) {
                    if (wq == 0) mbar_expect(sb + B_SB + 8 * (s & 1), C ? 2560 >> HS : (1280 >> HS) + 2048);
                    if (wq == 1 && s > 0 && s + 5 < NSEG) mbar_expect(sb + B_XT + ((s & 1) ? 0 : 16) + 4 * ((s + 1) & 2), (s & 1) ? 32768 : 40960);
                    if (wq == 3 && !C) mbar_expect(sb + B_VX + 8 * (s & 1), 8192);
                }
            }
            __syncwarp();
            if (s == 1) {
                if (!C) pad_code<PADC>();
                int lane = lane_o;
                asm volatile("" : "+r"(lane));
                if (wq == 3) xmax_gather(lane, sb);
                __syncwarp();
            }
            if (!C) load_kf(kf, (s + 1) & 3);
            const uint4* src = reinterpret_cast<const uint4*>(dst + (wq * 16 - role * 32) * 1024);
            dst += n3 == 0 ? -256 : 128;
            asm volatile("" : "+l"(dst));
            const int xp = (s + 5) >> 1, kb = wq + ((s & 1) ? 2 * role : 4 + 3 * role);
            const bool xl = !C && xp < NSEG / 2 && wq < ((s & 1) ? 2 : 3 - role);
            const uint32_t xs = wq == 3 && (s & 1) == 0 && xp < NSEG / 2;
            const uint32_t xd = sb + SM_X + (rx + kb >= 13 ? rx + kb - 13 : rx + kb) * 8192;
            mx2 = poll_mem(src, l16 + SM_M + wq * 2304, t0, [&]() {
                if (xs && lane_o < 2) asm volatile("mbarrier.arrive.relaxed.cluster.shared::cluster.b64 _, [%0];" :: "r"(mapa(sb + B_XF, lane_o)) : "memory");
                if (!C && (xl || s == 0) && (s & 1) == 0) mbar_wait(sb + B_XF, (uint32_t)(s >> 1) & 1u);
                if (lane_o == 0) {
                    if (xl) tma_2d_mc(xd, &tmx2, ((s & 1) ? kb + 5 : kb - 4) * 64, xp * 64, sb + B_XT + ((s & 1) ? 0 : 16) + 8 * (xp & 1));
                    if (!C && s == 0 && role == 1) tma_2d_mc(sb + SM_X + (9 + wq) * 8192, &tmx2, (wq + 5) * 64, 128, sb + B_XT);
                }
                __syncwarp();
            });
            if ((s & 1) == 0) rx = rx >= 4 ? rx - 4 : rx + 9;
            if (s == 0) TSQ(6);
            b3 = n3;
        }
        if (!C) bar_arrive(2, 384);
        };
        if (role == 2) helper_loop(Flag<true>()); else helper_loop(Flag<false>());
    }
    TS3C(1);
    if (role == 2 && warp >= 4) last_rows();
    cluster_sync_all();
}

extern "C" void kernel_launch(void* const* d_in, const int* in_sizes, int n_in, void* d_out, int out_size) {
    const bf16* x = (const bf16*)d_in[0];
    const bf16* mem0 = (const bf16*)d_in[1];
    const bf16* Wq = (const bf16*)d_in[2];
    const bf16* Wk = (const bf16*)d_in[3];
    const bf16* Wv = (const bf16*)d_in[4];
    const bf16* Wo = (const bf16*)d_in[5];
    const bf16* logA = (const bf16*)d_in[8];
    const bf16* Aim = (const bf16*)d_in[9];
    const bf16* Cre = (const bf16*)d_in[10];
    const bf16* Cim = (const bf16*)d_in[11];
    const bf16* logdt = (const bf16*)d_in[12];
    const bf16* dskip = (const bf16*)d_in[13];
    const bf16* gw = (const bf16*)d_in[14];
    bf16* out = (bf16*)d_out;
    static bool attr_done = false;
    typedef CUresult (*EncFn)(CUtensorMap*, CUtensorMapDataType, cuuint32_t, void*, const cuuint64_t*, const cuuint64_t*, const cuuint32_t*,
                              const cuuint32_t*, CUtensorMapInterleave, CUtensorMapSwizzle, CUtensorMapL2promotion, CUtensorMapFloatOOBfill);
    static EncFn enc = nullptr;
    if (!attr_done) {
        void* fn = nullptr;
        cudaDriverEntryPointQueryResult qr;
        cudaGetDriverEntryPoint("cuTensorMapEncodeTiled", &fn, cudaEnableDefault, &qr);
        enc = (EncFn)fn;
        cudaFuncSetAttribute(k_chain, cudaFuncAttributeMaxDynamicSharedMemorySize, 232448);
        cudaFuncSetAttribute(k_side, cudaFuncAttributeMaxDynamicSharedMemorySize, SIDE_SMEM);
        attr_done = true;
    }
    CUtensorMap tmw[3];
    for (int i = 0; i < 3; i++) {
        const cuuint64_t dims[2] = {(cuuint64_t)HD, (cuuint64_t)DM};
        const cuuint64_t strides[1] = {(cuuint64_t)HD * 2};
        const cuuint32_t box[2] = {64, 64};
        const cuuint32_t es[2] = {1, 1};
        enc(&tmw[i], CU_TENSOR_MAP_DATA_TYPE_BFLOAT16, 2, (void*)(i == 0 ? Wq : (i == 1 ? Wk : Wv)), dims, strides, box, es, CU_TENSOR_MAP_INTERLEAVE_NONE,
            CU_TENSOR_MAP_SWIZZLE_128B, CU_TENSOR_MAP_L2_PROMOTION_L2_256B, CU_TENSOR_MAP_FLOAT_OOB_FILL_NONE);
    }
    CUtensorMap tmo;
    {
        const cuuint64_t dims[2] = {(cuuint64_t)DM, (cuuint64_t)HD};
        const cuuint64_t strides[1] = {(cuuint64_t)DM * 2};
        const cuuint32_t box[2] = {64, 128};
        const cuuint32_t es[2] = {1, 1};
        enc(&tmo, CU_TENSOR_MAP_DATA_TYPE_BFLOAT16, 2, (void*)Wo, dims, strides, box, es, CU_TENSOR_MAP_INTERLEAVE_NONE,
            CU_TENSOR_MAP_SWIZZLE_128B, CU_TENSOR_MAP_L2_PROMOTION_L2_128B, CU_TENSOR_MAP_FLOAT_OOB_FILL_NONE);
    }
    CUtensorMap tmx2;
    {
        const cuuint64_t dims[2] = {(cuuint64_t)DM, (cuuint64_t)S_LEN};
        const cuuint64_t strides[1] = {(cuuint64_t)DM * 2};
        const cuuint32_t box[2] = {64, 64};
        const cuuint32_t es[2] = {1, 1};
        enc(&tmx2, CU_TENSOR_MAP_DATA_TYPE_BFLOAT16, 2, (void*)x, dims, strides, box, es, CU_TENSOR_MAP_INTERLEAVE_NONE,
            CU_TENSOR_MAP_SWIZZLE_128B, CU_TENSOR_MAP_L2_PROMOTION_L2_128B, CU_TENSOR_MAP_FLOAT_OOB_FILL_NONE);
    }
    CUtensorMap tmm;
    {
        const cuuint64_t dims[2] = {(cuuint64_t)DM, (cuuint64_t)MEMT};
        const cuuint64_t strides[1] = {(cuuint64_t)DM * 2};
        const cuuint32_t box[2] = {64, (cuuint32_t)MEMT};
        const cuuint32_t es[2] = {1, 1};
        enc(&tmm, CU_TENSOR_MAP_DATA_TYPE_BFLOAT16, 2, (void*)mem0, dims, strides, box, es, CU_TENSOR_MAP_INTERLEAVE_NONE,
            CU_TENSOR_MAP_SWIZZLE_128B, CU_TENSOR_MAP_L2_PROMOTION_L2_128B, CU_TENSOR_MAP_FLOAT_OOB_FILL_NONE);
    }
    k_chain<<<NCTA, 384, 232448>>>(tmw[0], tmw[1], tmw[2], tmx2, tmo, tmm, x);
    {
        cudaLaunchConfig_t cfg = {};
        cfg.gridDim = dim3(SD_NCTA); cfg.blockDim = dim3(512); cfg.dynamicSmemBytes = SIDE_SMEM; cfg.stream = cudaStreamPerThread;
        cudaLaunchAttribute at[1];
        at[0].id = cudaLaunchAttributeProgrammaticStreamSerialization;
        at[0].val.programmaticStreamSerializationAllowed = 1;
        cfg.attrs = at; cfg.numAttrs = 1;
        cudaLaunchKernelEx(&cfg, k_side, tmo, x, logA, Aim, Cre, Cim, logdt, Wo, dskip, gw, out);
    }
}
```

```cpp
#include <cuda_runtime.h>
#include <cuda.h>
#include <cuda_bf16.h>
#include <stdint.h>

typedef __nv_bfloat16 bf16;
#define LDV4 "ld.volatile.global.v4.u32 {%0,%1,%2,%3}, [%4];"
#define STV4 "st.volatile.global.v4.u32 [%0], {%1,%2,%3,%4};"
#define STV2 "st.volatile.global.v2.u32 [%0], {%1,%2};"

constexpr int S_LEN = 2048, DM = 576, NH = 32, DH = 128, HD = 4096, MEMT = 8, SEG = 32, NSEG = 64, NST = 128;

__device__ __align__(128) bf16 g_gate[S_LEN];
constexpr int NCTA = NH * 3;
__device__ __align__(1024) unsigned char g_acc[96 * 1024];
__device__ __align__(128) uint2 g_norm[NCTA];
__device__ __align__(128) uint4 g_wv[NH][2];
__device__ __align__(128) uint4 g_rx[NSEG][2];
__device__ __align__(128) unsigned char g_qkv[NSEG][NH][3][10240];
__device__ __align__(128) bf16 g_ox[S_LEN * HD];
__device__ __align__(128) uint4 g_fp[8][36][6][128];
__device__ __align__(128) unsigned g_flag[NH * NSEG];
__device__ __align__(128) unsigned g_prog[8 * 64];
__device__ unsigned g_gcnt[64];
__device__ unsigned g_epoch;
__device__ __align__(128) uint2 g_tick;
__device__ __align__(128) bf16 g_y[DM * S_LEN];

#define TS3(slot) do {} while (0)
#define TS3P(slot) do {} while (0)
#define TSQ(slot) do {} while (0)
#define TS3W(slot) do {} while (0)
#define TSS(row, slot) do {} while (0)
#define TS3C(slot) do {} while (0)
#define TST(slot) do {} while (0)
#define TSA(seg, slot) do {} while (0)
#define TSG(i) do {} while (0)
#define FS(i, dep) do {} while (0)
__device__ __forceinline__ uint32_t smem_u32(const void* p) { return (uint32_t)__cvta_generic_to_shared(p); }
__device__ __forceinline__ float bf16r(float x) { return __bfloat162float(__float2bfloat16_rn(x)); }
__device__ __forceinline__ uint32_t pack_bf16(float lo, float hi) {
    __nv_bfloat162 v = __floats2bfloat162_rn(lo, hi);
    return *reinterpret_cast<uint32_t*>(&v);
}
__device__ __forceinline__ void ldsm_x4(uint32_t (&r)[4], uint32_t addr) {
    asm volatile("ldmatrix.sync.aligned.m8n8.x4.shared.b16 {%0,%1,%2,%3}, [%4];"
                 : "=r"(r[0]), "=r"(r[1]), "=r"(r[2]), "=r"(r[3]) : "r"(addr));
}
__device__ __forceinline__ void ldsm_x4_t(uint32_t (&r)[4], uint32_t addr) {
    asm volatile("ldmatrix.sync.aligned.m8n8.x4.trans.shared.b16 {%0,%1,%2,%3}, [%4];"
                 : "=r"(r[0]), "=r"(r[1]), "=r"(r[2]), "=r"(r[3]) : "r"(addr));
}
__device__ __forceinline__ void mma_bf16(float (&d)[4], const uint32_t (&a)[4], uint32_t b0, uint32_t b1) {
    asm volatile("mma.sync.aligned.m16n8k16.row.col.f32.bf16.bf16.f32 {%0,%1,%2,%3}, {%4,%5,%6,%7}, {%8,%9}, {%0,%1,%2,%3};"
                 : "+f"(d[0]), "+f"(d[1]), "+f"(d[2]), "+f"(d[3])
                 : "r"(a[0]), "r"(a[1]), "r"(a[2]), "r"(a[3]), "r"(b0), "r"(b1));
}
__device__ __forceinline__ uint2 ld_vol_u2(const uint2* p) {
    uint2 v; asm volatile("ld.volatile.global.v2.u32 {%0,%1}, [%2];" : "=r"(v.x), "=r"(v.y) : "l"(p) : "memory"); return v;
}
__device__ __forceinline__ void st_vol_u2(uint2* p, uint2 v) {
    asm volatile(STV2 :: "l"(p), "r"(v.x), "r"(v.y) : "memory");
}
__device__ __forceinline__ unsigned ld_acq(const unsigned* p) {
    unsigned v; asm volatile("ld.acquire.gpu.global.u32 %0, [%1];" : "=r"(v) : "l"(p) : "memory"); return v;
}
#define NS 10
#define NP 4
#define GATE_A 950
#define GATE_B 450
#define GATE_P 1800u
#define RLX_SLEEP 300
#define VX_DELAY 100
#define UNGATE_G 3
#define W14_SLEEP 60
#define GL_A 1150
#define GL_B 530
#define GS_A 1300
#define GS_B 480
#define NC1 3
#define NC1C 5
#define KPRE 34
#define PADC 0
#define PAD1 0
#define PAD2 0
#define PAD3 0
#define PAD4 0
#define HS 1
#define KG1 20
#define WO_SLEEP 200
#define WO_LAG 500
#define TM 29
#define TM2 (TM - 1)
#define TL_DELAY 600
#define POLL_DELAY 590
#define UNGATE 6
constexpr unsigned SPIN_LIMIT = 1u << 20;
constexpr int NATT = NSEG - 2;

constexpr int SD_CH = 16;
constexpr int SD_NCTA = DM / SD_CH;
constexpr int SD_ROW = 528;
constexpr int SD_U = 8 * SD_ROW;
constexpr int SD_TAP = 5888;
constexpr int SD_CPY = 1376 * 2;
constexpr int SD_WSTR = SD_TAP + 2 * SD_CPY;
constexpr int SD_SMEM = SD_CH * SD_U + 8 * SD_WSTR;
constexpr int O_U = 79, O_U3 = 911, O_U4 = 1055, O_W79 = 1023, O_W35 = 1151, O_W610 = 1279, O_W511 = 1487;

__device__ __forceinline__ uint32_t lds32(uint32_t a) { uint32_t v; asm volatile("ld.shared.u32 %0, [%1];" : "=r"(v) : "r"(a)); return v; }
__device__ __forceinline__ void sts32(uint32_t a, uint32_t v) { asm volatile("st.shared.u32 [%0], %1;" :: "r"(a), "r"(v) : "memory"); }
__device__ __forceinline__ uint4 lds128(uint32_t a) {
    uint4 v; asm volatile("ld.shared.v4.u32 {%0,%1,%2,%3}, [%4];" : "=r"(v.x), "=r"(v.y), "=r"(v.z), "=r"(v.w) : "r"(a) : "memory"); return v;
}
__device__ __forceinline__ void tap_tile(uint32_t (&t)[4], uint32_t a) {
    asm volatile("ld.volatile.shared.u32 %0, [%4];\nld.volatile.shared.u32 %1, [%4+-16];\nld.volatile.shared.u32 %2, [%4+16];\nld.volatile.shared.u32 %3, [%4];"
                 : "=r"(t[0]), "=r"(t[1]), "=r"(t[2]), "=r"(t[3]) : "r"(a));
}
constexpr uint32_t sd_pass(int type, int dl, int o, int d0, int d1) { return (uint32_t)(type | dl << 2 | d0 << 8 | d1 << 12 | o << 17); }
__constant__ uint32_t SD_PASS[14] = {sd_pass(0, 0, O_U, 0, 2), sd_pass(0, 1, O_U + 96, 0, 2), sd_pass(0, 2, O_U + 192, 0, 4), sd_pass(0, 3, O_U + 288, 0, 2), sd_pass(1, 0, O_U3, 8, 8),
                                     sd_pass(0, 4, O_U + 384, 0, 2), sd_pass(1, 0, O_U4, 8, 15), sd_pass(0, 5, O_U + 480, 0, 2), sd_pass(0, 6, O_U + 576, 0, 4), sd_pass(0, 7, O_U + 672, 0, 2),
                                     sd_pass(2, 0, O_W35, 2, 8), sd_pass(3, 0, O_W79, 2, 4), sd_pass(2, 1, O_W610, 4, 8), sd_pass(3, 0, O_W511, 8, 15)};
__device__ __forceinline__ uint32_t band2(int x, int lo, int hi) { return (x >= lo && x <= hi ? 0x3f80u : 0u) | (x + 1 >= lo && x + 1 <= hi ? 0x3f800000u : 0u); }
__device__ __forceinline__ void mma_z(float (&d)[4], const uint32_t (&a)[4], uint32_t b0, uint32_t b1);
__device__ __forceinline__ void put_tap(uint32_t a, float v) {
    asm volatile("{\n.reg .b16 h;\ncvt.rn.bf16.f32 h, %1;\nst.shared.b16 [%0], h;\nst.shared.b16 [%0+%2], h;\n}" :: "r"(a), "f"(v), "n"(SD_CPY - 2) : "memory");
}

__device__ __forceinline__ void named_bar(int id, int n) { asm volatile("bar.sync %0, %1;" :: "r"(id), "r"(n) : "memory"); }
__device__ __forceinline__ uint32_t pack_f16(float lo, float hi) {
    uint32_t r; asm("cvt.rn.f16x2.f32 %0, %1, %2;" : "=r"(r) : "f"(hi), "f"(lo)); return r;
}
__device__ __forceinline__ void cexp_t(float lr, float turns, float& re, float& im) {
    float m;
    asm("ex2.approx.ftz.f32 %0, %1;" : "=f"(m) : "f"(lr));
    const float a = (turns - rintf(turns)) * 6.283185307179586f;
    re = m * __cosf(a); im = m * __sinf(a);
}
__device__ __forceinline__ void csq(float& re, float& im) { const float r = re * re - im * im; im = 2.f * re * im; re = r; }
__device__ __forceinline__ void kb_state(const float* tp, float gf, uint32_t (&a)[4][2], uint32_t (&b)[5]) {
    const float4 p0 = *reinterpret_cast<const float4*>(tp), p1 = *reinterpret_cast<const float4*>(tp + 4);
    float wr, wi;
    cexp_t(p0.x * gf, p0.y * gf, wr, wi);
    float vr = wr * p1.x - wi * p1.y, vi = wr * p1.y + wi * p1.x;
#pragma unroll
    for (int c = 0; c < 4; c++) {
        a[c][0] = pack_f16(wr, wi); a[c][1] = pack_f16(vr, vi);
        csq(wr, wi);
        if (c < 3) csq(vr, vi);
    }
    b[0] = pack_f16(p0.z * wr - p0.w * wi, -p0.z * wi - p0.w * wr);
    float er = wr * p1.z - wi * p1.w, ei = wr * p1.w + wi * p1.z;
#pragma unroll
    for (int c = 0; c < 4; c++) {
        b[1 + c] = pack_f16(p0.z * er - p0.w * ei, -p0.z * ei - p0.w * er);
        if (c < 3) csq(er, ei);
    }
}
__device__ __forceinline__ uint32_t bf2_mul(uint32_t a, uint32_t b) { uint32_t r; asm("mul.rn.bf16x2 %0, %1, %2;" : "=r"(r) : "r"(a), "r"(b)); return r; }
__device__ __forceinline__ uint32_t bf2_add(uint32_t a, uint32_t b) { uint32_t r; asm("add.rn.bf16x2 %0, %1, %2;" : "=r"(r) : "r"(a), "r"(b)); return r; }
__device__ __forceinline__ uint32_t bf2_sub(uint32_t a, uint32_t b) { uint32_t r; asm("sub.rn.bf16x2 %0, %1, %2;" : "=r"(r) : "r"(a), "r"(b)); return r; }
__device__ __forceinline__ void wait_cnt(const unsigned* p, unsigned target) {
    unsigned it = 0;
    while ((int)(ld_acq(p) - target) < 0 && ++it < SPIN_LIMIT) __nanosleep(64);
}
__device__ __forceinline__ uint32_t gtime32() { uint32_t t; asm volatile("mov.u32 %0, %%globaltimer_lo;" : "=r"(t) :: "memory"); return t; }
__device__ __forceinline__ void gate(uint32_t tick_addr, uint32_t ga = GATE_A, uint32_t gb = GATE_B) {
    uint32_t t1, p;
    asm volatile("ld.volatile.shared.v2.u32 {%0,%1}, [%2];" : "=r"(t1), "=r"(p) : "r"(tick_addr) : "memory");
    uint32_t d = gtime32() - t1;
    if (d < 4u * p) {
        d -= d >= 2u * p ? 2u * p : 0u;
        d -= d >= p ? p : 0u;
        if (d + ga >= p && d + gb < p) {
            const uint32_t t2 = gtime32() + (p - gb - d);
            while ((int)(gtime32() - t2) < 0) {}
        }
    }
}

__device__ __forceinline__ void read_tick(uint32_t tick_addr) {
    const uint2 tk = ld_vol_u2(&g_tick);
    uint32_t p = tk.x - tk.y;
    p = p > GATE_P + 100u ? GATE_P + 100u : p;
    asm volatile("st.volatile.shared.v2.u32 [%0], {%1,%2};" :: "r"(tick_addr), "r"(tk.x), "r"(p) : "memory");
}

__device__ __forceinline__ void s4d_phase(unsigned char* smem_raw, const bf16* __restrict__ x, const bf16* __restrict__ logA,
                                          const bf16* __restrict__ Aim, const bf16* __restrict__ Cre, const bf16* __restrict__ Cim,
                                          const bf16* __restrict__ logdt, const bf16* __restrict__ dskip, const bf16* __restrict__ wslice) {
    const int tid = threadIdx.x, warp = __shfl_sync(0xffffffffu, tid >> 5, 0), lane = tid & 31;
    const int d0 = blockIdx.x * SD_CH;
    float* tab = reinterpret_cast<float*>(smem_raw + SD_CH * SD_U + warp * SD_WSTR);
    const uint32_t wb = smem_u32(tab);
    const int g = lane >> 2, tq = lane & 3;
    uint2 prm[4];
    float ldt;
    auto load_prm = [&](int d) {
        prm[0] = __ldg(reinterpret_cast<const uint2*>(logA + d * NST) + lane); prm[1] = __ldg(reinterpret_cast<const uint2*>(Aim + d * NST) + lane);
        prm[2] = __ldg(reinterpret_cast<const uint2*>(Cre + d * NST) + lane); prm[3] = __ldg(reinterpret_cast<const uint2*>(Cim + d * NST) + lane);
        ldt = __bfloat162float(logdt[d]);
    };
    load_prm(d0 + warp);
    for (int i = lane; i < 2 * SD_CPY / 16; i += 32) reinterpret_cast<uint4*>(tab + SD_TAP / 4)[i] = make_uint4(0u, 0u, 0u, 0u);
    TS3(20);
#pragma unroll 1
    for (int ch = 0; ch < 2; ch++) {
        const int d = d0 + 8 * ch + warp;
        const uint32_t ub = smem_u32(smem_raw) + (8 * ch + warp) * SD_U;
        float k2048 = 0.f, sinv;
        {
            const float dt = bf16r(expf(ldt));
            uint32_t cm = __vmaxu2(__vmaxu2(prm[2].x & 0x7fff7fffu, prm[2].y & 0x7fff7fffu), __vmaxu2(prm[3].x & 0x7fff7fffu, prm[3].y & 0x7fff7fffu));
            cm = __reduce_max_sync(0xffffffffu, max(cm << 16, cm & 0xffff0000u));
            int e = 134 - (int)(__float_as_uint(__uint_as_float(cm) * dt) >> 23);
            e = e > 100 ? 100 : (e < -100 ? -100 : e);
            const float s2 = __uint_as_float((uint32_t)(128 + e) << 23);
            sinv = __uint_as_float((uint32_t)(127 - e) << 23);
#pragma unroll
            for (int j = 0; j < 4; j++) {
                float q[4];
#pragma unroll
                for (int i = 0; i < 4; i++) { const uint32_t w = j < 2 ? prm[i].x : prm[i].y; q[i] = __uint_as_float((j & 1) ? w & 0xffff0000u : w << 16); }
                const float zl = -bf16r(expf(q[0])) * dt * 1.4426950408889634f;
                const float zt = q[1] * dt * 0.15915494309189535f;
                const float cr = s2 * (q[2] * dt), ci = s2 * (q[3] * dt);
                float ar, ai, br, bi, er, ei;
                cexp_t(zl * 8.f, zt * 8.f, ar, ai);
                cexp_t(zl * 128.f, zt * 128.f, br, bi);
                cexp_t(zl * 2048.f, zt * 2048.f, er, ei);
                k2048 += cr * er - ci * ei;
                *reinterpret_cast<float4*>(tab + (lane + 32 * j) * 8) = make_float4(zl, zt, cr, ci);
                *reinterpret_cast<float4*>(tab + (lane + 32 * j) * 8 + 4) = make_float4(ar, ai, br, bi);
            }
#pragma unroll
            for (int o = 16; o; o >>= 1) k2048 += __shfl_xor_sync(0xffffffffu, k2048, o);
        }
        __syncwarp();
        {
            float kc[5][4];
#pragma unroll
            for (int i = 0; i < 5; i++) { kc[i][0] = kc[i][1] = kc[i][2] = kc[i][3] = 0.f; }
            const float gf = (float)g;
#pragma unroll 2
            for (int ks = 0; ks < 16; ks++) {
                uint32_t a0[4][2], a1[4][2], b0[5], b1[5];
                kb_state(tab + (8 * ks + tq) * 8, gf, a0, b0);
                kb_state(tab + (8 * ks + 4 + tq) * 8, gf, a1, b1);
#pragma unroll
                for (int i = 0; i < 5; i++) {
                    const int c = i > 0 ? i - 1 : 0;
                    asm volatile("mma.sync.aligned.m16n8k16.row.col.f32.f16.f16.f32 {%0,%1,%2,%3}, {%4,%5,%6,%7}, {%8,%9}, {%0,%1,%2,%3};"
                                 : "+f"(kc[i][0]), "+f"(kc[i][1]), "+f"(kc[i][2]), "+f"(kc[i][3])
                                 : "r"(a0[c][0]), "r"(a0[c][1]), "r"(a1[c][0]), "r"(a1[c][1]), "r"(b0[i]), "r"(b1[i]));
                }
            }
            const uint32_t tp = wb + SD_TAP;
            const uint32_t a0 = tp + 2 * (O_U + 96 * g - 4 * tq);
            const uint32_t a2 = tp + 2 * (((g & 1) ? O_U + 96 * (2 * (g & 3)) : ((g & 2) ? O_W35 : O_W79 + 1)) - 32 - 8 * tq - (g >> 2));
            const uint32_t a3 = tp + 2 * (((g & 1) ? O_W35 : O_W610 + 1) - 64 - 16 * tq - (g >> 1));
            const uint32_t a4 = tp + 2 * (-128 - 32 * tq - g);
#pragma unroll
            for (int c = 0; c < 4; c++) {
                const int e = (c & 1) * 16 + (c >> 1) * 8;
                const bool first = c == 0 && lane == 0;
                put_tap(a0 - e / 4, kc[0][c] * sinv);
                put_tap(a0 - 32 - e / 4, kc[1][c] * sinv);
                put_tap(first ? tp + 2 * (O_U - 32) : a2 - e / 2, kc[2][c] * sinv);
                put_tap(first ? tp + 2 * (O_W79 - 63) : a3 - e, kc[3][c] * sinv);
                put_tap(first ? tp + 2 * (O_W610 - 127) : a4 + 2 * (O_W511 + 1 - e), kc[4][c] * sinv);
                if ((g & 1) == 0) {
                    put_tap(a4 + 2 * (O_U4 - e), kc[4][c] * sinv);
                    put_tap(first ? tp + 2 * (O_U3 - 128) : a4 + 2 * (O_U4 + 1 - e), kc[4][c] * sinv);
                }
            }
            if (lane == 0) {
                put_tap(tp + 2 * (O_U + 96 - 32), kc[2][0] * sinv);
                put_tap(tp + 2 * (O_U + 192 - 64), kc[3][0] * sinv);
                put_tap(tp + 2 * (O_W511 - 255), k2048 * sinv);
                put_tap(tp + 2 * (O_U4 - 255), k2048 * sinv);
            }
        }
        TS3(21 + 2 * ch);
        if (ch == 0) named_bar(1, 384);
        else {
#pragma unroll
            for (int i = 0; i < 4; i++) asm volatile("prefetch.global.L2 [%0];" :: "l"(wslice + (size_t)((tid & 127) + 128 * i) * DM));
        }
        __syncwarp();
        if (tid == 0) TSS(18, 4 * ch);
        const uint32_t sh = wb + 80 + 11 * SD_ROW;
#pragma unroll
        for (int p = 0; p < 8; p++) {
            uint4 v;
            asm volatile("ld.shared.v4.u32 {%0,%1,%2,%3}, [%4];" : "=r"(v.x), "=r"(v.y), "=r"(v.z), "=r"(v.w) : "r"(ub + p * SD_ROW + lane * 16) : "memory");
            uint32_t pv = __shfl_up_sync(0xffffffffu, v.w, 1);
            pv = lane == 0 ? 0u : pv;
            asm volatile("st.shared.v4.u32 [%0], {%1,%2,%3,%4};" :: "r"(sh + (p - 8) * SD_ROW + lane * 16), "r"(__byte_perm(pv, v.x, 0x5432)), "r"(__byte_perm(v.x, v.y, 0x5432)),
                         "r"(__byte_perm(v.y, v.z, 0x5432)), "r"(__byte_perm(v.z, v.w, 0x5432)) : "memory");
            if (p >= 5) asm volatile("st.shared.v4.u32 [%0], {%1,%2,%3,%4};" :: "r"(sh + (p - 16) * SD_ROW + lane * 16), "r"(pv), "r"(v.x), "r"(v.y), "r"(v.z) : "memory");
        }
        __syncwarp();
        if (tid == 0) TSS(18, 4 * ch + 1);
        float acc[16][4];
#pragma unroll
        for (int i = 0; i < 16; i++) { acc[i][0] = acc[i][1] = acc[i][2] = acc[i][3] = 0.f; }
        {
            const uint32_t ka = wb + SD_TAP + ((g & 1) ? 0 : SD_CPY - 2) + 2 * (2 * tq - g);
            uint32_t b[16][2], b2[14][2];
#pragma unroll
            for (int k = 0; k < 16; k++) { b[k][0] = b[k][1] = 0u; if (k < 14) b2[k][0] = b2[k][1] = 0u; }
#pragma unroll 1
            for (int ps = 0; ps < 14; ps++) {
                const uint32_t pw = __shfl_sync(0xffffffffu, SD_PASS[ps], 0), type = pw & 3u, kp = ka + (pw >> 16);
                const int dl = (pw >> 2) & 7, d0 = (pw >> 8) & 15, d1 = (pw >> 12) & 15;
                uint32_t t[2][4];
                tap_tile(t[0], kp - 32 * d0);
                if (type == 0) {
                    const int p = (lane & 7) - dl;
                    const uint32_t ra = (p < 0 ? sh : ub) + p * SD_ROW + (lane >> 3) * 16;
#pragma unroll
                    for (int k = 0; k < 8; k++)
                        asm volatile("ldmatrix.sync.aligned.m8n8.x4.shared.b16 {%0,%1,%2,%3}, [%4];"
                                     : "=r"(b[2 * k][0]), "=r"(b[2 * k][1]), "=r"(b[2 * k + 1][0]), "=r"(b[2 * k + 1][1]) : "r"(ra + k * 64));
                } else if (type == 2) {
                    const int p = (lane & 15) - 11, xo = 2 * tq - g;
                    const uint32_t qa = (p < 0 ? sh : ub) + p * SD_ROW + (lane >> 4) * 16;
                    const int lx = 6 - 5 * dl, hx = 8 - 3 * dl, ly = 2 - 2 * dl, hy = 4 + 2 * dl;
                    const uint32_t sel[4] = {band2(xo, lx, hx), band2(xo, ly, hy), band2(xo + 8, lx, hx), band2(xo + 8, ly, hy)};
#pragma unroll
                    for (int k = 0; k < 14; k++) {
                        uint32_t q[4];
                        ldsm_x4_t(q, qa + k * 32);
#pragma unroll
                        for (int i = 0; i < 2; i++) {
                            float w[4];
                            mma_z(w, sel, q[2 * i], q[2 * i + 1]);
                            b[k][i] = pack_bf16(w[0], w[1]);
                            b2[k][i] = pack_bf16(w[2], w[3]);
                        }
                    }
                } else if (type == 3) {
#pragma unroll
                    for (int k = 0; k < 14; k++) { b[k][0] = b2[k][0]; b[k][1] = b2[k][1]; }
                }
#pragma unroll
                for (int d = 0; d < 16; d += 2) {
                    if (d >= 8 || d >= d0) {
                        tap_tile(t[1], kp - 32 * (d + 1));
#pragma unroll
                        for (int k = 0; k + d < 16; k++) mma_bf16(acc[k + d], t[0], b[k][0], b[k][1]);
                        if ((d == 2 || d == 4 || d == 8) && d == d1) break;
                        if (d < 14) tap_tile(t[0], kp - 32 * (d + 2));
#pragma unroll
                        for (int k = 0; k + d + 1 < 16; k++) mma_bf16(acc[k + d + 1], t[1], b[k][0], b[k][1]);
                    }
                }
            }
        }
        __syncwarp();
        if (tid == 0) TSS(18, 4 * ch + 2);
        load_prm(d0 + 8 + warp);
        if (ch == 0) {
            if (lane == 0) {
                unsigned ep;
                asm volatile("ld.volatile.global.u32 %0, [%1];" : "=r"(ep) : "l"(&g_epoch) : "memory");
                wait_cnt(&g_gcnt[0], SD_NCTA * (ep + 1u));
            }
            __syncwarp();
        }
        if (tid == 0) TSS(18, 4 * ch + 3);
        uint4 gv[8];
#pragma unroll
        for (int i = 0; i < 8; i++) gv[i] = __ldcg(reinterpret_cast<const uint4*>(g_gate) + lane + 32 * i);
        const uint32_t dd = __byte_perm(*reinterpret_cast<const unsigned short*>(dskip + d), 0u, 0x1010);
#pragma unroll
        for (int i = 0; i < 8; i++) {
            uint32_t u[4];
            ldsm_x4_t(u, ub + (lane & 7) * SD_ROW + (lane >> 3) * 16 + i * 64);
            asm volatile("stmatrix.sync.aligned.m8n8.x4.shared.b16 [%0], {%1,%2,%3,%4};"
                         :: "r"(wb + (lane + 32 * i) * 16),
                            "r"(bf2_add(pack_bf16(acc[2 * i][0], acc[2 * i][1]), bf2_mul(u[0], dd))), "r"(bf2_add(pack_bf16(acc[2 * i][2], acc[2 * i][3]), bf2_mul(u[1], dd))),
                            "r"(bf2_add(pack_bf16(acc[2 * i + 1][0], acc[2 * i + 1][1]), bf2_mul(u[2], dd))), "r"(bf2_add(pack_bf16(acc[2 * i + 1][2], acc[2 * i + 1][3]), bf2_mul(u[3], dd))) : "memory");
        }
        __syncwarp();
#pragma unroll
        for (int i = 0; i < 8; i++) {
            const uint4 y = *reinterpret_cast<const uint4*>(tab + (lane + 32 * i) * 4);
            *reinterpret_cast<uint4*>(g_y + (((lane >> 1) + 16 * i) * DM + d) * 16 + (lane & 1) * 8) =
                make_uint4(bf2_mul(bf2_sub(0x3f803f80u, gv[i].x), y.x), bf2_mul(bf2_sub(0x3f803f80u, gv[i].y), y.y),
                           bf2_mul(bf2_sub(0x3f803f80u, gv[i].z), y.z), bf2_mul(bf2_sub(0x3f803f80u, gv[i].w), y.w));
        }
        __syncwarp();
        if (ch == 0) asm volatile("bar.arrive 11, 288;" ::: "memory");
        TS3(22 + 2 * ch);
    }
}
__device__ __forceinline__ void s4d_stage_u(unsigned char* smem_raw, const bf16* __restrict__ x, int pt) {
    const int p = pt & 7, w0 = pt >> 3;
    const uint4* src = reinterpret_cast<const uint4*>(x + (size_t)(16 * w0 + p) * DM + blockIdx.x * SD_CH);
    uint32_t* dst = reinterpret_cast<uint32_t*>(smem_raw + p * SD_ROW) + w0;
#pragma unroll 1
    for (int b = 0; b < 4; b++) {
        uint4 v[2][2][2];
#pragma unroll
        for (int i = 0; i < 8; i++) v[i >> 2][(i >> 1) & 1][i & 1] = src[((b * 2 + (i >> 2)) * 256 + ((i >> 1) & 1) * 8) * (DM / 8) + (i & 1)];
#pragma unroll
        for (int i = 0; i < 4; i++) {
            const uint32_t* lo = reinterpret_cast<const uint32_t*>(&v[i >> 1][0][i & 1]);
            const uint32_t* hi = reinterpret_cast<const uint32_t*>(&v[i >> 1][1][i & 1]);
#pragma unroll
            for (int c = 0; c < 8; c++) dst[((i & 1) * 8 + c) * (SD_U / 4) + (b * 2 + (i >> 1)) * 16] = __byte_perm(lo[c >> 1], hi[c >> 1], (c & 1) ? 0x7632 : 0x5410);
        }
    }
    asm volatile("bar.arrive 1, 384;" ::: "memory");
}

constexpr int WOC = DM / 3;
constexpr int TBUF = 5 * DH * 16;
constexpr int XBUF = SEG * DM * 2;
constexpr int SM_BAR = 0;
constexpr int B_SB = 0, B_VX = 16, B_XT = 32, B_XF = 144, B_W = 64, B_E = 136;
constexpr int SM_SC = 256;
constexpr int SM_F = SM_SC + 1280;
constexpr int SM_VM = SM_F + 2048;
constexpr int SM_S = SM_VM + 2048;
constexpr int SM_O = SM_S + 2560;
constexpr int SM_M = SM_O + 2048;
constexpr int SM_WS = 19456;
constexpr int SM_T = SM_WS + 49152;
constexpr int SM_VX = SM_T + 4 * TBUF;
constexpr int SM_X = SM_VX + 2 * 8192;
constexpr int SM_X01 = SM_WS + DM * DH * 2;
__host__ __device__ constexpr int x01_off(int b) { return b < 2 ? 1024 + b * 9216 : SM_X01 + (b == 2 ? 6 : b - 3) * 9216; }
__host__ __device__ constexpr int x23_off(int b) { return b < 3 ? SM_WS + 7 * 16384 + b * 8192 : x01_off(b - 3); }
constexpr int CH_SMEM = SM_X01 + 8 * 8192;
static_assert(SM_M + DM * 16 <= SM_WS && SM_X + 13 * 8192 <= CH_SMEM && NS <= 10 && CH_SMEM <= 232448 && SM_X % 1024 == 0 && SM_X01 % 1024 == 0 && 1024 + 2 * 9216 <= SM_WS, "smem");
__device__ __forceinline__ uint32_t clock32() { uint32_t t; asm volatile("mov.u32 %0, %%clock;" : "=r"(t) :: "memory"); return t; }

__device__ __forceinline__ uint32_t mapa(uint32_t a, uint32_t rank) {
    uint32_t r; asm volatile("mapa.shared::cluster.u32 %0, %1, %2;" : "=r"(r) : "r"(a), "r"(rank)); return r;
}
__device__ __forceinline__ void st_async32(uint32_t addr, uint32_t v, uint32_t mbar) {
    asm volatile("st.async.weak.shared::cluster.mbarrier::complete_tx::bytes.b32 [%0], %1, [%2];" :: "r"(addr), "r"(v), "r"(mbar) : "memory");
}
__device__ __forceinline__ void mbar_init(uint32_t bar, uint32_t cnt) {
    asm volatile("mbarrier.init.shared::cta.b64 [%0], %1;" :: "r"(bar), "r"(cnt) : "memory");
}
__device__ __forceinline__ void mbar_expect(uint32_t bar, uint32_t bytes) {
    asm volatile("mbarrier.arrive.expect_tx.shared::cta.b64 _, [%0], %1;" :: "r"(bar), "r"(bytes) : "memory");
}
__device__ __forceinline__ void mbar_wait(uint32_t bar, uint32_t parity) {
    unsigned it = 0;
    uint32_t ok;
    do {
        ++it;
        asm volatile("{\n.reg .pred p;\nmbarrier.try_wait.parity.shared::cta.b64 p, [%1], %2;\nselp.u32 %0, 1, 0, p;\n}" : "=r"(ok) : "r"(bar), "r"(parity) : "memory");
    } while ((ok == 0u) & (it < SPIN_LIMIT));
}
__device__ __forceinline__ void mbar_wait_long(uint32_t bar, uint32_t parity) {
    unsigned it = 0;
    while (true) {
        uint32_t ok;
        asm volatile("{\n.reg .pred p;\nmbarrier.try_wait.parity.shared::cta.b64 p, [%1], %2, %3;\nselp.u32 %0, 1, 0, p;\n}"
                     : "=r"(ok) : "r"(bar), "r"(parity), "r"(20000u) : "memory");
        if (ok || ++it >= SPIN_LIMIT) break;
    }
}
__device__ __forceinline__ bool mbar_test(uint32_t bar, uint32_t parity) {
    uint32_t ok;
    asm volatile("{\n.reg .pred p;\nmbarrier.test_wait.parity.shared::cta.b64 p, [%1], %2;\nselp.u32 %0, 1, 0, p;\n}" : "=r"(ok) : "r"(bar), "r"(parity) : "memory");
    return ok != 0u;
}
__device__ __forceinline__ uint64_t policy_evict_first() {
    uint64_t pol; asm volatile("createpolicy.fractional.L2::evict_first.b64 %0, 1.0;" : "=l"(pol)); return pol;
}
__device__ __forceinline__ void cluster_sync_all() {
    asm volatile("barrier.cluster.arrive.release.aligned;\nbarrier.cluster.wait.acquire.aligned;" ::: "memory");
}
__device__ __forceinline__ uint4 ld_vol_u4(const uint4* p) {
    uint4 v; asm volatile(LDV4 : "=r"(v.x), "=r"(v.y), "=r"(v.z), "=r"(v.w) : "l"(p) : "memory"); return v;
}
__device__ __forceinline__ void ld_vol_u4_p(uint4& v, const uint4* p, uint32_t pred) {
    asm volatile("{\n.reg .pred p;\nsetp.ne.u32 p, %5, 0;\n@p " LDV4 "\n}"
                 : "+r"(v.x), "+r"(v.y), "+r"(v.z), "+r"(v.w) : "l"(p), "r"(pred) : "memory");
}
__device__ __forceinline__ void st_vol_u4(uint4* p, uint4 v) {
    asm volatile(STV4 :: "l"(p), "r"(v.x), "r"(v.y), "r"(v.z), "r"(v.w) : "memory");
}
__device__ __forceinline__ void mma_bf16_r(float (&d)[4], uint32_t a0, uint32_t a1, uint32_t a2, uint32_t a3, uint32_t b0, uint32_t b1) {
    asm volatile("mma.sync.aligned.m16n8k16.row.col.f32.bf16.bf16.f32 {%0,%1,%2,%3}, {%4,%5,%6,%7}, {%8,%9}, {%0,%1,%2,%3};"
                 : "+f"(d[0]), "+f"(d[1]), "+f"(d[2]), "+f"(d[3])
                 : "r"(a0), "r"(a1), "r"(a2), "r"(a3), "r"(b0), "r"(b1));
}

__device__ __forceinline__ uint64_t smem_desc(uint32_t addr, uint32_t lbo, uint32_t sbo) {
    return (uint64_t)((addr & 0x3FFFF) >> 4) | ((uint64_t)(lbo >> 4) << 16) | ((uint64_t)(sbo >> 4) << 32);
}
__device__ __forceinline__ void wg_fence() { asm volatile("wgmma.fence.sync.aligned;" ::: "memory"); }
__device__ __forceinline__ void wg_commit() { asm volatile("wgmma.commit_group.sync.aligned;" ::: "memory"); }
__device__ __forceinline__ void wg_wait0() { asm volatile("wgmma.wait_group.sync.aligned 0;" ::: "memory"); }
__device__ __forceinline__ void fence_async() { asm volatile("fence.proxy.async.shared::cta;" ::: "memory"); }
__device__ __forceinline__ void wgmma_n64_ss(float (&d)[32], uint64_t adesc, uint64_t bdesc) {
    asm volatile("{\n.reg .pred p;\nsetp.eq.b32 p, 0, 0;\n"
                 "wgmma.mma_async.sync.aligned.m64n64k16.f32.bf16.bf16 {%0,%1,%2,%3,%4,%5,%6,%7,%8,%9,%10,%11,%12,%13,%14,%15,%16,%17,%18,%19,%20,%21,%22,%23,%24,%25,%26,%27,%28,%29,%30,%31}, %32, %33, p, 1, 1, 1, 0;\n}"
                 : "+f"(d[0]), "+f"(d[1]), "+f"(d[2]), "+f"(d[3]), "+f"(d[4]), "+f"(d[5]), "+f"(d[6]), "+f"(d[7]), "+f"(d[8]), "+f"(d[9]), "+f"(d[10]), "+f"(d[11]), "+f"(d[12]), "+f"(d[13]), "+f"(d[14]), "+f"(d[15]), "+f"(d[16]), "+f"(d[17]), "+f"(d[18]), "+f"(d[19]), "+f"(d[20]), "+f"(d[21]), "+f"(d[22]), "+f"(d[23]), "+f"(d[24]), "+f"(d[25]), "+f"(d[26]), "+f"(d[27]), "+f"(d[28]), "+f"(d[29]), "+f"(d[30]), "+f"(d[31])
                 : "l"(adesc), "l"(bdesc));
}
__device__ __forceinline__ void wgmma_n72_ss(float (&d)[36], uint64_t adesc, uint64_t bdesc) {
    asm volatile("{\n.reg .pred p;\nsetp.eq.b32 p, 0, 0;\n"
                 "wgmma.mma_async.sync.aligned.m64n72k16.f32.bf16.bf16 {%0,%1,%2,%3,%4,%5,%6,%7,%8,%9,%10,%11,%12,%13,%14,%15,%16,%17,%18,%19,%20,%21,%22,%23,%24,%25,%26,%27,%28,%29,%30,%31,%32,%33,%34,%35}, %36, %37, p, 1, 1, 1, 0;\n}"
                 : "+f"(d[0]), "+f"(d[1]), "+f"(d[2]), "+f"(d[3]), "+f"(d[4]), "+f"(d[5]), "+f"(d[6]), "+f"(d[7]), "+f"(d[8]), "+f"(d[9]), "+f"(d[10]), "+f"(d[11]), "+f"(d[12]), "+f"(d[13]), "+f"(d[14]), "+f"(d[15]), "+f"(d[16]), "+f"(d[17]), "+f"(d[18]), "+f"(d[19]), "+f"(d[20]), "+f"(d[21]), "+f"(d[22]), "+f"(d[23]), "+f"(d[24]), "+f"(d[25]), "+f"(d[26]), "+f"(d[27]), "+f"(d[28]), "+f"(d[29]), "+f"(d[30]), "+f"(d[31]), "+f"(d[32]), "+f"(d[33]), "+f"(d[34]), "+f"(d[35])
                 : "l"(adesc), "l"(bdesc));
}
__device__ __forceinline__ void tma_2d(uint32_t dst, const CUtensorMap* tm, int c0, int c1, uint32_t mbar) {
    asm volatile("cp.async.bulk.tensor.2d.shared::cluster.global.tile.mbarrier::complete_tx::bytes [%0], [%1, {%2, %3}], [%4];"
                 :: "r"(dst), "l"(tm), "r"(c0), "r"(c1), "r"(mbar) : "memory");
}

__device__ __forceinline__ void bulk_g2s(uint32_t dst, const void* src, uint32_t bytes, uint32_t mbar) {
    asm volatile("cp.async.bulk.shared::cluster.global.mbarrier::complete_tx::bytes [%0], [%1], %2, [%3];"
                 :: "r"(dst), "l"(src), "r"(bytes), "r"(mbar) : "memory");
}
__device__ __forceinline__ void bulk_g2s_h(uint32_t dst, const void* src, uint32_t bytes, uint32_t mbar, uint64_t pol) {
    asm volatile("cp.async.bulk.shared::cluster.global.mbarrier::complete_tx::bytes.L2::cache_hint [%0], [%1], %2, [%3], %4;"
                 :: "r"(dst), "l"(src), "r"(bytes), "r"(mbar), "l"(pol) : "memory");
}
__device__ __forceinline__ void tma_2d_mc(uint32_t dst, const CUtensorMap* tm, int c0, int c1, uint32_t mbar) {
    asm volatile("cp.async.bulk.tensor.2d.shared::cluster.global.tile.mbarrier::complete_tx::bytes.multicast::cluster [%0], [%1, {%2, %3}], [%4], %5;"
                 :: "r"(dst), "l"(tm), "r"(c0), "r"(c1), "r"(mbar), "h"((unsigned short)7) : "memory");
}
__device__ __forceinline__ void bulk_s2s(uint32_t dst, uint32_t src, uint32_t bytes, uint32_t mbar) {
    asm volatile("cp.async.bulk.shared::cluster.shared::cta.mbarrier::complete_tx::bytes [%0], [%1], %2, [%3];"
                 :: "r"(dst), "r"(src), "r"(bytes), "r"(mbar) : "memory");
}
__device__ __forceinline__ void wgmma_n40_ss(float (&d)[20], uint64_t adesc, uint64_t bdesc, int scale_d) {
    asm volatile("{\n.reg .pred p;\nsetp.ne.b32 p, %22, 0;\n"
                 "wgmma.mma_async.sync.aligned.m64n40k16.f32.bf16.bf16 {%0,%1,%2,%3,%4,%5,%6,%7,%8,%9,%10,%11,%12,%13,%14,%15,%16,%17,%18,%19}, %20, %21, p, 1, 1, 1, 1;\n}"
                 : "+f"(d[0]), "+f"(d[1]), "+f"(d[2]), "+f"(d[3]), "+f"(d[4]), "+f"(d[5]), "+f"(d[6]), "+f"(d[7]),
                   "+f"(d[8]), "+f"(d[9]), "+f"(d[10]), "+f"(d[11]), "+f"(d[12]), "+f"(d[13]), "+f"(d[14]), "+f"(d[15]),
                   "+f"(d[16]), "+f"(d[17]), "+f"(d[18]), "+f"(d[19])
                 : "l"(adesc), "l"(bdesc), "r"(scale_d));
}
__device__ __forceinline__ void wgmma_n64_z(float (&d)[32], const uint32_t (&a)[4], uint64_t bdesc) {
    asm volatile("{\n.reg .pred p;\nsetp.ne.b32 p, 0, 0;\n"
                 "wgmma.mma_async.sync.aligned.m64n64k16.f32.bf16.bf16 {%0,%1,%2,%3,%4,%5,%6,%7,%8,%9,%10,%11,%12,%13,%14,%15,%16,%17,%18,%19,%20,%21,%22,%23,%24,%25,%26,%27,%28,%29,%30,%31}, {%32,%33,%34,%35}, %36, p, 1, 1, 0;\n}"
                 : "=f"(d[0]), "=f"(d[1]), "=f"(d[2]), "=f"(d[3]), "=f"(d[4]), "=f"(d[5]), "=f"(d[6]), "=f"(d[7]),
                   "=f"(d[8]), "=f"(d[9]), "=f"(d[10]), "=f"(d[11]), "=f"(d[12]), "=f"(d[13]), "=f"(d[14]), "=f"(d[15]),
                   "=f"(d[16]), "=f"(d[17]), "=f"(d[18]), "=f"(d[19]), "=f"(d[20]), "=f"(d[21]), "=f"(d[22]), "=f"(d[23]),
                   "=f"(d[24]), "=f"(d[25]), "=f"(d[26]), "=f"(d[27]), "=f"(d[28]), "=f"(d[29]), "=f"(d[30]), "=f"(d[31])
                 : "r"(a[0]), "r"(a[1]), "r"(a[2]), "r"(a[3]), "l"(bdesc));
}
__device__ __forceinline__ void wgmma_n64(float (&d)[32], const uint32_t (&a)[4], uint64_t bdesc, int scale_d) {
    asm volatile("{\n.reg .pred p;\nsetp.ne.b32 p, %37, 0;\n"
                 "wgmma.mma_async.sync.aligned.m64n64k16.f32.bf16.bf16 {%0,%1,%2,%3,%4,%5,%6,%7,%8,%9,%10,%11,%12,%13,%14,%15,%16,%17,%18,%19,%20,%21,%22,%23,%24,%25,%26,%27,%28,%29,%30,%31}, {%32,%33,%34,%35}, %36, p, 1, 1, 0;\n}"
                 : "+f"(d[0]), "+f"(d[1]), "+f"(d[2]), "+f"(d[3]), "+f"(d[4]), "+f"(d[5]), "+f"(d[6]), "+f"(d[7]),
                   "+f"(d[8]), "+f"(d[9]), "+f"(d[10]), "+f"(d[11]), "+f"(d[12]), "+f"(d[13]), "+f"(d[14]), "+f"(d[15]),
                   "+f"(d[16]), "+f"(d[17]), "+f"(d[18]), "+f"(d[19]), "+f"(d[20]), "+f"(d[21]), "+f"(d[22]), "+f"(d[23]),
                   "+f"(d[24]), "+f"(d[25]), "+f"(d[26]), "+f"(d[27]), "+f"(d[28]), "+f"(d[29]), "+f"(d[30]), "+f"(d[31])
                 : "r"(a[0]), "r"(a[1]), "r"(a[2]), "r"(a[3]), "l"(bdesc), "r"(scale_d));
}

constexpr int SB_FULL = 0, SB_EMPTY = 64, SB_QKF = 128, SB_VF = 144, SB_QKE = 160, SB_VE = 176, SB_OF = 192, SB_WO = 208  , SB_TICK = 216, SB_SEEN = 224, SB_FI = 232, SB_REQ = 240;
constexpr int AT_0 = 256, AT_ST = 10240 + 2 * 9216;
constexpr int FS_A = 58368;
constexpr int FS_P = FS_A + 131072;
constexpr int FS_I = FS_P + 16384;
constexpr int FS_O = FS_I + 12288;
constexpr int FS_Z = FS_O + 12288, FS_G = AT_0 + 2 * AT_ST;
constexpr int SIDE_SMEM = FS_Z + 2048;
static_assert(SIDE_SMEM <= 232448 && FS_G + 128 <= FS_A && FS_A + SD_SMEM <= SIDE_SMEM, "smem");

__device__ __forceinline__ void wg_wait1() { asm volatile("wgmma.wait_group.sync.aligned 1;" ::: "memory"); }
__device__ __forceinline__ void mbar_arrive(uint32_t bar) { asm volatile("mbarrier.arrive.shared::cta.b64 _, [%0];" :: "r"(bar) : "memory"); }
__device__ __forceinline__ void wait_cnt_rlx(const unsigned* p, unsigned target, bool urgent) {
    unsigned it = 0, v;
    while (true) {
        asm volatile("ld.relaxed.gpu.global.u32 %0, [%1];" : "=r"(v) : "l"(p) : "memory");
        if ((int)(v - target) >= 0 || ++it >= SPIN_LIMIT) break;
        if (!urgent) __nanosleep(RLX_SLEEP);
    }
}

__device__ __forceinline__ float xrow_softmax(float (&sc)[20], uint32_t (&p)[5], int wq, int lane) {
    constexpr float EC = (float)(1.4426950408889634 * 0.08838834764831845);
    const int lim = 8 * wq + (lane >> 2) - 2 * (lane & 3);
    float mx = fmaxf(sc[0], sc[1]);
#pragma unroll
    for (int j = 1; j < 5; j++) {
        sc[4 * j] = 8 * j - 8 > lim ? -INFINITY : sc[4 * j];
        sc[4 * j + 1] = 8 * j - 7 > lim ? -INFINITY : sc[4 * j + 1];
    }
    mx = fmaxf(fmaxf(mx, fmaxf(fmaxf(sc[4], sc[5]), fmaxf(sc[8], sc[9]))), fmaxf(fmaxf(sc[12], sc[13]), fmaxf(sc[16], sc[17])));
    {
        const float m1 = __shfl_xor_sync(0xffffffffu, mx, 1), m2 = __shfl_xor_sync(0xffffffffu, mx, 2), m3 = __shfl_xor_sync(0xffffffffu, mx, 3);
        mx = fmaxf(fmaxf(mx, m1), fmaxf(m2, m3));
    }
    float sum = 0.f;
#pragma unroll
    for (int j = 0; j < 5; j++) {
        float e0, e1;
        asm("ex2.approx.ftz.f32 %0, %1;" : "=f"(e0) : "f"((sc[4 * j] - mx) * EC));
        asm("ex2.approx.ftz.f32 %0, %1;" : "=f"(e1) : "f"((sc[4 * j + 1] - mx) * EC));
        p[j] = pack_bf16(e0, e1);
        sum += e0 + e1;
    }
    return sum;
}
__device__ __forceinline__ float xrow_inv(float sum) {
    sum += __shfl_xor_sync(0xffffffffu, sum, 1);
    sum += __shfl_xor_sync(0xffffffffu, sum, 2);
    float r;
    asm("rcp.approx.ftz.f32 %0, %1;" : "=f"(r) : "f"(sum));
    return r;
}

__device__ __forceinline__ void stsm_x4(uint32_t addr, uint32_t r0, uint32_t r1, uint32_t r2, uint32_t r3) {
    asm volatile("stmatrix.sync.aligned.m8n8.x4.shared.b16 [%0], {%1,%2,%3,%4};" :: "r"(addr), "r"(r0), "r"(r1), "r"(r2), "r"(r3) : "memory");
}
__device__ __forceinline__ void xrow_pv(uint32_t (&ob)[16], const uint32_t (&p)[5], float psum, uint32_t vt) {
    float o[32];
    const uint64_t dv = smem_desc(vt, 2048, 128);
    uint32_t pa[6][4];
#pragma unroll
    for (int i = 0; i < 6; i++) {
        const int ks = i >> 1, hf = i & 1;
        pa[i][hf] = p[2 * ks]; pa[i][hf ^ 1] = 0u;
        pa[i][2 + hf] = ks < 2 ? p[ks < 2 ? 2 * ks + 1 : 0] : 0u; pa[i][3 - hf] = 0u;
    }
    wg_fence();
#pragma unroll
    for (int i = 0; i < 6; i++) { if (i == 0) wgmma_n64_z(o, pa[0], dv); else wgmma_n64(o, pa[i], dv + (uint64_t)((i & 1) * 64 + (i >> 1) * 256), 1); }
    wg_commit();
    const float inv = xrow_inv(psum);
    wg_wait0();
#pragma unroll
    for (int i = 0; i < 8; i++) { ob[i] = pack_bf16(o[4 * i] * inv, o[4 * i + 1] * inv); ob[8 + i] = pack_bf16(o[4 * i + 2] * inv, o[4 * i + 3] * inv); }
}
__device__ __forceinline__ uint32_t h2_to_bf2(uint32_t h) {
    uint32_t r;
    asm("{\n.reg .f16 l, h;\n.reg .f32 a, b;\nmov.b32 {l, h}, %1;\ncvt.f32.f16 a, l;\ncvt.f32.f16 b, h;\ncvt.rn.bf16x2.f32 %0, b, a;\n}" : "=r"(r) : "r"(h));
    return r;
}
__device__ __forceinline__ uint32_t max_abs2(uint32_t a, uint32_t b) { uint32_t r; asm("max.NaN.xorsign.abs.bf16x2 %0, %1, %2;" : "=r"(r) : "r"(a), "r"(b)); return r; }
__device__ __forceinline__ uint32_t movm(uint32_t v) {
    uint32_t r; asm volatile("movmatrix.sync.aligned.m8n8.trans.b16 %0, %1;" : "=r"(r) : "r"(v)); return r;
}
__device__ __forceinline__ void bar_arrive(int id, int n) { asm volatile("bar.arrive %0, %1;" :: "r"(id), "r"(n) : "memory"); }
__device__ __forceinline__ void lds64(uint32_t& a, uint32_t& b, uint32_t addr) {
    asm volatile("ld.shared.v2.u32 {%0,%1}, [%2];" : "=r"(a), "=r"(b) : "r"(addr) : "memory");
}
__device__ __forceinline__ void lds64f(float& a, float& b, uint32_t addr) {
    asm volatile("ld.shared.v2.f32 {%0,%1}, [%2];" : "=f"(a), "=f"(b) : "r"(addr) : "memory");
}
__device__ __forceinline__ void st_async64(uint32_t addr, uint32_t a, uint32_t b, uint32_t mbar) {
    asm volatile("st.async.weak.shared::cluster.mbarrier::complete_tx::bytes.v2.b32 [%0], {%1,%2}, [%3];" :: "r"(addr), "r"(a), "r"(b), "r"(mbar) : "memory");
}
__device__ __forceinline__ void mma_z(float (&d)[4], const uint32_t (&a)[4], uint32_t b0, uint32_t b1) {
    asm volatile("mma.sync.aligned.m16n8k16.row.col.f32.bf16.bf16.f32 {%0,%1,%2,%3}, {%4,%5,%6,%7}, {%8,%9}, {%10,%10,%10,%10};"
                 : "=f"(d[0]), "=f"(d[1]), "=f"(d[2]), "=f"(d[3])
                 : "r"(a[0]), "r"(a[1]), "r"(a[2]), "r"(a[3]), "r"(b0), "r"(b1), "f"(0.f));
}
__device__ __forceinline__ void mma_k8(float (&d)[4], uint32_t a0, uint32_t a1, uint32_t b) {
    asm volatile("mma.sync.aligned.m16n8k8.row.col.f32.bf16.bf16.f32 {%0,%1,%2,%3}, {%4,%5}, {%6}, {%0,%1,%2,%3};"
                 : "+f"(d[0]), "+f"(d[1]), "+f"(d[2]), "+f"(d[3]) : "r"(a0), "r"(a1), "r"(b));
}
__global__ void __launch_bounds__(512, 1) k_side(const __grid_constant__ CUtensorMap tmo, const bf16* __restrict__ x, const bf16* __restrict__ logA, const bf16* __restrict__ Aim,
                                                 const bf16* __restrict__ Cre, const bf16* __restrict__ Cim, const bf16* __restrict__ logdt,
                                                 const bf16* __restrict__ Wo, const bf16* __restrict__ dskip, const bf16* __restrict__ gw,
                                                 bf16* __restrict__ out) {
    extern __shared__ __align__(1024) unsigned char smem_raw[];
    const uint32_t sbase = smem_u32(smem_raw);
    const int tid = threadIdx.x, warp = __shfl_sync(0xffffffffu, tid >> 5, 0), lane = tid & 31, cta = blockIdx.x;
    const int cb = cta >> 2, kq = cta & 3;
    if (tid == 0) {
        for (int i = 0; i < 8; i++) { mbar_init(sbase + SB_FULL + 8 * i, 1); mbar_init(sbase + SB_EMPTY + 8 * i, 4); }
        for (int i = 0; i < 2; i++) {
            mbar_init(sbase + SB_QKF + 8 * i, 1); mbar_init(sbase + SB_VF + 8 * i, 1); mbar_init(sbase + SB_QKE + 8 * i, 4);
            mbar_init(sbase + SB_VE + 8 * i, 1); mbar_init(sbase + SB_OF + 8 * i, 4);
        }
        mbar_init(sbase + SB_WO, 1);
        mbar_init(sbase + SB_WO + 40, 1);
        mbar_init(sbase + SB_FI, 1);
        mbar_init(sbase + SB_REQ, 4);
        *reinterpret_cast<uint2*>(smem_raw + SB_TICK) = make_uint2(0u, 0u);
        *reinterpret_cast<uint32_t*>(smem_raw + SB_SEEN) = 0u;
        asm volatile("fence.mbarrier_init.release.cluster;" ::: "memory");
    }
    TS3(0);
    asm volatile("fence.proxy.async;" ::: "memory");
    __syncthreads();
    auto epoch = []() {
        unsigned ep;
        asm volatile("ld.volatile.global.u32 %0, [%1];" : "=r"(ep) : "l"(&g_epoch) : "memory");
        return ep + 1u;
    };
    if (warp >= 12) {
      asm volatile("setmaxnreg.dec.sync.aligned.u32 40;");
      {
        uint32_t gwv[9];
#pragma unroll
        for (int i = 0; i < 9; i++) gwv[i] = reinterpret_cast<const uint32_t*>(gw)[lane + 32 * i];
#pragma unroll 1
        for (int i = 0; i < 8; i++) {
            uint32_t xv[2][9];
            float sm[2];
#pragma unroll
            for (int j = 0; j < 2; j++) {
                const int t = min(cta * 57 + 8 * i + 4 * j + warp - 12, S_LEN - 1);
#pragma unroll
                for (int k = 0; k < 9; k++) xv[j][k] = reinterpret_cast<const uint32_t*>(x + t * DM)[lane + 32 * k];
            }
#pragma unroll
            for (int j = 0; j < 2; j++) {
                sm[j] = 0.f;
#pragma unroll
                for (int k = 0; k < 9; k++) {
                    const uint32_t pr = bf2_mul(xv[j][k], gwv[k]);
                    sm[j] += __uint_as_float(pr << 16) + __uint_as_float(pr & 0xffff0000u);
                }
            }
            float v = (lane < 16 ? sm[0] : sm[1]) + __shfl_xor_sync(0xffffffffu, lane < 16 ? sm[1] : sm[0], 16);
#pragma unroll
            for (int o = 8; o; o >>= 1) v += __shfl_xor_sync(0xffffffffu, v, o);
            const float gv = 1.f / (1.f + expf(-bf16r(v)));
            const int tt = 8 * i + 4 * (lane >> 4) + warp - 12;
            if ((lane & 15) == 0 && tt < 57 && cta * 57 + tt < S_LEN) g_gate[cta * 57 + tt] = __float2bfloat16_rn(gv);
        }
        named_bar(2, 128);
        if (tid == 480) {
            __threadfence();
            asm volatile("red.relaxed.gpu.global.add.u32 [%0], 1;" :: "l"(&g_gcnt[0]) : "memory");
        }
        __syncwarp();
      }
      const unsigned ep = epoch();
      if (warp == 12 || warp == 15) {
        const int pi = warp == 12 ? 0 : 1;
        auto stage_wo = [&](int i0, int i1) {
            if (lane == 0) {
                fence_async();
#pragma unroll 1
                for (int i = i0; i < i1; i++) {
                    gate(sbase + SB_TICK);
                    tma_2d(sbase + FS_A + i * 16384, &tmo, cb * 64, kq * 1024 + i * 128, sbase + SB_WO + (i >> 2) * 40);
                    if (WO_SLEEP > 0) __nanosleep(WO_SLEEP);
                }
            }
            __syncwarp();
        };
        if (lane == 0) mbar_expect(sbase + SB_WO + pi * 40, 65536);
        if (pi == 0) {
            named_bar(11, 288);
            stage_wo(0, 2);
        }
        named_bar(3, 320);
        if (pi == 0) stage_wo(2, 4);
        else {
            if (WO_LAG > 0) __nanosleep(WO_LAG);
            stage_wo(4, 8);
        }
        if (lane == 0) TSS(17, 2 + pi);
        if (tid == 480) {
            __threadfence();
            asm volatile("red.relaxed.gpu.global.add.u32 [%0], 1;" :: "l"(&g_gcnt[32]) : "memory");
        }
        __syncwarp();
        named_bar(12 + pi, 160);
        if (lane == 0) {
            const int kb = 2 * kq + pi;
            fence_async();
            for (int pr = 0; pr < NSEG / 2; pr++) {
                const bool gon = pr < NSEG / 2 - UNGATE_G;
                wait_cnt_rlx(&g_prog[kb * 64 + pr], 8u * ep, pr >= NSEG / 2 - 2);
                if (pi == 0) asm volatile("st.volatile.shared.u32 [%0], %1;" :: "r"(sbase + SB_SEEN), "r"(pr + 1) : "memory");
                if (pr >= 30 && pi == 0) TSS(4 + pr - 30, 0);
                if (pr == 31) TS3P(26);
                if (pr == 30) TS3P(1);
#pragma unroll
                for (int j = 0; j < 4; j++) {
                    const int st = 4 * pi + j;
                    mbar_wait_long(sbase + SB_EMPTY + 8 * st, ((uint32_t)pr & 1u) ^ 1u);
                    mbar_expect(sbase + SB_FULL + 8 * st, 16384);
                    if (gon) gate(sbase + SB_TICK);
                    bulk_g2s(sbase + FS_A + st * 16384, g_ox + ((size_t)(pr * NH + 4 * kb + j)) * 8192, 16384, sbase + SB_FULL + 8 * st);
                }
            }
        }
        __syncwarp();
      } else if (warp == 13) {
        if (lane == 0) {
            const uint64_t pol = policy_evict_first();
            bool next_ok = false;
            for (int seg = 0; seg < NATT; seg++) {
                const uint32_t st = seg & 1, ph = (uint32_t)(seg >> 1) & 1u, ab = sbase + AT_0 + st * AT_ST;
                if (!next_ok) {
                    const unsigned* fp = &g_flag[(cta & (NH - 1)) * NSEG + seg];
                    unsigned it = 0, v0, v1;
                    while (true) {
                        asm volatile("ld.relaxed.gpu.global.u32 %0, [%1];" : "=r"(v0) : "l"(fp) : "memory");
                        asm volatile("ld.relaxed.gpu.global.u32 %0, [%1+4];" : "=r"(v1) : "l"(fp) : "memory");
                        read_tick(sbase + SB_TICK);
                        if ((int)(v0 - 3u * ep) >= 0 || ++it >= SPIN_LIMIT) break;
                        if (seg < NSEG - UNGATE || cta >= NH) __nanosleep(RLX_SLEEP);
                    }
                    next_ok = (int)(v1 - 3u * ep) >= 0;
                } else next_ok = false;
                if (cta < NH) {
                    TSA(seg, 0);
                    mbar_wait_long(sbase + SB_QKE + 8 * st, ph ^ 1u);
                    TSA(seg, 1);
                    mbar_expect(sbase + SB_QKF + 8 * st, 2 * 9216);
                    if (seg < NSEG - UNGATE) gate(sbase + SB_TICK, GL_A, GL_B);
                    TSA(seg, 2);
                    bulk_g2s_h(ab + 10240, &g_qkv[seg][cta][0][1024], 9216, sbase + SB_QKF + 8 * st, pol);
                    bulk_g2s_h(ab + 10240 + 9216, &g_qkv[seg][cta][1][1024], 9216, sbase + SB_QKF + 8 * st, pol);
                    mbar_wait_long(sbase + SB_VE + 8 * st, ph ^ 1u);
                    mbar_expect(sbase + SB_VF + 8 * st, 10240);
                    if (seg < NSEG - UNGATE) gate(sbase + SB_TICK, GL_A, GL_B);
                    TSA(seg, 3);
                    bulk_g2s_h(ab, &g_qkv[seg][cta][2][0], 10240, sbase + SB_VF + 8 * st, pol);
                }
            }
        }
        __syncwarp();
      } else if (warp == 14) {
        if (lane == 0) {
            int seg = cta < NH ? 0 : NATT, p = 0;
            unsigned it = 0;
            while ((seg < NATT || p < NSEG / 2 - 1) && ++it < 16 * SPIN_LIMIT) {
                if (p < NSEG / 2 - 1 && mbar_test(sbase + SB_REQ, (uint32_t)p & 1u)) {
                    if (p == 0) { wait_cnt(&g_gcnt[32], SD_NCTA * ep); asm volatile("fence.proxy.async;" ::: "memory"); }
                    mbar_expect(sbase + SB_FI, (p < NSEG / 2 - 2 ? 12288 : 2048 + 32) + 2048 + 32);
                    if (p < NSEG / 2 - UNGATE_G - 1) gate(sbase + SB_TICK);
                    if (p < NSEG / 2 - 2) bulk_g2s(sbase + FS_I, &g_fp[p & 7][cta][0][0], 12288, sbase + SB_FI);
                    else {
                        bulk_g2s(sbase + FS_I, g_y + ((p * 4 + 4 + kq) * DM + cb * 64) * 16, 2048, sbase + SB_FI);
                        bulk_g2s(sbase + FS_G + 32, g_gate + p * 64 + 64 + kq * 16, 32, sbase + SB_FI);
                    }
                    bulk_g2s(sbase + FS_Z, g_y + ((p * 4 + kq) * DM + cb * 64) * 16, 2048, sbase + SB_FI);
                    bulk_g2s(sbase + FS_G, g_gate + p * 64 + kq * 16, 32, sbase + SB_FI);
                    p++;
                } else if (seg < NATT && mbar_test(sbase + SB_OF + 8 * (seg & 1), (uint32_t)(seg >> 1) & 1u)) {
                    const uint32_t st = seg & 1, ab = sbase + AT_0 + st * AT_ST;
                    TSA(seg, 5);
                    if (seg < NSEG - UNGATE) gate(sbase + SB_TICK, GS_A, GS_B);
                    TSA(seg, 6);
                    unsigned char* dst = reinterpret_cast<unsigned char*>(g_ox) + ((size_t)((seg >> 1) * NH + cta)) * 16384 + (seg & 1) * 8192;
                    asm volatile("cp.async.bulk.global.shared::cta.bulk_group [%0], [%1], 8192;" :: "l"(dst), "r"(ab) : "memory");
                    asm volatile("cp.async.bulk.commit_group;" ::: "memory");
                    asm volatile("cp.async.bulk.wait_group.read 0;" ::: "memory");
                    mbar_arrive(sbase + SB_VE + 8 * st);
                    asm volatile("cp.async.bulk.wait_group 0;" ::: "memory");
                    asm volatile("red.relaxed.gpu.global.add.u32 [%0], 1;" :: "l"(&g_prog[(cta >> 2) * 64 + (seg >> 1)]) : "memory");
                    TSA(seg, 7);
                    seg++;
                } else if (seg < NSEG - UNGATE) __nanosleep(W14_SLEEP);
            }
        }
        __syncwarp();
      }
    } else if (warp >= 8) {
        asm volatile("setmaxnreg.dec.sync.aligned.u32 88;");
          s4d_stage_u(smem_raw + FS_A, x, tid - 256);
        const int wq = warp - 8;
        for (int seg = 0; seg < (cta < NH ? NATT : 0); seg++) {
            const uint32_t st = seg & 1, ph = (uint32_t)(seg >> 1) & 1u, ab = sbase + AT_0 + st * AT_ST;
            float sc[20];
            if (seg < NSEG - UNGATE) mbar_wait_long(sbase + SB_QKF + 8 * st, ph); else mbar_wait(sbase + SB_QKF + 8 * st, ph);
            if (tid == 256) TSA(seg, 4);
            {
                const uint64_t da = smem_desc(ab + 10240 + 1024, 128, 1024), db = smem_desc(ab + 10240, 128, 2048);
                wg_fence();
#pragma unroll
                for (int ks = 0; ks < 8; ks++) wgmma_n40_ss(sc, da + (uint64_t)((ks >> 2) * 576 + (ks & 3) * 16), db + (uint64_t)((ks >> 2) * 576 + (ks & 3) * 16), ks > 0);
                wg_commit();
                wg_wait0();
            }
            if (lane == 0) mbar_arrive(sbase + SB_QKE + 8 * st);
            uint32_t p[5], ob[16];
            const float psum = xrow_softmax(sc, p, wq, lane);
            mbar_wait(sbase + SB_VF + 8 * st, ph);
            xrow_pv(ob, p, psum, ab);
            named_bar(6, 128);
#pragma unroll
            for (int i = 0; i < 4; i++) stsm_x4(ab + wq * 2048 + i * 512 + lane * 16, ob[4 * i], ob[4 * i + 1], ob[4 * i + 2], ob[4 * i + 3]);
            fence_async();
            __syncwarp();
            if (lane == 0) mbar_arrive(sbase + SB_OF + 8 * st);
        }
    } else {
        asm volatile("setmaxnreg.inc.sync.aligned.u32 192;");
        const int wg = warp >> 2, wq = warp & 3;
        s4d_phase(smem_raw + FS_A, x, logA, Aim, Cre, Cim, logdt, dskip, Wo + (size_t)((2 * kq + wg) * 512) * DM + cb * 64);
        TS3(2);
        if (lane == 0) TSS(16, warp);
        named_bar(3, 320);
        if (tid == 0) TSS(17, 0);
        uint32_t wa[32][4];
        mbar_wait_long(sbase + SB_WO + wg * 40, 0);
        if (tid == 0) TSS(17, 1);
        {
            const uint32_t a = sbase + FS_A + wg * 65536 + ((lane >> 4) * 8 + (lane & 7)) * 128 + (((wq * 2 + ((lane >> 3) & 1)) ^ (lane & 7)) << 4);
#pragma unroll
            for (int ks = 0; ks < 32; ks++) ldsm_x4_t(wa[ks], a + ks * 2048);
        }
        named_bar(12 + wg, 160);
        TS3(3);
        if (tid == 0) TSS(17, 4);
        auto product = [&](float (&acc)[32], int pr, const int wg) {
                if (pr + wg > 0) named_bar(4 + wg, 256);
                const uint64_t db = smem_desc(sbase + FS_A + wg * 65536, 128, 2048);
                TSG(0);
#pragma unroll
                for (int j = 0; j < 4; j++) {
                    mbar_wait(sbase + SB_FULL + 8 * (4 * wg + j), (uint32_t)pr & 1u);
                    if (j == 0) TSG(1);
                    if (j == 3) TSG(2);
                    wg_fence();
#pragma unroll
                    for (int ks = 0; ks < 8; ks++) {
                        if ((j | ks) == 0) wgmma_n64_z(acc, wa[0], db);
                        else wgmma_n64(acc, wa[8 * j + ks], db + (uint64_t)(j * 1024 + ks * 16), 1);
                    }
                    wg_commit();
                    if (j == 3 && pr + wg < NSEG / 2) bar_arrive(4 + (wg ^ 1), 256);
                    if (j > 0) { wg_wait1(); if (lane == 0) mbar_arrive(sbase + SB_EMPTY + 8 * (4 * wg + j - 1)); }
                }
                wg_wait0();
                if (pr == 31) TS3W(27);
                TSG(3);
                if (lane == 0) mbar_arrive(sbase + SB_EMPTY + 8 * (4 * wg + 3));
        };
        if (wg == 1) {
            for (int pr = 0; pr < NSEG / 2; pr++) {
                uint32_t t16 = (uint32_t)(wq * 32 + lane) * 16u;
                asm volatile("" : "+r"(t16));
                float acc[32];
                product(acc, pr, 1);
                    uint32_t tag = ((uint32_t)(pr >> 3) & 1u) ^ 1u;
                    tag = __shfl_sync(0xffffffffu, tag, lane);
                    named_bar(8, 256);
                    unsigned char* dst = reinterpret_cast<unsigned char*>(&g_fp[pr & 7][4 * cb][2 * kq - 2][0]) + t16;
                    const uint32_t own = sbase + FS_O + (pr % 3) * 4096 + t16;
#pragma unroll
                    for (int q = 0; q < 8; q++) {
                        float4 p;
                        asm volatile("ld.shared.v4.f32 {%0,%1,%2,%3}, [%4];" : "=f"(p.x), "=f"(p.y), "=f"(p.z), "=f"(p.w) : "r"(sbase + FS_P + t16 + q * 2048) : "memory");
                        acc[4 * q] = __uint_as_float((__float_as_uint(acc[4 * q] + p.x) & ~1u) | tag); acc[4 * q + 1] = __uint_as_float((__float_as_uint(acc[4 * q + 1] + p.y) & ~1u) | tag);
                        acc[4 * q + 2] = __uint_as_float((__float_as_uint(acc[4 * q + 2] + p.z) & ~1u) | tag); acc[4 * q + 3] = __uint_as_float((__float_as_uint(acc[4 * q + 3] + p.w) & ~1u) | tag);
                    }
#pragma unroll
                    for (int q = 0; q < 8; q++) {
                        asm volatile("{\n.reg .pred p;\nsetp.ne.s32 p, %5, %6;\n@p st.volatile.global.v4.f32 [%0], {%1,%2,%3,%4};\n@!p st.shared.v4.f32 [%7], {%1,%2,%3,%4};\n}"
                                     :: "l"(dst + (q & 1) * 2048), "f"(acc[4 * q]), "f"(acc[4 * q + 1]), "f"(acc[4 * q + 2]), "f"(acc[4 * q + 3]), "r"(q >> 1), "r"(kq),
                                        "r"(own + (q & 1) * 2048) : "memory");
                        if (q & 1) dst += (q >> 1) == kq ? 12288 + 4096 : 12288;
                    }
                    bar_arrive(9, 256);
                    if (pr == 31) TS3W(28);
                TSG(4);
            }
        } else {
          int nsync = 0;
          int np = 1, nf = 0, pr = 0, pf = -1;
          while (true) {
            uint32_t t16 = (uint32_t)(wq * 32 + lane) * 16u;
            asm volatile("" : "+r"(t16));
            if (pr < 0) {
                if (nsync <= pf) { named_bar(9, 256); nsync++; }
                if (lane == 0 && pf < NSEG / 2 - 1) mbar_arrive(sbase + SB_REQ);
            } else {
                float acc[32];
                product(acc, pr, 0);
                if (nsync < pr) { named_bar(9, 256); nsync++; }
#pragma unroll
                for (int q = 0; q < 8; q++)
                    asm volatile("st.shared.v4.f32 [%0], {%1,%2,%3,%4};" :: "r"(sbase + FS_P + t16 + q * 2048), "f"(acc[4 * q]), "f"(acc[4 * q + 1]), "f"(acc[4 * q + 2]), "f"(acc[4 * q + 3]) : "memory");
                bar_arrive(8, 256);
                TSG(4);
            }
            uint32_t w[4] = {0u, 0u, 0u, 0u};
            const int pc = pf;
            if (pf >= 0) {
                const uint32_t tag = ((uint32_t)(pf >> 3) & 1u) ^ 1u;
                uint4 v[8];
                unsigned n = 0;
                const bool last = pf == NSEG / 2 - 1;
                const uint4* src = reinterpret_cast<const uint4*>(reinterpret_cast<const unsigned char*>(&g_fp[pf & 7][cta][0][0]) + t16);
                if (pf >= NSEG / 2 - 2) {
#pragma unroll
                    for (int r = 0; r < 6; r++) v[r] = ld_vol_u4(src + r * 128);
                    mbar_wait(sbase + SB_FI, 0u);
                } else {
                    mbar_wait(sbase + SB_FI, (uint32_t)pf & 1u);
#pragma unroll
                    for (int r = 0; r < 6; r++)
                        asm volatile("ld.shared.v4.u32 {%0,%1,%2,%3}, [%4];" : "=r"(v[r].x), "=r"(v[r].y), "=r"(v[r].z), "=r"(v[r].w) : "r"(sbase + t16 + FS_I + r * 2048) : "memory");
                }
                while (true) {
                    uint32_t any = 0u;
#pragma unroll
                    for (int r = 0; r < 6; r++) {
                        uint32_t c0_, c1_;
                        asm("lop3.b32 %0, %1, %2, %3, 0x7e;" : "=r"(c0_) : "r"(v[r].x), "r"(v[r].y), "r"(tag));
                        asm("lop3.b32 %0, %1, %2, %3, 0x7e;" : "=r"(c1_) : "r"(v[r].z), "r"(v[r].w), "r"(tag));
                        asm("lop3.b32 %0, %1, %2, %3, 0xfe;" : "=r"(any) : "r"(any), "r"(c0_), "r"(c1_));
                    }
                    if (!__any_sync(0xffffffffu, (any & 1u) != 0u) || ++n >= SPIN_LIMIT) break;
                    if (pf < NSEG / 2 - 2) __nanosleep(200);
#pragma unroll
                    for (int r = 0; r < 6; r++) v[r] = ld_vol_u4(src + r * 128);
                }
                if (pf == 31) TS3(29);
                TSG(5);
#pragma unroll
                for (int r = 6; r < 8; r++)
                    asm volatile("ld.shared.v4.u32 {%0,%1,%2,%3}, [%4];" : "=r"(v[r].x), "=r"(v[r].y), "=r"(v[r].z), "=r"(v[r].w)
                                 : "r"(sbase + t16 + FS_O + (pf % 3) * 4096 + (r - 6) * 2048) : "memory");
                uint32_t zv[4], gg[2];
                ldsm_x4_t(zv, sbase + (last ? FS_I : FS_Z) + (wq * 16 + (lane & 15)) * 32 + (lane >> 4) * 16);
#pragma unroll
                for (int k = 0; k < 2; k++) gg[k] = __byte_perm(*reinterpret_cast<const volatile unsigned short*>(smem_raw + FS_G + (last ? 32 : 0) + k * 16 + (lane >> 2) * 2), 0u, 0x1010);
#define PQS(k, f) (((__uint_as_float(v[k].f) + __uint_as_float(v[2 + k].f)) + __uint_as_float(v[4 + k].f)) + __uint_as_float(v[6 + k].f))
#pragma unroll
                for (int k = 0; k < 2; k++) {
                    w[2 * k] = bf2_add(bf2_mul(gg[k], movm(pack_bf16(PQS(k, x), PQS(k, y)))), zv[2 * k]);
                    w[2 * k + 1] = bf2_add(bf2_mul(gg[k], movm(pack_bf16(PQS(k, z), PQS(k, w)))), zv[2 * k + 1]);
                }
#undef PQS
            }
            const bool more = nf < NSEG / 2;
            if (more) {
                uint32_t r;
                asm volatile("{\n.reg .pred p, q;\n.reg .b32 v;\nld.volatile.shared.u32 v, [%1];\nsetp.gt.s32 p, v, %2;\nbar.red.or.pred q, 10, 128, p;\nselp.u32 %0, 1, 0, q;\n}"
                             : "=r"(r) : "r"(sbase + SB_SEEN), "r"(np) : "memory");
                const bool dop = np < NSEG / 2 && (__shfl_sync(0xffffffffu, r, 0) != 0u || nf == np || (np >= TM && nf + 1 >= np));
                TSG(6);
                pr = dop ? np++ : -1;
                pf = !dop || nf + (pr >= TM2 ? 1 : 2) <= pr ? nf++ : -1;
                if (dop && pf >= 0 && lane == 0) mbar_arrive(sbase + SB_REQ);
            }
            if (pc >= 0) {
                unsigned char* op = reinterpret_cast<unsigned char*>(out) + (uint32_t)((pc * 64 + kq * 16 + (lane >> 2)) * DM + cb * 64 + wq * 16 + 2 * (lane & 3)) * 2u;
#pragma unroll
                for (int k = 0; k < 4; k++) *reinterpret_cast<uint32_t*>(op + (k >> 1) * (16 * DM) + (k & 1) * 16) = w[k];
                if ((pc & 1) == 0) TS3(4 + pc / 2);
                if (pc == 31) TS3(25);
            }
            if (!more) break;
          }
        }
        if (cta == 0 && tid == 0) asm volatile("red.relaxed.gpu.global.add.u32 [%0], 1;" :: "l"(&g_epoch) : "memory");
    }
    asm volatile("griddepcontrol.wait;" ::: "memory");
}

template <class F>
__device__ __forceinline__ uint32_t poll_mem(const uint4* src, uint32_t dst, uint32_t t0, F next) {
    uint4 v[6];
    unsigned it = 0;
#pragma unroll
    for (int j = 0; j < 6; j++) v[j] = make_uint4(0u, 0u, 0u, 0u);
    while (clock32() - t0 < POLL_DELAY) {}
    FS(12, 0);
    bool more;
#pragma unroll 1
    do {
        asm volatile("{\n.reg .pred p<6>;\n"
                     "setp.ne.u32 p0, %3, 0x5000;\nsetp.ne.u32 p1, %7, 0x5000;\nsetp.ne.u32 p2, %11, 0x5000;\n"
                     "setp.ne.u32 p3, %15, 0x5000;\nsetp.ne.u32 p4, %19, 0x5000;\nsetp.ne.u32 p5, %23, 0x5000;\n"
                     "@p0 ld.volatile.global.v4.u32 {%0,%1,%2,%3}, [%24];\n@p1 ld.volatile.global.v4.u32 {%4,%5,%6,%7}, [%24+4096];\n"
                     "@p2 ld.volatile.global.v4.u32 {%8,%9,%10,%11}, [%24+8192];\n@p3 ld.volatile.global.v4.u32 {%12,%13,%14,%15}, [%24+12288];\n"
                     "@p4 ld.volatile.global.v4.u32 {%16,%17,%18,%19}, [%24+16384];\n@p5 ld.volatile.global.v4.u32 {%20,%21,%22,%23}, [%24+20480];\n}"
                     : "+r"(v[0].x), "+r"(v[0].y), "+r"(v[0].z), "+r"(v[0].w), "+r"(v[1].x), "+r"(v[1].y), "+r"(v[1].z), "+r"(v[1].w),
                       "+r"(v[2].x), "+r"(v[2].y), "+r"(v[2].z), "+r"(v[2].w), "+r"(v[3].x), "+r"(v[3].y), "+r"(v[3].z), "+r"(v[3].w),
                       "+r"(v[4].x), "+r"(v[4].y), "+r"(v[4].z), "+r"(v[4].w), "+r"(v[5].x), "+r"(v[5].y), "+r"(v[5].z), "+r"(v[5].w)
                     : "l"(src) : "memory");
        stsm_x4(dst, h2_to_bf2(v[0].x), h2_to_bf2(v[0].y), h2_to_bf2(v[0].z), h2_to_bf2(v[1].x));
        stsm_x4(dst + 512, h2_to_bf2(v[1].y), h2_to_bf2(v[1].z), h2_to_bf2(v[2].x), h2_to_bf2(v[2].y));
        const uint32_t all = ((v[0].w & v[1].w) & (v[2].w & v[3].w)) & (v[4].w & v[5].w);
        more = __any_sync(0xffffffffu, (all & 0x5000u) != 0x5000u && ++it < SPIN_LIMIT);
        stsm_x4(dst + 1024, h2_to_bf2(v[2].z), h2_to_bf2(v[3].x), h2_to_bf2(v[3].y), h2_to_bf2(v[3].z));
        asm volatile("stmatrix.sync.aligned.m8n8.x2.shared.b16 [%0], {%1,%2};" :: "r"(dst + 1536), "r"(h2_to_bf2(v[4].x)), "r"(h2_to_bf2(v[4].y)) : "memory");
        stsm_x4(dst + 1792, h2_to_bf2(v[4].z), h2_to_bf2(v[5].x), h2_to_bf2(v[5].y), h2_to_bf2(v[5].z));
        asm volatile("{\n.reg .pred p;\nsetp.eq.u32 p, %0, 0;\n@p bar.sync 1, 384;\n}" :: "r"((uint32_t)more) : "memory");
    } while (more);
    next();
    FS(13, it);
    FS(14, 0);
    uint32_t m = v[0].x, m1 = v[0].y, m2 = v[0].z;
#pragma unroll
    for (int j = 1; j < 6; j++) {
        asm volatile("max.NaN.xorsign.abs.f16x2 %0, %0, %1;" : "+r"(m) : "r"(v[j].x));
        asm volatile("max.NaN.xorsign.abs.f16x2 %0, %0, %1;" : "+r"(m1) : "r"(v[j].y));
        asm volatile("max.NaN.xorsign.abs.f16x2 %0, %0, %1;" : "+r"(m2) : "r"(v[j].z));
    }
    asm volatile("max.NaN.xorsign.abs.f16x2 %0, %0, %1;" : "+r"(m) : "r"(m1));
    asm volatile("max.NaN.xorsign.abs.f16x2 %0, %0, %1;" : "+r"(m) : "r"(m2));
    return h2_to_bf2(m) & 0x7fff7fffu;
}

template <int N> __device__ __forceinline__ void pad_code() {
#pragma unroll
    for (int i = 0; i < N; i++) asm volatile("pmevent 7;" ::: "memory");
}
template <bool V> struct Flag { static constexpr bool value = V; };
__device__ __forceinline__ void score_group(const uint32_t (&a)[2][4], const uint32_t (&kf)[2][4], uint32_t d0, uint32_t d1, uint32_t m1, uint32_t d2, uint32_t m2) {
    FS(4, a[1][0]);
    float sc[4][4];
    mma_z(sc[0], a[0], kf[0][0], kf[0][1]);
    mma_z(sc[1], a[0], kf[0][2], kf[0][3]);
    mma_z(sc[2], a[1], kf[1][0], kf[1][1]);
    mma_z(sc[3], a[1], kf[1][2], kf[1][3]);
    constexpr float EC = (float)(1.4426950408889634 * 0.08838834764831845);
    const uint32_t v0 = __float_as_uint(fmaf(sc[3][2], EC, ((sc[0][0] + sc[1][2]) + sc[2][0]) * EC)), v1 = __float_as_uint(fmaf(sc[3][3], EC, ((sc[0][1] + sc[1][3]) + sc[2][1]) * EC));
    FS(5, v0);
    const uint32_t pk = pack_bf16(__uint_as_float(v0), __uint_as_float(v1));
    st_async32(d2, pk, m2);
    st_async32(d1, pk, m1);
    asm volatile("st.shared.v2.u32 [%0], {%1,%2};" :: "r"(d0), "r"(v0), "r"(v1) : "memory");
}
__device__ __forceinline__ void store_tile(int s, int h, int role, uint32_t tile, uint32_t b0, uint32_t b1) {
    asm volatile("cp.async.bulk.global.shared::cta.bulk_group.L2::cache_hint [%0], [%1], %2, %3;"
                 :: "l"(&g_qkv[s][h][role][b0]), "r"(tile + b0), "r"(b1 - b0), "l"(policy_evict_first()) : "memory");
}
__device__ __forceinline__ uint32_t w_addr(uint32_t sbase, int warp, int lane) {
    return sbase + SM_WS + (warp >> 2) * 8192 + ((lane & 7) + ((lane >> 4) & 1) * 8) * 128 + ((((warp & 3) * 2 + ((lane >> 3) & 1)) ^ (lane & 7)) << 4);
}
__device__ __forceinline__ void vx_copy(uint32_t sbase, int j, int r) {
    bulk_s2s(mapa(sbase + SM_VX + (j & 1) * 8192, r), sbase + SM_T + (j & 3) * TBUF + DH * 16, 8192, mapa(sbase + B_VX + 8 * (j & 1), r));
}
__device__ __forceinline__ float to_scale(float bound) {
    int e = 141 - (int)((__float_as_uint(bound) >> 23) & 255u);
    e = e > 100 ? 100 : e;
    return __uint_as_float((uint32_t)(127 + e) << 23);
}
__device__ __forceinline__ void norms_gather(int lane, uint32_t sbase) {
    uint2 v[3];
    uint4 w[2];
    unsigned it = 0;
#pragma unroll
    for (int i = 0; i < 3; i++) v[i] = make_uint2(0u, 0u);
    w[0] = w[1] = make_uint4(0u, 0u, 0u, 0u);
    bool more;
    do {
#pragma unroll
        for (int i = 0; i < 3; i++) if ((v[i].x & 1u) == 0u) v[i] = ld_vol_u2(&g_norm[3 * lane + i]);
#pragma unroll
        for (int i = 0; i < 2; i++) if ((w[i].x & w[i].y & w[i].z & w[i].w & 1u) == 0u) w[i] = ld_vol_u4(&g_wv[lane][i]);
        more = __any_sync(0xffffffffu, (v[0].x & v[1].x & v[2].x & w[0].x & w[0].y & w[0].z & w[0].w & w[1].x & w[1].y & w[1].z & w[1].w & 1u) == 0u);
    } while (more && ++it < SPIN_LIMIT);
    float c;
    asm("sqrt.approx.f32 %0, %1;" : "=f"(c) : "f"(__uint_as_float(max(max(v[0].x, v[1].x), v[2].x))));
    c *= __uint_as_float(max(max(max(w[0].x, w[0].y), max(w[0].z, w[0].w)), max(max(w[1].x, w[1].y), max(w[1].z, w[1].w)))) * 272.f;
#pragma unroll
    for (int o = 16; o; o >>= 1) c += __shfl_xor_sync(0xffffffffu, c, o);
    const uint32_t r = __reduce_max_sync(0xffffffffu, v[0].y);
    if (lane < 3) {
        const uint32_t rb = mapa(sbase, lane);
        c *= 1.1f * 24.f;
        st_async64(rb + SM_SC, __float_as_uint(to_scale(__uint_as_float(r) * c)), __float_as_uint(c), rb + B_W + 8);
        st_async32(rb + SM_SC + 68, r, rb + B_W + 8);
    }
    __syncwarp();
}
__device__ __forceinline__ void xmax_gather(int lane, uint32_t sb) {
    uint4 v[4];
    unsigned it = 0;
    uint32_t ok;
    do {
#pragma unroll
        for (int i = 0; i < 4; i++) v[i] = ld_vol_u4(&g_rx[lane + 32 * (i >> 1)][i & 1]);
        ok = 1u;
#pragma unroll
        for (int i = 0; i < 4; i++) ok &= (v[i].x & v[i].y) & (v[i].z & v[i].w);
    } while (__any_sync(0xffffffffu, ok == 0u) && ++it < SPIN_LIMIT);
#pragma unroll
    for (int i = 0; i < 2; i++)
        sts32(sb + SM_SC + 64 + 4 * lane + 128 * i, max(max(max(v[2 * i].x, v[2 * i].y), max(v[2 * i].z, v[2 * i].w)), max(max(v[2 * i + 1].x, v[2 * i + 1].y), max(v[2 * i + 1].z, v[2 * i + 1].w))));
}
__device__ __forceinline__ uint32_t max_abs8(uint32_t m, uint32_t a, uint32_t b, uint32_t c, uint32_t d) { return max_abs2(max_abs2(m, max_abs2(a, b)), max_abs2(c, d)); }
__device__ __forceinline__ uint32_t warp_max_abs(uint32_t m) { return __reduce_max_sync(0xffffffffu, max((m << 16) & 0x7fff0000u, m & 0x7fff0000u)); }

__device__ __forceinline__ void last_rows() {
    extern __shared__ __align__(1024) unsigned char smem_raw[];
    const uint32_t sbase = smem_u32(smem_raw);
    const int tid = threadIdx.x, warp = __shfl_sync(0xffffffffu, tid >> 5, 0), h = blockIdx.x / 3;
    {
        const int sg = warp < 8, wq = warp & 3, lane = tid & 31;
        const uint32_t qk = sbase + SM_X + XBUF + sg * (2 * 9216), ob = sbase + SM_X + 2 * XBUF + sg * 8192;
        TST(0);
        mbar_wait(sbase + B_VX + 8 * sg, 0);
        fence_async();
        TST(1);
        float sc[20];
#pragma unroll
        for (int i = 0; i < 20; i++) sc[i] = 0.f;
        {
            const uint64_t da = smem_desc(qk + 1024, 128, 1024), db = smem_desc(qk, 128, 2048);
            wg_fence();
#pragma unroll
            for (int ks = 0; ks < 8; ks++) wgmma_n40_ss(sc, da + (uint64_t)((ks >> 2) * 576 + (ks & 3) * 16), db + (uint64_t)((ks >> 2) * 576 + (ks & 3) * 16), ks > 0);
            wg_commit();
            wg_wait0();
        }
        uint32_t p[5], o[16];
        const float psum = xrow_softmax(sc, p, wq, lane);
        xrow_pv(o, p, psum, sbase + SM_T + ((NSEG - 2 + sg) & 3) * TBUF);
        {
#pragma unroll
            for (int i = 0; i < 4; i++) stsm_x4(ob + wq * 2048 + i * 512 + lane * 16, o[4 * i], o[4 * i + 1], o[4 * i + 2], o[4 * i + 3]);
        }
        fence_async();
        named_bar(11 + sg, 128);
        TST(2);
        if ((tid & 127) == 0) {
            unsigned char* dst = reinterpret_cast<unsigned char*>(g_ox) + ((size_t)((NSEG / 2 - 1) * NH + h)) * 16384 + sg * 8192;
            asm volatile("cp.async.bulk.global.shared::cta.bulk_group [%0], [%1], 8192;" :: "l"(dst), "r"(ob) : "memory");
            asm volatile("cp.async.bulk.commit_group;" ::: "memory");
            asm volatile("cp.async.bulk.wait_group 0;" ::: "memory");
            asm volatile("red.relaxed.gpu.global.add.u32 [%0], 1;" :: "l"(&g_prog[(h >> 2) * 64 + NSEG / 2 - 1]) : "memory");
        }
        TST(3);
    }
    __syncwarp();
}

__global__ void __cluster_dims__(3, 1, 1) __launch_bounds__(384, 1)
k_chain(const __grid_constant__ CUtensorMap tmq, const __grid_constant__ CUtensorMap tmk,
        const __grid_constant__ CUtensorMap tmv, const __grid_constant__ CUtensorMap tmx2, const __grid_constant__ CUtensorMap tmo,
        const __grid_constant__ CUtensorMap tmm, const bf16* __restrict__ xg) {
    extern __shared__ __align__(1024) unsigned char smem_raw[];
    const uint32_t sbase = smem_u32(smem_raw);
    const int cta = blockIdx.x, h = cta / 3, role = cta - 3 * h;
    const int tid = threadIdx.x, warp = __shfl_sync(0xffffffffu, tid >> 5, 0), lane_o = tid & 31;
    TS3C(0);
    asm volatile("griddepcontrol.launch_dependents;" ::: "memory");
    auto stage_w = [&](int i) {
        tma_2d(sbase + SM_WS + i * 16384, role == 2 ? &tmv : &tmq, h * DH + (role == 1 ? 64 : 0), i * 64, sbase + B_W + 8 * i);
        tma_2d(sbase + SM_WS + i * 16384 + 8192, role == 2 ? &tmv : &tmk, h * DH + (role == 0 ? 0 : 64), i * 64, sbase + B_W + 8 * i);
    };
    auto stage_x = [&](int i) {
        tma_2d(sbase + x01_off(i), &tmx2, i * 64, 0, sbase + B_W + 8 * i);
        tma_2d(sbase + x01_off(i) + 8192, &tmm, i * 64, 0, sbase + B_W + 8 * i);
        if (i < 3) tma_2d(sbase + x23_off(i), &tmx2, i * 64, 64, sbase + B_W + 8 * i);
    };
    if (tid == 0) {
#pragma unroll
        for (int i = 0; i < 10; i++) mbar_init(sbase + B_W + 8 * i, 1);
        fence_async();
        TSQ(10);
#pragma unroll
        for (int i = 0; i < 3; i++) tma_2d(sbase + SM_X01 + i * 16384, &tmo, role * WOC + i * 64, h * DH, sbase + B_E);
        stage_x(0); stage_w(0);
        TSQ(11);
        mbar_expect(sbase + B_E, 49152);
#pragma unroll
        for (int i = 0; i < 9; i++) mbar_expect(sbase + B_W + 8 * i, 16384 + 9216 + (i < 3 ? 8192 : 0));
    } else if (tid == 32) {
#pragma unroll
        for (int i = 0; i < 8; i++) mbar_init(sbase + SM_BAR + 8 * i, 1);
        mbar_init(sbase + B_XF, 3);
        asm volatile("fence.mbarrier_init.release.cluster;" ::: "memory");
        for (int i = 0; i < 2; i++) {
            mbar_expect(sbase + B_SB + 8 * i, role == 2 ? 2560 >> HS : (1280 >> HS) + 2048);
            mbar_expect(sbase + B_VX + 8 * i, role != 2 ? 8192 : 2 * 9216);
            mbar_expect(sbase + B_XT + 8 * i, 32768);
            mbar_expect(sbase + B_XT + 16 + 8 * i, i == 0 ? 40960 : 0);
        }
    }
    __syncthreads();
    TS3C(8);
    if (tid == 0) {
#pragma unroll 1
        for (int i = 1; i < 3; i++) { stage_x(i); stage_w(i); }
        TSQ(12);
    }
    __syncwarp();
    if (warp < 8) {
        uint32_t wreg[36 - NS][4];
        uint32_t v0, v1;
        {
            const int lane = lane_o;
            const uint32_t a = w_addr(sbase, warp, lane);
            const uint64_t da = smem_desc(sbase + SM_WS + (warp >> 2) * 8192, 1024, 1024) | (1ull << 62);
            float acc[36], acc1[32];
            uint32_t m = 0u;
#pragma unroll
            for (int i = 0; i < 36; i++) acc[i] = 0.f;
#pragma unroll
            for (int i = 0; i < 32; i++) acc1[i] = 0.f;
#pragma unroll 1
            for (int b = 0; b < 7; b++) {
                if (b == 0) TSQ(0);
                mbar_wait(sbase + B_W + 8 * b, 0);
                TSQ(1 + b);
                const uint64_t db = smem_desc(sbase + x01_off(b), 16, 1024) | (1ull << 62);
                wg_fence();
#pragma unroll
                for (int k = 0; k < 4; k++) wgmma_n72_ss(acc, da + (uint64_t)(b * 1024 + k * 128), db + (uint64_t)(k * 2));
                wg_commit();
                if (b < 3) {
                    const uint64_t d1 = smem_desc(sbase + x23_off(b), 16, 1024) | (1ull << 62);
                    wg_fence();
#pragma unroll
                    for (int k = 0; k < 4; k++) wgmma_n64_ss(acc1, da + (uint64_t)(b * 1024 + k * 128), d1 + (uint64_t)(k * 2));
                    wg_commit();
                }
                if (b == 2) {
                    wg_wait0();
                    bar_arrive(10, 384);
                }
                if (b == 3) {
                    if (tid == 0) mbar_expect(sbase + B_W + 8, 12);
                    __syncwarp();
                    if (role == 2) {
#pragma unroll
                        for (int ks = 0; ks < NS; ks++) {
                            uint32_t t[4];
                            ldsm_x4_t(t, a + (ks >> 2) * 16384 + (ks & 3) * 2048);
                            m = max_abs8(m, t[0], t[1], t[2], t[3]);
                        }
                    }
#pragma unroll
                    for (int ks = NS; ks < 16; ks++) ldsm_x4_t(wreg[ks - NS], a + (ks >> 2) * 16384 + (ks & 3) * 2048);
                }
                if (b == 5) {
#pragma unroll
                    for (int ks = 16; ks < 24; ks++) ldsm_x4_t(wreg[ks - NS], a + (ks >> 2) * 16384 + (ks & 3) * 2048);
                    if (role == 2) {
#pragma unroll
                        for (int ks = NS; ks < 24; ks++) m = max_abs8(m, wreg[ks - NS][0], wreg[ks - NS][1], wreg[ks - NS][2], wreg[ks - NS][3]);
                    }
                }
            }
            mbar_wait(sbase + B_W + 16, 1);
            TSQ(13);
            wg_fence();
#pragma unroll
            for (int k = 12; k < 20; k++)
                wgmma_n64_ss(acc1, da + (uint64_t)((k >> 2) * 1024 + (k & 3) * 128), (smem_desc(sbase + x23_off(k >> 2), 16, 1024) | (1ull << 62)) + (uint64_t)((k & 3) * 2));
            wg_commit();
            wg_wait0();
            named_bar(11, 384);
#pragma unroll
            for (int i = 0; i < 8; i++)
                asm volatile("st.shared.v4.f32 [%0], {%1,%2,%3,%4};" :: "r"(sbase + SM_X + 5 * 8192 + i * 4096 + tid * 16),
                             "f"(acc1[4 * i]), "f"(acc1[4 * i + 1]), "f"(acc1[4 * i + 2]), "f"(acc1[4 * i + 3]) : "memory");
#pragma unroll
            for (int b = 7; b < 9; b++) {
#pragma unroll
                for (int ks = 4 * b - 4; ks < 4 * b; ks++) ldsm_x4_t(wreg[ks - NS], a + (ks >> 2) * 16384 + (ks & 3) * 2048);
                if (role == 2) {
#pragma unroll
                    for (int ks = 4 * b - 4; ks < 4 * b; ks++) m = max_abs8(m, wreg[ks - NS][0], wreg[ks - NS][1], wreg[ks - NS][2], wreg[ks - NS][3]);
                }
                const uint64_t db = smem_desc(sbase + x01_off(b), 16, 1024) | (1ull << 62);
                mbar_wait(sbase + B_W + 8 * b, 0);
                TSQ(1 + b);
                if (b == 8) TS3C(2);
                wg_fence();
#pragma unroll
                for (int k = 0; k < 4; k++) wgmma_n72_ss(acc, da + (uint64_t)(b * 1024 + k * 128), db + (uint64_t)(k * 2));
                wg_commit();
            }
#pragma unroll
            for (int ks = 32; ks < KPRE; ks++) ldsm_x4_t(wreg[ks - NS], a + (ks >> 2) * 16384 + (ks & 3) * 2048);
            if (role == 2) {
#pragma unroll
                for (int ks = KPRE; ks < 36; ks++) {
                    uint32_t t[4];
                    ldsm_x4_t(t, a + (ks >> 2) * 16384 + (ks & 3) * 2048);
                    m = max_abs8(m, t[0], t[1], t[2], t[3]);
                }
#pragma unroll
                for (int ks = 32; ks < KPRE; ks++) m = max_abs8(m, wreg[ks - NS][0], wreg[ks - NS][1], wreg[ks - NS][2], wreg[ks - NS][3]);
                m = warp_max_abs(m);
                if (lane == 0) asm volatile("st.volatile.global.u32 [%0], %1;" :: "l"(reinterpret_cast<uint32_t*>(&g_wv[h][0]) + warp), "r"(m | 1u) : "memory");
                __syncwarp();
            }
            wg_wait0();
            named_bar(9, 256);
            const uint32_t off = sbase + SM_T + (DH + warp * 16 + (lane & 15)) * 16 + (lane >> 4) * (DH * 16);
#pragma unroll
            for (int i = 0; i < 4; i++)
                stsm_x4(off + (i >> 1) * TBUF + (i & 1) * (2 * DH * 16), pack_bf16(acc[8 * i], acc[8 * i + 1]), pack_bf16(acc[8 * i + 2], acc[8 * i + 3]),
                        pack_bf16(acc[8 * i + 4], acc[8 * i + 5]), pack_bf16(acc[8 * i + 6], acc[8 * i + 7]));
            v0 = pack_bf16(acc[32], acc[33]);
            v1 = pack_bf16(acc[34], acc[35]);
#pragma unroll
            for (int ks = KPRE; ks < 36; ks++) ldsm_x4_t(wreg[ks - NS], a + (ks >> 2) * 16384 + (ks & 3) * 2048);
            if (role == 2) fence_async();
            bar_arrive(8, 384);
            named_bar(7, 256);
            asm volatile("barrier.cluster.arrive.relaxed.aligned;" ::: "memory");
        }
        TS3C(3);
        uint32_t ws[NS][4];
#pragma unroll
        for (int ks = NS - NP; ks < NS; ks++) ldsm_x4_t(ws[ks], w_addr(sbase, warp, lane_o) + (ks >> 2) * 16384 + (ks & 3) * 2048);
        asm volatile("barrier.cluster.wait.aligned;" ::: "memory");
        if (lane_o == 0 && role != 2 && warp < 2) tma_2d_mc(sbase + SM_X + (2 * role + warp) * 8192, &tmx2, (2 * role + warp + 5) * 64, 64, sbase + B_XT + 8);
        __syncwarp();
        TS3C(4);
        auto main_loop = [&](auto is_c) {
            constexpr bool C = decltype(is_c)::value;
            if (C) pad_code<PAD4>(); else pad_code<PAD3>();
            const uint32_t l16 = __shfl_sync(0xffffffffu, sbase + lane_o * 16, lane_o);
            const uint32_t ka = __shfl_sync(0xffffffffu, sbase + SM_T + (64 + (lane_o & 7) + ((lane_o >> 3) & 1) * 16 + (lane_o >> 4) * 8) * 16, lane_o);
            const uint32_t wa = __shfl_sync(0xffffffffu, w_addr(sbase, warp, lane_o), lane_o);
            auto post = [&](bool act, int s, uint32_t to, uint32_t ta, int scw, uint32_t v0, uint32_t v1) {
                int lane = lane_o;
                asm volatile("" : "+r"(lane));
                asm volatile("stmatrix.sync.aligned.m8n8.x2.shared.b16 [%0], {%1,%2};" :: "r"(l16 + ta), "r"(v0), "r"(v1) : "memory");
                if (C) {
                    if (act || s + 1 < NSEG) {
                        const uint32_t fo = (uint32_t)(warp * 256 + lane * 8);
                        const uint32_t rb0 = mapa(sbase, 0), rb1 = mapa(sbase, 1);
                        st_async64(rb0 + SM_VM + fo, v0, v1, rb0 + B_SB + 8 * (s & 1));
                        st_async64(rb1 + SM_VM + fo, v0, v1, rb1 + B_SB + 8 * (s & 1));
                        asm volatile("st.shared.v2.u32 [%0], {%1,%2};" :: "r"(sbase + SM_VM + fo), "r"(v0), "r"(v1) : "memory");
                        bar_arrive(2, 384);
                    }
                } else if (act) bar_arrive(2, 384);
                else {
                    named_bar(2, 384);
                    if (scw == 0) {
                        uint32_t kf[2][4], qf[2][4];
#pragma unroll
                        for (int k2 = 0; k2 < 2; k2++) { ldsm_x4_t(kf[k2], ka + to + k2 * 512); ldsm_x4_t(qf[k2], l16 + SM_T + to + k2 * 512); }
                        const uint32_t d0 = sbase + SM_S + lane * 8, bo = sbase + B_SB + 8 * (s & 1);
                        const uint32_t dr = HS ? d0 - lane * 4 : d0;
                        const uint32_t d1 = mapa(dr + 1280, role ^ 1), m1 = mapa(bo, role ^ 1), d2 = mapa(dr + role * 1280, 2), m2 = mapa(bo, 2);
                        score_group(qf, kf, d0, d1, m1, d2, m2);
                        bar_arrive(6, 160);
                        bar_arrive(5, 384);
                    }
                    if (scw == 8) {
                        const uint32_t dk = mapa(sbase + SM_X + XBUF + (2 + role) * 9216 + (warp - 4) * 256 + lane * 4, 2), mb = mapa(sbase + B_VX + 8, 2);
                        st_async32(dk, v0, mb);
                        st_async32(dk + 128, v1, mb);
                    }
                }
                FS(11, 0);
            };
            post(false, 0, 0, SM_T + warp * 256, warp ^ 7, v0, v1);
            if (tid == 128 && cta < NSEG) {
                fence_async();
                mbar_expect(sbase + B_E, XBUF);
                bulk_g2s(sbase + SM_X + 9 * 8192, xg + (size_t)cta * SEG * DM, 32768, sbase + B_E);
                bulk_g2s(sbase + SM_WS + 32768 + 4096, xg + (size_t)cta * SEG * DM + 16384, 4096, sbase + B_E);
            }
            __syncwarp();
            if (C) {
                named_bar(7, 256);
                if (warp == 1) norms_gather(lane_o, sbase);
            }
            auto chores = [&](int s, bool idle) {
                int lane = lane_o;
                asm volatile("" : "+r"(lane));
                const int hw = (s & 1) ? warp : warp - 4;
                const uint32_t tb = sbase + SM_T + (s & 3) * TBUF;
                if (idle) { if (hw != 2) named_bar(4, 384); else bar_arrive(4, 384); }
                if (hw == 2) {
                    if (lane == 0) {
                        {
                            if (C || !idle) fence_async();
                            if (C) {
                                store_tile(s + 1, h, 2, sbase + SM_T + ((s + 1) & 3) * TBUF, 2048, 10240);
                                store_tile(s, h, 2, tb, 0, idle ? 2048 : 10240);
                            } else store_tile(s, h, role, tb, 1024, 10240);
                            asm volatile("cp.async.bulk.commit_group;" ::: "memory");
                        }
                        {
                            asm volatile("cp.async.bulk.wait_group 0;" ::: "memory");
                            if (C) {
                                asm volatile("cp.async.bulk.shared::cluster.global.mbarrier::complete_tx::bytes.multicast::cluster [%0], [%1], 8192, [%2], %3;"
                                             :: "r"(sbase + SM_VX + ((s + 1) & 1) * 8192), "l"(&g_qkv[s + 1][h][2][2048]), "r"(sbase + B_VX + 8 * ((s + 1) & 1)), "h"((unsigned short)3) : "memory");
                            }
                            asm volatile("red.relaxed.gpu.global.add.u32 [%0], 1;" :: "l"(&g_flag[h * NSEG + s]) : "memory");
                        }
                    }
                    __syncwarp();
                    if (!C && (s & 1) && s + 4 < NSEG) bar_arrive(13, 160);
                }
                __syncwarp();
            };
            auto put_tiles = [&](const float (&acc)[32], uint32_t off) {
#pragma unroll
                for (int i = 0; i < 4; i++)
                    stsm_x4(off + (i >> 1) * TBUF + (i & 1) * (2 * DH * 16), pack_bf16(acc[8 * i], acc[8 * i + 1]), pack_bf16(acc[8 * i + 2], acc[8 * i + 3]),
                            pack_bf16(acc[8 * i + 4], acc[8 * i + 5]), pack_bf16(acc[8 * i + 6], acc[8 * i + 7]));
            };
            auto tile_off = [&](int p) {
                int lane = lane_o;
                asm volatile("" : "+r"(lane));
                return sbase + SM_T + (p & 1) * (2 * TBUF) + (DH + warp * 16 + (lane & 15)) * 16 + (lane >> 4) * (DH * 16);
            };
            {
                auto db = [&](int ks) { return (smem_desc(sbase + SM_X, 16, 1024) | (1ull << 62)) + (uint64_t)(((ks >> 2) - 5) * 512 + (ks & 3) * 2); };
                if (!C && warp != 7) bar_arrive(5, 384);
                if (warp == 5) {
                    mbar_wait(sbase + B_W + 8, 1);
                    bar_arrive(12, 160);
                }
                chores(0, false);
                float acc[32];
#pragma unroll
                for (int i = 0; i < 8; i++)
                    asm volatile("ld.shared.v4.f32 {%0,%1,%2,%3}, [%4];" : "=f"(acc[4 * i]), "=f"(acc[4 * i + 1]), "=f"(acc[4 * i + 2]), "=f"(acc[4 * i + 3])
                                 : "r"(l16 + warp * 512 + SM_X + 5 * 8192 + i * 4096) : "memory");
                mbar_wait(sbase + B_XT + 8, 0);
                FS(8, 0);
                named_bar(4, 384);
                wg_fence();
#pragma unroll
                for (int ks = 35; ks >= 20; ks--) wgmma_n64(acc, wreg[ks - NS], db(ks), 1);
                wg_commit();
                if (cta < NSEG) {
                    uint32_t m = 0u;
                    mbar_wait(sbase + B_E, 1);
#pragma unroll
                    for (int j = 0; j < 9; j++) {
                        const uint4 xv = lds128(l16 + warp * 512 + (j < 8 ? SM_X + 9 * 8192 + j * 4096 : SM_WS + 32768 + 4096));
                        m = max_abs8(m, xv.x, xv.y, xv.z, xv.w);
                    }
                    m = warp_max_abs(m);
                    if (lane_o == 0) asm volatile("st.volatile.global.u32 [%0], %1;" :: "l"(reinterpret_cast<uint32_t*>(&g_rx[cta][0]) + warp), "r"(m | 1u) : "memory");
                    __syncwarp();
                }
                FS(3, 0);
                wg_wait0();
                put_tiles(acc, tile_off(1));
                FS(7, __float_as_uint(acc[0]));
            }
            auto mem_proj = [&](uint32_t& u0, uint32_t& u1) {
#pragma unroll
                for (int ks = 0; ks < NS - NP; ks++) ldsm_x4_t(ws[ks], wa + (ks >> 2) * 16384 + (ks & 3) * 2048);
                FS(0, ws[0][0]);
                named_bar(1, 384);
                float acc[2][4], minv;
                uint32_t b[3][4];
#pragma unroll
                for (int kk = 0; kk < 3; kk++) ldsm_x4_t(b[kk], l16 + SM_M + kk * 512);
                FS(1, b[0][0]);
#pragma unroll
                for (int kk = 0; kk < 18; kk++) {
#pragma unroll
                    for (int i = 0; i < 2; i++) {
                        const int ks = 2 * kk + i;
                        if (ks < 2) mma_z(acc[i], ws[ks], b[kk % 3][2 * i], b[kk % 3][2 * i + 1]);
                        else if (ks < NS) mma_bf16(acc[i], ws[ks < NS ? ks : 0], b[kk % 3][2 * i], b[kk % 3][2 * i + 1]);
                        else mma_bf16(acc[i], wreg[ks >= NS ? ks - NS : 0], b[kk % 3][2 * i], b[kk % 3][2 * i + 1]);
                    }
                    if (kk + 3 < 18) ldsm_x4_t(b[kk % 3], l16 + SM_M + (kk + 3) * 512);
                    if (kk + 3 == 17) asm volatile("ld.shared.f32 %0, [%1];" : "=f"(minv) : "r"(sbase + SM_SC + 8) : "memory");
                }
                u0 = pack_bf16(fmaf(acc[1][0], minv, acc[0][0] * minv), fmaf(acc[1][1], minv, acc[0][1] * minv));
                u1 = pack_bf16(fmaf(acc[1][2], minv, acc[0][2] * minv), fmaf(acc[1][3], minv, acc[0][3] * minv));
                FS(2, u0);
            };
            int s = 0, rc = 9;
            bool act = warp >= 4;
            uint32_t to = TBUF, ta = SM_T + warp * 256 + TBUF;
            auto next_slot = [&]() {
                const uint32_t d = (s & 3) == 3 ? -3 * TBUF : TBUF;
                to += d; ta += d;
                asm volatile("" : "+r"(to), "+r"(ta));
            };
#pragma unroll 1
            for (;;) {
                uint32_t u0, u1;
                if (act) {
                    mem_proj(u0, u1);
                    s++;
                    post(true, s, to, ta, 1, u0, u1);
                    const int p = (s + 3) >> 1;
                    const uint32_t dlo = (uint32_t)smem_desc(sbase + SM_X, 16, 1024) + rc * 512;
                    const uint64_t da = smem_desc(sbase + SM_WS + (warp >> 2) * 8192, 1024, 1024) | (1ull << 62);
                    auto db = [&](int ks) {
                        const int j = ((ks >> 2) + 4) % 9;
                        return ((uint64_t)0x40000040u << 32) | (uint64_t)(dlo + (uint32_t)((j - (rc + j >= 13 ? 13 : 0)) * 512 + (ks & 3) * 2));
                    };
                    const uint32_t xph = (uint32_t)((p - 1) >> 1) & 1u;
                    float acc[32];
                    mbar_wait(sbase + B_XT + 8 * (p & 1), xph);
                    if (C) named_bar(7, 256); else named_bar(5, 384);
                    constexpr int N1 = C ? NC1C : NC1;
                    wg_fence();
#pragma unroll
                    for (int ks = 35; ks > 35 - N1; ks--) { if (ks == 35) wgmma_n64_z(acc, wreg[ks - NS], db(ks)); else wgmma_n64(acc, wreg[ks - NS], db(ks), 1); }
                    wg_commit();
                    wg_wait0();
                    FS(9, __float_as_uint(acc[0]));
                    next_slot();
                    FS(8, 0);
                    asm volatile("{\n.reg .pred p;\nsetp.ge.s32 p, %0, 0;\n@p bar.sync 4, 384;\n}" :: "r"(s) : "memory");
                    FS(3, 0);
                    wg_fence();
#pragma unroll
                    for (int ks = 35 - N1; ks >= KG1; ks--) wgmma_n64(acc, wreg[ks - NS], db(ks), 1);
                    wg_commit();
                    mbar_wait(sbase + B_XT + 16 + 8 * (p & 1), xph);
                    wg_fence();
#pragma unroll
                    for (int ks = 0; ks < NS; ks++) wgmma_n64_ss(acc, da + (uint64_t)((ks >> 2) * 1024 + (ks & 3) * 128), db(ks));
#pragma unroll
                    for (int ks = NS; ks < KG1; ks++) wgmma_n64(acc, wreg[ks - NS], db(ks), 1);
                    wg_commit();
                    if (!C && warp >= 4) named_bar(13, 160);
                    uint32_t off = tile_off(p);
                    rc = rc >= 4 ? rc - 4 : rc + 9;
                    asm volatile("" : "+r"(off), "+r"(rc));
                    wg_wait0();
                    put_tiles(acc, off);
                    FS(7, __float_as_uint(acc[0]));
                }
                int scw = s + 2 < NSEG ? warp ^ ((s & 1) ? 7 : 3) : (warp & 4) + 4;
                asm volatile("" : "+r"(scw));
                mem_proj(u0, u1);
                s++;
                post(false, s, to, ta, scw, u0, u1);
                if (s + 1 == NSEG) break;
                if (s + 2 < NSEG) {
                    if (!C && (warp & 3) == 2) fence_async();
                    if (C) named_bar(7, 256); else if (scw != 0) named_bar(5, 384);
                    chores(s, true);
                } else {
                    const uint32_t t0 = clock32();
                    const uint32_t dq = mapa(sbase + SM_X + XBUF + role * 9216, 2), mb = mapa(sbase + B_VX, 2);
                    if (!C) {
                        if (scw != 0) named_bar(5, 384);
                        if (tid == 64) { fence_async(); while (clock32() - t0 < TL_DELAY) {} bulk_s2s(dq, sbase + SM_T + 2 * TBUF + 1024, 9216, mb); }
                        __syncwarp();
                    }
                    named_bar(4, 384);
                    if (!C && tid == 64) { const uint32_t t1 = clock32(); while (clock32() - t1 < VX_DELAY) {} bulk_s2s(dq + 2 * 9216 + 1024, sbase + SM_T + 3 * TBUF + 2048, 8192, mb + 8); }
                    __syncwarp();
                }
                next_slot();
                act = s + 4 < NSEG;
            }
            if (C) named_bar(7, 256);
        };
        if (role == 2) main_loop(Flag<true>()); else main_loop(Flag<false>());
    } else {
        uint32_t wo[3][8][4];
        uint32_t mx2 = 0u;
        {
            const int pt = tid - 256, lane = lane_o, wq = warp - 8, g = lane >> 2, tq = lane & 3;
            TSQ(7);
            mbar_wait(sbase + B_E, 0);
            TSQ(8);
#pragma unroll
            for (int t = 0; t < 3; t++) {
                const int T = 3 * wq + t;
                const uint32_t a = sbase + SM_X01 + (T >> 2) * 16384 + ((lane >> 4) * 8 + (lane & 7)) * 128 + ((((T & 3) * 2 + ((lane >> 3) & 1)) ^ (lane & 7)) << 4);
#pragma unroll
                for (int kk = 0; kk < 8; kk++) ldsm_x4_t(wo[t][kk], a + ((2 * wq + kk) & 7) * 2048);
            }
            named_bar(3, 128);
            if (pt == 64) {
                fence_async();
#pragma unroll 1
                for (int i = 3; i < 9; i++) { stage_x(i); if (i < 7) stage_w(i); }
            }
            if (pt >= 96 && pt < 120) {
                *reinterpret_cast<uint4*>(g_acc + cta * 1024 + (pt - 96) * 16) = make_uint4(0u, 0u, 0u, 0u);
                __threadfence();
            }
            __syncwarp();
            TSQ(9);
            float c0 = 0.f;
#pragma unroll
            for (int t = 0; t < 3; t++) {
                float n[4][4];
#pragma unroll
                for (int i = 0; i < 4; i++) { n[i][0] = n[i][1] = n[i][2] = n[i][3] = 0.f; }
#pragma unroll
                for (int kk = 0; kk < 8; kk++)
#pragma unroll
                    for (int i = 0; i < 4; i++) mma_k8(n[i], wo[t][kk][i & 2], wo[t][kk][(i & 2) + 1], wo[t][kk][i]);
                if ((g >> 1) == tq) c0 = fmaxf(c0, (g & 1) ? fmaxf(n[0][1] + n[2][1], n[1][3] + n[3][3]) : fmaxf(n[0][0] + n[2][0], n[1][2] + n[3][2]));
            }
            c0 = __uint_as_float(__reduce_max_sync(0xffffffffu, __float_as_uint(c0)));
            uint32_t m = 0u;
            const int xb = role == 0 ? h % 9 : 9;
            auto x_max = [&]() {
                mbar_wait(sbase + B_W + 8 * xb, 0);
#pragma unroll
                for (int j = 0; j < 5; j++) {
                    uint4 xv;
                    asm volatile("ld.shared.v4.u32 {%0,%1,%2,%3}, [%4];" : "=r"(xv.x), "=r"(xv.y), "=r"(xv.z), "=r"(xv.w)
                                 : "r"(sbase + x01_off(xb) + (j < 4 ? pt + 128 * j : 512 + (pt & 63)) * 16) : "memory");
                    m = max_abs8(m, xv.x, xv.y, xv.z, xv.w);
                }
            };
            if (xb < 3) x_max();
            named_bar(10, 384);
            TSQ(10);
            if (pt == 64) {
                fence_async();
                mbar_expect(sbase + B_W + 16, 16384);
#pragma unroll
                for (int i = 3; i < 5; i++) tma_2d(sbase + x23_off(i), &tmx2, i * 64, 64, sbase + B_W + 16);
#pragma unroll 1
                for (int i = 7; i < 9; i++) stage_w(i);
            }
            __syncwarp();
            if (xb >= 3 && xb < 7) x_max();
            bar_arrive(11, 384);
            if (xb == 7 || xb == 8) x_max();
            asm volatile("barrier.cluster.arrive.relaxed.aligned;" ::: "memory");
            m = warp_max_abs(m);
            if (lane == 0) { sts32(sbase + SM_SC + 320 + 4 * wq, __float_as_uint(c0)); sts32(sbase + SM_SC + 336 + 4 * wq, m); }
            TSQ(1);
            named_bar(3, 128);
            if (pt == 0) {
                const uint4 a = lds128(sbase + SM_SC + 320), b = lds128(sbase + SM_SC + 336);
                st_vol_u2(&g_norm[cta], make_uint2(max(max(a.x, a.y), max(a.z, a.w)) | 1u, max(max(b.x, b.y), max(b.z, b.w)) | 1u));
            }
            __syncwarp();
            named_bar(8, 384);
            TSQ(2);
            asm volatile("barrier.cluster.wait.aligned;" ::: "memory");
            if (role == 2 && lane == 0 && wq < 2) vx_copy(sbase, 0, wq);
            __syncwarp();
        }
        const int wq = warp - 8;
        auto helper_loop = [&](auto is_c) {
        const bool C = is_c.value;
        if (C) pad_code<PAD2>(); else pad_code<PAD1>();
        const uint32_t sb = sbase;
        const uint32_t l8_o = __shfl_sync(0xffffffffu, sb + lane_o * 8, lane_o), l16_o = __shfl_sync(0xffffffffu, sb + lane_o * 16, lane_o);
        unsigned char* dst = g_acc + (role * 32 + wq * 8 + (lane_o >> 3)) * 1024 + (lane_o & 7) * 16;
        auto load_kf = [&](uint32_t (&kf)[2][4], int slot) {
            int lane = lane_o;
            asm volatile("" : "+r"(lane));
            const uint32_t ka = sb + SM_T + slot * TBUF + ((wq + 1) * DH + 64 + (lane & 7) + ((lane >> 3) & 1) * 16 + (lane >> 4) * 8) * 16;
#pragma unroll
            for (int k2 = 0; k2 < 2; k2++) ldsm_x4_t(kf[k2], ka + k2 * 512);
        };
        float minv = 1.f;
        uint32_t kf[2][4];
        if (!C) load_kf(kf, 0);
        int b3 = 0;
        int rx = 9;
        for (int s = 0; s + 1 < NSEG; s++) {
            const int n3 = b3 == 2 ? 0 : b3 + 1;
            uint32_t l8 = l8_o, l16 = l16_o;
            asm volatile("" : "+r"(l8), "+r"(l16));
            const uint32_t l4 = sb + ((l8 - sb) >> 1);
            {
                int lane = lane_o;
                asm volatile("" : "+r"(lane));
                if (C) {
                    if (lane == 0) {
                        if (wq == 3 && h == 0) {
                            const uint32_t t = gtime32();
                            st_vol_u2(&g_tick, make_uint2(t, lds32(sb + SM_SC + 12)));
                            sts32(sb + SM_SC + 12, t);
                        }
                    }
                    __syncwarp();
                    if (wq == 2 && s > 1 && lane < 24) {
                        *reinterpret_cast<uint4*>(g_acc + n3 * 128 + (3 * h + (lane >> 3)) * 1024 + (lane & 7) * 16) = make_uint4(0u, 0u, 0u, 0u);
                    }
                    if (wq == 1 && s == 3 && lane < 3) {
                        const int c = 3 * h + lane;
                        st_vol_u2(&g_norm[c], make_uint2(0u, 0u));
                        uint4* z = c < NSEG ? g_rx[c] : g_wv[c - NSEG];
                        st_vol_u4(z, make_uint4(0u, 0u, 0u, 0u)); st_vol_u4(z + 1, make_uint4(0u, 0u, 0u, 0u));
                    }
                    __syncwarp();
                }
                const uint32_t mw = __reduce_max_sync(0xffffffffu, max(mx2 << 16, mx2 & 0xffff0000u));
                if (lane == 0) sts32(sb + SM_SC + 16 + 4 * wq, mw);
            }
            const uint32_t to = SM_T + (s & 3) * TBUF;
            const uint32_t ph = (uint32_t)(s >> 1) & 1u;
            if (!C) {
                const uint32_t bo = sb + B_SB + 8 * (s & 1);
                uint32_t d0 = l8 + SM_S + (wq + 1) * 256, qa = l16 + to;
                const uint32_t dr = HS ? l4 + SM_S + (wq + 1) * 256 : d0;
                const uint32_t d1 = mapa(dr + 1280, role ^ 1), m1 = mapa(bo, role ^ 1), d2 = mapa(dr + role * 1280, 2), m2 = mapa(bo, 2);
                asm volatile("" : "+r"(d0), "+r"(qa));
                mbar_wait(sb + (s > 0 ? B_VX + 8 * (s & 1) : B_W), ph);
                FS(1, 0);
                named_bar(2, 384);
                uint32_t qf[2][4];
#pragma unroll
                for (int k2 = 0; k2 < 2; k2++) ldsm_x4_t(qf[k2], qa + k2 * 512);
                score_group(qf, kf, d0, d1, m1, d2, m2);
                bar_arrive(5, 384);
            } else named_bar(2, 384);
            if (!C && s == 0) {
                TSQ(3);
                mbar_wait(sb + B_VX, 0);
                TSQ(4);
            }
            float4 m4;
            asm volatile("ld.shared.v4.f32 {%0,%1,%2,%3}, [%4];" : "=f"(m4.x), "=f"(m4.y), "=f"(m4.z), "=f"(m4.w) : "r"(sb + SM_SC + 16) : "memory");
            const float c24 = __uint_as_float(lds32(sb + SM_SC + 4)), xb = __uint_as_float(lds32(sb + SM_SC + 64 + 4 * s));
            uint32_t vf[2][2][4], vm[2][2];
            uint32_t va = l16 + ((l16 >> 8) & 1) * 1792 + wq * 512 + (C ? to + DH * 16 : SM_VX + (s & 1) * 8192);
            auto load_vf = [&]() {
#pragma unroll
                for (int i = 0; i < 4; i++) ldsm_x4(vf[i & 1][i >> 1], va + (i & 1) * 256 + (i >> 1) * 4096);
            };
            load_vf();
            float scale = to_scale(fmaxf(fmaxf(fmaxf(m4.x, m4.y), fmaxf(m4.z, m4.w)) * minv, xb) * c24);
            uint32_t oa = l16 + wq * 512;
            asm volatile("" : "+f"(scale), "+r"(oa), "+r"(va));
            FS(7, __float_as_uint(scale));
            if (!C) named_bar(6, 160);
            if (C) mbar_wait(sb + B_SB + 8 * (s & 1), ph);
            float sv[5][2];
#pragma unroll
            for (int j = 0; j < 5; j++) {
                if (HS && C) { const uint32_t w = lds32(l4 + SM_S + j * 256); sv[j][0] = __uint_as_float(w << 16); sv[j][1] = __uint_as_float(w & 0xffff0000u); }
                else lds64f(sv[j][0], sv[j][1], l8 + SM_S + j * 256);
            }
            if (!C) mbar_wait(sb + B_SB + 8 * (s & 1), ph);
            FS(6, 0);
            uint32_t p[5];
            {
                float sr[5][2];
#pragma unroll
                for (int j = 0; j < 5; j++) {
                    if (HS) { const uint32_t w = lds32(l4 + SM_S + 1280 + j * 256); sr[j][0] = __uint_as_float(w << 16); sr[j][1] = __uint_as_float(w & 0xffff0000u); }
                    else lds64f(sr[j][0], sr[j][1], l8 + SM_S + 1280 + j * 256);
                }
                lds64(vm[0][0], vm[0][1], l8 + SM_VM + wq * 512);
                lds64(vm[1][0], vm[1][1], l8 + SM_VM + wq * 512 + 256);
#pragma unroll
                for (int j = 0; j < 5; j++) {
                    sv[j][0] += sr[j][0];
                    sv[j][1] += sr[j][1];
                }
                float mx = fmaxf(fmaxf(fmaxf(sv[0][0], sv[0][1]), fmaxf(sv[1][0], sv[1][1])), fmaxf(fmaxf(sv[2][0], sv[2][1]), fmaxf(sv[3][0], sv[3][1])));
                mx = fmaxf(mx, fmaxf(sv[4][0], sv[4][1]));
                {
                    const float m1 = __shfl_xor_sync(0xffffffffu, mx, 1), m2 = __shfl_xor_sync(0xffffffffu, mx, 2), m3 = __shfl_xor_sync(0xffffffffu, mx, 3);
                    mx = fmaxf(fmaxf(mx, m1), fmaxf(m2, m3));
                }
#pragma unroll
                for (int jj = 0; jj < 5; jj++) {
                    const int j = (jj + 1) % 5;
                    asm("ex2.approx.ftz.f32 %0, %1;" : "=f"(sv[j][0]) : "f"(sv[j][0] - mx));
                    asm("ex2.approx.ftz.f32 %0, %1;" : "=f"(sv[j][1]) : "f"(sv[j][1] - mx));
                    p[j] = pack_bf16(sv[j][0], sv[j][1]);
                }
            }
            FS(0, p[0]);
            uint32_t b[4][4];
            const uint32_t one4[4] = {0x3f803f80u, 0x3f803f80u, 0x3f803f80u, 0x3f803f80u};
            float zs[4];
            {
                float o0[2][4], o1[2][4];
                mma_z(o0[0], vf[0][0], p[1], p[2]);
                mma_z(o0[1], vf[1][0], p[1], p[2]);
                mma_z(o1[0], vf[0][1], p[3], p[4]);
                mma_z(o1[1], vf[1][1], p[3], p[4]);
                mma_k8(o0[0], vm[0][0], vm[0][1], p[0]);
                mma_k8(o0[1], vm[1][0], vm[1][1], p[0]);
                float z2[4];
                mma_z(zs, one4, p[1], p[2]);
                mma_z(z2, one4, p[3], p[4]);
                mma_k8(zs, one4[0], one4[1], p[0]);
                zs[0] += z2[0]; zs[1] += z2[1];
                uint32_t ow[4];
#pragma unroll
                for (int m = 0; m < 2; m++) {
                    ow[2 * m] = pack_bf16(o0[m][0] + o1[m][0], o0[m][1] + o1[m][1]);
                    ow[2 * m + 1] = pack_bf16(o0[m][2] + o1[m][2], o0[m][3] + o1[m][3]);
                }
                stsm_x4(oa + SM_O, ow[0], ow[1], ow[2], ow[3]);
                FS(2, 0);
                b[0][0] = movm(ow[0]); b[0][1] = movm(ow[1]);
                __syncwarp();
                asm volatile("ldmatrix.sync.aligned.m8n8.x2.trans.shared.b16 {%0,%1}, [%2];" : "=r"(b[0][2]), "=r"(b[0][3]) : "r"(oa + SM_O + 256));
            }
            float acc[3][2][4];
            named_bar(3, 128);
#pragma unroll
            for (int i = 1; i < 4; i++) ldsm_x4_t(b[i], l16 + SM_O + ((wq + i) & 3) * 512);
#pragma unroll
            for (int c = 0; c < 2; c++)
#pragma unroll
                for (int t = 0; t < 3; t++) mma_z(acc[t][c], wo[t][c], b[0][2 * c], b[0][2 * c + 1]);
            float z0, z1;
            asm volatile("rcp.approx.ftz.f32 %0, %1;" : "=f"(z0) : "f"(zs[0]));
            asm volatile("rcp.approx.ftz.f32 %0, %1;" : "=f"(z1) : "f"(zs[1]));
            asm volatile("{\n.reg .pred p;\nsetp.eq.s32 p, %1, 0;\n@p bar.sync 12, 160;\n@p ld.shared.f32 %0, [%2];\n}" : "+f"(scale) : "r"(s), "r"(sb + SM_SC) : "memory");
            z0 *= scale; z1 *= scale;
            FS(3, b[1][0]);
#pragma unroll
            for (int i = 1; i < 4; i++)
#pragma unroll
                for (int c = 0; c < 2; c++)
#pragma unroll
                    for (int t = 0; t < 3; t++) mma_bf16(acc[t][c], wo[t][2 * i + c], b[i][2 * c], b[i][2 * c + 1]);
            {
                uint32_t w[6];
#pragma unroll
                for (int t = 0; t < 3; t++) {
                    w[2 * t] = pack_f16(fmaf(acc[t][1][0], z0, acc[t][0][0] * z0), fmaf(acc[t][1][1], z1, acc[t][0][1] * z1));
                    w[2 * t + 1] = pack_f16(fmaf(acc[t][1][2], z0, acc[t][0][2] * z0), fmaf(acc[t][1][3], z1, acc[t][0][3] * z1));
                }
                FS(8, w[5]);
                asm volatile("red.relaxed.gpu.global.add.noftz.v4.f16x2 [%0], {%1,%2,%3,%4};" :: "l"(dst), "r"(w[0]), "r"(w[1]), "r"(w[2]), "r"(0x3c00u) : "memory");
                asm volatile("red.relaxed.gpu.global.add.noftz.v4.f16x2 [%0], {%1,%2,%3,%4};" :: "l"(dst + 4096), "r"(w[3]), "r"(w[4]), "r"(w[5]), "r"(0x3c00u) : "memory");
            }
            FS(9, 0);
            if (s == 0) TSQ(5);
            bar_arrive(4, 384);
            const uint32_t t0 = clock32();
            minv = __uint_as_float(0x7f000000u - __float_as_uint(scale));
            if (lane_o == 0) {
                if (wq == 0) sts32(sb + SM_SC + 8, __float_as_uint(minv));
                if (s + 3 < NSEG) {
                    if (wq == 0) mbar_expect(sb + B_SB + 8 * (s & 1), C ? 2560 >> HS : (1280 >> HS) + 2048);
                    if (wq == 1 && s > 0 && s + 5 < NSEG) mbar_expect(sb + B_XT + ((s & 1) ? 0 : 16) + 4 * ((s + 1) & 2), (s & 1) ? 32768 : 40960);
                    if (wq == 3 && !C) mbar_expect(sb + B_VX + 8 * (s & 1), 8192);
                }
            }
            __syncwarp();
            if (s == 1) {
                if (!C) pad_code<PADC>();
                int lane = lane_o;
                asm volatile("" : "+r"(lane));
                if (wq == 3) xmax_gather(lane, sb);
                __syncwarp();
            }
            if (!C) load_kf(kf, (s + 1) & 3);
            const uint4* src = reinterpret_cast<const uint4*>(dst + (wq * 16 - role * 32) * 1024);
            dst += n3 == 0 ? -256 : 128;
            asm volatile("" : "+l"(dst));
            const int xp = (s + 5) >> 1, kb = wq + ((s & 1) ? 2 * role : 4 + 3 * role);
            const bool xl = !C && xp < NSEG / 2 && wq < ((s & 1) ? 2 : 3 - role);
            const uint32_t xs = wq == 3 && (s & 1) == 0 && xp < NSEG / 2;
            const uint32_t xd = sb + SM_X + (rx + kb >= 13 ? rx + kb - 13 : rx + kb) * 8192;
            mx2 = poll_mem(src, l16 + SM_M + wq * 2304, t0, [&]() {
                if (xs && lane_o < 2) asm volatile("mbarrier.arrive.relaxed.cluster.shared::cluster.b64 _, [%0];" :: "r"(mapa(sb + B_XF, lane_o)) : "memory");
                if (!C && (xl || s == 0) && (s & 1) == 0) mbar_wait(sb + B_XF, (uint32_t)(s >> 1) & 1u);
                if (lane_o == 0) {
                    if (xl) tma_2d_mc(xd, &tmx2, ((s & 1) ? kb + 5 : kb - 4) * 64, xp * 64, sb + B_XT + ((s & 1) ? 0 : 16) + 8 * (xp & 1));
                    if (!C && s == 0 && role == 1) tma_2d_mc(sb + SM_X + (9 + wq) * 8192, &tmx2, (wq + 5) * 64, 128, sb + B_XT);
                }
                __syncwarp();
            });
            if ((s & 1) == 0) rx = rx >= 4 ? rx - 4 : rx + 9;
            if (s == 0) TSQ(6);
            b3 = n3;
        }
        if (!C) bar_arrive(2, 384);
        };
        if (role == 2) helper_loop(Flag<true>()); else helper_loop(Flag<false>());
    }
    TS3C(1);
    if (role == 2 && warp >= 4) last_rows();
    cluster_sync_all();
}

extern "C" void kernel_launch(void* const* d_in, const int* in_sizes, int n_in, void* d_out, int out_size) {
    const bf16* x = (const bf16*)d_in[0];
    const bf16* mem0 = (const bf16*)d_in[1];
    const bf16* Wq = (const bf16*)d_in[2];
    const bf16* Wk = (const bf16*)d_in[3];
    const bf16* Wv = (const bf16*)d_in[4];
    const bf16* Wo = (const bf16*)d_in[5];
    const bf16* logA = (const bf16*)d_in[8];
    const bf16* Aim = (const bf16*)d_in[9];
    const bf16* Cre = (const bf16*)d_in[10];
    const bf16* Cim = (const bf16*)d_in[11];
    const bf16* logdt = (const bf16*)d_in[12];
    const bf16* dskip = (const bf16*)d_in[13];
    const bf16* gw = (const bf16*)d_in[14];
    bf16* out = (bf16*)d_out;
    static bool attr_done = false;
    typedef CUresult (*EncFn)(CUtensorMap*, CUtensorMapDataType, cuuint32_t, void*, const cuuint64_t*, const cuuint64_t*, const cuuint32_t*,
                              const cuuint32_t*, CUtensorMapInterleave, CUtensorMapSwizzle, CUtensorMapL2promotion, CUtensorMapFloatOOBfill);
    static EncFn enc = nullptr;
    if (!attr_done) {
        void* fn = nullptr;
        cudaDriverEntryPointQueryResult qr;
        cudaGetDriverEntryPoint("cuTensorMapEncodeTiled", &fn, cudaEnableDefault, &qr);
        enc = (EncFn)fn;
        cudaFuncSetAttribute(k_chain, cudaFuncAttributeMaxDynamicSharedMemorySize, 232448);
        cudaFuncSetAttribute(k_side, cudaFuncAttributeMaxDynamicSharedMemorySize, SIDE_SMEM);
        attr_done = true;
    }
    CUtensorMap tmw[3];
    for (int i = 0; i < 3; i++) {
        const cuuint64_t dims[2] = {(cuuint64_t)HD, (cuuint64_t)DM};
        const cuuint64_t strides[1] = {(cuuint64_t)HD * 2};
        const cuuint32_t box[2] = {64, 64};
        const cuuint32_t es[2] = {1, 1};
        enc(&tmw[i], CU_TENSOR_MAP_DATA_TYPE_BFLOAT16, 2, (void*)(i == 0 ? Wq : (i == 1 ? Wk : Wv)), dims, strides, box, es, CU_TENSOR_MAP_INTERLEAVE_NONE,
            CU_TENSOR_MAP_SWIZZLE_128B, CU_TENSOR_MAP_L2_PROMOTION_L2_256B, CU_TENSOR_MAP_FLOAT_OOB_FILL_NONE);
    }
    CUtensorMap tmo;
    {
        const cuuint64_t dims[2] = {(cuuint64_t)DM, (cuuint64_t)HD};
        const cuuint64_t strides[1] = {(cuuint64_t)DM * 2};
        const cuuint32_t box[2] = {64, 128};
        const cuuint32_t es[2] = {1, 1};
        enc(&tmo, CU_TENSOR_MAP_DATA_TYPE_BFLOAT16, 2, (void*)Wo, dims, strides, box, es, CU_TENSOR_MAP_INTERLEAVE_NONE,
            CU_TENSOR_MAP_SWIZZLE_128B, CU_TENSOR_MAP_L2_PROMOTION_L2_128B, CU_TENSOR_MAP_FLOAT_OOB_FILL_NONE);
    }
    CUtensorMap tmx2;
    {
        const cuuint64_t dims[2] = {(cuuint64_t)DM, (cuuint64_t)S_LEN};
        const cuuint64_t strides[1] = {(cuuint64_t)DM * 2};
        const cuuint32_t box[2] = {64, 64};
        const cuuint32_t es[2] = {1, 1};
        enc(&tmx2, CU_TENSOR_MAP_DATA_TYPE_BFLOAT16, 2, (void*)x, dims, strides, box, es, CU_TENSOR_MAP_INTERLEAVE_NONE,
            CU_TENSOR_MAP_SWIZZLE_128B, CU_TENSOR_MAP_L2_PROMOTION_L2_128B, CU_TENSOR_MAP_FLOAT_OOB_FILL_NONE);
    }
    CUtensorMap tmm;
    {
        const cuuint64_t dims[2] = {(cuuint64_t)DM, (cuuint64_t)MEMT};
        const cuuint64_t strides[1] = {(cuuint64_t)DM * 2};
        const cuuint32_t box[2] = {64, (cuuint32_t)MEMT};
        const cuuint32_t es[2] = {1, 1};
        enc(&tmm, CU_TENSOR_MAP_DATA_TYPE_BFLOAT16, 2, (void*)mem0, dims, strides, box, es, CU_TENSOR_MAP_INTERLEAVE_NONE,
            CU_TENSOR_MAP_SWIZZLE_128B, CU_TENSOR_MAP_L2_PROMOTION_L2_128B, CU_TENSOR_MAP_FLOAT_OOB_FILL_NONE);
    }
    k_chain<<<NCTA, 384, 232448>>>(tmw[0], tmw[1], tmw[2], tmx2, tmo, tmm, x);
    {
        cudaLaunchConfig_t cfg = {};
        cfg.gridDim = dim3(SD_NCTA); cfg.blockDim = dim3(512); cfg.dynamicSmemBytes = SIDE_SMEM; cfg.stream = cudaStreamPerThread;
        cudaLaunchAttribute at[1];
        at[0].id = cudaLaunchAttributeProgrammaticStreamSerialization;
        at[0].val.programmaticStreamSerializationAllowed = 1;
        cfg.attrs = at; cfg.numAttrs = 1;
        cudaLaunchKernelEx(&cfg, k_side, tmo, x, logA, Aim, Cre, Cim, logdt, Wo, dskip, gw, out);
    }
}
```

```cpp
#include <cuda_runtime.h>
#include <cuda.h>
#include <cuda_bf16.h>
#include <stdint.h>

typedef __nv_bfloat16 bf16;
#define LDV4 "ld.volatile.global.v4.u32 {%0,%1,%2,%3}, [%4];"
#define STV4 "st.volatile.global.v4.u32 [%0], {%1,%2,%3,%4};"
#define STV2 "st.volatile.global.v2.u32 [%0], {%1,%2};"

constexpr int S_LEN = 2048, DM = 576, NH = 32, DH = 128, HD = 4096, MEMT = 8, SEG = 32, NSEG = 64, NST = 128;

__device__ __align__(128) bf16 g_gate[S_LEN];
constexpr int NCTA = NH * 3;
__device__ __align__(1024) unsigned char g_acc[96 * 1024];
__device__ __align__(128) uint2 g_norm[NCTA];
__device__ __align__(128) uint4 g_wv[NH][2];
__device__ __align__(128) uint4 g_rx[NSEG][2];
__device__ __align__(128) unsigned char g_qkv[NSEG][NH][3][10240];
__device__ __align__(128) bf16 g_ox[S_LEN * HD];
__device__ __align__(128) uint4 g_fp[8][36][6][128];
__device__ __align__(128) unsigned g_flag[NH * NSEG];
__device__ __align__(128) unsigned g_prog[8 * 64];
__device__ unsigned g_gcnt[64];
__device__ unsigned g_epoch;
__device__ __align__(128) uint2 g_tick;
__device__ __align__(128) bf16 g_y[DM * S_LEN];

#define TS3(slot) do {} while (0)
#define TS3P(slot) do {} while (0)
#define TSQ(slot) do {} while (0)
#define TS3W(slot) do {} while (0)
#define TSS(row, slot) do {} while (0)
#define TS3C(slot) do {} while (0)
#define TST(slot) do {} while (0)
#define TSA(seg, slot) do {} while (0)
#define TSG(i) do {} while (0)
#define FS(i, dep) do {} while (0)
__device__ __forceinline__ uint32_t smem_u32(const void* p) { return (uint32_t)__cvta_generic_to_shared(p); }
__device__ __forceinline__ float bf16r(float x) { return __bfloat162float(__float2bfloat16_rn(x)); }
__device__ __forceinline__ uint32_t pack_bf16(float lo, float hi) {
    __nv_bfloat162 v = __floats2bfloat162_rn(lo, hi);
    return *reinterpret_cast<uint32_t*>(&v);
}
__device__ __forceinline__ void ldsm_x4(uint32_t (&r)[4], uint32_t addr) {
    asm volatile("ldmatrix.sync.aligned.m8n8.x4.shared.b16 {%0,%1,%2,%3}, [%4];"
                 : "=r"(r[0]), "=r"(r[1]), "=r"(r[2]), "=r"(r[3]) : "r"(addr));
}
__device__ __forceinline__ void ldsm_x4_t(uint32_t (&r)[4], uint32_t addr) {
    asm volatile("ldmatrix.sync.aligned.m8n8.x4.trans.shared.b16 {%0,%1,%2,%3}, [%4];"
                 : "=r"(r[0]), "=r"(r[1]), "=r"(r[2]), "=r"(r[3]) : "r"(addr));
}
__device__ __forceinline__ void mma_bf16(float (&d)[4], const uint32_t (&a)[4], uint32_t b0, uint32_t b1) {
    asm volatile("mma.sync.aligned.m16n8k16.row.col.f32.bf16.bf16.f32 {%0,%1,%2,%3}, {%4,%5,%6,%7}, {%8,%9}, {%0,%1,%2,%3};"
                 : "+f"(d[0]), "+f"(d[1]), "+f"(d[2]), "+f"(d[3])
                 : "r"(a[0]), "r"(a[1]), "r"(a[2]), "r"(a[3]), "r"(b0), "r"(b1));
}
__device__ __forceinline__ uint2 ld_vol_u2(const uint2* p) {
    uint2 v; asm volatile("ld.volatile.global.v2.u32 {%0,%1}, [%2];" : "=r"(v.x), "=r"(v.y) : "l"(p) : "memory"); return v;
}
__device__ __forceinline__ void st_vol_u2(uint2* p, uint2 v) {
    asm volatile(STV2 :: "l"(p), "r"(v.x), "r"(v.y) : "memory");
}
__device__ __forceinline__ unsigned ld_acq(const unsigned* p) {
    unsigned v; asm volatile("ld.acquire.gpu.global.u32 %0, [%1];" : "=r"(v) : "l"(p) : "memory"); return v;
}
#define NS 10
#define NP 4
#define GATE_A 950
#define GATE_B 450
#define GATE_P 1800u
#define RLX_SLEEP 300
#define VX_DELAY 100
#define UNGATE_G 3
#define W14_SLEEP 60
#define GL_A 1150
#define GL_B 530
#define GS_A 1300
#define GS_B 480
#define NC1 3
#define NC1C 5
#define KPRE 34
#define PADC 0
#define PAD1 0
#define PAD2 0
#define PAD3 0
#define PAD4 0
#define KG1 20
#define WO_SLEEP 200
#define WO_LAG 500
#define TM 29
#define TM2 (TM - 1)
#define TL_DELAY 600
#define POLL_DELAY 590
#define UNGATE 6
constexpr unsigned SPIN_LIMIT = 1u << 20;
constexpr int NATT = NSEG - 2;

constexpr int SD_CH = 16;
constexpr int SD_NCTA = DM / SD_CH;
constexpr int SD_ROW = 528;
constexpr int SD_U = 8 * SD_ROW;
constexpr int SD_TAP = 5888;
constexpr int SD_CPY = 1376 * 2;
constexpr int SD_WSTR = SD_TAP + 2 * SD_CPY;
constexpr int SD_SMEM = SD_CH * SD_U + 8 * SD_WSTR;
constexpr int O_U = 79, O_U3 = 911, O_U4 = 1055, O_W79 = 1023, O_W35 = 1151, O_W610 = 1279, O_W511 = 1487;

__device__ __forceinline__ uint32_t lds32(uint32_t a) { uint32_t v; asm volatile("ld.shared.u32 %0, [%1];" : "=r"(v) : "r"(a)); return v; }
__device__ __forceinline__ void sts32(uint32_t a, uint32_t v) { asm volatile("st.shared.u32 [%0], %1;" :: "r"(a), "r"(v) : "memory"); }
__device__ __forceinline__ uint4 lds128(uint32_t a) {
    uint4 v; asm volatile("ld.shared.v4.u32 {%0,%1,%2,%3}, [%4];" : "=r"(v.x), "=r"(v.y), "=r"(v.z), "=r"(v.w) : "r"(a) : "memory"); return v;
}
__device__ __forceinline__ void tap_tile(uint32_t (&t)[4], uint32_t a) {
    asm volatile("ld.volatile.shared.u32 %0, [%4];\nld.volatile.shared.u32 %1, [%4+-16];\nld.volatile.shared.u32 %2, [%4+16];\nld.volatile.shared.u32 %3, [%4];"
                 : "=r"(t[0]), "=r"(t[1]), "=r"(t[2]), "=r"(t[3]) : "r"(a));
}
constexpr uint32_t sd_pass(int type, int dl, int o, int d0, int d1) { return (uint32_t)(type | dl << 2 | d0 << 8 | d1 << 12 | o << 17); }
__constant__ uint32_t SD_PASS[14] = {sd_pass(0, 0, O_U, 0, 2), sd_pass(0, 1, O_U + 96, 0, 2), sd_pass(0, 2, O_U + 192, 0, 4), sd_pass(0, 3, O_U + 288, 0, 2), sd_pass(1, 0, O_U3, 8, 8),
                                     sd_pass(0, 4, O_U + 384, 0, 2), sd_pass(1, 0, O_U4, 8, 15), sd_pass(0, 5, O_U + 480, 0, 2), sd_pass(0, 6, O_U + 576, 0, 4), sd_pass(0, 7, O_U + 672, 0, 2),
                                     sd_pass(2, 0, O_W35, 2, 8), sd_pass(3, 0, O_W79, 2, 4), sd_pass(2, 1, O_W610, 4, 8), sd_pass(3, 0, O_W511, 8, 15)};
__device__ __forceinline__ uint32_t band2(int x, int lo, int hi) { return (x >= lo && x <= hi ? 0x3f80u : 0u) | (x + 1 >= lo && x + 1 <= hi ? 0x3f800000u : 0u); }
__device__ __forceinline__ void mma_z(float (&d)[4], const uint32_t (&a)[4], uint32_t b0, uint32_t b1);
__device__ __forceinline__ void put_tap(uint32_t a, float v) {
    asm volatile("{\n.reg .b16 h;\ncvt.rn.bf16.f32 h, %1;\nst.shared.b16 [%0], h;\nst.shared.b16 [%0+%2], h;\n}" :: "r"(a), "f"(v), "n"(SD_CPY - 2) : "memory");
}

__device__ __forceinline__ void named_bar(int id, int n) { asm volatile("bar.sync %0, %1;" :: "r"(id), "r"(n) : "memory"); }
__device__ __forceinline__ uint32_t pack_f16(float lo, float hi) {
    uint32_t r; asm("cvt.rn.f16x2.f32 %0, %1, %2;" : "=r"(r) : "f"(hi), "f"(lo)); return r;
}
__device__ __forceinline__ void cexp_t(float lr, float turns, float& re, float& im) {
    float m;
    asm("ex2.approx.ftz.f32 %0, %1;" : "=f"(m) : "f"(lr));
    const float a = (turns - rintf(turns)) * 6.283185307179586f;
    re = m * __cosf(a); im = m * __sinf(a);
}
__device__ __forceinline__ void csq(float& re, float& im) { const float r = re * re - im * im; im = 2.f * re * im; re = r; }
__device__ __forceinline__ void kb_state(const float* tp, float gf, uint32_t (&a)[4][2], uint32_t (&b)[5]) {
    const float4 p0 = *reinterpret_cast<const float4*>(tp), p1 = *reinterpret_cast<const float4*>(tp + 4);
    float wr, wi;
    cexp_t(p0.x * gf, p0.y * gf, wr, wi);
    float vr = wr * p1.x - wi * p1.y, vi = wr * p1.y + wi * p1.x;
#pragma unroll
    for (int c = 0; c < 4; c++) {
        a[c][0] = pack_f16(wr, wi); a[c][1] = pack_f16(vr, vi);
        csq(wr, wi);
        if (c < 3) csq(vr, vi);
    }
    b[0] = pack_f16(p0.z * wr - p0.w * wi, -p0.z * wi - p0.w * wr);
    float er = wr * p1.z - wi * p1.w, ei = wr * p1.w + wi * p1.z;
#pragma unroll
    for (int c = 0; c < 4; c++) {
        b[1 + c] = pack_f16(p0.z * er - p0.w * ei, -p0.z * ei - p0.w * er);
        if (c < 3) csq(er, ei);
    }
}
__device__ __forceinline__ uint32_t bf2_mul(uint32_t a, uint32_t b) { uint32_t r; asm("mul.rn.bf16x2 %0, %1, %2;" : "=r"(r) : "r"(a), "r"(b)); return r; }
__device__ __forceinline__ uint32_t bf2_add(uint32_t a, uint32_t b) { uint32_t r; asm("add.rn.bf16x2 %0, %1, %2;" : "=r"(r) : "r"(a), "r"(b)); return r; }
__device__ __forceinline__ uint32_t bf2_sub(uint32_t a, uint32_t b) { uint32_t r; asm("sub.rn.bf16x2 %0, %1, %2;" : "=r"(r) : "r"(a), "r"(b)); return r; }
__device__ __forceinline__ void wait_cnt(const unsigned* p, unsigned target) {
    unsigned it = 0;
    while ((int)(ld_acq(p) - target) < 0 && ++it < SPIN_LIMIT) __nanosleep(64);
}
__device__ __forceinline__ uint32_t gtime32() { uint32_t t; asm volatile("mov.u32 %0, %%globaltimer_lo;" : "=r"(t) :: "memory"); return t; }
__device__ __forceinline__ void gate(uint32_t tick_addr, uint32_t ga = GATE_A, uint32_t gb = GATE_B) {
    uint32_t t1, p;
    asm volatile("ld.volatile.shared.v2.u32 {%0,%1}, [%2];" : "=r"(t1), "=r"(p) : "r"(tick_addr) : "memory");
    uint32_t d = gtime32() - t1;
    if (d < 4u * p) {
        d -= d >= 2u * p ? 2u * p : 0u;
        d -= d >= p ? p : 0u;
        if (d + ga >= p && d + gb < p) {
            const uint32_t t2 = gtime32() + (p - gb - d);
            while ((int)(gtime32() - t2) < 0) {}
        }
    }
}

__device__ __forceinline__ void read_tick(uint32_t tick_addr) {
    const uint2 tk = ld_vol_u2(&g_tick);
    uint32_t p = tk.x - tk.y;
    p = p > GATE_P + 100u ? GATE_P + 100u : p;
    asm volatile("st.volatile.shared.v2.u32 [%0], {%1,%2};" :: "r"(tick_addr), "r"(tk.x), "r"(p) : "memory");
}

__device__ __forceinline__ void s4d_phase(unsigned char* smem_raw, const bf16* __restrict__ x, const bf16* __restrict__ logA,
                                          const bf16* __restrict__ Aim, const bf16* __restrict__ Cre, const bf16* __restrict__ Cim,
                                          const bf16* __restrict__ logdt, const bf16* __restrict__ dskip, const bf16* __restrict__ wslice) {
    const int tid = threadIdx.x, warp = __shfl_sync(0xffffffffu, tid >> 5, 0), lane = tid & 31;
    const int d0 = blockIdx.x * SD_CH;
    float* tab = reinterpret_cast<float*>(smem_raw + SD_CH * SD_U + warp * SD_WSTR);
    const uint32_t wb = smem_u32(tab);
    const int g = lane >> 2, tq = lane & 3;
    uint2 prm[4];
    float ldt;
    auto load_prm = [&](int d) {
        prm[0] = __ldg(reinterpret_cast<const uint2*>(logA + d * NST) + lane); prm[1] = __ldg(reinterpret_cast<const uint2*>(Aim + d * NST) + lane);
        prm[2] = __ldg(reinterpret_cast<const uint2*>(Cre + d * NST) + lane); prm[3] = __ldg(reinterpret_cast<const uint2*>(Cim + d * NST) + lane);
        ldt = __bfloat162float(logdt[d]);
    };
    load_prm(d0 + warp);
    for (int i = lane; i < 2 * SD_CPY / 16; i += 32) reinterpret_cast<uint4*>(tab + SD_TAP / 4)[i] = make_uint4(0u, 0u, 0u, 0u);
    TS3(20);
#pragma unroll 1
    for (int ch = 0; ch < 2; ch++) {
        const int d = d0 + 8 * ch + warp;
        const uint32_t ub = smem_u32(smem_raw) + (8 * ch + warp) * SD_U;
        float k2048 = 0.f, sinv;
        {
            const float dt = bf16r(expf(ldt));
            uint32_t cm = __vmaxu2(__vmaxu2(prm[2].x & 0x7fff7fffu, prm[2].y & 0x7fff7fffu), __vmaxu2(prm[3].x & 0x7fff7fffu, prm[3].y & 0x7fff7fffu));
            cm = __reduce_max_sync(0xffffffffu, max(cm << 16, cm & 0xffff0000u));
            int e = 134 - (int)(__float_as_uint(__uint_as_float(cm) * dt) >> 23);
            e = e > 100 ? 100 : (e < -100 ? -100 : e);
            const float s2 = __uint_as_float((uint32_t)(128 + e) << 23);
            sinv = __uint_as_float((uint32_t)(127 - e) << 23);
#pragma unroll
            for (int j = 0; j < 4; j++) {
                float q[4];
#pragma unroll
                for (int i = 0; i < 4; i++) { const uint32_t w = j < 2 ? prm[i].x : prm[i].y; q[i] = __uint_as_float((j & 1) ? w & 0xffff0000u : w << 16); }
                const float zl = -bf16r(expf(q[0])) * dt * 1.4426950408889634f;
                const float zt = q[1] * dt * 0.15915494309189535f;
                const float cr = s2 * (q[2] * dt), ci = s2 * (q[3] * dt);
                float ar, ai, br, bi, er, ei;
                cexp_t(zl * 8.f, zt * 8.f, ar, ai);
                cexp_t(zl * 128.f, zt * 128.f, br, bi);
                cexp_t(zl * 2048.f, zt * 2048.f, er, ei);
                k2048 += cr * er - ci * ei;
                *reinterpret_cast<float4*>(tab + (lane + 32 * j) * 8) = make_float4(zl, zt, cr, ci);
                *reinterpret_cast<float4*>(tab + (lane + 32 * j) * 8 + 4) = make_float4(ar, ai, br, bi);
            }
#pragma unroll
            for (int o = 16; o; o >>= 1) k2048 += __shfl_xor_sync(0xffffffffu, k2048, o);
        }
        __syncwarp();
        {
            float kc[5][4];
#pragma unroll
            for (int i = 0; i < 5; i++) { kc[i][0] = kc[i][1] = kc[i][2] = kc[i][3] = 0.f; }
            const float gf = (float)g;
#pragma unroll 2
            for (int ks = 0; ks < 16; ks++) {
                uint32_t a0[4][2], a1[4][2], b0[5], b1[5];
                kb_state(tab + (8 * ks + tq) * 8, gf, a0, b0);
                kb_state(tab + (8 * ks + 4 + tq) * 8, gf, a1, b1);
#pragma unroll
                for (int i = 0; i < 5; i++) {
                    const int c = i > 0 ? i - 1 : 0;
                    asm volatile("mma.sync.aligned.m16n8k16.row.col.f32.f16.f16.f32 {%0,%1,%2,%3}, {%4,%5,%6,%7}, {%8,%9}, {%0,%1,%2,%3};"
                                 : "+f"(kc[i][0]), "+f"(kc[i][1]), "+f"(kc[i][2]), "+f"(kc[i][3])
                                 : "r"(a0[c][0]), "r"(a0[c][1]), "r"(a1[c][0]), "r"(a1[c][1]), "r"(b0[i]), "r"(b1[i]));
                }
            }
            const uint32_t tp = wb + SD_TAP;
            const uint32_t a0 = tp + 2 * (O_U + 96 * g - 4 * tq);
            const uint32_t a2 = tp + 2 * (((g & 1) ? O_U + 96 * (2 * (g & 3)) : ((g & 2) ? O_W35 : O_W79 + 1)) - 32 - 8 * tq - (g >> 2));
            const uint32_t a3 = tp + 2 * (((g & 1) ? O_W35 : O_W610 + 1) - 64 - 16 * tq - (g >> 1));
            const uint32_t a4 = tp + 2 * (-128 - 32 * tq - g);
#pragma unroll
            for (int c = 0; c < 4; c++) {
                const int e = (c & 1) * 16 + (c >> 1) * 8;
                const bool first = c == 0 && lane == 0;
                put_tap(a0 - e / 4, kc[0][c] * sinv);
                put_tap(a0 - 32 - e / 4, kc[1][c] * sinv);
                put_tap(first ? tp + 2 * (O_U - 32) : a2 - e / 2, kc[2][c] * sinv);
                put_tap(first ? tp + 2 * (O_W79 - 63) : a3 - e, kc[3][c] * sinv);
                put_tap(first ? tp + 2 * (O_W610 - 127) : a4 + 2 * (O_W511 + 1 - e), kc[4][c] * sinv);
                if ((g & 1) == 0) {
                    put_tap(a4 + 2 * (O_U4 - e), kc[4][c] * sinv);
                    put_tap(first ? tp + 2 * (O_U3 - 128) : a4 + 2 * (O_U4 + 1 - e), kc[4][c] * sinv);
                }
            }
            if (lane == 0) {
                put_tap(tp + 2 * (O_U + 96 - 32), kc[2][0] * sinv);
                put_tap(tp + 2 * (O_U + 192 - 64), kc[3][0] * sinv);
                put_tap(tp + 2 * (O_W511 - 255), k2048 * sinv);
                put_tap(tp + 2 * (O_U4 - 255), k2048 * sinv);
            }
        }
        TS3(21 + 2 * ch);
        if (ch == 0) named_bar(1, 384);
        else {
#pragma unroll
            for (int i = 0; i < 4; i++) asm volatile("prefetch.global.L2 [%0];" :: "l"(wslice + (size_t)((tid & 127) + 128 * i) * DM));
        }
        __syncwarp();
        if (tid == 0) TSS(18, 4 * ch);
        const uint32_t sh = wb + 80 + 11 * SD_ROW;
#pragma unroll
        for (int p = 0; p < 8; p++) {
            uint4 v;
            asm volatile("ld.shared.v4.u32 {%0,%1,%2,%3}, [%4];" : "=r"(v.x), "=r"(v.y), "=r"(v.z), "=r"(v.w) : "r"(ub + p * SD_ROW + lane * 16) : "memory");
            uint32_t pv = __shfl_up_sync(0xffffffffu, v.w, 1);
            pv = lane == 0 ? 0u : pv;
            asm volatile("st.shared.v4.u32 [%0], {%1,%2,%3,%4};" :: "r"(sh + (p - 8) * SD_ROW + lane * 16), "r"(__byte_perm(pv, v.x, 0x5432)), "r"(__byte_perm(v.x, v.y, 0x5432)),
                         "r"(__byte_perm(v.y, v.z, 0x5432)), "r"(__byte_perm(v.z, v.w, 0x5432)) : "memory");
            if (p >= 5) asm volatile("st.shared.v4.u32 [%0], {%1,%2,%3,%4};" :: "r"(sh + (p - 16) * SD_ROW + lane * 16), "r"(pv), "r"(v.x), "r"(v.y), "r"(v.z) : "memory");
        }
        __syncwarp();
        if (tid == 0) TSS(18, 4 * ch + 1);
        float acc[16][4];
#pragma unroll
        for (int i = 0; i < 16; i++) { acc[i][0] = acc[i][1] = acc[i][2] = acc[i][3] = 0.f; }
        {
            const uint32_t ka = wb + SD_TAP + ((g & 1) ? 0 : SD_CPY - 2) + 2 * (2 * tq - g);
            uint32_t b[16][2], b2[14][2];
#pragma unroll
            for (int k = 0; k < 16; k++) { b[k][0] = b[k][1] = 0u; if (k < 14) b2[k][0] = b2[k][1] = 0u; }
#pragma unroll 1
            for (int ps = 0; ps < 14; ps++) {
                const uint32_t pw = __shfl_sync(0xffffffffu, SD_PASS[ps], 0), type = pw & 3u, kp = ka + (pw >> 16);
                const int dl = (pw >> 2) & 7, d0 = (pw >> 8) & 15, d1 = (pw >> 12) & 15;
                uint32_t t[2][4];
                tap_tile(t[0], kp - 32 * d0);
                if (type == 0) {
                    const int p = (lane & 7) - dl;
                    const uint32_t ra = (p < 0 ? sh : ub) + p * SD_ROW + (lane >> 3) * 16;
#pragma unroll
                    for (int k = 0; k < 8; k++)
                        asm volatile("ldmatrix.sync.aligned.m8n8.x4.shared.b16 {%0,%1,%2,%3}, [%4];"
                                     : "=r"(b[2 * k][0]), "=r"(b[2 * k][1]), "=r"(b[2 * k + 1][0]), "=r"(b[2 * k + 1][1]) : "r"(ra + k * 64));
                } else if (type == 2) {
                    const int p = (lane & 15) - 11, xo = 2 * tq - g;
                    const uint32_t qa = (p < 0 ? sh : ub) + p * SD_ROW + (lane >> 4) * 16;
                    const int lx = 6 - 5 * dl, hx = 8 - 3 * dl, ly = 2 - 2 * dl, hy = 4 + 2 * dl;
                    const uint32_t sel[4] = {band2(xo, lx, hx), band2(xo, ly, hy), band2(xo + 8, lx, hx), band2(xo + 8, ly, hy)};
#pragma unroll
                    for (int k = 0; k < 14; k++) {
                        uint32_t q[4];
                        ldsm_x4_t(q, qa + k * 32);
#pragma unroll
                        for (int i = 0; i < 2; i++) {
                            float w[4];
                            mma_z(w, sel, q[2 * i], q[2 * i + 1]);
                            b[k][i] = pack_bf16(w[0], w[1]);
                            b2[k][i] = pack_bf16(w[2], w[3]);
                        }
                    }
                } else if (type == 3) {
#pragma unroll
                    for (int k = 0; k < 14; k++) { b[k][0] = b2[k][0]; b[k][1] = b2[k][1]; }
                }
#pragma unroll
                for (int d = 0; d < 16; d += 2) {
                    if (d >= 8 || d >= d0) {
                        tap_tile(t[1], kp - 32 * (d + 1));
#pragma unroll
                        for (int k = 0; k + d < 16; k++) mma_bf16(acc[k + d], t[0], b[k][0], b[k][1]);
                        if ((d == 2 || d == 4 || d == 8) && d == d1) break;
                        if (d < 14) tap_tile(t[0], kp - 32 * (d + 2));
#pragma unroll
                        for (int k = 0; k + d + 1 < 16; k++) mma_bf16(acc[k + d + 1], t[1], b[k][0], b[k][1]);
                    }
                }
            }
        }
        __syncwarp();
        if (tid == 0) TSS(18, 4 * ch + 2);
        load_prm(d0 + 8 + warp);
        if (ch == 0) {
            if (lane == 0) {
                unsigned ep;
                asm volatile("ld.volatile.global.u32 %0, [%1];" : "=r"(ep) : "l"(&g_epoch) : "memory");
                wait_cnt(&g_gcnt[0], SD_NCTA * (ep + 1u));
            }
            __syncwarp();
        }
        if (tid == 0) TSS(18, 4 * ch + 3);
        uint4 gv[8];
#pragma unroll
        for (int i = 0; i < 8; i++) gv[i] = __ldcg(reinterpret_cast<const uint4*>(g_gate) + lane + 32 * i);
        const uint32_t dd = __byte_perm(*reinterpret_cast<const unsigned short*>(dskip + d), 0u, 0x1010);
#pragma unroll
        for (int i = 0; i < 8; i++) {
            uint32_t u[4];
            ldsm_x4_t(u, ub + (lane & 7) * SD_ROW + (lane >> 3) * 16 + i * 64);
            asm volatile("stmatrix.sync.aligned.m8n8.x4.shared.b16 [%0], {%1,%2,%3,%4};"
                         :: "r"(wb + (lane + 32 * i) * 16),
                            "r"(bf2_add(pack_bf16(acc[2 * i][0], acc[2 * i][1]), bf2_mul(u[0], dd))), "r"(bf2_add(pack_bf16(acc[2 * i][2], acc[2 * i][3]), bf2_mul(u[1], dd))),
                            "r"(bf2_add(pack_bf16(acc[2 * i + 1][0], acc[2 * i + 1][1]), bf2_mul(u[2], dd))), "r"(bf2_add(pack_bf16(acc[2 * i + 1][2], acc[2 * i + 1][3]), bf2_mul(u[3], dd))) : "memory");
        }
        __syncwarp();
#pragma unroll
        for (int i = 0; i < 8; i++) {
            const uint4 y = *reinterpret_cast<const uint4*>(tab + (lane + 32 * i) * 4);
            *reinterpret_cast<uint4*>(g_y + (((lane >> 1) + 16 * i) * DM + d) * 16 + (lane & 1) * 8) =
                make_uint4(bf2_mul(bf2_sub(0x3f803f80u, gv[i].x), y.x), bf2_mul(bf2_sub(0x3f803f80u, gv[i].y), y.y),
                           bf2_mul(bf2_sub(0x3f803f80u, gv[i].z), y.z), bf2_mul(bf2_sub(0x3f803f80u, gv[i].w), y.w));
        }
        __syncwarp();
        if (ch == 0) asm volatile("bar.arrive 11, 288;" ::: "memory");
        TS3(22 + 2 * ch);
    }
}
__device__ __forceinline__ void s4d_stage_u(unsigned char* smem_raw, const bf16* __restrict__ x, int pt) {
    const int p = pt & 7, w0 = pt >> 3;
    const uint4* src = reinterpret_cast<const uint4*>(x + (size_t)(16 * w0 + p) * DM + blockIdx.x * SD_CH);
    uint32_t* dst = reinterpret_cast<uint32_t*>(smem_raw + p * SD_ROW) + w0;
#pragma unroll 1
    for (int b = 0; b < 4; b++) {
        uint4 v[2][2][2];
#pragma unroll
        for (int i = 0; i < 8; i++) v[i >> 2][(i >> 1) & 1][i & 1] = src[((b * 2 + (i >> 2)) * 256 + ((i >> 1) & 1) * 8) * (DM / 8) + (i & 1)];
#pragma unroll
        for (int i = 0; i < 4; i++) {
            const uint32_t* lo = reinterpret_cast<const uint32_t*>(&v[i >> 1][0][i & 1]);
            const uint32_t* hi = reinterpret_cast<const uint32_t*>(&v[i >> 1][1][i & 1]);
#pragma unroll
            for (int c = 0; c < 8; c++) dst[((i & 1) * 8 + c) * (SD_U / 4) + (b * 2 + (i >> 1)) * 16] = __byte_perm(lo[c >> 1], hi[c >> 1], (c & 1) ? 0x7632 : 0x5410);
        }
    }
    asm volatile("bar.arrive 1, 384;" ::: "memory");
}

constexpr int WOC = DM / 3;
constexpr int TBUF = 5 * DH * 16;
constexpr int XBUF = SEG * DM * 2;
constexpr int SM_BAR = 0;
constexpr int B_SB = 0, B_VX = 16, B_XT = 32, B_XF = 144, B_W = 64, B_E = 136;
constexpr int SM_SC = 256;
constexpr int SM_F = SM_SC + 1280;
constexpr int SM_VM = SM_F + 2048;
constexpr int SM_S = SM_VM + 2048;
constexpr int SM_O = SM_S + 2560;
constexpr int SM_M = SM_O + 2048;
constexpr int SM_WS = 19456;
constexpr int SM_T = SM_WS + 49152;
constexpr int SM_VX = SM_T + 4 * TBUF;
constexpr int SM_X = SM_VX + 2 * 8192;
constexpr int SM_X01 = SM_WS + DM * DH * 2;
__host__ __device__ constexpr int x01_off(int b) { return b < 2 ? 1024 + b * 9216 : SM_X01 + (b == 2 ? 6 : b - 3) * 9216; }
__host__ __device__ constexpr int x23_off(int b) { return b < 3 ? SM_WS + 7 * 16384 + b * 8192 : x01_off(b - 3); }
constexpr int CH_SMEM = SM_X01 + 8 * 8192;
static_assert(SM_M + DM * 16 <= SM_WS && SM_X + 13 * 8192 <= CH_SMEM && NS <= 10 && CH_SMEM <= 232448 && SM_X % 1024 == 0 && SM_X01 % 1024 == 0 && 1024 + 2 * 9216 <= SM_WS, "smem");
__device__ __forceinline__ uint32_t clock32() { uint32_t t; asm volatile("mov.u32 %0, %%clock;" : "=r"(t) :: "memory"); return t; }

__device__ __forceinline__ uint32_t mapa(uint32_t a, uint32_t rank) {
    uint32_t r; asm volatile("mapa.shared::cluster.u32 %0, %1, %2;" : "=r"(r) : "r"(a), "r"(rank)); return r;
}
__device__ __forceinline__ void st_async32(uint32_t addr, uint32_t v, uint32_t mbar) {
    asm volatile("st.async.weak.shared::cluster.mbarrier::complete_tx::bytes.b32 [%0], %1, [%2];" :: "r"(addr), "r"(v), "r"(mbar) : "memory");
}
__device__ __forceinline__ void mbar_init(uint32_t bar, uint32_t cnt) {
    asm volatile("mbarrier.init.shared::cta.b64 [%0], %1;" :: "r"(bar), "r"(cnt) : "memory");
}
__device__ __forceinline__ void mbar_expect(uint32_t bar, uint32_t bytes) {
    asm volatile("mbarrier.arrive.expect_tx.shared::cta.b64 _, [%0], %1;" :: "r"(bar), "r"(bytes) : "memory");
}
__device__ __forceinline__ void mbar_wait(uint32_t bar, uint32_t parity) {
    unsigned it = 0;
    uint32_t ok;
    do {
        ++it;
        asm volatile("{\n.reg .pred p;\nmbarrier.try_wait.parity.shared::cta.b64 p, [%1], %2;\nselp.u32 %0, 1, 0, p;\n}" : "=r"(ok) : "r"(bar), "r"(parity) : "memory");
    } while ((ok == 0u) & (it < SPIN_LIMIT));
}
__device__ __forceinline__ void mbar_wait_long(uint32_t bar, uint32_t parity) {
    unsigned it = 0;
    while (true) {
        uint32_t ok;
        asm volatile("{\n.reg .pred p;\nmbarrier.try_wait.parity.shared::cta.b64 p, [%1], %2, %3;\nselp.u32 %0, 1, 0, p;\n}"
                     : "=r"(ok) : "r"(bar), "r"(parity), "r"(20000u) : "memory");
        if (ok || ++it >= SPIN_LIMIT) break;
    }
}
__device__ __forceinline__ bool mbar_test(uint32_t bar, uint32_t parity) {
    uint32_t ok;
    asm volatile("{\n.reg .pred p;\nmbarrier.test_wait.parity.shared::cta.b64 p, [%1], %2;\nselp.u32 %0, 1, 0, p;\n}" : "=r"(ok) : "r"(bar), "r"(parity) : "memory");
    return ok != 0u;
}
__device__ __forceinline__ uint64_t policy_evict_first() {
    uint64_t pol; asm volatile("createpolicy.fractional.L2::evict_first.b64 %0, 1.0;" : "=l"(pol)); return pol;
}
__device__ __forceinline__ void cluster_sync_all() {
    asm volatile("barrier.cluster.arrive.release.aligned;\nbarrier.cluster.wait.acquire.aligned;" ::: "memory");
}
__device__ __forceinline__ uint4 ld_vol_u4(const uint4* p) {
    uint4 v; asm volatile(LDV4 : "=r"(v.x), "=r"(v.y), "=r"(v.z), "=r"(v.w) : "l"(p) : "memory"); return v;
}
__device__ __forceinline__ void ld_vol_u4_p(uint4& v, const uint4* p, uint32_t pred) {
    asm volatile("{\n.reg .pred p;\nsetp.ne.u32 p, %5, 0;\n@p " LDV4 "\n}"
                 : "+r"(v.x), "+r"(v.y), "+r"(v.z), "+r"(v.w) : "l"(p), "r"(pred) : "memory");
}
__device__ __forceinline__ void st_vol_u4(uint4* p, uint4 v) {
    asm volatile(STV4 :: "l"(p), "r"(v.x), "r"(v.y), "r"(v.z), "r"(v.w) : "memory");
}
__device__ __forceinline__ void mma_bf16_r(float (&d)[4], uint32_t a0, uint32_t a1, uint32_t a2, uint32_t a3, uint32_t b0, uint32_t b1) {
    asm volatile("mma.sync.aligned.m16n8k16.row.col.f32.bf16.bf16.f32 {%0,%1,%2,%3}, {%4,%5,%6,%7}, {%8,%9}, {%0,%1,%2,%3};"
                 : "+f"(d[0]), "+f"(d[1]), "+f"(d[2]), "+f"(d[3])
                 : "r"(a0), "r"(a1), "r"(a2), "r"(a3), "r"(b0), "r"(b1));
}

__device__ __forceinline__ uint64_t smem_desc(uint32_t addr, uint32_t lbo, uint32_t sbo) {
    return (uint64_t)((addr & 0x3FFFF) >> 4) | ((uint64_t)(lbo >> 4) << 16) | ((uint64_t)(sbo >> 4) << 32);
}
__device__ __forceinline__ void wg_fence() { asm volatile("wgmma.fence.sync.aligned;" ::: "memory"); }
__device__ __forceinline__ void wg_commit() { asm volatile("wgmma.commit_group.sync.aligned;" ::: "memory"); }
__device__ __forceinline__ void wg_wait0() { asm volatile("wgmma.wait_group.sync.aligned 0;" ::: "memory"); }
__device__ __forceinline__ void fence_async() { asm volatile("fence.proxy.async.shared::cta;" ::: "memory"); }
__device__ __forceinline__ void wgmma_n64_ss(float (&d)[32], uint64_t adesc, uint64_t bdesc) {
    asm volatile("{\n.reg .pred p;\nsetp.eq.b32 p, 0, 0;\n"
                 "wgmma.mma_async.sync.aligned.m64n64k16.f32.bf16.bf16 {%0,%1,%2,%3,%4,%5,%6,%7,%8,%9,%10,%11,%12,%13,%14,%15,%16,%17,%18,%19,%20,%21,%22,%23,%24,%25,%26,%27,%28,%29,%30,%31}, %32, %33, p, 1, 1, 1, 0;\n}"
                 : "+f"(d[0]), "+f"(d[1]), "+f"(d[2]), "+f"(d[3]), "+f"(d[4]), "+f"(d[5]), "+f"(d[6]), "+f"(d[7]), "+f"(d[8]), "+f"(d[9]), "+f"(d[10]), "+f"(d[11]), "+f"(d[12]), "+f"(d[13]), "+f"(d[14]), "+f"(d[15]), "+f"(d[16]), "+f"(d[17]), "+f"(d[18]), "+f"(d[19]), "+f"(d[20]), "+f"(d[21]), "+f"(d[22]), "+f"(d[23]), "+f"(d[24]), "+f"(d[25]), "+f"(d[26]), "+f"(d[27]), "+f"(d[28]), "+f"(d[29]), "+f"(d[30]), "+f"(d[31])
                 : "l"(adesc), "l"(bdesc));
}
__device__ __forceinline__ void wgmma_n72_ss(float (&d)[36], uint64_t adesc, uint64_t bdesc) {
    asm volatile("{\n.reg .pred p;\nsetp.eq.b32 p, 0, 0;\n"
                 "wgmma.mma_async.sync.aligned.m64n72k16.f32.bf16.bf16 {%0,%1,%2,%3,%4,%5,%6,%7,%8,%9,%10,%11,%12,%13,%14,%15,%16,%17,%18,%19,%20,%21,%22,%23,%24,%25,%26,%27,%28,%29,%30,%31,%32,%33,%34,%35}, %36, %37, p, 1, 1, 1, 0;\n}"
                 : "+f"(d[0]), "+f"(d[1]), "+f"(d[2]), "+f"(d[3]), "+f"(d[4]), "+f"(d[5]), "+f"(d[6]), "+f"(d[7]), "+f"(d[8]), "+f"(d[9]), "+f"(d[10]), "+f"(d[11]), "+f"(d[12]), "+f"(d[13]), "+f"(d[14]), "+f"(d[15]), "+f"(d[16]), "+f"(d[17]), "+f"(d[18]), "+f"(d[19]), "+f"(d[20]), "+f"(d[21]), "+f"(d[22]), "+f"(d[23]), "+f"(d[24]), "+f"(d[25]), "+f"(d[26]), "+f"(d[27]), "+f"(d[28]), "+f"(d[29]), "+f"(d[30]), "+f"(d[31]), "+f"(d[32]), "+f"(d[33]), "+f"(d[34]), "+f"(d[35])
                 : "l"(adesc), "l"(bdesc));
}
__device__ __forceinline__ void tma_2d(uint32_t dst, const CUtensorMap* tm, int c0, int c1, uint32_t mbar) {
    asm volatile("cp.async.bulk.tensor.2d.shared::cluster.global.tile.mbarrier::complete_tx::bytes [%0], [%1, {%2, %3}], [%4];"
                 :: "r"(dst), "l"(tm), "r"(c0), "r"(c1), "r"(mbar) : "memory");
}

__device__ __forceinline__ void bulk_g2s(uint32_t dst, const void* src, uint32_t bytes, uint32_t mbar) {
    asm volatile("cp.async.bulk.shared::cluster.global.mbarrier::complete_tx::bytes [%0], [%1], %2, [%3];"
                 :: "r"(dst), "l"(src), "r"(bytes), "r"(mbar) : "memory");
}
__device__ __forceinline__ void bulk_g2s_h(uint32_t dst, const void* src, uint32_t bytes, uint32_t mbar, uint64_t pol) {
    asm volatile("cp.async.bulk.shared::cluster.global.mbarrier::complete_tx::bytes.L2::cache_hint [%0], [%1], %2, [%3], %4;"
                 :: "r"(dst), "l"(src), "r"(bytes), "r"(mbar), "l"(pol) : "memory");
}
__device__ __forceinline__ void tma_2d_mc(uint32_t dst, const CUtensorMap* tm, int c0, int c1, uint32_t mbar) {
    asm volatile("cp.async.bulk.tensor.2d.shared::cluster.global.tile.mbarrier::complete_tx::bytes.multicast::cluster [%0], [%1, {%2, %3}], [%4], %5;"
                 :: "r"(dst), "l"(tm), "r"(c0), "r"(c1), "r"(mbar), "h"((unsigned short)7) : "memory");
}
__device__ __forceinline__ void bulk_s2s(uint32_t dst, uint32_t src, uint32_t bytes, uint32_t mbar) {
    asm volatile("cp.async.bulk.shared::cluster.shared::cta.mbarrier::complete_tx::bytes [%0], [%1], %2, [%3];"
                 :: "r"(dst), "r"(src), "r"(bytes), "r"(mbar) : "memory");
}
__device__ __forceinline__ void wgmma_n40_ss(float (&d)[20], uint64_t adesc, uint64_t bdesc, int scale_d) {
    asm volatile("{\n.reg .pred p;\nsetp.ne.b32 p, %22, 0;\n"
                 "wgmma.mma_async.sync.aligned.m64n40k16.f32.bf16.bf16 {%0,%1,%2,%3,%4,%5,%6,%7,%8,%9,%10,%11,%12,%13,%14,%15,%16,%17,%18,%19}, %20, %21, p, 1, 1, 1, 1;\n}"
                 : "+f"(d[0]), "+f"(d[1]), "+f"(d[2]), "+f"(d[3]), "+f"(d[4]), "+f"(d[5]), "+f"(d[6]), "+f"(d[7]),
                   "+f"(d[8]), "+f"(d[9]), "+f"(d[10]), "+f"(d[11]), "+f"(d[12]), "+f"(d[13]), "+f"(d[14]), "+f"(d[15]),
                   "+f"(d[16]), "+f"(d[17]), "+f"(d[18]), "+f"(d[19])
                 : "l"(adesc), "l"(bdesc), "r"(scale_d));
}
__device__ __forceinline__ void wgmma_n64_z(float (&d)[32], const uint32_t (&a)[4], uint64_t bdesc) {
    asm volatile("{\n.reg .pred p;\nsetp.ne.b32 p, 0, 0;\n"
                 "wgmma.mma_async.sync.aligned.m64n64k16.f32.bf16.bf16 {%0,%1,%2,%3,%4,%5,%6,%7,%8,%9,%10,%11,%12,%13,%14,%15,%16,%17,%18,%19,%20,%21,%22,%23,%24,%25,%26,%27,%28,%29,%30,%31}, {%32,%33,%34,%35}, %36, p, 1, 1, 0;\n}"
                 : "=f"(d[0]), "=f"(d[1]), "=f"(d[2]), "=f"(d[3]), "=f"(d[4]), "=f"(d[5]), "=f"(d[6]), "=f"(d[7]),
                   "=f"(d[8]), "=f"(d[9]), "=f"(d[10]), "=f"(d[11]), "=f"(d[12]), "=f"(d[13]), "=f"(d[14]), "=f"(d[15]),
                   "=f"(d[16]), "=f"(d[17]), "=f"(d[18]), "=f"(d[19]), "=f"(d[20]), "=f"(d[21]), "=f"(d[22]), "=f"(d[23]),
                   "=f"(d[24]), "=f"(d[25]), "=f"(d[26]), "=f"(d[27]), "=f"(d[28]), "=f"(d[29]), "=f"(d[30]), "=f"(d[31])
                 : "r"(a[0]), "r"(a[1]), "r"(a[2]), "r"(a[3]), "l"(bdesc));
}
__device__ __forceinline__ void wgmma_n64(float (&d)[32], const uint32_t (&a)[4], uint64_t bdesc, int scale_d) {
    asm volatile("{\n.reg .pred p;\nsetp.ne.b32 p, %37, 0;\n"
                 "wgmma.mma_async.sync.aligned.m64n64k16.f32.bf16.bf16 {%0,%1,%2,%3,%4,%5,%6,%7,%8,%9,%10,%11,%12,%13,%14,%15,%16,%17,%18,%19,%20,%21,%22,%23,%24,%25,%26,%27,%28,%29,%30,%31}, {%32,%33,%34,%35}, %36, p, 1, 1, 0;\n}"
                 : "+f"(d[0]), "+f"(d[1]), "+f"(d[2]), "+f"(d[3]), "+f"(d[4]), "+f"(d[5]), "+f"(d[6]), "+f"(d[7]),
                   "+f"(d[8]), "+f"(d[9]), "+f"(d[10]), "+f"(d[11]), "+f"(d[12]), "+f"(d[13]), "+f"(d[14]), "+f"(d[15]),
                   "+f"(d[16]), "+f"(d[17]), "+f"(d[18]), "+f"(d[19]), "+f"(d[20]), "+f"(d[21]), "+f"(d[22]), "+f"(d[23]),
                   "+f"(d[24]), "+f"(d[25]), "+f"(d[26]), "+f"(d[27]), "+f"(d[28]), "+f"(d[29]), "+f"(d[30]), "+f"(d[31])
                 : "r"(a[0]), "r"(a[1]), "r"(a[2]), "r"(a[3]), "l"(bdesc), "r"(scale_d));
}

constexpr int SB_FULL = 0, SB_EMPTY = 64, SB_QKF = 128, SB_VF = 144, SB_QKE = 160, SB_VE = 176, SB_OF = 192, SB_WO = 208  , SB_TICK = 216, SB_SEEN = 224, SB_FI = 232, SB_REQ = 240;
constexpr int AT_0 = 256, AT_ST = 10240 + 2 * 9216;
constexpr int FS_A = 58368;
constexpr int FS_P = FS_A + 131072;
constexpr int FS_I = FS_P + 16384;
constexpr int FS_O = FS_I + 12288;
constexpr int FS_Z = FS_O + 12288, FS_G = AT_0 + 2 * AT_ST;
constexpr int SIDE_SMEM = FS_Z + 2048;
static_assert(SIDE_SMEM <= 232448 && FS_G + 128 <= FS_A && FS_A + SD_SMEM <= SIDE_SMEM, "smem");

__device__ __forceinline__ void wg_wait1() { asm volatile("wgmma.wait_group.sync.aligned 1;" ::: "memory"); }
__device__ __forceinline__ void mbar_arrive(uint32_t bar) { asm volatile("mbarrier.arrive.shared::cta.b64 _, [%0];" :: "r"(bar) : "memory"); }
__device__ __forceinline__ void wait_cnt_rlx(const unsigned* p, unsigned target, bool urgent) {
    unsigned it = 0, v;
    while (true) {
        asm volatile("ld.relaxed.gpu.global.u32 %0, [%1];" : "=r"(v) : "l"(p) : "memory");
        if ((int)(v - target) >= 0 || ++it >= SPIN_LIMIT) break;
        if (!urgent) __nanosleep(RLX_SLEEP);
    }
}

__device__ __forceinline__ float xrow_softmax(float (&sc)[20], uint32_t (&p)[5], int wq, int lane) {
    constexpr float EC = (float)(1.4426950408889634 * 0.08838834764831845);
    const int lim = 8 * wq + (lane >> 2) - 2 * (lane & 3);
    float mx = fmaxf(sc[0], sc[1]);
#pragma unroll
    for (int j = 1; j < 5; j++) {
        sc[4 * j] = 8 * j - 8 > lim ? -INFINITY : sc[4 * j];
        sc[4 * j + 1] = 8 * j - 7 > lim ? -INFINITY : sc[4 * j + 1];
    }
    mx = fmaxf(fmaxf(mx, fmaxf(fmaxf(sc[4], sc[5]), fmaxf(sc[8], sc[9]))), fmaxf(fmaxf(sc[12], sc[13]), fmaxf(sc[16], sc[17])));
    {
        const float m1 = __shfl_xor_sync(0xffffffffu, mx, 1), m2 = __shfl_xor_sync(0xffffffffu, mx, 2), m3 = __shfl_xor_sync(0xffffffffu, mx, 3);
        mx = fmaxf(fmaxf(mx, m1), fmaxf(m2, m3));
    }
    float sum = 0.f;
#pragma unroll
    for (int j = 0; j < 5; j++) {
        float e0, e1;
        asm("ex2.approx.ftz.f32 %0, %1;" : "=f"(e0) : "f"((sc[4 * j] - mx) * EC));
        asm("ex2.approx.ftz.f32 %0, %1;" : "=f"(e1) : "f"((sc[4 * j + 1] - mx) * EC));
        p[j] = pack_bf16(e0, e1);
        sum += e0 + e1;
    }
    return sum;
}
__device__ __forceinline__ float xrow_inv(float sum) {
    sum += __shfl_xor_sync(0xffffffffu, sum, 1);
    sum += __shfl_xor_sync(0xffffffffu, sum, 2);
    float r;
    asm("rcp.approx.ftz.f32 %0, %1;" : "=f"(r) : "f"(sum));
    return r;
}

__device__ __forceinline__ void stsm_x4(uint32_t addr, uint32_t r0, uint32_t r1, uint32_t r2, uint32_t r3) {
    asm volatile("stmatrix.sync.aligned.m8n8.x4.shared.b16 [%0], {%1,%2,%3,%4};" :: "r"(addr), "r"(r0), "r"(r1), "r"(r2), "r"(r3) : "memory");
}
__device__ __forceinline__ void xrow_pv(uint32_t (&ob)[16], const uint32_t (&p)[5], float psum, uint32_t vt) {
    float o[32];
    const uint64_t dv = smem_desc(vt, 2048, 128);
    uint32_t pa[6][4];
#pragma unroll
    for (int i = 0; i < 6; i++) {
        const int ks = i >> 1, hf = i & 1;
        pa[i][hf] = p[2 * ks]; pa[i][hf ^ 1] = 0u;
        pa[i][2 + hf] = ks < 2 ? p[ks < 2 ? 2 * ks + 1 : 0] : 0u; pa[i][3 - hf] = 0u;
    }
    wg_fence();
#pragma unroll
    for (int i = 0; i < 6; i++) { if (i == 0) wgmma_n64_z(o, pa[0], dv); else wgmma_n64(o, pa[i], dv + (uint64_t)((i & 1) * 64 + (i >> 1) * 256), 1); }
    wg_commit();
    const float inv = xrow_inv(psum);
    wg_wait0();
#pragma unroll
    for (int i = 0; i < 8; i++) { ob[i] = pack_bf16(o[4 * i] * inv, o[4 * i + 1] * inv); ob[8 + i] = pack_bf16(o[4 * i + 2] * inv, o[4 * i + 3] * inv); }
}
__device__ __forceinline__ uint32_t h2_to_bf2(uint32_t h) {
    uint32_t r;
    asm("{\n.reg .f16 l, h;\n.reg .f32 a, b;\nmov.b32 {l, h}, %1;\ncvt.f32.f16 a, l;\ncvt.f32.f16 b, h;\ncvt.rn.bf16x2.f32 %0, b, a;\n}" : "=r"(r) : "r"(h));
    return r;
}
__device__ __forceinline__ uint32_t max_abs2(uint32_t a, uint32_t b) { uint32_t r; asm("max.NaN.xorsign.abs.bf16x2 %0, %1, %2;" : "=r"(r) : "r"(a), "r"(b)); return r; }
__device__ __forceinline__ uint32_t movm(uint32_t v) {
    uint32_t r; asm volatile("movmatrix.sync.aligned.m8n8.trans.b16 %0, %1;" : "=r"(r) : "r"(v)); return r;
}
__device__ __forceinline__ void bar_arrive(int id, int n) { asm volatile("bar.arrive %0, %1;" :: "r"(id), "r"(n) : "memory"); }
__device__ __forceinline__ void lds64(uint32_t& a, uint32_t& b, uint32_t addr) {
    asm volatile("ld.shared.v2.u32 {%0,%1}, [%2];" : "=r"(a), "=r"(b) : "r"(addr) : "memory");
}
__device__ __forceinline__ void lds64f(float& a, float& b, uint32_t addr) {
    asm volatile("ld.shared.v2.f32 {%0,%1}, [%2];" : "=f"(a), "=f"(b) : "r"(addr) : "memory");
}
__device__ __forceinline__ void st_async64(uint32_t addr, uint32_t a, uint32_t b, uint32_t mbar) {
    asm volatile("st.async.weak.shared::cluster.mbarrier::complete_tx::bytes.v2.b32 [%0], {%1,%2}, [%3];" :: "r"(addr), "r"(a), "r"(b), "r"(mbar) : "memory");
}
__device__ __forceinline__ void mma_z(float (&d)[4], const uint32_t (&a)[4], uint32_t b0, uint32_t b1) {
    asm volatile("mma.sync.aligned.m16n8k16.row.col.f32.bf16.bf16.f32 {%0,%1,%2,%3}, {%4,%5,%6,%7}, {%8,%9}, {%10,%10,%10,%10};"
                 : "=f"(d[0]), "=f"(d[1]), "=f"(d[2]), "=f"(d[3])
                 : "r"(a[0]), "r"(a[1]), "r"(a[2]), "r"(a[3]), "r"(b0), "r"(b1), "f"(0.f));
}
__device__ __forceinline__ void mma_k8(float (&d)[4], uint32_t a0, uint32_t a1, uint32_t b) {
    asm volatile("mma.sync.aligned.m16n8k8.row.col.f32.bf16.bf16.f32 {%0,%1,%2,%3}, {%4,%5}, {%6}, {%0,%1,%2,%3};"
                 : "+f"(d[0]), "+f"(d[1]), "+f"(d[2]), "+f"(d[3]) : "r"(a0), "r"(a1), "r"(b));
}
__global__ void __launch_bounds__(512, 1) k_side(const __grid_constant__ CUtensorMap tmo, const bf16* __restrict__ x, const bf16* __restrict__ logA, const bf16* __restrict__ Aim,
                                                 const bf16* __restrict__ Cre, const bf16* __restrict__ Cim, const bf16* __restrict__ logdt,
                                                 const bf16* __restrict__ Wo, const bf16* __restrict__ dskip, const bf16* __restrict__ gw,
                                                 bf16* __restrict__ out) {
    extern __shared__ __align__(1024) unsigned char smem_raw[];
    const uint32_t sbase = smem_u32(smem_raw);
    const int tid = threadIdx.x, warp = __shfl_sync(0xffffffffu, tid >> 5, 0), lane = tid & 31, cta = blockIdx.x;
    const int cb = cta >> 2, kq = cta & 3;
    if (tid == 0) {
        for (int i = 0; i < 8; i++) { mbar_init(sbase + SB_FULL + 8 * i, 1); mbar_init(sbase + SB_EMPTY + 8 * i, 4); }
        for (int i = 0; i < 2; i++) {
            mbar_init(sbase + SB_QKF + 8 * i, 1); mbar_init(sbase + SB_VF + 8 * i, 1); mbar_init(sbase + SB_QKE + 8 * i, 4);
            mbar_init(sbase + SB_VE + 8 * i, 1); mbar_init(sbase + SB_OF + 8 * i, 4);
        }
        mbar_init(sbase + SB_WO, 1);
        mbar_init(sbase + SB_WO + 40, 1);
        mbar_init(sbase + SB_FI, 1);
        mbar_init(sbase + SB_REQ, 4);
        *reinterpret_cast<uint2*>(smem_raw + SB_TICK) = make_uint2(0u, 0u);
        *reinterpret_cast<uint32_t*>(smem_raw + SB_SEEN) = 0u;
        asm volatile("fence.mbarrier_init.release.cluster;" ::: "memory");
    }
    TS3(0);
    asm volatile("fence.proxy.async;" ::: "memory");
    __syncthreads();
    auto epoch = []() {
        unsigned ep;
        asm volatile("ld.volatile.global.u32 %0, [%1];" : "=r"(ep) : "l"(&g_epoch) : "memory");
        return ep + 1u;
    };
    if (warp >= 12) {
      asm volatile("setmaxnreg.dec.sync.aligned.u32 40;");
      {
        uint32_t gwv[9];
#pragma unroll
        for (int i = 0; i < 9; i++) gwv[i] = reinterpret_cast<const uint32_t*>(gw)[lane + 32 * i];
#pragma unroll 1
        for (int i = 0; i < 8; i++) {
            uint32_t xv[2][9];
            float sm[2];
#pragma unroll
            for (int j = 0; j < 2; j++) {
                const int t = min(cta * 57 + 8 * i + 4 * j + warp - 12, S_LEN - 1);
#pragma unroll
                for (int k = 0; k < 9; k++) xv[j][k] = reinterpret_cast<const uint32_t*>(x + t * DM)[lane + 32 * k];
            }
#pragma unroll
            for (int j = 0; j < 2; j++) {
                sm[j] = 0.f;
#pragma unroll
                for (int k = 0; k < 9; k++) {
                    const uint32_t pr = bf2_mul(xv[j][k], gwv[k]);
                    sm[j] += __uint_as_float(pr << 16) + __uint_as_float(pr & 0xffff0000u);
                }
            }
            float v = (lane < 16 ? sm[0] : sm[1]) + __shfl_xor_sync(0xffffffffu, lane < 16 ? sm[1] : sm[0], 16);
#pragma unroll
            for (int o = 8; o; o >>= 1) v += __shfl_xor_sync(0xffffffffu, v, o);
            const float gv = 1.f / (1.f + expf(-bf16r(v)));
            const int tt = 8 * i + 4 * (lane >> 4) + warp - 12;
            if ((lane & 15) == 0 && tt < 57 && cta * 57 + tt < S_LEN) g_gate[cta * 57 + tt] = __float2bfloat16_rn(gv);
        }
        named_bar(2, 128);
        if (tid == 480) {
            __threadfence();
            asm volatile("red.relaxed.gpu.global.add.u32 [%0], 1;" :: "l"(&g_gcnt[0]) : "memory");
        }
        __syncwarp();
      }
      const unsigned ep = epoch();
      if (warp == 12 || warp == 15) {
        const int pi = warp == 12 ? 0 : 1;
        auto stage_wo = [&](int i0, int i1) {
            if (lane == 0) {
                fence_async();
#pragma unroll 1
                for (int i = i0; i < i1; i++) {
                    gate(sbase + SB_TICK);
                    tma_2d(sbase + FS_A + i * 16384, &tmo, cb * 64, kq * 1024 + i * 128, sbase + SB_WO + (i >> 2) * 40);
                    if (WO_SLEEP > 0) __nanosleep(WO_SLEEP);
                }
            }
            __syncwarp();
        };
        if (lane == 0) mbar_expect(sbase + SB_WO + pi * 40, 65536);
        if (pi == 0) {
            named_bar(11, 288);
            stage_wo(0, 2);
        }
        named_bar(3, 320);
        if (pi == 0) stage_wo(2, 4);
        else {
            if (WO_LAG > 0) __nanosleep(WO_LAG);
            stage_wo(4, 8);
        }
        if (lane == 0) TSS(17, 2 + pi);
        if (tid == 480) {
            __threadfence();
            asm volatile("red.relaxed.gpu.global.add.u32 [%0], 1;" :: "l"(&g_gcnt[32]) : "memory");
        }
        __syncwarp();
        named_bar(12 + pi, 160);
        if (lane == 0) {
            const int kb = 2 * kq + pi;
            fence_async();
            for (int pr = 0; pr < NSEG / 2; pr++) {
                const bool gon = pr < NSEG / 2 - UNGATE_G;
                wait_cnt_rlx(&g_prog[kb * 64 + pr], 8u * ep, pr >= NSEG / 2 - 2);
                if (pi == 0) asm volatile("st.volatile.shared.u32 [%0], %1;" :: "r"(sbase + SB_SEEN), "r"(pr + 1) : "memory");
                if (pr >= 30 && pi == 0) TSS(4 + pr - 30, 0);
                if (pr == 31) TS3P(26);
                if (pr == 30) TS3P(1);
#pragma unroll
                for (int j = 0; j < 4; j++) {
                    const int st = 4 * pi + j;
                    mbar_wait_long(sbase + SB_EMPTY + 8 * st, ((uint32_t)pr & 1u) ^ 1u);
                    mbar_expect(sbase + SB_FULL + 8 * st, 16384);
                    if (gon) gate(sbase + SB_TICK);
                    bulk_g2s(sbase + FS_A + st * 16384, g_ox + ((size_t)(pr * NH + 4 * kb + j)) * 8192, 16384, sbase + SB_FULL + 8 * st);
                }
            }
        }
        __syncwarp();
      } else if (warp == 13) {
        if (lane == 0) {
            const uint64_t pol = policy_evict_first();
            bool next_ok = false;
            for (int seg = 0; seg < NATT; seg++) {
                const uint32_t st = seg & 1, ph = (uint32_t)(seg >> 1) & 1u, ab = sbase + AT_0 + st * AT_ST;
                if (!next_ok) {
                    const unsigned* fp = &g_flag[(cta & (NH - 1)) * NSEG + seg];
                    unsigned it = 0, v0, v1;
                    while (true) {
                        asm volatile("ld.relaxed.gpu.global.u32 %0, [%1];" : "=r"(v0) : "l"(fp) : "memory");
                        asm volatile("ld.relaxed.gpu.global.u32 %0, [%1+4];" : "=r"(v1) : "l"(fp) : "memory");
                        read_tick(sbase + SB_TICK);
                        if ((int)(v0 - 3u * ep) >= 0 || ++it >= SPIN_LIMIT) break;
                        if (seg < NSEG - UNGATE || cta >= NH) __nanosleep(RLX_SLEEP);
                    }
                    next_ok = (int)(v1 - 3u * ep) >= 0;
                } else next_ok = false;
                if (cta < NH) {
                    TSA(seg, 0);
                    mbar_wait_long(sbase + SB_QKE + 8 * st, ph ^ 1u);
                    TSA(seg, 1);
                    mbar_expect(sbase + SB_QKF + 8 * st, 2 * 9216);
                    if (seg < NSEG - UNGATE) gate(sbase + SB_TICK, GL_A, GL_B);
                    TSA(seg, 2);
                    bulk_g2s_h(ab + 10240, &g_qkv[seg][cta][0][1024], 9216, sbase + SB_QKF + 8 * st, pol);
                    bulk_g2s_h(ab + 10240 + 9216, &g_qkv[seg][cta][1][1024], 9216, sbase + SB_QKF + 8 * st, pol);
                    mbar_wait_long(sbase + SB_VE + 8 * st, ph ^ 1u);
                    mbar_expect(sbase + SB_VF + 8 * st, 10240);
                    if (seg < NSEG - UNGATE) gate(sbase + SB_TICK, GL_A, GL_B);
                    TSA(seg, 3);
                    bulk_g2s_h(ab, &g_qkv[seg][cta][2][0], 10240, sbase + SB_VF + 8 * st, pol);
                }
            }
        }
        __syncwarp();
      } else if (warp == 14) {
        if (lane == 0) {
            int seg = cta < NH ? 0 : NATT, p = 0;
            unsigned it = 0;
            while ((seg < NATT || p < NSEG / 2 - 1) && ++it < 16 * SPIN_LIMIT) {
                if (p < NSEG / 2 - 1 && mbar_test(sbase + SB_REQ, (uint32_t)p & 1u)) {
                    if (p == 0) { wait_cnt(&g_gcnt[32], SD_NCTA * ep); asm volatile("fence.proxy.async;" ::: "memory"); }
                    mbar_expect(sbase + SB_FI, (p < NSEG / 2 - 2 ? 12288 : 2048 + 32) + 2048 + 32);
                    if (p < NSEG / 2 - UNGATE_G - 1) gate(sbase + SB_TICK);
                    if (p < NSEG / 2 - 2) bulk_g2s(sbase + FS_I, &g_fp[p & 7][cta][0][0], 12288, sbase + SB_FI);
                    else {
                        bulk_g2s(sbase + FS_I, g_y + ((p * 4 + 4 + kq) * DM + cb * 64) * 16, 2048, sbase + SB_FI);
                        bulk_g2s(sbase + FS_G + 32, g_gate + p * 64 + 64 + kq * 16, 32, sbase + SB_FI);
                    }
                    bulk_g2s(sbase + FS_Z, g_y + ((p * 4 + kq) * DM + cb * 64) * 16, 2048, sbase + SB_FI);
                    bulk_g2s(sbase + FS_G, g_gate + p * 64 + kq * 16, 32, sbase + SB_FI);
                    p++;
                } else if (seg < NATT && mbar_test(sbase + SB_OF + 8 * (seg & 1), (uint32_t)(seg >> 1) & 1u)) {
                    const uint32_t st = seg & 1, ab = sbase + AT_0 + st * AT_ST;
                    TSA(seg, 5);
                    if (seg < NSEG - UNGATE) gate(sbase + SB_TICK, GS_A, GS_B);
                    TSA(seg, 6);
                    unsigned char* dst = reinterpret_cast<unsigned char*>(g_ox) + ((size_t)((seg >> 1) * NH + cta)) * 16384 + (seg & 1) * 8192;
                    asm volatile("cp.async.bulk.global.shared::cta.bulk_group [%0], [%1], 8192;" :: "l"(dst), "r"(ab) : "memory");
                    asm volatile("cp.async.bulk.commit_group;" ::: "memory");
                    asm volatile("cp.async.bulk.wait_group.read 0;" ::: "memory");
                    mbar_arrive(sbase + SB_VE + 8 * st);
                    asm volatile("cp.async.bulk.wait_group 0;" ::: "memory");
                    asm volatile("red.relaxed.gpu.global.add.u32 [%0], 1;" :: "l"(&g_prog[(cta >> 2) * 64 + (seg >> 1)]) : "memory");
                    TSA(seg, 7);
                    seg++;
                } else if (seg < NSEG - UNGATE) __nanosleep(W14_SLEEP);
            }
        }
        __syncwarp();
      }
    } else if (warp >= 8) {
        asm volatile("setmaxnreg.dec.sync.aligned.u32 88;");
          s4d_stage_u(smem_raw + FS_A, x, tid - 256);
        const int wq = warp - 8;
        for (int seg = 0; seg < (cta < NH ? NATT : 0); seg++) {
            const uint32_t st = seg & 1, ph = (uint32_t)(seg >> 1) & 1u, ab = sbase + AT_0 + st * AT_ST;
            float sc[20];
            if (seg < NSEG - UNGATE) mbar_wait_long(sbase + SB_QKF + 8 * st, ph); else mbar_wait(sbase + SB_QKF + 8 * st, ph);
            if (tid == 256) TSA(seg, 4);
            {
                const uint64_t da = smem_desc(ab + 10240 + 1024, 128, 1024), db = smem_desc(ab + 10240, 128, 2048);
                wg_fence();
#pragma unroll
                for (int ks = 0; ks < 8; ks++) wgmma_n40_ss(sc, da + (uint64_t)((ks >> 2) * 576 + (ks & 3) * 16), db + (uint64_t)((ks >> 2) * 576 + (ks & 3) * 16), ks > 0);
                wg_commit();
                wg_wait0();
            }
            if (lane == 0) mbar_arrive(sbase + SB_QKE + 8 * st);
            uint32_t p[5], ob[16];
            const float psum = xrow_softmax(sc, p, wq, lane);
            mbar_wait(sbase + SB_VF + 8 * st, ph);
            xrow_pv(ob, p, psum, ab);
            named_bar(6, 128);
#pragma unroll
            for (int i = 0; i < 4; i++) stsm_x4(ab + wq * 2048 + i * 512 + lane * 16, ob[4 * i], ob[4 * i + 1], ob[4 * i + 2], ob[4 * i + 3]);
            fence_async();
            __syncwarp();
            if (lane == 0) mbar_arrive(sbase + SB_OF + 8 * st);
        }
    } else {
        asm volatile("setmaxnreg.inc.sync.aligned.u32 192;");
        const int wg = warp >> 2, wq = warp & 3;
        s4d_phase(smem_raw + FS_A, x, logA, Aim, Cre, Cim, logdt, dskip, Wo + (size_t)((2 * kq + wg) * 512) * DM + cb * 64);
        TS3(2);
        if (lane == 0) TSS(16, warp);
        named_bar(3, 320);
        if (tid == 0) TSS(17, 0);
        uint32_t wa[32][4];
        mbar_wait_long(sbase + SB_WO + wg * 40, 0);
        if (tid == 0) TSS(17, 1);
        {
            const uint32_t a = sbase + FS_A + wg * 65536 + ((lane >> 4) * 8 + (lane & 7)) * 128 + (((wq * 2 + ((lane >> 3) & 1)) ^ (lane & 7)) << 4);
#pragma unroll
            for (int ks = 0; ks < 32; ks++) ldsm_x4_t(wa[ks], a + ks * 2048);
        }
        named_bar(12 + wg, 160);
        TS3(3);
        if (tid == 0) TSS(17, 4);
        auto product = [&](float (&acc)[32], int pr, const int wg) {
                if (pr + wg > 0) named_bar(4 + wg, 256);
                const uint64_t db = smem_desc(sbase + FS_A + wg * 65536, 128, 2048);
                TSG(0);
#pragma unroll
                for (int j = 0; j < 4; j++) {
                    mbar_wait(sbase + SB_FULL + 8 * (4 * wg + j), (uint32_t)pr & 1u);
                    if (j == 0) TSG(1);
                    if (j == 3) TSG(2);
                    wg_fence();
#pragma unroll
                    for (int ks = 0; ks < 8; ks++) {
                        if ((j | ks) == 0) wgmma_n64_z(acc, wa[0], db);
                        else wgmma_n64(acc, wa[8 * j + ks], db + (uint64_t)(j * 1024 + ks * 16), 1);
                    }
                    wg_commit();
                    if (j == 3 && pr + wg < NSEG / 2) bar_arrive(4 + (wg ^ 1), 256);
                    if (j > 0) { wg_wait1(); if (lane == 0) mbar_arrive(sbase + SB_EMPTY + 8 * (4 * wg + j - 1)); }
                }
                wg_wait0();
                if (pr == 31) TS3W(27);
                TSG(3);
                if (lane == 0) mbar_arrive(sbase + SB_EMPTY + 8 * (4 * wg + 3));
        };
        if (wg == 1) {
            for (int pr = 0; pr < NSEG / 2; pr++) {
                uint32_t t16 = (uint32_t)(wq * 32 + lane) * 16u;
                asm volatile("" : "+r"(t16));
                float acc[32];
                product(acc, pr, 1);
                    uint32_t tag = ((uint32_t)(pr >> 3) & 1u) ^ 1u;
                    tag = __shfl_sync(0xffffffffu, tag, lane);
                    named_bar(8, 256);
                    unsigned char* dst = reinterpret_cast<unsigned char*>(&g_fp[pr & 7][4 * cb][2 * kq - 2][0]) + t16;
                    const uint32_t own = sbase + FS_O + (pr % 3) * 4096 + t16;
#pragma unroll
                    for (int q = 0; q < 8; q++) {
                        float4 p;
                        asm volatile("ld.shared.v4.f32 {%0,%1,%2,%3}, [%4];" : "=f"(p.x), "=f"(p.y), "=f"(p.z), "=f"(p.w) : "r"(sbase + FS_P + t16 + q * 2048) : "memory");
                        acc[4 * q] = __uint_as_float((__float_as_uint(acc[4 * q] + p.x) & ~1u) | tag); acc[4 * q + 1] = __uint_as_float((__float_as_uint(acc[4 * q + 1] + p.y) & ~1u) | tag);
                        acc[4 * q + 2] = __uint_as_float((__float_as_uint(acc[4 * q + 2] + p.z) & ~1u) | tag); acc[4 * q + 3] = __uint_as_float((__float_as_uint(acc[4 * q + 3] + p.w) & ~1u) | tag);
                    }
#pragma unroll
                    for (int q = 0; q < 8; q++) {
                        asm volatile("{\n.reg .pred p;\nsetp.ne.s32 p, %5, %6;\n@p st.volatile.global.v4.f32 [%0], {%1,%2,%3,%4};\n@!p st.shared.v4.f32 [%7], {%1,%2,%3,%4};\n}"
                                     :: "l"(dst + (q & 1) * 2048), "f"(acc[4 * q]), "f"(acc[4 * q + 1]), "f"(acc[4 * q + 2]), "f"(acc[4 * q + 3]), "r"(q >> 1), "r"(kq),
                                        "r"(own + (q & 1) * 2048) : "memory");
                        if (q & 1) dst += (q >> 1) == kq ? 12288 + 4096 : 12288;
                    }
                    bar_arrive(9, 256);
                    if (pr == 31) TS3W(28);
                TSG(4);
            }
        } else {
          int nsync = 0;
          int np = 1, nf = 0, pr = 0, pf = -1;
          while (true) {
            uint32_t t16 = (uint32_t)(wq * 32 + lane) * 16u;
            asm volatile("" : "+r"(t16));
            if (pr < 0) {
                if (nsync <= pf) { named_bar(9, 256); nsync++; }
                if (lane == 0 && pf < NSEG / 2 - 1) mbar_arrive(sbase + SB_REQ);
            } else {
                float acc[32];
                product(acc, pr, 0);
                if (nsync < pr) { named_bar(9, 256); nsync++; }
#pragma unroll
                for (int q = 0; q < 8; q++)
                    asm volatile("st.shared.v4.f32 [%0], {%1,%2,%3,%4};" :: "r"(sbase + FS_P + t16 + q * 2048), "f"(acc[4 * q]), "f"(acc[4 * q + 1]), "f"(acc[4 * q + 2]), "f"(acc[4 * q + 3]) : "memory");
                bar_arrive(8, 256);
                TSG(4);
            }
            uint32_t w[4] = {0u, 0u, 0u, 0u};
            const int pc = pf;
            if (pf >= 0) {
                const uint32_t tag = ((uint32_t)(pf >> 3) & 1u) ^ 1u;
                uint4 v[8];
                unsigned n = 0;
                const bool last = pf == NSEG / 2 - 1;
                const uint4* src = reinterpret_cast<const uint4*>(reinterpret_cast<const unsigned char*>(&g_fp[pf & 7][cta][0][0]) + t16);
                if (pf >= NSEG / 2 - 2) {
#pragma unroll
                    for (int r = 0; r < 6; r++) v[r] = ld_vol_u4(src + r * 128);
                    mbar_wait(sbase + SB_FI, 0u);
                } else {
                    mbar_wait(sbase + SB_FI, (uint32_t)pf & 1u);
#pragma unroll
                    for (int r = 0; r < 6; r++)
                        asm volatile("ld.shared.v4.u32 {%0,%1,%2,%3}, [%4];" : "=r"(v[r].x), "=r"(v[r].y), "=r"(v[r].z), "=r"(v[r].w) : "r"(sbase + t16 + FS_I + r * 2048) : "memory");
                }
                while (true) {
                    uint32_t any = 0u;
#pragma unroll
                    for (int r = 0; r < 6; r++) {
                        uint32_t c0_, c1_;
                        asm("lop3.b32 %0, %1, %2, %3, 0x7e;" : "=r"(c0_) : "r"(v[r].x), "r"(v[r].y), "r"(tag));
                        asm("lop3.b32 %0, %1, %2, %3, 0x7e;" : "=r"(c1_) : "r"(v[r].z), "r"(v[r].w), "r"(tag));
                        asm("lop3.b32 %0, %1, %2, %3, 0xfe;" : "=r"(any) : "r"(any), "r"(c0_), "r"(c1_));
                    }
                    if (!__any_sync(0xffffffffu, (any & 1u) != 0u) || ++n >= SPIN_LIMIT) break;
                    if (pf < NSEG / 2 - 2) __nanosleep(200);
#pragma unroll
                    for (int r = 0; r < 6; r++) v[r] = ld_vol_u4(src + r * 128);
                }
                if (pf == 31) TS3(29);
                TSG(5);
#pragma unroll
                for (int r = 6; r < 8; r++)
                    asm volatile("ld.shared.v4.u32 {%0,%1,%2,%3}, [%4];" : "=r"(v[r].x), "=r"(v[r].y), "=r"(v[r].z), "=r"(v[r].w)
                                 : "r"(sbase + t16 + FS_O + (pf % 3) * 4096 + (r - 6) * 2048) : "memory");
                uint32_t zv[4], gg[2];
                ldsm_x4_t(zv, sbase + (last ? FS_I : FS_Z) + (wq * 16 + (lane & 15)) * 32 + (lane >> 4) * 16);
#pragma unroll
                for (int k = 0; k < 2; k++) gg[k] = __byte_perm(*reinterpret_cast<const volatile unsigned short*>(smem_raw + FS_G + (last ? 32 : 0) + k * 16 + (lane >> 2) * 2), 0u, 0x1010);
#define PQS(k, f) (((__uint_as_float(v[k].f) + __uint_as_float(v[2 + k].f)) + __uint_as_float(v[4 + k].f)) + __uint_as_float(v[6 + k].f))
#pragma unroll
                for (int k = 0; k < 2; k++) {
                    w[2 * k] = bf2_add(bf2_mul(gg[k], movm(pack_bf16(PQS(k, x), PQS(k, y)))), zv[2 * k]);
                    w[2 * k + 1] = bf2_add(bf2_mul(gg[k], movm(pack_bf16(PQS(k, z), PQS(k, w)))), zv[2 * k + 1]);
                }
#undef PQS
            }
            const bool more = nf < NSEG / 2;
            if (more) {
                uint32_t r;
                asm volatile("{\n.reg .pred p, q;\n.reg .b32 v;\nld.volatile.shared.u32 v, [%1];\nsetp.gt.s32 p, v, %2;\nbar.red.or.pred q, 10, 128, p;\nselp.u32 %0, 1, 0, q;\n}"
                             : "=r"(r) : "r"(sbase + SB_SEEN), "r"(np) : "memory");
                const bool dop = np < NSEG / 2 && (__shfl_sync(0xffffffffu, r, 0) != 0u || nf == np || (np >= TM && nf + 1 >= np));
                TSG(6);
                pr = dop ? np++ : -1;
                pf = !dop || nf + (pr >= TM2 ? 1 : 2) <= pr ? nf++ : -1;
                if (dop && pf >= 0 && lane == 0) mbar_arrive(sbase + SB_REQ);
            }
            if (pc >= 0) {
                unsigned char* op = reinterpret_cast<unsigned char*>(out) + (uint32_t)((pc * 64 + kq * 16 + (lane >> 2)) * DM + cb * 64 + wq * 16 + 2 * (lane & 3)) * 2u;
#pragma unroll
                for (int k = 0; k < 4; k++) *reinterpret_cast<uint32_t*>(op + (k >> 1) * (16 * DM) + (k & 1) * 16) = w[k];
                if ((pc & 1) == 0) TS3(4 + pc / 2);
                if (pc == 31) TS3(25);
            }
            if (!more) break;
          }
        }
        if (cta == 0 && tid == 0) asm volatile("red.relaxed.gpu.global.add.u32 [%0], 1;" :: "l"(&g_epoch) : "memory");
    }
    asm volatile("griddepcontrol.wait;" ::: "memory");
}

template <class F>
__device__ __forceinline__ uint32_t poll_mem(const uint4* src, uint32_t dst, uint32_t t0, F next) {
    uint4 v[6];
    unsigned it = 0;
#pragma unroll
    for (int j = 0; j < 6; j++) v[j] = make_uint4(0u, 0u, 0u, 0u);
    while (clock32() - t0 < POLL_DELAY) {}
    FS(12, 0);
    bool more;
#pragma unroll 1
    do {
        asm volatile("{\n.reg .pred p<6>;\n"
                     "setp.ne.u32 p0, %3, 0x5000;\nsetp.ne.u32 p1, %7, 0x5000;\nsetp.ne.u32 p2, %11, 0x5000;\n"
                     "setp.ne.u32 p3, %15, 0x5000;\nsetp.ne.u32 p4, %19, 0x5000;\nsetp.ne.u32 p5, %23, 0x5000;\n"
                     "@p0 ld.volatile.global.v4.u32 {%0,%1,%2,%3}, [%24];\n@p1 ld.volatile.global.v4.u32 {%4,%5,%6,%7}, [%24+4096];\n"
                     "@p2 ld.volatile.global.v4.u32 {%8,%9,%10,%11}, [%24+8192];\n@p3 ld.volatile.global.v4.u32 {%12,%13,%14,%15}, [%24+12288];\n"
                     "@p4 ld.volatile.global.v4.u32 {%16,%17,%18,%19}, [%24+16384];\n@p5 ld.volatile.global.v4.u32 {%20,%21,%22,%23}, [%24+20480];\n}"
                     : "+r"(v[0].x), "+r"(v[0].y), "+r"(v[0].z), "+r"(v[0].w), "+r"(v[1].x), "+r"(v[1].y), "+r"(v[1].z), "+r"(v[1].w),
                       "+r"(v[2].x), "+r"(v[2].y), "+r"(v[2].z), "+r"(v[2].w), "+r"(v[3].x), "+r"(v[3].y), "+r"(v[3].z), "+r"(v[3].w),
                       "+r"(v[4].x), "+r"(v[4].y), "+r"(v[4].z), "+r"(v[4].w), "+r"(v[5].x), "+r"(v[5].y), "+r"(v[5].z), "+r"(v[5].w)
                     : "l"(src) : "memory");
        stsm_x4(dst, h2_to_bf2(v[0].x), h2_to_bf2(v[0].y), h2_to_bf2(v[0].z), h2_to_bf2(v[1].x));
        stsm_x4(dst + 512, h2_to_bf2(v[1].y), h2_to_bf2(v[1].z), h2_to_bf2(v[2].x), h2_to_bf2(v[2].y));
        const uint32_t all = ((v[0].w & v[1].w) & (v[2].w & v[3].w)) & (v[4].w & v[5].w);
        more = __any_sync(0xffffffffu, (all & 0x5000u) != 0x5000u && ++it < SPIN_LIMIT);
        stsm_x4(dst + 1024, h2_to_bf2(v[2].z), h2_to_bf2(v[3].x), h2_to_bf2(v[3].y), h2_to_bf2(v[3].z));
        asm volatile("stmatrix.sync.aligned.m8n8.x2.shared.b16 [%0], {%1,%2};" :: "r"(dst + 1536), "r"(h2_to_bf2(v[4].x)), "r"(h2_to_bf2(v[4].y)) : "memory");
        stsm_x4(dst + 1792, h2_to_bf2(v[4].z), h2_to_bf2(v[5].x), h2_to_bf2(v[5].y), h2_to_bf2(v[5].z));
        asm volatile("{\n.reg .pred p;\nsetp.eq.u32 p, %0, 0;\n@p bar.sync 1, 384;\n}" :: "r"((uint32_t)more) : "memory");
    } while (more);
    next();
    FS(13, it);
    FS(14, 0);
    uint32_t m = v[0].x, m1 = v[0].y, m2 = v[0].z;
#pragma unroll
    for (int j = 1; j < 6; j++) {
        asm volatile("max.NaN.xorsign.abs.f16x2 %0, %0, %1;" : "+r"(m) : "r"(v[j].x));
        asm volatile("max.NaN.xorsign.abs.f16x2 %0, %0, %1;" : "+r"(m1) : "r"(v[j].y));
        asm volatile("max.NaN.xorsign.abs.f16x2 %0, %0, %1;" : "+r"(m2) : "r"(v[j].z));
    }
    asm volatile("max.NaN.xorsign.abs.f16x2 %0, %0, %1;" : "+r"(m) : "r"(m1));
    asm volatile("max.NaN.xorsign.abs.f16x2 %0, %0, %1;" : "+r"(m) : "r"(m2));
    return h2_to_bf2(m) & 0x7fff7fffu;
}

template <int N> __device__ __forceinline__ void pad_code() {
#pragma unroll
    for (int i = 0; i < N; i++) asm volatile("pmevent 7;" ::: "memory");
}
template <bool V> struct Flag { static constexpr bool value = V; };
__device__ __forceinline__ void score_group(const uint32_t (&a)[2][4], const uint32_t (&kf)[2][4], uint32_t d0, uint32_t d1, uint32_t m1, uint32_t d2, uint32_t m2) {
    FS(4, a[1][0]);
    float sc[4][4];
    mma_z(sc[0], a[0], kf[0][0], kf[0][1]);
    mma_z(sc[1], a[0], kf[0][2], kf[0][3]);
    mma_z(sc[2], a[1], kf[1][0], kf[1][1]);
    mma_z(sc[3], a[1], kf[1][2], kf[1][3]);
    constexpr float EC = (float)(1.4426950408889634 * 0.08838834764831845);
    const uint32_t v0 = __float_as_uint(fmaf(sc[3][2], EC, fmaf(sc[2][0], EC, (sc[0][0] + sc[1][2]) * EC))), v1 = __float_as_uint(fmaf(sc[3][3], EC, fmaf(sc[2][1], EC, (sc[0][1] + sc[1][3]) * EC)));
    FS(5, v0);
    const uint32_t pk = pack_bf16(__uint_as_float(v0), __uint_as_float(v1));
    st_async32(d1, pk, m1);
    st_async32(d2, pk, m2);
    asm volatile("st.shared.v2.u32 [%0], {%1,%2};" :: "r"(d0), "r"(v0), "r"(v1) : "memory");
}
__device__ __forceinline__ void store_tile(int s, int h, int role, uint32_t tile, uint32_t b0, uint32_t b1) {
    asm volatile("cp.async.bulk.global.shared::cta.bulk_group.L2::cache_hint [%0], [%1], %2, %3;"
                 :: "l"(&g_qkv[s][h][role][b0]), "r"(tile + b0), "r"(b1 - b0), "l"(policy_evict_first()) : "memory");
}
__device__ __forceinline__ uint32_t w_addr(uint32_t sbase, int warp, int lane) {
    return sbase + SM_WS + (warp >> 2) * 8192 + ((lane & 7) + ((lane >> 4) & 1) * 8) * 128 + ((((warp & 3) * 2 + ((lane >> 3) & 1)) ^ (lane & 7)) << 4);
}
__device__ __forceinline__ void vx_copy(uint32_t sbase, int j, int r) {
    bulk_s2s(mapa(sbase + SM_VX + (j & 1) * 8192, r), sbase + SM_T + (j & 3) * TBUF + DH * 16, 8192, mapa(sbase + B_VX + 8 * (j & 1), r));
}
__device__ __forceinline__ float to_scale(float bound) {
    int e = 141 - (int)((__float_as_uint(bound) >> 23) & 255u);
    e = e > 100 ? 100 : e;
    return __uint_as_float((uint32_t)(127 + e) << 23);
}
__device__ __forceinline__ void norms_gather(int lane, uint32_t sbase) {
    uint2 v[3];
    uint4 w[2];
    unsigned it = 0;
#pragma unroll
    for (int i = 0; i < 3; i++) v[i] = make_uint2(0u, 0u);
    w[0] = w[1] = make_uint4(0u, 0u, 0u, 0u);
    bool more;
    do {
#pragma unroll
        for (int i = 0; i < 3; i++) if ((v[i].x & 1u) == 0u) v[i] = ld_vol_u2(&g_norm[3 * lane + i]);
#pragma unroll
        for (int i = 0; i < 2; i++) if ((w[i].x & w[i].y & w[i].z & w[i].w & 1u) == 0u) w[i] = ld_vol_u4(&g_wv[lane][i]);
        more = __any_sync(0xffffffffu, (v[0].x & v[1].x & v[2].x & w[0].x & w[0].y & w[0].z & w[0].w & w[1].x & w[1].y & w[1].z & w[1].w & 1u) == 0u);
    } while (more && ++it < SPIN_LIMIT);
    float c;
    asm("sqrt.approx.f32 %0, %1;" : "=f"(c) : "f"(__uint_as_float(max(max(v[0].x, v[1].x), v[2].x))));
    c *= __uint_as_float(max(max(max(w[0].x, w[0].y), max(w[0].z, w[0].w)), max(max(w[1].x, w[1].y), max(w[1].z, w[1].w)))) * 272.f;
#pragma unroll
    for (int o = 16; o; o >>= 1) c += __shfl_xor_sync(0xffffffffu, c, o);
    const uint32_t r = __reduce_max_sync(0xffffffffu, v[0].y);
    if (lane < 3) {
        const uint32_t rb = mapa(sbase, lane);
        c *= 1.1f * 24.f;
        st_async64(rb + SM_SC, __float_as_uint(to_scale(__uint_as_float(r) * c)), __float_as_uint(c), rb + B_W + 8);
        st_async32(rb + SM_SC + 68, r, rb + B_W + 8);
    }
    __syncwarp();
}
__device__ __forceinline__ void xmax_gather(int lane, uint32_t sb) {
    uint4 v[4];
    unsigned it = 0;
    uint32_t ok;
    do {
#pragma unroll
        for (int i = 0; i < 4; i++) v[i] = ld_vol_u4(&g_rx[lane + 32 * (i >> 1)][i & 1]);
        ok = 1u;
#pragma unroll
        for (int i = 0; i < 4; i++) ok &= (v[i].x & v[i].y) & (v[i].z & v[i].w);
    } while (__any_sync(0xffffffffu, ok == 0u) && ++it < SPIN_LIMIT);
#pragma unroll
    for (int i = 0; i < 2; i++)
        sts32(sb + SM_SC + 64 + 4 * lane + 128 * i, max(max(max(v[2 * i].x, v[2 * i].y), max(v[2 * i].z, v[2 * i].w)), max(max(v[2 * i + 1].x, v[2 * i + 1].y), max(v[2 * i + 1].z, v[2 * i + 1].w))));
}
__device__ __forceinline__ uint32_t max_abs8(uint32_t m, uint32_t a, uint32_t b, uint32_t c, uint32_t d) { return max_abs2(max_abs2(m, max_abs2(a, b)), max_abs2(c, d)); }
__device__ __forceinline__ uint32_t warp_max_abs(uint32_t m) { return __reduce_max_sync(0xffffffffu, max((m << 16) & 0x7fff0000u, m & 0x7fff0000u)); }

__device__ __forceinline__ void last_rows() {
    extern __shared__ __align__(1024) unsigned char smem_raw[];
    const uint32_t sbase = smem_u32(smem_raw);
    const int tid = threadIdx.x, warp = __shfl_sync(0xffffffffu, tid >> 5, 0), h = blockIdx.x / 3;
    {
        const int sg = warp < 8, wq = warp & 3, lane = tid & 31;
        const uint32_t qk = sbase + SM_X + XBUF + sg * (2 * 9216), ob = sbase + SM_X + 2 * XBUF + sg * 8192;
        TST(0);
        mbar_wait(sbase + B_VX + 8 * sg, 0);
        fence_async();
        TST(1);
        float sc[20];
#pragma unroll
        for (int i = 0; i < 20; i++) sc[i] = 0.f;
        {
            const uint64_t da = smem_desc(qk + 1024, 128, 1024), db = smem_desc(qk, 128, 2048);
            wg_fence();
#pragma unroll
            for (int ks = 0; ks < 8; ks++) wgmma_n40_ss(sc, da + (uint64_t)((ks >> 2) * 576 + (ks & 3) * 16), db + (uint64_t)((ks >> 2) * 576 + (ks & 3) * 16), ks > 0);
            wg_commit();
            wg_wait0();
        }
        uint32_t p[5], o[16];
        const float psum = xrow_softmax(sc, p, wq, lane);
        xrow_pv(o, p, psum, sbase + SM_T + ((NSEG - 2 + sg) & 3) * TBUF);
        {
#pragma unroll
            for (int i = 0; i < 4; i++) stsm_x4(ob + wq * 2048 + i * 512 + lane * 16, o[4 * i], o[4 * i + 1], o[4 * i + 2], o[4 * i + 3]);
        }
        fence_async();
        named_bar(11 + sg, 128);
        TST(2);
        if ((tid & 127) == 0) {
            unsigned char* dst = reinterpret_cast<unsigned char*>(g_ox) + ((size_t)((NSEG / 2 - 1) * NH + h)) * 16384 + sg * 8192;
            asm volatile("cp.async.bulk.global.shared::cta.bulk_group [%0], [%1], 8192;" :: "l"(dst), "r"(ob) : "memory");
            asm volatile("cp.async.bulk.commit_group;" ::: "memory");
            asm volatile("cp.async.bulk.wait_group 0;" ::: "memory");
            asm volatile("red.relaxed.gpu.global.add.u32 [%0], 1;" :: "l"(&g_prog[(h >> 2) * 64 + NSEG / 2 - 1]) : "memory");
        }
        TST(3);
    }
    __syncwarp();
}

__global__ void __cluster_dims__(3, 1, 1) __launch_bounds__(384, 1)
k_chain(const __grid_constant__ CUtensorMap tmq, const __grid_constant__ CUtensorMap tmk,
        const __grid_constant__ CUtensorMap tmv, const __grid_constant__ CUtensorMap tmx2, const __grid_constant__ CUtensorMap tmo,
        const __grid_constant__ CUtensorMap tmm, const bf16* __restrict__ xg) {
    extern __shared__ __align__(1024) unsigned char smem_raw[];
    const uint32_t sbase = smem_u32(smem_raw);
    const int cta = blockIdx.x, h = cta / 3, role = cta - 3 * h;
    const int tid = threadIdx.x, warp = __shfl_sync(0xffffffffu, tid >> 5, 0), lane_o = tid & 31;
    TS3C(0);
    asm volatile("griddepcontrol.launch_dependents;" ::: "memory");
    auto stage_w = [&](int i) {
        tma_2d(sbase + SM_WS + i * 16384, role == 2 ? &tmv : &tmq, h * DH + (role == 1 ? 64 : 0), i * 64, sbase + B_W + 8 * i);
        tma_2d(sbase + SM_WS + i * 16384 + 8192, role == 2 ? &tmv : &tmk, h * DH + (role == 0 ? 0 : 64), i * 64, sbase + B_W + 8 * i);
    };
    auto stage_x = [&](int i) {
        tma_2d(sbase + x01_off(i), &tmx2, i * 64, 0, sbase + B_W + 8 * i);
        tma_2d(sbase + x01_off(i) + 8192, &tmm, i * 64, 0, sbase + B_W + 8 * i);
        if (i < 3) tma_2d(sbase + x23_off(i), &tmx2, i * 64, 64, sbase + B_W + 8 * i);
    };
    if (tid == 0) {
#pragma unroll
        for (int i = 0; i < 10; i++) mbar_init(sbase + B_W + 8 * i, 1);
        fence_async();
        TSQ(10);
#pragma unroll
        for (int i = 0; i < 3; i++) tma_2d(sbase + SM_X01 + i * 16384, &tmo, role * WOC + i * 64, h * DH, sbase + B_E);
        stage_x(0); stage_w(0);
        TSQ(11);
        mbar_expect(sbase + B_E, 49152);
#pragma unroll
        for (int i = 0; i < 9; i++) mbar_expect(sbase + B_W + 8 * i, 16384 + 9216 + (i < 3 ? 8192 : 0));
    } else if (tid == 32) {
#pragma unroll
        for (int i = 0; i < 8; i++) mbar_init(sbase + SM_BAR + 8 * i, 1);
        mbar_init(sbase + B_XF, 3);
        asm volatile("fence.mbarrier_init.release.cluster;" ::: "memory");
        for (int i = 0; i < 2; i++) {
            mbar_expect(sbase + B_SB + 8 * i, role == 2 ? 1280 : 640 + 2048);
            mbar_expect(sbase + B_VX + 8 * i, role != 2 ? 8192 : 2 * 9216);
            mbar_expect(sbase + B_XT + 8 * i, 32768);
            mbar_expect(sbase + B_XT + 16 + 8 * i, i == 0 ? 40960 : 0);
        }
    }
    __syncthreads();
    TS3C(8);
    if (tid == 0) {
#pragma unroll 1
        for (int i = 1; i < 3; i++) { stage_x(i); stage_w(i); }
        TSQ(12);
    }
    __syncwarp();
    if (warp < 8) {
        uint32_t wreg[36 - NS][4];
        uint32_t v0, v1;
        {
            const int lane = lane_o;
            const uint32_t a = w_addr(sbase, warp, lane);
            const uint64_t da = smem_desc(sbase + SM_WS + (warp >> 2) * 8192, 1024, 1024) | (1ull << 62);
            float acc[36], acc1[32];
            uint32_t m = 0u;
#pragma unroll
            for (int i = 0; i < 36; i++) acc[i] = 0.f;
#pragma unroll
            for (int i = 0; i < 32; i++) acc1[i] = 0.f;
#pragma unroll 1
            for (int b = 0; b < 7; b++) {
                if (b == 0) TSQ(0);
                mbar_wait(sbase + B_W + 8 * b, 0);
                TSQ(1 + b);
                const uint64_t db = smem_desc(sbase + x01_off(b), 16, 1024) | (1ull << 62);
                wg_fence();
#pragma unroll
                for (int k = 0; k < 4; k++) wgmma_n72_ss(acc, da + (uint64_t)(b * 1024 + k * 128), db + (uint64_t)(k * 2));
                wg_commit();
                if (b < 3) {
                    const uint64_t d1 = smem_desc(sbase + x23_off(b), 16, 1024) | (1ull << 62);
                    wg_fence();
#pragma unroll
                    for (int k = 0; k < 4; k++) wgmma_n64_ss(acc1, da + (uint64_t)(b * 1024 + k * 128), d1 + (uint64_t)(k * 2));
                    wg_commit();
                }
                if (b == 2) {
                    wg_wait0();
                    bar_arrive(10, 384);
                }
                if (b == 3) {
                    if (tid == 0) mbar_expect(sbase + B_W + 8, 12);
                    __syncwarp();
                    if (role == 2) {
#pragma unroll
                        for (int ks = 0; ks < NS; ks++) {
                            uint32_t t[4];
                            ldsm_x4_t(t, a + (ks >> 2) * 16384 + (ks & 3) * 2048);
                            m = max_abs8(m, t[0], t[1], t[2], t[3]);
                        }
                    }
#pragma unroll
                    for (int ks = NS; ks < 16; ks++) ldsm_x4_t(wreg[ks - NS], a + (ks >> 2) * 16384 + (ks & 3) * 2048);
                }
                if (b == 5) {
#pragma unroll
                    for (int ks = 16; ks < 24; ks++) ldsm_x4_t(wreg[ks - NS], a + (ks >> 2) * 16384 + (ks & 3) * 2048);
                    if (role == 2) {
#pragma unroll
                        for (int ks = NS; ks < 24; ks++) m = max_abs8(m, wreg[ks - NS][0], wreg[ks - NS][1], wreg[ks - NS][2], wreg[ks - NS][3]);
                    }
                }
            }
            mbar_wait(sbase + B_W + 16, 1);
            TSQ(13);
            wg_fence();
#pragma unroll
            for (int k = 12; k < 20; k++)
                wgmma_n64_ss(acc1, da + (uint64_t)((k >> 2) * 1024 + (k & 3) * 128), (smem_desc(sbase + x23_off(k >> 2), 16, 1024) | (1ull << 62)) + (uint64_t)((k & 3) * 2));
            wg_commit();
            wg_wait0();
            named_bar(11, 384);
#pragma unroll
            for (int i = 0; i < 8; i++)
                asm volatile("st.shared.v4.f32 [%0], {%1,%2,%3,%4};" :: "r"(sbase + SM_X + 5 * 8192 + i * 4096 + tid * 16),
                             "f"(acc1[4 * i]), "f"(acc1[4 * i + 1]), "f"(acc1[4 * i + 2]), "f"(acc1[4 * i + 3]) : "memory");
#pragma unroll
            for (int b = 7; b < 9; b++) {
#pragma unroll
                for (int ks = 4 * b - 4; ks < 4 * b; ks++) ldsm_x4_t(wreg[ks - NS], a + (ks >> 2) * 16384 + (ks & 3) * 2048);
                if (role == 2) {
#pragma unroll
                    for (int ks = 4 * b - 4; ks < 4 * b; ks++) m = max_abs8(m, wreg[ks - NS][0], wreg[ks - NS][1], wreg[ks - NS][2], wreg[ks - NS][3]);
                }
                const uint64_t db = smem_desc(sbase + x01_off(b), 16, 1024) | (1ull << 62);
                mbar_wait(sbase + B_W + 8 * b, 0);
                TSQ(1 + b);
                if (b == 8) TS3C(2);
                wg_fence();
#pragma unroll
                for (int k = 0; k < 4; k++) wgmma_n72_ss(acc, da + (uint64_t)(b * 1024 + k * 128), db + (uint64_t)(k * 2));
                wg_commit();
            }
#pragma unroll
            for (int ks = 32; ks < KPRE; ks++) ldsm_x4_t(wreg[ks - NS], a + (ks >> 2) * 16384 + (ks & 3) * 2048);
            if (role == 2) {
#pragma unroll
                for (int ks = KPRE; ks < 36; ks++) {
                    uint32_t t[4];
                    ldsm_x4_t(t, a + (ks >> 2) * 16384 + (ks & 3) * 2048);
                    m = max_abs8(m, t[0], t[1], t[2], t[3]);
                }
#pragma unroll
                for (int ks = 32; ks < KPRE; ks++) m = max_abs8(m, wreg[ks - NS][0], wreg[ks - NS][1], wreg[ks - NS][2], wreg[ks - NS][3]);
                m = warp_max_abs(m);
                if (lane == 0) asm volatile("st.volatile.global.u32 [%0], %1;" :: "l"(reinterpret_cast<uint32_t*>(&g_wv[h][0]) + warp), "r"(m | 1u) : "memory");
                __syncwarp();
            }
            wg_wait0();
            named_bar(9, 256);
            const uint32_t off = sbase + SM_T + (DH + warp * 16 + (lane & 15)) * 16 + (lane >> 4) * (DH * 16);
#pragma unroll
            for (int i = 0; i < 4; i++)
                stsm_x4(off + (i >> 1) * TBUF + (i & 1) * (2 * DH * 16), pack_bf16(acc[8 * i], acc[8 * i + 1]), pack_bf16(acc[8 * i + 2], acc[8 * i + 3]),
                        pack_bf16(acc[8 * i + 4], acc[8 * i + 5]), pack_bf16(acc[8 * i + 6], acc[8 * i + 7]));
            v0 = pack_bf16(acc[32], acc[33]);
            v1 = pack_bf16(acc[34], acc[35]);
#pragma unroll
            for (int ks = KPRE; ks < 36; ks++) ldsm_x4_t(wreg[ks - NS], a + (ks >> 2) * 16384 + (ks & 3) * 2048);
            if (role == 2) fence_async();
            bar_arrive(8, 384);
            named_bar(7, 256);
            asm volatile("barrier.cluster.arrive.relaxed.aligned;" ::: "memory");
        }
        TS3C(3);
        uint32_t ws[NS][4];
#pragma unroll
        for (int ks = NS - NP; ks < NS; ks++) ldsm_x4_t(ws[ks], w_addr(sbase, warp, lane_o) + (ks >> 2) * 16384 + (ks & 3) * 2048);
        asm volatile("barrier.cluster.wait.aligned;" ::: "memory");
        if (lane_o == 0 && role != 2 && warp < 2) tma_2d_mc(sbase + SM_X + (2 * role + warp) * 8192, &tmx2, (2 * role + warp + 5) * 64, 64, sbase + B_XT + 8);
        __syncwarp();
        TS3C(4);
        auto main_loop = [&](auto is_c) {
            constexpr bool C = decltype(is_c)::value;
            if (C) pad_code<PAD4>(); else pad_code<PAD3>();
            const uint32_t l16 = __shfl_sync(0xffffffffu, sbase + lane_o * 16, lane_o);
            const uint32_t ka = __shfl_sync(0xffffffffu, sbase + SM_T + (64 + (lane_o & 7) + ((lane_o >> 3) & 1) * 16 + (lane_o >> 4) * 8) * 16, lane_o);
            const uint32_t wa = __shfl_sync(0xffffffffu, w_addr(sbase, warp, lane_o), lane_o);
            auto post = [&](bool act, int s, uint32_t to, uint32_t ta, int scw, uint32_t v0, uint32_t v1) {
                int lane = lane_o;
                asm volatile("" : "+r"(lane));
                asm volatile("stmatrix.sync.aligned.m8n8.x2.shared.b16 [%0], {%1,%2};" :: "r"(l16 + ta), "r"(v0), "r"(v1) : "memory");
                if (C) {
                    if (act || s + 1 < NSEG) {
                        const uint32_t fo = (uint32_t)(warp * 256 + lane * 8);
                        const uint32_t rb0 = mapa(sbase, 0), rb1 = mapa(sbase, 1);
                        st_async64(rb0 + SM_VM + fo, v0, v1, rb0 + B_SB + 8 * (s & 1));
                        st_async64(rb1 + SM_VM + fo, v0, v1, rb1 + B_SB + 8 * (s & 1));
                        asm volatile("st.shared.v2.u32 [%0], {%1,%2};" :: "r"(sbase + SM_VM + fo), "r"(v0), "r"(v1) : "memory");
                        bar_arrive(2, 384);
                    }
                } else if (act) bar_arrive(2, 384);
                else {
                    named_bar(2, 384);
                    if (scw == 0) {
                        uint32_t kf[2][4], qf[2][4];
#pragma unroll
                        for (int k2 = 0; k2 < 2; k2++) { ldsm_x4_t(kf[k2], ka + to + k2 * 512); ldsm_x4_t(qf[k2], l16 + SM_T + to + k2 * 512); }
                        const uint32_t d0 = sbase + SM_S + lane * 8, bo = sbase + B_SB + 8 * (s & 1);
                        const uint32_t d1 = mapa(sbase + SM_S + 1280, role ^ 1) + lane * 4, m1 = mapa(bo, role ^ 1), d2 = mapa(sbase + SM_S + role * 1280, 2) + lane * 4, m2 = mapa(bo, 2);
                        score_group(qf, kf, d0, d1, m1, d2, m2);
                        bar_arrive(6, 160);
                        bar_arrive(5, 384);
                    }
                    if (scw == 8) {
                        const uint32_t dk = mapa(sbase + SM_X + XBUF + (2 + role) * 9216 + (warp - 4) * 256 + lane * 4, 2), mb = mapa(sbase + B_VX + 8, 2);
                        st_async32(dk, v0, mb);
                        st_async32(dk + 128, v1, mb);
                    }
                }
                FS(11, 0);
            };
            post(false, 0, 0, SM_T + warp * 256, warp ^ 7, v0, v1);
            if (tid == 128 && cta < NSEG) {
                fence_async();
                mbar_expect(sbase + B_E, XBUF);
                bulk_g2s(sbase + SM_X + 9 * 8192, xg + (size_t)cta * SEG * DM, 32768, sbase + B_E);
                bulk_g2s(sbase + SM_WS + 32768 + 4096, xg + (size_t)cta * SEG * DM + 16384, 4096, sbase + B_E);
            }
            __syncwarp();
            if (C) {
                named_bar(7, 256);
                if (warp == 1) norms_gather(lane_o, sbase);
            }
            auto chores = [&](int s, bool idle) {
                int lane = lane_o;
                asm volatile("" : "+r"(lane));
                const int hw = (s & 1) ? warp : warp - 4;
                const uint32_t tb = sbase + SM_T + (s & 3) * TBUF;
                if (idle) { if (hw != 2) named_bar(4, 384); else bar_arrive(4, 384); }
                if (hw == 2) {
                    if (lane == 0) {
                        {
                            if (C || !idle) fence_async();
                            if (C) {
                                store_tile(s + 1, h, 2, sbase + SM_T + ((s + 1) & 3) * TBUF, 2048, 10240);
                                store_tile(s, h, 2, tb, 0, idle ? 2048 : 10240);
                            } else store_tile(s, h, role, tb, 1024, 10240);
                            asm volatile("cp.async.bulk.commit_group;" ::: "memory");
                        }
                        {
                            asm volatile("cp.async.bulk.wait_group 0;" ::: "memory");
                            if (C) {
                                asm volatile("cp.async.bulk.shared::cluster.global.mbarrier::complete_tx::bytes.multicast::cluster [%0], [%1], 8192, [%2], %3;"
                                             :: "r"(sbase + SM_VX + ((s + 1) & 1) * 8192), "l"(&g_qkv[s + 1][h][2][2048]), "r"(sbase + B_VX + 8 * ((s + 1) & 1)), "h"((unsigned short)3) : "memory");
                            }
                            asm volatile("red.relaxed.gpu.global.add.u32 [%0], 1;" :: "l"(&g_flag[h * NSEG + s]) : "memory");
                        }
                    }
                    __syncwarp();
                    if (!C && (s & 1) && s + 4 < NSEG) bar_arrive(13, 160);
                }
                __syncwarp();
            };
            auto put_tiles = [&](const float (&acc)[32], uint32_t off) {
#pragma unroll
                for (int i = 0; i < 4; i++)
                    stsm_x4(off + (i >> 1) * TBUF + (i & 1) * (2 * DH * 16), pack_bf16(acc[8 * i], acc[8 * i + 1]), pack_bf16(acc[8 * i + 2], acc[8 * i + 3]),
                            pack_bf16(acc[8 * i + 4], acc[8 * i + 5]), pack_bf16(acc[8 * i + 6], acc[8 * i + 7]));
            };
            auto tile_off = [&](int p) {
                int lane = lane_o;
                asm volatile("" : "+r"(lane));
                return sbase + SM_T + (p & 1) * (2 * TBUF) + (DH + warp * 16 + (lane & 15)) * 16 + (lane >> 4) * (DH * 16);
            };
            {
                auto db = [&](int ks) { return (smem_desc(sbase + SM_X, 16, 1024) | (1ull << 62)) + (uint64_t)(((ks >> 2) - 5) * 512 + (ks & 3) * 2); };
                if (!C && warp != 7) bar_arrive(5, 384);
                if (warp == 5) {
                    mbar_wait(sbase + B_W + 8, 1);
                    bar_arrive(12, 160);
                }
                chores(0, false);
                float acc[32];
#pragma unroll
                for (int i = 0; i < 8; i++)
                    asm volatile("ld.shared.v4.f32 {%0,%1,%2,%3}, [%4];" : "=f"(acc[4 * i]), "=f"(acc[4 * i + 1]), "=f"(acc[4 * i + 2]), "=f"(acc[4 * i + 3])
                                 : "r"(l16 + warp * 512 + SM_X + 5 * 8192 + i * 4096) : "memory");
                mbar_wait(sbase + B_XT + 8, 0);
                FS(8, 0);
                named_bar(4, 384);
                wg_fence();
#pragma unroll
                for (int ks = 35; ks >= 20; ks--) wgmma_n64(acc, wreg[ks - NS], db(ks), 1);
                wg_commit();
                if (cta < NSEG) {
                    uint32_t m = 0u;
                    mbar_wait(sbase + B_E, 1);
#pragma unroll
                    for (int j = 0; j < 9; j++) {
                        const uint4 xv = lds128(l16 + warp * 512 + (j < 8 ? SM_X + 9 * 8192 + j * 4096 : SM_WS + 32768 + 4096));
                        m = max_abs8(m, xv.x, xv.y, xv.z, xv.w);
                    }
                    m = warp_max_abs(m);
                    if (lane_o == 0) asm volatile("st.volatile.global.u32 [%0], %1;" :: "l"(reinterpret_cast<uint32_t*>(&g_rx[cta][0]) + warp), "r"(m | 1u) : "memory");
                    __syncwarp();
                }
                FS(3, 0);
                wg_wait0();
                put_tiles(acc, tile_off(1));
                FS(7, __float_as_uint(acc[0]));
            }
            auto mem_proj = [&](uint32_t& u0, uint32_t& u1) {
#pragma unroll
                for (int ks = 0; ks < NS - NP; ks++) ldsm_x4_t(ws[ks], wa + (ks >> 2) * 16384 + (ks & 3) * 2048);
                FS(0, ws[0][0]);
                named_bar(1, 384);
                float acc[2][4], minv;
                uint32_t b[3][4];
#pragma unroll
                for (int kk = 0; kk < 3; kk++) ldsm_x4_t(b[kk], l16 + SM_M + kk * 512);
                FS(1, b[0][0]);
#pragma unroll
                for (int kk = 0; kk < 18; kk++) {
#pragma unroll
                    for (int i = 0; i < 2; i++) {
                        const int ks = 2 * kk + i;
                        if (ks < 2) mma_z(acc[i], ws[ks], b[kk % 3][2 * i], b[kk % 3][2 * i + 1]);
                        else if (ks < NS) mma_bf16(acc[i], ws[ks < NS ? ks : 0], b[kk % 3][2 * i], b[kk % 3][2 * i + 1]);
                        else mma_bf16(acc[i], wreg[ks >= NS ? ks - NS : 0], b[kk % 3][2 * i], b[kk % 3][2 * i + 1]);
                    }
                    if (kk + 3 < 18) ldsm_x4_t(b[kk % 3], l16 + SM_M + (kk + 3) * 512);
                    if (kk + 3 == 17) asm volatile("ld.shared.f32 %0, [%1];" : "=f"(minv) : "r"(sbase + SM_SC + 8) : "memory");
                }
                u0 = pack_bf16(fmaf(acc[1][0], minv, acc[0][0] * minv), fmaf(acc[1][1], minv, acc[0][1] * minv));
                u1 = pack_bf16(fmaf(acc[1][2], minv, acc[0][2] * minv), fmaf(acc[1][3], minv, acc[0][3] * minv));
                FS(2, u0);
            };
            int s = 0, rc = 9;
            bool act = warp >= 4;
            uint32_t to = TBUF, ta = SM_T + warp * 256 + TBUF;
            auto next_slot = [&]() {
                const uint32_t d = (s & 3) == 3 ? -3 * TBUF : TBUF;
                to += d; ta += d;
                asm volatile("" : "+r"(to), "+r"(ta));
            };
#pragma unroll 1
            for (;;) {
                uint32_t u0, u1;
                if (act) {
                    mem_proj(u0, u1);
                    s++;
                    post(true, s, to, ta, 1, u0, u1);
                    const int p = (s + 3) >> 1;
                    const uint32_t dlo = (uint32_t)smem_desc(sbase + SM_X, 16, 1024) + rc * 512;
                    const uint64_t da = smem_desc(sbase + SM_WS + (warp >> 2) * 8192, 1024, 1024) | (1ull << 62);
                    auto db = [&](int ks) {
                        const int j = ((ks >> 2) + 4) % 9;
                        return ((uint64_t)0x40000040u << 32) | (uint64_t)(dlo + (uint32_t)((j - (rc + j >= 13 ? 13 : 0)) * 512 + (ks & 3) * 2));
                    };
                    const uint32_t xph = (uint32_t)((p - 1) >> 1) & 1u;
                    float acc[32];
                    mbar_wait(sbase + B_XT + 8 * (p & 1), xph);
                    if (C) named_bar(7, 256); else named_bar(5, 384);
                    constexpr int N1 = C ? NC1C : NC1;
                    wg_fence();
#pragma unroll
                    for (int ks = 35; ks > 35 - N1; ks--) { if (ks == 35) wgmma_n64_z(acc, wreg[ks - NS], db(ks)); else wgmma_n64(acc, wreg[ks - NS], db(ks), 1); }
                    wg_commit();
                    wg_wait0();
                    FS(9, __float_as_uint(acc[0]));
                    next_slot();
                    FS(8, 0);
                    asm volatile("{\n.reg .pred p;\nsetp.ge.s32 p, %0, 0;\n@p bar.sync 4, 384;\n}" :: "r"(s) : "memory");
                    FS(3, 0);
                    wg_fence();
#pragma unroll
                    for (int ks = 35 - N1; ks >= KG1; ks--) wgmma_n64(acc, wreg[ks - NS], db(ks), 1);
                    wg_commit();
                    mbar_wait(sbase + B_XT + 16 + 8 * (p & 1), xph);
                    wg_fence();
#pragma unroll
                    for (int ks = 0; ks < NS; ks++) wgmma_n64_ss(acc, da + (uint64_t)((ks >> 2) * 1024 + (ks & 3) * 128), db(ks));
#pragma unroll
                    for (int ks = NS; ks < KG1; ks++) wgmma_n64(acc, wreg[ks - NS], db(ks), 1);
                    wg_commit();
                    if (!C && warp >= 4) named_bar(13, 160);
                    uint32_t off = tile_off(p);
                    rc = rc >= 4 ? rc - 4 : rc + 9;
                    asm volatile("" : "+r"(off), "+r"(rc));
                    wg_wait0();
                    put_tiles(acc, off);
                    FS(7, __float_as_uint(acc[0]));
                }
                int scw = s + 2 < NSEG ? warp ^ ((s & 1) ? 7 : 3) : (warp & 4) + 4;
                asm volatile("" : "+r"(scw));
                mem_proj(u0, u1);
                s++;
                post(false, s, to, ta, scw, u0, u1);
                if (s + 1 == NSEG) break;
                if (s + 2 < NSEG) {
                    if (!C && (warp & 3) == 2) fence_async();
                    if (C) named_bar(7, 256); else if (scw != 0) named_bar(5, 384);
                    chores(s, true);
                } else {
                    const uint32_t t0 = clock32();
                    const uint32_t dq = mapa(sbase + SM_X + XBUF + role * 9216, 2), mb = mapa(sbase + B_VX, 2);
                    if (!C) {
                        if (scw != 0) named_bar(5, 384);
                        if (tid == 64) { fence_async(); while (clock32() - t0 < TL_DELAY) {} bulk_s2s(dq, sbase + SM_T + 2 * TBUF + 1024, 9216, mb); }
                        __syncwarp();
                    }
                    named_bar(4, 384);
                    if (!C && tid == 64) { const uint32_t t1 = clock32(); while (clock32() - t1 < VX_DELAY) {} bulk_s2s(dq + 2 * 9216 + 1024, sbase + SM_T + 3 * TBUF + 2048, 8192, mb + 8); }
                    __syncwarp();
                }
                next_slot();
                act = s + 4 < NSEG;
            }
            if (C) named_bar(7, 256);
        };
        if (role == 2) main_loop(Flag<true>()); else main_loop(Flag<false>());
    } else {
        uint32_t wo[3][8][4];
        uint32_t mx2 = 0u;
        {
            const int pt = tid - 256, lane = lane_o, wq = warp - 8, g = lane >> 2, tq = lane & 3;
            TSQ(7);
            mbar_wait(sbase + B_E, 0);
            TSQ(8);
#pragma unroll
            for (int t = 0; t < 3; t++) {
                const int T = 3 * wq + t;
                const uint32_t a = sbase + SM_X01 + (T >> 2) * 16384 + ((lane >> 4) * 8 + (lane & 7)) * 128 + ((((T & 3) * 2 + ((lane >> 3) & 1)) ^ (lane & 7)) << 4);
#pragma unroll
                for (int kk = 0; kk < 8; kk++) ldsm_x4_t(wo[t][kk], a + ((2 * wq + kk) & 7) * 2048);
            }
            named_bar(3, 128);
            if (pt == 64) {
                fence_async();
#pragma unroll 1
                for (int i = 3; i < 9; i++) { stage_x(i); if (i < 7) stage_w(i); }
            }
            if (pt >= 96 && pt < 120) {
                *reinterpret_cast<uint4*>(g_acc + cta * 1024 + (pt - 96) * 16) = make_uint4(0u, 0u, 0u, 0u);
                __threadfence();
            }
            __syncwarp();
            TSQ(9);
            float c0 = 0.f;
#pragma unroll
            for (int t = 0; t < 3; t++) {
                float n[4][4];
#pragma unroll
                for (int i = 0; i < 4; i++) { n[i][0] = n[i][1] = n[i][2] = n[i][3] = 0.f; }
#pragma unroll
                for (int kk = 0; kk < 8; kk++)
#pragma unroll
                    for (int i = 0; i < 4; i++) mma_k8(n[i], wo[t][kk][i & 2], wo[t][kk][(i & 2) + 1], wo[t][kk][i]);
                if ((g >> 1) == tq) c0 = fmaxf(c0, (g & 1) ? fmaxf(n[0][1] + n[2][1], n[1][3] + n[3][3]) : fmaxf(n[0][0] + n[2][0], n[1][2] + n[3][2]));
            }
            c0 = __uint_as_float(__reduce_max_sync(0xffffffffu, __float_as_uint(c0)));
            uint32_t m = 0u;
            const int xb = role == 0 ? h % 9 : 9;
            auto x_max = [&]() {
                mbar_wait(sbase + B_W + 8 * xb, 0);
#pragma unroll
                for (int j = 0; j < 5; j++) {
                    uint4 xv;
                    asm volatile("ld.shared.v4.u32 {%0,%1,%2,%3}, [%4];" : "=r"(xv.x), "=r"(xv.y), "=r"(xv.z), "=r"(xv.w)
                                 : "r"(sbase + x01_off(xb) + (j < 4 ? pt + 128 * j : 512 + (pt & 63)) * 16) : "memory");
                    m = max_abs8(m, xv.x, xv.y, xv.z, xv.w);
                }
            };
            if (xb < 3) x_max();
            named_bar(10, 384);
            TSQ(10);
            if (pt == 64) {
                fence_async();
                mbar_expect(sbase + B_W + 16, 16384);
#pragma unroll
                for (int i = 3; i < 5; i++) tma_2d(sbase + x23_off(i), &tmx2, i * 64, 64, sbase + B_W + 16);
#pragma unroll 1
                for (int i = 7; i < 9; i++) stage_w(i);
            }
            __syncwarp();
            if (xb >= 3 && xb < 7) x_max();
            bar_arrive(11, 384);
            if (xb == 7 || xb == 8) x_max();
            asm volatile("barrier.cluster.arrive.relaxed.aligned;" ::: "memory");
            m = warp_max_abs(m);
            if (lane == 0) { sts32(sbase + SM_SC + 320 + 4 * wq, __float_as_uint(c0)); sts32(sbase + SM_SC + 336 + 4 * wq, m); }
            TSQ(1);
            named_bar(3, 128);
            if (pt == 0) {
                const uint4 a = lds128(sbase + SM_SC + 320), b = lds128(sbase + SM_SC + 336);
                st_vol_u2(&g_norm[cta], make_uint2(max(max(a.x, a.y), max(a.z, a.w)) | 1u, max(max(b.x, b.y), max(b.z, b.w)) | 1u));
            }
            __syncwarp();
            named_bar(8, 384);
            TSQ(2);
            asm volatile("barrier.cluster.wait.aligned;" ::: "memory");
            if (role == 2 && lane == 0 && wq < 2) vx_copy(sbase, 0, wq);
            __syncwarp();
        }
        const int wq = warp - 8;
        auto helper_loop = [&](auto is_c) {
        const bool C = is_c.value;
        if (C) pad_code<PAD2>(); else pad_code<PAD1>();
        const uint32_t sb = sbase;
        const uint32_t l8_o = __shfl_sync(0xffffffffu, sb + lane_o * 8, lane_o), l16_o = __shfl_sync(0xffffffffu, sb + lane_o * 16, lane_o);
        unsigned char* dst = g_acc + (role * 32 + wq * 8 + (lane_o >> 3)) * 1024 + (lane_o & 7) * 16;
        auto load_kf = [&](uint32_t (&kf)[2][4], int slot) {
            int lane = lane_o;
            asm volatile("" : "+r"(lane));
            const uint32_t ka = sb + SM_T + slot * TBUF + ((wq + 1) * DH + 64 + (lane & 7) + ((lane >> 3) & 1) * 16 + (lane >> 4) * 8) * 16;
#pragma unroll
            for (int k2 = 0; k2 < 2; k2++) ldsm_x4_t(kf[k2], ka + k2 * 512);
        };
        float minv = 1.f;
        uint32_t kf[2][4];
        if (!C) load_kf(kf, 0);
        int b3 = 0;
        int rx = 9;
        for (int s = 0; s + 1 < NSEG; s++) {
            const int n3 = b3 == 2 ? 0 : b3 + 1;
            uint32_t l8 = l8_o, l16 = l16_o;
            asm volatile("" : "+r"(l8), "+r"(l16));
            const uint32_t l4 = sb + ((l8 - sb) >> 1);
            {
                int lane = lane_o;
                asm volatile("" : "+r"(lane));
                if (C) {
                    if (lane == 0) {
                        if (wq == 3 && h == 0) {
                            const uint32_t t = gtime32();
                            st_vol_u2(&g_tick, make_uint2(t, lds32(sb + SM_SC + 12)));
                            sts32(sb + SM_SC + 12, t);
                        }
                    }
                    __syncwarp();
                    if (wq == 2 && s > 1 && lane < 24) {
                        *reinterpret_cast<uint4*>(g_acc + n3 * 128 + (3 * h + (lane >> 3)) * 1024 + (lane & 7) * 16) = make_uint4(0u, 0u, 0u, 0u);
                    }
                    if (wq == 1 && s == 3 && lane < 3) {
                        const int c = 3 * h + lane;
                        st_vol_u2(&g_norm[c], make_uint2(0u, 0u));
                        uint4* z = c < NSEG ? g_rx[c] : g_wv[c - NSEG];
                        st_vol_u4(z, make_uint4(0u, 0u, 0u, 0u)); st_vol_u4(z + 1, make_uint4(0u, 0u, 0u, 0u));
                    }
                    __syncwarp();
                }
                const uint32_t mw = __reduce_max_sync(0xffffffffu, max(mx2 << 16, mx2 & 0xffff0000u));
                if (lane == 0) sts32(sb + SM_SC + 16 + 4 * wq, mw);
            }
            const uint32_t to = SM_T + (s & 3) * TBUF;
            const uint32_t ph = (uint32_t)(s >> 1) & 1u;
            if (!C) {
                const uint32_t bo = sb + B_SB + 8 * (s & 1);
                uint32_t d0 = l8 + SM_S + (wq + 1) * 256, qa = l16 + to;
                const uint32_t dr = l4 + SM_S + (wq + 1) * 256;
                const uint32_t d1 = mapa(dr + 1280, role ^ 1), m1 = mapa(bo, role ^ 1), d2 = mapa(dr + role * 1280, 2), m2 = mapa(bo, 2);
                asm volatile("" : "+r"(d0), "+r"(qa));
                mbar_wait(sb + (s > 0 ? B_VX + 8 * (s & 1) : B_W), ph);
                FS(1, 0);
                named_bar(2, 384);
                uint32_t qf[2][4];
#pragma unroll
                for (int k2 = 0; k2 < 2; k2++) ldsm_x4_t(qf[k2], qa + k2 * 512);
                score_group(qf, kf, d0, d1, m1, d2, m2);
                bar_arrive(5, 384);
            } else named_bar(2, 384);
            if (!C && s == 0) {
                TSQ(3);
                mbar_wait(sb + B_VX, 0);
                TSQ(4);
            }
            float4 m4;
            asm volatile("ld.shared.v4.f32 {%0,%1,%2,%3}, [%4];" : "=f"(m4.x), "=f"(m4.y), "=f"(m4.z), "=f"(m4.w) : "r"(sb + SM_SC + 16) : "memory");
            const float c24 = __uint_as_float(lds32(sb + SM_SC + 4)), xb = __uint_as_float(lds32(sb + SM_SC + 64 + 4 * s));
            uint32_t vf[2][2][4], vm[2][2];
            uint32_t va = l16 + ((l16 >> 8) & 1) * 1792 + wq * 512 + (C ? to + DH * 16 : SM_VX + (s & 1) * 8192);
            auto load_vf = [&]() {
#pragma unroll
                for (int i = 0; i < 4; i++) ldsm_x4(vf[i & 1][i >> 1], va + (i & 1) * 256 + (i >> 1) * 4096);
            };
            load_vf();
            float scale = to_scale(fmaxf(fmaxf(fmaxf(m4.x, m4.y), fmaxf(m4.z, m4.w)) * minv, xb) * c24);
            uint32_t oa = l16 + wq * 512;
            asm volatile("" : "+f"(scale), "+r"(oa), "+r"(va));
            FS(7, __float_as_uint(scale));
            if (!C) named_bar(6, 160);
            if (C) mbar_wait(sb + B_SB + 8 * (s & 1), ph);
            float sv[5][2];
#pragma unroll
            for (int j = 0; j < 5; j++) {
                if (C) { const uint32_t w = lds32(l4 + SM_S + j * 256); sv[j][0] = __uint_as_float(w << 16); sv[j][1] = __uint_as_float(w & 0xffff0000u); }
                else lds64f(sv[j][0], sv[j][1], l8 + SM_S + j * 256);
            }
            if (!C) mbar_wait(sb + B_SB + 8 * (s & 1), ph);
            FS(6, 0);
            uint32_t p[5];
            {
                float sr[5][2];
#pragma unroll
                for (int j = 0; j < 5; j++) {
                    const uint32_t w = lds32(l4 + SM_S + 1280 + j * 256);
                    sr[j][0] = __uint_as_float(w << 16); sr[j][1] = __uint_as_float(w & 0xffff0000u);
                }
                lds64(vm[0][0], vm[0][1], l8 + SM_VM + wq * 512);
                lds64(vm[1][0], vm[1][1], l8 + SM_VM + wq * 512 + 256);
#pragma unroll
                for (int j = 0; j < 5; j++) {
                    sv[j][0] += sr[j][0];
                    sv[j][1] += sr[j][1];
                }
                float mx = fmaxf(fmaxf(fmaxf(sv[0][0], sv[0][1]), fmaxf(sv[1][0], sv[1][1])), fmaxf(fmaxf(sv[2][0], sv[2][1]), fmaxf(sv[3][0], sv[3][1])));
                mx = fmaxf(mx, fmaxf(sv[4][0], sv[4][1]));
                {
                    const float m1 = __shfl_xor_sync(0xffffffffu, mx, 1), m2 = __shfl_xor_sync(0xffffffffu, mx, 2), m3 = __shfl_xor_sync(0xffffffffu, mx, 3);
                    mx = fmaxf(fmaxf(mx, m1), fmaxf(m2, m3));
                }
#pragma unroll
                for (int jj = 0; jj < 5; jj++) {
                    const int j = (jj + 1) % 5;
                    asm("ex2.approx.ftz.f32 %0, %1;" : "=f"(sv[j][0]) : "f"(sv[j][0] - mx));
                    asm("ex2.approx.ftz.f32 %0, %1;" : "=f"(sv[j][1]) : "f"(sv[j][1] - mx));
                    p[j] = pack_bf16(sv[j][0], sv[j][1]);
                }
            }
            FS(0, p[0]);
            uint32_t b[4][4];
            const uint32_t one4[4] = {0x3f803f80u, 0x3f803f80u, 0x3f803f80u, 0x3f803f80u};
            float zs[4];
            {
                float o0[2][4], o1[2][4];
                mma_z(o0[0], vf[0][0], p[1], p[2]);
                mma_z(o0[1], vf[1][0], p[1], p[2]);
                mma_z(o1[0], vf[0][1], p[3], p[4]);
                mma_z(o1[1], vf[1][1], p[3], p[4]);
                mma_k8(o0[0], vm[0][0], vm[0][1], p[0]);
                mma_k8(o0[1], vm[1][0], vm[1][1], p[0]);
                float z2[4];
                mma_z(zs, one4, p[1], p[2]);
                mma_z(z2, one4, p[3], p[4]);
                mma_k8(zs, one4[0], one4[1], p[0]);
                zs[0] += z2[0]; zs[1] += z2[1];
                uint32_t ow[4];
#pragma unroll
                for (int m = 0; m < 2; m++) {
                    ow[2 * m] = pack_bf16(o0[m][0] + o1[m][0], o0[m][1] + o1[m][1]);
                    ow[2 * m + 1] = pack_bf16(o0[m][2] + o1[m][2], o0[m][3] + o1[m][3]);
                }
                stsm_x4(oa + SM_O, ow[0], ow[1], ow[2], ow[3]);
                FS(2, 0);
                b[0][0] = movm(ow[0]); b[0][1] = movm(ow[1]);
                __syncwarp();
                asm volatile("ldmatrix.sync.aligned.m8n8.x2.trans.shared.b16 {%0,%1}, [%2];" : "=r"(b[0][2]), "=r"(b[0][3]) : "r"(oa + SM_O + 256));
            }
            float acc[3][2][4];
            named_bar(3, 128);
#pragma unroll
            for (int i = 1; i < 4; i++) ldsm_x4_t(b[i], l16 + SM_O + ((wq + i) & 3) * 512);
#pragma unroll
            for (int c = 0; c < 2; c++)
#pragma unroll
                for (int t = 0; t < 3; t++) mma_z(acc[t][c], wo[t][c], b[0][2 * c], b[0][2 * c + 1]);
            float z0, z1;
            asm volatile("rcp.approx.ftz.f32 %0, %1;" : "=f"(z0) : "f"(zs[0]));
            asm volatile("rcp.approx.ftz.f32 %0, %1;" : "=f"(z1) : "f"(zs[1]));
            asm volatile("{\n.reg .pred p;\nsetp.eq.s32 p, %1, 0;\n@p bar.sync 12, 160;\n@p ld.shared.f32 %0, [%2];\n}" : "+f"(scale) : "r"(s), "r"(sb + SM_SC) : "memory");
            z0 *= scale; z1 *= scale;
            FS(3, b[1][0]);
#pragma unroll
            for (int i = 1; i < 4; i++)
#pragma unroll
                for (int c = 0; c < 2; c++)
#pragma unroll
                    for (int t = 0; t < 3; t++) mma_bf16(acc[t][c], wo[t][2 * i + c], b[i][2 * c], b[i][2 * c + 1]);
            {
                uint32_t w[6];
#pragma unroll
                for (int t = 0; t < 3; t++) {
                    w[2 * t] = pack_f16(fmaf(acc[t][1][0], z0, acc[t][0][0] * z0), fmaf(acc[t][1][1], z1, acc[t][0][1] * z1));
                    w[2 * t + 1] = pack_f16(fmaf(acc[t][1][2], z0, acc[t][0][2] * z0), fmaf(acc[t][1][3], z1, acc[t][0][3] * z1));
                }
                FS(8, w[5]);
                asm volatile("red.relaxed.gpu.global.add.noftz.v4.f16x2 [%0], {%1,%2,%3,%4};" :: "l"(dst), "r"(w[0]), "r"(w[1]), "r"(w[2]), "r"(0x3c00u) : "memory");
                asm volatile("red.relaxed.gpu.global.add.noftz.v4.f16x2 [%0], {%1,%2,%3,%4};" :: "l"(dst + 4096), "r"(w[3]), "r"(w[4]), "r"(w[5]), "r"(0x3c00u) : "memory");
            }
            FS(9, 0);
            if (s == 0) TSQ(5);
            bar_arrive(4, 384);
            const uint32_t t0 = clock32();
            minv = __uint_as_float(0x7f000000u - __float_as_uint(scale));
            if (lane_o == 0) {
                if (wq == 0) sts32(sb + SM_SC + 8, __float_as_uint(minv));
                if (s + 3 < NSEG) {
                    if (wq == 0) mbar_expect(sb + B_SB + 8 * (s & 1), C ? 1280 : 640 + 2048);
                    if (wq == 1 && s > 0 && s + 5 < NSEG) mbar_expect(sb + B_XT + ((s & 1) ? 0 : 16) + 4 * ((s + 1) & 2), (s & 1) ? 32768 : 40960);
                    if (wq == 3 && !C) mbar_expect(sb + B_VX + 8 * (s & 1), 8192);
                }
            }
            __syncwarp();
            if (s == 1) {
                if (!C) pad_code<PADC>();
                int lane = lane_o;
                asm volatile("" : "+r"(lane));
                if (wq == 3) xmax_gather(lane, sb);
                __syncwarp();
            }
            if (!C) load_kf(kf, (s + 1) & 3);
            const uint4* src = reinterpret_cast<const uint4*>(dst + (wq * 16 - role * 32) * 1024);
            dst += n3 == 0 ? -256 : 128;
            asm volatile("" : "+l"(dst));
            const int xp = (s + 5) >> 1, kb = wq + ((s & 1) ? 2 * role : 4 + 3 * role);
            const bool xl = !C && xp < NSEG / 2 && wq < ((s & 1) ? 2 : 3 - role);
            const uint32_t xs = wq == 3 && (s & 1) == 0 && xp < NSEG / 2;
            const uint32_t xd = sb + SM_X + (rx + kb >= 13 ? rx + kb - 13 : rx + kb) * 8192;
            mx2 = poll_mem(src, l16 + SM_M + wq * 2304, t0, [&]() {
                if (xs && lane_o < 2) asm volatile("mbarrier.arrive.relaxed.cluster.shared::cluster.b64 _, [%0];" :: "r"(mapa(sb + B_XF, lane_o)) : "memory");
                if (!C && (xl || s == 0) && (s & 1) == 0) mbar_wait(sb + B_XF, (uint32_t)(s >> 1) & 1u);
                if (lane_o == 0) {
                    if (xl) tma_2d_mc(xd, &tmx2, ((s & 1) ? kb + 5 : kb - 4) * 64, xp * 64, sb + B_XT + ((s & 1) ? 0 : 16) + 8 * (xp & 1));
                    if (!C && s == 0 && role == 1) tma_2d_mc(sb + SM_X + (9 + wq) * 8192, &tmx2, (wq + 5) * 64, 128, sb + B_XT);
                }
                __syncwarp();
            });
            if ((s & 1) == 0) rx = rx >= 4 ? rx - 4 : rx + 9;
            if (s == 0) TSQ(6);
            b3 = n3;
        }
        if (!C) bar_arrive(2, 384);
        };
        if (role == 2) helper_loop(Flag<true>()); else helper_loop(Flag<false>());
    }
    TS3C(1);
    if (role == 2 && warp >= 4) last_rows();
    cluster_sync_all();
}

extern "C" void kernel_launch(void* const* d_in, const int* in_sizes, int n_in, void* d_out, int out_size) {
    const bf16* x = (const bf16*)d_in[0];
    const bf16* mem0 = (const bf16*)d_in[1];
    const bf16* Wq = (const bf16*)d_in[2];
    const bf16* Wk = (const bf16*)d_in[3];
    const bf16* Wv = (const bf16*)d_in[4];
    const bf16* Wo = (const bf16*)d_in[5];
    const bf16* logA = (const bf16*)d_in[8];
    const bf16* Aim = (const bf16*)d_in[9];
    const bf16* Cre = (const bf16*)d_in[10];
    const bf16* Cim = (const bf16*)d_in[11];
    const bf16* logdt = (const bf16*)d_in[12];
    const bf16* dskip = (const bf16*)d_in[13];
    const bf16* gw = (const bf16*)d_in[14];
    bf16* out = (bf16*)d_out;
    static bool attr_done = false;
    typedef CUresult (*EncFn)(CUtensorMap*, CUtensorMapDataType, cuuint32_t, void*, const cuuint64_t*, const cuuint64_t*, const cuuint32_t*,
                              const cuuint32_t*, CUtensorMapInterleave, CUtensorMapSwizzle, CUtensorMapL2promotion, CUtensorMapFloatOOBfill);
    static EncFn enc = nullptr;
    if (!attr_done) {
        void* fn = nullptr;
        cudaDriverEntryPointQueryResult qr;
        cudaGetDriverEntryPoint("cuTensorMapEncodeTiled", &fn, cudaEnableDefault, &qr);
        enc = (EncFn)fn;
        cudaFuncSetAttribute(k_chain, cudaFuncAttributeMaxDynamicSharedMemorySize, 232448);
        cudaFuncSetAttribute(k_side, cudaFuncAttributeMaxDynamicSharedMemorySize, SIDE_SMEM);
        attr_done = true;
    }
    CUtensorMap tmw[3];
    for (int i = 0; i < 3; i++) {
        const cuuint64_t dims[2] = {(cuuint64_t)HD, (cuuint64_t)DM};
        const cuuint64_t strides[1] = {(cuuint64_t)HD * 2};
        const cuuint32_t box[2] = {64, 64};
        const cuuint32_t es[2] = {1, 1};
        enc(&tmw[i], CU_TENSOR_MAP_DATA_TYPE_BFLOAT16, 2, (void*)(i == 0 ? Wq : (i == 1 ? Wk : Wv)), dims, strides, box, es, CU_TENSOR_MAP_INTERLEAVE_NONE,
            CU_TENSOR_MAP_SWIZZLE_128B, CU_TENSOR_MAP_L2_PROMOTION_L2_256B, CU_TENSOR_MAP_FLOAT_OOB_FILL_NONE);
    }
    CUtensorMap tmo;
    {
        const cuuint64_t dims[2] = {(cuuint64_t)DM, (cuuint64_t)HD};
        const cuuint64_t strides[1] = {(cuuint64_t)DM * 2};
        const cuuint32_t box[2] = {64, 128};
        const cuuint32_t es[2] = {1, 1};
        enc(&tmo, CU_TENSOR_MAP_DATA_TYPE_BFLOAT16, 2, (void*)Wo, dims, strides, box, es, CU_TENSOR_MAP_INTERLEAVE_NONE,
            CU_TENSOR_MAP_SWIZZLE_128B, CU_TENSOR_MAP_L2_PROMOTION_L2_128B, CU_TENSOR_MAP_FLOAT_OOB_FILL_NONE);
    }
    CUtensorMap tmx2;
    {
        const cuuint64_t dims[2] = {(cuuint64_t)DM, (cuuint64_t)S_LEN};
        const cuuint64_t strides[1] = {(cuuint64_t)DM * 2};
        const cuuint32_t box[2] = {64, 64};
        const cuuint32_t es[2] = {1, 1};
        enc(&tmx2, CU_TENSOR_MAP_DATA_TYPE_BFLOAT16, 2, (void*)x, dims, strides, box, es, CU_TENSOR_MAP_INTERLEAVE_NONE,
            CU_TENSOR_MAP_SWIZZLE_128B, CU_TENSOR_MAP_L2_PROMOTION_L2_128B, CU_TENSOR_MAP_FLOAT_OOB_FILL_NONE);
    }
    CUtensorMap tmm;
    {
        const cuuint64_t dims[2] = {(cuuint64_t)DM, (cuuint64_t)MEMT};
        const cuuint64_t strides[1] = {(cuuint64_t)DM * 2};
        const cuuint32_t box[2] = {64, (cuuint32_t)MEMT};
        const cuuint32_t es[2] = {1, 1};
        enc(&tmm, CU_TENSOR_MAP_DATA_TYPE_BFLOAT16, 2, (void*)mem0, dims, strides, box, es, CU_TENSOR_MAP_INTERLEAVE_NONE,
            CU_TENSOR_MAP_SWIZZLE_128B, CU_TENSOR_MAP_L2_PROMOTION_L2_128B, CU_TENSOR_MAP_FLOAT_OOB_FILL_NONE);
    }
    k_chain<<<NCTA, 384, 232448>>>(tmw[0], tmw[1], tmw[2], tmx2, tmo, tmm, x);
    {
        cudaLaunchConfig_t cfg = {};
        cfg.gridDim = dim3(SD_NCTA); cfg.blockDim = dim3(512); cfg.dynamicSmemBytes = SIDE_SMEM; cfg.stream = cudaStreamPerThread;
        cudaLaunchAttribute at[1];
        at[0].id = cudaLaunchAttributeProgrammaticStreamSerialization;
        at[0].val.programmaticStreamSerializationAllowed = 1;
        cfg.attrs = at; cfg.numAttrs = 1;
        cudaLaunchKernelEx(&cfg, k_side, tmo, x, logA, Aim, Cre, Cim, logdt, Wo, dskip, gw, out);
    }
}
```

```cpp
#include <cuda_runtime.h>
#include <cuda.h>
#include <cuda_bf16.h>
#include <stdint.h>

typedef __nv_bfloat16 bf16;
#define LDV4 "ld.volatile.global.v4.u32 {%0,%1,%2,%3}, [%4];"
#define STV4 "st.volatile.global.v4.u32 [%0], {%1,%2,%3,%4};"
#define STV2 "st.volatile.global.v2.u32 [%0], {%1,%2};"

constexpr int S_LEN = 2048, DM = 576, NH = 32, DH = 128, HD = 4096, MEMT = 8, SEG = 32, NSEG = 64, NST = 128;

__device__ __align__(128) bf16 g_gate[S_LEN];
constexpr int NCTA = NH * 3;
__device__ __align__(1024) unsigned char g_acc[96 * 1024];
__device__ __align__(128) uint2 g_norm[NCTA];
__device__ __align__(128) uint4 g_wv[NH][2];
__device__ __align__(128) uint4 g_rx[NSEG][2];
__device__ __align__(128) unsigned char g_qkv[NSEG][NH][3][10240];
__device__ __align__(128) bf16 g_ox[S_LEN * HD];
__device__ __align__(128) uint4 g_fp[8][36][6][128];
__device__ __align__(128) unsigned g_flag[NH * NSEG];
__device__ __align__(128) unsigned g_prog[8 * 64];
__device__ unsigned g_gcnt[64];
__device__ unsigned g_epoch;
__device__ __align__(128) uint2 g_tick;
__device__ __align__(128) bf16 g_y[DM * S_LEN];

#define TS3(slot) do {} while (0)
#define TS3P(slot) do {} while (0)
#define TSQ(slot) do {} while (0)
#define TS3W(slot) do {} while (0)
#define TSS(row, slot) do {} while (0)
#define TS3C(slot) do {} while (0)
#define TST(slot) do {} while (0)
#define TSA(seg, slot) do {} while (0)
#define TSG(i) do {} while (0)
#define FS(i, dep) do {} while (0)
__device__ __forceinline__ uint32_t smem_u32(const void* p) { return (uint32_t)__cvta_generic_to_shared(p); }
__device__ __forceinline__ float bf16r(float x) { return __bfloat162float(__float2bfloat16_rn(x)); }
__device__ __forceinline__ uint32_t pack_bf16(float lo, float hi) {
    __nv_bfloat162 v = __floats2bfloat162_rn(lo, hi);
    return *reinterpret_cast<uint32_t*>(&v);
}
__device__ __forceinline__ void ldsm_x4(uint32_t (&r)[4], uint32_t addr) {
    asm volatile("ldmatrix.sync.aligned.m8n8.x4.shared.b16 {%0,%1,%2,%3}, [%4];"
                 : "=r"(r[0]), "=r"(r[1]), "=r"(r[2]), "=r"(r[3]) : "r"(addr));
}
__device__ __forceinline__ void ldsm_x4_t(uint32_t (&r)[4], uint32_t addr) {
    asm volatile("ldmatrix.sync.aligned.m8n8.x4.trans.shared.b16 {%0,%1,%2,%3}, [%4];"
                 : "=r"(r[0]), "=r"(r[1]), "=r"(r[2]), "=r"(r[3]) : "r"(addr));
}
__device__ __forceinline__ void mma_bf16(float (&d)[4], const uint32_t (&a)[4], uint32_t b0, uint32_t b1) {
    asm volatile("mma.sync.aligned.m16n8k16.row.col.f32.bf16.bf16.f32 {%0,%1,%2,%3}, {%4,%5,%6,%7}, {%8,%9}, {%0,%1,%2,%3};"
                 : "+f"(d[0]), "+f"(d[1]), "+f"(d[2]), "+f"(d[3])
                 : "r"(a[0]), "r"(a[1]), "r"(a[2]), "r"(a[3]), "r"(b0), "r"(b1));
}
__device__ __forceinline__ uint2 ld_vol_u2(const uint2* p) {
    uint2 v; asm volatile("ld.volatile.global.v2.u32 {%0,%1}, [%2];" : "=r"(v.x), "=r"(v.y) : "l"(p) : "memory"); return v;
}
__device__ __forceinline__ void st_vol_u2(uint2* p, uint2 v) {
    asm volatile(STV2 :: "l"(p), "r"(v.x), "r"(v.y) : "memory");
}
__device__ __forceinline__ unsigned ld_acq(const unsigned* p) {
    unsigned v; asm volatile("ld.acquire.gpu.global.u32 %0, [%1];" : "=r"(v) : "l"(p) : "memory"); return v;
}
#define NS 10
#define NP 4
#define GATE_A 950
#define GATE_B 450
#define GATE_P 1800u
#define RLX_SLEEP 300
#define VX_DELAY 100
#define UNGATE_G 3
#define W14_SLEEP 60
#define GL_A 1150
#define GL_B 530
#define GS_A 1300
#define GS_B 480
#define NC1 3
#define NC1C 5
#define KPRE 34
#define PADC 0
#define PAD1 0
#define PAD2 0
#define PAD3 0
#define PAD4 0
#define EXF 1
#define KG1 20
#define WO_SLEEP 200
#define WO_LAG 500
#define TM 29
#define TM2 (TM - 1)
#define TL_DELAY 600
#define POLL_DELAY 590
#define UNGATE 6
constexpr unsigned SPIN_LIMIT = 1u << 20;
constexpr int NATT = NSEG - 2;

constexpr int SD_CH = 16;
constexpr int SD_NCTA = DM / SD_CH;
constexpr int SD_ROW = 528;
constexpr int SD_U = 8 * SD_ROW;
constexpr int SD_TAP = 5888;
constexpr int SD_CPY = 1376 * 2;
constexpr int SD_WSTR = SD_TAP + 2 * SD_CPY;
constexpr int SD_SMEM = SD_CH * SD_U + 8 * SD_WSTR;
constexpr int O_U = 79, O_U3 = 911, O_U4 = 1055, O_W79 = 1023, O_W35 = 1151, O_W610 = 1279, O_W511 = 1487;

__device__ __forceinline__ uint32_t lds32(uint32_t a) { uint32_t v; asm volatile("ld.shared.u32 %0, [%1];" : "=r"(v) : "r"(a)); return v; }
__device__ __forceinline__ void sts32(uint32_t a, uint32_t v) { asm volatile("st.shared.u32 [%0], %1;" :: "r"(a), "r"(v) : "memory"); }
__device__ __forceinline__ uint4 lds128(uint32_t a) {
    uint4 v; asm volatile("ld.shared.v4.u32 {%0,%1,%2,%3}, [%4];" : "=r"(v.x), "=r"(v.y), "=r"(v.z), "=r"(v.w) : "r"(a) : "memory"); return v;
}
__device__ __forceinline__ void tap_tile(uint32_t (&t)[4], uint32_t a) {
    asm volatile("ld.volatile.shared.u32 %0, [%4];\nld.volatile.shared.u32 %1, [%4+-16];\nld.volatile.shared.u32 %2, [%4+16];\nld.volatile.shared.u32 %3, [%4];"
                 : "=r"(t[0]), "=r"(t[1]), "=r"(t[2]), "=r"(t[3]) : "r"(a));
}
constexpr uint32_t sd_pass(int type, int dl, int o, int d0, int d1) { return (uint32_t)(type | dl << 2 | d0 << 8 | d1 << 12 | o << 17); }
__constant__ uint32_t SD_PASS[14] = {sd_pass(0, 0, O_U, 0, 2), sd_pass(0, 1, O_U + 96, 0, 2), sd_pass(0, 2, O_U + 192, 0, 4), sd_pass(0, 3, O_U + 288, 0, 2), sd_pass(1, 0, O_U3, 8, 8),
                                     sd_pass(0, 4, O_U + 384, 0, 2), sd_pass(1, 0, O_U4, 8, 15), sd_pass(0, 5, O_U + 480, 0, 2), sd_pass(0, 6, O_U + 576, 0, 4), sd_pass(0, 7, O_U + 672, 0, 2),
                                     sd_pass(2, 0, O_W35, 2, 8), sd_pass(3, 0, O_W79, 2, 4), sd_pass(2, 1, O_W610, 4, 8), sd_pass(3, 0, O_W511, 8, 15)};
__device__ __forceinline__ uint32_t band2(int x, int lo, int hi) { return (x >= lo && x <= hi ? 0x3f80u : 0u) | (x + 1 >= lo && x + 1 <= hi ? 0x3f800000u : 0u); }
__device__ __forceinline__ void mma_z(float (&d)[4], const uint32_t (&a)[4], uint32_t b0, uint32_t b1);
__device__ __forceinline__ void put_tap(uint32_t a, float v) {
    asm volatile("{\n.reg .b16 h;\ncvt.rn.bf16.f32 h, %1;\nst.shared.b16 [%0], h;\nst.shared.b16 [%0+%2], h;\n}" :: "r"(a), "f"(v), "n"(SD_CPY - 2) : "memory");
}

__device__ __forceinline__ void named_bar(int id, int n) { asm volatile("bar.sync %0, %1;" :: "r"(id), "r"(n) : "memory"); }
__device__ __forceinline__ uint32_t pack_f16(float lo, float hi) {
    uint32_t r; asm("cvt.rn.f16x2.f32 %0, %1, %2;" : "=r"(r) : "f"(hi), "f"(lo)); return r;
}
__device__ __forceinline__ void cexp_t(float lr, float turns, float& re, float& im) {
    float m;
    asm("ex2.approx.ftz.f32 %0, %1;" : "=f"(m) : "f"(lr));
    const float a = (turns - rintf(turns)) * 6.283185307179586f;
    re = m * __cosf(a); im = m * __sinf(a);
}
__device__ __forceinline__ void csq(float& re, float& im) { const float r = re * re - im * im; im = 2.f * re * im; re = r; }
__device__ __forceinline__ void kb_state(const float* tp, float gf, uint32_t (&a)[4][2], uint32_t (&b)[5]) {
    const float4 p0 = *reinterpret_cast<const float4*>(tp), p1 = *reinterpret_cast<const float4*>(tp + 4);
    float wr, wi;
    cexp_t(p0.x * gf, p0.y * gf, wr, wi);
    float vr = wr * p1.x - wi * p1.y, vi = wr * p1.y + wi * p1.x;
#pragma unroll
    for (int c = 0; c < 4; c++) {
        a[c][0] = pack_f16(wr, wi); a[c][1] = pack_f16(vr, vi);
        csq(wr, wi);
        if (c < 3) csq(vr, vi);
    }
    b[0] = pack_f16(p0.z * wr - p0.w * wi, -p0.z * wi - p0.w * wr);
    float er = wr * p1.z - wi * p1.w, ei = wr * p1.w + wi * p1.z;
#pragma unroll
    for (int c = 0; c < 4; c++) {
        b[1 + c] = pack_f16(p0.z * er - p0.w * ei, -p0.z * ei - p0.w * er);
        if (c < 3) csq(er, ei);
    }
}
__device__ __forceinline__ uint32_t bf2_mul(uint32_t a, uint32_t b) { uint32_t r; asm("mul.rn.bf16x2 %0, %1, %2;" : "=r"(r) : "r"(a), "r"(b)); return r; }
__device__ __forceinline__ uint32_t bf2_add(uint32_t a, uint32_t b) { uint32_t r; asm("add.rn.bf16x2 %0, %1, %2;" : "=r"(r) : "r"(a), "r"(b)); return r; }
__device__ __forceinline__ uint32_t bf2_sub(uint32_t a, uint32_t b) { uint32_t r; asm("sub.rn.bf16x2 %0, %1, %2;" : "=r"(r) : "r"(a), "r"(b)); return r; }
__device__ __forceinline__ void wait_cnt(const unsigned* p, unsigned target) {
    unsigned it = 0;
    while ((int)(ld_acq(p) - target) < 0 && ++it < SPIN_LIMIT) __nanosleep(64);
}
__device__ __forceinline__ uint32_t gtime32() { uint32_t t; asm volatile("mov.u32 %0, %%globaltimer_lo;" : "=r"(t) :: "memory"); return t; }
__device__ __forceinline__ void gate(uint32_t tick_addr, uint32_t ga = GATE_A, uint32_t gb = GATE_B) {
    uint32_t t1, p;
    asm volatile("ld.volatile.shared.v2.u32 {%0,%1}, [%2];" : "=r"(t1), "=r"(p) : "r"(tick_addr) : "memory");
    uint32_t d = gtime32() - t1;
    if (d < 4u * p) {
        d -= d >= 2u * p ? 2u * p : 0u;
        d -= d >= p ? p : 0u;
        if (d + ga >= p && d + gb < p) {
            const uint32_t t2 = gtime32() + (p - gb - d);
            while ((int)(gtime32() - t2) < 0) {}
        }
    }
}

__device__ __forceinline__ void read_tick(uint32_t tick_addr) {
    const uint2 tk = ld_vol_u2(&g_tick);
    uint32_t p = tk.x - tk.y;
    p = p > GATE_P + 100u ? GATE_P + 100u : p;
    asm volatile("st.volatile.shared.v2.u32 [%0], {%1,%2};" :: "r"(tick_addr), "r"(tk.x), "r"(p) : "memory");
}

__device__ __forceinline__ void s4d_phase(unsigned char* smem_raw, const bf16* __restrict__ x, const bf16* __restrict__ logA,
                                          const bf16* __restrict__ Aim, const bf16* __restrict__ Cre, const bf16* __restrict__ Cim,
                                          const bf16* __restrict__ logdt, const bf16* __restrict__ dskip, const bf16* __restrict__ wslice) {
    const int tid = threadIdx.x, warp = __shfl_sync(0xffffffffu, tid >> 5, 0), lane = tid & 31;
    const int d0 = blockIdx.x * SD_CH;
    float* tab = reinterpret_cast<float*>(smem_raw + SD_CH * SD_U + warp * SD_WSTR);
    const uint32_t wb = smem_u32(tab);
    const int g = lane >> 2, tq = lane & 3;
    uint2 prm[4];
    float ldt;
    auto load_prm = [&](int d) {
        prm[0] = __ldg(reinterpret_cast<const uint2*>(logA + d * NST) + lane); prm[1] = __ldg(reinterpret_cast<const uint2*>(Aim + d * NST) + lane);
        prm[2] = __ldg(reinterpret_cast<const uint2*>(Cre + d * NST) + lane); prm[3] = __ldg(reinterpret_cast<const uint2*>(Cim + d * NST) + lane);
        ldt = __bfloat162float(logdt[d]);
    };
    load_prm(d0 + warp);
    for (int i = lane; i < 2 * SD_CPY / 16; i += 32) reinterpret_cast<uint4*>(tab + SD_TAP / 4)[i] = make_uint4(0u, 0u, 0u, 0u);
    TS3(20);
#pragma unroll 1
    for (int ch = 0; ch < 2; ch++) {
        const int d = d0 + 8 * ch + warp;
        const uint32_t ub = smem_u32(smem_raw) + (8 * ch + warp) * SD_U;
        float k2048 = 0.f, sinv;
        {
            const float dt = bf16r(expf(ldt));
            uint32_t cm = __vmaxu2(__vmaxu2(prm[2].x & 0x7fff7fffu, prm[2].y & 0x7fff7fffu), __vmaxu2(prm[3].x & 0x7fff7fffu, prm[3].y & 0x7fff7fffu));
            cm = __reduce_max_sync(0xffffffffu, max(cm << 16, cm & 0xffff0000u));
            int e = 134 - (int)(__float_as_uint(__uint_as_float(cm) * dt) >> 23);
            e = e > 100 ? 100 : (e < -100 ? -100 : e);
            const float s2 = __uint_as_float((uint32_t)(128 + e) << 23);
            sinv = __uint_as_float((uint32_t)(127 - e) << 23);
#pragma unroll
            for (int j = 0; j < 4; j++) {
                float q[4];
#pragma unroll
                for (int i = 0; i < 4; i++) { const uint32_t w = j < 2 ? prm[i].x : prm[i].y; q[i] = __uint_as_float((j & 1) ? w & 0xffff0000u : w << 16); }
                const float zl = -bf16r(expf(q[0])) * dt * 1.4426950408889634f;
                const float zt = q[1] * dt * 0.15915494309189535f;
                const float cr = s2 * (q[2] * dt), ci = s2 * (q[3] * dt);
                float ar, ai, br, bi, er, ei;
                cexp_t(zl * 8.f, zt * 8.f, ar, ai);
                cexp_t(zl * 128.f, zt * 128.f, br, bi);
                cexp_t(zl * 2048.f, zt * 2048.f, er, ei);
                k2048 += cr * er - ci * ei;
                *reinterpret_cast<float4*>(tab + (lane + 32 * j) * 8) = make_float4(zl, zt, cr, ci);
                *reinterpret_cast<float4*>(tab + (lane + 32 * j) * 8 + 4) = make_float4(ar, ai, br, bi);
            }
#pragma unroll
            for (int o = 16; o; o >>= 1) k2048 += __shfl_xor_sync(0xffffffffu, k2048, o);
        }
        __syncwarp();
        {
            float kc[5][4];
#pragma unroll
            for (int i = 0; i < 5; i++) { kc[i][0] = kc[i][1] = kc[i][2] = kc[i][3] = 0.f; }
            const float gf = (float)g;
#pragma unroll 2
            for (int ks = 0; ks < 16; ks++) {
                uint32_t a0[4][2], a1[4][2], b0[5], b1[5];
                kb_state(tab + (8 * ks + tq) * 8, gf, a0, b0);
                kb_state(tab + (8 * ks + 4 + tq) * 8, gf, a1, b1);
#pragma unroll
                for (int i = 0; i < 5; i++) {
                    const int c = i > 0 ? i - 1 : 0;
                    asm volatile("mma.sync.aligned.m16n8k16.row.col.f32.f16.f16.f32 {%0,%1,%2,%3}, {%4,%5,%6,%7}, {%8,%9}, {%0,%1,%2,%3};"
                                 : "+f"(kc[i][0]), "+f"(kc[i][1]), "+f"(kc[i][2]), "+f"(kc[i][3])
                                 : "r"(a0[c][0]), "r"(a0[c][1]), "r"(a1[c][0]), "r"(a1[c][1]), "r"(b0[i]), "r"(b1[i]));
                }
            }
            const uint32_t tp = wb + SD_TAP;
            const uint32_t a0 = tp + 2 * (O_U + 96 * g - 4 * tq);
            const uint32_t a2 = tp + 2 * (((g & 1) ? O_U + 96 * (2 * (g & 3)) : ((g & 2) ? O_W35 : O_W79 + 1)) - 32 - 8 * tq - (g >> 2));
            const uint32_t a3 = tp + 2 * (((g & 1) ? O_W35 : O_W610 + 1) - 64 - 16 * tq - (g >> 1));
            const uint32_t a4 = tp + 2 * (-128 - 32 * tq - g);
#pragma unroll
            for (int c = 0; c < 4; c++) {
                const int e = (c & 1) * 16 + (c >> 1) * 8;
                const bool first = c == 0 && lane == 0;
                put_tap(a0 - e / 4, kc[0][c] * sinv);
                put_tap(a0 - 32 - e / 4, kc[1][c] * sinv);
                put_tap(first ? tp + 2 * (O_U - 32) : a2 - e / 2, kc[2][c] * sinv);
                put_tap(first ? tp + 2 * (O_W79 - 63) : a3 - e, kc[3][c] * sinv);
                put_tap(first ? tp + 2 * (O_W610 - 127) : a4 + 2 * (O_W511 + 1 - e), kc[4][c] * sinv);
                if ((g & 1) == 0) {
                    put_tap(a4 + 2 * (O_U4 - e), kc[4][c] * sinv);
                    put_tap(first ? tp + 2 * (O_U3 - 128) : a4 + 2 * (O_U4 + 1 - e), kc[4][c] * sinv);
                }
            }
            if (lane == 0) {
                put_tap(tp + 2 * (O_U + 96 - 32), kc[2][0] * sinv);
                put_tap(tp + 2 * (O_U + 192 - 64), kc[3][0] * sinv);
                put_tap(tp + 2 * (O_W511 - 255), k2048 * sinv);
                put_tap(tp + 2 * (O_U4 - 255), k2048 * sinv);
            }
        }
        TS3(21 + 2 * ch);
        if (ch == 0) named_bar(1, 384);
        else {
#pragma unroll
            for (int i = 0; i < 4; i++) asm volatile("prefetch.global.L2 [%0];" :: "l"(wslice + (size_t)((tid & 127) + 128 * i) * DM));
        }
        __syncwarp();
        if (tid == 0) TSS(18, 4 * ch);
        const uint32_t sh = wb + 80 + 11 * SD_ROW;
#pragma unroll
        for (int p = 0; p < 8; p++) {
            uint4 v;
            asm volatile("ld.shared.v4.u32 {%0,%1,%2,%3}, [%4];" : "=r"(v.x), "=r"(v.y), "=r"(v.z), "=r"(v.w) : "r"(ub + p * SD_ROW + lane * 16) : "memory");
            uint32_t pv = __shfl_up_sync(0xffffffffu, v.w, 1);
            pv = lane == 0 ? 0u : pv;
            asm volatile("st.shared.v4.u32 [%0], {%1,%2,%3,%4};" :: "r"(sh + (p - 8) * SD_ROW + lane * 16), "r"(__byte_perm(pv, v.x, 0x5432)), "r"(__byte_perm(v.x, v.y, 0x5432)),
                         "r"(__byte_perm(v.y, v.z, 0x5432)), "r"(__byte_perm(v.z, v.w, 0x5432)) : "memory");
            if (p >= 5) asm volatile("st.shared.v4.u32 [%0], {%1,%2,%3,%4};" :: "r"(sh + (p - 16) * SD_ROW + lane * 16), "r"(pv), "r"(v.x), "r"(v.y), "r"(v.z) : "memory");
        }
        __syncwarp();
        if (tid == 0) TSS(18, 4 * ch + 1);
        float acc[16][4];
#pragma unroll
        for (int i = 0; i < 16; i++) { acc[i][0] = acc[i][1] = acc[i][2] = acc[i][3] = 0.f; }
        {
            const uint32_t ka = wb + SD_TAP + ((g & 1) ? 0 : SD_CPY - 2) + 2 * (2 * tq - g);
            uint32_t b[16][2], b2[14][2];
#pragma unroll
            for (int k = 0; k < 16; k++) { b[k][0] = b[k][1] = 0u; if (k < 14) b2[k][0] = b2[k][1] = 0u; }
#pragma unroll 1
            for (int ps = 0; ps < 14; ps++) {
                const uint32_t pw = __shfl_sync(0xffffffffu, SD_PASS[ps], 0), type = pw & 3u, kp = ka + (pw >> 16);
                const int dl = (pw >> 2) & 7, d0 = (pw >> 8) & 15, d1 = (pw >> 12) & 15;
                uint32_t t[2][4];
                tap_tile(t[0], kp - 32 * d0);
                if (type == 0) {
                    const int p = (lane & 7) - dl;
                    const uint32_t ra = (p < 0 ? sh : ub) + p * SD_ROW + (lane >> 3) * 16;
#pragma unroll
                    for (int k = 0; k < 8; k++)
                        asm volatile("ldmatrix.sync.aligned.m8n8.x4.shared.b16 {%0,%1,%2,%3}, [%4];"
                                     : "=r"(b[2 * k][0]), "=r"(b[2 * k][1]), "=r"(b[2 * k + 1][0]), "=r"(b[2 * k + 1][1]) : "r"(ra + k * 64));
                } else if (type == 2) {
                    const int p = (lane & 15) - 11, xo = 2 * tq - g;
                    const uint32_t qa = (p < 0 ? sh : ub) + p * SD_ROW + (lane >> 4) * 16;
                    const int lx = 6 - 5 * dl, hx = 8 - 3 * dl, ly = 2 - 2 * dl, hy = 4 + 2 * dl;
                    const uint32_t sel[4] = {band2(xo, lx, hx), band2(xo, ly, hy), band2(xo + 8, lx, hx), band2(xo + 8, ly, hy)};
#pragma unroll
                    for (int k = 0; k < 14; k++) {
                        uint32_t q[4];
                        ldsm_x4_t(q, qa + k * 32);
#pragma unroll
                        for (int i = 0; i < 2; i++) {
                            float w[4];
                            mma_z(w, sel, q[2 * i], q[2 * i + 1]);
                            b[k][i] = pack_bf16(w[0], w[1]);
                            b2[k][i] = pack_bf16(w[2], w[3]);
                        }
                    }
                } else if (type == 3) {
#pragma unroll
                    for (int k = 0; k < 14; k++) { b[k][0] = b2[k][0]; b[k][1] = b2[k][1]; }
                }
#pragma unroll
                for (int d = 0; d < 16; d += 2) {
                    if (d >= 8 || d >= d0) {
                        tap_tile(t[1], kp - 32 * (d + 1));
#pragma unroll
                        for (int k = 0; k + d < 16; k++) mma_bf16(acc[k + d], t[0], b[k][0], b[k][1]);
                        if ((d == 2 || d == 4 || d == 8) && d == d1) break;
                        if (d < 14) tap_tile(t[0], kp - 32 * (d + 2));
#pragma unroll
                        for (int k = 0; k + d + 1 < 16; k++) mma_bf16(acc[k + d + 1], t[1], b[k][0], b[k][1]);
                    }
                }
            }
        }
        __syncwarp();
        if (tid == 0) TSS(18, 4 * ch + 2);
        load_prm(d0 + 8 + warp);
        if (ch == 0) {
            if (lane == 0) {
                unsigned ep;
                asm volatile("ld.volatile.global.u32 %0, [%1];" : "=r"(ep) : "l"(&g_epoch) : "memory");
                wait_cnt(&g_gcnt[0], SD_NCTA * (ep + 1u));
            }
            __syncwarp();
        }
        if (tid == 0) TSS(18, 4 * ch + 3);
        uint4 gv[8];
#pragma unroll
        for (int i = 0; i < 8; i++) gv[i] = __ldcg(reinterpret_cast<const uint4*>(g_gate) + lane + 32 * i);
        const uint32_t dd = __byte_perm(*reinterpret_cast<const unsigned short*>(dskip + d), 0u, 0x1010);
#pragma unroll
        for (int i = 0; i < 8; i++) {
            uint32_t u[4];
            ldsm_x4_t(u, ub + (lane & 7) * SD_ROW + (lane >> 3) * 16 + i * 64);
            asm volatile("stmatrix.sync.aligned.m8n8.x4.shared.b16 [%0], {%1,%2,%3,%4};"
                         :: "r"(wb + (lane + 32 * i) * 16),
                            "r"(bf2_add(pack_bf16(acc[2 * i][0], acc[2 * i][1]), bf2_mul(u[0], dd))), "r"(bf2_add(pack_bf16(acc[2 * i][2], acc[2 * i][3]), bf2_mul(u[1], dd))),
                            "r"(bf2_add(pack_bf16(acc[2 * i + 1][0], acc[2 * i + 1][1]), bf2_mul(u[2], dd))), "r"(bf2_add(pack_bf16(acc[2 * i + 1][2], acc[2 * i + 1][3]), bf2_mul(u[3], dd))) : "memory");
        }
        __syncwarp();
#pragma unroll
        for (int i = 0; i < 8; i++) {
            const uint4 y = *reinterpret_cast<const uint4*>(tab + (lane + 32 * i) * 4);
            *reinterpret_cast<uint4*>(g_y + (((lane >> 1) + 16 * i) * DM + d) * 16 + (lane & 1) * 8) =
                make_uint4(bf2_mul(bf2_sub(0x3f803f80u, gv[i].x), y.x), bf2_mul(bf2_sub(0x3f803f80u, gv[i].y), y.y),
                           bf2_mul(bf2_sub(0x3f803f80u, gv[i].z), y.z), bf2_mul(bf2_sub(0x3f803f80u, gv[i].w), y.w));
        }
        __syncwarp();
        if (ch == 0) asm volatile("bar.arrive 11, 288;" ::: "memory");
        TS3(22 + 2 * ch);
    }
}
__device__ __forceinline__ void s4d_stage_u(unsigned char* smem_raw, const bf16* __restrict__ x, int pt) {
    const int p = pt & 7, w0 = pt >> 3;
    const uint4* src = reinterpret_cast<const uint4*>(x + (size_t)(16 * w0 + p) * DM + blockIdx.x * SD_CH);
    uint32_t* dst = reinterpret_cast<uint32_t*>(smem_raw + p * SD_ROW) + w0;
#pragma unroll 1
    for (int b = 0; b < 4; b++) {
        uint4 v[2][2][2];
#pragma unroll
        for (int i = 0; i < 8; i++) v[i >> 2][(i >> 1) & 1][i & 1] = src[((b * 2 + (i >> 2)) * 256 + ((i >> 1) & 1) * 8) * (DM / 8) + (i & 1)];
#pragma unroll
        for (int i = 0; i < 4; i++) {
            const uint32_t* lo = reinterpret_cast<const uint32_t*>(&v[i >> 1][0][i & 1]);
            const uint32_t* hi = reinterpret_cast<const uint32_t*>(&v[i >> 1][1][i & 1]);
#pragma unroll
            for (int c = 0; c < 8; c++) dst[((i & 1) * 8 + c) * (SD_U / 4) + (b * 2 + (i >> 1)) * 16] = __byte_perm(lo[c >> 1], hi[c >> 1], (c & 1) ? 0x7632 : 0x5410);
        }
    }
    asm volatile("bar.arrive 1, 384;" ::: "memory");
}

constexpr int WOC = DM / 3;
constexpr int TBUF = 5 * DH * 16;
constexpr int XBUF = SEG * DM * 2;
constexpr int SM_BAR = 0;
constexpr int B_SB = 0, B_VX = 16, B_XT = 32, B_XF = 144, B_W = 64, B_E = 136;
constexpr int SM_SC = 256;
constexpr int SM_F = SM_SC + 1280;
constexpr int SM_VM = SM_F + 2048;
constexpr int SM_S = SM_VM + 2048;
constexpr int SM_O = SM_S + 2560;
constexpr int SM_M = SM_O + 2048;
constexpr int SM_WS = 19456;
constexpr int SM_T = SM_WS + 49152;
constexpr int SM_VX = SM_T + 4 * TBUF;
constexpr int SM_X = SM_VX + 2 * 8192;
constexpr int SM_X01 = SM_WS + DM * DH * 2;
__host__ __device__ constexpr int x01_off(int b) { return b < 2 ? 1024 + b * 9216 : SM_X01 + (b == 2 ? 6 : b - 3) * 9216; }
__host__ __device__ constexpr int x23_off(int b) { return b < 3 ? SM_WS + 7 * 16384 + b * 8192 : x01_off(b - 3); }
constexpr int CH_SMEM = SM_X01 + 8 * 8192;
static_assert(SM_M + DM * 16 <= SM_WS && SM_X + 13 * 8192 <= CH_SMEM && NS <= 10 && CH_SMEM <= 232448 && SM_X % 1024 == 0 && SM_X01 % 1024 == 0 && 1024 + 2 * 9216 <= SM_WS, "smem");
__device__ __forceinline__ uint32_t clock32() { uint32_t t; asm volatile("mov.u32 %0, %%clock;" : "=r"(t) :: "memory"); return t; }

__device__ __forceinline__ uint32_t mapa(uint32_t a, uint32_t rank) {
    uint32_t r; asm volatile("mapa.shared::cluster.u32 %0, %1, %2;" : "=r"(r) : "r"(a), "r"(rank)); return r;
}
__device__ __forceinline__ void st_async32(uint32_t addr, uint32_t v, uint32_t mbar) {
    asm volatile("st.async.weak.shared::cluster.mbarrier::complete_tx::bytes.b32 [%0], %1, [%2];" :: "r"(addr), "r"(v), "r"(mbar) : "memory");
}
__device__ __forceinline__ void mbar_init(uint32_t bar, uint32_t cnt) {
    asm volatile("mbarrier.init.shared::cta.b64 [%0], %1;" :: "r"(bar), "r"(cnt) : "memory");
}
__device__ __forceinline__ void mbar_expect(uint32_t bar, uint32_t bytes) {
    asm volatile("mbarrier.arrive.expect_tx.shared::cta.b64 _, [%0], %1;" :: "r"(bar), "r"(bytes) : "memory");
}
__device__ __forceinline__ void mbar_wait(uint32_t bar, uint32_t parity) {
    unsigned it = 0;
    uint32_t ok;
    do {
        ++it;
        asm volatile("{\n.reg .pred p;\nmbarrier.try_wait.parity.shared::cta.b64 p, [%1], %2;\nselp.u32 %0, 1, 0, p;\n}" : "=r"(ok) : "r"(bar), "r"(parity) : "memory");
    } while ((ok == 0u) & (it < SPIN_LIMIT));
}
__device__ __forceinline__ void mbar_wait_long(uint32_t bar, uint32_t parity) {
    unsigned it = 0;
    while (true) {
        uint32_t ok;
        asm volatile("{\n.reg .pred p;\nmbarrier.try_wait.parity.shared::cta.b64 p, [%1], %2, %3;\nselp.u32 %0, 1, 0, p;\n}"
                     : "=r"(ok) : "r"(bar), "r"(parity), "r"(20000u) : "memory");
        if (ok || ++it >= SPIN_LIMIT) break;
    }
}
__device__ __forceinline__ bool mbar_test(uint32_t bar, uint32_t parity) {
    uint32_t ok;
    asm volatile("{\n.reg .pred p;\nmbarrier.test_wait.parity.shared::cta.b64 p, [%1], %2;\nselp.u32 %0, 1, 0, p;\n}" : "=r"(ok) : "r"(bar), "r"(parity) : "memory");
    return ok != 0u;
}
__device__ __forceinline__ uint64_t policy_evict_first() {
    uint64_t pol; asm volatile("createpolicy.fractional.L2::evict_first.b64 %0, 1.0;" : "=l"(pol)); return pol;
}
__device__ __forceinline__ void cluster_sync_all() {
    asm volatile("barrier.cluster.arrive.release.aligned;\nbarrier.cluster.wait.acquire.aligned;" ::: "memory");
}
__device__ __forceinline__ uint4 ld_vol_u4(const uint4* p) {
    uint4 v; asm volatile(LDV4 : "=r"(v.x), "=r"(v.y), "=r"(v.z), "=r"(v.w) : "l"(p) : "memory"); return v;
}
__device__ __forceinline__ void ld_vol_u4_p(uint4& v, const uint4* p, uint32_t pred) {
    asm volatile("{\n.reg .pred p;\nsetp.ne.u32 p, %5, 0;\n@p " LDV4 "\n}"
                 : "+r"(v.x), "+r"(v.y), "+r"(v.z), "+r"(v.w) : "l"(p), "r"(pred) : "memory");
}
__device__ __forceinline__ void st_vol_u4(uint4* p, uint4 v) {
    asm volatile(STV4 :: "l"(p), "r"(v.x), "r"(v.y), "r"(v.z), "r"(v.w) : "memory");
}
__device__ __forceinline__ void mma_bf16_r(float (&d)[4], uint32_t a0, uint32_t a1, uint32_t a2, uint32_t a3, uint32_t b0, uint32_t b1) {
    asm volatile("mma.sync.aligned.m16n8k16.row.col.f32.bf16.bf16.f32 {%0,%1,%2,%3}, {%4,%5,%6,%7}, {%8,%9}, {%0,%1,%2,%3};"
                 : "+f"(d[0]), "+f"(d[1]), "+f"(d[2]), "+f"(d[3])
                 : "r"(a0), "r"(a1), "r"(a2), "r"(a3), "r"(b0), "r"(b1));
}

__device__ __forceinline__ uint64_t smem_desc(uint32_t addr, uint32_t lbo, uint32_t sbo) {
    return (uint64_t)((addr & 0x3FFFF) >> 4) | ((uint64_t)(lbo >> 4) << 16) | ((uint64_t)(sbo >> 4) << 32);
}
__device__ __forceinline__ void wg_fence() { asm volatile("wgmma.fence.sync.aligned;" ::: "memory"); }
__device__ __forceinline__ void wg_commit() { asm volatile("wgmma.commit_group.sync.aligned;" ::: "memory"); }
__device__ __forceinline__ void wg_wait0() { asm volatile("wgmma.wait_group.sync.aligned 0;" ::: "memory"); }
__device__ __forceinline__ void fence_async() { asm volatile("fence.proxy.async.shared::cta;" ::: "memory"); }
__device__ __forceinline__ void wgmma_n64_ss(float (&d)[32], uint64_t adesc, uint64_t bdesc) {
    asm volatile("{\n.reg .pred p;\nsetp.eq.b32 p, 0, 0;\n"
                 "wgmma.mma_async.sync.aligned.m64n64k16.f32.bf16.bf16 {%0,%1,%2,%3,%4,%5,%6,%7,%8,%9,%10,%11,%12,%13,%14,%15,%16,%17,%18,%19,%20,%21,%22,%23,%24,%25,%26,%27,%28,%29,%30,%31}, %32, %33, p, 1, 1, 1, 0;\n}"
                 : "+f"(d[0]), "+f"(d[1]), "+f"(d[2]), "+f"(d[3]), "+f"(d[4]), "+f"(d[5]), "+f"(d[6]), "+f"(d[7]), "+f"(d[8]), "+f"(d[9]), "+f"(d[10]), "+f"(d[11]), "+f"(d[12]), "+f"(d[13]), "+f"(d[14]), "+f"(d[15]), "+f"(d[16]), "+f"(d[17]), "+f"(d[18]), "+f"(d[19]), "+f"(d[20]), "+f"(d[21]), "+f"(d[22]), "+f"(d[23]), "+f"(d[24]), "+f"(d[25]), "+f"(d[26]), "+f"(d[27]), "+f"(d[28]), "+f"(d[29]), "+f"(d[30]), "+f"(d[31])
                 : "l"(adesc), "l"(bdesc));
}
__device__ __forceinline__ void wgmma_n72_ss(float (&d)[36], uint64_t adesc, uint64_t bdesc) {
    asm volatile("{\n.reg .pred p;\nsetp.eq.b32 p, 0, 0;\n"
                 "wgmma.mma_async.sync.aligned.m64n72k16.f32.bf16.bf16 {%0,%1,%2,%3,%4,%5,%6,%7,%8,%9,%10,%11,%12,%13,%14,%15,%16,%17,%18,%19,%20,%21,%22,%23,%24,%25,%26,%27,%28,%29,%30,%31,%32,%33,%34,%35}, %36, %37, p, 1, 1, 1, 0;\n}"
                 : "+f"(d[0]), "+f"(d[1]), "+f"(d[2]), "+f"(d[3]), "+f"(d[4]), "+f"(d[5]), "+f"(d[6]), "+f"(d[7]), "+f"(d[8]), "+f"(d[9]), "+f"(d[10]), "+f"(d[11]), "+f"(d[12]), "+f"(d[13]), "+f"(d[14]), "+f"(d[15]), "+f"(d[16]), "+f"(d[17]), "+f"(d[18]), "+f"(d[19]), "+f"(d[20]), "+f"(d[21]), "+f"(d[22]), "+f"(d[23]), "+f"(d[24]), "+f"(d[25]), "+f"(d[26]), "+f"(d[27]), "+f"(d[28]), "+f"(d[29]), "+f"(d[30]), "+f"(d[31]), "+f"(d[32]), "+f"(d[33]), "+f"(d[34]), "+f"(d[35])
                 : "l"(adesc), "l"(bdesc));
}
__device__ __forceinline__ void tma_2d(uint32_t dst, const CUtensorMap* tm, int c0, int c1, uint32_t mbar) {
    asm volatile("cp.async.bulk.tensor.2d.shared::cluster.global.tile.mbarrier::complete_tx::bytes [%0], [%1, {%2, %3}], [%4];"
                 :: "r"(dst), "l"(tm), "r"(c0), "r"(c1), "r"(mbar) : "memory");
}

__device__ __forceinline__ void bulk_g2s(uint32_t dst, const void* src, uint32_t bytes, uint32_t mbar) {
    asm volatile("cp.async.bulk.shared::cluster.global.mbarrier::complete_tx::bytes [%0], [%1], %2, [%3];"
                 :: "r"(dst), "l"(src), "r"(bytes), "r"(mbar) : "memory");
}
__device__ __forceinline__ void bulk_g2s_h(uint32_t dst, const void* src, uint32_t bytes, uint32_t mbar, uint64_t pol) {
    asm volatile("cp.async.bulk.shared::cluster.global.mbarrier::complete_tx::bytes.L2::cache_hint [%0], [%1], %2, [%3], %4;"
                 :: "r"(dst), "l"(src), "r"(bytes), "r"(mbar), "l"(pol) : "memory");
}
__device__ __forceinline__ void tma_2d_mc(uint32_t dst, const CUtensorMap* tm, int c0, int c1, uint32_t mbar) {
    asm volatile("cp.async.bulk.tensor.2d.shared::cluster.global.tile.mbarrier::complete_tx::bytes.multicast::cluster [%0], [%1, {%2, %3}], [%4], %5;"
                 :: "r"(dst), "l"(tm), "r"(c0), "r"(c1), "r"(mbar), "h"((unsigned short)7) : "memory");
}
__device__ __forceinline__ void bulk_s2s(uint32_t dst, uint32_t src, uint32_t bytes, uint32_t mbar) {
    asm volatile("cp.async.bulk.shared::cluster.shared::cta.mbarrier::complete_tx::bytes [%0], [%1], %2, [%3];"
                 :: "r"(dst), "r"(src), "r"(bytes), "r"(mbar) : "memory");
}
__device__ __forceinline__ void wgmma_n40_ss(float (&d)[20], uint64_t adesc, uint64_t bdesc, int scale_d) {
    asm volatile("{\n.reg .pred p;\nsetp.ne.b32 p, %22, 0;\n"
                 "wgmma.mma_async.sync.aligned.m64n40k16.f32.bf16.bf16 {%0,%1,%2,%3,%4,%5,%6,%7,%8,%9,%10,%11,%12,%13,%14,%15,%16,%17,%18,%19}, %20, %21, p, 1, 1, 1, 1;\n}"
                 : "+f"(d[0]), "+f"(d[1]), "+f"(d[2]), "+f"(d[3]), "+f"(d[4]), "+f"(d[5]), "+f"(d[6]), "+f"(d[7]),
                   "+f"(d[8]), "+f"(d[9]), "+f"(d[10]), "+f"(d[11]), "+f"(d[12]), "+f"(d[13]), "+f"(d[14]), "+f"(d[15]),
                   "+f"(d[16]), "+f"(d[17]), "+f"(d[18]), "+f"(d[19])
                 : "l"(adesc), "l"(bdesc), "r"(scale_d));
}
__device__ __forceinline__ void wgmma_n64_z(float (&d)[32], const uint32_t (&a)[4], uint64_t bdesc) {
    asm volatile("{\n.reg .pred p;\nsetp.ne.b32 p, 0, 0;\n"
                 "wgmma.mma_async.sync.aligned.m64n64k16.f32.bf16.bf16 {%0,%1,%2,%3,%4,%5,%6,%7,%8,%9,%10,%11,%12,%13,%14,%15,%16,%17,%18,%19,%20,%21,%22,%23,%24,%25,%26,%27,%28,%29,%30,%31}, {%32,%33,%34,%35}, %36, p, 1, 1, 0;\n}"
                 : "=f"(d[0]), "=f"(d[1]), "=f"(d[2]), "=f"(d[3]), "=f"(d[4]), "=f"(d[5]), "=f"(d[6]), "=f"(d[7]),
                   "=f"(d[8]), "=f"(d[9]), "=f"(d[10]), "=f"(d[11]), "=f"(d[12]), "=f"(d[13]), "=f"(d[14]), "=f"(d[15]),
                   "=f"(d[16]), "=f"(d[17]), "=f"(d[18]), "=f"(d[19]), "=f"(d[20]), "=f"(d[21]), "=f"(d[22]), "=f"(d[23]),
                   "=f"(d[24]), "=f"(d[25]), "=f"(d[26]), "=f"(d[27]), "=f"(d[28]), "=f"(d[29]), "=f"(d[30]), "=f"(d[31])
                 : "r"(a[0]), "r"(a[1]), "r"(a[2]), "r"(a[3]), "l"(bdesc));
}
__device__ __forceinline__ void wgmma_n64(float (&d)[32], const uint32_t (&a)[4], uint64_t bdesc, int scale_d) {
    asm volatile("{\n.reg .pred p;\nsetp.ne.b32 p, %37, 0;\n"
                 "wgmma.mma_async.sync.aligned.m64n64k16.f32.bf16.bf16 {%0,%1,%2,%3,%4,%5,%6,%7,%8,%9,%10,%11,%12,%13,%14,%15,%16,%17,%18,%19,%20,%21,%22,%23,%24,%25,%26,%27,%28,%29,%30,%31}, {%32,%33,%34,%35}, %36, p, 1, 1, 0;\n}"
                 : "+f"(d[0]), "+f"(d[1]), "+f"(d[2]), "+f"(d[3]), "+f"(d[4]), "+f"(d[5]), "+f"(d[6]), "+f"(d[7]),
                   "+f"(d[8]), "+f"(d[9]), "+f"(d[10]), "+f"(d[11]), "+f"(d[12]), "+f"(d[13]), "+f"(d[14]), "+f"(d[15]),
                   "+f"(d[16]), "+f"(d[17]), "+f"(d[18]), "+f"(d[19]), "+f"(d[20]), "+f"(d[21]), "+f"(d[22]), "+f"(d[23]),
                   "+f"(d[24]), "+f"(d[25]), "+f"(d[26]), "+f"(d[27]), "+f"(d[28]), "+f"(d[29]), "+f"(d[30]), "+f"(d[31])
                 : "r"(a[0]), "r"(a[1]), "r"(a[2]), "r"(a[3]), "l"(bdesc), "r"(scale_d));
}

constexpr int SB_FULL = 0, SB_EMPTY = 64, SB_QKF = 128, SB_VF = 144, SB_QKE = 160, SB_VE = 176, SB_OF = 192, SB_WO = 208  , SB_TICK = 216, SB_SEEN = 224, SB_FI = 232, SB_REQ = 240;
constexpr int AT_0 = 256, AT_ST = 10240 + 2 * 9216;
constexpr int FS_A = 58368;
constexpr int FS_P = FS_A + 131072;
constexpr int FS_I = FS_P + 16384;
constexpr int FS_O = FS_I + 12288;
constexpr int FS_Z = FS_O + 12288, FS_G = AT_0 + 2 * AT_ST;
constexpr int SIDE_SMEM = FS_Z + 2048;
static_assert(SIDE_SMEM <= 232448 && FS_G + 128 <= FS_A && FS_A + SD_SMEM <= SIDE_SMEM, "smem");

__device__ __forceinline__ void wg_wait1() { asm volatile("wgmma.wait_group.sync.aligned 1;" ::: "memory"); }
__device__ __forceinline__ void mbar_arrive(uint32_t bar) { asm volatile("mbarrier.arrive.shared::cta.b64 _, [%0];" :: "r"(bar) : "memory"); }
__device__ __forceinline__ void wait_cnt_rlx(const unsigned* p, unsigned target, bool urgent) {
    unsigned it = 0, v;
    while (true) {
        asm volatile("ld.relaxed.gpu.global.u32 %0, [%1];" : "=r"(v) : "l"(p) : "memory");
        if ((int)(v - target) >= 0 || ++it >= SPIN_LIMIT) break;
        if (!urgent) __nanosleep(RLX_SLEEP);
    }
}

__device__ __forceinline__ float xrow_softmax(float (&sc)[20], uint32_t (&p)[5], int wq, int lane) {
    constexpr float EC = (float)(1.4426950408889634 * 0.08838834764831845);
    const int lim = 8 * wq + (lane >> 2) - 2 * (lane & 3);
    float mx = fmaxf(sc[0], sc[1]);
#pragma unroll
    for (int j = 1; j < 5; j++) {
        sc[4 * j] = 8 * j - 8 > lim ? -INFINITY : sc[4 * j];
        sc[4 * j + 1] = 8 * j - 7 > lim ? -INFINITY : sc[4 * j + 1];
    }
    mx = fmaxf(fmaxf(mx, fmaxf(fmaxf(sc[4], sc[5]), fmaxf(sc[8], sc[9]))), fmaxf(fmaxf(sc[12], sc[13]), fmaxf(sc[16], sc[17])));
    {
        const float m1 = __shfl_xor_sync(0xffffffffu, mx, 1), m2 = __shfl_xor_sync(0xffffffffu, mx, 2), m3 = __shfl_xor_sync(0xffffffffu, mx, 3);
        mx = fmaxf(fmaxf(mx, m1), fmaxf(m2, m3));
    }
    float sum = 0.f;
#pragma unroll
    for (int j = 0; j < 5; j++) {
        float e0, e1;
        asm("ex2.approx.ftz.f32 %0, %1;" : "=f"(e0) : "f"((sc[4 * j] - mx) * EC));
        asm("ex2.approx.ftz.f32 %0, %1;" : "=f"(e1) : "f"((sc[4 * j + 1] - mx) * EC));
        p[j] = pack_bf16(e0, e1);
        sum += e0 + e1;
    }
    return sum;
}
__device__ __forceinline__ float xrow_inv(float sum) {
    sum += __shfl_xor_sync(0xffffffffu, sum, 1);
    sum += __shfl_xor_sync(0xffffffffu, sum, 2);
    float r;
    asm("rcp.approx.ftz.f32 %0, %1;" : "=f"(r) : "f"(sum));
    return r;
}

__device__ __forceinline__ void stsm_x4(uint32_t addr, uint32_t r0, uint32_t r1, uint32_t r2, uint32_t r3) {
    asm volatile("stmatrix.sync.aligned.m8n8.x4.shared.b16 [%0], {%1,%2,%3,%4};" :: "r"(addr), "r"(r0), "r"(r1), "r"(r2), "r"(r3) : "memory");
}
__device__ __forceinline__ void xrow_pv(uint32_t (&ob)[16], const uint32_t (&p)[5], float psum, uint32_t vt) {
    float o[32];
    const uint64_t dv = smem_desc(vt, 2048, 128);
    uint32_t pa[6][4];
#pragma unroll
    for (int i = 0; i < 6; i++) {
        const int ks = i >> 1, hf = i & 1;
        pa[i][hf] = p[2 * ks]; pa[i][hf ^ 1] = 0u;
        pa[i][2 + hf] = ks < 2 ? p[ks < 2 ? 2 * ks + 1 : 0] : 0u; pa[i][3 - hf] = 0u;
    }
    wg_fence();
#pragma unroll
    for (int i = 0; i < 6; i++) { if (i == 0) wgmma_n64_z(o, pa[0], dv); else wgmma_n64(o, pa[i], dv + (uint64_t)((i & 1) * 64 + (i >> 1) * 256), 1); }
    wg_commit();
    const float inv = xrow_inv(psum);
    wg_wait0();
#pragma unroll
    for (int i = 0; i < 8; i++) { ob[i] = pack_bf16(o[4 * i] * inv, o[4 * i + 1] * inv); ob[8 + i] = pack_bf16(o[4 * i + 2] * inv, o[4 * i + 3] * inv); }
}
__device__ __forceinline__ uint32_t h2_to_bf2(uint32_t h) {
    uint32_t r;
    asm("{\n.reg .f16 l, h;\n.reg .f32 a, b;\nmov.b32 {l, h}, %1;\ncvt.f32.f16 a, l;\ncvt.f32.f16 b, h;\ncvt.rn.bf16x2.f32 %0, b, a;\n}" : "=r"(r) : "r"(h));
    return r;
}
__device__ __forceinline__ uint32_t max_abs2(uint32_t a, uint32_t b) { uint32_t r; asm("max.NaN.xorsign.abs.bf16x2 %0, %1, %2;" : "=r"(r) : "r"(a), "r"(b)); return r; }
__device__ __forceinline__ uint32_t movm(uint32_t v) {
    uint32_t r; asm volatile("movmatrix.sync.aligned.m8n8.trans.b16 %0, %1;" : "=r"(r) : "r"(v)); return r;
}
__device__ __forceinline__ void bar_arrive(int id, int n) { asm volatile("bar.arrive %0, %1;" :: "r"(id), "r"(n) : "memory"); }
__device__ __forceinline__ void lds64(uint32_t& a, uint32_t& b, uint32_t addr) {
    asm volatile("ld.shared.v2.u32 {%0,%1}, [%2];" : "=r"(a), "=r"(b) : "r"(addr) : "memory");
}
__device__ __forceinline__ void lds64f(float& a, float& b, uint32_t addr) {
    asm volatile("ld.shared.v2.f32 {%0,%1}, [%2];" : "=f"(a), "=f"(b) : "r"(addr) : "memory");
}
__device__ __forceinline__ void st_async64(uint32_t addr, uint32_t a, uint32_t b, uint32_t mbar) {
    asm volatile("st.async.weak.shared::cluster.mbarrier::complete_tx::bytes.v2.b32 [%0], {%1,%2}, [%3];" :: "r"(addr), "r"(a), "r"(b), "r"(mbar) : "memory");
}
__device__ __forceinline__ void mma_z(float (&d)[4], const uint32_t (&a)[4], uint32_t b0, uint32_t b1) {
    asm volatile("mma.sync.aligned.m16n8k16.row.col.f32.bf16.bf16.f32 {%0,%1,%2,%3}, {%4,%5,%6,%7}, {%8,%9}, {%10,%10,%10,%10};"
                 : "=f"(d[0]), "=f"(d[1]), "=f"(d[2]), "=f"(d[3])
                 : "r"(a[0]), "r"(a[1]), "r"(a[2]), "r"(a[3]), "r"(b0), "r"(b1), "f"(0.f));
}
__device__ __forceinline__ void mma_k8(float (&d)[4], uint32_t a0, uint32_t a1, uint32_t b) {
    asm volatile("mma.sync.aligned.m16n8k8.row.col.f32.bf16.bf16.f32 {%0,%1,%2,%3}, {%4,%5}, {%6}, {%0,%1,%2,%3};"
                 : "+f"(d[0]), "+f"(d[1]), "+f"(d[2]), "+f"(d[3]) : "r"(a0), "r"(a1), "r"(b));
}
__global__ void __launch_bounds__(512, 1) k_side(const __grid_constant__ CUtensorMap tmo, const bf16* __restrict__ x, const bf16* __restrict__ logA, const bf16* __restrict__ Aim,
                                                 const bf16* __restrict__ Cre, const bf16* __restrict__ Cim, const bf16* __restrict__ logdt,
                                                 const bf16* __restrict__ Wo, const bf16* __restrict__ dskip, const bf16* __restrict__ gw,
                                                 bf16* __restrict__ out) {
    extern __shared__ __align__(1024) unsigned char smem_raw[];
    const uint32_t sbase = smem_u32(smem_raw);
    const int tid = threadIdx.x, warp = __shfl_sync(0xffffffffu, tid >> 5, 0), lane = tid & 31, cta = blockIdx.x;
    const int cb = cta >> 2, kq = cta & 3;
    if (tid == 0) {
        for (int i = 0; i < 8; i++) { mbar_init(sbase + SB_FULL + 8 * i, 1); mbar_init(sbase + SB_EMPTY + 8 * i, 4); }
        for (int i = 0; i < 2; i++) {
            mbar_init(sbase + SB_QKF + 8 * i, 1); mbar_init(sbase + SB_VF + 8 * i, 1); mbar_init(sbase + SB_QKE + 8 * i, 4);
            mbar_init(sbase + SB_VE + 8 * i, 1); mbar_init(sbase + SB_OF + 8 * i, 4);
        }
        mbar_init(sbase + SB_WO, 1);
        mbar_init(sbase + SB_WO + 40, 1);
        mbar_init(sbase + SB_FI, 1);
        mbar_init(sbase + SB_REQ, 4);
        *reinterpret_cast<uint2*>(smem_raw + SB_TICK) = make_uint2(0u, 0u);
        *reinterpret_cast<uint32_t*>(smem_raw + SB_SEEN) = 0u;
        asm volatile("fence.mbarrier_init.release.cluster;" ::: "memory");
    }
    TS3(0);
    asm volatile("fence.proxy.async;" ::: "memory");
    __syncthreads();
    auto epoch = []() {
        unsigned ep;
        asm volatile("ld.volatile.global.u32 %0, [%1];" : "=r"(ep) : "l"(&g_epoch) : "memory");
        return ep + 1u;
    };
    if (warp >= 12) {
      asm volatile("setmaxnreg.dec.sync.aligned.u32 40;");
      {
        uint32_t gwv[9];
#pragma unroll
        for (int i = 0; i < 9; i++) gwv[i] = reinterpret_cast<const uint32_t*>(gw)[lane + 32 * i];
#pragma unroll 1
        for (int i = 0; i < 8; i++) {
            uint32_t xv[2][9];
            float sm[2];
#pragma unroll
            for (int j = 0; j < 2; j++) {
                const int t = min(cta * 57 + 8 * i + 4 * j + warp - 12, S_LEN - 1);
#pragma unroll
                for (int k = 0; k < 9; k++) xv[j][k] = reinterpret_cast<const uint32_t*>(x + t * DM)[lane + 32 * k];
            }
#pragma unroll
            for (int j = 0; j < 2; j++) {
                sm[j] = 0.f;
#pragma unroll
                for (int k = 0; k < 9; k++) {
                    const uint32_t pr = bf2_mul(xv[j][k], gwv[k]);
                    sm[j] += __uint_as_float(pr << 16) + __uint_as_float(pr & 0xffff0000u);
                }
            }
            float v = (lane < 16 ? sm[0] : sm[1]) + __shfl_xor_sync(0xffffffffu, lane < 16 ? sm[1] : sm[0], 16);
#pragma unroll
            for (int o = 8; o; o >>= 1) v += __shfl_xor_sync(0xffffffffu, v, o);
            const float gv = 1.f / (1.f + expf(-bf16r(v)));
            const int tt = 8 * i + 4 * (lane >> 4) + warp - 12;
            if ((lane & 15) == 0 && tt < 57 && cta * 57 + tt < S_LEN) g_gate[cta * 57 + tt] = __float2bfloat16_rn(gv);
        }
        named_bar(2, 128);
        if (tid == 480) {
            __threadfence();
            asm volatile("red.relaxed.gpu.global.add.u32 [%0], 1;" :: "l"(&g_gcnt[0]) : "memory");
        }
        __syncwarp();
      }
      const unsigned ep = epoch();
      if (warp == 12 || warp == 15) {
        const int pi = warp == 12 ? 0 : 1;
        auto stage_wo = [&](int i0, int i1) {
            if (lane == 0) {
                fence_async();
#pragma unroll 1
                for (int i = i0; i < i1; i++) {
                    gate(sbase + SB_TICK);
                    tma_2d(sbase + FS_A + i * 16384, &tmo, cb * 64, kq * 1024 + i * 128, sbase + SB_WO + (i >> 2) * 40);
                    if (WO_SLEEP > 0) __nanosleep(WO_SLEEP);
                }
            }
            __syncwarp();
        };
        if (lane == 0) mbar_expect(sbase + SB_WO + pi * 40, 65536);
        if (pi == 0) {
            named_bar(11, 288);
            stage_wo(0, 2);
        }
        named_bar(3, 320);
        if (pi == 0) stage_wo(2, 4);
        else {
            if (WO_LAG > 0) __nanosleep(WO_LAG);
            stage_wo(4, 8);
        }
        if (lane == 0) TSS(17, 2 + pi);
        if (tid == 480) {
            __threadfence();
            asm volatile("red.relaxed.gpu.global.add.u32 [%0], 1;" :: "l"(&g_gcnt[32]) : "memory");
        }
        __syncwarp();
        named_bar(12 + pi, 160);
        if (lane == 0) {
            const int kb = 2 * kq + pi;
            fence_async();
            for (int pr = 0; pr < NSEG / 2; pr++) {
                const bool gon = pr < NSEG / 2 - UNGATE_G;
                wait_cnt_rlx(&g_prog[kb * 64 + pr], 8u * ep, pr >= NSEG / 2 - 2);
                if (pi == 0) asm volatile("st.volatile.shared.u32 [%0], %1;" :: "r"(sbase + SB_SEEN), "r"(pr + 1) : "memory");
                if (pr >= 30 && pi == 0) TSS(4 + pr - 30, 0);
                if (pr == 31) TS3P(26);
                if (pr == 30) TS3P(1);
#pragma unroll
                for (int j = 0; j < 4; j++) {
                    const int st = 4 * pi + j;
                    mbar_wait_long(sbase + SB_EMPTY + 8 * st, ((uint32_t)pr & 1u) ^ 1u);
                    mbar_expect(sbase + SB_FULL + 8 * st, 16384);
                    if (gon) gate(sbase + SB_TICK);
                    bulk_g2s(sbase + FS_A + st * 16384, g_ox + ((size_t)(pr * NH + 4 * kb + j)) * 8192, 16384, sbase + SB_FULL + 8 * st);
                }
            }
        }
        __syncwarp();
      } else if (warp == 13) {
        if (lane == 0) {
            const uint64_t pol = policy_evict_first();
            bool next_ok = false;
            for (int seg = 0; seg < NATT; seg++) {
                const uint32_t st = seg & 1, ph = (uint32_t)(seg >> 1) & 1u, ab = sbase + AT_0 + st * AT_ST;
                if (!next_ok) {
                    const unsigned* fp = &g_flag[(cta & (NH - 1)) * NSEG + seg];
                    unsigned it = 0, v0, v1;
                    while (true) {
                        asm volatile("ld.relaxed.gpu.global.u32 %0, [%1];" : "=r"(v0) : "l"(fp) : "memory");
                        asm volatile("ld.relaxed.gpu.global.u32 %0, [%1+4];" : "=r"(v1) : "l"(fp) : "memory");
                        read_tick(sbase + SB_TICK);
                        if ((int)(v0 - 3u * ep) >= 0 || ++it >= SPIN_LIMIT) break;
                        if (seg < NSEG - UNGATE || cta >= NH) __nanosleep(RLX_SLEEP);
                    }
                    next_ok = (int)(v1 - 3u * ep) >= 0;
                } else next_ok = false;
                if (cta < NH) {
                    TSA(seg, 0);
                    mbar_wait_long(sbase + SB_QKE + 8 * st, ph ^ 1u);
                    TSA(seg, 1);
                    mbar_expect(sbase + SB_QKF + 8 * st, 2 * 9216);
                    if (seg < NSEG - UNGATE) gate(sbase + SB_TICK, GL_A, GL_B);
                    TSA(seg, 2);
                    bulk_g2s_h(ab + 10240, &g_qkv[seg][cta][0][1024], 9216, sbase + SB_QKF + 8 * st, pol);
                    bulk_g2s_h(ab + 10240 + 9216, &g_qkv[seg][cta][1][1024], 9216, sbase + SB_QKF + 8 * st, pol);
                    mbar_wait_long(sbase + SB_VE + 8 * st, ph ^ 1u);
                    mbar_expect(sbase + SB_VF + 8 * st, 10240);
                    if (seg < NSEG - UNGATE) gate(sbase + SB_TICK, GL_A, GL_B);
                    TSA(seg, 3);
                    bulk_g2s_h(ab, &g_qkv[seg][cta][2][0], 10240, sbase + SB_VF + 8 * st, pol);
                }
            }
        }
        __syncwarp();
      } else if (warp == 14) {
        if (lane == 0) {
            int seg = cta < NH ? 0 : NATT, p = 0;
            unsigned it = 0;
            while ((seg < NATT || p < NSEG / 2 - 1) && ++it < 16 * SPIN_LIMIT) {
                if (p < NSEG / 2 - 1 && mbar_test(sbase + SB_REQ, (uint32_t)p & 1u)) {
                    if (p == 0) { wait_cnt(&g_gcnt[32], SD_NCTA * ep); asm volatile("fence.proxy.async;" ::: "memory"); }
                    mbar_expect(sbase + SB_FI, (p < NSEG / 2 - 2 ? 12288 : 2048 + 32) + 2048 + 32);
                    if (p < NSEG / 2 - UNGATE_G - 1) gate(sbase + SB_TICK);
                    if (p < NSEG / 2 - 2) bulk_g2s(sbase + FS_I, &g_fp[p & 7][cta][0][0], 12288, sbase + SB_FI);
                    else {
                        bulk_g2s(sbase + FS_I, g_y + ((p * 4 + 4 + kq) * DM + cb * 64) * 16, 2048, sbase + SB_FI);
                        bulk_g2s(sbase + FS_G + 32, g_gate + p * 64 + 64 + kq * 16, 32, sbase + SB_FI);
                    }
                    bulk_g2s(sbase + FS_Z, g_y + ((p * 4 + kq) * DM + cb * 64) * 16, 2048, sbase + SB_FI);
                    bulk_g2s(sbase + FS_G, g_gate + p * 64 + kq * 16, 32, sbase + SB_FI);
                    p++;
                } else if (seg < NATT && mbar_test(sbase + SB_OF + 8 * (seg & 1), (uint32_t)(seg >> 1) & 1u)) {
                    const uint32_t st = seg & 1, ab = sbase + AT_0 + st * AT_ST;
                    TSA(seg, 5);
                    if (seg < NSEG - UNGATE) gate(sbase + SB_TICK, GS_A, GS_B);
                    TSA(seg, 6);
                    unsigned char* dst = reinterpret_cast<unsigned char*>(g_ox) + ((size_t)((seg >> 1) * NH + cta)) * 16384 + (seg & 1) * 8192;
                    asm volatile("cp.async.bulk.global.shared::cta.bulk_group [%0], [%1], 8192;" :: "l"(dst), "r"(ab) : "memory");
                    asm volatile("cp.async.bulk.commit_group;" ::: "memory");
                    asm volatile("cp.async.bulk.wait_group.read 0;" ::: "memory");
                    mbar_arrive(sbase + SB_VE + 8 * st);
                    asm volatile("cp.async.bulk.wait_group 0;" ::: "memory");
                    asm volatile("red.relaxed.gpu.global.add.u32 [%0], 1;" :: "l"(&g_prog[(cta >> 2) * 64 + (seg >> 1)]) : "memory");
                    TSA(seg, 7);
                    seg++;
                } else if (seg < NSEG - UNGATE) __nanosleep(W14_SLEEP);
            }
        }
        __syncwarp();
      }
    } else if (warp >= 8) {
        asm volatile("setmaxnreg.dec.sync.aligned.u32 88;");
          s4d_stage_u(smem_raw + FS_A, x, tid - 256);
        const int wq = warp - 8;
        for (int seg = 0; seg < (cta < NH ? NATT : 0); seg++) {
            const uint32_t st = seg & 1, ph = (uint32_t)(seg >> 1) & 1u, ab = sbase + AT_0 + st * AT_ST;
            float sc[20];
            if (seg < NSEG - UNGATE) mbar_wait_long(sbase + SB_QKF + 8 * st, ph); else mbar_wait(sbase + SB_QKF + 8 * st, ph);
            if (tid == 256) TSA(seg, 4);
            {
                const uint64_t da = smem_desc(ab + 10240 + 1024, 128, 1024), db = smem_desc(ab + 10240, 128, 2048);
                wg_fence();
#pragma unroll
                for (int ks = 0; ks < 8; ks++) wgmma_n40_ss(sc, da + (uint64_t)((ks >> 2) * 576 + (ks & 3) * 16), db + (uint64_t)((ks >> 2) * 576 + (ks & 3) * 16), ks > 0);
                wg_commit();
                wg_wait0();
            }
            if (lane == 0) mbar_arrive(sbase + SB_QKE + 8 * st);
            uint32_t p[5], ob[16];
            const float psum = xrow_softmax(sc, p, wq, lane);
            mbar_wait(sbase + SB_VF + 8 * st, ph);
            xrow_pv(ob, p, psum, ab);
            named_bar(6, 128);
#pragma unroll
            for (int i = 0; i < 4; i++) stsm_x4(ab + wq * 2048 + i * 512 + lane * 16, ob[4 * i], ob[4 * i + 1], ob[4 * i + 2], ob[4 * i + 3]);
            fence_async();
            __syncwarp();
            if (lane == 0) mbar_arrive(sbase + SB_OF + 8 * st);
        }
    } else {
        asm volatile("setmaxnreg.inc.sync.aligned.u32 192;");
        const int wg = warp >> 2, wq = warp & 3;
        s4d_phase(smem_raw + FS_A, x, logA, Aim, Cre, Cim, logdt, dskip, Wo + (size_t)((2 * kq + wg) * 512) * DM + cb * 64);
        TS3(2);
        if (lane == 0) TSS(16, warp);
        named_bar(3, 320);
        if (tid == 0) TSS(17, 0);
        uint32_t wa[32][4];
        mbar_wait_long(sbase + SB_WO + wg * 40, 0);
        if (tid == 0) TSS(17, 1);
        {
            const uint32_t a = sbase + FS_A + wg * 65536 + ((lane >> 4) * 8 + (lane & 7)) * 128 + (((wq * 2 + ((lane >> 3) & 1)) ^ (lane & 7)) << 4);
#pragma unroll
            for (int ks = 0; ks < 32; ks++) ldsm_x4_t(wa[ks], a + ks * 2048);
        }
        named_bar(12 + wg, 160);
        TS3(3);
        if (tid == 0) TSS(17, 4);
        auto product = [&](float (&acc)[32], int pr, const int wg) {
                if (pr + wg > 0) named_bar(4 + wg, 256);
                const uint64_t db = smem_desc(sbase + FS_A + wg * 65536, 128, 2048);
                TSG(0);
#pragma unroll
                for (int j = 0; j < 4; j++) {
                    mbar_wait(sbase + SB_FULL + 8 * (4 * wg + j), (uint32_t)pr & 1u);
                    if (j == 0) TSG(1);
                    if (j == 3) TSG(2);
                    wg_fence();
#pragma unroll
                    for (int ks = 0; ks < 8; ks++) {
                        if ((j | ks) == 0) wgmma_n64_z(acc, wa[0], db);
                        else wgmma_n64(acc, wa[8 * j + ks], db + (uint64_t)(j * 1024 + ks * 16), 1);
                    }
                    wg_commit();
                    if (j == 3 && pr + wg < NSEG / 2) bar_arrive(4 + (wg ^ 1), 256);
                    if (j > 0) { wg_wait1(); if (lane == 0) mbar_arrive(sbase + SB_EMPTY + 8 * (4 * wg + j - 1)); }
                }
                wg_wait0();
                if (pr == 31) TS3W(27);
                TSG(3);
                if (lane == 0) mbar_arrive(sbase + SB_EMPTY + 8 * (4 * wg + 3));
        };
        if (wg == 1) {
            for (int pr = 0; pr < NSEG / 2; pr++) {
                uint32_t t16 = (uint32_t)(wq * 32 + lane) * 16u;
                asm volatile("" : "+r"(t16));
                float acc[32];
                product(acc, pr, 1);
                    uint32_t tag = ((uint32_t)(pr >> 3) & 1u) ^ 1u;
                    tag = __shfl_sync(0xffffffffu, tag, lane);
                    named_bar(8, 256);
                    unsigned char* dst = reinterpret_cast<unsigned char*>(&g_fp[pr & 7][4 * cb][2 * kq - 2][0]) + t16;
                    const uint32_t own = sbase + FS_O + (pr % 3) * 4096 + t16;
#pragma unroll
                    for (int q = 0; q < 8; q++) {
                        float4 p;
                        asm volatile("ld.shared.v4.f32 {%0,%1,%2,%3}, [%4];" : "=f"(p.x), "=f"(p.y), "=f"(p.z), "=f"(p.w) : "r"(sbase + FS_P + t16 + q * 2048) : "memory");
                        acc[4 * q] = __uint_as_float((__float_as_uint(acc[4 * q] + p.x) & ~1u) | tag); acc[4 * q + 1] = __uint_as_float((__float_as_uint(acc[4 * q + 1] + p.y) & ~1u) | tag);
                        acc[4 * q + 2] = __uint_as_float((__float_as_uint(acc[4 * q + 2] + p.z) & ~1u) | tag); acc[4 * q + 3] = __uint_as_float((__float_as_uint(acc[4 * q + 3] + p.w) & ~1u) | tag);
                    }
#pragma unroll
                    for (int q = 0; q < 8; q++) {
                        asm volatile("{\n.reg .pred p;\nsetp.ne.s32 p, %5, %6;\n@p st.volatile.global.v4.f32 [%0], {%1,%2,%3,%4};\n@!p st.shared.v4.f32 [%7], {%1,%2,%3,%4};\n}"
                                     :: "l"(dst + (q & 1) * 2048), "f"(acc[4 * q]), "f"(acc[4 * q + 1]), "f"(acc[4 * q + 2]), "f"(acc[4 * q + 3]), "r"(q >> 1), "r"(kq),
                                        "r"(own + (q & 1) * 2048) : "memory");
                        if (q & 1) dst += (q >> 1) == kq ? 12288 + 4096 : 12288;
                    }
                    bar_arrive(9, 256);
                    if (pr == 31) TS3W(28);
                TSG(4);
            }
        } else {
          int nsync = 0;
          int np = 1, nf = 0, pr = 0, pf = -1;
          while (true) {
            uint32_t t16 = (uint32_t)(wq * 32 + lane) * 16u;
            asm volatile("" : "+r"(t16));
            if (pr < 0) {
                if (nsync <= pf) { named_bar(9, 256); nsync++; }
                if (lane == 0 && pf < NSEG / 2 - 1) mbar_arrive(sbase + SB_REQ);
            } else {
                float acc[32];
                product(acc, pr, 0);
                if (nsync < pr) { named_bar(9, 256); nsync++; }
#pragma unroll
                for (int q = 0; q < 8; q++)
                    asm volatile("st.shared.v4.f32 [%0], {%1,%2,%3,%4};" :: "r"(sbase + FS_P + t16 + q * 2048), "f"(acc[4 * q]), "f"(acc[4 * q + 1]), "f"(acc[4 * q + 2]), "f"(acc[4 * q + 3]) : "memory");
                bar_arrive(8, 256);
                TSG(4);
            }
            uint32_t w[4] = {0u, 0u, 0u, 0u};
            const int pc = pf;
            if (pf >= 0) {
                const uint32_t tag = ((uint32_t)(pf >> 3) & 1u) ^ 1u;
                uint4 v[8];
                unsigned n = 0;
                const bool last = pf == NSEG / 2 - 1;
                const uint4* src = reinterpret_cast<const uint4*>(reinterpret_cast<const unsigned char*>(&g_fp[pf & 7][cta][0][0]) + t16);
                if (pf >= NSEG / 2 - 2) {
#pragma unroll
                    for (int r = 0; r < 6; r++) v[r] = ld_vol_u4(src + r * 128);
                    mbar_wait(sbase + SB_FI, 0u);
                } else {
                    mbar_wait(sbase + SB_FI, (uint32_t)pf & 1u);
#pragma unroll
                    for (int r = 0; r < 6; r++)
                        asm volatile("ld.shared.v4.u32 {%0,%1,%2,%3}, [%4];" : "=r"(v[r].x), "=r"(v[r].y), "=r"(v[r].z), "=r"(v[r].w) : "r"(sbase + t16 + FS_I + r * 2048) : "memory");
                }
                while (true) {
                    uint32_t any = 0u;
#pragma unroll
                    for (int r = 0; r < 6; r++) {
                        uint32_t c0_, c1_;
                        asm("lop3.b32 %0, %1, %2, %3, 0x7e;" : "=r"(c0_) : "r"(v[r].x), "r"(v[r].y), "r"(tag));
                        asm("lop3.b32 %0, %1, %2, %3, 0x7e;" : "=r"(c1_) : "r"(v[r].z), "r"(v[r].w), "r"(tag));
                        asm("lop3.b32 %0, %1, %2, %3, 0xfe;" : "=r"(any) : "r"(any), "r"(c0_), "r"(c1_));
                    }
                    if (!__any_sync(0xffffffffu, (any & 1u) != 0u) || ++n >= SPIN_LIMIT) break;
                    if (pf < NSEG / 2 - 2) __nanosleep(200);
#pragma unroll
                    for (int r = 0; r < 6; r++) v[r] = ld_vol_u4(src + r * 128);
                }
                if (pf == 31) TS3(29);
                TSG(5);
#pragma unroll
                for (int r = 6; r < 8; r++)
                    asm volatile("ld.shared.v4.u32 {%0,%1,%2,%3}, [%4];" : "=r"(v[r].x), "=r"(v[r].y), "=r"(v[r].z), "=r"(v[r].w)
                                 : "r"(sbase + t16 + FS_O + (pf % 3) * 4096 + (r - 6) * 2048) : "memory");
                uint32_t zv[4], gg[2];
                ldsm_x4_t(zv, sbase + (last ? FS_I : FS_Z) + (wq * 16 + (lane & 15)) * 32 + (lane >> 4) * 16);
#pragma unroll
                for (int k = 0; k < 2; k++) gg[k] = __byte_perm(*reinterpret_cast<const volatile unsigned short*>(smem_raw + FS_G + (last ? 32 : 0) + k * 16 + (lane >> 2) * 2), 0u, 0x1010);
#define PQS(k, f) (((__uint_as_float(v[k].f) + __uint_as_float(v[2 + k].f)) + __uint_as_float(v[4 + k].f)) + __uint_as_float(v[6 + k].f))
#pragma unroll
                for (int k = 0; k < 2; k++) {
                    w[2 * k] = bf2_add(bf2_mul(gg[k], movm(pack_bf16(PQS(k, x), PQS(k, y)))), zv[2 * k]);
                    w[2 * k + 1] = bf2_add(bf2_mul(gg[k], movm(pack_bf16(PQS(k, z), PQS(k, w)))), zv[2 * k + 1]);
                }
#undef PQS
            }
            const bool more = nf < NSEG / 2;
            if (more) {
                uint32_t r;
                asm volatile("{\n.reg .pred p, q;\n.reg .b32 v;\nld.volatile.shared.u32 v, [%1];\nsetp.gt.s32 p, v, %2;\nbar.red.or.pred q, 10, 128, p;\nselp.u32 %0, 1, 0, q;\n}"
                             : "=r"(r) : "r"(sbase + SB_SEEN), "r"(np) : "memory");
                const bool dop = np < NSEG / 2 && (__shfl_sync(0xffffffffu, r, 0) != 0u || nf == np || (np >= TM && nf + 1 >= np));
                TSG(6);
                pr = dop ? np++ : -1;
                pf = !dop || nf + (pr >= TM2 ? 1 : 2) <= pr ? nf++ : -1;
                if (dop && pf >= 0 && lane == 0) mbar_arrive(sbase + SB_REQ);
            }
            if (pc >= 0) {
                unsigned char* op = reinterpret_cast<unsigned char*>(out) + (uint32_t)((pc * 64 + kq * 16 + (lane >> 2)) * DM + cb * 64 + wq * 16 + 2 * (lane & 3)) * 2u;
#pragma unroll
                for (int k = 0; k < 4; k++) *reinterpret_cast<uint32_t*>(op + (k >> 1) * (16 * DM) + (k & 1) * 16) = w[k];
                if ((pc & 1) == 0) TS3(4 + pc / 2);
                if (pc == 31) TS3(25);
            }
            if (!more) break;
          }
        }
        if (cta == 0 && tid == 0) asm volatile("red.relaxed.gpu.global.add.u32 [%0], 1;" :: "l"(&g_epoch) : "memory");
    }
    asm volatile("griddepcontrol.wait;" ::: "memory");
}

template <class F>
__device__ __forceinline__ uint32_t poll_mem(const uint4* src, uint32_t dst, uint32_t t0, F next) {
    uint4 v[6];
    unsigned it = 0;
#pragma unroll
    for (int j = 0; j < 6; j++) v[j] = make_uint4(0u, 0u, 0u, 0u);
    while (clock32() - t0 < POLL_DELAY) {}
    FS(12, 0);
    bool more;
#pragma unroll 1
    do {
        asm volatile("{\n.reg .pred p<6>;\n"
                     "setp.ne.u32 p0, %3, 0x5000;\nsetp.ne.u32 p1, %7, 0x5000;\nsetp.ne.u32 p2, %11, 0x5000;\n"
                     "setp.ne.u32 p3, %15, 0x5000;\nsetp.ne.u32 p4, %19, 0x5000;\nsetp.ne.u32 p5, %23, 0x5000;\n"
                     "@p0 ld.volatile.global.v4.u32 {%0,%1,%2,%3}, [%24];\n@p1 ld.volatile.global.v4.u32 {%4,%5,%6,%7}, [%24+4096];\n"
                     "@p2 ld.volatile.global.v4.u32 {%8,%9,%10,%11}, [%24+8192];\n@p3 ld.volatile.global.v4.u32 {%12,%13,%14,%15}, [%24+12288];\n"
                     "@p4 ld.volatile.global.v4.u32 {%16,%17,%18,%19}, [%24+16384];\n@p5 ld.volatile.global.v4.u32 {%20,%21,%22,%23}, [%24+20480];\n}"
                     : "+r"(v[0].x), "+r"(v[0].y), "+r"(v[0].z), "+r"(v[0].w), "+r"(v[1].x), "+r"(v[1].y), "+r"(v[1].z), "+r"(v[1].w),
                       "+r"(v[2].x), "+r"(v[2].y), "+r"(v[2].z), "+r"(v[2].w), "+r"(v[3].x), "+r"(v[3].y), "+r"(v[3].z), "+r"(v[3].w),
                       "+r"(v[4].x), "+r"(v[4].y), "+r"(v[4].z), "+r"(v[4].w), "+r"(v[5].x), "+r"(v[5].y), "+r"(v[5].z), "+r"(v[5].w)
                     : "l"(src) : "memory");
        stsm_x4(dst, h2_to_bf2(v[0].x), h2_to_bf2(v[0].y), h2_to_bf2(v[0].z), h2_to_bf2(v[1].x));
        stsm_x4(dst + 512, h2_to_bf2(v[1].y), h2_to_bf2(v[1].z), h2_to_bf2(v[2].x), h2_to_bf2(v[2].y));
        const uint32_t all = ((v[0].w & v[1].w) & (v[2].w & v[3].w)) & (v[4].w & v[5].w);
        more = __any_sync(0xffffffffu, (all & 0x5000u) != 0x5000u && ++it < SPIN_LIMIT);
        stsm_x4(dst + 1024, h2_to_bf2(v[2].z), h2_to_bf2(v[3].x), h2_to_bf2(v[3].y), h2_to_bf2(v[3].z));
        asm volatile("stmatrix.sync.aligned.m8n8.x2.shared.b16 [%0], {%1,%2};" :: "r"(dst + 1536), "r"(h2_to_bf2(v[4].x)), "r"(h2_to_bf2(v[4].y)) : "memory");
        stsm_x4(dst + 1792, h2_to_bf2(v[4].z), h2_to_bf2(v[5].x), h2_to_bf2(v[5].y), h2_to_bf2(v[5].z));
        asm volatile("{\n.reg .pred p;\nsetp.eq.u32 p, %0, 0;\n@p bar.sync 1, 384;\n}" :: "r"((uint32_t)more) : "memory");
    } while (more);
    next();
    FS(13, it);
    FS(14, 0);
    uint32_t m = v[0].x, m1 = v[0].y, m2 = v[0].z;
#pragma unroll
    for (int j = 1; j < 6; j++) {
        asm volatile("max.NaN.xorsign.abs.f16x2 %0, %0, %1;" : "+r"(m) : "r"(v[j].x));
        asm volatile("max.NaN.xorsign.abs.f16x2 %0, %0, %1;" : "+r"(m1) : "r"(v[j].y));
        asm volatile("max.NaN.xorsign.abs.f16x2 %0, %0, %1;" : "+r"(m2) : "r"(v[j].z));
    }
    asm volatile("max.NaN.xorsign.abs.f16x2 %0, %0, %1;" : "+r"(m) : "r"(m1));
    asm volatile("max.NaN.xorsign.abs.f16x2 %0, %0, %1;" : "+r"(m) : "r"(m2));
    return h2_to_bf2(m) & 0x7fff7fffu;
}

template <int N> __device__ __forceinline__ void pad_code() {
#pragma unroll
    for (int i = 0; i < N; i++) asm volatile("pmevent 7;" ::: "memory");
}
template <bool V> struct Flag { static constexpr bool value = V; };
__device__ __forceinline__ void score_group(const uint32_t (&a)[2][4], const uint32_t (&kf)[2][4], uint32_t d0, uint32_t d1, uint32_t m1, uint32_t d2, uint32_t m2) {
    FS(4, a[1][0]);
    float sc[4][4];
    mma_z(sc[0], a[0], kf[0][0], kf[0][1]);
    mma_z(sc[1], a[0], kf[0][2], kf[0][3]);
    mma_z(sc[2], a[1], kf[1][0], kf[1][1]);
    mma_z(sc[3], a[1], kf[1][2], kf[1][3]);
    constexpr float EC = (float)(1.4426950408889634 * 0.08838834764831845);
    const uint32_t v0 = __float_as_uint(fmaf(sc[3][2], EC, fmaf(sc[2][0], EC, (sc[0][0] + sc[1][2]) * EC))), v1 = __float_as_uint(fmaf(sc[3][3], EC, fmaf(sc[2][1], EC, (sc[0][1] + sc[1][3]) * EC)));
    FS(5, v0);
    const uint32_t pk = pack_bf16(__uint_as_float(v0), __uint_as_float(v1));
    st_async32(d1, pk, m1);
    st_async32(d2, pk, m2);
    asm volatile("st.shared.v2.u32 [%0], {%1,%2};" :: "r"(d0), "r"(v0), "r"(v1) : "memory");
}
__device__ __forceinline__ void store_tile(int s, int h, int role, uint32_t tile, uint32_t b0, uint32_t b1) {
    asm volatile("cp.async.bulk.global.shared::cta.bulk_group.L2::cache_hint [%0], [%1], %2, %3;"
                 :: "l"(&g_qkv[s][h][role][b0]), "r"(tile + b0), "r"(b1 - b0), "l"(policy_evict_first()) : "memory");
}
__device__ __forceinline__ uint32_t w_addr(uint32_t sbase, int warp, int lane) {
    return sbase + SM_WS + (warp >> 2) * 8192 + ((lane & 7) + ((lane >> 4) & 1) * 8) * 128 + ((((warp & 3) * 2 + ((lane >> 3) & 1)) ^ (lane & 7)) << 4);
}
__device__ __forceinline__ void vx_copy(uint32_t sbase, int j, int r) {
    bulk_s2s(mapa(sbase + SM_VX + (j & 1) * 8192, r), sbase + SM_T + (j & 3) * TBUF + DH * 16, 8192, mapa(sbase + B_VX + 8 * (j & 1), r));
}
__device__ __forceinline__ float to_scale(float bound) {
    int e = 141 - (int)((__float_as_uint(bound) >> 23) & 255u);
    e = e > 100 ? 100 : e;
    return __uint_as_float((uint32_t)(127 + e) << 23);
}
__device__ __forceinline__ void norms_gather(int lane, uint32_t sbase) {
    uint2 v[3];
    uint4 w[2];
    unsigned it = 0;
#pragma unroll
    for (int i = 0; i < 3; i++) v[i] = make_uint2(0u, 0u);
    w[0] = w[1] = make_uint4(0u, 0u, 0u, 0u);
    bool more;
    do {
#pragma unroll
        for (int i = 0; i < 3; i++) if ((v[i].x & 1u) == 0u) v[i] = ld_vol_u2(&g_norm[3 * lane + i]);
#pragma unroll
        for (int i = 0; i < 2; i++) if ((w[i].x & w[i].y & w[i].z & w[i].w & 1u) == 0u) w[i] = ld_vol_u4(&g_wv[lane][i]);
        more = __any_sync(0xffffffffu, (v[0].x & v[1].x & v[2].x & w[0].x & w[0].y & w[0].z & w[0].w & w[1].x & w[1].y & w[1].z & w[1].w & 1u) == 0u);
    } while (more && ++it < SPIN_LIMIT);
    float c;
    asm("sqrt.approx.f32 %0, %1;" : "=f"(c) : "f"(__uint_as_float(max(max(v[0].x, v[1].x), v[2].x))));
    c *= __uint_as_float(max(max(max(w[0].x, w[0].y), max(w[0].z, w[0].w)), max(max(w[1].x, w[1].y), max(w[1].z, w[1].w)))) * 272.f;
#pragma unroll
    for (int o = 16; o; o >>= 1) c += __shfl_xor_sync(0xffffffffu, c, o);
    const uint32_t r = __reduce_max_sync(0xffffffffu, v[0].y);
    if (lane < 3) {
        const uint32_t rb = mapa(sbase, lane);
        c *= 1.1f * 24.f;
        st_async64(rb + SM_SC, __float_as_uint(to_scale(__uint_as_float(r) * c)), __float_as_uint(c), rb + B_W + 8);
        st_async32(rb + SM_SC + 68, r, rb + B_W + 8);
    }
    __syncwarp();
}
__device__ __forceinline__ void xmax_gather(int lane, uint32_t sb) {
    uint4 v[4];
    unsigned it = 0;
    uint32_t ok;
    do {
#pragma unroll
        for (int i = 0; i < 4; i++) v[i] = ld_vol_u4(&g_rx[lane + 32 * (i >> 1)][i & 1]);
        ok = 1u;
#pragma unroll
        for (int i = 0; i < 4; i++) ok &= (v[i].x & v[i].y) & (v[i].z & v[i].w);
    } while (__any_sync(0xffffffffu, ok == 0u) && ++it < SPIN_LIMIT);
#pragma unroll
    for (int i = 0; i < 2; i++)
        sts32(sb + SM_SC + 64 + 4 * lane + 128 * i, max(max(max(v[2 * i].x, v[2 * i].y), max(v[2 * i].z, v[2 * i].w)), max(max(v[2 * i + 1].x, v[2 * i + 1].y), max(v[2 * i + 1].z, v[2 * i + 1].w))));
}
__device__ __forceinline__ uint32_t max_abs8(uint32_t m, uint32_t a, uint32_t b, uint32_t c, uint32_t d) { return max_abs2(max_abs2(m, max_abs2(a, b)), max_abs2(c, d)); }
__device__ __forceinline__ uint32_t warp_max_abs(uint32_t m) { return __reduce_max_sync(0xffffffffu, max((m << 16) & 0x7fff0000u, m & 0x7fff0000u)); }

__device__ __forceinline__ void last_rows() {
    extern __shared__ __align__(1024) unsigned char smem_raw[];
    const uint32_t sbase = smem_u32(smem_raw);
    const int tid = threadIdx.x, warp = __shfl_sync(0xffffffffu, tid >> 5, 0), h = blockIdx.x / 3;
    {
        const int sg = warp < 8, wq = warp & 3, lane = tid & 31;
        const uint32_t qk = sbase + SM_X + XBUF + sg * (2 * 9216), ob = sbase + SM_X + 2 * XBUF + sg * 8192;
        TST(0);
        mbar_wait(sbase + B_VX + 8 * sg, 0);
        fence_async();
        TST(1);
        float sc[20];
#pragma unroll
        for (int i = 0; i < 20; i++) sc[i] = 0.f;
        {
            const uint64_t da = smem_desc(qk + 1024, 128, 1024), db = smem_desc(qk, 128, 2048);
            wg_fence();
#pragma unroll
            for (int ks = 0; ks < 8; ks++) wgmma_n40_ss(sc, da + (uint64_t)((ks >> 2) * 576 + (ks & 3) * 16), db + (uint64_t)((ks >> 2) * 576 + (ks & 3) * 16), ks > 0);
            wg_commit();
            wg_wait0();
        }
        uint32_t p[5], o[16];
        const float psum = xrow_softmax(sc, p, wq, lane);
        xrow_pv(o, p, psum, sbase + SM_T + ((NSEG - 2 + sg) & 3) * TBUF);
        {
#pragma unroll
            for (int i = 0; i < 4; i++) stsm_x4(ob + wq * 2048 + i * 512 + lane * 16, o[4 * i], o[4 * i + 1], o[4 * i + 2], o[4 * i + 3]);
        }
        fence_async();
        named_bar(11 + sg, 128);
        TST(2);
        if ((tid & 127) == 0) {
            unsigned char* dst = reinterpret_cast<unsigned char*>(g_ox) + ((size_t)((NSEG / 2 - 1) * NH + h)) * 16384 + sg * 8192;
            asm volatile("cp.async.bulk.global.shared::cta.bulk_group [%0], [%1], 8192;" :: "l"(dst), "r"(ob) : "memory");
            asm volatile("cp.async.bulk.commit_group;" ::: "memory");
            asm volatile("cp.async.bulk.wait_group 0;" ::: "memory");
            asm volatile("red.relaxed.gpu.global.add.u32 [%0], 1;" :: "l"(&g_prog[(h >> 2) * 64 + NSEG / 2 - 1]) : "memory");
        }
        TST(3);
    }
    __syncwarp();
}

__global__ void __cluster_dims__(3, 1, 1) __launch_bounds__(384, 1)
k_chain(const __grid_constant__ CUtensorMap tmq, const __grid_constant__ CUtensorMap tmk,
        const __grid_constant__ CUtensorMap tmv, const __grid_constant__ CUtensorMap tmx2, const __grid_constant__ CUtensorMap tmo,
        const __grid_constant__ CUtensorMap tmm, const bf16* __restrict__ xg) {
    extern __shared__ __align__(1024) unsigned char smem_raw[];
    const uint32_t sbase = smem_u32(smem_raw);
    const int cta = blockIdx.x, h = cta / 3, role = cta - 3 * h;
    const int tid = threadIdx.x, warp = __shfl_sync(0xffffffffu, tid >> 5, 0), lane_o = tid & 31;
    TS3C(0);
    asm volatile("griddepcontrol.launch_dependents;" ::: "memory");
    auto stage_w = [&](int i) {
        tma_2d(sbase + SM_WS + i * 16384, role == 2 ? &tmv : &tmq, h * DH + (role == 1 ? 64 : 0), i * 64, sbase + B_W + 8 * i);
        tma_2d(sbase + SM_WS + i * 16384 + 8192, role == 2 ? &tmv : &tmk, h * DH + (role == 0 ? 0 : 64), i * 64, sbase + B_W + 8 * i);
    };
    auto stage_x = [&](int i) {
        tma_2d(sbase + x01_off(i), &tmx2, i * 64, 0, sbase + B_W + 8 * i);
        tma_2d(sbase + x01_off(i) + 8192, &tmm, i * 64, 0, sbase + B_W + 8 * i);
        if (i < 3) tma_2d(sbase + x23_off(i), &tmx2, i * 64, 64, sbase + B_W + 8 * i);
    };
    if (tid == 0) {
#pragma unroll
        for (int i = 0; i < 10; i++) mbar_init(sbase + B_W + 8 * i, 1);
        fence_async();
        TSQ(10);
#pragma unroll
        for (int i = 0; i < 3; i++) tma_2d(sbase + SM_X01 + i * 16384, &tmo, role * WOC + i * 64, h * DH, sbase + B_E);
        stage_x(0); stage_w(0);
        TSQ(11);
        mbar_expect(sbase + B_E, 49152);
#pragma unroll
        for (int i = 0; i < 9; i++) mbar_expect(sbase + B_W + 8 * i, 16384 + 9216 + (i < 3 ? 8192 : 0));
    } else if (tid == 32) {
#pragma unroll
        for (int i = 0; i < 8; i++) mbar_init(sbase + SM_BAR + 8 * i, 1);
        mbar_init(sbase + B_XF, 3);
        asm volatile("fence.mbarrier_init.release.cluster;" ::: "memory");
        for (int i = 0; i < 2; i++) {
            mbar_expect(sbase + B_SB + 8 * i, role == 2 ? 1280 : 640 + 2048);
            mbar_expect(sbase + B_VX + 8 * i, role != 2 ? 8192 : 2 * 9216);
            mbar_expect(sbase + B_XT + 8 * i, 32768);
            mbar_expect(sbase + B_XT + 16 + 8 * i, i == 0 ? 40960 : 0);
        }
    }
    __syncthreads();
    TS3C(8);
    if (tid == 0) {
#pragma unroll 1
        for (int i = 1; i < 3; i++) { stage_x(i); stage_w(i); }
        TSQ(12);
    }
    __syncwarp();
    if (warp < 8) {
        uint32_t wreg[36 - NS][4];
        uint32_t v0, v1;
        {
            const int lane = lane_o;
            const uint32_t a = w_addr(sbase, warp, lane);
            const uint64_t da = smem_desc(sbase + SM_WS + (warp >> 2) * 8192, 1024, 1024) | (1ull << 62);
            float acc[36], acc1[32];
            uint32_t m = 0u;
#pragma unroll
            for (int i = 0; i < 36; i++) acc[i] = 0.f;
#pragma unroll
            for (int i = 0; i < 32; i++) acc1[i] = 0.f;
#pragma unroll 1
            for (int b = 0; b < 7; b++) {
                if (b == 0) TSQ(0);
                mbar_wait(sbase + B_W + 8 * b, 0);
                TSQ(1 + b);
                const uint64_t db = smem_desc(sbase + x01_off(b), 16, 1024) | (1ull << 62);
                wg_fence();
#pragma unroll
                for (int k = 0; k < 4; k++) wgmma_n72_ss(acc, da + (uint64_t)(b * 1024 + k * 128), db + (uint64_t)(k * 2));
                wg_commit();
                if (b < 3) {
                    const uint64_t d1 = smem_desc(sbase + x23_off(b), 16, 1024) | (1ull << 62);
                    wg_fence();
#pragma unroll
                    for (int k = 0; k < 4; k++) wgmma_n64_ss(acc1, da + (uint64_t)(b * 1024 + k * 128), d1 + (uint64_t)(k * 2));
                    wg_commit();
                }
                if (b == 2) {
                    wg_wait0();
                    bar_arrive(10, 384);
                }
                if (b == 3) {
                    if (tid == 0) mbar_expect(sbase + B_W + 8, 12);
                    __syncwarp();
                    if (role == 2) {
#pragma unroll
                        for (int ks = 0; ks < NS; ks++) {
                            uint32_t t[4];
                            ldsm_x4_t(t, a + (ks >> 2) * 16384 + (ks & 3) * 2048);
                            m = max_abs8(m, t[0], t[1], t[2], t[3]);
                        }
                    }
#pragma unroll
                    for (int ks = NS; ks < 16; ks++) ldsm_x4_t(wreg[ks - NS], a + (ks >> 2) * 16384 + (ks & 3) * 2048);
                }
                if (b == 5) {
#pragma unroll
                    for (int ks = 16; ks < 24; ks++) ldsm_x4_t(wreg[ks - NS], a + (ks >> 2) * 16384 + (ks & 3) * 2048);
                    if (role == 2) {
#pragma unroll
                        for (int ks = NS; ks < 24; ks++) m = max_abs8(m, wreg[ks - NS][0], wreg[ks - NS][1], wreg[ks - NS][2], wreg[ks - NS][3]);
                    }
                }
            }
            mbar_wait(sbase + B_W + 16, 1);
            TSQ(13);
            wg_fence();
#pragma unroll
            for (int k = 12; k < 20; k++)
                wgmma_n64_ss(acc1, da + (uint64_t)((k >> 2) * 1024 + (k & 3) * 128), (smem_desc(sbase + x23_off(k >> 2), 16, 1024) | (1ull << 62)) + (uint64_t)((k & 3) * 2));
            wg_commit();
            wg_wait0();
            named_bar(11, 384);
#pragma unroll
            for (int i = 0; i < 8; i++)
                asm volatile("st.shared.v4.f32 [%0], {%1,%2,%3,%4};" :: "r"(sbase + SM_X + 5 * 8192 + i * 4096 + tid * 16),
                             "f"(acc1[4 * i]), "f"(acc1[4 * i + 1]), "f"(acc1[4 * i + 2]), "f"(acc1[4 * i + 3]) : "memory");
#pragma unroll
            for (int b = 7; b < 9; b++) {
#pragma unroll
                for (int ks = 4 * b - 4; ks < 4 * b; ks++) ldsm_x4_t(wreg[ks - NS], a + (ks >> 2) * 16384 + (ks & 3) * 2048);
                if (role == 2) {
#pragma unroll
                    for (int ks = 4 * b - 4; ks < 4 * b; ks++) m = max_abs8(m, wreg[ks - NS][0], wreg[ks - NS][1], wreg[ks - NS][2], wreg[ks - NS][3]);
                }
                const uint64_t db = smem_desc(sbase + x01_off(b), 16, 1024) | (1ull << 62);
                mbar_wait(sbase + B_W + 8 * b, 0);
                TSQ(1 + b);
                if (b == 8) TS3C(2);
                wg_fence();
#pragma unroll
                for (int k = 0; k < 4; k++) wgmma_n72_ss(acc, da + (uint64_t)(b * 1024 + k * 128), db + (uint64_t)(k * 2));
                wg_commit();
            }
#pragma unroll
            for (int ks = 32; ks < KPRE; ks++) ldsm_x4_t(wreg[ks - NS], a + (ks >> 2) * 16384 + (ks & 3) * 2048);
            if (role == 2) {
#pragma unroll
                for (int ks = KPRE; ks < 36; ks++) {
                    uint32_t t[4];
                    ldsm_x4_t(t, a + (ks >> 2) * 16384 + (ks & 3) * 2048);
                    m = max_abs8(m, t[0], t[1], t[2], t[3]);
                }
#pragma unroll
                for (int ks = 32; ks < KPRE; ks++) m = max_abs8(m, wreg[ks - NS][0], wreg[ks - NS][1], wreg[ks - NS][2], wreg[ks - NS][3]);
                m = warp_max_abs(m);
                if (lane == 0) asm volatile("st.volatile.global.u32 [%0], %1;" :: "l"(reinterpret_cast<uint32_t*>(&g_wv[h][0]) + warp), "r"(m | 1u) : "memory");
                __syncwarp();
            }
            wg_wait0();
            named_bar(9, 256);
            const uint32_t off = sbase + SM_T + (DH + warp * 16 + (lane & 15)) * 16 + (lane >> 4) * (DH * 16);
#pragma unroll
            for (int i = 0; i < 4; i++)
                stsm_x4(off + (i >> 1) * TBUF + (i & 1) * (2 * DH * 16), pack_bf16(acc[8 * i], acc[8 * i + 1]), pack_bf16(acc[8 * i + 2], acc[8 * i + 3]),
                        pack_bf16(acc[8 * i + 4], acc[8 * i + 5]), pack_bf16(acc[8 * i + 6], acc[8 * i + 7]));
            v0 = pack_bf16(acc[32], acc[33]);
            v1 = pack_bf16(acc[34], acc[35]);
#pragma unroll
            for (int ks = KPRE; ks < 36; ks++) ldsm_x4_t(wreg[ks - NS], a + (ks >> 2) * 16384 + (ks & 3) * 2048);
            if (role == 2) fence_async();
            bar_arrive(8, 384);
            named_bar(7, 256);
            asm volatile("barrier.cluster.arrive.relaxed.aligned;" ::: "memory");
        }
        TS3C(3);
        uint32_t ws[NS][4];
#pragma unroll
        for (int ks = NS - NP; ks < NS; ks++) ldsm_x4_t(ws[ks], w_addr(sbase, warp, lane_o) + (ks >> 2) * 16384 + (ks & 3) * 2048);
        asm volatile("barrier.cluster.wait.aligned;" ::: "memory");
        if (lane_o == 0 && role != 2 && warp < 2) tma_2d_mc(sbase + SM_X + (2 * role + warp) * 8192, &tmx2, (2 * role + warp + 5) * 64, 64, sbase + B_XT + 8);
        __syncwarp();
        TS3C(4);
        auto main_loop = [&](auto is_c) {
            constexpr bool C = decltype(is_c)::value;
            if (C) pad_code<PAD4>(); else pad_code<PAD3>();
            const uint32_t l16 = __shfl_sync(0xffffffffu, sbase + lane_o * 16, lane_o);
            const uint32_t ka = __shfl_sync(0xffffffffu, sbase + SM_T + (64 + (lane_o & 7) + ((lane_o >> 3) & 1) * 16 + (lane_o >> 4) * 8) * 16, lane_o);
            const uint32_t wa = __shfl_sync(0xffffffffu, w_addr(sbase, warp, lane_o), lane_o);
            auto post = [&](bool act, int s, uint32_t to, uint32_t ta, int scw, uint32_t v0, uint32_t v1) {
                int lane = lane_o;
                asm volatile("" : "+r"(lane));
                asm volatile("stmatrix.sync.aligned.m8n8.x2.shared.b16 [%0], {%1,%2};" :: "r"(l16 + ta), "r"(v0), "r"(v1) : "memory");
                if (C) {
                    if (act || s + 1 < NSEG) {
                        const uint32_t fo = (uint32_t)(warp * 256 + lane * 8);
                        const uint32_t rb0 = mapa(sbase, 0), rb1 = mapa(sbase, 1);
                        st_async64(rb0 + SM_VM + fo, v0, v1, rb0 + B_SB + 8 * (s & 1));
                        st_async64(rb1 + SM_VM + fo, v0, v1, rb1 + B_SB + 8 * (s & 1));
                        asm volatile("st.shared.v2.u32 [%0], {%1,%2};" :: "r"(sbase + SM_VM + fo), "r"(v0), "r"(v1) : "memory");
                        bar_arrive(2, 384);
                    }
                } else if (act) bar_arrive(2, 384);
                else {
                    named_bar(2, 384);
                    if (scw == 0) {
                        uint32_t kf[2][4], qf[2][4];
#pragma unroll
                        for (int k2 = 0; k2 < 2; k2++) { ldsm_x4_t(kf[k2], ka + to + k2 * 512); ldsm_x4_t(qf[k2], l16 + SM_T + to + k2 * 512); }
                        const uint32_t d0 = sbase + SM_S + lane * 8, bo = sbase + B_SB + 8 * (s & 1);
                        const uint32_t d1 = mapa(sbase + SM_S + 1280, role ^ 1) + lane * 4, m1 = mapa(bo, role ^ 1), d2 = mapa(sbase + SM_S + role * 1280, 2) + lane * 4, m2 = mapa(bo, 2);
                        score_group(qf, kf, d0, d1, m1, d2, m2);
                        bar_arrive(6, 160);
                        bar_arrive(5, 384);
                    }
                    if (scw == 8) {
                        const uint32_t dk = mapa(sbase + SM_X + XBUF + (2 + role) * 9216 + (warp - 4) * 256 + lane * 4, 2), mb = mapa(sbase + B_VX + 8, 2);
                        st_async32(dk, v0, mb);
                        st_async32(dk + 128, v1, mb);
                    }
                }
                FS(11, 0);
            };
            post(false, 0, 0, SM_T + warp * 256, warp ^ 7, v0, v1);
            if (tid == 128 && cta < NSEG) {
                fence_async();
                mbar_expect(sbase + B_E, XBUF);
                bulk_g2s(sbase + SM_X + 9 * 8192, xg + (size_t)cta * SEG * DM, 32768, sbase + B_E);
                bulk_g2s(sbase + SM_WS + 32768 + 4096, xg + (size_t)cta * SEG * DM + 16384, 4096, sbase + B_E);
            }
            __syncwarp();
            if (C) {
                named_bar(7, 256);
                if (warp == 1) norms_gather(lane_o, sbase);
            }
            auto chores = [&](int s, bool idle) {
                int lane = lane_o;
                asm volatile("" : "+r"(lane));
                const int hw = (s & 1) ? warp : warp - 4;
                const uint32_t tb = sbase + SM_T + (s & 3) * TBUF;
                if (idle) { if (hw != 2) named_bar(4, 384); else bar_arrive(4, 384); }
                if (hw == 2) {
                    if (lane == 0) {
                        {
                            if (C || !idle) fence_async();
                            if (C) {
                                store_tile(s + 1, h, 2, sbase + SM_T + ((s + 1) & 3) * TBUF, 2048, 10240);
                                store_tile(s, h, 2, tb, 0, idle ? 2048 : 10240);
                            } else store_tile(s, h, role, tb, 1024, 10240);
                            asm volatile("cp.async.bulk.commit_group;" ::: "memory");
                        }
                        {
                            asm volatile("cp.async.bulk.wait_group 0;" ::: "memory");
                            if (C) {
                                asm volatile("cp.async.bulk.shared::cluster.global.mbarrier::complete_tx::bytes.multicast::cluster [%0], [%1], 8192, [%2], %3;"
                                             :: "r"(sbase + SM_VX + ((s + 1) & 1) * 8192), "l"(&g_qkv[s + 1][h][2][2048]), "r"(sbase + B_VX + 8 * ((s + 1) & 1)), "h"((unsigned short)3) : "memory");
                            }
                            asm volatile("red.relaxed.gpu.global.add.u32 [%0], 1;" :: "l"(&g_flag[h * NSEG + s]) : "memory");
                        }
                    }
                    __syncwarp();
                    if (!C && (s & 1) && s + 4 < NSEG) bar_arrive(13, 160);
                }
                __syncwarp();
            };
            auto put_tiles = [&](const float (&acc)[32], uint32_t off) {
#pragma unroll
                for (int i = 0; i < 4; i++)
                    stsm_x4(off + (i >> 1) * TBUF + (i & 1) * (2 * DH * 16), pack_bf16(acc[8 * i], acc[8 * i + 1]), pack_bf16(acc[8 * i + 2], acc[8 * i + 3]),
                            pack_bf16(acc[8 * i + 4], acc[8 * i + 5]), pack_bf16(acc[8 * i + 6], acc[8 * i + 7]));
            };
            auto tile_off = [&](int p) {
                int lane = lane_o;
                asm volatile("" : "+r"(lane));
                return sbase + SM_T + (p & 1) * (2 * TBUF) + (DH + warp * 16 + (lane & 15)) * 16 + (lane >> 4) * (DH * 16);
            };
            {
                auto db = [&](int ks) { return (smem_desc(sbase + SM_X, 16, 1024) | (1ull << 62)) + (uint64_t)(((ks >> 2) - 5) * 512 + (ks & 3) * 2); };
                if (!C && warp != 7) bar_arrive(5, 384);
                if (warp == 5) {
                    mbar_wait(sbase + B_W + 8, 1);
                    bar_arrive(12, 160);
                }
                chores(0, false);
                float acc[32];
#pragma unroll
                for (int i = 0; i < 8; i++)
                    asm volatile("ld.shared.v4.f32 {%0,%1,%2,%3}, [%4];" : "=f"(acc[4 * i]), "=f"(acc[4 * i + 1]), "=f"(acc[4 * i + 2]), "=f"(acc[4 * i + 3])
                                 : "r"(l16 + warp * 512 + SM_X + 5 * 8192 + i * 4096) : "memory");
                mbar_wait(sbase + B_XT + 8, 0);
                FS(8, 0);
                named_bar(4, 384);
                wg_fence();
#pragma unroll
                for (int ks = 35; ks >= 20; ks--) wgmma_n64(acc, wreg[ks - NS], db(ks), 1);
                wg_commit();
                if (cta < NSEG) {
                    uint32_t m = 0u;
                    mbar_wait(sbase + B_E, 1);
#pragma unroll
                    for (int j = 0; j < 9; j++) {
                        const uint4 xv = lds128(l16 + warp * 512 + (j < 8 ? SM_X + 9 * 8192 + j * 4096 : SM_WS + 32768 + 4096));
                        m = max_abs8(m, xv.x, xv.y, xv.z, xv.w);
                    }
                    m = warp_max_abs(m);
                    if (lane_o == 0) asm volatile("st.volatile.global.u32 [%0], %1;" :: "l"(reinterpret_cast<uint32_t*>(&g_rx[cta][0]) + warp), "r"(m | 1u) : "memory");
                    __syncwarp();
                }
                FS(3, 0);
                wg_wait0();
                put_tiles(acc, tile_off(1));
                FS(7, __float_as_uint(acc[0]));
            }
            auto mem_proj = [&](uint32_t& u0, uint32_t& u1, bool xf) {
#pragma unroll
                for (int ks = 0; ks < NS - NP; ks++) ldsm_x4_t(ws[ks], wa + (ks >> 2) * 16384 + (ks & 3) * 2048);
                if (xf) {
                    named_bar(15, 160);
                    if (lane_o < 2) asm volatile("mbarrier.arrive.relaxed.cluster.shared::cluster.b64 _, [%0];" :: "r"(mapa(sbase + B_XF, lane_o)) : "memory");
                    __syncwarp();
                }
                FS(0, ws[0][0]);
                named_bar(1, 384);
                float acc[2][4], minv;
                uint32_t b[3][4];
#pragma unroll
                for (int kk = 0; kk < 3; kk++) ldsm_x4_t(b[kk], l16 + SM_M + kk * 512);
                FS(1, b[0][0]);
#pragma unroll
                for (int kk = 0; kk < 18; kk++) {
#pragma unroll
                    for (int i = 0; i < 2; i++) {
                        const int ks = 2 * kk + i;
                        if (ks < 2) mma_z(acc[i], ws[ks], b[kk % 3][2 * i], b[kk % 3][2 * i + 1]);
                        else if (ks < NS) mma_bf16(acc[i], ws[ks < NS ? ks : 0], b[kk % 3][2 * i], b[kk % 3][2 * i + 1]);
                        else mma_bf16(acc[i], wreg[ks >= NS ? ks - NS : 0], b[kk % 3][2 * i], b[kk % 3][2 * i + 1]);
                    }
                    if (kk + 3 < 18) ldsm_x4_t(b[kk % 3], l16 + SM_M + (kk + 3) * 512);
                    if (kk + 3 == 17) asm volatile("ld.shared.f32 %0, [%1];" : "=f"(minv) : "r"(sbase + SM_SC + 8) : "memory");
                }
                u0 = pack_bf16(fmaf(acc[1][0], minv, acc[0][0] * minv), fmaf(acc[1][1], minv, acc[0][1] * minv));
                u1 = pack_bf16(fmaf(acc[1][2], minv, acc[0][2] * minv), fmaf(acc[1][3], minv, acc[0][3] * minv));
                FS(2, u0);
            };
            int s = 0, rc = 9;
            bool act = warp >= 4;
            uint32_t to = TBUF, ta = SM_T + warp * 256 + TBUF;
            auto next_slot = [&]() {
                const uint32_t d = (s & 3) == 3 ? -3 * TBUF : TBUF;
                to += d; ta += d;
                asm volatile("" : "+r"(to), "+r"(ta));
            };
#pragma unroll 1
            for (;;) {
                uint32_t u0, u1;
                if (act) {
                    mem_proj(u0, u1, EXF && warp == 4 && s > 0);
                    s++;
                    post(true, s, to, ta, 1, u0, u1);
                    const int p = (s + 3) >> 1;
                    const uint32_t dlo = (uint32_t)smem_desc(sbase + SM_X, 16, 1024) + rc * 512;
                    const uint64_t da = smem_desc(sbase + SM_WS + (warp >> 2) * 8192, 1024, 1024) | (1ull << 62);
                    auto db = [&](int ks) {
                        const int j = ((ks >> 2) + 4) % 9;
                        return ((uint64_t)0x40000040u << 32) | (uint64_t)(dlo + (uint32_t)((j - (rc + j >= 13 ? 13 : 0)) * 512 + (ks & 3) * 2));
                    };
                    const uint32_t xph = (uint32_t)((p - 1) >> 1) & 1u;
                    float acc[32];
                    mbar_wait(sbase + B_XT + 8 * (p & 1), xph);
                    if (C) named_bar(7, 256); else named_bar(5, 384);
                    constexpr int N1 = C ? NC1C : NC1;
                    wg_fence();
#pragma unroll
                    for (int ks = 35; ks > 35 - N1; ks--) { if (ks == 35) wgmma_n64_z(acc, wreg[ks - NS], db(ks)); else wgmma_n64(acc, wreg[ks - NS], db(ks), 1); }
                    wg_commit();
                    wg_wait0();
                    FS(9, __float_as_uint(acc[0]));
                    next_slot();
                    FS(8, 0);
                    asm volatile("{\n.reg .pred p;\nsetp.ge.s32 p, %0, 0;\n@p bar.sync 4, 384;\n}" :: "r"(s) : "memory");
                    FS(3, 0);
                    wg_fence();
#pragma unroll
                    for (int ks = 35 - N1; ks >= KG1; ks--) wgmma_n64(acc, wreg[ks - NS], db(ks), 1);
                    wg_commit();
                    mbar_wait(sbase + B_XT + 16 + 8 * (p & 1), xph);
                    wg_fence();
#pragma unroll
                    for (int ks = 0; ks < NS; ks++) {
                        wgmma_n64_ss(acc, da + (uint64_t)((ks >> 2) * 1024 + (ks & 3) * 128), db(ks));
                        if (EXF && ks == 3) wg_commit();
                    }
                    if (EXF) {
                        wg_commit();
                        wg_wait1();
                        asm volatile("{\n.reg .pred p;\nsetp.lt.s32 p, %0, %1;\n@p bar.arrive 15, 160;\n}" :: "r"(s + (warp >> 2) * NSEG), "n"(NSEG - 5) : "memory");
                    }
#pragma unroll
                    for (int ks = NS; ks < KG1; ks++) wgmma_n64(acc, wreg[ks - NS], db(ks), 1);
                    wg_commit();
                    if (!C && warp >= 4) named_bar(13, 160);
                    uint32_t off = tile_off(p);
                    rc = rc >= 4 ? rc - 4 : rc + 9;
                    asm volatile("" : "+r"(off), "+r"(rc));
                    wg_wait0();
                    put_tiles(acc, off);
                    FS(7, __float_as_uint(acc[0]));
                }
                int scw = s + 2 < NSEG ? warp ^ ((s & 1) ? 7 : 3) : (warp & 4) + 4;
                asm volatile("" : "+r"(scw));
                mem_proj(u0, u1, false);
                s++;
                post(false, s, to, ta, scw, u0, u1);
                if (s + 1 == NSEG) break;
                if (s + 2 < NSEG) {
                    if (!C && (warp & 3) == 2) fence_async();
                    if (C) named_bar(7, 256); else if (scw != 0) named_bar(5, 384);
                    chores(s, true);
                } else {
                    const uint32_t t0 = clock32();
                    const uint32_t dq = mapa(sbase + SM_X + XBUF + role * 9216, 2), mb = mapa(sbase + B_VX, 2);
                    if (!C) {
                        if (scw != 0) named_bar(5, 384);
                        if (tid == 64) { fence_async(); while (clock32() - t0 < TL_DELAY) {} bulk_s2s(dq, sbase + SM_T + 2 * TBUF + 1024, 9216, mb); }
                        __syncwarp();
                    }
                    named_bar(4, 384);
                    if (!C && tid == 64) { const uint32_t t1 = clock32(); while (clock32() - t1 < VX_DELAY) {} bulk_s2s(dq + 2 * 9216 + 1024, sbase + SM_T + 3 * TBUF + 2048, 8192, mb + 8); }
                    __syncwarp();
                }
                next_slot();
                act = s + 4 < NSEG;
            }
            if (C) named_bar(7, 256);
        };
        if (role == 2) main_loop(Flag<true>()); else main_loop(Flag<false>());
    } else {
        uint32_t wo[3][8][4];
        uint32_t mx2 = 0u;
        {
            const int pt = tid - 256, lane = lane_o, wq = warp - 8, g = lane >> 2, tq = lane & 3;
            TSQ(7);
            mbar_wait(sbase + B_E, 0);
            TSQ(8);
#pragma unroll
            for (int t = 0; t < 3; t++) {
                const int T = 3 * wq + t;
                const uint32_t a = sbase + SM_X01 + (T >> 2) * 16384 + ((lane >> 4) * 8 + (lane & 7)) * 128 + ((((T & 3) * 2 + ((lane >> 3) & 1)) ^ (lane & 7)) << 4);
#pragma unroll
                for (int kk = 0; kk < 8; kk++) ldsm_x4_t(wo[t][kk], a + ((2 * wq + kk) & 7) * 2048);
            }
            named_bar(3, 128);
            if (pt == 64) {
                fence_async();
#pragma unroll 1
                for (int i = 3; i < 9; i++) { stage_x(i); if (i < 7) stage_w(i); }
            }
            if (pt >= 96 && pt < 120) {
                *reinterpret_cast<uint4*>(g_acc + cta * 1024 + (pt - 96) * 16) = make_uint4(0u, 0u, 0u, 0u);
                __threadfence();
            }
            __syncwarp();
            TSQ(9);
            float c0 = 0.f;
#pragma unroll
            for (int t = 0; t < 3; t++) {
                float n[4][4];
#pragma unroll
                for (int i = 0; i < 4; i++) { n[i][0] = n[i][1] = n[i][2] = n[i][3] = 0.f; }
#pragma unroll
                for (int kk = 0; kk < 8; kk++)
#pragma unroll
                    for (int i = 0; i < 4; i++) mma_k8(n[i], wo[t][kk][i & 2], wo[t][kk][(i & 2) + 1], wo[t][kk][i]);
                if ((g >> 1) == tq) c0 = fmaxf(c0, (g & 1) ? fmaxf(n[0][1] + n[2][1], n[1][3] + n[3][3]) : fmaxf(n[0][0] + n[2][0], n[1][2] + n[3][2]));
            }
            c0 = __uint_as_float(__reduce_max_sync(0xffffffffu, __float_as_uint(c0)));
            uint32_t m = 0u;
            const int xb = role == 0 ? h % 9 : 9;
            auto x_max = [&]() {
                mbar_wait(sbase + B_W + 8 * xb, 0);
#pragma unroll
                for (int j = 0; j < 5; j++) {
                    uint4 xv;
                    asm volatile("ld.shared.v4.u32 {%0,%1,%2,%3}, [%4];" : "=r"(xv.x), "=r"(xv.y), "=r"(xv.z), "=r"(xv.w)
                                 : "r"(sbase + x01_off(xb) + (j < 4 ? pt + 128 * j : 512 + (pt & 63)) * 16) : "memory");
                    m = max_abs8(m, xv.x, xv.y, xv.z, xv.w);
                }
            };
            if (xb < 3) x_max();
            named_bar(10, 384);
            TSQ(10);
            if (pt == 64) {
                fence_async();
                mbar_expect(sbase + B_W + 16, 16384);
#pragma unroll
                for (int i = 3; i < 5; i++) tma_2d(sbase + x23_off(i), &tmx2, i * 64, 64, sbase + B_W + 16);
#pragma unroll 1
                for (int i = 7; i < 9; i++) stage_w(i);
            }
            __syncwarp();
            if (xb >= 3 && xb < 7) x_max();
            bar_arrive(11, 384);
            if (xb == 7 || xb == 8) x_max();
            asm volatile("barrier.cluster.arrive.relaxed.aligned;" ::: "memory");
            m = warp_max_abs(m);
            if (lane == 0) { sts32(sbase + SM_SC + 320 + 4 * wq, __float_as_uint(c0)); sts32(sbase + SM_SC + 336 + 4 * wq, m); }
            TSQ(1);
            named_bar(3, 128);
            if (pt == 0) {
                const uint4 a = lds128(sbase + SM_SC + 320), b = lds128(sbase + SM_SC + 336);
                st_vol_u2(&g_norm[cta], make_uint2(max(max(a.x, a.y), max(a.z, a.w)) | 1u, max(max(b.x, b.y), max(b.z, b.w)) | 1u));
            }
            __syncwarp();
            named_bar(8, 384);
            TSQ(2);
            asm volatile("barrier.cluster.wait.aligned;" ::: "memory");
            if (role == 2 && lane == 0 && wq < 2) vx_copy(sbase, 0, wq);
            __syncwarp();
        }
        const int wq = warp - 8;
        auto helper_loop = [&](auto is_c) {
        const bool C = is_c.value;
        if (C) pad_code<PAD2>(); else pad_code<PAD1>();
        const uint32_t sb = sbase;
        const uint32_t l8_o = __shfl_sync(0xffffffffu, sb + lane_o * 8, lane_o), l16_o = __shfl_sync(0xffffffffu, sb + lane_o * 16, lane_o);
        unsigned char* dst = g_acc + (role * 32 + wq * 8 + (lane_o >> 3)) * 1024 + (lane_o & 7) * 16;
        auto load_kf = [&](uint32_t (&kf)[2][4], int slot) {
            int lane = lane_o;
            asm volatile("" : "+r"(lane));
            const uint32_t ka = sb + SM_T + slot * TBUF + ((wq + 1) * DH + 64 + (lane & 7) + ((lane >> 3) & 1) * 16 + (lane >> 4) * 8) * 16;
#pragma unroll
            for (int k2 = 0; k2 < 2; k2++) ldsm_x4_t(kf[k2], ka + k2 * 512);
        };
        float minv = 1.f;
        uint32_t kf[2][4];
        if (!C) load_kf(kf, 0);
        int b3 = 0;
        int rx = 9;
        for (int s = 0; s + 1 < NSEG; s++) {
            const int n3 = b3 == 2 ? 0 : b3 + 1;
            uint32_t l8 = l8_o, l16 = l16_o;
            asm volatile("" : "+r"(l8), "+r"(l16));
            const uint32_t l4 = sb + ((l8 - sb) >> 1);
            {
                int lane = lane_o;
                asm volatile("" : "+r"(lane));
                if (C) {
                    if (lane == 0) {
                        if (wq == 3 && h == 0) {
                            const uint32_t t = gtime32();
                            st_vol_u2(&g_tick, make_uint2(t, lds32(sb + SM_SC + 12)));
                            sts32(sb + SM_SC + 12, t);
                        }
                    }
                    __syncwarp();
                    if (wq == 2 && s > 1 && lane < 24) {
                        *reinterpret_cast<uint4*>(g_acc + n3 * 128 + (3 * h + (lane >> 3)) * 1024 + (lane & 7) * 16) = make_uint4(0u, 0u, 0u, 0u);
                    }
                    if (wq == 1 && s == 3 && lane < 3) {
                        const int c = 3 * h + lane;
                        st_vol_u2(&g_norm[c], make_uint2(0u, 0u));
                        uint4* z = c < NSEG ? g_rx[c] : g_wv[c - NSEG];
                        st_vol_u4(z, make_uint4(0u, 0u, 0u, 0u)); st_vol_u4(z + 1, make_uint4(0u, 0u, 0u, 0u));
                    }
                    __syncwarp();
                }
                const uint32_t mw = __reduce_max_sync(0xffffffffu, max(mx2 << 16, mx2 & 0xffff0000u));
                if (lane == 0) sts32(sb + SM_SC + 16 + 4 * wq, mw);
            }
            const uint32_t to = SM_T + (s & 3) * TBUF;
            const uint32_t ph = (uint32_t)(s >> 1) & 1u;
            if (!C) {
                const uint32_t bo = sb + B_SB + 8 * (s & 1);
                uint32_t d0 = l8 + SM_S + (wq + 1) * 256, qa = l16 + to;
                const uint32_t dr = l4 + SM_S + (wq + 1) * 256;
                const uint32_t d1 = mapa(dr + 1280, role ^ 1), m1 = mapa(bo, role ^ 1), d2 = mapa(dr + role * 1280, 2), m2 = mapa(bo, 2);
                asm volatile("" : "+r"(d0), "+r"(qa));
                mbar_wait(sb + (s > 0 ? B_VX + 8 * (s & 1) : B_W), ph);
                FS(1, 0);
                named_bar(2, 384);
                uint32_t qf[2][4];
#pragma unroll
                for (int k2 = 0; k2 < 2; k2++) ldsm_x4_t(qf[k2], qa + k2 * 512);
                score_group(qf, kf, d0, d1, m1, d2, m2);
                bar_arrive(5, 384);
            } else named_bar(2, 384);
            if (!C && s == 0) {
                TSQ(3);
                mbar_wait(sb + B_VX, 0);
                TSQ(4);
            }
            float4 m4;
            asm volatile("ld.shared.v4.f32 {%0,%1,%2,%3}, [%4];" : "=f"(m4.x), "=f"(m4.y), "=f"(m4.z), "=f"(m4.w) : "r"(sb + SM_SC + 16) : "memory");
            const float c24 = __uint_as_float(lds32(sb + SM_SC + 4)), xb = __uint_as_float(lds32(sb + SM_SC + 64 + 4 * s));
            uint32_t vf[2][2][4], vm[2][2];
            uint32_t va = l16 + ((l16 >> 8) & 1) * 1792 + wq * 512 + (C ? to + DH * 16 : SM_VX + (s & 1) * 8192);
            auto load_vf = [&]() {
#pragma unroll
                for (int i = 0; i < 4; i++) ldsm_x4(vf[i & 1][i >> 1], va + (i & 1) * 256 + (i >> 1) * 4096);
            };
            load_vf();
            float scale = to_scale(fmaxf(fmaxf(fmaxf(m4.x, m4.y), fmaxf(m4.z, m4.w)) * minv, xb) * c24);
            uint32_t oa = l16 + wq * 512;
            asm volatile("" : "+f"(scale), "+r"(oa), "+r"(va));
            FS(7, __float_as_uint(scale));
            if (!C) named_bar(6, 160);
            if (C) mbar_wait(sb + B_SB + 8 * (s & 1), ph);
            float sv[5][2];
#pragma unroll
            for (int j = 0; j < 5; j++) {
                if (C) { const uint32_t w = lds32(l4 + SM_S + j * 256); sv[j][0] = __uint_as_float(w << 16); sv[j][1] = __uint_as_float(w & 0xffff0000u); }
                else lds64f(sv[j][0], sv[j][1], l8 + SM_S + j * 256);
            }
            if (!C) mbar_wait(sb + B_SB + 8 * (s & 1), ph);
            FS(6, 0);
            uint32_t p[5];
            {
                float sr[5][2];
#pragma unroll
                for (int j = 0; j < 5; j++) {
                    const uint32_t w = lds32(l4 + SM_S + 1280 + j * 256);
                    sr[j][0] = __uint_as_float(w << 16); sr[j][1] = __uint_as_float(w & 0xffff0000u);
                }
                lds64(vm[0][0], vm[0][1], l8 + SM_VM + wq * 512);
                lds64(vm[1][0], vm[1][1], l8 + SM_VM + wq * 512 + 256);
#pragma unroll
                for (int j = 0; j < 5; j++) {
                    sv[j][0] += sr[j][0];
                    sv[j][1] += sr[j][1];
                }
                float mx = fmaxf(fmaxf(fmaxf(sv[0][0], sv[0][1]), fmaxf(sv[1][0], sv[1][1])), fmaxf(fmaxf(sv[2][0], sv[2][1]), fmaxf(sv[3][0], sv[3][1])));
                mx = fmaxf(mx, fmaxf(sv[4][0], sv[4][1]));
                {
                    const float m1 = __shfl_xor_sync(0xffffffffu, mx, 1), m2 = __shfl_xor_sync(0xffffffffu, mx, 2), m3 = __shfl_xor_sync(0xffffffffu, mx, 3);
                    mx = fmaxf(fmaxf(mx, m1), fmaxf(m2, m3));
                }
#pragma unroll
                for (int jj = 0; jj < 5; jj++) {
                    const int j = (jj + 1) % 5;
                    asm("ex2.approx.ftz.f32 %0, %1;" : "=f"(sv[j][0]) : "f"(sv[j][0] - mx));
                    asm("ex2.approx.ftz.f32 %0, %1;" : "=f"(sv[j][1]) : "f"(sv[j][1] - mx));
                    p[j] = pack_bf16(sv[j][0], sv[j][1]);
                }
            }
            FS(0, p[0]);
            uint32_t b[4][4];
            const uint32_t one4[4] = {0x3f803f80u, 0x3f803f80u, 0x3f803f80u, 0x3f803f80u};
            float zs[4];
            {
                float o0[2][4], o1[2][4];
                mma_z(o0[0], vf[0][0], p[1], p[2]);
                mma_z(o0[1], vf[1][0], p[1], p[2]);
                mma_z(o1[0], vf[0][1], p[3], p[4]);
                mma_z(o1[1], vf[1][1], p[3], p[4]);
                mma_k8(o0[0], vm[0][0], vm[0][1], p[0]);
                mma_k8(o0[1], vm[1][0], vm[1][1], p[0]);
                float z2[4];
                mma_z(zs, one4, p[1], p[2]);
                mma_z(z2, one4, p[3], p[4]);
                mma_k8(zs, one4[0], one4[1], p[0]);
                zs[0] += z2[0]; zs[1] += z2[1];
                uint32_t ow[4];
#pragma unroll
                for (int m = 0; m < 2; m++) {
                    ow[2 * m] = pack_bf16(o0[m][0] + o1[m][0], o0[m][1] + o1[m][1]);
                    ow[2 * m + 1] = pack_bf16(o0[m][2] + o1[m][2], o0[m][3] + o1[m][3]);
                }
                stsm_x4(oa + SM_O, ow[0], ow[1], ow[2], ow[3]);
                FS(2, 0);
                b[0][0] = movm(ow[0]); b[0][1] = movm(ow[1]);
                __syncwarp();
                asm volatile("ldmatrix.sync.aligned.m8n8.x2.trans.shared.b16 {%0,%1}, [%2];" : "=r"(b[0][2]), "=r"(b[0][3]) : "r"(oa + SM_O + 256));
            }
            float acc[3][2][4];
            named_bar(3, 128);
#pragma unroll
            for (int i = 1; i < 4; i++) ldsm_x4_t(b[i], l16 + SM_O + ((wq + i) & 3) * 512);
#pragma unroll
            for (int c = 0; c < 2; c++)
#pragma unroll
                for (int t = 0; t < 3; t++) mma_z(acc[t][c], wo[t][c], b[0][2 * c], b[0][2 * c + 1]);
            float z0, z1;
            asm volatile("rcp.approx.ftz.f32 %0, %1;" : "=f"(z0) : "f"(zs[0]));
            asm volatile("rcp.approx.ftz.f32 %0, %1;" : "=f"(z1) : "f"(zs[1]));
            asm volatile("{\n.reg .pred p;\nsetp.eq.s32 p, %1, 0;\n@p bar.sync 12, 160;\n@p ld.shared.f32 %0, [%2];\n}" : "+f"(scale) : "r"(s), "r"(sb + SM_SC) : "memory");
            z0 *= scale; z1 *= scale;
            FS(3, b[1][0]);
#pragma unroll
            for (int i = 1; i < 4; i++)
#pragma unroll
                for (int c = 0; c < 2; c++)
#pragma unroll
                    for (int t = 0; t < 3; t++) mma_bf16(acc[t][c], wo[t][2 * i + c], b[i][2 * c], b[i][2 * c + 1]);
            {
                uint32_t w[6];
#pragma unroll
                for (int t = 0; t < 3; t++) {
                    w[2 * t] = pack_f16(fmaf(acc[t][1][0], z0, acc[t][0][0] * z0), fmaf(acc[t][1][1], z1, acc[t][0][1] * z1));
                    w[2 * t + 1] = pack_f16(fmaf(acc[t][1][2], z0, acc[t][0][2] * z0), fmaf(acc[t][1][3], z1, acc[t][0][3] * z1));
                }
                FS(8, w[5]);
                asm volatile("red.relaxed.gpu.global.add.noftz.v4.f16x2 [%0], {%1,%2,%3,%4};" :: "l"(dst), "r"(w[0]), "r"(w[1]), "r"(w[2]), "r"(0x3c00u) : "memory");
                asm volatile("red.relaxed.gpu.global.add.noftz.v4.f16x2 [%0], {%1,%2,%3,%4};" :: "l"(dst + 4096), "r"(w[3]), "r"(w[4]), "r"(w[5]), "r"(0x3c00u) : "memory");
            }
            FS(9, 0);
            if (s == 0) TSQ(5);
            bar_arrive(4, 384);
            const uint32_t t0 = clock32();
            minv = __uint_as_float(0x7f000000u - __float_as_uint(scale));
            if (lane_o == 0) {
                if (wq == 0) sts32(sb + SM_SC + 8, __float_as_uint(minv));
                if (s + 3 < NSEG) {
                    if (wq == 0) mbar_expect(sb + B_SB + 8 * (s & 1), C ? 1280 : 640 + 2048);
                    if (wq == 1 && s > 0 && s + 5 < NSEG) mbar_expect(sb + B_XT + ((s & 1) ? 0 : 16) + 4 * ((s + 1) & 2), (s & 1) ? 32768 : 40960);
                    if (wq == 3 && !C) mbar_expect(sb + B_VX + 8 * (s & 1), 8192);
                }
            }
            __syncwarp();
            if (s == 1) {
                if (!C) pad_code<PADC>();
                int lane = lane_o;
                asm volatile("" : "+r"(lane));
                if (wq == 3) xmax_gather(lane, sb);
                __syncwarp();
            }
            if (!C) load_kf(kf, (s + 1) & 3);
            const uint4* src = reinterpret_cast<const uint4*>(dst + (wq * 16 - role * 32) * 1024);
            dst += n3 == 0 ? -256 : 128;
            asm volatile("" : "+l"(dst));
            const int xp = (s + 5) >> 1, kb = wq + ((s & 1) ? 2 * role : 4 + 3 * role);
            const bool xl = !C && xp < NSEG / 2 && wq < ((s & 1) ? 2 : 3 - role);
            const uint32_t xs = wq == 3 && (EXF ? s == 0 : (s & 1) == 0 && xp < NSEG / 2);
            const uint32_t xd = sb + SM_X + (rx + kb >= 13 ? rx + kb - 13 : rx + kb) * 8192;
            mx2 = poll_mem(src, l16 + SM_M + wq * 2304, t0, [&]() {
                if (xs && lane_o < 2) asm volatile("mbarrier.arrive.relaxed.cluster.shared::cluster.b64 _, [%0];" :: "r"(mapa(sb + B_XF, lane_o)) : "memory");
                if (!C && (xl || s == 0) && (s & 1) == 0) mbar_wait(sb + B_XF, (uint32_t)(s >> 1) & 1u);
                if (lane_o == 0) {
                    if (xl) tma_2d_mc(xd, &tmx2, ((s & 1) ? kb + 5 : kb - 4) * 64, xp * 64, sb + B_XT + ((s & 1) ? 0 : 16) + 8 * (xp & 1));
                    if (!C && s == 0 && role == 1) tma_2d_mc(sb + SM_X + (9 + wq) * 8192, &tmx2, (wq + 5) * 64, 128, sb + B_XT);
                }
                __syncwarp();
            });
            if ((s & 1) == 0) rx = rx >= 4 ? rx - 4 : rx + 9;
            if (s == 0) TSQ(6);
            b3 = n3;
        }
        if (!C) bar_arrive(2, 384);
        };
        if (role == 2) helper_loop(Flag<true>()); else helper_loop(Flag<false>());
    }
    TS3C(1);
    if (role == 2 && warp >= 4) last_rows();
    cluster_sync_all();
}

extern "C" void kernel_launch(void* const* d_in, const int* in_sizes, int n_in, void* d_out, int out_size) {
    const bf16* x = (const bf16*)d_in[0];
    const bf16* mem0 = (const bf16*)d_in[1];
    const bf16* Wq = (const bf16*)d_in[2];
    const bf16* Wk = (const bf16*)d_in[3];
    const bf16* Wv = (const bf16*)d_in[4];
    const bf16* Wo = (const bf16*)d_in[5];
    const bf16* logA = (const bf16*)d_in[8];
    const bf16* Aim = (const bf16*)d_in[9];
    const bf16* Cre = (const bf16*)d_in[10];
    const bf16* Cim = (const bf16*)d_in[11];
    const bf16* logdt = (const bf16*)d_in[12];
    const bf16* dskip = (const bf16*)d_in[13];
    const bf16* gw = (const bf16*)d_in[14];
    bf16* out = (bf16*)d_out;
    static bool attr_done = false;
    typedef CUresult (*EncFn)(CUtensorMap*, CUtensorMapDataType, cuuint32_t, void*, const cuuint64_t*, const cuuint64_t*, const cuuint32_t*,
                              const cuuint32_t*, CUtensorMapInterleave, CUtensorMapSwizzle, CUtensorMapL2promotion, CUtensorMapFloatOOBfill);
    static EncFn enc = nullptr;
    if (!attr_done) {
        void* fn = nullptr;
        cudaDriverEntryPointQueryResult qr;
        cudaGetDriverEntryPoint("cuTensorMapEncodeTiled", &fn, cudaEnableDefault, &qr);
        enc = (EncFn)fn;
        cudaFuncSetAttribute(k_chain, cudaFuncAttributeMaxDynamicSharedMemorySize, 232448);
        cudaFuncSetAttribute(k_side, cudaFuncAttributeMaxDynamicSharedMemorySize, SIDE_SMEM);
        attr_done = true;
    }
    CUtensorMap tmw[3];
    for (int i = 0; i < 3; i++) {
        const cuuint64_t dims[2] = {(cuuint64_t)HD, (cuuint64_t)DM};
        const cuuint64_t strides[1] = {(cuuint64_t)HD * 2};
        const cuuint32_t box[2] = {64, 64};
        const cuuint32_t es[2] = {1, 1};
        enc(&tmw[i], CU_TENSOR_MAP_DATA_TYPE_BFLOAT16, 2, (void*)(i == 0 ? Wq : (i == 1 ? Wk : Wv)), dims, strides, box, es, CU_TENSOR_MAP_INTERLEAVE_NONE,
            CU_TENSOR_MAP_SWIZZLE_128B, CU_TENSOR_MAP_L2_PROMOTION_L2_256B, CU_TENSOR_MAP_FLOAT_OOB_FILL_NONE);
    }
    CUtensorMap tmo;
    {
        const cuuint64_t dims[2] = {(cuuint64_t)DM, (cuuint64_t)HD};
        const cuuint64_t strides[1] = {(cuuint64_t)DM * 2};
        const cuuint32_t box[2] = {64, 128};
        const cuuint32_t es[2] = {1, 1};
        enc(&tmo, CU_TENSOR_MAP_DATA_TYPE_BFLOAT16, 2, (void*)Wo, dims, strides, box, es, CU_TENSOR_MAP_INTERLEAVE_NONE,
            CU_TENSOR_MAP_SWIZZLE_128B, CU_TENSOR_MAP_L2_PROMOTION_L2_128B, CU_TENSOR_MAP_FLOAT_OOB_FILL_NONE);
    }
    CUtensorMap tmx2;
    {
        const cuuint64_t dims[2] = {(cuuint64_t)DM, (cuuint64_t)S_LEN};
        const cuuint64_t strides[1] = {(cuuint64_t)DM * 2};
        const cuuint32_t box[2] = {64, 64};
        const cuuint32_t es[2] = {1, 1};
        enc(&tmx2, CU_TENSOR_MAP_DATA_TYPE_BFLOAT16, 2, (void*)x, dims, strides, box, es, CU_TENSOR_MAP_INTERLEAVE_NONE,
            CU_TENSOR_MAP_SWIZZLE_128B, CU_TENSOR_MAP_L2_PROMOTION_L2_128B, CU_TENSOR_MAP_FLOAT_OOB_FILL_NONE);
    }
    CUtensorMap tmm;
    {
        const cuuint64_t dims[2] = {(cuuint64_t)DM, (cuuint64_t)MEMT};
        const cuuint64_t strides[1] = {(cuuint64_t)DM * 2};
        const cuuint32_t box[2] = {64, (cuuint32_t)MEMT};
        const cuuint32_t es[2] = {1, 1};
        enc(&tmm, CU_TENSOR_MAP_DATA_TYPE_BFLOAT16, 2, (void*)mem0, dims, strides, box, es, CU_TENSOR_MAP_INTERLEAVE_NONE,
            CU_TENSOR_MAP_SWIZZLE_128B, CU_TENSOR_MAP_L2_PROMOTION_L2_128B, CU_TENSOR_MAP_FLOAT_OOB_FILL_NONE);
    }
    k_chain<<<NCTA, 384, 232448>>>(tmw[0], tmw[1], tmw[2], tmx2, tmo, tmm, x);
    {
        cudaLaunchConfig_t cfg = {};
        cfg.gridDim = dim3(SD_NCTA); cfg.blockDim = dim3(512); cfg.dynamicSmemBytes = SIDE_SMEM; cfg.stream = cudaStreamPerThread;
        cudaLaunchAttribute at[1];
        at[0].id = cudaLaunchAttributeProgrammaticStreamSerialization;
        at[0].val.programmaticStreamSerializationAllowed = 1;
        cfg.attrs = at; cfg.numAttrs = 1;
        cudaLaunchKernelEx(&cfg, k_side, tmo, x, logA, Aim, Cre, Cim, logdt, Wo, dskip, gw, out);
    }
}
```

```cpp
#include <cuda_runtime.h>
#include <cuda.h>
#include <cuda_bf16.h>
#include <stdint.h>

typedef __nv_bfloat16 bf16;
#define LDV4 "ld.volatile.global.v4.u32 {%0,%1,%2,%3}, [%4];"
#define STV4 "st.volatile.global.v4.u32 [%0], {%1,%2,%3,%4};"
#define STV2 "st.volatile.global.v2.u32 [%0], {%1,%2};"

constexpr int S_LEN = 2048, DM = 576, NH = 32, DH = 128, HD = 4096, MEMT = 8, SEG = 32, NSEG = 64, NST = 128;

__device__ __align__(128) bf16 g_gate[S_LEN];
constexpr int NCTA = NH * 3;
__device__ __align__(1024) unsigned char g_acc[96 * 1024];
__device__ __align__(128) uint2 g_norm[NCTA];
__device__ __align__(128) uint4 g_wv[NH][2];
__device__ __align__(128) uint4 g_rx[NSEG][2];
__device__ __align__(128) unsigned char g_qkv[NSEG][NH][3][10240];
__device__ __align__(128) bf16 g_ox[S_LEN * HD];
__device__ __align__(128) uint4 g_fp[8][36][6][128];
__device__ __align__(128) unsigned g_flag[NH * NSEG];
__device__ __align__(128) unsigned g_prog[8 * 64];
__device__ unsigned g_gcnt[64];
__device__ unsigned g_epoch;
__device__ __align__(128) uint2 g_tick;
__device__ __align__(128) bf16 g_y[DM * S_LEN];

#define TS3(slot) do {} while (0)
#define TS3P(slot) do {} while (0)
#define TSQ(slot) do {} while (0)
#define TS3W(slot) do {} while (0)
#define TSS(row, slot) do {} while (0)
#define TS3C(slot) do {} while (0)
#define TST(slot) do {} while (0)
#define TSA(seg, slot) do {} while (0)
#define TSG(i) do {} while (0)
#define FS(i, dep) do {} while (0)
__device__ __forceinline__ uint32_t smem_u32(const void* p) { return (uint32_t)__cvta_generic_to_shared(p); }
__device__ __forceinline__ float bf16r(float x) { return __bfloat162float(__float2bfloat16_rn(x)); }
__device__ __forceinline__ uint32_t pack_bf16(float lo, float hi) {
    __nv_bfloat162 v = __floats2bfloat162_rn(lo, hi);
    return *reinterpret_cast<uint32_t*>(&v);
}
__device__ __forceinline__ void ldsm_x4(uint32_t (&r)[4], uint32_t addr) {
    asm volatile("ldmatrix.sync.aligned.m8n8.x4.shared.b16 {%0,%1,%2,%3}, [%4];"
                 : "=r"(r[0]), "=r"(r[1]), "=r"(r[2]), "=r"(r[3]) : "r"(addr));
}
__device__ __forceinline__ void ldsm_x4_t(uint32_t (&r)[4], uint32_t addr) {
    asm volatile("ldmatrix.sync.aligned.m8n8.x4.trans.shared.b16 {%0,%1,%2,%3}, [%4];"
                 : "=r"(r[0]), "=r"(r[1]), "=r"(r[2]), "=r"(r[3]) : "r"(addr));
}
__device__ __forceinline__ void mma_bf16(float (&d)[4], const uint32_t (&a)[4], uint32_t b0, uint32_t b1) {
    asm volatile("mma.sync.aligned.m16n8k16.row.col.f32.bf16.bf16.f32 {%0,%1,%2,%3}, {%4,%5,%6,%7}, {%8,%9}, {%0,%1,%2,%3};"
                 : "+f"(d[0]), "+f"(d[1]), "+f"(d[2]), "+f"(d[3])
                 : "r"(a[0]), "r"(a[1]), "r"(a[2]), "r"(a[3]), "r"(b0), "r"(b1));
}
__device__ __forceinline__ uint2 ld_vol_u2(const uint2* p) {
    uint2 v; asm volatile("ld.volatile.global.v2.u32 {%0,%1}, [%2];" : "=r"(v.x), "=r"(v.y) : "l"(p) : "memory"); return v;
}
__device__ __forceinline__ void st_vol_u2(uint2* p, uint2 v) {
    asm volatile(STV2 :: "l"(p), "r"(v.x), "r"(v.y) : "memory");
}
__device__ __forceinline__ unsigned ld_acq(const unsigned* p) {
    unsigned v; asm volatile("ld.acquire.gpu.global.u32 %0, [%1];" : "=r"(v) : "l"(p) : "memory"); return v;
}
#define NS 10
#define NP 4
#define GATE_A 950
#define GATE_B 450
#define GATE_P 1800u
#define RLX_SLEEP 300
#define VX_DELAY 100
#define UNGATE_G 3
#define W14_SLEEP 60
#define GL_A 1150
#define GL_B 530
#define GS_A 1300
#define GS_B 480
#define NC1 3
#define NC1C 5
#define KPRE 34
#define WO_SLEEP 200
#define WO_LAG 500
#define TM 29
#define TM2 (TM - 1)
#define TL_DELAY 600
#define POLL_DELAY 590
#define UNGATE 6
constexpr unsigned SPIN_LIMIT = 1u << 20;
constexpr int NATT = NSEG - 2;

constexpr int SD_CH = 16;
constexpr int SD_NCTA = DM / SD_CH;
constexpr int SD_ROW = 528;
constexpr int SD_U = 8 * SD_ROW;
constexpr int SD_TAP = 5888;
constexpr int SD_CPY = 1376 * 2;
constexpr int SD_WSTR = SD_TAP + 2 * SD_CPY;
constexpr int SD_SMEM = SD_CH * SD_U + 8 * SD_WSTR;
constexpr int O_U = 79, O_U3 = 911, O_U4 = 1055, O_W79 = 1023, O_W35 = 1151, O_W610 = 1279, O_W511 = 1487;

__device__ __forceinline__ uint32_t lds32(uint32_t a) { uint32_t v; asm volatile("ld.shared.u32 %0, [%1];" : "=r"(v) : "r"(a)); return v; }
__device__ __forceinline__ void sts32(uint32_t a, uint32_t v) { asm volatile("st.shared.u32 [%0], %1;" :: "r"(a), "r"(v) : "memory"); }
__device__ __forceinline__ uint4 lds128(uint32_t a) {
    uint4 v; asm volatile("ld.shared.v4.u32 {%0,%1,%2,%3}, [%4];" : "=r"(v.x), "=r"(v.y), "=r"(v.z), "=r"(v.w) : "r"(a) : "memory"); return v;
}
__device__ __forceinline__ void tap_tile(uint32_t (&t)[4], uint32_t a) {
    asm volatile("ld.volatile.shared.u32 %0, [%4];\nld.volatile.shared.u32 %1, [%4+-16];\nld.volatile.shared.u32 %2, [%4+16];\nld.volatile.shared.u32 %3, [%4];"
                 : "=r"(t[0]), "=r"(t[1]), "=r"(t[2]), "=r"(t[3]) : "r"(a));
}
constexpr uint32_t sd_pass(int type, int dl, int o, int d0, int d1) { return (uint32_t)(type | dl << 2 | d0 << 8 | d1 << 12 | o << 17); }
__constant__ uint32_t SD_PASS[14] = {sd_pass(0, 0, O_U, 0, 2), sd_pass(0, 1, O_U + 96, 0, 2), sd_pass(0, 2, O_U + 192, 0, 4), sd_pass(0, 3, O_U + 288, 0, 2), sd_pass(1, 0, O_U3, 8, 8),
                                     sd_pass(0, 4, O_U + 384, 0, 2), sd_pass(1, 0, O_U4, 8, 15), sd_pass(0, 5, O_U + 480, 0, 2), sd_pass(0, 6, O_U + 576, 0, 4), sd_pass(0, 7, O_U + 672, 0, 2),
                                     sd_pass(2, 0, O_W35, 2, 8), sd_pass(3, 0, O_W79, 2, 4), sd_pass(2, 1, O_W610, 4, 8), sd_pass(3, 0, O_W511, 8, 15)};
__device__ __forceinline__ uint32_t band2(int x, int lo, int hi) { return (x >= lo && x <= hi ? 0x3f80u : 0u) | (x + 1 >= lo && x + 1 <= hi ? 0x3f800000u : 0u); }
__device__ __forceinline__ void mma_z(float (&d)[4], const uint32_t (&a)[4], uint32_t b0, uint32_t b1);
__device__ __forceinline__ void put_tap(uint32_t a, float v) {
    asm volatile("{\n.reg .b16 h;\ncvt.rn.bf16.f32 h, %1;\nst.shared.b16 [%0], h;\nst.shared.b16 [%0+%2], h;\n}" :: "r"(a), "f"(v), "n"(SD_CPY - 2) : "memory");
}

__device__ __forceinline__ void named_bar(int id, int n) { asm volatile("bar.sync %0, %1;" :: "r"(id), "r"(n) : "memory"); }
__device__ __forceinline__ uint32_t pack_f16(float lo, float hi) {
    uint32_t r; asm("cvt.rn.f16x2.f32 %0, %1, %2;" : "=r"(r) : "f"(hi), "f"(lo)); return r;
}
__device__ __forceinline__ void cexp_t(float lr, float turns, float& re, float& im) {
    float m;
    asm("ex2.approx.ftz.f32 %0, %1;" : "=f"(m) : "f"(lr));
    const float a = (turns - rintf(turns)) * 6.283185307179586f;
    re = m * __cosf(a); im = m * __sinf(a);
}
__device__ __forceinline__ void csq(float& re, float& im) { const float r = re * re - im * im; im = 2.f * re * im; re = r; }
__device__ __forceinline__ void kb_state(const float* tp, float gf, uint32_t (&a)[4][2], uint32_t (&b)[5]) {
    const float4 p0 = *reinterpret_cast<const float4*>(tp), p1 = *reinterpret_cast<const float4*>(tp + 4);
    float wr, wi;
    cexp_t(p0.x * gf, p0.y * gf, wr, wi);
    float vr = wr * p1.x - wi * p1.y, vi = wr * p1.y + wi * p1.x;
#pragma unroll
    for (int c = 0; c < 4; c++) {
        a[c][0] = pack_f16(wr, wi); a[c][1] = pack_f16(vr, vi);
        csq(wr, wi);
        if (c < 3) csq(vr, vi);
    }
    b[0] = pack_f16(p0.z * wr - p0.w * wi, -p0.z * wi - p0.w * wr);
    float er = wr * p1.z - wi * p1.w, ei = wr * p1.w + wi * p1.z;
#pragma unroll
    for (int c = 0; c < 4; c++) {
        b[1 + c] = pack_f16(p0.z * er - p0.w * ei, -p0.z * ei - p0.w * er);
        if (c < 3) csq(er, ei);
    }
}
__device__ __forceinline__ uint32_t bf2_mul(uint32_t a, uint32_t b) { uint32_t r; asm("mul.rn.bf16x2 %0, %1, %2;" : "=r"(r) : "r"(a), "r"(b)); return r; }
__device__ __forceinline__ uint32_t bf2_add(uint32_t a, uint32_t b) { uint32_t r; asm("add.rn.bf16x2 %0, %1, %2;" : "=r"(r) : "r"(a), "r"(b)); return r; }
__device__ __forceinline__ uint32_t bf2_sub(uint32_t a, uint32_t b) { uint32_t r; asm("sub.rn.bf16x2 %0, %1, %2;" : "=r"(r) : "r"(a), "r"(b)); return r; }
__device__ __forceinline__ void wait_cnt(const unsigned* p, unsigned target) {
    unsigned it = 0;
    while ((int)(ld_acq(p) - target) < 0 && ++it < SPIN_LIMIT) __nanosleep(64);
}
__device__ __forceinline__ uint32_t gtime32() { uint32_t t; asm volatile("mov.u32 %0, %%globaltimer_lo;" : "=r"(t) :: "memory"); return t; }
__device__ __forceinline__ void gate(uint32_t tick_addr, uint32_t ga = GATE_A, uint32_t gb = GATE_B) {
    uint32_t t1, p;
    asm volatile("ld.volatile.shared.v2.u32 {%0,%1}, [%2];" : "=r"(t1), "=r"(p) : "r"(tick_addr) : "memory");
    uint32_t d = gtime32() - t1;
    if (d < 4u * p) {
        d -= d >= 2u * p ? 2u * p : 0u;
        d -= d >= p ? p : 0u;
        if (d + ga >= p && d + gb < p) {
            const uint32_t t2 = gtime32() + (p - gb - d);
            while ((int)(gtime32() - t2) < 0) {}
        }
    }
}

__device__ __forceinline__ void read_tick(uint32_t tick_addr) {
    const uint2 tk = ld_vol_u2(&g_tick);
    uint32_t p = tk.x - tk.y;
    p = p > GATE_P + 100u ? GATE_P + 100u : p;
    asm volatile("st.volatile.shared.v2.u32 [%0], {%1,%2};" :: "r"(tick_addr), "r"(tk.x), "r"(p) : "memory");
}

__device__ __forceinline__ void s4d_phase(unsigned char* smem_raw, const bf16* __restrict__ x, const bf16* __restrict__ logA,
                                          const bf16* __restrict__ Aim, const bf16* __restrict__ Cre, const bf16* __restrict__ Cim,
                                          const bf16* __restrict__ logdt, const bf16* __restrict__ dskip, const bf16* __restrict__ wslice) {
    const int tid = threadIdx.x, warp = __shfl_sync(0xffffffffu, tid >> 5, 0), lane = tid & 31;
    const int d0 = blockIdx.x * SD_CH;
    float* tab = reinterpret_cast<float*>(smem_raw + SD_CH * SD_U + warp * SD_WSTR);
    const uint32_t wb = smem_u32(tab);
    const int g = lane >> 2, tq = lane & 3;
    uint2 prm[4];
    float ldt;
    auto load_prm = [&](int d) {
        prm[0] = __ldg(reinterpret_cast<const uint2*>(logA + d * NST) + lane); prm[1] = __ldg(reinterpret_cast<const uint2*>(Aim + d * NST) + lane);
        prm[2] = __ldg(reinterpret_cast<const uint2*>(Cre + d * NST) + lane); prm[3] = __ldg(reinterpret_cast<const uint2*>(Cim + d * NST) + lane);
        ldt = __bfloat162float(logdt[d]);
    };
    load_prm(d0 + warp);
    for (int i = lane; i < 2 * SD_CPY / 16; i += 32) reinterpret_cast<uint4*>(tab + SD_TAP / 4)[i] = make_uint4(0u, 0u, 0u, 0u);
    TS3(20);
#pragma unroll 1
    for (int ch = 0; ch < 2; ch++) {
        const int d = d0 + 8 * ch + warp;
        const uint32_t ub = smem_u32(smem_raw) + (8 * ch + warp) * SD_U;
        float k2048 = 0.f, sinv;
        {
            const float dt = bf16r(expf(ldt));
            uint32_t cm = __vmaxu2(__vmaxu2(prm[2].x & 0x7fff7fffu, prm[2].y & 0x7fff7fffu), __vmaxu2(prm[3].x & 0x7fff7fffu, prm[3].y & 0x7fff7fffu));
            cm = __reduce_max_sync(0xffffffffu, max(cm << 16, cm & 0xffff0000u));
            int e = 134 - (int)(__float_as_uint(__uint_as_float(cm) * dt) >> 23);
            e = e > 100 ? 100 : (e < -100 ? -100 : e);
            const float s2 = __uint_as_float((uint32_t)(128 + e) << 23);
            sinv = __uint_as_float((uint32_t)(127 - e) << 23);
#pragma unroll
            for (int j = 0; j < 4; j++) {
                float q[4];
#pragma unroll
                for (int i = 0; i < 4; i++) { const uint32_t w = j < 2 ? prm[i].x : prm[i].y; q[i] = __uint_as_float((j & 1) ? w & 0xffff0000u : w << 16); }
                const float zl = -bf16r(expf(q[0])) * dt * 1.4426950408889634f;
                const float zt = q[1] * dt * 0.15915494309189535f;
                const float cr = s2 * (q[2] * dt), ci = s2 * (q[3] * dt);
                float ar, ai, br, bi, er, ei;
                cexp_t(zl * 8.f, zt * 8.f, ar, ai);
                cexp_t(zl * 128.f, zt * 128.f, br, bi);
                cexp_t(zl * 2048.f, zt * 2048.f, er, ei);
                k2048 += cr * er - ci * ei;
                *reinterpret_cast<float4*>(tab + (lane + 32 * j) * 8) = make_float4(zl, zt, cr, ci);
                *reinterpret_cast<float4*>(tab + (lane + 32 * j) * 8 + 4) = make_float4(ar, ai, br, bi);
            }
#pragma unroll
            for (int o = 16; o; o >>= 1) k2048 += __shfl_xor_sync(0xffffffffu, k2048, o);
        }
        __syncwarp();
        {
            float kc[5][4];
#pragma unroll
            for (int i = 0; i < 5; i++) { kc[i][0] = kc[i][1] = kc[i][2] = kc[i][3] = 0.f; }
            const float gf = (float)g;
#pragma unroll 2
            for (int ks = 0; ks < 16; ks++) {
                uint32_t a0[4][2], a1[4][2], b0[5], b1[5];
                kb_state(tab + (8 * ks + tq) * 8, gf, a0, b0);
                kb_state(tab + (8 * ks + 4 + tq) * 8, gf, a1, b1);
#pragma unroll
                for (int i = 0; i < 5; i++) {
                    const int c = i > 0 ? i - 1 : 0;
                    asm volatile("mma.sync.aligned.m16n8k16.row.col.f32.f16.f16.f32 {%0,%1,%2,%3}, {%4,%5,%6,%7}, {%8,%9}, {%0,%1,%2,%3};"
                                 : "+f"(kc[i][0]), "+f"(kc[i][1]), "+f"(kc[i][2]), "+f"(kc[i][3])
                                 : "r"(a0[c][0]), "r"(a0[c][1]), "r"(a1[c][0]), "r"(a1[c][1]), "r"(b0[i]), "r"(b1[i]));
                }
            }
            const uint32_t tp = wb + SD_TAP;
            const uint32_t a0 = tp + 2 * (O_U + 96 * g - 4 * tq);
            const uint32_t a2 = tp + 2 * (((g & 1) ? O_U + 96 * (2 * (g & 3)) : ((g & 2) ? O_W35 : O_W79 + 1)) - 32 - 8 * tq - (g >> 2));
            const uint32_t a3 = tp + 2 * (((g & 1) ? O_W35 : O_W610 + 1) - 64 - 16 * tq - (g >> 1));
            const uint32_t a4 = tp + 2 * (-128 - 32 * tq - g);
#pragma unroll
            for (int c = 0; c < 4; c++) {
                const int e = (c & 1) * 16 + (c >> 1) * 8;
                const bool first = c == 0 && lane == 0;
                put_tap(a0 - e / 4, kc[0][c] * sinv);
                put_tap(a0 - 32 - e / 4, kc[1][c] * sinv);
                put_tap(first ? tp + 2 * (O_U - 32) : a2 - e / 2, kc[2][c] * sinv);
                put_tap(first ? tp + 2 * (O_W79 - 63) : a3 - e, kc[3][c] * sinv);
                put_tap(first ? tp + 2 * (O_W610 - 127) : a4 + 2 * (O_W511 + 1 - e), kc[4][c] * sinv);
                if ((g & 1) == 0) {
                    put_tap(a4 + 2 * (O_U4 - e), kc[4][c] * sinv);
                    put_tap(first ? tp + 2 * (O_U3 - 128) : a4 + 2 * (O_U4 + 1 - e), kc[4][c] * sinv);
                }
            }
            if (lane == 0) {
                put_tap(tp + 2 * (O_U + 96 - 32), kc[2][0] * sinv);
                put_tap(tp + 2 * (O_U + 192 - 64), kc[3][0] * sinv);
                put_tap(tp + 2 * (O_W511 - 255), k2048 * sinv);
                put_tap(tp + 2 * (O_U4 - 255), k2048 * sinv);
            }
        }
        TS3(21 + 2 * ch);
        if (ch == 0) named_bar(1, 384);
        else {
#pragma unroll
            for (int i = 0; i < 4; i++) asm volatile("prefetch.global.L2 [%0];" :: "l"(wslice + (size_t)((tid & 127) + 128 * i) * DM));
        }
        __syncwarp();
        if (tid == 0) TSS(18, 4 * ch);
        const uint32_t sh = wb + 80 + 11 * SD_ROW;
#pragma unroll
        for (int p = 0; p < 8; p++) {
            uint4 v;
            asm volatile("ld.shared.v4.u32 {%0,%1,%2,%3}, [%4];" : "=r"(v.x), "=r"(v.y), "=r"(v.z), "=r"(v.w) : "r"(ub + p * SD_ROW + lane * 16) : "memory");
            uint32_t pv = __shfl_up_sync(0xffffffffu, v.w, 1);
            pv = lane == 0 ? 0u : pv;
            asm volatile("st.shared.v4.u32 [%0], {%1,%2,%3,%4};" :: "r"(sh + (p - 8) * SD_ROW + lane * 16), "r"(__byte_perm(pv, v.x, 0x5432)), "r"(__byte_perm(v.x, v.y, 0x5432)),
                         "r"(__byte_perm(v.y, v.z, 0x5432)), "r"(__byte_perm(v.z, v.w, 0x5432)) : "memory");
            if (p >= 5) asm volatile("st.shared.v4.u32 [%0], {%1,%2,%3,%4};" :: "r"(sh + (p - 16) * SD_ROW + lane * 16), "r"(pv), "r"(v.x), "r"(v.y), "r"(v.z) : "memory");
        }
        __syncwarp();
        if (tid == 0) TSS(18, 4 * ch + 1);
        float acc[16][4];
#pragma unroll
        for (int i = 0; i < 16; i++) { acc[i][0] = acc[i][1] = acc[i][2] = acc[i][3] = 0.f; }
        {
            const uint32_t ka = wb + SD_TAP + ((g & 1) ? 0 : SD_CPY - 2) + 2 * (2 * tq - g);
            uint32_t b[16][2], b2[14][2];
#pragma unroll
            for (int k = 0; k < 16; k++) { b[k][0] = b[k][1] = 0u; if (k < 14) b2[k][0] = b2[k][1] = 0u; }
#pragma unroll 1
            for (int ps = 0; ps < 14; ps++) {
                const uint32_t pw = __shfl_sync(0xffffffffu, SD_PASS[ps], 0), type = pw & 3u, kp = ka + (pw >> 16);
                const int dl = (pw >> 2) & 7, d0 = (pw >> 8) & 15, d1 = (pw >> 12) & 15;
                uint32_t t[2][4];
                tap_tile(t[0], kp - 32 * d0);
                if (type == 0) {
                    const int p = (lane & 7) - dl;
                    const uint32_t ra = (p < 0 ? sh : ub) + p * SD_ROW + (lane >> 3) * 16;
#pragma unroll
                    for (int k = 0; k < 8; k++)
                        asm volatile("ldmatrix.sync.aligned.m8n8.x4.shared.b16 {%0,%1,%2,%3}, [%4];"
                                     : "=r"(b[2 * k][0]), "=r"(b[2 * k][1]), "=r"(b[2 * k + 1][0]), "=r"(b[2 * k + 1][1]) : "r"(ra + k * 64));
                } else if (type == 2) {
                    const int p = (lane & 15) - 11, xo = 2 * tq - g;
                    const uint32_t qa = (p < 0 ? sh : ub) + p * SD_ROW + (lane >> 4) * 16;
                    const int lx = 6 - 5 * dl, hx = 8 - 3 * dl, ly = 2 - 2 * dl, hy = 4 + 2 * dl;
                    const uint32_t sel[4] = {band2(xo, lx, hx), band2(xo, ly, hy), band2(xo + 8, lx, hx), band2(xo + 8, ly, hy)};
#pragma unroll
                    for (int k = 0; k < 14; k++) {
                        uint32_t q[4];
                        ldsm_x4_t(q, qa + k * 32);
#pragma unroll
                        for (int i = 0; i < 2; i++) {
                            float w[4];
                            mma_z(w, sel, q[2 * i], q[2 * i + 1]);
                            b[k][i] = pack_bf16(w[0], w[1]);
                            b2[k][i] = pack_bf16(w[2], w[3]);
                        }
                    }
                } else if (type == 3) {
#pragma unroll
                    for (int k = 0; k < 14; k++) { b[k][0] = b2[k][0]; b[k][1] = b2[k][1]; }
                }
#pragma unroll
                for (int d = 0; d < 16; d += 2) {
                    if (d >= 8 || d >= d0) {
                        tap_tile(t[1], kp - 32 * (d + 1));
#pragma unroll
                        for (int k = 0; k + d < 16; k++) mma_bf16(acc[k + d], t[0], b[k][0], b[k][1]);
                        if ((d == 2 || d == 4 || d == 8) && d == d1) break;
                        if (d < 14) tap_tile(t[0], kp - 32 * (d + 2));
#pragma unroll
                        for (int k = 0; k + d + 1 < 16; k++) mma_bf16(acc[k + d + 1], t[1], b[k][0], b[k][1]);
                    }
                }
            }
        }
        __syncwarp();
        if (tid == 0) TSS(18, 4 * ch + 2);
        load_prm(d0 + 8 + warp);
        if (ch == 0) {
            if (lane == 0) {
                unsigned ep;
                asm volatile("ld.volatile.global.u32 %0, [%1];" : "=r"(ep) : "l"(&g_epoch) : "memory");
                wait_cnt(&g_gcnt[0], SD_NCTA * (ep + 1u));
            }
            __syncwarp();
        }
        if (tid == 0) TSS(18, 4 * ch + 3);
        uint4 gv[8];
#pragma unroll
        for (int i = 0; i < 8; i++) gv[i] = __ldcg(reinterpret_cast<const uint4*>(g_gate) + lane + 32 * i);
        const uint32_t dd = __byte_perm(*reinterpret_cast<const unsigned short*>(dskip + d), 0u, 0x1010);
#pragma unroll
        for (int i = 0; i < 8; i++) {
            uint32_t u[4];
            ldsm_x4_t(u, ub + (lane & 7) * SD_ROW + (lane >> 3) * 16 + i * 64);
            asm volatile("stmatrix.sync.aligned.m8n8.x4.shared.b16 [%0], {%1,%2,%3,%4};"
                         :: "r"(wb + (lane + 32 * i) * 16),
                            "r"(bf2_add(pack_bf16(acc[2 * i][0], acc[2 * i][1]), bf2_mul(u[0], dd))), "r"(bf2_add(pack_bf16(acc[2 * i][2], acc[2 * i][3]), bf2_mul(u[1], dd))),
                            "r"(bf2_add(pack_bf16(acc[2 * i + 1][0], acc[2 * i + 1][1]), bf2_mul(u[2], dd))), "r"(bf2_add(pack_bf16(acc[2 * i + 1][2], acc[2 * i + 1][3]), bf2_mul(u[3], dd))) : "memory");
        }
        __syncwarp();
#pragma unroll
        for (int i = 0; i < 8; i++) {
            const uint4 y = *reinterpret_cast<const uint4*>(tab + (lane + 32 * i) * 4);
            *reinterpret_cast<uint4*>(g_y + (((lane >> 1) + 16 * i) * DM + d) * 16 + (lane & 1) * 8) =
                make_uint4(bf2_mul(bf2_sub(0x3f803f80u, gv[i].x), y.x), bf2_mul(bf2_sub(0x3f803f80u, gv[i].y), y.y),
                           bf2_mul(bf2_sub(0x3f803f80u, gv[i].z), y.z), bf2_mul(bf2_sub(0x3f803f80u, gv[i].w), y.w));
        }
        __syncwarp();
        if (ch == 0) asm volatile("bar.arrive 11, 288;" ::: "memory");
        TS3(22 + 2 * ch);
    }
}
__device__ __forceinline__ void s4d_stage_u(unsigned char* smem_raw, const bf16* __restrict__ x, int pt) {
    const int p = pt & 7, w0 = pt >> 3;
    const uint4* src = reinterpret_cast<const uint4*>(x + (size_t)(16 * w0 + p) * DM + blockIdx.x * SD_CH);
    uint32_t* dst = reinterpret_cast<uint32_t*>(smem_raw + p * SD_ROW) + w0;
#pragma unroll 1
    for (int b = 0; b < 4; b++) {
        uint4 v[2][2][2];
#pragma unroll
        for (int i = 0; i < 8; i++) v[i >> 2][(i >> 1) & 1][i & 1] = src[((b * 2 + (i >> 2)) * 256 + ((i >> 1) & 1) * 8) * (DM / 8) + (i & 1)];
#pragma unroll
        for (int i = 0; i < 4; i++) {
            const uint32_t* lo = reinterpret_cast<const uint32_t*>(&v[i >> 1][0][i & 1]);
            const uint32_t* hi = reinterpret_cast<const uint32_t*>(&v[i >> 1][1][i & 1]);
#pragma unroll
            for (int c = 0; c < 8; c++) dst[((i & 1) * 8 + c) * (SD_U / 4) + (b * 2 + (i >> 1)) * 16] = __byte_perm(lo[c >> 1], hi[c >> 1], (c & 1) ? 0x7632 : 0x5410);
        }
    }
    asm volatile("bar.arrive 1, 384;" ::: "memory");
}

constexpr int WOC = DM / 3;
constexpr int TBUF = 5 * DH * 16;
constexpr int XBUF = SEG * DM * 2;
constexpr int SM_BAR = 0;
constexpr int B_SB = 0, B_VX = 16, B_XT = 32, B_XF = 144, B_W = 64, B_E = 136;
constexpr int SM_SC = 256;
constexpr int SM_F = SM_SC + 1280;
constexpr int SM_VM = SM_F + 2048;
constexpr int SM_S = SM_VM + 2048;
constexpr int SM_O = SM_S + 2560;
constexpr int SM_M = SM_O + 2048;
constexpr int SM_WS = 19456;
constexpr int SM_T = SM_WS + 49152;
constexpr int SM_VX = SM_T + 4 * TBUF;
constexpr int SM_X = SM_VX + 2 * 8192;
constexpr int SM_X01 = SM_WS + DM * DH * 2;
__host__ __device__ constexpr int x01_off(int b) { return b < 2 ? 1024 + b * 9216 : SM_X01 + (b == 2 ? 6 : b - 3) * 9216; }
__host__ __device__ constexpr int x23_off(int b) { return b < 3 ? SM_WS + 7 * 16384 + b * 8192 : x01_off(b - 3); }
constexpr int CH_SMEM = SM_X01 + 8 * 8192;
static_assert(SM_M + DM * 16 <= SM_WS && SM_X + 13 * 8192 <= CH_SMEM && NS <= 10 && CH_SMEM <= 232448 && SM_X % 1024 == 0 && SM_X01 % 1024 == 0 && 1024 + 2 * 9216 <= SM_WS, "smem");
__device__ __forceinline__ uint32_t clock32() { uint32_t t; asm volatile("mov.u32 %0, %%clock;" : "=r"(t) :: "memory"); return t; }

__device__ __forceinline__ uint32_t mapa(uint32_t a, uint32_t rank) {
    uint32_t r; asm volatile("mapa.shared::cluster.u32 %0, %1, %2;" : "=r"(r) : "r"(a), "r"(rank)); return r;
}
__device__ __forceinline__ void st_async32(uint32_t addr, uint32_t v, uint32_t mbar) {
    asm volatile("st.async.weak.shared::cluster.mbarrier::complete_tx::bytes.b32 [%0], %1, [%2];" :: "r"(addr), "r"(v), "r"(mbar) : "memory");
}
__device__ __forceinline__ void mbar_init(uint32_t bar, uint32_t cnt) {
    asm volatile("mbarrier.init.shared::cta.b64 [%0], %1;" :: "r"(bar), "r"(cnt) : "memory");
}
__device__ __forceinline__ void mbar_expect(uint32_t bar, uint32_t bytes) {
    asm volatile("mbarrier.arrive.expect_tx.shared::cta.b64 _, [%0], %1;" :: "r"(bar), "r"(bytes) : "memory");
}
__device__ __forceinline__ void mbar_wait(uint32_t bar, uint32_t parity) {
    unsigned it = 0;
    uint32_t ok;
    do {
        ++it;
        asm volatile("{\n.reg .pred p;\nmbarrier.try_wait.parity.shared::cta.b64 p, [%1], %2;\nselp.u32 %0, 1, 0, p;\n}" : "=r"(ok) : "r"(bar), "r"(parity) : "memory");
    } while ((ok == 0u) & (it < SPIN_LIMIT));
}
__device__ __forceinline__ void mbar_wait_long(uint32_t bar, uint32_t parity) {
    unsigned it = 0;
    while (true) {
        uint32_t ok;
        asm volatile("{\n.reg .pred p;\nmbarrier.try_wait.parity.shared::cta.b64 p, [%1], %2, %3;\nselp.u32 %0, 1, 0, p;\n}"
                     : "=r"(ok) : "r"(bar), "r"(parity), "r"(20000u) : "memory");
        if (ok || ++it >= SPIN_LIMIT) break;
    }
}
__device__ __forceinline__ bool mbar_test(uint32_t bar, uint32_t parity) {
    uint32_t ok;
    asm volatile("{\n.reg .pred p;\nmbarrier.test_wait.parity.shared::cta.b64 p, [%1], %2;\nselp.u32 %0, 1, 0, p;\n}" : "=r"(ok) : "r"(bar), "r"(parity) : "memory");
    return ok != 0u;
}
__device__ __forceinline__ uint64_t policy_evict_first() {
    uint64_t pol; asm volatile("createpolicy.fractional.L2::evict_first.b64 %0, 1.0;" : "=l"(pol)); return pol;
}
__device__ __forceinline__ void cluster_sync_all() {
    asm volatile("barrier.cluster.arrive.release.aligned;\nbarrier.cluster.wait.acquire.aligned;" ::: "memory");
}
__device__ __forceinline__ uint4 ld_vol_u4(const uint4* p) {
    uint4 v; asm volatile(LDV4 : "=r"(v.x), "=r"(v.y), "=r"(v.z), "=r"(v.w) : "l"(p) : "memory"); return v;
}
__device__ __forceinline__ void ld_vol_u4_p(uint4& v, const uint4* p, uint32_t pred) {
    asm volatile("{\n.reg .pred p;\nsetp.ne.u32 p, %5, 0;\n@p " LDV4 "\n}"
                 : "+r"(v.x), "+r"(v.y), "+r"(v.z), "+r"(v.w) : "l"(p), "r"(pred) : "memory");
}
__device__ __forceinline__ void st_vol_u4(uint4* p, uint4 v) {
    asm volatile(STV4 :: "l"(p), "r"(v.x), "r"(v.y), "r"(v.z), "r"(v.w) : "memory");
}
__device__ __forceinline__ void mma_bf16_r(float (&d)[4], uint32_t a0, uint32_t a1, uint32_t a2, uint32_t a3, uint32_t b0, uint32_t b1) {
    asm volatile("mma.sync.aligned.m16n8k16.row.col.f32.bf16.bf16.f32 {%0,%1,%2,%3}, {%4,%5,%6,%7}, {%8,%9}, {%0,%1,%2,%3};"
                 : "+f"(d[0]), "+f"(d[1]), "+f"(d[2]), "+f"(d[3])
                 : "r"(a0), "r"(a1), "r"(a2), "r"(a3), "r"(b0), "r"(b1));
}

__device__ __forceinline__ uint64_t smem_desc(uint32_t addr, uint32_t lbo, uint32_t sbo) {
    return (uint64_t)((addr & 0x3FFFF) >> 4) | ((uint64_t)(lbo >> 4) << 16) | ((uint64_t)(sbo >> 4) << 32);
}
__device__ __forceinline__ void wg_fence() { asm volatile("wgmma.fence.sync.aligned;" ::: "memory"); }
__device__ __forceinline__ void wg_commit() { asm volatile("wgmma.commit_group.sync.aligned;" ::: "memory"); }
__device__ __forceinline__ void wg_wait0() { asm volatile("wgmma.wait_group.sync.aligned 0;" ::: "memory"); }
__device__ __forceinline__ void fence_async() { asm volatile("fence.proxy.async.shared::cta;" ::: "memory"); }
__device__ __forceinline__ void wgmma_n64_ss(float (&d)[32], uint64_t adesc, uint64_t bdesc) {
    asm volatile("{\n.reg .pred p;\nsetp.eq.b32 p, 0, 0;\n"
                 "wgmma.mma_async.sync.aligned.m64n64k16.f32.bf16.bf16 {%0,%1,%2,%3,%4,%5,%6,%7,%8,%9,%10,%11,%12,%13,%14,%15,%16,%17,%18,%19,%20,%21,%22,%23,%24,%25,%26,%27,%28,%29,%30,%31}, %32, %33, p, 1, 1, 1, 0;\n}"
                 : "+f"(d[0]), "+f"(d[1]), "+f"(d[2]), "+f"(d[3]), "+f"(d[4]), "+f"(d[5]), "+f"(d[6]), "+f"(d[7]), "+f"(d[8]), "+f"(d[9]), "+f"(d[10]), "+f"(d[11]), "+f"(d[12]), "+f"(d[13]), "+f"(d[14]), "+f"(d[15]), "+f"(d[16]), "+f"(d[17]), "+f"(d[18]), "+f"(d[19]), "+f"(d[20]), "+f"(d[21]), "+f"(d[22]), "+f"(d[23]), "+f"(d[24]), "+f"(d[25]), "+f"(d[26]), "+f"(d[27]), "+f"(d[28]), "+f"(d[29]), "+f"(d[30]), "+f"(d[31])
                 : "l"(adesc), "l"(bdesc));
}
__device__ __forceinline__ void wgmma_n72_ss(float (&d)[36], uint64_t adesc, uint64_t bdesc) {
    asm volatile("{\n.reg .pred p;\nsetp.eq.b32 p, 0, 0;\n"
                 "wgmma.mma_async.sync.aligned.m64n72k16.f32.bf16.bf16 {%0,%1,%2,%3,%4,%5,%6,%7,%8,%9,%10,%11,%12,%13,%14,%15,%16,%17,%18,%19,%20,%21,%22,%23,%24,%25,%26,%27,%28,%29,%30,%31,%32,%33,%34,%35}, %36, %37, p, 1, 1, 1, 0;\n}"
                 : "+f"(d[0]), "+f"(d[1]), "+f"(d[2]), "+f"(d[3]), "+f"(d[4]), "+f"(d[5]), "+f"(d[6]), "+f"(d[7]), "+f"(d[8]), "+f"(d[9]), "+f"(d[10]), "+f"(d[11]), "+f"(d[12]), "+f"(d[13]), "+f"(d[14]), "+f"(d[15]), "+f"(d[16]), "+f"(d[17]), "+f"(d[18]), "+f"(d[19]), "+f"(d[20]), "+f"(d[21]), "+f"(d[22]), "+f"(d[23]), "+f"(d[24]), "+f"(d[25]), "+f"(d[26]), "+f"(d[27]), "+f"(d[28]), "+f"(d[29]), "+f"(d[30]), "+f"(d[31]), "+f"(d[32]), "+f"(d[33]), "+f"(d[34]), "+f"(d[35])
                 : "l"(adesc), "l"(bdesc));
}
__device__ __forceinline__ void tma_2d(uint32_t dst, const CUtensorMap* tm, int c0, int c1, uint32_t mbar) {
    asm volatile("cp.async.bulk.tensor.2d.shared::cluster.global.tile.mbarrier::complete_tx::bytes [%0], [%1, {%2, %3}], [%4];"
                 :: "r"(dst), "l"(tm), "r"(c0), "r"(c1), "r"(mbar) : "memory");
}

__device__ __forceinline__ void bulk_g2s(uint32_t dst, const void* src, uint32_t bytes, uint32_t mbar) {
    asm volatile("cp.async.bulk.shared::cluster.global.mbarrier::complete_tx::bytes [%0], [%1], %2, [%3];"
                 :: "r"(dst), "l"(src), "r"(bytes), "r"(mbar) : "memory");
}
__device__ __forceinline__ void bulk_g2s_h(uint32_t dst, const void* src, uint32_t bytes, uint32_t mbar, uint64_t pol) {
    asm volatile("cp.async.bulk.shared::cluster.global.mbarrier::complete_tx::bytes.L2::cache_hint [%0], [%1], %2, [%3], %4;"
                 :: "r"(dst), "l"(src), "r"(bytes), "r"(mbar), "l"(pol) : "memory");
}
__device__ __forceinline__ void tma_2d_mc(uint32_t dst, const CUtensorMap* tm, int c0, int c1, uint32_t mbar) {
    asm volatile("cp.async.bulk.tensor.2d.shared::cluster.global.tile.mbarrier::complete_tx::bytes.multicast::cluster [%0], [%1, {%2, %3}], [%4], %5;"
                 :: "r"(dst), "l"(tm), "r"(c0), "r"(c1), "r"(mbar), "h"((unsigned short)7) : "memory");
}
__device__ __forceinline__ void bulk_s2s(uint32_t dst, uint32_t src, uint32_t bytes, uint32_t mbar) {
    asm volatile("cp.async.bulk.shared::cluster.shared::cta.mbarrier::complete_tx::bytes [%0], [%1], %2, [%3];"
                 :: "r"(dst), "r"(src), "r"(bytes), "r"(mbar) : "memory");
}
__device__ __forceinline__ void wgmma_n40_ss(float (&d)[20], uint64_t adesc, uint64_t bdesc, int scale_d) {
    asm volatile("{\n.reg .pred p;\nsetp.ne.b32 p, %22, 0;\n"
                 "wgmma.mma_async.sync.aligned.m64n40k16.f32.bf16.bf16 {%0,%1,%2,%3,%4,%5,%6,%7,%8,%9,%10,%11,%12,%13,%14,%15,%16,%17,%18,%19}, %20, %21, p, 1, 1, 1, 1;\n}"
                 : "+f"(d[0]), "+f"(d[1]), "+f"(d[2]), "+f"(d[3]), "+f"(d[4]), "+f"(d[5]), "+f"(d[6]), "+f"(d[7]),
                   "+f"(d[8]), "+f"(d[9]), "+f"(d[10]), "+f"(d[11]), "+f"(d[12]), "+f"(d[13]), "+f"(d[14]), "+f"(d[15]),
                   "+f"(d[16]), "+f"(d[17]), "+f"(d[18]), "+f"(d[19])
                 : "l"(adesc), "l"(bdesc), "r"(scale_d));
}
__device__ __forceinline__ void wgmma_n64_z(float (&d)[32], const uint32_t (&a)[4], uint64_t bdesc) {
    asm volatile("{\n.reg .pred p;\nsetp.ne.b32 p, 0, 0;\n"
                 "wgmma.mma_async.sync.aligned.m64n64k16.f32.bf16.bf16 {%0,%1,%2,%3,%4,%5,%6,%7,%8,%9,%10,%11,%12,%13,%14,%15,%16,%17,%18,%19,%20,%21,%22,%23,%24,%25,%26,%27,%28,%29,%30,%31}, {%32,%33,%34,%35}, %36, p, 1, 1, 0;\n}"
                 : "=f"(d[0]), "=f"(d[1]), "=f"(d[2]), "=f"(d[3]), "=f"(d[4]), "=f"(d[5]), "=f"(d[6]), "=f"(d[7]),
                   "=f"(d[8]), "=f"(d[9]), "=f"(d[10]), "=f"(d[11]), "=f"(d[12]), "=f"(d[13]), "=f"(d[14]), "=f"(d[15]),
                   "=f"(d[16]), "=f"(d[17]), "=f"(d[18]), "=f"(d[19]), "=f"(d[20]), "=f"(d[21]), "=f"(d[22]), "=f"(d[23]),
                   "=f"(d[24]), "=f"(d[25]), "=f"(d[26]), "=f"(d[27]), "=f"(d[28]), "=f"(d[29]), "=f"(d[30]), "=f"(d[31])
                 : "r"(a[0]), "r"(a[1]), "r"(a[2]), "r"(a[3]), "l"(bdesc));
}
__device__ __forceinline__ void wgmma_n64(float (&d)[32], const uint32_t (&a)[4], uint64_t bdesc, int scale_d) {
    asm volatile("{\n.reg .pred p;\nsetp.ne.b32 p, %37, 0;\n"
                 "wgmma.mma_async.sync.aligned.m64n64k16.f32.bf16.bf16 {%0,%1,%2,%3,%4,%5,%6,%7,%8,%9,%10,%11,%12,%13,%14,%15,%16,%17,%18,%19,%20,%21,%22,%23,%24,%25,%26,%27,%28,%29,%30,%31}, {%32,%33,%34,%35}, %36, p, 1, 1, 0;\n}"
                 : "+f"(d[0]), "+f"(d[1]), "+f"(d[2]), "+f"(d[3]), "+f"(d[4]), "+f"(d[5]), "+f"(d[6]), "+f"(d[7]),
                   "+f"(d[8]), "+f"(d[9]), "+f"(d[10]), "+f"(d[11]), "+f"(d[12]), "+f"(d[13]), "+f"(d[14]), "+f"(d[15]),
                   "+f"(d[16]), "+f"(d[17]), "+f"(d[18]), "+f"(d[19]), "+f"(d[20]), "+f"(d[21]), "+f"(d[22]), "+f"(d[23]),
                   "+f"(d[24]), "+f"(d[25]), "+f"(d[26]), "+f"(d[27]), "+f"(d[28]), "+f"(d[29]), "+f"(d[30]), "+f"(d[31])
                 : "r"(a[0]), "r"(a[1]), "r"(a[2]), "r"(a[3]), "l"(bdesc), "r"(scale_d));
}

constexpr int SB_FULL = 0, SB_EMPTY = 64, SB_QKF = 128, SB_VF = 144, SB_QKE = 160, SB_VE = 176, SB_OF = 192, SB_WO = 208  , SB_TICK = 216, SB_SEEN = 224, SB_FI = 232, SB_REQ = 240;
constexpr int AT_0 = 256, AT_ST = 10240 + 2 * 9216;
constexpr int FS_A = 58368;
constexpr int FS_P = FS_A + 131072;
constexpr int FS_I = FS_P + 16384;
constexpr int FS_O = FS_I + 12288;
constexpr int FS_Z = FS_O + 12288, FS_G = AT_0 + 2 * AT_ST;
constexpr int SIDE_SMEM = FS_Z + 2048;
static_assert(SIDE_SMEM <= 232448 && FS_G + 128 <= FS_A && FS_A + SD_SMEM <= SIDE_SMEM, "smem");

__device__ __forceinline__ void wg_wait1() { asm volatile("wgmma.wait_group.sync.aligned 1;" ::: "memory"); }
__device__ __forceinline__ void mbar_arrive(uint32_t bar) { asm volatile("mbarrier.arrive.shared::cta.b64 _, [%0];" :: "r"(bar) : "memory"); }
__device__ __forceinline__ void wait_cnt_rlx(const unsigned* p, unsigned target, bool urgent) {
    unsigned it = 0, v;
    while (true) {
        asm volatile("ld.relaxed.gpu.global.u32 %0, [%1];" : "=r"(v) : "l"(p) : "memory");
        if ((int)(v - target) >= 0 || ++it >= SPIN_LIMIT) break;
        if (!urgent) __nanosleep(RLX_SLEEP);
    }
}

__device__ __forceinline__ float xrow_softmax(float (&sc)[20], uint32_t (&p)[5], int wq, int lane) {
    constexpr float EC = (float)(1.4426950408889634 * 0.08838834764831845);
    const int lim = 8 * wq + (lane >> 2) - 2 * (lane & 3);
    float mx = fmaxf(sc[0], sc[1]);
#pragma unroll
    for (int j = 1; j < 5; j++) {
        sc[4 * j] = 8 * j - 8 > lim ? -INFINITY : sc[4 * j];
        sc[4 * j + 1] = 8 * j - 7 > lim ? -INFINITY : sc[4 * j + 1];
    }
    mx = fmaxf(fmaxf(mx, fmaxf(fmaxf(sc[4], sc[5]), fmaxf(sc[8], sc[9]))), fmaxf(fmaxf(sc[12], sc[13]), fmaxf(sc[16], sc[17])));
    {
        const float m1 = __shfl_xor_sync(0xffffffffu, mx, 1), m2 = __shfl_xor_sync(0xffffffffu, mx, 2), m3 = __shfl_xor_sync(0xffffffffu, mx, 3);
        mx = fmaxf(fmaxf(mx, m1), fmaxf(m2, m3));
    }
    float sum = 0.f;
#pragma unroll
    for (int j = 0; j < 5; j++) {
        float e0, e1;
        asm("ex2.approx.ftz.f32 %0, %1;" : "=f"(e0) : "f"((sc[4 * j] - mx) * EC));
        asm("ex2.approx.ftz.f32 %0, %1;" : "=f"(e1) : "f"((sc[4 * j + 1] - mx) * EC));
        p[j] = pack_bf16(e0, e1);
        sum += e0 + e1;
    }
    return sum;
}
__device__ __forceinline__ float xrow_inv(float sum) {
    sum += __shfl_xor_sync(0xffffffffu, sum, 1);
    sum += __shfl_xor_sync(0xffffffffu, sum, 2);
    float r;
    asm("rcp.approx.ftz.f32 %0, %1;" : "=f"(r) : "f"(sum));
    return r;
}

__device__ __forceinline__ void stsm_x4(uint32_t addr, uint32_t r0, uint32_t r1, uint32_t r2, uint32_t r3) {
    asm volatile("stmatrix.sync.aligned.m8n8.x4.shared.b16 [%0], {%1,%2,%3,%4};" :: "r"(addr), "r"(r0), "r"(r1), "r"(r2), "r"(r3) : "memory");
}
__device__ __forceinline__ void xrow_pv(uint32_t (&ob)[16], const uint32_t (&p)[5], float psum, uint32_t vt) {
    float o[32];
    const uint64_t dv = smem_desc(vt, 2048, 128);
    uint32_t pa[6][4];
#pragma unroll
    for (int i = 0; i < 6; i++) {
        const int ks = i >> 1, hf = i & 1;
        pa[i][hf] = p[2 * ks]; pa[i][hf ^ 1] = 0u;
        pa[i][2 + hf] = ks < 2 ? p[ks < 2 ? 2 * ks + 1 : 0] : 0u; pa[i][3 - hf] = 0u;
    }
    wg_fence();
#pragma unroll
    for (int i = 0; i < 6; i++) { if (i == 0) wgmma_n64_z(o, pa[0], dv); else wgmma_n64(o, pa[i], dv + (uint64_t)((i & 1) * 64 + (i >> 1) * 256), 1); }
    wg_commit();
    const float inv = xrow_inv(psum);
    wg_wait0();
#pragma unroll
    for (int i = 0; i < 8; i++) { ob[i] = pack_bf16(o[4 * i] * inv, o[4 * i + 1] * inv); ob[8 + i] = pack_bf16(o[4 * i + 2] * inv, o[4 * i + 3] * inv); }
}
__device__ __forceinline__ uint32_t h2_to_bf2(uint32_t h) {
    uint32_t r;
    asm("{\n.reg .f16 l, h;\n.reg .f32 a, b;\nmov.b32 {l, h}, %1;\ncvt.f32.f16 a, l;\ncvt.f32.f16 b, h;\ncvt.rn.bf16x2.f32 %0, b, a;\n}" : "=r"(r) : "r"(h));
    return r;
}
__device__ __forceinline__ uint32_t max_abs2(uint32_t a, uint32_t b) { uint32_t r; asm("max.NaN.xorsign.abs.bf16x2 %0, %1, %2;" : "=r"(r) : "r"(a), "r"(b)); return r; }
__device__ __forceinline__ uint32_t movm(uint32_t v) {
    uint32_t r; asm volatile("movmatrix.sync.aligned.m8n8.trans.b16 %0, %1;" : "=r"(r) : "r"(v)); return r;
}
__device__ __forceinline__ void bar_arrive(int id, int n) { asm volatile("bar.arrive %0, %1;" :: "r"(id), "r"(n) : "memory"); }
__device__ __forceinline__ void lds64(uint32_t& a, uint32_t& b, uint32_t addr) {
    asm volatile("ld.shared.v2.u32 {%0,%1}, [%2];" : "=r"(a), "=r"(b) : "r"(addr) : "memory");
}
__device__ __forceinline__ void lds64f(float& a, float& b, uint32_t addr) {
    asm volatile("ld.shared.v2.f32 {%0,%1}, [%2];" : "=f"(a), "=f"(b) : "r"(addr) : "memory");
}
__device__ __forceinline__ void st_async64(uint32_t addr, uint32_t a, uint32_t b, uint32_t mbar) {
    asm volatile("st.async.weak.shared::cluster.mbarrier::complete_tx::bytes.v2.b32 [%0], {%1,%2}, [%3];" :: "r"(addr), "r"(a), "r"(b), "r"(mbar) : "memory");
}
__device__ __forceinline__ void mma_z(float (&d)[4], const uint32_t (&a)[4], uint32_t b0, uint32_t b1) {
    asm volatile("mma.sync.aligned.m16n8k16.row.col.f32.bf16.bf16.f32 {%0,%1,%2,%3}, {%4,%5,%6,%7}, {%8,%9}, {%10,%10,%10,%10};"
                 : "=f"(d[0]), "=f"(d[1]), "=f"(d[2]), "=f"(d[3])
                 : "r"(a[0]), "r"(a[1]), "r"(a[2]), "r"(a[3]), "r"(b0), "r"(b1), "f"(0.f));
}
__device__ __forceinline__ void mma_k8(float (&d)[4], uint32_t a0, uint32_t a1, uint32_t b) {
    asm volatile("mma.sync.aligned.m16n8k8.row.col.f32.bf16.bf16.f32 {%0,%1,%2,%3}, {%4,%5}, {%6}, {%0,%1,%2,%3};"
                 : "+f"(d[0]), "+f"(d[1]), "+f"(d[2]), "+f"(d[3]) : "r"(a0), "r"(a1), "r"(b));
}
__global__ void __launch_bounds__(512, 1) k_side(const __grid_constant__ CUtensorMap tmo, const bf16* __restrict__ x, const bf16* __restrict__ logA, const bf16* __restrict__ Aim,
                                                 const bf16* __restrict__ Cre, const bf16* __restrict__ Cim, const bf16* __restrict__ logdt,
                                                 const bf16* __restrict__ Wo, const bf16* __restrict__ dskip, const bf16* __restrict__ gw,
                                                 bf16* __restrict__ out) {
    extern __shared__ __align__(1024) unsigned char smem_raw[];
    const uint32_t sbase = smem_u32(smem_raw);
    const int tid = threadIdx.x, warp = __shfl_sync(0xffffffffu, tid >> 5, 0), lane = tid & 31, cta = blockIdx.x;
    const int cb = cta >> 2, kq = cta & 3;
    if (tid == 0) {
        for (int i = 0; i < 8; i++) { mbar_init(sbase + SB_FULL + 8 * i, 1); mbar_init(sbase + SB_EMPTY + 8 * i, 4); }
        for (int i = 0; i < 2; i++) {
            mbar_init(sbase + SB_QKF + 8 * i, 1); mbar_init(sbase + SB_VF + 8 * i, 1); mbar_init(sbase + SB_QKE + 8 * i, 4);
            mbar_init(sbase + SB_VE + 8 * i, 1); mbar_init(sbase + SB_OF + 8 * i, 4);
        }
        mbar_init(sbase + SB_WO, 1);
        mbar_init(sbase + SB_WO + 40, 1);
        mbar_init(sbase + SB_FI, 1);
        mbar_init(sbase + SB_REQ, 4);
        *reinterpret_cast<uint2*>(smem_raw + SB_TICK) = make_uint2(0u, 0u);
        *reinterpret_cast<uint32_t*>(smem_raw + SB_SEEN) = 0u;
        asm volatile("fence.mbarrier_init.release.cluster;" ::: "memory");
    }
    TS3(0);
    asm volatile("fence.proxy.async;" ::: "memory");
    __syncthreads();
    auto epoch = []() {
        unsigned ep;
        asm volatile("ld.volatile.global.u32 %0, [%1];" : "=r"(ep) : "l"(&g_epoch) : "memory");
        return ep + 1u;
    };
    if (warp >= 12) {
      asm volatile("setmaxnreg.dec.sync.aligned.u32 40;");
      {
        uint32_t gwv[9];
#pragma unroll
        for (int i = 0; i < 9; i++) gwv[i] = reinterpret_cast<const uint32_t*>(gw)[lane + 32 * i];
#pragma unroll 1
        for (int i = 0; i < 8; i++) {
            uint32_t xv[2][9];
            float sm[2];
#pragma unroll
            for (int j = 0; j < 2; j++) {
                const int t = min(cta * 57 + 8 * i + 4 * j + warp - 12, S_LEN - 1);
#pragma unroll
                for (int k = 0; k < 9; k++) xv[j][k] = reinterpret_cast<const uint32_t*>(x + t * DM)[lane + 32 * k];
            }
#pragma unroll
            for (int j = 0; j < 2; j++) {
                sm[j] = 0.f;
#pragma unroll
                for (int k = 0; k < 9; k++) {
                    const uint32_t pr = bf2_mul(xv[j][k], gwv[k]);
                    sm[j] += __uint_as_float(pr << 16) + __uint_as_float(pr & 0xffff0000u);
                }
            }
            float v = (lane < 16 ? sm[0] : sm[1]) + __shfl_xor_sync(0xffffffffu, lane < 16 ? sm[1] : sm[0], 16);
#pragma unroll
            for (int o = 8; o; o >>= 1) v += __shfl_xor_sync(0xffffffffu, v, o);
            const float gv = 1.f / (1.f + expf(-bf16r(v)));
            const int tt = 8 * i + 4 * (lane >> 4) + warp - 12;
            if ((lane & 15) == 0 && tt < 57 && cta * 57 + tt < S_LEN) g_gate[cta * 57 + tt] = __float2bfloat16_rn(gv);
        }
        named_bar(2, 128);
        if (tid == 480) {
            __threadfence();
            asm volatile("red.relaxed.gpu.global.add.u32 [%0], 1;" :: "l"(&g_gcnt[0]) : "memory");
        }
        __syncwarp();
      }
      const unsigned ep = epoch();
      if (warp == 12 || warp == 15) {
        const int pi = warp == 12 ? 0 : 1;
        auto stage_wo = [&](int i0, int i1) {
            if (lane == 0) {
                fence_async();
#pragma unroll 1
                for (int i = i0; i < i1; i++) {
                    gate(sbase + SB_TICK);
                    tma_2d(sbase + FS_A + i * 16384, &tmo, cb * 64, kq * 1024 + i * 128, sbase + SB_WO + (i >> 2) * 40);
                    if (WO_SLEEP > 0) __nanosleep(WO_SLEEP);
                }
            }
            __syncwarp();
        };
        if (lane == 0) mbar_expect(sbase + SB_WO + pi * 40, 65536);
        if (pi == 0) {
            named_bar(11, 288);
            stage_wo(0, 2);
        }
        named_bar(3, 320);
        if (pi == 0) stage_wo(2, 4);
        else {
            if (WO_LAG > 0) __nanosleep(WO_LAG);
            stage_wo(4, 8);
        }
        if (lane == 0) TSS(17, 2 + pi);
        if (tid == 480) {
            __threadfence();
            asm volatile("red.relaxed.gpu.global.add.u32 [%0], 1;" :: "l"(&g_gcnt[32]) : "memory");
        }
        __syncwarp();
        named_bar(12 + pi, 160);
        if (lane == 0) {
            const int kb = 2 * kq + pi;
            fence_async();
            for (int pr = 0; pr < NSEG / 2; pr++) {
                const bool gon = pr < NSEG / 2 - UNGATE_G;
                wait_cnt_rlx(&g_prog[kb * 64 + pr], 8u * ep, pr >= NSEG / 2 - 2);
                if (pi == 0) asm volatile("st.volatile.shared.u32 [%0], %1;" :: "r"(sbase + SB_SEEN), "r"(pr + 1) : "memory");
                if (pr >= 30 && pi == 0) TSS(4 + pr - 30, 0);
                if (pr == 31) TS3P(26);
                if (pr == 30) TS3P(1);
#pragma unroll
                for (int j = 0; j < 4; j++) {
                    const int st = 4 * pi + j;
                    mbar_wait_long(sbase + SB_EMPTY + 8 * st, ((uint32_t)pr & 1u) ^ 1u);
                    mbar_expect(sbase + SB_FULL + 8 * st, 16384);
                    if (gon) gate(sbase + SB_TICK);
                    bulk_g2s(sbase + FS_A + st * 16384, g_ox + ((size_t)(pr * NH + 4 * kb + j)) * 8192, 16384, sbase + SB_FULL + 8 * st);
                }
            }
        }
        __syncwarp();
      } else if (warp == 13) {
        if (lane == 0) {
            const uint64_t pol = policy_evict_first();
            bool next_ok = false;
            for (int seg = 0; seg < NATT; seg++) {
                const uint32_t st = seg & 1, ph = (uint32_t)(seg >> 1) & 1u, ab = sbase + AT_0 + st * AT_ST;
                if (!next_ok) {
                    const unsigned* fp = &g_flag[(cta & (NH - 1)) * NSEG + seg];
                    unsigned it = 0, v0, v1;
                    while (true) {
                        asm volatile("ld.relaxed.gpu.global.u32 %0, [%1];" : "=r"(v0) : "l"(fp) : "memory");
                        asm volatile("ld.relaxed.gpu.global.u32 %0, [%1+4];" : "=r"(v1) : "l"(fp) : "memory");
                        read_tick(sbase + SB_TICK);
                        if ((int)(v0 - 3u * ep) >= 0 || ++it >= SPIN_LIMIT) break;
                        if (seg < NSEG - UNGATE || cta >= NH) __nanosleep(RLX_SLEEP);
                    }
                    next_ok = (int)(v1 - 3u * ep) >= 0;
                } else next_ok = false;
                if (cta < NH) {
                    TSA(seg, 0);
                    mbar_wait_long(sbase + SB_QKE + 8 * st, ph ^ 1u);
                    TSA(seg, 1);
                    mbar_expect(sbase + SB_QKF + 8 * st, 2 * 9216);
                    if (seg < NSEG - UNGATE) gate(sbase + SB_TICK, GL_A, GL_B);
                    TSA(seg, 2);
                    bulk_g2s_h(ab + 10240, &g_qkv[seg][cta][0][1024], 9216, sbase + SB_QKF + 8 * st, pol);
                    bulk_g2s_h(ab + 10240 + 9216, &g_qkv[seg][cta][1][1024], 9216, sbase + SB_QKF + 8 * st, pol);
                    mbar_wait_long(sbase + SB_VE + 8 * st, ph ^ 1u);
                    mbar_expect(sbase + SB_VF + 8 * st, 10240);
                    if (seg < NSEG - UNGATE) gate(sbase + SB_TICK, GL_A, GL_B);
                    TSA(seg, 3);
                    bulk_g2s_h(ab, &g_qkv[seg][cta][2][0], 10240, sbase + SB_VF + 8 * st, pol);
                }
            }
        }
        __syncwarp();
      } else if (warp == 14) {
        if (lane == 0) {
            int seg = cta < NH ? 0 : NATT, p = 0;
            unsigned it = 0;
            while ((seg < NATT || p < NSEG / 2 - 1) && ++it < 16 * SPIN_LIMIT) {
                if (p < NSEG / 2 - 1 && mbar_test(sbase + SB_REQ, (uint32_t)p & 1u)) {
                    if (p == 0) { wait_cnt(&g_gcnt[32], SD_NCTA * ep); asm volatile("fence.proxy.async;" ::: "memory"); }
                    mbar_expect(sbase + SB_FI, (p < NSEG / 2 - 2 ? 12288 : 2048 + 32) + 2048 + 32);
                    if (p < NSEG / 2 - UNGATE_G - 1) gate(sbase + SB_TICK);
                    if (p < NSEG / 2 - 2) bulk_g2s(sbase + FS_I, &g_fp[p & 7][cta][0][0], 12288, sbase + SB_FI);
                    else {
                        bulk_g2s(sbase + FS_I, g_y + ((p * 4 + 4 + kq) * DM + cb * 64) * 16, 2048, sbase + SB_FI);
                        bulk_g2s(sbase + FS_G + 32, g_gate + p * 64 + 64 + kq * 16, 32, sbase + SB_FI);
                    }
                    bulk_g2s(sbase + FS_Z, g_y + ((p * 4 + kq) * DM + cb * 64) * 16, 2048, sbase + SB_FI);
                    bulk_g2s(sbase + FS_G, g_gate + p * 64 + kq * 16, 32, sbase + SB_FI);
                    p++;
                } else if (seg < NATT && mbar_test(sbase + SB_OF + 8 * (seg & 1), (uint32_t)(seg >> 1) & 1u)) {
                    const uint32_t st = seg & 1, ab = sbase + AT_0 + st * AT_ST;
                    TSA(seg, 5);
                    if (seg < NSEG - UNGATE) gate(sbase + SB_TICK, GS_A, GS_B);
                    TSA(seg, 6);
                    unsigned char* dst = reinterpret_cast<unsigned char*>(g_ox) + ((size_t)((seg >> 1) * NH + cta)) * 16384 + (seg & 1) * 8192;
                    asm volatile("cp.async.bulk.global.shared::cta.bulk_group [%0], [%1], 8192;" :: "l"(dst), "r"(ab) : "memory");
                    asm volatile("cp.async.bulk.commit_group;" ::: "memory");
                    asm volatile("cp.async.bulk.wait_group.read 0;" ::: "memory");
                    mbar_arrive(sbase + SB_VE + 8 * st);
                    asm volatile("cp.async.bulk.wait_group 0;" ::: "memory");
                    asm volatile("red.relaxed.gpu.global.add.u32 [%0], 1;" :: "l"(&g_prog[(cta >> 2) * 64 + (seg >> 1)]) : "memory");
                    TSA(seg, 7);
                    seg++;
                } else if (seg < NSEG - UNGATE) __nanosleep(W14_SLEEP);
            }
        }
        __syncwarp();
      }
    } else if (warp >= 8) {
        asm volatile("setmaxnreg.dec.sync.aligned.u32 88;");
          s4d_stage_u(smem_raw + FS_A, x, tid - 256);
        const int wq = warp - 8;
        for (int seg = 0; seg < (cta < NH ? NATT : 0); seg++) {
            const uint32_t st = seg & 1, ph = (uint32_t)(seg >> 1) & 1u, ab = sbase + AT_0 + st * AT_ST;
            float sc[20];
            if (seg < NSEG - UNGATE) mbar_wait_long(sbase + SB_QKF + 8 * st, ph); else mbar_wait(sbase + SB_QKF + 8 * st, ph);
            if (tid == 256) TSA(seg, 4);
            {
                const uint64_t da = smem_desc(ab + 10240 + 1024, 128, 1024), db = smem_desc(ab + 10240, 128, 2048);
                wg_fence();
#pragma unroll
                for (int ks = 0; ks < 8; ks++) wgmma_n40_ss(sc, da + (uint64_t)((ks >> 2) * 576 + (ks & 3) * 16), db + (uint64_t)((ks >> 2) * 576 + (ks & 3) * 16), ks > 0);
                wg_commit();
                wg_wait0();
            }
            if (lane == 0) mbar_arrive(sbase + SB_QKE + 8 * st);
            uint32_t p[5], ob[16];
            const float psum = xrow_softmax(sc, p, wq, lane);
            mbar_wait(sbase + SB_VF + 8 * st, ph);
            xrow_pv(ob, p, psum, ab);
            named_bar(6, 128);
#pragma unroll
            for (int i = 0; i < 4; i++) stsm_x4(ab + wq * 2048 + i * 512 + lane * 16, ob[4 * i], ob[4 * i + 1], ob[4 * i + 2], ob[4 * i + 3]);
            fence_async();
            __syncwarp();
            if (lane == 0) mbar_arrive(sbase + SB_OF + 8 * st);
        }
    } else {
        asm volatile("setmaxnreg.inc.sync.aligned.u32 192;");
        const int wg = warp >> 2, wq = warp & 3;
        s4d_phase(smem_raw + FS_A, x, logA, Aim, Cre, Cim, logdt, dskip, Wo + (size_t)((2 * kq + wg) * 512) * DM + cb * 64);
        TS3(2);
        if (lane == 0) TSS(16, warp);
        named_bar(3, 320);
        if (tid == 0) TSS(17, 0);
        uint32_t wa[32][4];
        mbar_wait_long(sbase + SB_WO + wg * 40, 0);
        if (tid == 0) TSS(17, 1);
        {
            const uint32_t a = sbase + FS_A + wg * 65536 + ((lane >> 4) * 8 + (lane & 7)) * 128 + (((wq * 2 + ((lane >> 3) & 1)) ^ (lane & 7)) << 4);
#pragma unroll
            for (int ks = 0; ks < 32; ks++) ldsm_x4_t(wa[ks], a + ks * 2048);
        }
        named_bar(12 + wg, 160);
        TS3(3);
        if (tid == 0) TSS(17, 4);
        auto product = [&](float (&acc)[32], int pr, const int wg) {
                if (pr + wg > 0) named_bar(4 + wg, 256);
                const uint64_t db = smem_desc(sbase + FS_A + wg * 65536, 128, 2048);
                TSG(0);
#pragma unroll
                for (int j = 0; j < 4; j++) {
                    mbar_wait(sbase + SB_FULL + 8 * (4 * wg + j), (uint32_t)pr & 1u);
                    if (j == 0) TSG(1);
                    if (j == 3) TSG(2);
                    wg_fence();
#pragma unroll
                    for (int ks = 0; ks < 8; ks++) {
                        if ((j | ks) == 0) wgmma_n64_z(acc, wa[0], db);
                        else wgmma_n64(acc, wa[8 * j + ks], db + (uint64_t)(j * 1024 + ks * 16), 1);
                    }
                    wg_commit();
                    if (j == 3 && pr + wg < NSEG / 2) bar_arrive(4 + (wg ^ 1), 256);
                    if (j > 0) { wg_wait1(); if (lane == 0) mbar_arrive(sbase + SB_EMPTY + 8 * (4 * wg + j - 1)); }
                }
                wg_wait0();
                if (pr == 31) TS3W(27);
                TSG(3);
                if (lane == 0) mbar_arrive(sbase + SB_EMPTY + 8 * (4 * wg + 3));
        };
        if (wg == 1) {
            for (int pr = 0; pr < NSEG / 2; pr++) {
                uint32_t t16 = (uint32_t)(wq * 32 + lane) * 16u;
                asm volatile("" : "+r"(t16));
                float acc[32];
                product(acc, pr, 1);
                    uint32_t tag = ((uint32_t)(pr >> 3) & 1u) ^ 1u;
                    tag = __shfl_sync(0xffffffffu, tag, lane);
                    named_bar(8, 256);
                    unsigned char* dst = reinterpret_cast<unsigned char*>(&g_fp[pr & 7][4 * cb][2 * kq - 2][0]) + t16;
                    const uint32_t own = sbase + FS_O + (pr % 3) * 4096 + t16;
#pragma unroll
                    for (int q = 0; q < 8; q++) {
                        float4 p;
                        asm volatile("ld.shared.v4.f32 {%0,%1,%2,%3}, [%4];" : "=f"(p.x), "=f"(p.y), "=f"(p.z), "=f"(p.w) : "r"(sbase + FS_P + t16 + q * 2048) : "memory");
                        acc[4 * q] = __uint_as_float((__float_as_uint(acc[4 * q] + p.x) & ~1u) | tag); acc[4 * q + 1] = __uint_as_float((__float_as_uint(acc[4 * q + 1] + p.y) & ~1u) | tag);
                        acc[4 * q + 2] = __uint_as_float((__float_as_uint(acc[4 * q + 2] + p.z) & ~1u) | tag); acc[4 * q + 3] = __uint_as_float((__float_as_uint(acc[4 * q + 3] + p.w) & ~1u) | tag);
                    }
#pragma unroll
                    for (int q = 0; q < 8; q++) {
                        asm volatile("{\n.reg .pred p;\nsetp.ne.s32 p, %5, %6;\n@p st.volatile.global.v4.f32 [%0], {%1,%2,%3,%4};\n@!p st.shared.v4.f32 [%7], {%1,%2,%3,%4};\n}"
                                     :: "l"(dst + (q & 1) * 2048), "f"(acc[4 * q]), "f"(acc[4 * q + 1]), "f"(acc[4 * q + 2]), "f"(acc[4 * q + 3]), "r"(q >> 1), "r"(kq),
                                        "r"(own + (q & 1) * 2048) : "memory");
                        if (q & 1) dst += (q >> 1) == kq ? 12288 + 4096 : 12288;
                    }
                    bar_arrive(9, 256);
                    if (pr == 31) TS3W(28);
                TSG(4);
            }
        } else {
          int nsync = 0;
          int np = 1, nf = 0, pr = 0, pf = -1;
          while (true) {
            uint32_t t16 = (uint32_t)(wq * 32 + lane) * 16u;
            asm volatile("" : "+r"(t16));
            if (pr < 0) {
                if (nsync <= pf) { named_bar(9, 256); nsync++; }
                if (lane == 0 && pf < NSEG / 2 - 1) mbar_arrive(sbase + SB_REQ);
            } else {
                float acc[32];
                product(acc, pr, 0);
                if (nsync < pr) { named_bar(9, 256); nsync++; }
#pragma unroll
                for (int q = 0; q < 8; q++)
                    asm volatile("st.shared.v4.f32 [%0], {%1,%2,%3,%4};" :: "r"(sbase + FS_P + t16 + q * 2048), "f"(acc[4 * q]), "f"(acc[4 * q + 1]), "f"(acc[4 * q + 2]), "f"(acc[4 * q + 3]) : "memory");
                bar_arrive(8, 256);
                TSG(4);
            }
            uint32_t w[4] = {0u, 0u, 0u, 0u};
            const int pc = pf;
            if (pf >= 0) {
                const uint32_t tag = ((uint32_t)(pf >> 3) & 1u) ^ 1u;
                uint4 v[8];
                unsigned n = 0;
                const bool last = pf == NSEG / 2 - 1;
                const uint4* src = reinterpret_cast<const uint4*>(reinterpret_cast<const unsigned char*>(&g_fp[pf & 7][cta][0][0]) + t16);
                if (pf >= NSEG / 2 - 2) {
#pragma unroll
                    for (int r = 0; r < 6; r++) v[r] = ld_vol_u4(src + r * 128);
                    mbar_wait(sbase + SB_FI, 0u);
                } else {
                    mbar_wait(sbase + SB_FI, (uint32_t)pf & 1u);
#pragma unroll
                    for (int r = 0; r < 6; r++)
                        asm volatile("ld.shared.v4.u32 {%0,%1,%2,%3}, [%4];" : "=r"(v[r].x), "=r"(v[r].y), "=r"(v[r].z), "=r"(v[r].w) : "r"(sbase + t16 + FS_I + r * 2048) : "memory");
                }
                while (true) {
                    uint32_t any = 0u;
#pragma unroll
                    for (int r = 0; r < 6; r++) {
                        uint32_t c0_, c1_;
                        asm("lop3.b32 %0, %1, %2, %3, 0x7e;" : "=r"(c0_) : "r"(v[r].x), "r"(v[r].y), "r"(tag));
                        asm("lop3.b32 %0, %1, %2, %3, 0x7e;" : "=r"(c1_) : "r"(v[r].z), "r"(v[r].w), "r"(tag));
                        asm("lop3.b32 %0, %1, %2, %3, 0xfe;" : "=r"(any) : "r"(any), "r"(c0_), "r"(c1_));
                    }
                    if (!__any_sync(0xffffffffu, (any & 1u) != 0u) || ++n >= SPIN_LIMIT) break;
                    if (pf < NSEG / 2 - 2) __nanosleep(200);
#pragma unroll
                    for (int r = 0; r < 6; r++) v[r] = ld_vol_u4(src + r * 128);
                }
                if (pf == 31) TS3(29);
                TSG(5);
#pragma unroll
                for (int r = 6; r < 8; r++)
                    asm volatile("ld.shared.v4.u32 {%0,%1,%2,%3}, [%4];" : "=r"(v[r].x), "=r"(v[r].y), "=r"(v[r].z), "=r"(v[r].w)
                                 : "r"(sbase + t16 + FS_O + (pf % 3) * 4096 + (r - 6) * 2048) : "memory");
                uint32_t zv[4], gg[2];
                ldsm_x4_t(zv, sbase + (last ? FS_I : FS_Z) + (wq * 16 + (lane & 15)) * 32 + (lane >> 4) * 16);
#pragma unroll
                for (int k = 0; k < 2; k++) gg[k] = __byte_perm(*reinterpret_cast<const volatile unsigned short*>(smem_raw + FS_G + (last ? 32 : 0) + k * 16 + (lane >> 2) * 2), 0u, 0x1010);
#define PQS(k, f) (((__uint_as_float(v[k].f) + __uint_as_float(v[2 + k].f)) + __uint_as_float(v[4 + k].f)) + __uint_as_float(v[6 + k].f))
#pragma unroll
                for (int k = 0; k < 2; k++) {
                    w[2 * k] = bf2_add(bf2_mul(gg[k], movm(pack_bf16(PQS(k, x), PQS(k, y)))), zv[2 * k]);
                    w[2 * k + 1] = bf2_add(bf2_mul(gg[k], movm(pack_bf16(PQS(k, z), PQS(k, w)))), zv[2 * k + 1]);
                }
#undef PQS
            }
            const bool more = nf < NSEG / 2;
            if (more) {
                uint32_t r;
                asm volatile("{\n.reg .pred p, q;\n.reg .b32 v;\nld.volatile.shared.u32 v, [%1];\nsetp.gt.s32 p, v, %2;\nbar.red.or.pred q, 10, 128, p;\nselp.u32 %0, 1, 0, q;\n}"
                             : "=r"(r) : "r"(sbase + SB_SEEN), "r"(np) : "memory");
                const bool dop = np < NSEG / 2 && (__shfl_sync(0xffffffffu, r, 0) != 0u || nf == np || (np >= TM && nf + 1 >= np));
                TSG(6);
                pr = dop ? np++ : -1;
                pf = !dop || nf + (pr >= TM2 ? 1 : 2) <= pr ? nf++ : -1;
                if (dop && pf >= 0 && lane == 0) mbar_arrive(sbase + SB_REQ);
            }
            if (pc >= 0) {
                unsigned char* op = reinterpret_cast<unsigned char*>(out) + (uint32_t)((pc * 64 + kq * 16 + (lane >> 2)) * DM + cb * 64 + wq * 16 + 2 * (lane & 3)) * 2u;
#pragma unroll
                for (int k = 0; k < 4; k++) *reinterpret_cast<uint32_t*>(op + (k >> 1) * (16 * DM) + (k & 1) * 16) = w[k];
                if ((pc & 1) == 0) TS3(4 + pc / 2);
                if (pc == 31) TS3(25);
            }
            if (!more) break;
          }
        }
        if (cta == 0 && tid == 0) asm volatile("red.relaxed.gpu.global.add.u32 [%0], 1;" :: "l"(&g_epoch) : "memory");
    }
    asm volatile("griddepcontrol.wait;" ::: "memory");
}

template <class F>
__device__ __forceinline__ uint32_t poll_mem(const uint4* src, uint32_t dst, uint32_t t0, F next) {
    uint4 v[6];
    unsigned it = 0;
#pragma unroll
    for (int j = 0; j < 6; j++) v[j] = make_uint4(0u, 0u, 0u, 0u);
    while (clock32() - t0 < POLL_DELAY) {}
    FS(12, 0);
    bool more;
#pragma unroll 1
    do {
        asm volatile("{\n.reg .pred p<6>;\n"
                     "setp.ne.u32 p0, %3, 0x5000;\nsetp.ne.u32 p1, %7, 0x5000;\nsetp.ne.u32 p2, %11, 0x5000;\n"
                     "setp.ne.u32 p3, %15, 0x5000;\nsetp.ne.u32 p4, %19, 0x5000;\nsetp.ne.u32 p5, %23, 0x5000;\n"
                     "@p0 ld.volatile.global.v4.u32 {%0,%1,%2,%3}, [%24];\n@p1 ld.volatile.global.v4.u32 {%4,%5,%6,%7}, [%24+4096];\n"
                     "@p2 ld.volatile.global.v4.u32 {%8,%9,%10,%11}, [%24+8192];\n@p3 ld.volatile.global.v4.u32 {%12,%13,%14,%15}, [%24+12288];\n"
                     "@p4 ld.volatile.global.v4.u32 {%16,%17,%18,%19}, [%24+16384];\n@p5 ld.volatile.global.v4.u32 {%20,%21,%22,%23}, [%24+20480];\n}"
                     : "+r"(v[0].x), "+r"(v[0].y), "+r"(v[0].z), "+r"(v[0].w), "+r"(v[1].x), "+r"(v[1].y), "+r"(v[1].z), "+r"(v[1].w),
                       "+r"(v[2].x), "+r"(v[2].y), "+r"(v[2].z), "+r"(v[2].w), "+r"(v[3].x), "+r"(v[3].y), "+r"(v[3].z), "+r"(v[3].w),
                       "+r"(v[4].x), "+r"(v[4].y), "+r"(v[4].z), "+r"(v[4].w), "+r"(v[5].x), "+r"(v[5].y), "+r"(v[5].z), "+r"(v[5].w)
                     : "l"(src) : "memory");
        stsm_x4(dst, h2_to_bf2(v[0].x), h2_to_bf2(v[0].y), h2_to_bf2(v[0].z), h2_to_bf2(v[1].x));
        stsm_x4(dst + 512, h2_to_bf2(v[1].y), h2_to_bf2(v[1].z), h2_to_bf2(v[2].x), h2_to_bf2(v[2].y));
        const uint32_t all = ((v[0].w & v[1].w) & (v[2].w & v[3].w)) & (v[4].w & v[5].w);
        more = __any_sync(0xffffffffu, (all & 0x5000u) != 0x5000u && ++it < SPIN_LIMIT);
        stsm_x4(dst + 1024, h2_to_bf2(v[2].z), h2_to_bf2(v[3].x), h2_to_bf2(v[3].y), h2_to_bf2(v[3].z));
        asm volatile("stmatrix.sync.aligned.m8n8.x2.shared.b16 [%0], {%1,%2};" :: "r"(dst + 1536), "r"(h2_to_bf2(v[4].x)), "r"(h2_to_bf2(v[4].y)) : "memory");
        stsm_x4(dst + 1792, h2_to_bf2(v[4].z), h2_to_bf2(v[5].x), h2_to_bf2(v[5].y), h2_to_bf2(v[5].z));
        asm volatile("{\n.reg .pred p;\nsetp.eq.u32 p, %0, 0;\n@p bar.sync 1, 384;\n}" :: "r"((uint32_t)more) : "memory");
    } while (more);
    next();
    FS(13, it);
    FS(14, 0);
    uint32_t m = v[0].x, m1 = v[0].y, m2 = v[0].z;
#pragma unroll
    for (int j = 1; j < 6; j++) {
        asm volatile("max.NaN.xorsign.abs.f16x2 %0, %0, %1;" : "+r"(m) : "r"(v[j].x));
        asm volatile("max.NaN.xorsign.abs.f16x2 %0, %0, %1;" : "+r"(m1) : "r"(v[j].y));
        asm volatile("max.NaN.xorsign.abs.f16x2 %0, %0, %1;" : "+r"(m2) : "r"(v[j].z));
    }
    asm volatile("max.NaN.xorsign.abs.f16x2 %0, %0, %1;" : "+r"(m) : "r"(m1));
    asm volatile("max.NaN.xorsign.abs.f16x2 %0, %0, %1;" : "+r"(m) : "r"(m2));
    return h2_to_bf2(m) & 0x7fff7fffu;
}

template <bool V> struct Flag { static constexpr bool value = V; };
__device__ __forceinline__ void score_group(const uint32_t (&a)[2][4], const uint32_t (&kf)[2][4], uint32_t d0, uint32_t d1, uint32_t m1, uint32_t d2, uint32_t m2) {
    FS(4, a[1][0]);
    float sc[4][4];
    mma_z(sc[0], a[0], kf[0][0], kf[0][1]);
    mma_z(sc[1], a[0], kf[0][2], kf[0][3]);
    mma_z(sc[2], a[1], kf[1][0], kf[1][1]);
    mma_z(sc[3], a[1], kf[1][2], kf[1][3]);
    constexpr float EC = (float)(1.4426950408889634 * 0.08838834764831845);
    const uint32_t v0 = __float_as_uint(fmaf(sc[3][2], EC, fmaf(sc[2][0], EC, (sc[0][0] + sc[1][2]) * EC))), v1 = __float_as_uint(fmaf(sc[3][3], EC, fmaf(sc[2][1], EC, (sc[0][1] + sc[1][3]) * EC)));
    FS(5, v0);
    const uint32_t pk = pack_bf16(__uint_as_float(v0), __uint_as_float(v1));
    st_async32(d1, pk, m1);
    st_async32(d2, pk, m2);
    asm volatile("st.shared.v2.u32 [%0], {%1,%2};" :: "r"(d0), "r"(v0), "r"(v1) : "memory");
}
__device__ __forceinline__ void store_tile(int s, int h, int role, uint32_t tile, uint32_t b0, uint32_t b1) {
    asm volatile("cp.async.bulk.global.shared::cta.bulk_group.L2::cache_hint [%0], [%1], %2, %3;"
                 :: "l"(&g_qkv[s][h][role][b0]), "r"(tile + b0), "r"(b1 - b0), "l"(policy_evict_first()) : "memory");
}
__device__ __forceinline__ uint32_t w_addr(uint32_t sbase, int warp, int lane) {
    return sbase + SM_WS + (warp >> 2) * 8192 + ((lane & 7) + ((lane >> 4) & 1) * 8) * 128 + ((((warp & 3) * 2 + ((lane >> 3) & 1)) ^ (lane & 7)) << 4);
}
__device__ __forceinline__ void vx_copy(uint32_t sbase, int j, int r) {
    bulk_s2s(mapa(sbase + SM_VX + (j & 1) * 8192, r), sbase + SM_T + (j & 3) * TBUF + DH * 16, 8192, mapa(sbase + B_VX + 8 * (j & 1), r));
}
__device__ __forceinline__ float to_scale(float bound) {
    int e = 141 - (int)((__float_as_uint(bound) >> 23) & 255u);
    e = e > 100 ? 100 : e;
    return __uint_as_float((uint32_t)(127 + e) << 23);
}
__device__ __forceinline__ void norms_gather(int lane, uint32_t sbase) {
    uint2 v[3];
    uint4 w[2];
    unsigned it = 0;
#pragma unroll
    for (int i = 0; i < 3; i++) v[i] = make_uint2(0u, 0u);
    w[0] = w[1] = make_uint4(0u, 0u, 0u, 0u);
    bool more;
    do {
#pragma unroll
        for (int i = 0; i < 3; i++) if ((v[i].x & 1u) == 0u) v[i] = ld_vol_u2(&g_norm[3 * lane + i]);
#pragma unroll
        for (int i = 0; i < 2; i++) if ((w[i].x & w[i].y & w[i].z & w[i].w & 1u) == 0u) w[i] = ld_vol_u4(&g_wv[lane][i]);
        more = __any_sync(0xffffffffu, (v[0].x & v[1].x & v[2].x & w[0].x & w[0].y & w[0].z & w[0].w & w[1].x & w[1].y & w[1].z & w[1].w & 1u) == 0u);
    } while (more && ++it < SPIN_LIMIT);
    float c;
    asm("sqrt.approx.f32 %0, %1;" : "=f"(c) : "f"(__uint_as_float(max(max(v[0].x, v[1].x), v[2].x))));
    c *= __uint_as_float(max(max(max(w[0].x, w[0].y), max(w[0].z, w[0].w)), max(max(w[1].x, w[1].y), max(w[1].z, w[1].w)))) * 272.f;
#pragma unroll
    for (int o = 16; o; o >>= 1) c += __shfl_xor_sync(0xffffffffu, c, o);
    const uint32_t r = __reduce_max_sync(0xffffffffu, v[0].y);
    if (lane < 3) {
        const uint32_t rb = mapa(sbase, lane);
        c *= 1.1f * 24.f;
        st_async64(rb + SM_SC, __float_as_uint(to_scale(__uint_as_float(r) * c)), __float_as_uint(c), rb + B_W + 8);
        st_async32(rb + SM_SC + 68, r, rb + B_W + 8);
    }
    __syncwarp();
}
__device__ __forceinline__ void xmax_gather(int lane, uint32_t sb) {
    uint4 v[4];
    unsigned it = 0;
    uint32_t ok;
    do {
#pragma unroll
        for (int i = 0; i < 4; i++) v[i] = ld_vol_u4(&g_rx[lane + 32 * (i >> 1)][i & 1]);
        ok = 1u;
#pragma unroll
        for (int i = 0; i < 4; i++) ok &= (v[i].x & v[i].y) & (v[i].z & v[i].w);
    } while (__any_sync(0xffffffffu, ok == 0u) && ++it < SPIN_LIMIT);
#pragma unroll
    for (int i = 0; i < 2; i++)
        sts32(sb + SM_SC + 64 + 4 * lane + 128 * i, max(max(max(v[2 * i].x, v[2 * i].y), max(v[2 * i].z, v[2 * i].w)), max(max(v[2 * i + 1].x, v[2 * i + 1].y), max(v[2 * i + 1].z, v[2 * i + 1].w))));
}
__device__ __forceinline__ uint32_t max_abs8(uint32_t m, uint32_t a, uint32_t b, uint32_t c, uint32_t d) { return max_abs2(max_abs2(m, max_abs2(a, b)), max_abs2(c, d)); }
__device__ __forceinline__ uint32_t warp_max_abs(uint32_t m) { return __reduce_max_sync(0xffffffffu, max((m << 16) & 0x7fff0000u, m & 0x7fff0000u)); }

__device__ __forceinline__ void last_rows() {
    extern __shared__ __align__(1024) unsigned char smem_raw[];
    const uint32_t sbase = smem_u32(smem_raw);
    const int tid = threadIdx.x, warp = __shfl_sync(0xffffffffu, tid >> 5, 0), h = blockIdx.x / 3;
    {
        const int sg = warp < 8, wq = warp & 3, lane = tid & 31;
        const uint32_t qk = sbase + SM_X + XBUF + sg * (2 * 9216), ob = sbase + SM_X + 2 * XBUF + sg * 8192;
        TST(0);
        mbar_wait(sbase + B_VX + 8 * sg, 0);
        fence_async();
        TST(1);
        float sc[20];
#pragma unroll
        for (int i = 0; i < 20; i++) sc[i] = 0.f;
        {
            const uint64_t da = smem_desc(qk + 1024, 128, 1024), db = smem_desc(qk, 128, 2048);
            wg_fence();
#pragma unroll
            for (int ks = 0; ks < 8; ks++) wgmma_n40_ss(sc, da + (uint64_t)((ks >> 2) * 576 + (ks & 3) * 16), db + (uint64_t)((ks >> 2) * 576 + (ks & 3) * 16), ks > 0);
            wg_commit();
            wg_wait0();
        }
        uint32_t p[5], o[16];
        const float psum = xrow_softmax(sc, p, wq, lane);
        xrow_pv(o, p, psum, sbase + SM_T + ((NSEG - 2 + sg) & 3) * TBUF);
        {
#pragma unroll
            for (int i = 0; i < 4; i++) stsm_x4(ob + wq * 2048 + i * 512 + lane * 16, o[4 * i], o[4 * i + 1], o[4 * i + 2], o[4 * i + 3]);
        }
        fence_async();
        named_bar(11 + sg, 128);
        TST(2);
        if ((tid & 127) == 0) {
            unsigned char* dst = reinterpret_cast<unsigned char*>(g_ox) + ((size_t)((NSEG / 2 - 1) * NH + h)) * 16384 + sg * 8192;
            asm volatile("cp.async.bulk.global.shared::cta.bulk_group [%0], [%1], 8192;" :: "l"(dst), "r"(ob) : "memory");
            asm volatile("cp.async.bulk.commit_group;" ::: "memory");
            asm volatile("cp.async.bulk.wait_group 0;" ::: "memory");
            asm volatile("red.relaxed.gpu.global.add.u32 [%0], 1;" :: "l"(&g_prog[(h >> 2) * 64 + NSEG / 2 - 1]) : "memory");
        }
        TST(3);
    }
    __syncwarp();
}

__global__ void __cluster_dims__(3, 1, 1) __launch_bounds__(384, 1)
k_chain(const __grid_constant__ CUtensorMap tmq, const __grid_constant__ CUtensorMap tmk,
        const __grid_constant__ CUtensorMap tmv, const __grid_constant__ CUtensorMap tmx2, const __grid_constant__ CUtensorMap tmo,
        const __grid_constant__ CUtensorMap tmm, const bf16* __restrict__ xg) {
    extern __shared__ __align__(1024) unsigned char smem_raw[];
    const uint32_t sbase = smem_u32(smem_raw);
    const int cta = blockIdx.x, h = cta / 3, role = cta - 3 * h;
    const int tid = threadIdx.x, warp = __shfl_sync(0xffffffffu, tid >> 5, 0), lane_o = tid & 31;
    TS3C(0);
    asm volatile("griddepcontrol.launch_dependents;" ::: "memory");
    auto stage_w = [&](int i) {
        tma_2d(sbase + SM_WS + i * 16384, role == 2 ? &tmv : &tmq, h * DH + (role == 1 ? 64 : 0), i * 64, sbase + B_W + 8 * i);
        tma_2d(sbase + SM_WS + i * 16384 + 8192, role == 2 ? &tmv : &tmk, h * DH + (role == 0 ? 0 : 64), i * 64, sbase + B_W + 8 * i);
    };
    auto stage_x = [&](int i) {
        tma_2d(sbase + x01_off(i), &tmx2, i * 64, 0, sbase + B_W + 8 * i);
        tma_2d(sbase + x01_off(i) + 8192, &tmm, i * 64, 0, sbase + B_W + 8 * i);
        if (i < 3) tma_2d(sbase + x23_off(i), &tmx2, i * 64, 64, sbase + B_W + 8 * i);
    };
    if (tid == 0) {
#pragma unroll
        for (int i = 0; i < 10; i++) mbar_init(sbase + B_W + 8 * i, 1);
        fence_async();
        TSQ(10);
#pragma unroll
        for (int i = 0; i < 3; i++) tma_2d(sbase + SM_X01 + i * 16384, &tmo, role * WOC + i * 64, h * DH, sbase + B_E);
        stage_x(0); stage_w(0);
        TSQ(11);
        mbar_expect(sbase + B_E, 49152);
#pragma unroll
        for (int i = 0; i < 9; i++) mbar_expect(sbase + B_W + 8 * i, 16384 + 9216 + (i < 3 ? 8192 : 0));
    } else if (tid == 32) {
#pragma unroll
        for (int i = 0; i < 8; i++) mbar_init(sbase + SM_BAR + 8 * i, 1);
        mbar_init(sbase + B_XF, 3);
        asm volatile("fence.mbarrier_init.release.cluster;" ::: "memory");
        for (int i = 0; i < 2; i++) {
            mbar_expect(sbase + B_SB + 8 * i, role == 2 ? 1280 : 640 + 2048);
            mbar_expect(sbase + B_VX + 8 * i, role != 2 ? 8192 : 2 * 9216);
            mbar_expect(sbase + B_XT + 8 * i, 32768);
            mbar_expect(sbase + B_XT + 16 + 8 * i, i == 0 ? 40960 : 0);
        }
    }
    __syncthreads();
    TS3C(8);
    if (tid == 0) {
#pragma unroll 1
        for (int i = 1; i < 3; i++) { stage_x(i); stage_w(i); }
        TSQ(12);
    }
    __syncwarp();
    if (warp < 8) {
        uint32_t wreg[36 - NS][4];
        uint32_t v0, v1;
        {
            const int lane = lane_o;
            const uint32_t a = w_addr(sbase, warp, lane);
            const uint64_t da = smem_desc(sbase + SM_WS + (warp >> 2) * 8192, 1024, 1024) | (1ull << 62);
            float acc[36], acc1[32];
            uint32_t m = 0u;
#pragma unroll
            for (int i = 0; i < 36; i++) acc[i] = 0.f;
#pragma unroll
            for (int i = 0; i < 32; i++) acc1[i] = 0.f;
#pragma unroll 1
            for (int b = 0; b < 7; b++) {
                if (b == 0) TSQ(0);
                mbar_wait(sbase + B_W + 8 * b, 0);
                TSQ(1 + b);
                const uint64_t db = smem_desc(sbase + x01_off(b), 16, 1024) | (1ull << 62);
                wg_fence();
#pragma unroll
                for (int k = 0; k < 4; k++) wgmma_n72_ss(acc, da + (uint64_t)(b * 1024 + k * 128), db + (uint64_t)(k * 2));
                wg_commit();
                if (b < 3) {
                    const uint64_t d1 = smem_desc(sbase + x23_off(b), 16, 1024) | (1ull << 62);
                    wg_fence();
#pragma unroll
                    for (int k = 0; k < 4; k++) wgmma_n64_ss(acc1, da + (uint64_t)(b * 1024 + k * 128), d1 + (uint64_t)(k * 2));
                    wg_commit();
                }
                if (b == 2) {
                    wg_wait0();
                    bar_arrive(10, 384);
                }
                if (b == 3) {
                    if (tid == 0) mbar_expect(sbase + B_W + 8, 12);
                    __syncwarp();
                    if (role == 2) {
#pragma unroll
                        for (int ks = 0; ks < NS; ks++) {
                            uint32_t t[4];
                            ldsm_x4_t(t, a + (ks >> 2) * 16384 + (ks & 3) * 2048);
                            m = max_abs8(m, t[0], t[1], t[2], t[3]);
                        }
                    }
#pragma unroll
                    for (int ks = NS; ks < 16; ks++) ldsm_x4_t(wreg[ks - NS], a + (ks >> 2) * 16384 + (ks & 3) * 2048);
                }
                if (b == 5) {
#pragma unroll
                    for (int ks = 16; ks < 24; ks++) ldsm_x4_t(wreg[ks - NS], a + (ks >> 2) * 16384 + (ks & 3) * 2048);
                    if (role == 2) {
#pragma unroll
                        for (int ks = NS; ks < 24; ks++) m = max_abs8(m, wreg[ks - NS][0], wreg[ks - NS][1], wreg[ks - NS][2], wreg[ks - NS][3]);
                    }
                }
            }
            mbar_wait(sbase + B_W + 16, 1);
            TSQ(13);
            wg_fence();
#pragma unroll
            for (int k = 12; k < 20; k++)
                wgmma_n64_ss(acc1, da + (uint64_t)((k >> 2) * 1024 + (k & 3) * 128), (smem_desc(sbase + x23_off(k >> 2), 16, 1024) | (1ull << 62)) + (uint64_t)((k & 3) * 2));
            wg_commit();
            wg_wait0();
            named_bar(11, 384);
#pragma unroll
            for (int i = 0; i < 8; i++)
                asm volatile("st.shared.v4.f32 [%0], {%1,%2,%3,%4};" :: "r"(sbase + SM_X + 5 * 8192 + i * 4096 + tid * 16),
                             "f"(acc1[4 * i]), "f"(acc1[4 * i + 1]), "f"(acc1[4 * i + 2]), "f"(acc1[4 * i + 3]) : "memory");
#pragma unroll
            for (int b = 7; b < 9; b++) {
#pragma unroll
                for (int ks = 4 * b - 4; ks < 4 * b; ks++) ldsm_x4_t(wreg[ks - NS], a + (ks >> 2) * 16384 + (ks & 3) * 2048);
                if (role == 2) {
#pragma unroll
                    for (int ks = 4 * b - 4; ks < 4 * b; ks++) m = max_abs8(m, wreg[ks - NS][0], wreg[ks - NS][1], wreg[ks - NS][2], wreg[ks - NS][3]);
                }
                const uint64_t db = smem_desc(sbase + x01_off(b), 16, 1024) | (1ull << 62);
                mbar_wait(sbase + B_W + 8 * b, 0);
                TSQ(1 + b);
                if (b == 8) TS3C(2);
                wg_fence();
#pragma unroll
                for (int k = 0; k < 4; k++) wgmma_n72_ss(acc, da + (uint64_t)(b * 1024 + k * 128), db + (uint64_t)(k * 2));
                wg_commit();
            }
#pragma unroll
            for (int ks = 32; ks < KPRE; ks++) ldsm_x4_t(wreg[ks - NS], a + (ks >> 2) * 16384 + (ks & 3) * 2048);
            if (role == 2) {
#pragma unroll
                for (int ks = KPRE; ks < 36; ks++) {
                    uint32_t t[4];
                    ldsm_x4_t(t, a + (ks >> 2) * 16384 + (ks & 3) * 2048);
                    m = max_abs8(m, t[0], t[1], t[2], t[3]);
                }
#pragma unroll
                for (int ks = 32; ks < KPRE; ks++) m = max_abs8(m, wreg[ks - NS][0], wreg[ks - NS][1], wreg[ks - NS][2], wreg[ks - NS][3]);
                m = warp_max_abs(m);
                if (lane == 0) asm volatile("st.volatile.global.u32 [%0], %1;" :: "l"(reinterpret_cast<uint32_t*>(&g_wv[h][0]) + warp), "r"(m | 1u) : "memory");
                __syncwarp();
            }
            wg_wait0();
            named_bar(9, 256);
            const uint32_t off = sbase + SM_T + (DH + warp * 16 + (lane & 15)) * 16 + (lane >> 4) * (DH * 16);
#pragma unroll
            for (int i = 0; i < 4; i++)
                stsm_x4(off + (i >> 1) * TBUF + (i & 1) * (2 * DH * 16), pack_bf16(acc[8 * i], acc[8 * i + 1]), pack_bf16(acc[8 * i + 2], acc[8 * i + 3]),
                        pack_bf16(acc[8 * i + 4], acc[8 * i + 5]), pack_bf16(acc[8 * i + 6], acc[8 * i + 7]));
            v0 = pack_bf16(acc[32], acc[33]);
            v1 = pack_bf16(acc[34], acc[35]);
#pragma unroll
            for (int ks = KPRE; ks < 36; ks++) ldsm_x4_t(wreg[ks - NS], a + (ks >> 2) * 16384 + (ks & 3) * 2048);
            if (role == 2) fence_async();
            bar_arrive(8, 384);
            named_bar(7, 256);
            asm volatile("barrier.cluster.arrive.relaxed.aligned;" ::: "memory");
        }
        TS3C(3);
        uint32_t ws[NS][4];
#pragma unroll
        for (int ks = NS - NP; ks < NS; ks++) ldsm_x4_t(ws[ks], w_addr(sbase, warp, lane_o) + (ks >> 2) * 16384 + (ks & 3) * 2048);
        asm volatile("barrier.cluster.wait.aligned;" ::: "memory");
        if (lane_o == 0 && role != 2 && warp < 2) tma_2d_mc(sbase + SM_X + (2 * role + warp) * 8192, &tmx2, (2 * role + warp + 5) * 64, 64, sbase + B_XT + 8);
        __syncwarp();
        TS3C(4);
        auto main_loop = [&](auto is_c) {
            constexpr bool C = decltype(is_c)::value;
            const uint32_t l16 = __shfl_sync(0xffffffffu, sbase + lane_o * 16, lane_o);
            const uint32_t ka = __shfl_sync(0xffffffffu, sbase + SM_T + (64 + (lane_o & 7) + ((lane_o >> 3) & 1) * 16 + (lane_o >> 4) * 8) * 16, lane_o);
            const uint32_t wa = __shfl_sync(0xffffffffu, w_addr(sbase, warp, lane_o), lane_o);
            auto post = [&](bool act, int s, uint32_t to, uint32_t ta, int scw, uint32_t v0, uint32_t v1) {
                int lane = lane_o;
                asm volatile("" : "+r"(lane));
                asm volatile("stmatrix.sync.aligned.m8n8.x2.shared.b16 [%0], {%1,%2};" :: "r"(l16 + ta), "r"(v0), "r"(v1) : "memory");
                if (C) {
                    if (act || s + 1 < NSEG) {
                        const uint32_t fo = (uint32_t)(warp * 256 + lane * 8);
                        const uint32_t rb0 = mapa(sbase, 0), rb1 = mapa(sbase, 1);
                        st_async64(rb0 + SM_VM + fo, v0, v1, rb0 + B_SB + 8 * (s & 1));
                        st_async64(rb1 + SM_VM + fo, v0, v1, rb1 + B_SB + 8 * (s & 1));
                        asm volatile("st.shared.v2.u32 [%0], {%1,%2};" :: "r"(sbase + SM_VM + fo), "r"(v0), "r"(v1) : "memory");
                        bar_arrive(2, 384);
                    }
                } else if (act) bar_arrive(2, 384);
                else {
                    named_bar(2, 384);
                    if (scw == 0) {
                        uint32_t kf[2][4], qf[2][4];
#pragma unroll
                        for (int k2 = 0; k2 < 2; k2++) { ldsm_x4_t(kf[k2], ka + to + k2 * 512); ldsm_x4_t(qf[k2], l16 + SM_T + to + k2 * 512); }
                        const uint32_t d0 = sbase + SM_S + lane * 8, bo = sbase + B_SB + 8 * (s & 1);
                        const uint32_t d1 = mapa(sbase + SM_S + 1280, role ^ 1) + lane * 4, m1 = mapa(bo, role ^ 1), d2 = mapa(sbase + SM_S + role * 1280, 2) + lane * 4, m2 = mapa(bo, 2);
                        score_group(qf, kf, d0, d1, m1, d2, m2);
                        bar_arrive(6, 160);
                        bar_arrive(5, 384);
                    }
                    if (scw == 8) {
                        const uint32_t dk = mapa(sbase + SM_X + XBUF + (2 + role) * 9216 + (warp - 4) * 256 + lane * 4, 2), mb = mapa(sbase + B_VX + 8, 2);
                        st_async32(dk, v0, mb);
                        st_async32(dk + 128, v1, mb);
                    }
                }
                FS(11, 0);
            };
            post(false, 0, 0, SM_T + warp * 256, warp ^ 7, v0, v1);
            if (tid == 128 && cta < NSEG) {
                fence_async();
                mbar_expect(sbase + B_E, XBUF);
                bulk_g2s(sbase + SM_X + 9 * 8192, xg + (size_t)cta * SEG * DM, 32768, sbase + B_E);
                bulk_g2s(sbase + SM_WS + 32768 + 4096, xg + (size_t)cta * SEG * DM + 16384, 4096, sbase + B_E);
            }
            __syncwarp();
            if (C) {
                named_bar(7, 256);
                if (warp == 1) norms_gather(lane_o, sbase);
            }
            auto chores = [&](int s, bool idle) {
                int lane = lane_o;
                asm volatile("" : "+r"(lane));
                const int hw = (s & 1) ? warp : warp - 4;
                const uint32_t tb = sbase + SM_T + (s & 3) * TBUF;
                if (idle) { if (hw != 2) named_bar(4, 384); else bar_arrive(4, 384); }
                if (hw == 2) {
                    if (lane == 0) {
                        {
                            if (C || !idle) fence_async();
                            if (C) {
                                store_tile(s + 1, h, 2, sbase + SM_T + ((s + 1) & 3) * TBUF, 2048, 10240);
                                store_tile(s, h, 2, tb, 0, idle ? 2048 : 10240);
                            } else store_tile(s, h, role, tb, 1024, 10240);
                            asm volatile("cp.async.bulk.commit_group;" ::: "memory");
                        }
                        {
                            asm volatile("cp.async.bulk.wait_group 0;" ::: "memory");
                            if (C) {
                                asm volatile("cp.async.bulk.shared::cluster.global.mbarrier::complete_tx::bytes.multicast::cluster [%0], [%1], 8192, [%2], %3;"
                                             :: "r"(sbase + SM_VX + ((s + 1) & 1) * 8192), "l"(&g_qkv[s + 1][h][2][2048]), "r"(sbase + B_VX + 8 * ((s + 1) & 1)), "h"((unsigned short)3) : "memory");
                            }
                            asm volatile("red.relaxed.gpu.global.add.u32 [%0], 1;" :: "l"(&g_flag[h * NSEG + s]) : "memory");
                        }
                    }
                    __syncwarp();
                    if (!C && (s & 1) && s + 4 < NSEG) bar_arrive(13, 160);
                }
                __syncwarp();
            };
            auto put_tiles = [&](const float (&acc)[32], uint32_t off) {
#pragma unroll
                for (int i = 0; i < 4; i++)
                    stsm_x4(off + (i >> 1) * TBUF + (i & 1) * (2 * DH * 16), pack_bf16(acc[8 * i], acc[8 * i + 1]), pack_bf16(acc[8 * i + 2], acc[8 * i + 3]),
                            pack_bf16(acc[8 * i + 4], acc[8 * i + 5]), pack_bf16(acc[8 * i + 6], acc[8 * i + 7]));
            };
            auto tile_off = [&](int p) {
                int lane = lane_o;
                asm volatile("" : "+r"(lane));
                return sbase + SM_T + (p & 1) * (2 * TBUF) + (DH + warp * 16 + (lane & 15)) * 16 + (lane >> 4) * (DH * 16);
            };
            {
                auto db = [&](int ks) { return (smem_desc(sbase + SM_X, 16, 1024) | (1ull << 62)) + (uint64_t)(((ks >> 2) - 5) * 512 + (ks & 3) * 2); };
                if (!C && warp != 7) bar_arrive(5, 384);
                if (warp == 5) {
                    mbar_wait(sbase + B_W + 8, 1);
                    bar_arrive(12, 160);
                }
                chores(0, false);
                float acc[32];
#pragma unroll
                for (int i = 0; i < 8; i++)
                    asm volatile("ld.shared.v4.f32 {%0,%1,%2,%3}, [%4];" : "=f"(acc[4 * i]), "=f"(acc[4 * i + 1]), "=f"(acc[4 * i + 2]), "=f"(acc[4 * i + 3])
                                 : "r"(l16 + warp * 512 + SM_X + 5 * 8192 + i * 4096) : "memory");
                mbar_wait(sbase + B_XT + 8, 0);
                FS(8, 0);
                named_bar(4, 384);
                wg_fence();
#pragma unroll
                for (int ks = 35; ks >= 20; ks--) wgmma_n64(acc, wreg[ks - NS], db(ks), 1);
                wg_commit();
                if (cta < NSEG) {
                    uint32_t m = 0u;
                    mbar_wait(sbase + B_E, 1);
#pragma unroll
                    for (int j = 0; j < 9; j++) {
                        const uint4 xv = lds128(l16 + warp * 512 + (j < 8 ? SM_X + 9 * 8192 + j * 4096 : SM_WS + 32768 + 4096));
                        m = max_abs8(m, xv.x, xv.y, xv.z, xv.w);
                    }
                    m = warp_max_abs(m);
                    if (lane_o == 0) asm volatile("st.volatile.global.u32 [%0], %1;" :: "l"(reinterpret_cast<uint32_t*>(&g_rx[cta][0]) + warp), "r"(m | 1u) : "memory");
                    __syncwarp();
                }
                FS(3, 0);
                wg_wait0();
                put_tiles(acc, tile_off(1));
                FS(7, __float_as_uint(acc[0]));
            }
            auto mem_proj = [&](uint32_t& u0, uint32_t& u1, bool xf) {
#pragma unroll
                for (int ks = 0; ks < NS - NP; ks++) ldsm_x4_t(ws[ks], wa + (ks >> 2) * 16384 + (ks & 3) * 2048);
                if (xf) {
                    named_bar(15, 160);
                    if (lane_o < 2) asm volatile("mbarrier.arrive.relaxed.cluster.shared::cluster.b64 _, [%0];" :: "r"(mapa(sbase + B_XF, lane_o)) : "memory");
                    __syncwarp();
                }
                FS(0, ws[0][0]);
                named_bar(1, 384);
                float acc[2][4], minv;
                uint32_t b[3][4];
#pragma unroll
                for (int kk = 0; kk < 3; kk++) ldsm_x4_t(b[kk], l16 + SM_M + kk * 512);
                FS(1, b[0][0]);
#pragma unroll
                for (int kk = 0; kk < 18; kk++) {
#pragma unroll
                    for (int i = 0; i < 2; i++) {
                        const int ks = 2 * kk + i;
                        if (ks < 2) mma_z(acc[i], ws[ks], b[kk % 3][2 * i], b[kk % 3][2 * i + 1]);
                        else if (ks < NS) mma_bf16(acc[i], ws[ks < NS ? ks : 0], b[kk % 3][2 * i], b[kk % 3][2 * i + 1]);
                        else mma_bf16(acc[i], wreg[ks >= NS ? ks - NS : 0], b[kk % 3][2 * i], b[kk % 3][2 * i + 1]);
                    }
                    if (kk + 3 < 18) ldsm_x4_t(b[kk % 3], l16 + SM_M + (kk + 3) * 512);
                    if (kk + 3 == 17) asm volatile("ld.shared.f32 %0, [%1];" : "=f"(minv) : "r"(sbase + SM_SC + 8) : "memory");
                }
                u0 = pack_bf16(fmaf(acc[1][0], minv, acc[0][0] * minv), fmaf(acc[1][1], minv, acc[0][1] * minv));
                u1 = pack_bf16(fmaf(acc[1][2], minv, acc[0][2] * minv), fmaf(acc[1][3], minv, acc[0][3] * minv));
                FS(2, u0);
            };
            int s = 0, rc = 9;
            bool act = warp >= 4;
            uint32_t to = TBUF, ta = SM_T + warp * 256 + TBUF;
            auto next_slot = [&]() {
                const uint32_t d = (s & 3) == 3 ? -3 * TBUF : TBUF;
                to += d; ta += d;
                asm volatile("" : "+r"(to), "+r"(ta));
            };
#pragma unroll 1
            for (;;) {
                uint32_t u0, u1;
                if (act) {
                    mem_proj(u0, u1, warp == 4 && s > 0);
                    s++;
                    post(true, s, to, ta, 1, u0, u1);
                    const int p = (s + 3) >> 1;
                    const uint32_t dlo = (uint32_t)smem_desc(sbase + SM_X, 16, 1024) + rc * 512;
                    const uint64_t da = smem_desc(sbase + SM_WS + (warp >> 2) * 8192, 1024, 1024) | (1ull << 62);
                    auto db = [&](int ks) {
                        const int j = ((ks >> 2) + 4) % 9;
                        return ((uint64_t)0x40000040u << 32) | (uint64_t)(dlo + (uint32_t)((j - (rc + j >= 13 ? 13 : 0)) * 512 + (ks & 3) * 2));
                    };
                    const uint32_t xph = (uint32_t)((p - 1) >> 1) & 1u;
                    float acc[32];
                    mbar_wait(sbase + B_XT + 8 * (p & 1), xph);
                    if (C) named_bar(7, 256); else named_bar(5, 384);
                    constexpr int N1 = C ? NC1C : NC1;
                    wg_fence();
#pragma unroll
                    for (int ks = 35; ks > 35 - N1; ks--) { if (ks == 35) wgmma_n64_z(acc, wreg[ks - NS], db(ks)); else wgmma_n64(acc, wreg[ks - NS], db(ks), 1); }
                    wg_commit();
                    wg_wait0();
                    FS(9, __float_as_uint(acc[0]));
                    next_slot();
                    FS(8, 0);
                    asm volatile("{\n.reg .pred p;\nsetp.ge.s32 p, %0, 0;\n@p bar.sync 4, 384;\n}" :: "r"(s) : "memory");
                    FS(3, 0);
                    wg_fence();
#pragma unroll
                    for (int ks = 35 - N1; ks >= 20; ks--) wgmma_n64(acc, wreg[ks - NS], db(ks), 1);
                    wg_commit();
                    mbar_wait(sbase + B_XT + 16 + 8 * (p & 1), xph);
                    wg_fence();
#pragma unroll
                    for (int ks = 0; ks < NS; ks++) {
                        wgmma_n64_ss(acc, da + (uint64_t)((ks >> 2) * 1024 + (ks & 3) * 128), db(ks));
                        if (ks == 3) wg_commit();
                    }
                    {
                        wg_commit();
                        wg_wait1();
                        asm volatile("{\n.reg .pred p;\nsetp.lt.s32 p, %0, %1;\n@p bar.arrive 15, 160;\n}" :: "r"(s + (warp >> 2) * NSEG), "n"(NSEG - 5) : "memory");
                    }
#pragma unroll
                    for (int ks = NS; ks < 20; ks++) wgmma_n64(acc, wreg[ks - NS], db(ks), 1);
                    wg_commit();
                    if (!C && warp >= 4) named_bar(13, 160);
                    uint32_t off = tile_off(p);
                    rc = rc >= 4 ? rc - 4 : rc + 9;
                    asm volatile("" : "+r"(off), "+r"(rc));
                    wg_wait0();
                    put_tiles(acc, off);
                    FS(7, __float_as_uint(acc[0]));
                }
                int scw = s + 2 < NSEG ? warp ^ ((s & 1) ? 7 : 3) : (warp & 4) + 4;
                asm volatile("" : "+r"(scw));
                mem_proj(u0, u1, false);
                s++;
                post(false, s, to, ta, scw, u0, u1);
                if (s + 1 == NSEG) break;
                if (s + 2 < NSEG) {
                    if (!C && (warp & 3) == 2) fence_async();
                    if (C) named_bar(7, 256); else if (scw != 0) named_bar(5, 384);
                    chores(s, true);
                } else {
                    const uint32_t t0 = clock32();
                    const uint32_t dq = mapa(sbase + SM_X + XBUF + role * 9216, 2), mb = mapa(sbase + B_VX, 2);
                    if (!C) {
                        if (scw != 0) named_bar(5, 384);
                        if (tid == 64) { fence_async(); while (clock32() - t0 < TL_DELAY) {} bulk_s2s(dq, sbase + SM_T + 2 * TBUF + 1024, 9216, mb); }
                        __syncwarp();
                    }
                    named_bar(4, 384);
                    if (!C && tid == 64) { const uint32_t t1 = clock32(); while (clock32() - t1 < VX_DELAY) {} bulk_s2s(dq + 2 * 9216 + 1024, sbase + SM_T + 3 * TBUF + 2048, 8192, mb + 8); }
                    __syncwarp();
                }
                next_slot();
                act = s + 4 < NSEG;
            }
            if (C) named_bar(7, 256);
        };
        if (role == 2) main_loop(Flag<true>()); else main_loop(Flag<false>());
    } else {
        uint32_t wo[3][8][4];
        uint32_t mx2 = 0u;
        {
            const int pt = tid - 256, lane = lane_o, wq = warp - 8, g = lane >> 2, tq = lane & 3;
            TSQ(7);
            mbar_wait(sbase + B_E, 0);
            TSQ(8);
#pragma unroll
            for (int t = 0; t < 3; t++) {
                const int T = 3 * wq + t;
                const uint32_t a = sbase + SM_X01 + (T >> 2) * 16384 + ((lane >> 4) * 8 + (lane & 7)) * 128 + ((((T & 3) * 2 + ((lane >> 3) & 1)) ^ (lane & 7)) << 4);
#pragma unroll
                for (int kk = 0; kk < 8; kk++) ldsm_x4_t(wo[t][kk], a + ((2 * wq + kk) & 7) * 2048);
            }
            named_bar(3, 128);
            if (pt == 64) {
                fence_async();
#pragma unroll 1
                for (int i = 3; i < 9; i++) { stage_x(i); if (i < 7) stage_w(i); }
            }
            if (pt >= 96 && pt < 120) {
                *reinterpret_cast<uint4*>(g_acc + cta * 1024 + (pt - 96) * 16) = make_uint4(0u, 0u, 0u, 0u);
                __threadfence();
            }
            __syncwarp();
            TSQ(9);
            float c0 = 0.f;
#pragma unroll
            for (int t = 0; t < 3; t++) {
                float n[4][4];
#pragma unroll
                for (int i = 0; i < 4; i++) { n[i][0] = n[i][1] = n[i][2] = n[i][3] = 0.f; }
#pragma unroll
                for (int kk = 0; kk < 8; kk++)
#pragma unroll
                    for (int i = 0; i < 4; i++) mma_k8(n[i], wo[t][kk][i & 2], wo[t][kk][(i & 2) + 1], wo[t][kk][i]);
                if ((g >> 1) == tq) c0 = fmaxf(c0, (g & 1) ? fmaxf(n[0][1] + n[2][1], n[1][3] + n[3][3]) : fmaxf(n[0][0] + n[2][0], n[1][2] + n[3][2]));
            }
            c0 = __uint_as_float(__reduce_max_sync(0xffffffffu, __float_as_uint(c0)));
            uint32_t m = 0u;
            const int xb = role == 0 ? h % 9 : 9;
            auto x_max = [&]() {
                mbar_wait(sbase + B_W + 8 * xb, 0);
#pragma unroll
                for (int j = 0; j < 5; j++) {
                    uint4 xv;
                    asm volatile("ld.shared.v4.u32 {%0,%1,%2,%3}, [%4];" : "=r"(xv.x), "=r"(xv.y), "=r"(xv.z), "=r"(xv.w)
                                 : "r"(sbase + x01_off(xb) + (j < 4 ? pt + 128 * j : 512 + (pt & 63)) * 16) : "memory");
                    m = max_abs8(m, xv.x, xv.y, xv.z, xv.w);
                }
            };
            if (xb < 3) x_max();
            named_bar(10, 384);
            TSQ(10);
            if (pt == 64) {
                fence_async();
                mbar_expect(sbase + B_W + 16, 16384);
#pragma unroll
                for (int i = 3; i < 5; i++) tma_2d(sbase + x23_off(i), &tmx2, i * 64, 64, sbase + B_W + 16);
#pragma unroll 1
                for (int i = 7; i < 9; i++) stage_w(i);
            }
            __syncwarp();
            if (xb >= 3 && xb < 7) x_max();
            bar_arrive(11, 384);
            if (xb == 7 || xb == 8) x_max();
            asm volatile("barrier.cluster.arrive.relaxed.aligned;" ::: "memory");
            m = warp_max_abs(m);
            if (lane == 0) { sts32(sbase + SM_SC + 320 + 4 * wq, __float_as_uint(c0)); sts32(sbase + SM_SC + 336 + 4 * wq, m); }
            TSQ(1);
            named_bar(3, 128);
            if (pt == 0) {
                const uint4 a = lds128(sbase + SM_SC + 320), b = lds128(sbase + SM_SC + 336);
                st_vol_u2(&g_norm[cta], make_uint2(max(max(a.x, a.y), max(a.z, a.w)) | 1u, max(max(b.x, b.y), max(b.z, b.w)) | 1u));
            }
            __syncwarp();
            named_bar(8, 384);
            TSQ(2);
            asm volatile("barrier.cluster.wait.aligned;" ::: "memory");
            if (role == 2 && lane == 0 && wq < 2) vx_copy(sbase, 0, wq);
            __syncwarp();
        }
        const int wq = warp - 8;
        auto helper_loop = [&](auto is_c) {
        const bool C = is_c.value;
        const uint32_t sb = sbase;
        const uint32_t l8_o = __shfl_sync(0xffffffffu, sb + lane_o * 8, lane_o), l16_o = __shfl_sync(0xffffffffu, sb + lane_o * 16, lane_o);
        unsigned char* dst = g_acc + (role * 32 + wq * 8 + (lane_o >> 3)) * 1024 + (lane_o & 7) * 16;
        auto load_kf = [&](uint32_t (&kf)[2][4], int slot) {
            int lane = lane_o;
            asm volatile("" : "+r"(lane));
            const uint32_t ka = sb + SM_T + slot * TBUF + ((wq + 1) * DH + 64 + (lane & 7) + ((lane >> 3) & 1) * 16 + (lane >> 4) * 8) * 16;
#pragma unroll
            for (int k2 = 0; k2 < 2; k2++) ldsm_x4_t(kf[k2], ka + k2 * 512);
        };
        float minv = 1.f;
        uint32_t kf[2][4];
        if (!C) load_kf(kf, 0);
        int b3 = 0;
        int rx = 9;
        for (int s = 0; s + 1 < NSEG; s++) {
            const int n3 = b3 == 2 ? 0 : b3 + 1;
            uint32_t l8 = l8_o, l16 = l16_o;
            asm volatile("" : "+r"(l8), "+r"(l16));
            const uint32_t l4 = sb + ((l8 - sb) >> 1);
            {
                int lane = lane_o;
                asm volatile("" : "+r"(lane));
                if (C) {
                    if (lane == 0) {
                        if (wq == 3 && h == 0) {
                            const uint32_t t = gtime32();
                            st_vol_u2(&g_tick, make_uint2(t, lds32(sb + SM_SC + 12)));
                            sts32(sb + SM_SC + 12, t);
                        }
                    }
                    __syncwarp();
                    if (wq == 2 && s > 1 && lane < 24) {
                        *reinterpret_cast<uint4*>(g_acc + n3 * 128 + (3 * h + (lane >> 3)) * 1024 + (lane & 7) * 16) = make_uint4(0u, 0u, 0u, 0u);
                    }
                    if (wq == 1 && s == 3 && lane < 3) {
                        const int c = 3 * h + lane;
                        st_vol_u2(&g_norm[c], make_uint2(0u, 0u));
                        uint4* z = c < NSEG ? g_rx[c] : g_wv[c - NSEG];
                        st_vol_u4(z, make_uint4(0u, 0u, 0u, 0u)); st_vol_u4(z + 1, make_uint4(0u, 0u, 0u, 0u));
                    }
                    __syncwarp();
                }
                const uint32_t mw = __reduce_max_sync(0xffffffffu, max(mx2 << 16, mx2 & 0xffff0000u));
                if (lane == 0) sts32(sb + SM_SC + 16 + 4 * wq, mw);
            }
            const uint32_t to = SM_T + (s & 3) * TBUF;
            const uint32_t ph = (uint32_t)(s >> 1) & 1u;
            if (!C) {
                const uint32_t bo = sb + B_SB + 8 * (s & 1);
                uint32_t d0 = l8 + SM_S + (wq + 1) * 256, qa = l16 + to;
                const uint32_t dr = l4 + SM_S + (wq + 1) * 256;
                const uint32_t d1 = mapa(dr + 1280, role ^ 1), m1 = mapa(bo, role ^ 1), d2 = mapa(dr + role * 1280, 2), m2 = mapa(bo, 2);
                asm volatile("" : "+r"(d0), "+r"(qa));
                mbar_wait(sb + (s > 0 ? B_VX + 8 * (s & 1) : B_W), ph);
                FS(1, 0);
                named_bar(2, 384);
                uint32_t qf[2][4];
#pragma unroll
                for (int k2 = 0; k2 < 2; k2++) ldsm_x4_t(qf[k2], qa + k2 * 512);
                score_group(qf, kf, d0, d1, m1, d2, m2);
                bar_arrive(5, 384);
            } else named_bar(2, 384);
            if (!C && s == 0) {
                TSQ(3);
                mbar_wait(sb + B_VX, 0);
                TSQ(4);
            }
            float4 m4;
            asm volatile("ld.shared.v4.f32 {%0,%1,%2,%3}, [%4];" : "=f"(m4.x), "=f"(m4.y), "=f"(m4.z), "=f"(m4.w) : "r"(sb + SM_SC + 16) : "memory");
            const float c24 = __uint_as_float(lds32(sb + SM_SC + 4)), xb = __uint_as_float(lds32(sb + SM_SC + 64 + 4 * s));
            uint32_t vf[2][2][4], vm[2][2];
            uint32_t va = l16 + ((l16 >> 8) & 1) * 1792 + wq * 512 + (C ? to + DH * 16 : SM_VX + (s & 1) * 8192);
            auto load_vf = [&]() {
#pragma unroll
                for (int i = 0; i < 4; i++) ldsm_x4(vf[i & 1][i >> 1], va + (i & 1) * 256 + (i >> 1) * 4096);
            };
            load_vf();
            float scale = to_scale(fmaxf(fmaxf(fmaxf(m4.x, m4.y), fmaxf(m4.z, m4.w)) * minv, xb) * c24);
            uint32_t oa = l16 + wq * 512;
            asm volatile("" : "+f"(scale), "+r"(oa), "+r"(va));
            FS(7, __float_as_uint(scale));
            if (!C) named_bar(6, 160);
            if (C) mbar_wait(sb + B_SB + 8 * (s & 1), ph);
            float sv[5][2];
#pragma unroll
            for (int j = 0; j < 5; j++) {
                if (C) { const uint32_t w = lds32(l4 + SM_S + j * 256); sv[j][0] = __uint_as_float(w << 16); sv[j][1] = __uint_as_float(w & 0xffff0000u); }
                else lds64f(sv[j][0], sv[j][1], l8 + SM_S + j * 256);
            }
            if (!C) mbar_wait(sb + B_SB + 8 * (s & 1), ph);
            FS(6, 0);
            uint32_t p[5];
            {
                float sr[5][2];
#pragma unroll
                for (int j = 0; j < 5; j++) {
                    const uint32_t w = lds32(l4 + SM_S + 1280 + j * 256);
                    sr[j][0] = __uint_as_float(w << 16); sr[j][1] = __uint_as_float(w & 0xffff0000u);
                }
                lds64(vm[0][0], vm[0][1], l8 + SM_VM + wq * 512);
                lds64(vm[1][0], vm[1][1], l8 + SM_VM + wq * 512 + 256);
#pragma unroll
                for (int j = 0; j < 5; j++) {
                    sv[j][0] += sr[j][0];
                    sv[j][1] += sr[j][1];
                }
                float mx = fmaxf(fmaxf(fmaxf(sv[0][0], sv[0][1]), fmaxf(sv[1][0], sv[1][1])), fmaxf(fmaxf(sv[2][0], sv[2][1]), fmaxf(sv[3][0], sv[3][1])));
                mx = fmaxf(mx, fmaxf(sv[4][0], sv[4][1]));
                {
                    const float m1 = __shfl_xor_sync(0xffffffffu, mx, 1), m2 = __shfl_xor_sync(0xffffffffu, mx, 2), m3 = __shfl_xor_sync(0xffffffffu, mx, 3);
                    mx = fmaxf(fmaxf(mx, m1), fmaxf(m2, m3));
                }
#pragma unroll
                for (int jj = 0; jj < 5; jj++) {
                    const int j = (jj + 1) % 5;
                    asm("ex2.approx.ftz.f32 %0, %1;" : "=f"(sv[j][0]) : "f"(sv[j][0] - mx));
                    asm("ex2.approx.ftz.f32 %0, %1;" : "=f"(sv[j][1]) : "f"(sv[j][1] - mx));
                    p[j] = pack_bf16(sv[j][0], sv[j][1]);
                }
            }
            FS(0, p[0]);
            uint32_t b[4][4];
            const uint32_t one4[4] = {0x3f803f80u, 0x3f803f80u, 0x3f803f80u, 0x3f803f80u};
            float zs[4];
            {
                float o0[2][4], o1[2][4];
                mma_z(o0[0], vf[0][0], p[1], p[2]);
                mma_z(o0[1], vf[1][0], p[1], p[2]);
                mma_z(o1[0], vf[0][1], p[3], p[4]);
                mma_z(o1[1], vf[1][1], p[3], p[4]);
                mma_k8(o0[0], vm[0][0], vm[0][1], p[0]);
                mma_k8(o0[1], vm[1][0], vm[1][1], p[0]);
                float z2[4];
                mma_z(zs, one4, p[1], p[2]);
                mma_z(z2, one4, p[3], p[4]);
                mma_k8(zs, one4[0], one4[1], p[0]);
                zs[0] += z2[0]; zs[1] += z2[1];
                uint32_t ow[4];
#pragma unroll
                for (int m = 0; m < 2; m++) {
                    ow[2 * m] = pack_bf16(o0[m][0] + o1[m][0], o0[m][1] + o1[m][1]);
                    ow[2 * m + 1] = pack_bf16(o0[m][2] + o1[m][2], o0[m][3] + o1[m][3]);
                }
                stsm_x4(oa + SM_O, ow[0], ow[1], ow[2], ow[3]);
                FS(2, 0);
                b[0][0] = movm(ow[0]); b[0][1] = movm(ow[1]);
                __syncwarp();
                asm volatile("ldmatrix.sync.aligned.m8n8.x2.trans.shared.b16 {%0,%1}, [%2];" : "=r"(b[0][2]), "=r"(b[0][3]) : "r"(oa + SM_O + 256));
            }
            float acc[3][2][4];
            named_bar(3, 128);
#pragma unroll
            for (int i = 1; i < 4; i++) ldsm_x4_t(b[i], l16 + SM_O + ((wq + i) & 3) * 512);
#pragma unroll
            for (int c = 0; c < 2; c++)
#pragma unroll
                for (int t = 0; t < 3; t++) mma_z(acc[t][c], wo[t][c], b[0][2 * c], b[0][2 * c + 1]);
            float z0, z1;
            asm volatile("rcp.approx.ftz.f32 %0, %1;" : "=f"(z0) : "f"(zs[0]));
            asm volatile("rcp.approx.ftz.f32 %0, %1;" : "=f"(z1) : "f"(zs[1]));
            asm volatile("{\n.reg .pred p;\nsetp.eq.s32 p, %1, 0;\n@p bar.sync 12, 160;\n@p ld.shared.f32 %0, [%2];\n}" : "+f"(scale) : "r"(s), "r"(sb + SM_SC) : "memory");
            z0 *= scale; z1 *= scale;
            FS(3, b[1][0]);
#pragma unroll
            for (int i = 1; i < 4; i++)
#pragma unroll
                for (int c = 0; c < 2; c++)
#pragma unroll
                    for (int t = 0; t < 3; t++) mma_bf16(acc[t][c], wo[t][2 * i + c], b[i][2 * c], b[i][2 * c + 1]);
            {
                uint32_t w[6];
#pragma unroll
                for (int t = 0; t < 3; t++) {
                    w[2 * t] = pack_f16(fmaf(acc[t][1][0], z0, acc[t][0][0] * z0), fmaf(acc[t][1][1], z1, acc[t][0][1] * z1));
                    w[2 * t + 1] = pack_f16(fmaf(acc[t][1][2], z0, acc[t][0][2] * z0), fmaf(acc[t][1][3], z1, acc[t][0][3] * z1));
                }
                FS(8, w[5]);
                asm volatile("red.relaxed.gpu.global.add.noftz.v4.f16x2 [%0], {%1,%2,%3,%4};" :: "l"(dst), "r"(w[0]), "r"(w[1]), "r"(w[2]), "r"(0x3c00u) : "memory");
                asm volatile("red.relaxed.gpu.global.add.noftz.v4.f16x2 [%0], {%1,%2,%3,%4};" :: "l"(dst + 4096), "r"(w[3]), "r"(w[4]), "r"(w[5]), "r"(0x3c00u) : "memory");
            }
            FS(9, 0);
            if (s == 0) TSQ(5);
            bar_arrive(4, 384);
            const uint32_t t0 = clock32();
            minv = __uint_as_float(0x7f000000u - __float_as_uint(scale));
            if (lane_o == 0) {
                if (wq == 0) sts32(sb + SM_SC + 8, __float_as_uint(minv));
                if (s + 3 < NSEG) {
                    if (wq == 0) mbar_expect(sb + B_SB + 8 * (s & 1), C ? 1280 : 640 + 2048);
                    if (wq == 1 && s > 0 && s + 5 < NSEG) mbar_expect(sb + B_XT + ((s & 1) ? 0 : 16) + 4 * ((s + 1) & 2), (s & 1) ? 32768 : 40960);
                    if (wq == 3 && !C) mbar_expect(sb + B_VX + 8 * (s & 1), 8192);
                }
            }
            __syncwarp();
            if (s == 1) {
                int lane = lane_o;
                asm volatile("" : "+r"(lane));
                if (wq == 3) xmax_gather(lane, sb);
                __syncwarp();
            }
            if (!C) load_kf(kf, (s + 1) & 3);
            const uint4* src = reinterpret_cast<const uint4*>(dst + (wq * 16 - role * 32) * 1024);
            dst += n3 == 0 ? -256 : 128;
            asm volatile("" : "+l"(dst));
            const int xp = (s + 5) >> 1, kb = wq + ((s & 1) ? 2 * role : 4 + 3 * role);
            const bool xl = !C && xp < NSEG / 2 && wq < ((s & 1) ? 2 : 3 - role);
            const uint32_t xs = wq == 3 && s == 0;
            const uint32_t xd = sb + SM_X + (rx + kb >= 13 ? rx + kb - 13 : rx + kb) * 8192;
            mx2 = poll_mem(src, l16 + SM_M + wq * 2304, t0, [&]() {
                if (xs && lane_o < 2) asm volatile("mbarrier.arrive.relaxed.cluster.shared::cluster.b64 _, [%0];" :: "r"(mapa(sb + B_XF, lane_o)) : "memory");
                if (!C && (xl || s == 0) && (s & 1) == 0) mbar_wait(sb + B_XF, (uint32_t)(s >> 1) & 1u);
                if (lane_o == 0) {
                    if (xl) tma_2d_mc(xd, &tmx2, ((s & 1) ? kb + 5 : kb - 4) * 64, xp * 64, sb + B_XT + ((s & 1) ? 0 : 16) + 8 * (xp & 1));
                    if (!C && s == 0 && role == 1) tma_2d_mc(sb + SM_X + (9 + wq) * 8192, &tmx2, (wq + 5) * 64, 128, sb + B_XT);
                }
                __syncwarp();
            });
            if ((s & 1) == 0) rx = rx >= 4 ? rx - 4 : rx + 9;
            if (s == 0) TSQ(6);
            b3 = n3;
        }
        if (!C) bar_arrive(2, 384);
        };
        if (role == 2) helper_loop(Flag<true>()); else helper_loop(Flag<false>());
    }
    TS3C(1);
    if (role == 2 && warp >= 4) last_rows();
    cluster_sync_all();
}

extern "C" void kernel_launch(void* const* d_in, const int* in_sizes, int n_in, void* d_out, int out_size) {
    const bf16* x = (const bf16*)d_in[0];
    const bf16* mem0 = (const bf16*)d_in[1];
    const bf16* Wq = (const bf16*)d_in[2];
    const bf16* Wk = (const bf16*)d_in[3];
    const bf16* Wv = (const bf16*)d_in[4];
    const bf16* Wo = (const bf16*)d_in[5];
    const bf16* logA = (const bf16*)d_in[8];
    const bf16* Aim = (const bf16*)d_in[9];
    const bf16* Cre = (const bf16*)d_in[10];
    const bf16* Cim = (const bf16*)d_in[11];
    const bf16* logdt = (const bf16*)d_in[12];
    const bf16* dskip = (const bf16*)d_in[13];
    const bf16* gw = (const bf16*)d_in[14];
    bf16* out = (bf16*)d_out;
    static bool attr_done = false;
    typedef CUresult (*EncFn)(CUtensorMap*, CUtensorMapDataType, cuuint32_t, void*, const cuuint64_t*, const cuuint64_t*, const cuuint32_t*,
                              const cuuint32_t*, CUtensorMapInterleave, CUtensorMapSwizzle, CUtensorMapL2promotion, CUtensorMapFloatOOBfill);
    static EncFn enc = nullptr;
    if (!attr_done) {
        void* fn = nullptr;
        cudaDriverEntryPointQueryResult qr;
        cudaGetDriverEntryPoint("cuTensorMapEncodeTiled", &fn, cudaEnableDefault, &qr);
        enc = (EncFn)fn;
        cudaFuncSetAttribute(k_chain, cudaFuncAttributeMaxDynamicSharedMemorySize, 232448);
        cudaFuncSetAttribute(k_side, cudaFuncAttributeMaxDynamicSharedMemorySize, SIDE_SMEM);
        attr_done = true;
    }
    CUtensorMap tmw[3];
    for (int i = 0; i < 3; i++) {
        const cuuint64_t dims[2] = {(cuuint64_t)HD, (cuuint64_t)DM};
        const cuuint64_t strides[1] = {(cuuint64_t)HD * 2};
        const cuuint32_t box[2] = {64, 64};
        const cuuint32_t es[2] = {1, 1};
        enc(&tmw[i], CU_TENSOR_MAP_DATA_TYPE_BFLOAT16, 2, (void*)(i == 0 ? Wq : (i == 1 ? Wk : Wv)), dims, strides, box, es, CU_TENSOR_MAP_INTERLEAVE_NONE,
            CU_TENSOR_MAP_SWIZZLE_128B, CU_TENSOR_MAP_L2_PROMOTION_L2_256B, CU_TENSOR_MAP_FLOAT_OOB_FILL_NONE);
    }
    CUtensorMap tmo;
    {
        const cuuint64_t dims[2] = {(cuuint64_t)DM, (cuuint64_t)HD};
        const cuuint64_t strides[1] = {(cuuint64_t)DM * 2};
        const cuuint32_t box[2] = {64, 128};
        const cuuint32_t es[2] = {1, 1};
        enc(&tmo, CU_TENSOR_MAP_DATA_TYPE_BFLOAT16, 2, (void*)Wo, dims, strides, box, es, CU_TENSOR_MAP_INTERLEAVE_NONE,
            CU_TENSOR_MAP_SWIZZLE_128B, CU_TENSOR_MAP_L2_PROMOTION_L2_128B, CU_TENSOR_MAP_FLOAT_OOB_FILL_NONE);
    }
    CUtensorMap tmx2;
    {
        const cuuint64_t dims[2] = {(cuuint64_t)DM, (cuuint64_t)S_LEN};
        const cuuint64_t strides[1] = {(cuuint64_t)DM * 2};
        const cuuint32_t box[2] = {64, 64};
        const cuuint32_t es[2] = {1, 1};
        enc(&tmx2, CU_TENSOR_MAP_DATA_TYPE_BFLOAT16, 2, (void*)x, dims, strides, box, es, CU_TENSOR_MAP_INTERLEAVE_NONE,
            CU_TENSOR_MAP_SWIZZLE_128B, CU_TENSOR_MAP_L2_PROMOTION_L2_128B, CU_TENSOR_MAP_FLOAT_OOB_FILL_NONE);
    }
    CUtensorMap tmm;
    {
        const cuuint64_t dims[2] = {(cuuint64_t)DM, (cuuint64_t)MEMT};
        const cuuint64_t strides[1] = {(cuuint64_t)DM * 2};
        const cuuint32_t box[2] = {64, (cuuint32_t)MEMT};
        const cuuint32_t es[2] = {1, 1};
        enc(&tmm, CU_TENSOR_MAP_DATA_TYPE_BFLOAT16, 2, (void*)mem0, dims, strides, box, es, CU_TENSOR_MAP_INTERLEAVE_NONE,
            CU_TENSOR_MAP_SWIZZLE_128B, CU_TENSOR_MAP_L2_PROMOTION_L2_128B, CU_TENSOR_MAP_FLOAT_OOB_FILL_NONE);
    }
    k_chain<<<NCTA, 384, 232448>>>(tmw[0], tmw[1], tmw[2], tmx2, tmo, tmm, x);
    {
        cudaLaunchConfig_t cfg = {};
        cfg.gridDim = dim3(SD_NCTA); cfg.blockDim = dim3(512); cfg.dynamicSmemBytes = SIDE_SMEM; cfg.stream = cudaStreamPerThread;
        cudaLaunchAttribute at[1];
        at[0].id = cudaLaunchAttributeProgrammaticStreamSerialization;
        at[0].val.programmaticStreamSerializationAllowed = 1;
        cfg.attrs = at; cfg.numAttrs = 1;
        cudaLaunchKernelEx(&cfg, k_side, tmo, x, logA, Aim, Cre, Cim, logdt, Wo, dskip, gw, out);
    }
}
```

```cpp
#include <cuda_runtime.h>
#include <cuda.h>
#include <cuda_bf16.h>
#include <stdint.h>

typedef __nv_bfloat16 bf16;
#define LDV4 "ld.volatile.global.v4.u32 {%0,%1,%2,%3}, [%4];"
#define STV4 "st.volatile.global.v4.u32 [%0], {%1,%2,%3,%4};"
#define STV2 "st.volatile.global.v2.u32 [%0], {%1,%2};"

constexpr int S_LEN = 2048, DM = 576, NH = 32, DH = 128, HD = 4096, MEMT = 8, SEG = 32, NSEG = 64, NST = 128;

__device__ __align__(128) bf16 g_gate[S_LEN];
constexpr int NCTA = NH * 3;
__device__ __align__(1024) unsigned char g_acc[96 * 1024];
__device__ __align__(128) uint2 g_norm[NCTA];
__device__ __align__(128) uint4 g_wv[NH][2];
__device__ __align__(128) uint4 g_rx[NSEG][2];
__device__ __align__(128) unsigned char g_qkv[NSEG][NH][3][10240];
__device__ __align__(128) bf16 g_ox[S_LEN * HD];
__device__ __align__(128) uint4 g_fp[8][36][6][128];
__device__ __align__(128) unsigned g_flag[NH * NSEG];
__device__ __align__(128) unsigned g_prog[8 * 64];
__device__ unsigned g_gcnt[64];
__device__ unsigned g_epoch;
__device__ __align__(128) uint2 g_tick;
__device__ __align__(128) bf16 g_y[DM * S_LEN];

#define TS3(slot) do {} while (0)
#define TS3P(slot) do {} while (0)
#define TSQ(slot) do {} while (0)
#define TS3W(slot) do {} while (0)
#define TSS(row, slot) do {} while (0)
#define TS3C(slot) do {} while (0)
#define TST(slot) do {} while (0)
#define TSA(seg, slot) do {} while (0)
#define TSG(i) do {} while (0)
#define FS(i, dep) do {} while (0)
__device__ __forceinline__ uint32_t smem_u32(const void* p) { return (uint32_t)__cvta_generic_to_shared(p); }
__device__ __forceinline__ float bf16r(float x) { return __bfloat162float(__float2bfloat16_rn(x)); }
__device__ __forceinline__ uint32_t pack_bf16(float lo, float hi) {
    __nv_bfloat162 v = __floats2bfloat162_rn(lo, hi);
    return *reinterpret_cast<uint32_t*>(&v);
}
__device__ __forceinline__ void ldsm_x4(uint32_t (&r)[4], uint32_t addr) {
    asm volatile("ldmatrix.sync.aligned.m8n8.x4.shared.b16 {%0,%1,%2,%3}, [%4];"
                 : "=r"(r[0]), "=r"(r[1]), "=r"(r[2]), "=r"(r[3]) : "r"(addr));
}
__device__ __forceinline__ void ldsm_x4_t(uint32_t (&r)[4], uint32_t addr) {
    asm volatile("ldmatrix.sync.aligned.m8n8.x4.trans.shared.b16 {%0,%1,%2,%3}, [%4];"
                 : "=r"(r[0]), "=r"(r[1]), "=r"(r[2]), "=r"(r[3]) : "r"(addr));
}
__device__ __forceinline__ void mma_bf16(float (&d)[4], const uint32_t (&a)[4], uint32_t b0, uint32_t b1) {
    asm volatile("mma.sync.aligned.m16n8k16.row.col.f32.bf16.bf16.f32 {%0,%1,%2,%3}, {%4,%5,%6,%7}, {%8,%9}, {%0,%1,%2,%3};"
                 : "+f"(d[0]), "+f"(d[1]), "+f"(d[2]), "+f"(d[3])
                 : "r"(a[0]), "r"(a[1]), "r"(a[2]), "r"(a[3]), "r"(b0), "r"(b1));
}
__device__ __forceinline__ uint2 ld_vol_u2(const uint2* p) {
    uint2 v; asm volatile("ld.volatile.global.v2.u32 {%0,%1}, [%2];" : "=r"(v.x), "=r"(v.y) : "l"(p) : "memory"); return v;
}
__device__ __forceinline__ void st_vol_u2(uint2* p, uint2 v) {
    asm volatile(STV2 :: "l"(p), "r"(v.x), "r"(v.y) : "memory");
}
__device__ __forceinline__ unsigned ld_acq(const unsigned* p) {
    unsigned v; asm volatile("ld.acquire.gpu.global.u32 %0, [%1];" : "=r"(v) : "l"(p) : "memory"); return v;
}
#define NS 10
#define NP 4
#define GATE_A 950
#define GATE_B 450
#define GATE_P 1800u
#define RLX_SLEEP 20
#define VX_DELAY 100
#define UNGATE_G 3
#define W14_SLEEP 30
#define GL_A 1150
#define GL_B 530
#define GS_A 1300
#define GS_B 480
#define NC1 3
#define NC1C 5
#define KPRE 34
#define WO_SLEEP 200
#define WO_LAG 500
#define PRG_SLEEP 250
#define TM 29
#define TM2 (TM - 1)
#define TL_DELAY 600
#define POLL_DELAY 590
#define UNGATE 6
constexpr unsigned SPIN_LIMIT = 1u << 20;
constexpr int NATT = NSEG - 2;

constexpr int SD_CH = 16;
constexpr int SD_NCTA = DM / SD_CH;
constexpr int SD_ROW = 528;
constexpr int SD_U = 8 * SD_ROW;
constexpr int SD_TAP = 5888;
constexpr int SD_CPY = 1376 * 2;
constexpr int SD_WSTR = SD_TAP + 2 * SD_CPY;
constexpr int SD_SMEM = SD_CH * SD_U + 8 * SD_WSTR;
constexpr int O_U = 79, O_U3 = 911, O_U4 = 1055, O_W79 = 1023, O_W35 = 1151, O_W610 = 1279, O_W511 = 1487;

__device__ __forceinline__ uint32_t lds32(uint32_t a) { uint32_t v; asm volatile("ld.shared.u32 %0, [%1];" : "=r"(v) : "r"(a)); return v; }
__device__ __forceinline__ void sts32(uint32_t a, uint32_t v) { asm volatile("st.shared.u32 [%0], %1;" :: "r"(a), "r"(v) : "memory"); }
__device__ __forceinline__ uint4 lds128(uint32_t a) {
    uint4 v; asm volatile("ld.shared.v4.u32 {%0,%1,%2,%3}, [%4];" : "=r"(v.x), "=r"(v.y), "=r"(v.z), "=r"(v.w) : "r"(a) : "memory"); return v;
}
__device__ __forceinline__ void tap_tile(uint32_t (&t)[4], uint32_t a) {
    asm volatile("ld.volatile.shared.u32 %0, [%4];\nld.volatile.shared.u32 %1, [%4+-16];\nld.volatile.shared.u32 %2, [%4+16];\nld.volatile.shared.u32 %3, [%4];"
                 : "=r"(t[0]), "=r"(t[1]), "=r"(t[2]), "=r"(t[3]) : "r"(a));
}
constexpr uint32_t sd_pass(int type, int dl, int o, int d0, int d1) { return (uint32_t)(type | dl << 2 | d0 << 8 | d1 << 12 | o << 17); }
__constant__ uint32_t SD_PASS[14] = {sd_pass(0, 0, O_U, 0, 2), sd_pass(0, 1, O_U + 96, 0, 2), sd_pass(0, 2, O_U + 192, 0, 4), sd_pass(0, 3, O_U + 288, 0, 2), sd_pass(1, 0, O_U3, 8, 8),
                                     sd_pass(0, 4, O_U + 384, 0, 2), sd_pass(1, 0, O_U4, 8, 15), sd_pass(0, 5, O_U + 480, 0, 2), sd_pass(0, 6, O_U + 576, 0, 4), sd_pass(0, 7, O_U + 672, 0, 2),
                                     sd_pass(2, 0, O_W35, 2, 8), sd_pass(3, 0, O_W79, 2, 4), sd_pass(2, 1, O_W610, 4, 8), sd_pass(3, 0, O_W511, 8, 15)};
__device__ __forceinline__ uint32_t band2(int x, int lo, int hi) { return (x >= lo && x <= hi ? 0x3f80u : 0u) | (x + 1 >= lo && x + 1 <= hi ? 0x3f800000u : 0u); }
__device__ __forceinline__ void mma_z(float (&d)[4], const uint32_t (&a)[4], uint32_t b0, uint32_t b1);
__device__ __forceinline__ void put_tap(uint32_t a, float v) {
    asm volatile("{\n.reg .b16 h;\ncvt.rn.bf16.f32 h, %1;\nst.shared.b16 [%0], h;\nst.shared.b16 [%0+%2], h;\n}" :: "r"(a), "f"(v), "n"(SD_CPY - 2) : "memory");
}

__device__ __forceinline__ void named_bar(int id, int n) { asm volatile("bar.sync %0, %1;" :: "r"(id), "r"(n) : "memory"); }
__device__ __forceinline__ uint32_t pack_f16(float lo, float hi) {
    uint32_t r; asm("cvt.rn.f16x2.f32 %0, %1, %2;" : "=r"(r) : "f"(hi), "f"(lo)); return r;
}
__device__ __forceinline__ void cexp_t(float lr, float turns, float& re, float& im) {
    float m;
    asm("ex2.approx.ftz.f32 %0, %1;" : "=f"(m) : "f"(lr));
    const float a = (turns - rintf(turns)) * 6.283185307179586f;
    re = m * __cosf(a); im = m * __sinf(a);
}
__device__ __forceinline__ void csq(float& re, float& im) { const float r = re * re - im * im; im = 2.f * re * im; re = r; }
__device__ __forceinline__ void kb_state(const float* tp, float gf, uint32_t (&a)[4][2], uint32_t (&b)[5]) {
    const float4 p0 = *reinterpret_cast<const float4*>(tp), p1 = *reinterpret_cast<const float4*>(tp + 4);
    float wr, wi;
    cexp_t(p0.x * gf, p0.y * gf, wr, wi);
    float vr = wr * p1.x - wi * p1.y, vi = wr * p1.y + wi * p1.x;
#pragma unroll
    for (int c = 0; c < 4; c++) {
        a[c][0] = pack_f16(wr, wi); a[c][1] = pack_f16(vr, vi);
        csq(wr, wi);
        if (c < 3) csq(vr, vi);
    }
    b[0] = pack_f16(p0.z * wr - p0.w * wi, -p0.z * wi - p0.w * wr);
    float er = wr * p1.z - wi * p1.w, ei = wr * p1.w + wi * p1.z;
#pragma unroll
    for (int c = 0; c < 4; c++) {
        b[1 + c] = pack_f16(p0.z * er - p0.w * ei, -p0.z * ei - p0.w * er);
        if (c < 3) csq(er, ei);
    }
}
__device__ __forceinline__ uint32_t bf2_mul(uint32_t a, uint32_t b) { uint32_t r; asm("mul.rn.bf16x2 %0, %1, %2;" : "=r"(r) : "r"(a), "r"(b)); return r; }
__device__ __forceinline__ uint32_t bf2_add(uint32_t a, uint32_t b) { uint32_t r; asm("add.rn.bf16x2 %0, %1, %2;" : "=r"(r) : "r"(a), "r"(b)); return r; }
__device__ __forceinline__ uint32_t bf2_sub(uint32_t a, uint32_t b) { uint32_t r; asm("sub.rn.bf16x2 %0, %1, %2;" : "=r"(r) : "r"(a), "r"(b)); return r; }
__device__ __forceinline__ void wait_cnt(const unsigned* p, unsigned target) {
    unsigned it = 0;
    while ((int)(ld_acq(p) - target) < 0 && ++it < SPIN_LIMIT) __nanosleep(64);
}
__device__ __forceinline__ uint32_t gtime32() { uint32_t t; asm volatile("mov.u32 %0, %%globaltimer_lo;" : "=r"(t) :: "memory"); return t; }
__device__ __forceinline__ void gate(uint32_t tick_addr, uint32_t ga = GATE_A, uint32_t gb = GATE_B) {
    uint32_t t1, p;
    asm volatile("ld.volatile.shared.v2.u32 {%0,%1}, [%2];" : "=r"(t1), "=r"(p) : "r"(tick_addr) : "memory");
    uint32_t d = gtime32() - t1;
    if (d < 4u * p) {
        d -= d >= 2u * p ? 2u * p : 0u;
        d -= d >= p ? p : 0u;
        if (d + ga >= p && d + gb < p) {
            const uint32_t t2 = gtime32() + (p - gb - d);
            while ((int)(gtime32() - t2) < 0) {}
        }
    }
}

__device__ __forceinline__ void read_tick(uint32_t tick_addr) {
    const uint2 tk = ld_vol_u2(&g_tick);
    uint32_t p = tk.x - tk.y;
    p = p > GATE_P + 100u ? GATE_P + 100u : p;
    asm volatile("st.volatile.shared.v2.u32 [%0], {%1,%2};" :: "r"(tick_addr), "r"(tk.x), "r"(p) : "memory");
}

__device__ __forceinline__ void s4d_phase(unsigned char* smem_raw, const bf16* __restrict__ x, const bf16* __restrict__ logA,
                                          const bf16* __restrict__ Aim, const bf16* __restrict__ Cre, const bf16* __restrict__ Cim,
                                          const bf16* __restrict__ logdt, const bf16* __restrict__ dskip, const bf16* __restrict__ wslice) {
    const int tid = threadIdx.x, warp = __shfl_sync(0xffffffffu, tid >> 5, 0), lane = tid & 31;
    const int d0 = blockIdx.x * SD_CH;
    float* tab = reinterpret_cast<float*>(smem_raw + SD_CH * SD_U + warp * SD_WSTR);
    const uint32_t wb = smem_u32(tab);
    const int g = lane >> 2, tq = lane & 3;
    uint2 prm[4];
    float ldt;
    auto load_prm = [&](int d) {
        prm[0] = __ldg(reinterpret_cast<const uint2*>(logA + d * NST) + lane); prm[1] = __ldg(reinterpret_cast<const uint2*>(Aim + d * NST) + lane);
        prm[2] = __ldg(reinterpret_cast<const uint2*>(Cre + d * NST) + lane); prm[3] = __ldg(reinterpret_cast<const uint2*>(Cim + d * NST) + lane);
        ldt = __bfloat162float(logdt[d]);
    };
    load_prm(d0 + warp);
    for (int i = lane; i < 2 * SD_CPY / 16; i += 32) reinterpret_cast<uint4*>(tab + SD_TAP / 4)[i] = make_uint4(0u, 0u, 0u, 0u);
    TS3(20);
#pragma unroll 1
    for (int ch = 0; ch < 2; ch++) {
        const int d = d0 + 8 * ch + warp;
        const uint32_t ub = smem_u32(smem_raw) + (8 * ch + warp) * SD_U;
        float k2048 = 0.f, sinv;
        {
            const float dt = bf16r(expf(ldt));
            uint32_t cm = __vmaxu2(__vmaxu2(prm[2].x & 0x7fff7fffu, prm[2].y & 0x7fff7fffu), __vmaxu2(prm[3].x & 0x7fff7fffu, prm[3].y & 0x7fff7fffu));
            cm = __reduce_max_sync(0xffffffffu, max(cm << 16, cm & 0xffff0000u));
            int e = 134 - (int)(__float_as_uint(__uint_as_float(cm) * dt) >> 23);
            e = e > 100 ? 100 : (e < -100 ? -100 : e);
            const float s2 = __uint_as_float((uint32_t)(128 + e) << 23);
            sinv = __uint_as_float((uint32_t)(127 - e) << 23);
#pragma unroll
            for (int j = 0; j < 4; j++) {
                float q[4];
#pragma unroll
                for (int i = 0; i < 4; i++) { const uint32_t w = j < 2 ? prm[i].x : prm[i].y; q[i] = __uint_as_float((j & 1) ? w & 0xffff0000u : w << 16); }
                const float zl = -bf16r(expf(q[0])) * dt * 1.4426950408889634f;
                const float zt = q[1] * dt * 0.15915494309189535f;
                const float cr = s2 * (q[2] * dt), ci = s2 * (q[3] * dt);
                float ar, ai, br, bi, er, ei;
                cexp_t(zl * 8.f, zt * 8.f, ar, ai);
                cexp_t(zl * 128.f, zt * 128.f, br, bi);
                cexp_t(zl * 2048.f, zt * 2048.f, er, ei);
                k2048 += cr * er - ci * ei;
                *reinterpret_cast<float4*>(tab + (lane + 32 * j) * 8) = make_float4(zl, zt, cr, ci);
                *reinterpret_cast<float4*>(tab + (lane + 32 * j) * 8 + 4) = make_float4(ar, ai, br, bi);
            }
#pragma unroll
            for (int o = 16; o; o >>= 1) k2048 += __shfl_xor_sync(0xffffffffu, k2048, o);
        }
        __syncwarp();
        {
            float kc[5][4];
#pragma unroll
            for (int i = 0; i < 5; i++) { kc[i][0] = kc[i][1] = kc[i][2] = kc[i][3] = 0.f; }
            const float gf = (float)g;
#pragma unroll 2
            for (int ks = 0; ks < 16; ks++) {
                uint32_t a0[4][2], a1[4][2], b0[5], b1[5];
                kb_state(tab + (8 * ks + tq) * 8, gf, a0, b0);
                kb_state(tab + (8 * ks + 4 + tq) * 8, gf, a1, b1);
#pragma unroll
                for (int i = 0; i < 5; i++) {
                    const int c = i > 0 ? i - 1 : 0;
                    asm volatile("mma.sync.aligned.m16n8k16.row.col.f32.f16.f16.f32 {%0,%1,%2,%3}, {%4,%5,%6,%7}, {%8,%9}, {%0,%1,%2,%3};"
                                 : "+f"(kc[i][0]), "+f"(kc[i][1]), "+f"(kc[i][2]), "+f"(kc[i][3])
                                 : "r"(a0[c][0]), "r"(a0[c][1]), "r"(a1[c][0]), "r"(a1[c][1]), "r"(b0[i]), "r"(b1[i]));
                }
            }
            const uint32_t tp = wb + SD_TAP;
            const uint32_t a0 = tp + 2 * (O_U + 96 * g - 4 * tq);
            const uint32_t a2 = tp + 2 * (((g & 1) ? O_U + 96 * (2 * (g & 3)) : ((g & 2) ? O_W35 : O_W79 + 1)) - 32 - 8 * tq - (g >> 2));
            const uint32_t a3 = tp + 2 * (((g & 1) ? O_W35 : O_W610 + 1) - 64 - 16 * tq - (g >> 1));
            const uint32_t a4 = tp + 2 * (-128 - 32 * tq - g);
#pragma unroll
            for (int c = 0; c < 4; c++) {
                const int e = (c & 1) * 16 + (c >> 1) * 8;
                const bool first = c == 0 && lane == 0;
                put_tap(a0 - e / 4, kc[0][c] * sinv);
                put_tap(a0 - 32 - e / 4, kc[1][c] * sinv);
                put_tap(first ? tp + 2 * (O_U - 32) : a2 - e / 2, kc[2][c] * sinv);
                put_tap(first ? tp + 2 * (O_W79 - 63) : a3 - e, kc[3][c] * sinv);
                put_tap(first ? tp + 2 * (O_W610 - 127) : a4 + 2 * (O_W511 + 1 - e), kc[4][c] * sinv);
                if ((g & 1) == 0) {
                    put_tap(a4 + 2 * (O_U4 - e), kc[4][c] * sinv);
                    put_tap(first ? tp + 2 * (O_U3 - 128) : a4 + 2 * (O_U4 + 1 - e), kc[4][c] * sinv);
                }
            }
            if (lane == 0) {
                put_tap(tp + 2 * (O_U + 96 - 32), kc[2][0] * sinv);
                put_tap(tp + 2 * (O_U + 192 - 64), kc[3][0] * sinv);
                put_tap(tp + 2 * (O_W511 - 255), k2048 * sinv);
                put_tap(tp + 2 * (O_U4 - 255), k2048 * sinv);
            }
        }
        TS3(21 + 2 * ch);
        if (ch == 0) named_bar(1, 384);
        else {
#pragma unroll
            for (int i = 0; i < 4; i++) asm volatile("prefetch.global.L2 [%0];" :: "l"(wslice + (size_t)((tid & 127) + 128 * i) * DM));
        }
        __syncwarp();
        if (tid == 0) TSS(18, 4 * ch);
        const uint32_t sh = wb + 80 + 11 * SD_ROW;
#pragma unroll
        for (int p = 0; p < 8; p++) {
            uint4 v;
            asm volatile("ld.shared.v4.u32 {%0,%1,%2,%3}, [%4];" : "=r"(v.x), "=r"(v.y), "=r"(v.z), "=r"(v.w) : "r"(ub + p * SD_ROW + lane * 16) : "memory");
            uint32_t pv = __shfl_up_sync(0xffffffffu, v.w, 1);
            pv = lane == 0 ? 0u : pv;
            asm volatile("st.shared.v4.u32 [%0], {%1,%2,%3,%4};" :: "r"(sh + (p - 8) * SD_ROW + lane * 16), "r"(__byte_perm(pv, v.x, 0x5432)), "r"(__byte_perm(v.x, v.y, 0x5432)),
                         "r"(__byte_perm(v.y, v.z, 0x5432)), "r"(__byte_perm(v.z, v.w, 0x5432)) : "memory");
            if (p >= 5) asm volatile("st.shared.v4.u32 [%0], {%1,%2,%3,%4};" :: "r"(sh + (p - 16) * SD_ROW + lane * 16), "r"(pv), "r"(v.x), "r"(v.y), "r"(v.z) : "memory");
        }
        __syncwarp();
        if (tid == 0) TSS(18, 4 * ch + 1);
        float acc[16][4];
#pragma unroll
        for (int i = 0; i < 16; i++) { acc[i][0] = acc[i][1] = acc[i][2] = acc[i][3] = 0.f; }
        {
            const uint32_t ka = wb + SD_TAP + ((g & 1) ? 0 : SD_CPY - 2) + 2 * (2 * tq - g);
            uint32_t b[16][2], b2[14][2];
#pragma unroll
            for (int k = 0; k < 16; k++) { b[k][0] = b[k][1] = 0u; if (k < 14) b2[k][0] = b2[k][1] = 0u; }
#pragma unroll 1
            for (int ps = 0; ps < 14; ps++) {
                const uint32_t pw = __shfl_sync(0xffffffffu, SD_PASS[ps], 0), type = pw & 3u, kp = ka + (pw >> 16);
                const int dl = (pw >> 2) & 7, d0 = (pw >> 8) & 15, d1 = (pw >> 12) & 15;
                uint32_t t[2][4];
                tap_tile(t[0], kp - 32 * d0);
                if (type == 0) {
                    const int p = (lane & 7) - dl;
                    const uint32_t ra = (p < 0 ? sh : ub) + p * SD_ROW + (lane >> 3) * 16;
#pragma unroll
                    for (int k = 0; k < 8; k++)
                        asm volatile("ldmatrix.sync.aligned.m8n8.x4.shared.b16 {%0,%1,%2,%3}, [%4];"
                                     : "=r"(b[2 * k][0]), "=r"(b[2 * k][1]), "=r"(b[2 * k + 1][0]), "=r"(b[2 * k + 1][1]) : "r"(ra + k * 64));
                } else if (type == 2) {
                    const int p = (lane & 15) - 11, xo = 2 * tq - g;
                    const uint32_t qa = (p < 0 ? sh : ub) + p * SD_ROW + (lane >> 4) * 16;
                    const int lx = 6 - 5 * dl, hx = 8 - 3 * dl, ly = 2 - 2 * dl, hy = 4 + 2 * dl;
                    const uint32_t sel[4] = {band2(xo, lx, hx), band2(xo, ly, hy), band2(xo + 8, lx, hx), band2(xo + 8, ly, hy)};
#pragma unroll
                    for (int k = 0; k < 14; k++) {
                        uint32_t q[4];
                        ldsm_x4_t(q, qa + k * 32);
#pragma unroll
                        for (int i = 0; i < 2; i++) {
                            float w[4];
                            mma_z(w, sel, q[2 * i], q[2 * i + 1]);
                            b[k][i] = pack_bf16(w[0], w[1]);
                            b2[k][i] = pack_bf16(w[2], w[3]);
                        }
                    }
                } else if (type == 3) {
#pragma unroll
                    for (int k = 0; k < 14; k++) { b[k][0] = b2[k][0]; b[k][1] = b2[k][1]; }
                }
#pragma unroll
                for (int d = 0; d < 16; d += 2) {
                    if (d >= 8 || d >= d0) {
                        tap_tile(t[1], kp - 32 * (d + 1));
#pragma unroll
                        for (int k = 0; k + d < 16; k++) mma_bf16(acc[k + d], t[0], b[k][0], b[k][1]);
                        if ((d == 2 || d == 4 || d == 8) && d == d1) break;
                        if (d < 14) tap_tile(t[0], kp - 32 * (d + 2));
#pragma unroll
                        for (int k = 0; k + d + 1 < 16; k++) mma_bf16(acc[k + d + 1], t[1], b[k][0], b[k][1]);
                    }
                }
            }
        }
        __syncwarp();
        if (tid == 0) TSS(18, 4 * ch + 2);
        load_prm(d0 + 8 + warp);
        if (ch == 0) {
            if (lane == 0) {
                unsigned ep;
                asm volatile("ld.volatile.global.u32 %0, [%1];" : "=r"(ep) : "l"(&g_epoch) : "memory");
                wait_cnt(&g_gcnt[0], SD_NCTA * (ep + 1u));
            }
            __syncwarp();
        }
        if (tid == 0) TSS(18, 4 * ch + 3);
        uint4 gv[8];
#pragma unroll
        for (int i = 0; i < 8; i++) gv[i] = __ldcg(reinterpret_cast<const uint4*>(g_gate) + lane + 32 * i);
        const uint32_t dd = __byte_perm(*reinterpret_cast<const unsigned short*>(dskip + d), 0u, 0x1010);
#pragma unroll
        for (int i = 0; i < 8; i++) {
            uint32_t u[4];
            ldsm_x4_t(u, ub + (lane & 7) * SD_ROW + (lane >> 3) * 16 + i * 64);
            asm volatile("stmatrix.sync.aligned.m8n8.x4.shared.b16 [%0], {%1,%2,%3,%4};"
                         :: "r"(wb + (lane + 32 * i) * 16),
                            "r"(bf2_add(pack_bf16(acc[2 * i][0], acc[2 * i][1]), bf2_mul(u[0], dd))), "r"(bf2_add(pack_bf16(acc[2 * i][2], acc[2 * i][3]), bf2_mul(u[1], dd))),
                            "r"(bf2_add(pack_bf16(acc[2 * i + 1][0], acc[2 * i + 1][1]), bf2_mul(u[2], dd))), "r"(bf2_add(pack_bf16(acc[2 * i + 1][2], acc[2 * i + 1][3]), bf2_mul(u[3], dd))) : "memory");
        }
        __syncwarp();
#pragma unroll
        for (int i = 0; i < 8; i++) {
            const uint4 y = *reinterpret_cast<const uint4*>(tab + (lane + 32 * i) * 4);
            *reinterpret_cast<uint4*>(g_y + (((lane >> 1) + 16 * i) * DM + d) * 16 + (lane & 1) * 8) =
                make_uint4(bf2_mul(bf2_sub(0x3f803f80u, gv[i].x), y.x), bf2_mul(bf2_sub(0x3f803f80u, gv[i].y), y.y),
                           bf2_mul(bf2_sub(0x3f803f80u, gv[i].z), y.z), bf2_mul(bf2_sub(0x3f803f80u, gv[i].w), y.w));
        }
        __syncwarp();
        if (ch == 0) asm volatile("bar.arrive 11, 288;" ::: "memory");
        TS3(22 + 2 * ch);
    }
}
__device__ __forceinline__ void s4d_stage_u(unsigned char* smem_raw, const bf16* __restrict__ x, int pt) {
    const int p = pt & 7, w0 = pt >> 3;
    const uint4* src = reinterpret_cast<const uint4*>(x + (size_t)(16 * w0 + p) * DM + blockIdx.x * SD_CH);
    uint32_t* dst = reinterpret_cast<uint32_t*>(smem_raw + p * SD_ROW) + w0;
#pragma unroll 1
    for (int b = 0; b < 4; b++) {
        uint4 v[2][2][2];
#pragma unroll
        for (int i = 0; i < 8; i++) v[i >> 2][(i >> 1) & 1][i & 1] = src[((b * 2 + (i >> 2)) * 256 + ((i >> 1) & 1) * 8) * (DM / 8) + (i & 1)];
#pragma unroll
        for (int i = 0; i < 4; i++) {
            const uint32_t* lo = reinterpret_cast<const uint32_t*>(&v[i >> 1][0][i & 1]);
            const uint32_t* hi = reinterpret_cast<const uint32_t*>(&v[i >> 1][1][i & 1]);
#pragma unroll
            for (int c = 0; c < 8; c++) dst[((i & 1) * 8 + c) * (SD_U / 4) + (b * 2 + (i >> 1)) * 16] = __byte_perm(lo[c >> 1], hi[c >> 1], (c & 1) ? 0x7632 : 0x5410);
        }
    }
    asm volatile("bar.arrive 1, 384;" ::: "memory");
}

constexpr int WOC = DM / 3;
constexpr int TBUF = 5 * DH * 16;
constexpr int XBUF = SEG * DM * 2;
constexpr int SM_BAR = 0;
constexpr int B_SB = 0, B_VX = 16, B_XT = 32, B_XF = 144, B_W = 64, B_E = 136;
constexpr int SM_SC = 256;
constexpr int SM_F = SM_SC + 1280;
constexpr int SM_VM = SM_F + 2048;
constexpr int SM_S = SM_VM + 2048;
constexpr int SM_O = SM_S + 2560;
constexpr int SM_M = SM_O + 2048;
constexpr int SM_WS = 19456;
constexpr int SM_T = SM_WS + 49152;
constexpr int SM_VX = SM_T + 4 * TBUF;
constexpr int SM_X = SM_VX + 2 * 8192;
constexpr int SM_X01 = SM_WS + DM * DH * 2;
__host__ __device__ constexpr int x01_off(int b) { return b < 2 ? 1024 + b * 9216 : SM_X01 + (b == 2 ? 6 : b - 3) * 9216; }
__host__ __device__ constexpr int x23_off(int b) { return b < 3 ? SM_WS + 7 * 16384 + b * 8192 : x01_off(b - 3); }
constexpr int CH_SMEM = SM_X01 + 8 * 8192;
static_assert(SM_M + DM * 16 <= SM_WS && SM_X + 13 * 8192 <= CH_SMEM && NS <= 10 && CH_SMEM <= 232448 && SM_X % 1024 == 0 && SM_X01 % 1024 == 0 && 1024 + 2 * 9216 <= SM_WS, "smem");
__device__ __forceinline__ uint32_t clock32() { uint32_t t; asm volatile("mov.u32 %0, %%clock;" : "=r"(t) :: "memory"); return t; }

__device__ __forceinline__ uint32_t mapa(uint32_t a, uint32_t rank) {
    uint32_t r; asm volatile("mapa.shared::cluster.u32 %0, %1, %2;" : "=r"(r) : "r"(a), "r"(rank)); return r;
}
__device__ __forceinline__ void st_async32(uint32_t addr, uint32_t v, uint32_t mbar) {
    asm volatile("st.async.weak.shared::cluster.mbarrier::complete_tx::bytes.b32 [%0], %1, [%2];" :: "r"(addr), "r"(v), "r"(mbar) : "memory");
}
__device__ __forceinline__ void mbar_init(uint32_t bar, uint32_t cnt) {
    asm volatile("mbarrier.init.shared::cta.b64 [%0], %1;" :: "r"(bar), "r"(cnt) : "memory");
}
__device__ __forceinline__ void mbar_expect(uint32_t bar, uint32_t bytes) {
    asm volatile("mbarrier.arrive.expect_tx.shared::cta.b64 _, [%0], %1;" :: "r"(bar), "r"(bytes) : "memory");
}
__device__ __forceinline__ void mbar_wait(uint32_t bar, uint32_t parity) {
    unsigned it = 0;
    uint32_t ok;
    do {
        ++it;
        asm volatile("{\n.reg .pred p;\nmbarrier.try_wait.parity.shared::cta.b64 p, [%1], %2;\nselp.u32 %0, 1, 0, p;\n}" : "=r"(ok) : "r"(bar), "r"(parity) : "memory");
    } while ((ok == 0u) & (it < SPIN_LIMIT));
}
__device__ __forceinline__ void mbar_wait_long(uint32_t bar, uint32_t parity) {
    unsigned it = 0;
    while (true) {
        uint32_t ok;
        asm volatile("{\n.reg .pred p;\nmbarrier.try_wait.parity.shared::cta.b64 p, [%1], %2, %3;\nselp.u32 %0, 1, 0, p;\n}"
                     : "=r"(ok) : "r"(bar), "r"(parity), "r"(20000u) : "memory");
        if (ok || ++it >= SPIN_LIMIT) break;
    }
}
__device__ __forceinline__ bool mbar_test(uint32_t bar, uint32_t parity) {
    uint32_t ok;
    asm volatile("{\n.reg .pred p;\nmbarrier.test_wait.parity.shared::cta.b64 p, [%1], %2;\nselp.u32 %0, 1, 0, p;\n}" : "=r"(ok) : "r"(bar), "r"(parity) : "memory");
    return ok != 0u;
}
__device__ __forceinline__ uint64_t policy_evict_first() {
    uint64_t pol; asm volatile("createpolicy.fractional.L2::evict_first.b64 %0, 1.0;" : "=l"(pol)); return pol;
}
__device__ __forceinline__ void cluster_sync_all() {
    asm volatile("barrier.cluster.arrive.release.aligned;\nbarrier.cluster.wait.acquire.aligned;" ::: "memory");
}
__device__ __forceinline__ uint4 ld_vol_u4(const uint4* p) {
    uint4 v; asm volatile(LDV4 : "=r"(v.x), "=r"(v.y), "=r"(v.z), "=r"(v.w) : "l"(p) : "memory"); return v;
}
__device__ __forceinline__ void ld_vol_u4_p(uint4& v, const uint4* p, uint32_t pred) {
    asm volatile("{\n.reg .pred p;\nsetp.ne.u32 p, %5, 0;\n@p " LDV4 "\n}"
                 : "+r"(v.x), "+r"(v.y), "+r"(v.z), "+r"(v.w) : "l"(p), "r"(pred) : "memory");
}
__device__ __forceinline__ void st_vol_u4(uint4* p, uint4 v) {
    asm volatile(STV4 :: "l"(p), "r"(v.x), "r"(v.y), "r"(v.z), "r"(v.w) : "memory");
}
__device__ __forceinline__ void mma_bf16_r(float (&d)[4], uint32_t a0, uint32_t a1, uint32_t a2, uint32_t a3, uint32_t b0, uint32_t b1) {
    asm volatile("mma.sync.aligned.m16n8k16.row.col.f32.bf16.bf16.f32 {%0,%1,%2,%3}, {%4,%5,%6,%7}, {%8,%9}, {%0,%1,%2,%3};"
                 : "+f"(d[0]), "+f"(d[1]), "+f"(d[2]), "+f"(d[3])
                 : "r"(a0), "r"(a1), "r"(a2), "r"(a3), "r"(b0), "r"(b1));
}

__device__ __forceinline__ uint64_t smem_desc(uint32_t addr, uint32_t lbo, uint32_t sbo) {
    return (uint64_t)((addr & 0x3FFFF) >> 4) | ((uint64_t)(lbo >> 4) << 16) | ((uint64_t)(sbo >> 4) << 32);
}
__device__ __forceinline__ void wg_fence() { asm volatile("wgmma.fence.sync.aligned;" ::: "memory"); }
__device__ __forceinline__ void wg_commit() { asm volatile("wgmma.commit_group.sync.aligned;" ::: "memory"); }
__device__ __forceinline__ void wg_wait0() { asm volatile("wgmma.wait_group.sync.aligned 0;" ::: "memory"); }
__device__ __forceinline__ void fence_async() { asm volatile("fence.proxy.async.shared::cta;" ::: "memory"); }
__device__ __forceinline__ void wgmma_n64_ss(float (&d)[32], uint64_t adesc, uint64_t bdesc) {
    asm volatile("{\n.reg .pred p;\nsetp.eq.b32 p, 0, 0;\n"
                 "wgmma.mma_async.sync.aligned.m64n64k16.f32.bf16.bf16 {%0,%1,%2,%3,%4,%5,%6,%7,%8,%9,%10,%11,%12,%13,%14,%15,%16,%17,%18,%19,%20,%21,%22,%23,%24,%25,%26,%27,%28,%29,%30,%31}, %32, %33, p, 1, 1, 1, 0;\n}"
                 : "+f"(d[0]), "+f"(d[1]), "+f"(d[2]), "+f"(d[3]), "+f"(d[4]), "+f"(d[5]), "+f"(d[6]), "+f"(d[7]), "+f"(d[8]), "+f"(d[9]), "+f"(d[10]), "+f"(d[11]), "+f"(d[12]), "+f"(d[13]), "+f"(d[14]), "+f"(d[15]), "+f"(d[16]), "+f"(d[17]), "+f"(d[18]), "+f"(d[19]), "+f"(d[20]), "+f"(d[21]), "+f"(d[22]), "+f"(d[23]), "+f"(d[24]), "+f"(d[25]), "+f"(d[26]), "+f"(d[27]), "+f"(d[28]), "+f"(d[29]), "+f"(d[30]), "+f"(d[31])
                 : "l"(adesc), "l"(bdesc));
}
__device__ __forceinline__ void wgmma_n72_ss(float (&d)[36], uint64_t adesc, uint64_t bdesc) {
    asm volatile("{\n.reg .pred p;\nsetp.eq.b32 p, 0, 0;\n"
                 "wgmma.mma_async.sync.aligned.m64n72k16.f32.bf16.bf16 {%0,%1,%2,%3,%4,%5,%6,%7,%8,%9,%10,%11,%12,%13,%14,%15,%16,%17,%18,%19,%20,%21,%22,%23,%24,%25,%26,%27,%28,%29,%30,%31,%32,%33,%34,%35}, %36, %37, p, 1, 1, 1, 0;\n}"
                 : "+f"(d[0]), "+f"(d[1]), "+f"(d[2]), "+f"(d[3]), "+f"(d[4]), "+f"(d[5]), "+f"(d[6]), "+f"(d[7]), "+f"(d[8]), "+f"(d[9]), "+f"(d[10]), "+f"(d[11]), "+f"(d[12]), "+f"(d[13]), "+f"(d[14]), "+f"(d[15]), "+f"(d[16]), "+f"(d[17]), "+f"(d[18]), "+f"(d[19]), "+f"(d[20]), "+f"(d[21]), "+f"(d[22]), "+f"(d[23]), "+f"(d[24]), "+f"(d[25]), "+f"(d[26]), "+f"(d[27]), "+f"(d[28]), "+f"(d[29]), "+f"(d[30]), "+f"(d[31]), "+f"(d[32]), "+f"(d[33]), "+f"(d[34]), "+f"(d[35])
                 : "l"(adesc), "l"(bdesc));
}
__device__ __forceinline__ void tma_2d(uint32_t dst, const CUtensorMap* tm, int c0, int c1, uint32_t mbar) {
    asm volatile("cp.async.bulk.tensor.2d.shared::cluster.global.tile.mbarrier::complete_tx::bytes [%0], [%1, {%2, %3}], [%4];"
                 :: "r"(dst), "l"(tm), "r"(c0), "r"(c1), "r"(mbar) : "memory");
}

__device__ __forceinline__ void bulk_g2s(uint32_t dst, const void* src, uint32_t bytes, uint32_t mbar) {
    asm volatile("cp.async.bulk.shared::cluster.global.mbarrier::complete_tx::bytes [%0], [%1], %2, [%3];"
                 :: "r"(dst), "l"(src), "r"(bytes), "r"(mbar) : "memory");
}
__device__ __forceinline__ void bulk_g2s_h(uint32_t dst, const void* src, uint32_t bytes, uint32_t mbar, uint64_t pol) {
    asm volatile("cp.async.bulk.shared::cluster.global.mbarrier::complete_tx::bytes.L2::cache_hint [%0], [%1], %2, [%3], %4;"
                 :: "r"(dst), "l"(src), "r"(bytes), "r"(mbar), "l"(pol) : "memory");
}
__device__ __forceinline__ void tma_2d_mc(uint32_t dst, const CUtensorMap* tm, int c0, int c1, uint32_t mbar) {
    asm volatile("cp.async.bulk.tensor.2d.shared::cluster.global.tile.mbarrier::complete_tx::bytes.multicast::cluster [%0], [%1, {%2, %3}], [%4], %5;"
                 :: "r"(dst), "l"(tm), "r"(c0), "r"(c1), "r"(mbar), "h"((unsigned short)7) : "memory");
}
__device__ __forceinline__ void bulk_s2s(uint32_t dst, uint32_t src, uint32_t bytes, uint32_t mbar) {
    asm volatile("cp.async.bulk.shared::cluster.shared::cta.mbarrier::complete_tx::bytes [%0], [%1], %2, [%3];"
                 :: "r"(dst), "r"(src), "r"(bytes), "r"(mbar) : "memory");
}
__device__ __forceinline__ void wgmma_n40_ss(float (&d)[20], uint64_t adesc, uint64_t bdesc, int scale_d) {
    asm volatile("{\n.reg .pred p;\nsetp.ne.b32 p, %22, 0;\n"
                 "wgmma.mma_async.sync.aligned.m64n40k16.f32.bf16.bf16 {%0,%1,%2,%3,%4,%5,%6,%7,%8,%9,%10,%11,%12,%13,%14,%15,%16,%17,%18,%19}, %20, %21, p, 1, 1, 1, 1;\n}"
                 : "+f"(d[0]), "+f"(d[1]), "+f"(d[2]), "+f"(d[3]), "+f"(d[4]), "+f"(d[5]), "+f"(d[6]), "+f"(d[7]),
                   "+f"(d[8]), "+f"(d[9]), "+f"(d[10]), "+f"(d[11]), "+f"(d[12]), "+f"(d[13]), "+f"(d[14]), "+f"(d[15]),
                   "+f"(d[16]), "+f"(d[17]), "+f"(d[18]), "+f"(d[19])
                 : "l"(adesc), "l"(bdesc), "r"(scale_d));
}
__device__ __forceinline__ void wgmma_n64_z(float (&d)[32], const uint32_t (&a)[4], uint64_t bdesc) {
    asm volatile("{\n.reg .pred p;\nsetp.ne.b32 p, 0, 0;\n"
                 "wgmma.mma_async.sync.aligned.m64n64k16.f32.bf16.bf16 {%0,%1,%2,%3,%4,%5,%6,%7,%8,%9,%10,%11,%12,%13,%14,%15,%16,%17,%18,%19,%20,%21,%22,%23,%24,%25,%26,%27,%28,%29,%30,%31}, {%32,%33,%34,%35}, %36, p, 1, 1, 0;\n}"
                 : "=f"(d[0]), "=f"(d[1]), "=f"(d[2]), "=f"(d[3]), "=f"(d[4]), "=f"(d[5]), "=f"(d[6]), "=f"(d[7]),
                   "=f"(d[8]), "=f"(d[9]), "=f"(d[10]), "=f"(d[11]), "=f"(d[12]), "=f"(d[13]), "=f"(d[14]), "=f"(d[15]),
                   "=f"(d[16]), "=f"(d[17]), "=f"(d[18]), "=f"(d[19]), "=f"(d[20]), "=f"(d[21]), "=f"(d[22]), "=f"(d[23]),
                   "=f"(d[24]), "=f"(d[25]), "=f"(d[26]), "=f"(d[27]), "=f"(d[28]), "=f"(d[29]), "=f"(d[30]), "=f"(d[31])
                 : "r"(a[0]), "r"(a[1]), "r"(a[2]), "r"(a[3]), "l"(bdesc));
}
__device__ __forceinline__ void wgmma_n64(float (&d)[32], const uint32_t (&a)[4], uint64_t bdesc, int scale_d) {
    asm volatile("{\n.reg .pred p;\nsetp.ne.b32 p, %37, 0;\n"
                 "wgmma.mma_async.sync.aligned.m64n64k16.f32.bf16.bf16 {%0,%1,%2,%3,%4,%5,%6,%7,%8,%9,%10,%11,%12,%13,%14,%15,%16,%17,%18,%19,%20,%21,%22,%23,%24,%25,%26,%27,%28,%29,%30,%31}, {%32,%33,%34,%35}, %36, p, 1, 1, 0;\n}"
                 : "+f"(d[0]), "+f"(d[1]), "+f"(d[2]), "+f"(d[3]), "+f"(d[4]), "+f"(d[5]), "+f"(d[6]), "+f"(d[7]),
                   "+f"(d[8]), "+f"(d[9]), "+f"(d[10]), "+f"(d[11]), "+f"(d[12]), "+f"(d[13]), "+f"(d[14]), "+f"(d[15]),
                   "+f"(d[16]), "+f"(d[17]), "+f"(d[18]), "+f"(d[19]), "+f"(d[20]), "+f"(d[21]), "+f"(d[22]), "+f"(d[23]),
                   "+f"(d[24]), "+f"(d[25]), "+f"(d[26]), "+f"(d[27]), "+f"(d[28]), "+f"(d[29]), "+f"(d[30]), "+f"(d[31])
                 : "r"(a[0]), "r"(a[1]), "r"(a[2]), "r"(a[3]), "l"(bdesc), "r"(scale_d));
}

constexpr int SB_FULL = 0, SB_EMPTY = 64, SB_QKF = 128, SB_VF = 144, SB_QKE = 160, SB_VE = 176, SB_OF = 192, SB_WO = 208  , SB_TICK = 216, SB_SEEN = 224, SB_FI = 232, SB_REQ = 240;
constexpr int AT_0 = 256, AT_ST = 10240 + 2 * 9216;
constexpr int FS_A = 58368;
constexpr int FS_P = FS_A + 131072;
constexpr int FS_I = FS_P + 16384;
constexpr int FS_O = FS_I + 12288;
constexpr int FS_Z = FS_O + 12288, FS_G = AT_0 + 2 * AT_ST;
constexpr int SIDE_SMEM = FS_Z + 2048;
static_assert(SIDE_SMEM <= 232448 && FS_G + 128 <= FS_A && FS_A + SD_SMEM <= SIDE_SMEM, "smem");

__device__ __forceinline__ void wg_wait1() { asm volatile("wgmma.wait_group.sync.aligned 1;" ::: "memory"); }
__device__ __forceinline__ void mbar_arrive(uint32_t bar) { asm volatile("mbarrier.arrive.shared::cta.b64 _, [%0];" :: "r"(bar) : "memory"); }
__device__ __forceinline__ void wait_cnt_rlx(const unsigned* p, unsigned target, bool urgent) {
    unsigned it = 0, v;
    while (true) {
        asm volatile("ld.relaxed.gpu.global.u32 %0, [%1];" : "=r"(v) : "l"(p) : "memory");
        if ((int)(v - target) >= 0 || ++it >= SPIN_LIMIT) break;
        if (!urgent) __nanosleep(PRG_SLEEP);
    }
}

__device__ __forceinline__ float xrow_softmax(float (&sc)[20], uint32_t (&p)[5], int wq, int lane) {
    constexpr float EC = (float)(1.4426950408889634 * 0.08838834764831845);
    const int lim = 8 * wq + (lane >> 2) - 2 * (lane & 3);
    float mx = fmaxf(sc[0], sc[1]);
#pragma unroll
    for (int j = 1; j < 5; j++) {
        sc[4 * j] = 8 * j - 8 > lim ? -INFINITY : sc[4 * j];
        sc[4 * j + 1] = 8 * j - 7 > lim ? -INFINITY : sc[4 * j + 1];
    }
    mx = fmaxf(fmaxf(mx, fmaxf(fmaxf(sc[4], sc[5]), fmaxf(sc[8], sc[9]))), fmaxf(fmaxf(sc[12], sc[13]), fmaxf(sc[16], sc[17])));
    {
        const float m1 = __shfl_xor_sync(0xffffffffu, mx, 1), m2 = __shfl_xor_sync(0xffffffffu, mx, 2), m3 = __shfl_xor_sync(0xffffffffu, mx, 3);
        mx = fmaxf(fmaxf(mx, m1), fmaxf(m2, m3));
    }
    float sum = 0.f;
#pragma unroll
    for (int j = 0; j < 5; j++) {
        float e0, e1;
        asm("ex2.approx.ftz.f32 %0, %1;" : "=f"(e0) : "f"((sc[4 * j] - mx) * EC));
        asm("ex2.approx.ftz.f32 %0, %1;" : "=f"(e1) : "f"((sc[4 * j + 1] - mx) * EC));
        p[j] = pack_bf16(e0, e1);
        sum += e0 + e1;
    }
    return sum;
}
__device__ __forceinline__ float xrow_inv(float sum) {
    sum += __shfl_xor_sync(0xffffffffu, sum, 1);
    sum += __shfl_xor_sync(0xffffffffu, sum, 2);
    float r;
    asm("rcp.approx.ftz.f32 %0, %1;" : "=f"(r) : "f"(sum));
    return r;
}

__device__ __forceinline__ void stsm_x4(uint32_t addr, uint32_t r0, uint32_t r1, uint32_t r2, uint32_t r3) {
    asm volatile("stmatrix.sync.aligned.m8n8.x4.shared.b16 [%0], {%1,%2,%3,%4};" :: "r"(addr), "r"(r0), "r"(r1), "r"(r2), "r"(r3) : "memory");
}
__device__ __forceinline__ void xrow_pv(uint32_t (&ob)[16], const uint32_t (&p)[5], float psum, uint32_t vt) {
    float o[32];
    const uint64_t dv = smem_desc(vt, 2048, 128);
    uint32_t pa[6][4];
#pragma unroll
    for (int i = 0; i < 6; i++) {
        const int ks = i >> 1, hf = i & 1;
        pa[i][hf] = p[2 * ks]; pa[i][hf ^ 1] = 0u;
        pa[i][2 + hf] = ks < 2 ? p[ks < 2 ? 2 * ks + 1 : 0] : 0u; pa[i][3 - hf] = 0u;
    }
    wg_fence();
#pragma unroll
    for (int i = 0; i < 6; i++) { if (i == 0) wgmma_n64_z(o, pa[0], dv); else wgmma_n64(o, pa[i], dv + (uint64_t)((i & 1) * 64 + (i >> 1) * 256), 1); }
    wg_commit();
    const float inv = xrow_inv(psum);
    wg_wait0();
#pragma unroll
    for (int i = 0; i < 8; i++) { ob[i] = pack_bf16(o[4 * i] * inv, o[4 * i + 1] * inv); ob[8 + i] = pack_bf16(o[4 * i + 2] * inv, o[4 * i + 3] * inv); }
}
__device__ __forceinline__ uint32_t h2_to_bf2(uint32_t h) {
    uint32_t r;
    asm("{\n.reg .f16 l, h;\n.reg .f32 a, b;\nmov.b32 {l, h}, %1;\ncvt.f32.f16 a, l;\ncvt.f32.f16 b, h;\ncvt.rn.bf16x2.f32 %0, b, a;\n}" : "=r"(r) : "r"(h));
    return r;
}
__device__ __forceinline__ uint32_t max_abs2(uint32_t a, uint32_t b) { uint32_t r; asm("max.NaN.xorsign.abs.bf16x2 %0, %1, %2;" : "=r"(r) : "r"(a), "r"(b)); return r; }
__device__ __forceinline__ uint32_t movm(uint32_t v) {
    uint32_t r; asm volatile("movmatrix.sync.aligned.m8n8.trans.b16 %0, %1;" : "=r"(r) : "r"(v)); return r;
}
__device__ __forceinline__ void bar_arrive(int id, int n) { asm volatile("bar.arrive %0, %1;" :: "r"(id), "r"(n) : "memory"); }
__device__ __forceinline__ void lds64(uint32_t& a, uint32_t& b, uint32_t addr) {
    asm volatile("ld.shared.v2.u32 {%0,%1}, [%2];" : "=r"(a), "=r"(b) : "r"(addr) : "memory");
}
__device__ __forceinline__ void lds64f(float& a, float& b, uint32_t addr) {
    asm volatile("ld.shared.v2.f32 {%0,%1}, [%2];" : "=f"(a), "=f"(b) : "r"(addr) : "memory");
}
__device__ __forceinline__ void st_async64(uint32_t addr, uint32_t a, uint32_t b, uint32_t mbar) {
    asm volatile("st.async.weak.shared::cluster.mbarrier::complete_tx::bytes.v2.b32 [%0], {%1,%2}, [%3];" :: "r"(addr), "r"(a), "r"(b), "r"(mbar) : "memory");
}
__device__ __forceinline__ void mma_z(float (&d)[4], const uint32_t (&a)[4], uint32_t b0, uint32_t b1) {
    asm volatile("mma.sync.aligned.m16n8k16.row.col.f32.bf16.bf16.f32 {%0,%1,%2,%3}, {%4,%5,%6,%7}, {%8,%9}, {%10,%10,%10,%10};"
                 : "=f"(d[0]), "=f"(d[1]), "=f"(d[2]), "=f"(d[3])
                 : "r"(a[0]), "r"(a[1]), "r"(a[2]), "r"(a[3]), "r"(b0), "r"(b1), "f"(0.f));
}
__device__ __forceinline__ void mma_k8(float (&d)[4], uint32_t a0, uint32_t a1, uint32_t b) {
    asm volatile("mma.sync.aligned.m16n8k8.row.col.f32.bf16.bf16.f32 {%0,%1,%2,%3}, {%4,%5}, {%6}, {%0,%1,%2,%3};"
                 : "+f"(d[0]), "+f"(d[1]), "+f"(d[2]), "+f"(d[3]) : "r"(a0), "r"(a1), "r"(b));
}
__global__ void __launch_bounds__(512, 1) k_side(const __grid_constant__ CUtensorMap tmo, const bf16* __restrict__ x, const bf16* __restrict__ logA, const bf16* __restrict__ Aim,
                                                 const bf16* __restrict__ Cre, const bf16* __restrict__ Cim, const bf16* __restrict__ logdt,
                                                 const bf16* __restrict__ Wo, const bf16* __restrict__ dskip, const bf16* __restrict__ gw,
                                                 bf16* __restrict__ out) {
    extern __shared__ __align__(1024) unsigned char smem_raw[];
    const uint32_t sbase = smem_u32(smem_raw);
    const int tid = threadIdx.x, warp = __shfl_sync(0xffffffffu, tid >> 5, 0), lane = tid & 31, cta = blockIdx.x;
    const int cb = cta >> 2, kq = cta & 3;
    if (tid == 0) {
        for (int i = 0; i < 8; i++) { mbar_init(sbase + SB_FULL + 8 * i, 1); mbar_init(sbase + SB_EMPTY + 8 * i, 4); }
        for (int i = 0; i < 2; i++) {
            mbar_init(sbase + SB_QKF + 8 * i, 1); mbar_init(sbase + SB_VF + 8 * i, 1); mbar_init(sbase + SB_QKE + 8 * i, 4);
            mbar_init(sbase + SB_VE + 8 * i, 1); mbar_init(sbase + SB_OF + 8 * i, 4);
        }
        mbar_init(sbase + SB_WO, 1);
        mbar_init(sbase + SB_WO + 40, 1);
        mbar_init(sbase + SB_FI, 1);
        mbar_init(sbase + SB_REQ, 4);
        *reinterpret_cast<uint2*>(smem_raw + SB_TICK) = make_uint2(0u, 0u);
        *reinterpret_cast<uint32_t*>(smem_raw + SB_SEEN) = 0u;
        asm volatile("fence.mbarrier_init.release.cluster;" ::: "memory");
    }
    TS3(0);
    asm volatile("fence.proxy.async;" ::: "memory");
    __syncthreads();
    auto epoch = []() {
        unsigned ep;
        asm volatile("ld.volatile.global.u32 %0, [%1];" : "=r"(ep) : "l"(&g_epoch) : "memory");
        return ep + 1u;
    };
    if (warp >= 12) {
      asm volatile("setmaxnreg.dec.sync.aligned.u32 40;");
      {
        uint32_t gwv[9];
#pragma unroll
        for (int i = 0; i < 9; i++) gwv[i] = reinterpret_cast<const uint32_t*>(gw)[lane + 32 * i];
#pragma unroll 1
        for (int i = 0; i < 8; i++) {
            uint32_t xv[2][9];
            float sm[2];
#pragma unroll
            for (int j = 0; j < 2; j++) {
                const int t = min(cta * 57 + 8 * i + 4 * j + warp - 12, S_LEN - 1);
#pragma unroll
                for (int k = 0; k < 9; k++) xv[j][k] = reinterpret_cast<const uint32_t*>(x + t * DM)[lane + 32 * k];
            }
#pragma unroll
            for (int j = 0; j < 2; j++) {
                sm[j] = 0.f;
#pragma unroll
                for (int k = 0; k < 9; k++) {
                    const uint32_t pr = bf2_mul(xv[j][k], gwv[k]);
                    sm[j] += __uint_as_float(pr << 16) + __uint_as_float(pr & 0xffff0000u);
                }
            }
            float v = (lane < 16 ? sm[0] : sm[1]) + __shfl_xor_sync(0xffffffffu, lane < 16 ? sm[1] : sm[0], 16);
#pragma unroll
            for (int o = 8; o; o >>= 1) v += __shfl_xor_sync(0xffffffffu, v, o);
            const float gv = 1.f / (1.f + expf(-bf16r(v)));
            const int tt = 8 * i + 4 * (lane >> 4) + warp - 12;
            if ((lane & 15) == 0 && tt < 57 && cta * 57 + tt < S_LEN) g_gate[cta * 57 + tt] = __float2bfloat16_rn(gv);
        }
        named_bar(2, 128);
        if (tid == 480) {
            __threadfence();
            asm volatile("red.relaxed.gpu.global.add.u32 [%0], 1;" :: "l"(&g_gcnt[0]) : "memory");
        }
        __syncwarp();
      }
      const unsigned ep = epoch();
      if (warp == 12 || warp == 15) {
        const int pi = warp == 12 ? 0 : 1;
        auto stage_wo = [&](int i0, int i1) {
            if (lane == 0) {
                fence_async();
#pragma unroll 1
                for (int i = i0; i < i1; i++) {
                    gate(sbase + SB_TICK);
                    tma_2d(sbase + FS_A + i * 16384, &tmo, cb * 64, kq * 1024 + i * 128, sbase + SB_WO + (i >> 2) * 40);
                    if (WO_SLEEP > 0) __nanosleep(WO_SLEEP);
                }
            }
            __syncwarp();
        };
        if (lane == 0) mbar_expect(sbase + SB_WO + pi * 40, 65536);
        if (pi == 0) {
            named_bar(11, 288);
            stage_wo(0, 2);
        }
        named_bar(3, 320);
        if (pi == 0) stage_wo(2, 4);
        else {
            if (WO_LAG > 0) __nanosleep(WO_LAG);
            stage_wo(4, 8);
        }
        if (lane == 0) TSS(17, 2 + pi);
        if (tid == 480) {
            __threadfence();
            asm volatile("red.relaxed.gpu.global.add.u32 [%0], 1;" :: "l"(&g_gcnt[32]) : "memory");
        }
        __syncwarp();
        named_bar(12 + pi, 160);
        if (lane == 0) {
            const int kb = 2 * kq + pi;
            fence_async();
            for (int pr = 0; pr < NSEG / 2; pr++) {
                const bool gon = pr < NSEG / 2 - UNGATE_G;
                wait_cnt_rlx(&g_prog[kb * 64 + pr], 8u * ep, pr >= NSEG / 2 - 2);
                if (pi == 0) asm volatile("st.volatile.shared.u32 [%0], %1;" :: "r"(sbase + SB_SEEN), "r"(pr + 1) : "memory");
                if (pr >= 30 && pi == 0) TSS(4 + pr - 30, 0);
                if (pr == 31) TS3P(26);
                if (pr == 30) TS3P(1);
#pragma unroll
                for (int j = 0; j < 4; j++) {
                    const int st = 4 * pi + j;
                    mbar_wait_long(sbase + SB_EMPTY + 8 * st, ((uint32_t)pr & 1u) ^ 1u);
                    mbar_expect(sbase + SB_FULL + 8 * st, 16384);
                    if (gon) gate(sbase + SB_TICK);
                    bulk_g2s(sbase + FS_A + st * 16384, g_ox + ((size_t)(pr * NH + 4 * kb + j)) * 8192, 16384, sbase + SB_FULL + 8 * st);
                }
            }
        }
        __syncwarp();
      } else if (warp == 13) {
        if (lane == 0) {
            const uint64_t pol = policy_evict_first();
            bool next_ok = false;
            for (int seg = 0; seg < NATT; seg++) {
                const uint32_t st = seg & 1, ph = (uint32_t)(seg >> 1) & 1u, ab = sbase + AT_0 + st * AT_ST;
                if (!next_ok) {
                    const unsigned* fp = &g_flag[(cta & (NH - 1)) * NSEG + seg];
                    unsigned it = 0, v0, v1;
                    while (true) {
                        asm volatile("ld.relaxed.gpu.global.u32 %0, [%1];" : "=r"(v0) : "l"(fp) : "memory");
                        asm volatile("ld.relaxed.gpu.global.u32 %0, [%1+4];" : "=r"(v1) : "l"(fp) : "memory");
                        read_tick(sbase + SB_TICK);
                        if ((int)(v0 - 3u * ep) >= 0 || ++it >= SPIN_LIMIT) break;
                        if (seg < NSEG - UNGATE || cta >= NH) __nanosleep(RLX_SLEEP);
                    }
                    next_ok = (int)(v1 - 3u * ep) >= 0;
                } else next_ok = false;
                if (cta < NH) {
                    TSA(seg, 0);
                    mbar_wait_long(sbase + SB_QKE + 8 * st, ph ^ 1u);
                    TSA(seg, 1);
                    mbar_expect(sbase + SB_QKF + 8 * st, 2 * 9216);
                    if (seg < NSEG - UNGATE) gate(sbase + SB_TICK, GL_A, GL_B);
                    TSA(seg, 2);
                    bulk_g2s_h(ab + 10240, &g_qkv[seg][cta][0][1024], 9216, sbase + SB_QKF + 8 * st, pol);
                    bulk_g2s_h(ab + 10240 + 9216, &g_qkv[seg][cta][1][1024], 9216, sbase + SB_QKF + 8 * st, pol);
                    mbar_wait_long(sbase + SB_VE + 8 * st, ph ^ 1u);
                    mbar_expect(sbase + SB_VF + 8 * st, 10240);
                    if (seg < NSEG - UNGATE) gate(sbase + SB_TICK, GL_A, GL_B);
                    TSA(seg, 3);
                    bulk_g2s_h(ab, &g_qkv[seg][cta][2][0], 10240, sbase + SB_VF + 8 * st, pol);
                }
            }
        }
        __syncwarp();
      } else if (warp == 14) {
        if (lane == 0) {
            int seg = cta < NH ? 0 : NATT, p = 0;
            unsigned it = 0;
            while ((seg < NATT || p < NSEG / 2 - 1) && ++it < 16 * SPIN_LIMIT) {
                if (p < NSEG / 2 - 1 && mbar_test(sbase + SB_REQ, (uint32_t)p & 1u)) {
                    if (p == 0) { wait_cnt(&g_gcnt[32], SD_NCTA * ep); asm volatile("fence.proxy.async;" ::: "memory"); }
                    mbar_expect(sbase + SB_FI, (p < NSEG / 2 - 2 ? 12288 : 2048 + 32) + 2048 + 32);
                    if (p < NSEG / 2 - UNGATE_G - 1) gate(sbase + SB_TICK);
                    if (p < NSEG / 2 - 2) bulk_g2s(sbase + FS_I, &g_fp[p & 7][cta][0][0], 12288, sbase + SB_FI);
                    else {
                        bulk_g2s(sbase + FS_I, g_y + ((p * 4 + 4 + kq) * DM + cb * 64) * 16, 2048, sbase + SB_FI);
                        bulk_g2s(sbase + FS_G + 32, g_gate + p * 64 + 64 + kq * 16, 32, sbase + SB_FI);
                    }
                    bulk_g2s(sbase + FS_Z, g_y + ((p * 4 + kq) * DM + cb * 64) * 16, 2048, sbase + SB_FI);
                    bulk_g2s(sbase + FS_G, g_gate + p * 64 + kq * 16, 32, sbase + SB_FI);
                    p++;
                } else if (seg < NATT && mbar_test(sbase + SB_OF + 8 * (seg & 1), (uint32_t)(seg >> 1) & 1u)) {
                    const uint32_t st = seg & 1, ab = sbase + AT_0 + st * AT_ST;
                    TSA(seg, 5);
                    if (seg < NSEG - UNGATE) gate(sbase + SB_TICK, GS_A, GS_B);
                    TSA(seg, 6);
                    unsigned char* dst = reinterpret_cast<unsigned char*>(g_ox) + ((size_t)((seg >> 1) * NH + cta)) * 16384 + (seg & 1) * 8192;
                    asm volatile("cp.async.bulk.global.shared::cta.bulk_group [%0], [%1], 8192;" :: "l"(dst), "r"(ab) : "memory");
                    asm volatile("cp.async.bulk.commit_group;" ::: "memory");
                    asm volatile("cp.async.bulk.wait_group.read 0;" ::: "memory");
                    mbar_arrive(sbase + SB_VE + 8 * st);
                    asm volatile("cp.async.bulk.wait_group 0;" ::: "memory");
                    asm volatile("red.relaxed.gpu.global.add.u32 [%0], 1;" :: "l"(&g_prog[(cta >> 2) * 64 + (seg >> 1)]) : "memory");
                    TSA(seg, 7);
                    seg++;
                } else if (seg < NSEG - UNGATE) __nanosleep(W14_SLEEP);
            }
        }
        __syncwarp();
      }
    } else if (warp >= 8) {
        asm volatile("setmaxnreg.dec.sync.aligned.u32 88;");
          s4d_stage_u(smem_raw + FS_A, x, tid - 256);
        const int wq = warp - 8;
        for (int seg = 0; seg < (cta < NH ? NATT : 0); seg++) {
            const uint32_t st = seg & 1, ph = (uint32_t)(seg >> 1) & 1u, ab = sbase + AT_0 + st * AT_ST;
            float sc[20];
            if (seg < NSEG - UNGATE) mbar_wait_long(sbase + SB_QKF + 8 * st, ph); else mbar_wait(sbase + SB_QKF + 8 * st, ph);
            if (tid == 256) TSA(seg, 4);
            {
                const uint64_t da = smem_desc(ab + 10240 + 1024, 128, 1024), db = smem_desc(ab + 10240, 128, 2048);
                wg_fence();
#pragma unroll
                for (int ks = 0; ks < 8; ks++) wgmma_n40_ss(sc, da + (uint64_t)((ks >> 2) * 576 + (ks & 3) * 16), db + (uint64_t)((ks >> 2) * 576 + (ks & 3) * 16), ks > 0);
                wg_commit();
                wg_wait0();
            }
            if (lane == 0) mbar_arrive(sbase + SB_QKE + 8 * st);
            uint32_t p[5], ob[16];
            const float psum = xrow_softmax(sc, p, wq, lane);
            mbar_wait(sbase + SB_VF + 8 * st, ph);
            xrow_pv(ob, p, psum, ab);
            named_bar(6, 128);
#pragma unroll
            for (int i = 0; i < 4; i++) stsm_x4(ab + wq * 2048 + i * 512 + lane * 16, ob[4 * i], ob[4 * i + 1], ob[4 * i + 2], ob[4 * i + 3]);
            fence_async();
            __syncwarp();
            if (lane == 0) mbar_arrive(sbase + SB_OF + 8 * st);
        }
    } else {
        asm volatile("setmaxnreg.inc.sync.aligned.u32 192;");
        const int wg = warp >> 2, wq = warp & 3;
        s4d_phase(smem_raw + FS_A, x, logA, Aim, Cre, Cim, logdt, dskip, Wo + (size_t)((2 * kq + wg) * 512) * DM + cb * 64);
        TS3(2);
        if (lane == 0) TSS(16, warp);
        named_bar(3, 320);
        if (tid == 0) TSS(17, 0);
        uint32_t wa[32][4];
        mbar_wait_long(sbase + SB_WO + wg * 40, 0);
        if (tid == 0) TSS(17, 1);
        {
            const uint32_t a = sbase + FS_A + wg * 65536 + ((lane >> 4) * 8 + (lane & 7)) * 128 + (((wq * 2 + ((lane >> 3) & 1)) ^ (lane & 7)) << 4);
#pragma unroll
            for (int ks = 0; ks < 32; ks++) ldsm_x4_t(wa[ks], a + ks * 2048);
        }
        named_bar(12 + wg, 160);
        TS3(3);
        if (tid == 0) TSS(17, 4);
        auto product = [&](float (&acc)[32], int pr, const int wg) {
                if (pr + wg > 0) named_bar(4 + wg, 256);
                const uint64_t db = smem_desc(sbase + FS_A + wg * 65536, 128, 2048);
                TSG(0);
#pragma unroll
                for (int j = 0; j < 4; j++) {
                    mbar_wait(sbase + SB_FULL + 8 * (4 * wg + j), (uint32_t)pr & 1u);
                    if (j == 0) TSG(1);
                    if (j == 3) TSG(2);
                    wg_fence();
#pragma unroll
                    for (int ks = 0; ks < 8; ks++) {
                        if ((j | ks) == 0) wgmma_n64_z(acc, wa[0], db);
                        else wgmma_n64(acc, wa[8 * j + ks], db + (uint64_t)(j * 1024 + ks * 16), 1);
                    }
                    wg_commit();
                    if (j == 3 && pr + wg < NSEG / 2) bar_arrive(4 + (wg ^ 1), 256);
                    if (j > 0) { wg_wait1(); if (lane == 0) mbar_arrive(sbase + SB_EMPTY + 8 * (4 * wg + j - 1)); }
                }
                wg_wait0();
                if (pr == 31) TS3W(27);
                TSG(3);
                if (lane == 0) mbar_arrive(sbase + SB_EMPTY + 8 * (4 * wg + 3));
        };
        if (wg == 1) {
            for (int pr = 0; pr < NSEG / 2; pr++) {
                uint32_t t16 = (uint32_t)(wq * 32 + lane) * 16u;
                asm volatile("" : "+r"(t16));
                float acc[32];
                product(acc, pr, 1);
                    uint32_t tag = ((uint32_t)(pr >> 3) & 1u) ^ 1u;
                    tag = __shfl_sync(0xffffffffu, tag, lane);
                    named_bar(8, 256);
                    unsigned char* dst = reinterpret_cast<unsigned char*>(&g_fp[pr & 7][4 * cb][2 * kq - 2][0]) + t16;
                    const uint32_t own = sbase + FS_O + (pr % 3) * 4096 + t16;
#pragma unroll
                    for (int q = 0; q < 8; q++) {
                        float4 p;
                        asm volatile("ld.shared.v4.f32 {%0,%1,%2,%3}, [%4];" : "=f"(p.x), "=f"(p.y), "=f"(p.z), "=f"(p.w) : "r"(sbase + FS_P + t16 + q * 2048) : "memory");
                        acc[4 * q] = __uint_as_float((__float_as_uint(acc[4 * q] + p.x) & ~1u) | tag); acc[4 * q + 1] = __uint_as_float((__float_as_uint(acc[4 * q + 1] + p.y) & ~1u) | tag);
                        acc[4 * q + 2] = __uint_as_float((__float_as_uint(acc[4 * q + 2] + p.z) & ~1u) | tag); acc[4 * q + 3] = __uint_as_float((__float_as_uint(acc[4 * q + 3] + p.w) & ~1u) | tag);
                    }
#pragma unroll
                    for (int q = 0; q < 8; q++) {
                        asm volatile("{\n.reg .pred p;\nsetp.ne.s32 p, %5, %6;\n@p st.volatile.global.v4.f32 [%0], {%1,%2,%3,%4};\n@!p st.shared.v4.f32 [%7], {%1,%2,%3,%4};\n}"
                                     :: "l"(dst + (q & 1) * 2048), "f"(acc[4 * q]), "f"(acc[4 * q + 1]), "f"(acc[4 * q + 2]), "f"(acc[4 * q + 3]), "r"(q >> 1), "r"(kq),
                                        "r"(own + (q & 1) * 2048) : "memory");
                        if (q & 1) dst += (q >> 1) == kq ? 12288 + 4096 : 12288;
                    }
                    bar_arrive(9, 256);
                    if (pr == 31) TS3W(28);
                TSG(4);
            }
        } else {
          int nsync = 0;
          int np = 1, nf = 0, pr = 0, pf = -1;
          while (true) {
            uint32_t t16 = (uint32_t)(wq * 32 + lane) * 16u;
            asm volatile("" : "+r"(t16));
            if (pr < 0) {
                if (nsync <= pf) { named_bar(9, 256); nsync++; }
                if (lane == 0 && pf < NSEG / 2 - 1) mbar_arrive(sbase + SB_REQ);
            } else {
                float acc[32];
                product(acc, pr, 0);
                if (nsync < pr) { named_bar(9, 256); nsync++; }
#pragma unroll
                for (int q = 0; q < 8; q++)
                    asm volatile("st.shared.v4.f32 [%0], {%1,%2,%3,%4};" :: "r"(sbase + FS_P + t16 + q * 2048), "f"(acc[4 * q]), "f"(acc[4 * q + 1]), "f"(acc[4 * q + 2]), "f"(acc[4 * q + 3]) : "memory");
                bar_arrive(8, 256);
                TSG(4);
            }
            uint32_t w[4] = {0u, 0u, 0u, 0u};
            const int pc = pf;
            if (pf >= 0) {
                const uint32_t tag = ((uint32_t)(pf >> 3) & 1u) ^ 1u;
                uint4 v[8];
                unsigned n = 0;
                const bool last = pf == NSEG / 2 - 1;
                const uint4* src = reinterpret_cast<const uint4*>(reinterpret_cast<const unsigned char*>(&g_fp[pf & 7][cta][0][0]) + t16);
                if (pf >= NSEG / 2 - 2) {
#pragma unroll
                    for (int r = 0; r < 6; r++) v[r] = ld_vol_u4(src + r * 128);
                    mbar_wait(sbase + SB_FI, 0u);
                } else {
                    mbar_wait(sbase + SB_FI, (uint32_t)pf & 1u);
#pragma unroll
                    for (int r = 0; r < 6; r++)
                        asm volatile("ld.shared.v4.u32 {%0,%1,%2,%3}, [%4];" : "=r"(v[r].x), "=r"(v[r].y), "=r"(v[r].z), "=r"(v[r].w) : "r"(sbase + t16 + FS_I + r * 2048) : "memory");
                }
                while (true) {
                    uint32_t any = 0u;
#pragma unroll
                    for (int r = 0; r < 6; r++) {
                        uint32_t c0_, c1_;
                        asm("lop3.b32 %0, %1, %2, %3, 0x7e;" : "=r"(c0_) : "r"(v[r].x), "r"(v[r].y), "r"(tag));
                        asm("lop3.b32 %0, %1, %2, %3, 0x7e;" : "=r"(c1_) : "r"(v[r].z), "r"(v[r].w), "r"(tag));
                        asm("lop3.b32 %0, %1, %2, %3, 0xfe;" : "=r"(any) : "r"(any), "r"(c0_), "r"(c1_));
                    }
                    if (!__any_sync(0xffffffffu, (any & 1u) != 0u) || ++n >= SPIN_LIMIT) break;
                    if (pf < NSEG / 2 - 2) __nanosleep(200);
#pragma unroll
                    for (int r = 0; r < 6; r++) v[r] = ld_vol_u4(src + r * 128);
                }
                if (pf == 31) TS3(29);
                TSG(5);
#pragma unroll
                for (int r = 6; r < 8; r++)
                    asm volatile("ld.shared.v4.u32 {%0,%1,%2,%3}, [%4];" : "=r"(v[r].x), "=r"(v[r].y), "=r"(v[r].z), "=r"(v[r].w)
                                 : "r"(sbase + t16 + FS_O + (pf % 3) * 4096 + (r - 6) * 2048) : "memory");
                uint32_t zv[4], gg[2];
                ldsm_x4_t(zv, sbase + (last ? FS_I : FS_Z) + (wq * 16 + (lane & 15)) * 32 + (lane >> 4) * 16);
#pragma unroll
                for (int k = 0; k < 2; k++) gg[k] = __byte_perm(*reinterpret_cast<const volatile unsigned short*>(smem_raw + FS_G + (last ? 32 : 0) + k * 16 + (lane >> 2) * 2), 0u, 0x1010);
#define PQS(k, f) (((__uint_as_float(v[k].f) + __uint_as_float(v[2 + k].f)) + __uint_as_float(v[4 + k].f)) + __uint_as_float(v[6 + k].f))
#pragma unroll
                for (int k = 0; k < 2; k++) {
                    w[2 * k] = bf2_add(bf2_mul(gg[k], movm(pack_bf16(PQS(k, x), PQS(k, y)))), zv[2 * k]);
                    w[2 * k + 1] = bf2_add(bf2_mul(gg[k], movm(pack_bf16(PQS(k, z), PQS(k, w)))), zv[2 * k + 1]);
                }
#undef PQS
            }
            const bool more = nf < NSEG / 2;
            if (more) {
                uint32_t r;
                asm volatile("{\n.reg .pred p, q;\n.reg .b32 v;\nld.volatile.shared.u32 v, [%1];\nsetp.gt.s32 p, v, %2;\nbar.red.or.pred q, 10, 128, p;\nselp.u32 %0, 1, 0, q;\n}"
                             : "=r"(r) : "r"(sbase + SB_SEEN), "r"(np) : "memory");
                const bool dop = np < NSEG / 2 && (__shfl_sync(0xffffffffu, r, 0) != 0u || nf == np || (np >= TM && nf + 1 >= np));
                TSG(6);
                pr = dop ? np++ : -1;
                pf = !dop || nf + (pr >= TM2 ? 1 : 2) <= pr ? nf++ : -1;
                if (dop && pf >= 0 && lane == 0) mbar_arrive(sbase + SB_REQ);
            }
            if (pc >= 0) {
                unsigned char* op = reinterpret_cast<unsigned char*>(out) + (uint32_t)((pc * 64 + kq * 16 + (lane >> 2)) * DM + cb * 64 + wq * 16 + 2 * (lane & 3)) * 2u;
#pragma unroll
                for (int k = 0; k < 4; k++) *reinterpret_cast<uint32_t*>(op + (k >> 1) * (16 * DM) + (k & 1) * 16) = w[k];
                if ((pc & 1) == 0) TS3(4 + pc / 2);
                if (pc == 31) TS3(25);
            }
            if (!more) break;
          }
        }
        if (cta == 0 && tid == 0) asm volatile("red.relaxed.gpu.global.add.u32 [%0], 1;" :: "l"(&g_epoch) : "memory");
    }
    asm volatile("griddepcontrol.wait;" ::: "memory");
}

template <class F>
__device__ __forceinline__ uint32_t poll_mem(const uint4* src, uint32_t dst, uint32_t t0, F next) {
    uint4 v[6];
    unsigned it = 0;
#pragma unroll
    for (int j = 0; j < 6; j++) v[j] = make_uint4(0u, 0u, 0u, 0u);
    while (clock32() - t0 < POLL_DELAY) {}
    FS(12, 0);
    bool more;
#pragma unroll 1
    do {
        asm volatile("{\n.reg .pred p<6>;\n"
                     "setp.ne.u32 p0, %3, 0x5000;\nsetp.ne.u32 p1, %7, 0x5000;\nsetp.ne.u32 p2, %11, 0x5000;\n"
                     "setp.ne.u32 p3, %15, 0x5000;\nsetp.ne.u32 p4, %19, 0x5000;\nsetp.ne.u32 p5, %23, 0x5000;\n"
                     "@p0 ld.volatile.global.v4.u32 {%0,%1,%2,%3}, [%24];\n@p1 ld.volatile.global.v4.u32 {%4,%5,%6,%7}, [%24+4096];\n"
                     "@p2 ld.volatile.global.v4.u32 {%8,%9,%10,%11}, [%24+8192];\n@p3 ld.volatile.global.v4.u32 {%12,%13,%14,%15}, [%24+12288];\n"
                     "@p4 ld.volatile.global.v4.u32 {%16,%17,%18,%19}, [%24+16384];\n@p5 ld.volatile.global.v4.u32 {%20,%21,%22,%23}, [%24+20480];\n}"
                     : "+r"(v[0].x), "+r"(v[0].y), "+r"(v[0].z), "+r"(v[0].w), "+r"(v[1].x), "+r"(v[1].y), "+r"(v[1].z), "+r"(v[1].w),
                       "+r"(v[2].x), "+r"(v[2].y), "+r"(v[2].z), "+r"(v[2].w), "+r"(v[3].x), "+r"(v[3].y), "+r"(v[3].z), "+r"(v[3].w),
                       "+r"(v[4].x), "+r"(v[4].y), "+r"(v[4].z), "+r"(v[4].w), "+r"(v[5].x), "+r"(v[5].y), "+r"(v[5].z), "+r"(v[5].w)
                     : "l"(src) : "memory");
        stsm_x4(dst, h2_to_bf2(v[0].x), h2_to_bf2(v[0].y), h2_to_bf2(v[0].z), h2_to_bf2(v[1].x));
        stsm_x4(dst + 512, h2_to_bf2(v[1].y), h2_to_bf2(v[1].z), h2_to_bf2(v[2].x), h2_to_bf2(v[2].y));
        const uint32_t all = ((v[0].w & v[1].w) & (v[2].w & v[3].w)) & (v[4].w & v[5].w);
        more = __any_sync(0xffffffffu, (all & 0x5000u) != 0x5000u && ++it < SPIN_LIMIT);
        stsm_x4(dst + 1024, h2_to_bf2(v[2].z), h2_to_bf2(v[3].x), h2_to_bf2(v[3].y), h2_to_bf2(v[3].z));
        asm volatile("stmatrix.sync.aligned.m8n8.x2.shared.b16 [%0], {%1,%2};" :: "r"(dst + 1536), "r"(h2_to_bf2(v[4].x)), "r"(h2_to_bf2(v[4].y)) : "memory");
        stsm_x4(dst + 1792, h2_to_bf2(v[4].z), h2_to_bf2(v[5].x), h2_to_bf2(v[5].y), h2_to_bf2(v[5].z));
        asm volatile("{\n.reg .pred p;\nsetp.eq.u32 p, %0, 0;\n@p bar.sync 1, 384;\n}" :: "r"((uint32_t)more) : "memory");
    } while (more);
    next();
    FS(13, it);
    FS(14, 0);
    uint32_t m = v[0].x, m1 = v[0].y, m2 = v[0].z;
#pragma unroll
    for (int j = 1; j < 6; j++) {
        asm volatile("max.NaN.xorsign.abs.f16x2 %0, %0, %1;" : "+r"(m) : "r"(v[j].x));
        asm volatile("max.NaN.xorsign.abs.f16x2 %0, %0, %1;" : "+r"(m1) : "r"(v[j].y));
        asm volatile("max.NaN.xorsign.abs.f16x2 %0, %0, %1;" : "+r"(m2) : "r"(v[j].z));
    }
    asm volatile("max.NaN.xorsign.abs.f16x2 %0, %0, %1;" : "+r"(m) : "r"(m1));
    asm volatile("max.NaN.xorsign.abs.f16x2 %0, %0, %1;" : "+r"(m) : "r"(m2));
    return h2_to_bf2(m) & 0x7fff7fffu;
}

template <bool V> struct Flag { static constexpr bool value = V; };
__device__ __forceinline__ void score_group(const uint32_t (&a)[2][4], const uint32_t (&kf)[2][4], uint32_t d0, uint32_t d1, uint32_t m1, uint32_t d2, uint32_t m2) {
    FS(4, a[1][0]);
    float sc[4][4];
    mma_z(sc[0], a[0], kf[0][0], kf[0][1]);
    mma_z(sc[1], a[0], kf[0][2], kf[0][3]);
    mma_z(sc[2], a[1], kf[1][0], kf[1][1]);
    mma_z(sc[3], a[1], kf[1][2], kf[1][3]);
    constexpr float EC = (float)(1.4426950408889634 * 0.08838834764831845);
    const uint32_t v0 = __float_as_uint(fmaf(sc[3][2], EC, fmaf(sc[2][0], EC, (sc[0][0] + sc[1][2]) * EC))), v1 = __float_as_uint(fmaf(sc[3][3], EC, fmaf(sc[2][1], EC, (sc[0][1] + sc[1][3]) * EC)));
    FS(5, v0);
    const uint32_t pk = pack_bf16(__uint_as_float(v0), __uint_as_float(v1));
    st_async32(d1, pk, m1);
    st_async32(d2, pk, m2);
    asm volatile("st.shared.v2.u32 [%0], {%1,%2};" :: "r"(d0), "r"(v0), "r"(v1) : "memory");
}
__device__ __forceinline__ void store_tile(int s, int h, int role, uint32_t tile, uint32_t b0, uint32_t b1) {
    asm volatile("cp.async.bulk.global.shared::cta.bulk_group.L2::cache_hint [%0], [%1], %2, %3;"
                 :: "l"(&g_qkv[s][h][role][b0]), "r"(tile + b0), "r"(b1 - b0), "l"(policy_evict_first()) : "memory");
}
__device__ __forceinline__ uint32_t w_addr(uint32_t sbase, int warp, int lane) {
    return sbase + SM_WS + (warp >> 2) * 8192 + ((lane & 7) + ((lane >> 4) & 1) * 8) * 128 + ((((warp & 3) * 2 + ((lane >> 3) & 1)) ^ (lane & 7)) << 4);
}
__device__ __forceinline__ void vx_copy(uint32_t sbase, int j, int r) {
    bulk_s2s(mapa(sbase + SM_VX + (j & 1) * 8192, r), sbase + SM_T + (j & 3) * TBUF + DH * 16, 8192, mapa(sbase + B_VX + 8 * (j & 1), r));
}
__device__ __forceinline__ float to_scale(float bound) {
    int e = 141 - (int)((__float_as_uint(bound) >> 23) & 255u);
    e = e > 100 ? 100 : e;
    return __uint_as_float((uint32_t)(127 + e) << 23);
}
__device__ __forceinline__ void norms_gather(int lane, uint32_t sbase) {
    uint2 v[3];
    uint4 w[2];
    unsigned it = 0;
#pragma unroll
    for (int i = 0; i < 3; i++) v[i] = make_uint2(0u, 0u);
    w[0] = w[1] = make_uint4(0u, 0u, 0u, 0u);
    bool more;
    do {
#pragma unroll
        for (int i = 0; i < 3; i++) if ((v[i].x & 1u) == 0u) v[i] = ld_vol_u2(&g_norm[3 * lane + i]);
#pragma unroll
        for (int i = 0; i < 2; i++) if ((w[i].x & w[i].y & w[i].z & w[i].w & 1u) == 0u) w[i] = ld_vol_u4(&g_wv[lane][i]);
        more = __any_sync(0xffffffffu, (v[0].x & v[1].x & v[2].x & w[0].x & w[0].y & w[0].z & w[0].w & w[1].x & w[1].y & w[1].z & w[1].w & 1u) == 0u);
    } while (more && ++it < SPIN_LIMIT);
    float c;
    asm("sqrt.approx.f32 %0, %1;" : "=f"(c) : "f"(__uint_as_float(max(max(v[0].x, v[1].x), v[2].x))));
    c *= __uint_as_float(max(max(max(w[0].x, w[0].y), max(w[0].z, w[0].w)), max(max(w[1].x, w[1].y), max(w[1].z, w[1].w)))) * 272.f;
#pragma unroll
    for (int o = 16; o; o >>= 1) c += __shfl_xor_sync(0xffffffffu, c, o);
    const uint32_t r = __reduce_max_sync(0xffffffffu, v[0].y);
    if (lane < 3) {
        const uint32_t rb = mapa(sbase, lane);
        c *= 1.1f * 24.f;
        st_async64(rb + SM_SC, __float_as_uint(to_scale(__uint_as_float(r) * c)), __float_as_uint(c), rb + B_W + 8);
        st_async32(rb + SM_SC + 68, r, rb + B_W + 8);
    }
    __syncwarp();
}
__device__ __forceinline__ void xmax_gather(int lane, uint32_t sb) {
    uint4 v[4];
    unsigned it = 0;
    uint32_t ok;
    do {
#pragma unroll
        for (int i = 0; i < 4; i++) v[i] = ld_vol_u4(&g_rx[lane + 32 * (i >> 1)][i & 1]);
        ok = 1u;
#pragma unroll
        for (int i = 0; i < 4; i++) ok &= (v[i].x & v[i].y) & (v[i].z & v[i].w);
    } while (__any_sync(0xffffffffu, ok == 0u) && ++it < SPIN_LIMIT);
#pragma unroll
    for (int i = 0; i < 2; i++)
        sts32(sb + SM_SC + 64 + 4 * lane + 128 * i, max(max(max(v[2 * i].x, v[2 * i].y), max(v[2 * i].z, v[2 * i].w)), max(max(v[2 * i + 1].x, v[2 * i + 1].y), max(v[2 * i + 1].z, v[2 * i + 1].w))));
}
__device__ __forceinline__ uint32_t max_abs8(uint32_t m, uint32_t a, uint32_t b, uint32_t c, uint32_t d) { return max_abs2(max_abs2(m, max_abs2(a, b)), max_abs2(c, d)); }
__device__ __forceinline__ uint32_t warp_max_abs(uint32_t m) { return __reduce_max_sync(0xffffffffu, max((m << 16) & 0x7fff0000u, m & 0x7fff0000u)); }

__device__ __forceinline__ void last_rows() {
    extern __shared__ __align__(1024) unsigned char smem_raw[];
    const uint32_t sbase = smem_u32(smem_raw);
    const int tid = threadIdx.x, warp = __shfl_sync(0xffffffffu, tid >> 5, 0), h = blockIdx.x / 3;
    {
        const int sg = warp < 8, wq = warp & 3, lane = tid & 31;
        const uint32_t qk = sbase + SM_X + XBUF + sg * (2 * 9216), ob = sbase + SM_X + 2 * XBUF + sg * 8192;
        TST(0);
        mbar_wait(sbase + B_VX + 8 * sg, 0);
        fence_async();
        TST(1);
        float sc[20];
#pragma unroll
        for (int i = 0; i < 20; i++) sc[i] = 0.f;
        {
            const uint64_t da = smem_desc(qk + 1024, 128, 1024), db = smem_desc(qk, 128, 2048);
            wg_fence();
#pragma unroll
            for (int ks = 0; ks < 8; ks++) wgmma_n40_ss(sc, da + (uint64_t)((ks >> 2) * 576 + (ks & 3) * 16), db + (uint64_t)((ks >> 2) * 576 + (ks & 3) * 16), ks > 0);
            wg_commit();
            wg_wait0();
        }
        uint32_t p[5], o[16];
        const float psum = xrow_softmax(sc, p, wq, lane);
        xrow_pv(o, p, psum, sbase + SM_T + ((NSEG - 2 + sg) & 3) * TBUF);
        {
#pragma unroll
            for (int i = 0; i < 4; i++) stsm_x4(ob + wq * 2048 + i * 512 + lane * 16, o[4 * i], o[4 * i + 1], o[4 * i + 2], o[4 * i + 3]);
        }
        fence_async();
        named_bar(11 + sg, 128);
        TST(2);
        if ((tid & 127) == 0) {
            unsigned char* dst = reinterpret_cast<unsigned char*>(g_ox) + ((size_t)((NSEG / 2 - 1) * NH + h)) * 16384 + sg * 8192;
            asm volatile("cp.async.bulk.global.shared::cta.bulk_group [%0], [%1], 8192;" :: "l"(dst), "r"(ob) : "memory");
            asm volatile("cp.async.bulk.commit_group;" ::: "memory");
            asm volatile("cp.async.bulk.wait_group 0;" ::: "memory");
            asm volatile("red.relaxed.gpu.global.add.u32 [%0], 1;" :: "l"(&g_prog[(h >> 2) * 64 + NSEG / 2 - 1]) : "memory");
        }
        TST(3);
    }
    __syncwarp();
}

__global__ void __cluster_dims__(3, 1, 1) __launch_bounds__(384, 1)
k_chain(const __grid_constant__ CUtensorMap tmq, const __grid_constant__ CUtensorMap tmk,
        const __grid_constant__ CUtensorMap tmv, const __grid_constant__ CUtensorMap tmx2, const __grid_constant__ CUtensorMap tmo,
        const __grid_constant__ CUtensorMap tmm, const bf16* __restrict__ xg) {
    extern __shared__ __align__(1024) unsigned char smem_raw[];
    const uint32_t sbase = smem_u32(smem_raw);
    const int cta = blockIdx.x, h = cta / 3, role = cta - 3 * h;
    const int tid = threadIdx.x, warp = __shfl_sync(0xffffffffu, tid >> 5, 0), lane_o = tid & 31;
    TS3C(0);
    asm volatile("griddepcontrol.launch_dependents;" ::: "memory");
    auto stage_w = [&](int i) {
        tma_2d(sbase + SM_WS + i * 16384, role == 2 ? &tmv : &tmq, h * DH + (role == 1 ? 64 : 0), i * 64, sbase + B_W + 8 * i);
        tma_2d(sbase + SM_WS + i * 16384 + 8192, role == 2 ? &tmv : &tmk, h * DH + (role == 0 ? 0 : 64), i * 64, sbase + B_W + 8 * i);
    };
    auto stage_x = [&](int i) {
        tma_2d(sbase + x01_off(i), &tmx2, i * 64, 0, sbase + B_W + 8 * i);
        tma_2d(sbase + x01_off(i) + 8192, &tmm, i * 64, 0, sbase + B_W + 8 * i);
        if (i < 3) tma_2d(sbase + x23_off(i), &tmx2, i * 64, 64, sbase + B_W + 8 * i);
    };
    if (tid == 0) {
#pragma unroll
        for (int i = 0; i < 10; i++) mbar_init(sbase + B_W + 8 * i, 1);
        fence_async();
        TSQ(10);
#pragma unroll
        for (int i = 0; i < 3; i++) tma_2d(sbase + SM_X01 + i * 16384, &tmo, role * WOC + i * 64, h * DH, sbase + B_E);
        stage_x(0); stage_w(0);
        TSQ(11);
        mbar_expect(sbase + B_E, 49152);
#pragma unroll
        for (int i = 0; i < 9; i++) mbar_expect(sbase + B_W + 8 * i, 16384 + 9216 + (i < 3 ? 8192 : 0));
    } else if (tid == 32) {
#pragma unroll
        for (int i = 0; i < 8; i++) mbar_init(sbase + SM_BAR + 8 * i, 1);
        mbar_init(sbase + B_XF, 3);
        asm volatile("fence.mbarrier_init.release.cluster;" ::: "memory");
        for (int i = 0; i < 2; i++) {
            mbar_expect(sbase + B_SB + 8 * i, role == 2 ? 1280 : 640 + 2048);
            mbar_expect(sbase + B_VX + 8 * i, role != 2 ? 8192 : 2 * 9216);
            mbar_expect(sbase + B_XT + 8 * i, 32768);
            mbar_expect(sbase + B_XT + 16 + 8 * i, i == 0 ? 40960 : 0);
        }
    }
    __syncthreads();
    TS3C(8);
    if (tid == 0) {
#pragma unroll 1
        for (int i = 1; i < 3; i++) { stage_x(i); stage_w(i); }
        TSQ(12);
    }
    __syncwarp();
    if (warp < 8) {
        uint32_t wreg[36 - NS][4];
        uint32_t v0, v1;
        {
            const int lane = lane_o;
            const uint32_t a = w_addr(sbase, warp, lane);
            const uint64_t da = smem_desc(sbase + SM_WS + (warp >> 2) * 8192, 1024, 1024) | (1ull << 62);
            float acc[36], acc1[32];
            uint32_t m = 0u;
#pragma unroll
            for (int i = 0; i < 36; i++) acc[i] = 0.f;
#pragma unroll
            for (int i = 0; i < 32; i++) acc1[i] = 0.f;
#pragma unroll 1
            for (int b = 0; b < 7; b++) {
                if (b == 0) TSQ(0);
                mbar_wait(sbase + B_W + 8 * b, 0);
                TSQ(1 + b);
                const uint64_t db = smem_desc(sbase + x01_off(b), 16, 1024) | (1ull << 62);
                wg_fence();
#pragma unroll
                for (int k = 0; k < 4; k++) wgmma_n72_ss(acc, da + (uint64_t)(b * 1024 + k * 128), db + (uint64_t)(k * 2));
                wg_commit();
                if (b < 3) {
                    const uint64_t d1 = smem_desc(sbase + x23_off(b), 16, 1024) | (1ull << 62);
                    wg_fence();
#pragma unroll
                    for (int k = 0; k < 4; k++) wgmma_n64_ss(acc1, da + (uint64_t)(b * 1024 + k * 128), d1 + (uint64_t)(k * 2));
                    wg_commit();
                }
                if (b == 2) {
                    wg_wait0();
                    bar_arrive(10, 384);
                }
                if (b == 3) {
                    if (tid == 0) mbar_expect(sbase + B_W + 8, 12);
                    __syncwarp();
                    if (role == 2) {
#pragma unroll
                        for (int ks = 0; ks < NS; ks++) {
                            uint32_t t[4];
                            ldsm_x4_t(t, a + (ks >> 2) * 16384 + (ks & 3) * 2048);
                            m = max_abs8(m, t[0], t[1], t[2], t[3]);
                        }
                    }
#pragma unroll
                    for (int ks = NS; ks < 16; ks++) ldsm_x4_t(wreg[ks - NS], a + (ks >> 2) * 16384 + (ks & 3) * 2048);
                }
                if (b == 5) {
#pragma unroll
                    for (int ks = 16; ks < 24; ks++) ldsm_x4_t(wreg[ks - NS], a + (ks >> 2) * 16384 + (ks & 3) * 2048);
                    if (role == 2) {
#pragma unroll
                        for (int ks = NS; ks < 24; ks++) m = max_abs8(m, wreg[ks - NS][0], wreg[ks - NS][1], wreg[ks - NS][2], wreg[ks - NS][3]);
                    }
                }
            }
            mbar_wait(sbase + B_W + 16, 1);
            TSQ(13);
            wg_fence();
#pragma unroll
            for (int k = 12; k < 20; k++)
                wgmma_n64_ss(acc1, da + (uint64_t)((k >> 2) * 1024 + (k & 3) * 128), (smem_desc(sbase + x23_off(k >> 2), 16, 1024) | (1ull << 62)) + (uint64_t)((k & 3) * 2));
            wg_commit();
            wg_wait0();
            named_bar(11, 384);
#pragma unroll
            for (int i = 0; i < 8; i++)
                asm volatile("st.shared.v4.f32 [%0], {%1,%2,%3,%4};" :: "r"(sbase + SM_X + 5 * 8192 + i * 4096 + tid * 16),
                             "f"(acc1[4 * i]), "f"(acc1[4 * i + 1]), "f"(acc1[4 * i + 2]), "f"(acc1[4 * i + 3]) : "memory");
#pragma unroll
            for (int b = 7; b < 9; b++) {
#pragma unroll
                for (int ks = 4 * b - 4; ks < 4 * b; ks++) ldsm_x4_t(wreg[ks - NS], a + (ks >> 2) * 16384 + (ks & 3) * 2048);
                if (role == 2) {
#pragma unroll
                    for (int ks = 4 * b - 4; ks < 4 * b; ks++) m = max_abs8(m, wreg[ks - NS][0], wreg[ks - NS][1], wreg[ks - NS][2], wreg[ks - NS][3]);
                }
                const uint64_t db = smem_desc(sbase + x01_off(b), 16, 1024) | (1ull << 62);
                mbar_wait(sbase + B_W + 8 * b, 0);
                TSQ(1 + b);
                if (b == 8) TS3C(2);
                wg_fence();
#pragma unroll
                for (int k = 0; k < 4; k++) wgmma_n72_ss(acc, da + (uint64_t)(b * 1024 + k * 128), db + (uint64_t)(k * 2));
                wg_commit();
            }
#pragma unroll
            for (int ks = 32; ks < KPRE; ks++) ldsm_x4_t(wreg[ks - NS], a + (ks >> 2) * 16384 + (ks & 3) * 2048);
            if (role == 2) {
#pragma unroll
                for (int ks = KPRE; ks < 36; ks++) {
                    uint32_t t[4];
                    ldsm_x4_t(t, a + (ks >> 2) * 16384 + (ks & 3) * 2048);
                    m = max_abs8(m, t[0], t[1], t[2], t[3]);
                }
#pragma unroll
                for (int ks = 32; ks < KPRE; ks++) m = max_abs8(m, wreg[ks - NS][0], wreg[ks - NS][1], wreg[ks - NS][2], wreg[ks - NS][3]);
                m = warp_max_abs(m);
                if (lane == 0) asm volatile("st.volatile.global.u32 [%0], %1;" :: "l"(reinterpret_cast<uint32_t*>(&g_wv[h][0]) + warp), "r"(m | 1u) : "memory");
                __syncwarp();
            }
            wg_wait0();
            named_bar(9, 256);
            const uint32_t off = sbase + SM_T + (DH + warp * 16 + (lane & 15)) * 16 + (lane >> 4) * (DH * 16);
#pragma unroll
            for (int i = 0; i < 4; i++)
                stsm_x4(off + (i >> 1) * TBUF + (i & 1) * (2 * DH * 16), pack_bf16(acc[8 * i], acc[8 * i + 1]), pack_bf16(acc[8 * i + 2], acc[8 * i + 3]),
                        pack_bf16(acc[8 * i + 4], acc[8 * i + 5]), pack_bf16(acc[8 * i + 6], acc[8 * i + 7]));
            v0 = pack_bf16(acc[32], acc[33]);
            v1 = pack_bf16(acc[34], acc[35]);
#pragma unroll
            for (int ks = KPRE; ks < 36; ks++) ldsm_x4_t(wreg[ks - NS], a + (ks >> 2) * 16384 + (ks & 3) * 2048);
            if (role == 2) fence_async();
            bar_arrive(8, 384);
            named_bar(7, 256);
            asm volatile("barrier.cluster.arrive.relaxed.aligned;" ::: "memory");
        }
        TS3C(3);
        uint32_t ws[NS][4];
#pragma unroll
        for (int ks = NS - NP; ks < NS; ks++) ldsm_x4_t(ws[ks], w_addr(sbase, warp, lane_o) + (ks >> 2) * 16384 + (ks & 3) * 2048);
        asm volatile("barrier.cluster.wait.aligned;" ::: "memory");
        if (lane_o == 0 && role != 2 && warp < 2) tma_2d_mc(sbase + SM_X + (2 * role + warp) * 8192, &tmx2, (2 * role + warp + 5) * 64, 64, sbase + B_XT + 8);
        __syncwarp();
        TS3C(4);
        auto main_loop = [&](auto is_c) {
            constexpr bool C = decltype(is_c)::value;
            const uint32_t l16 = __shfl_sync(0xffffffffu, sbase + lane_o * 16, lane_o);
            const uint32_t ka = __shfl_sync(0xffffffffu, sbase + SM_T + (64 + (lane_o & 7) + ((lane_o >> 3) & 1) * 16 + (lane_o >> 4) * 8) * 16, lane_o);
            const uint32_t wa = __shfl_sync(0xffffffffu, w_addr(sbase, warp, lane_o), lane_o);
            auto post = [&](bool act, int s, uint32_t to, uint32_t ta, int scw, uint32_t v0, uint32_t v1) {
                int lane = lane_o;
                asm volatile("" : "+r"(lane));
                asm volatile("stmatrix.sync.aligned.m8n8.x2.shared.b16 [%0], {%1,%2};" :: "r"(l16 + ta), "r"(v0), "r"(v1) : "memory");
                if (C) {
                    if (act || s + 1 < NSEG) {
                        const uint32_t fo = (uint32_t)(warp * 256 + lane * 8);
                        const uint32_t rb0 = mapa(sbase, 0), rb1 = mapa(sbase, 1);
                        st_async64(rb0 + SM_VM + fo, v0, v1, rb0 + B_SB + 8 * (s & 1));
                        st_async64(rb1 + SM_VM + fo, v0, v1, rb1 + B_SB + 8 * (s & 1));
                        asm volatile("st.shared.v2.u32 [%0], {%1,%2};" :: "r"(sbase + SM_VM + fo), "r"(v0), "r"(v1) : "memory");
                        bar_arrive(2, 384);
                    }
                } else if (act) bar_arrive(2, 384);
                else {
                    named_bar(2, 384);
                    if (scw == 0) {
                        uint32_t kf[2][4], qf[2][4];
#pragma unroll
                        for (int k2 = 0; k2 < 2; k2++) { ldsm_x4_t(kf[k2], ka + to + k2 * 512); ldsm_x4_t(qf[k2], l16 + SM_T + to + k2 * 512); }
                        const uint32_t d0 = sbase + SM_S + lane * 8, bo = sbase + B_SB + 8 * (s & 1);
                        const uint32_t d1 = mapa(sbase + SM_S + 1280, role ^ 1) + lane * 4, m1 = mapa(bo, role ^ 1), d2 = mapa(sbase + SM_S + role * 1280, 2) + lane * 4, m2 = mapa(bo, 2);
                        score_group(qf, kf, d0, d1, m1, d2, m2);
                        bar_arrive(6, 160);
                        bar_arrive(5, 384);
                    }
                    if (scw == 8) {
                        const uint32_t dk = mapa(sbase + SM_X + XBUF + (2 + role) * 9216 + (warp - 4) * 256 + lane * 4, 2), mb = mapa(sbase + B_VX + 8, 2);
                        st_async32(dk, v0, mb);
                        st_async32(dk + 128, v1, mb);
                    }
                }
                FS(11, 0);
            };
            post(false, 0, 0, SM_T + warp * 256, warp ^ 7, v0, v1);
            if (tid == 128 && cta < NSEG) {
                fence_async();
                mbar_expect(sbase + B_E, XBUF);
                bulk_g2s(sbase + SM_X + 9 * 8192, xg + (size_t)cta * SEG * DM, 32768, sbase + B_E);
                bulk_g2s(sbase + SM_WS + 32768 + 4096, xg + (size_t)cta * SEG * DM + 16384, 4096, sbase + B_E);
            }
            __syncwarp();
            if (C) {
                named_bar(7, 256);
                if (warp == 1) norms_gather(lane_o, sbase);
            }
            auto chores = [&](int s, bool idle) {
                int lane = lane_o;
                asm volatile("" : "+r"(lane));
                const int hw = (s & 1) ? warp : warp - 4;
                const uint32_t tb = sbase + SM_T + (s & 3) * TBUF;
                if (idle) { if (hw != 2) named_bar(4, 384); else bar_arrive(4, 384); }
                if (hw == 2) {
                    if (lane == 0) {
                        {
                            if (C || !idle) fence_async();
                            if (C) {
                                store_tile(s + 1, h, 2, sbase + SM_T + ((s + 1) & 3) * TBUF, 2048, 10240);
                                store_tile(s, h, 2, tb, 0, idle ? 2048 : 10240);
                            } else store_tile(s, h, role, tb, 1024, 10240);
                            asm volatile("cp.async.bulk.commit_group;" ::: "memory");
                        }
                        {
                            asm volatile("cp.async.bulk.wait_group 0;" ::: "memory");
                            if (C) {
                                asm volatile("cp.async.bulk.shared::cluster.global.mbarrier::complete_tx::bytes.multicast::cluster [%0], [%1], 8192, [%2], %3;"
                                             :: "r"(sbase + SM_VX + ((s + 1) & 1) * 8192), "l"(&g_qkv[s + 1][h][2][2048]), "r"(sbase + B_VX + 8 * ((s + 1) & 1)), "h"((unsigned short)3) : "memory");
                            }
                            asm volatile("red.relaxed.gpu.global.add.u32 [%0], 1;" :: "l"(&g_flag[h * NSEG + s]) : "memory");
                        }
                    }
                    __syncwarp();
                    if (!C && (s & 1) && s + 4 < NSEG) bar_arrive(13, 160);
                }
                __syncwarp();
            };
            auto put_tiles = [&](const float (&acc)[32], uint32_t off) {
#pragma unroll
                for (int i = 0; i < 4; i++)
                    stsm_x4(off + (i >> 1) * TBUF + (i & 1) * (2 * DH * 16), pack_bf16(acc[8 * i], acc[8 * i + 1]), pack_bf16(acc[8 * i + 2], acc[8 * i + 3]),
                            pack_bf16(acc[8 * i + 4], acc[8 * i + 5]), pack_bf16(acc[8 * i + 6], acc[8 * i + 7]));
            };
            auto tile_off = [&](int p) {
                int lane = lane_o;
                asm volatile("" : "+r"(lane));
                return sbase + SM_T + (p & 1) * (2 * TBUF) + (DH + warp * 16 + (lane & 15)) * 16 + (lane >> 4) * (DH * 16);
            };
            {
                auto db = [&](int ks) { return (smem_desc(sbase + SM_X, 16, 1024) | (1ull << 62)) + (uint64_t)(((ks >> 2) - 5) * 512 + (ks & 3) * 2); };
                if (!C && warp != 7) bar_arrive(5, 384);
                if (warp == 5) {
                    mbar_wait(sbase + B_W + 8, 1);
                    bar_arrive(12, 160);
                }
                chores(0, false);
                float acc[32];
#pragma unroll
                for (int i = 0; i < 8; i++)
                    asm volatile("ld.shared.v4.f32 {%0,%1,%2,%3}, [%4];" : "=f"(acc[4 * i]), "=f"(acc[4 * i + 1]), "=f"(acc[4 * i + 2]), "=f"(acc[4 * i + 3])
                                 : "r"(l16 + warp * 512 + SM_X + 5 * 8192 + i * 4096) : "memory");
                mbar_wait(sbase + B_XT + 8, 0);
                FS(8, 0);
                named_bar(4, 384);
                wg_fence();
#pragma unroll
                for (int ks = 35; ks >= 20; ks--) wgmma_n64(acc, wreg[ks - NS], db(ks), 1);
                wg_commit();
                if (cta < NSEG) {
                    uint32_t m = 0u;
                    mbar_wait(sbase + B_E, 1);
#pragma unroll
                    for (int j = 0; j < 9; j++) {
                        const uint4 xv = lds128(l16 + warp * 512 + (j < 8 ? SM_X + 9 * 8192 + j * 4096 : SM_WS + 32768 + 4096));
                        m = max_abs8(m, xv.x, xv.y, xv.z, xv.w);
                    }
                    m = warp_max_abs(m);
                    if (lane_o == 0) asm volatile("st.volatile.global.u32 [%0], %1;" :: "l"(reinterpret_cast<uint32_t*>(&g_rx[cta][0]) + warp), "r"(m | 1u) : "memory");
                    __syncwarp();
                }
                FS(3, 0);
                wg_wait0();
                put_tiles(acc, tile_off(1));
                FS(7, __float_as_uint(acc[0]));
            }
            auto mem_proj = [&](uint32_t& u0, uint32_t& u1, bool xf) {
#pragma unroll
                for (int ks = 0; ks < NS - NP; ks++) ldsm_x4_t(ws[ks], wa + (ks >> 2) * 16384 + (ks & 3) * 2048);
                if (xf) {
                    named_bar(15, 160);
                    if (lane_o < 2) asm volatile("mbarrier.arrive.relaxed.cluster.shared::cluster.b64 _, [%0];" :: "r"(mapa(sbase + B_XF, lane_o)) : "memory");
                    __syncwarp();
                }
                FS(0, ws[0][0]);
                named_bar(1, 384);
                float acc[2][4], minv;
                uint32_t b[3][4];
#pragma unroll
                for (int kk = 0; kk < 3; kk++) ldsm_x4_t(b[kk], l16 + SM_M + kk * 512);
                FS(1, b[0][0]);
#pragma unroll
                for (int kk = 0; kk < 18; kk++) {
#pragma unroll
                    for (int i = 0; i < 2; i++) {
                        const int ks = 2 * kk + i;
                        if (ks < 2) mma_z(acc[i], ws[ks], b[kk % 3][2 * i], b[kk % 3][2 * i + 1]);
                        else if (ks < NS) mma_bf16(acc[i], ws[ks < NS ? ks : 0], b[kk % 3][2 * i], b[kk % 3][2 * i + 1]);
                        else mma_bf16(acc[i], wreg[ks >= NS ? ks - NS : 0], b[kk % 3][2 * i], b[kk % 3][2 * i + 1]);
                    }
                    if (kk + 3 < 18) ldsm_x4_t(b[kk % 3], l16 + SM_M + (kk + 3) * 512);
                    if (kk + 3 == 17) asm volatile("ld.shared.f32 %0, [%1];" : "=f"(minv) : "r"(sbase + SM_SC + 8) : "memory");
                }
                u0 = pack_bf16(fmaf(acc[1][0], minv, acc[0][0] * minv), fmaf(acc[1][1], minv, acc[0][1] * minv));
                u1 = pack_bf16(fmaf(acc[1][2], minv, acc[0][2] * minv), fmaf(acc[1][3], minv, acc[0][3] * minv));
                FS(2, u0);
            };
            int s = 0, rc = 9;
            bool act = warp >= 4;
            uint32_t to = TBUF, ta = SM_T + warp * 256 + TBUF;
            auto next_slot = [&]() {
                const uint32_t d = (s & 3) == 3 ? -3 * TBUF : TBUF;
                to += d; ta += d;
                asm volatile("" : "+r"(to), "+r"(ta));
            };
#pragma unroll 1
            for (;;) {
                uint32_t u0, u1;
                if (act) {
                    mem_proj(u0, u1, warp == 4 && s > 0);
                    s++;
                    post(true, s, to, ta, 1, u0, u1);
                    const int p = (s + 3) >> 1;
                    const uint32_t dlo = (uint32_t)smem_desc(sbase + SM_X, 16, 1024) + rc * 512;
                    const uint64_t da = smem_desc(sbase + SM_WS + (warp >> 2) * 8192, 1024, 1024) | (1ull << 62);
                    auto db = [&](int ks) {
                        const int j = ((ks >> 2) + 4) % 9;
                        return ((uint64_t)0x40000040u << 32) | (uint64_t)(dlo + (uint32_t)((j - (rc + j >= 13 ? 13 : 0)) * 512 + (ks & 3) * 2));
                    };
                    const uint32_t xph = (uint32_t)((p - 1) >> 1) & 1u;
                    float acc[32];
                    mbar_wait(sbase + B_XT + 8 * (p & 1), xph);
                    if (C) named_bar(7, 256); else named_bar(5, 384);
                    constexpr int N1 = C ? NC1C : NC1;
                    wg_fence();
#pragma unroll
                    for (int ks = 35; ks > 35 - N1; ks--) { if (ks == 35) wgmma_n64_z(acc, wreg[ks - NS], db(ks)); else wgmma_n64(acc, wreg[ks - NS], db(ks), 1); }
                    wg_commit();
                    wg_wait0();
                    FS(9, __float_as_uint(acc[0]));
                    next_slot();
                    FS(8, 0);
                    asm volatile("{\n.reg .pred p;\nsetp.ge.s32 p, %0, 0;\n@p bar.sync 4, 384;\n}" :: "r"(s) : "memory");
                    FS(3, 0);
                    wg_fence();
#pragma unroll
                    for (int ks = 35 - N1; ks >= 20; ks--) wgmma_n64(acc, wreg[ks - NS], db(ks), 1);
                    wg_commit();
                    mbar_wait(sbase + B_XT + 16 + 8 * (p & 1), xph);
                    wg_fence();
#pragma unroll
                    for (int ks = 0; ks < NS; ks++) {
                        wgmma_n64_ss(acc, da + (uint64_t)((ks >> 2) * 1024 + (ks & 3) * 128), db(ks));
                        if (ks == 3) wg_commit();
                    }
                    {
                        wg_commit();
                        wg_wait1();
                        asm volatile("{\n.reg .pred p;\nsetp.lt.s32 p, %0, %1;\n@p bar.arrive 15, 160;\n}" :: "r"(s + (warp >> 2) * NSEG), "n"(NSEG - 5) : "memory");
                    }
#pragma unroll
                    for (int ks = NS; ks < 20; ks++) wgmma_n64(acc, wreg[ks - NS], db(ks), 1);
                    wg_commit();
                    if (!C && warp >= 4) named_bar(13, 160);
                    uint32_t off = tile_off(p);
                    rc = rc >= 4 ? rc - 4 : rc + 9;
                    asm volatile("" : "+r"(off), "+r"(rc));
                    wg_wait0();
                    put_tiles(acc, off);
                    FS(7, __float_as_uint(acc[0]));
                }
                int scw = s + 2 < NSEG ? warp ^ ((s & 1) ? 7 : 3) : (warp & 4) + 4;
                asm volatile("" : "+r"(scw));
                mem_proj(u0, u1, false);
                s++;
                post(false, s, to, ta, scw, u0, u1);
                if (s + 1 == NSEG) break;
                if (s + 2 < NSEG) {
                    if (!C && (warp & 3) == 2) fence_async();
                    if (C) named_bar(7, 256); else if (scw != 0) named_bar(5, 384);
                    chores(s, true);
                } else {
                    const uint32_t t0 = clock32();
                    const uint32_t dq = mapa(sbase + SM_X + XBUF + role * 9216, 2), mb = mapa(sbase + B_VX, 2);
                    if (!C) {
                        if (scw != 0) named_bar(5, 384);
                        if (tid == 64) { fence_async(); while (clock32() - t0 < TL_DELAY) {} bulk_s2s(dq, sbase + SM_T + 2 * TBUF + 1024, 9216, mb); }
                        __syncwarp();
                    }
                    named_bar(4, 384);
                    if (!C && tid == 64) { const uint32_t t1 = clock32(); while (clock32() - t1 < VX_DELAY) {} bulk_s2s(dq + 2 * 9216 + 1024, sbase + SM_T + 3 * TBUF + 2048, 8192, mb + 8); }
                    __syncwarp();
                }
                next_slot();
                act = s + 4 < NSEG;
            }
            if (C) named_bar(7, 256);
        };
        if (role == 2) main_loop(Flag<true>()); else main_loop(Flag<false>());
    } else {
        uint32_t wo[3][8][4];
        uint32_t mx2 = 0u;
        {
            const int pt = tid - 256, lane = lane_o, wq = warp - 8, g = lane >> 2, tq = lane & 3;
            TSQ(7);
            mbar_wait(sbase + B_E, 0);
            TSQ(8);
#pragma unroll
            for (int t = 0; t < 3; t++) {
                const int T = 3 * wq + t;
                const uint32_t a = sbase + SM_X01 + (T >> 2) * 16384 + ((lane >> 4) * 8 + (lane & 7)) * 128 + ((((T & 3) * 2 + ((lane >> 3) & 1)) ^ (lane & 7)) << 4);
#pragma unroll
                for (int kk = 0; kk < 8; kk++) ldsm_x4_t(wo[t][kk], a + ((2 * wq + kk) & 7) * 2048);
            }
            named_bar(3, 128);
            if (pt == 64) {
                fence_async();
#pragma unroll 1
                for (int i = 3; i < 9; i++) { stage_x(i); if (i < 7) stage_w(i); }
            }
            if (pt >= 96 && pt < 120) {
                *reinterpret_cast<uint4*>(g_acc + cta * 1024 + (pt - 96) * 16) = make_uint4(0u, 0u, 0u, 0u);
                __threadfence();
            }
            __syncwarp();
            TSQ(9);
            float c0 = 0.f;
#pragma unroll
            for (int t = 0; t < 3; t++) {
                float n[4][4];
#pragma unroll
                for (int i = 0; i < 4; i++) { n[i][0] = n[i][1] = n[i][2] = n[i][3] = 0.f; }
#pragma unroll
                for (int kk = 0; kk < 8; kk++)
#pragma unroll
                    for (int i = 0; i < 4; i++) mma_k8(n[i], wo[t][kk][i & 2], wo[t][kk][(i & 2) + 1], wo[t][kk][i]);
                if ((g >> 1) == tq) c0 = fmaxf(c0, (g & 1) ? fmaxf(n[0][1] + n[2][1], n[1][3] + n[3][3]) : fmaxf(n[0][0] + n[2][0], n[1][2] + n[3][2]));
            }
            c0 = __uint_as_float(__reduce_max_sync(0xffffffffu, __float_as_uint(c0)));
            uint32_t m = 0u;
            const int xb = role == 0 ? h % 9 : 9;
            auto x_max = [&]() {
                mbar_wait(sbase + B_W + 8 * xb, 0);
#pragma unroll
                for (int j = 0; j < 5; j++) {
                    uint4 xv;
                    asm volatile("ld.shared.v4.u32 {%0,%1,%2,%3}, [%4];" : "=r"(xv.x), "=r"(xv.y), "=r"(xv.z), "=r"(xv.w)
                                 : "r"(sbase + x01_off(xb) + (j < 4 ? pt + 128 * j : 512 + (pt & 63)) * 16) : "memory");
                    m = max_abs8(m, xv.x, xv.y, xv.z, xv.w);
                }
            };
            if (xb < 3) x_max();
            named_bar(10, 384);
            TSQ(10);
            if (pt == 64) {
                fence_async();
                mbar_expect(sbase + B_W + 16, 16384);
#pragma unroll
                for (int i = 3; i < 5; i++) tma_2d(sbase + x23_off(i), &tmx2, i * 64, 64, sbase + B_W + 16);
#pragma unroll 1
                for (int i = 7; i < 9; i++) stage_w(i);
            }
            __syncwarp();
            if (xb >= 3 && xb < 7) x_max();
            bar_arrive(11, 384);
            if (xb == 7 || xb == 8) x_max();
            asm volatile("barrier.cluster.arrive.relaxed.aligned;" ::: "memory");
            m = warp_max_abs(m);
            if (lane == 0) { sts32(sbase + SM_SC + 320 + 4 * wq, __float_as_uint(c0)); sts32(sbase + SM_SC + 336 + 4 * wq, m); }
            TSQ(1);
            named_bar(3, 128);
            if (pt == 0) {
                const uint4 a = lds128(sbase + SM_SC + 320), b = lds128(sbase + SM_SC + 336);
                st_vol_u2(&g_norm[cta], make_uint2(max(max(a.x, a.y), max(a.z, a.w)) | 1u, max(max(b.x, b.y), max(b.z, b.w)) | 1u));
            }
            __syncwarp();
            named_bar(8, 384);
            TSQ(2);
            asm volatile("barrier.cluster.wait.aligned;" ::: "memory");
            if (role == 2 && lane == 0 && wq < 2) vx_copy(sbase, 0, wq);
            __syncwarp();
        }
        const int wq = warp - 8;
        auto helper_loop = [&](auto is_c) {
        const bool C = is_c.value;
        const uint32_t sb = sbase;
        const uint32_t l8_o = __shfl_sync(0xffffffffu, sb + lane_o * 8, lane_o), l16_o = __shfl_sync(0xffffffffu, sb + lane_o * 16, lane_o);
        unsigned char* dst = g_acc + (role * 32 + wq * 8 + (lane_o >> 3)) * 1024 + (lane_o & 7) * 16;
        auto load_kf = [&](uint32_t (&kf)[2][4], int slot) {
            int lane = lane_o;
            asm volatile("" : "+r"(lane));
            const uint32_t ka = sb + SM_T + slot * TBUF + ((wq + 1) * DH + 64 + (lane & 7) + ((lane >> 3) & 1) * 16 + (lane >> 4) * 8) * 16;
#pragma unroll
            for (int k2 = 0; k2 < 2; k2++) ldsm_x4_t(kf[k2], ka + k2 * 512);
        };
        float minv = 1.f;
        uint32_t kf[2][4];
        if (!C) load_kf(kf, 0);
        int b3 = 0;
        int rx = 9;
        for (int s = 0; s + 1 < NSEG; s++) {
            const int n3 = b3 == 2 ? 0 : b3 + 1;
            uint32_t l8 = l8_o, l16 = l16_o;
            asm volatile("" : "+r"(l8), "+r"(l16));
            const uint32_t l4 = sb + ((l8 - sb) >> 1);
            {
                int lane = lane_o;
                asm volatile("" : "+r"(lane));
                if (C) {
                    if (lane == 0) {
                        if (wq == 3 && h == 0) {
                            const uint32_t t = gtime32();
                            st_vol_u2(&g_tick, make_uint2(t, lds32(sb + SM_SC + 12)));
                            sts32(sb + SM_SC + 12, t);
                        }
                    }
                    __syncwarp();
                    if (wq == 2 && s > 1 && lane < 24) {
                        *reinterpret_cast<uint4*>(g_acc + n3 * 128 + (3 * h + (lane >> 3)) * 1024 + (lane & 7) * 16) = make_uint4(0u, 0u, 0u, 0u);
                    }
                    if (wq == 1 && s == 3 && lane < 3) {
                        const int c = 3 * h + lane;
                        st_vol_u2(&g_norm[c], make_uint2(0u, 0u));
                        uint4* z = c < NSEG ? g_rx[c] : g_wv[c - NSEG];
                        st_vol_u4(z, make_uint4(0u, 0u, 0u, 0u)); st_vol_u4(z + 1, make_uint4(0u, 0u, 0u, 0u));
                    }
                    __syncwarp();
                }
                const uint32_t mw = __reduce_max_sync(0xffffffffu, max(mx2 << 16, mx2 & 0xffff0000u));
                if (lane == 0) sts32(sb + SM_SC + 16 + 4 * wq, mw);
            }
            const uint32_t to = SM_T + (s & 3) * TBUF;
            const uint32_t ph = (uint32_t)(s >> 1) & 1u;
            if (!C) {
                const uint32_t bo = sb + B_SB + 8 * (s & 1);
                uint32_t d0 = l8 + SM_S + (wq + 1) * 256, qa = l16 + to;
                const uint32_t dr = l4 + SM_S + (wq + 1) * 256;
                const uint32_t d1 = mapa(dr + 1280, role ^ 1), m1 = mapa(bo, role ^ 1), d2 = mapa(dr + role * 1280, 2), m2 = mapa(bo, 2);
                asm volatile("" : "+r"(d0), "+r"(qa));
                mbar_wait(sb + (s > 0 ? B_VX + 8 * (s & 1) : B_W), ph);
                FS(1, 0);
                named_bar(2, 384);
                uint32_t qf[2][4];
#pragma unroll
                for (int k2 = 0; k2 < 2; k2++) ldsm_x4_t(qf[k2], qa + k2 * 512);
                score_group(qf, kf, d0, d1, m1, d2, m2);
                bar_arrive(5, 384);
            } else named_bar(2, 384);
            if (!C && s == 0) {
                TSQ(3);
                mbar_wait(sb + B_VX, 0);
                TSQ(4);
            }
            float4 m4;
            asm volatile("ld.shared.v4.f32 {%0,%1,%2,%3}, [%4];" : "=f"(m4.x), "=f"(m4.y), "=f"(m4.z), "=f"(m4.w) : "r"(sb + SM_SC + 16) : "memory");
            const float c24 = __uint_as_float(lds32(sb + SM_SC + 4)), xb = __uint_as_float(lds32(sb + SM_SC + 64 + 4 * s));
            uint32_t vf[2][2][4], vm[2][2];
            uint32_t va = l16 + ((l16 >> 8) & 1) * 1792 + wq * 512 + (C ? to + DH * 16 : SM_VX + (s & 1) * 8192);
            auto load_vf = [&]() {
#pragma unroll
                for (int i = 0; i < 4; i++) ldsm_x4(vf[i & 1][i >> 1], va + (i & 1) * 256 + (i >> 1) * 4096);
            };
            load_vf();
            float scale = to_scale(fmaxf(fmaxf(fmaxf(m4.x, m4.y), fmaxf(m4.z, m4.w)) * minv, xb) * c24);
            uint32_t oa = l16 + wq * 512;
            asm volatile("" : "+f"(scale), "+r"(oa), "+r"(va));
            FS(7, __float_as_uint(scale));
            if (!C) named_bar(6, 160);
            if (C) mbar_wait(sb + B_SB + 8 * (s & 1), ph);
            float sv[5][2];
#pragma unroll
            for (int j = 0; j < 5; j++) {
                if (C) { const uint32_t w = lds32(l4 + SM_S + j * 256); sv[j][0] = __uint_as_float(w << 16); sv[j][1] = __uint_as_float(w & 0xffff0000u); }
                else lds64f(sv[j][0], sv[j][1], l8 + SM_S + j * 256);
            }
            if (!C) mbar_wait(sb + B_SB + 8 * (s & 1), ph);
            FS(6, 0);
            uint32_t p[5];
            {
                float sr[5][2];
#pragma unroll
                for (int j = 0; j < 5; j++) {
                    const uint32_t w = lds32(l4 + SM_S + 1280 + j * 256);
                    sr[j][0] = __uint_as_float(w << 16); sr[j][1] = __uint_as_float(w & 0xffff0000u);
                }
                lds64(vm[0][0], vm[0][1], l8 + SM_VM + wq * 512);
                lds64(vm[1][0], vm[1][1], l8 + SM_VM + wq * 512 + 256);
#pragma unroll
                for (int j = 0; j < 5; j++) {
                    sv[j][0] += sr[j][0];
                    sv[j][1] += sr[j][1];
                }
                float mx = fmaxf(fmaxf(fmaxf(sv[0][0], sv[0][1]), fmaxf(sv[1][0], sv[1][1])), fmaxf(fmaxf(sv[2][0], sv[2][1]), fmaxf(sv[3][0], sv[3][1])));
                mx = fmaxf(mx, fmaxf(sv[4][0], sv[4][1]));
                {
                    const float m1 = __shfl_xor_sync(0xffffffffu, mx, 1), m2 = __shfl_xor_sync(0xffffffffu, mx, 2), m3 = __shfl_xor_sync(0xffffffffu, mx, 3);
                    mx = fmaxf(fmaxf(mx, m1), fmaxf(m2, m3));
                }
#pragma unroll
                for (int jj = 0; jj < 5; jj++) {
                    const int j = (jj + 1) % 5;
                    asm("ex2.approx.ftz.f32 %0, %1;" : "=f"(sv[j][0]) : "f"(sv[j][0] - mx));
                    asm("ex2.approx.ftz.f32 %0, %1;" : "=f"(sv[j][1]) : "f"(sv[j][1] - mx));
                    p[j] = pack_bf16(sv[j][0], sv[j][1]);
                }
            }
            FS(0, p[0]);
            uint32_t b[4][4];
            const uint32_t one4[4] = {0x3f803f80u, 0x3f803f80u, 0x3f803f80u, 0x3f803f80u};
            float zs[4];
            {
                float o0[2][4], o1[2][4];
                mma_z(o0[0], vf[0][0], p[1], p[2]);
                mma_z(o0[1], vf[1][0], p[1], p[2]);
                mma_z(o1[0], vf[0][1], p[3], p[4]);
                mma_z(o1[1], vf[1][1], p[3], p[4]);
                mma_k8(o0[0], vm[0][0], vm[0][1], p[0]);
                mma_k8(o0[1], vm[1][0], vm[1][1], p[0]);
                float z2[4];
                mma_z(zs, one4, p[1], p[2]);
                mma_z(z2, one4, p[3], p[4]);
                mma_k8(zs, one4[0], one4[1], p[0]);
                zs[0] += z2[0]; zs[1] += z2[1];
                uint32_t ow[4];
#pragma unroll
                for (int m = 0; m < 2; m++) {
                    ow[2 * m] = pack_bf16(o0[m][0] + o1[m][0], o0[m][1] + o1[m][1]);
                    ow[2 * m + 1] = pack_bf16(o0[m][2] + o1[m][2], o0[m][3] + o1[m][3]);
                }
                stsm_x4(oa + SM_O, ow[0], ow[1], ow[2], ow[3]);
                FS(2, 0);
                b[0][0] = movm(ow[0]); b[0][1] = movm(ow[1]);
                __syncwarp();
                asm volatile("ldmatrix.sync.aligned.m8n8.x2.trans.shared.b16 {%0,%1}, [%2];" : "=r"(b[0][2]), "=r"(b[0][3]) : "r"(oa + SM_O + 256));
            }
            float acc[3][2][4];
            named_bar(3, 128);
#pragma unroll
            for (int i = 1; i < 4; i++) ldsm_x4_t(b[i], l16 + SM_O + ((wq + i) & 3) * 512);
#pragma unroll
            for (int c = 0; c < 2; c++)
#pragma unroll
                for (int t = 0; t < 3; t++) mma_z(acc[t][c], wo[t][c], b[0][2 * c], b[0][2 * c + 1]);
            float z0, z1;
            asm volatile("rcp.approx.ftz.f32 %0, %1;" : "=f"(z0) : "f"(zs[0]));
            asm volatile("rcp.approx.ftz.f32 %0, %1;" : "=f"(z1) : "f"(zs[1]));
            asm volatile("{\n.reg .pred p;\nsetp.eq.s32 p, %1, 0;\n@p bar.sync 12, 160;\n@p ld.shared.f32 %0, [%2];\n}" : "+f"(scale) : "r"(s), "r"(sb + SM_SC) : "memory");
            z0 *= scale; z1 *= scale;
            FS(3, b[1][0]);
#pragma unroll
            for (int i = 1; i < 4; i++)
#pragma unroll
                for (int c = 0; c < 2; c++)
#pragma unroll
                    for (int t = 0; t < 3; t++) mma_bf16(acc[t][c], wo[t][2 * i + c], b[i][2 * c], b[i][2 * c + 1]);
            {
                uint32_t w[6];
#pragma unroll
                for (int t = 0; t < 3; t++) {
                    w[2 * t] = pack_f16(fmaf(acc[t][1][0], z0, acc[t][0][0] * z0), fmaf(acc[t][1][1], z1, acc[t][0][1] * z1));
                    w[2 * t + 1] = pack_f16(fmaf(acc[t][1][2], z0, acc[t][0][2] * z0), fmaf(acc[t][1][3], z1, acc[t][0][3] * z1));
                }
                FS(8, w[5]);
                asm volatile("red.relaxed.gpu.global.add.noftz.v4.f16x2 [%0], {%1,%2,%3,%4};" :: "l"(dst), "r"(w[0]), "r"(w[1]), "r"(w[2]), "r"(0x3c00u) : "memory");
                asm volatile("red.relaxed.gpu.global.add.noftz.v4.f16x2 [%0], {%1,%2,%3,%4};" :: "l"(dst + 4096), "r"(w[3]), "r"(w[4]), "r"(w[5]), "r"(0x3c00u) : "memory");
            }
            FS(9, 0);
            if (s == 0) TSQ(5);
            bar_arrive(4, 384);
            const uint32_t t0 = clock32();
            minv = __uint_as_float(0x7f000000u - __float_as_uint(scale));
            if (lane_o == 0) {
                if (wq == 0) sts32(sb + SM_SC + 8, __float_as_uint(minv));
                if (s + 3 < NSEG) {
                    if (wq == 0) mbar_expect(sb + B_SB + 8 * (s & 1), C ? 1280 : 640 + 2048);
                    if (wq == 1 && s > 0 && s + 5 < NSEG) mbar_expect(sb + B_XT + ((s & 1) ? 0 : 16) + 4 * ((s + 1) & 2), (s & 1) ? 32768 : 40960);
                    if (wq == 3 && !C) mbar_expect(sb + B_VX + 8 * (s & 1), 8192);
                }
            }
            __syncwarp();
            if (s == 1) {
                int lane = lane_o;
                asm volatile("" : "+r"(lane));
                if (wq == 3) xmax_gather(lane, sb);
                __syncwarp();
            }
            if (!C) load_kf(kf, (s + 1) & 3);
            const uint4* src = reinterpret_cast<const uint4*>(dst + (wq * 16 - role * 32) * 1024);
            dst += n3 == 0 ? -256 : 128;
            asm volatile("" : "+l"(dst));
            const int xp = (s + 5) >> 1, kb = wq + ((s & 1) ? 2 * role : 4 + 3 * role);
            const bool xl = !C && xp < NSEG / 2 && wq < ((s & 1) ? 2 : 3 - role);
            const uint32_t xs = wq == 3 && s == 0;
            const uint32_t xd = sb + SM_X + (rx + kb >= 13 ? rx + kb - 13 : rx + kb) * 8192;
            mx2 = poll_mem(src, l16 + SM_M + wq * 2304, t0, [&]() {
                if (xs && lane_o < 2) asm volatile("mbarrier.arrive.relaxed.cluster.shared::cluster.b64 _, [%0];" :: "r"(mapa(sb + B_XF, lane_o)) : "memory");
                if (!C && (xl || s == 0) && (s & 1) == 0) mbar_wait(sb + B_XF, (uint32_t)(s >> 1) & 1u);
                if (lane_o == 0) {
                    if (xl) tma_2d_mc(xd, &tmx2, ((s & 1) ? kb + 5 : kb - 4) * 64, xp * 64, sb + B_XT + ((s & 1) ? 0 : 16) + 8 * (xp & 1));
                    if (!C && s == 0 && role == 1) tma_2d_mc(sb + SM_X + (9 + wq) * 8192, &tmx2, (wq + 5) * 64, 128, sb + B_XT);
                }
                __syncwarp();
            });
            if ((s & 1) == 0) rx = rx >= 4 ? rx - 4 : rx + 9;
            if (s == 0) TSQ(6);
            b3 = n3;
        }
        if (!C) bar_arrive(2, 384);
        };
        if (role == 2) helper_loop(Flag<true>()); else helper_loop(Flag<false>());
    }
    TS3C(1);
    if (role == 2 && warp >= 4) last_rows();
    cluster_sync_all();
}

extern "C" void kernel_launch(void* const* d_in, const int* in_sizes, int n_in, void* d_out, int out_size) {
    const bf16* x = (const bf16*)d_in[0];
    const bf16* mem0 = (const bf16*)d_in[1];
    const bf16* Wq = (const bf16*)d_in[2];
    const bf16* Wk = (const bf16*)d_in[3];
    const bf16* Wv = (const bf16*)d_in[4];
    const bf16* Wo = (const bf16*)d_in[5];
    const bf16* logA = (const bf16*)d_in[8];
    const bf16* Aim = (const bf16*)d_in[9];
    const bf16* Cre = (const bf16*)d_in[10];
    const bf16* Cim = (const bf16*)d_in[11];
    const bf16* logdt = (const bf16*)d_in[12];
    const bf16* dskip = (const bf16*)d_in[13];
    const bf16* gw = (const bf16*)d_in[14];
    bf16* out = (bf16*)d_out;
    static bool attr_done = false;
    typedef CUresult (*EncFn)(CUtensorMap*, CUtensorMapDataType, cuuint32_t, void*, const cuuint64_t*, const cuuint64_t*, const cuuint32_t*,
                              const cuuint32_t*, CUtensorMapInterleave, CUtensorMapSwizzle, CUtensorMapL2promotion, CUtensorMapFloatOOBfill);
    static EncFn enc = nullptr;
    if (!attr_done) {
        void* fn = nullptr;
        cudaDriverEntryPointQueryResult qr;
        cudaGetDriverEntryPoint("cuTensorMapEncodeTiled", &fn, cudaEnableDefault, &qr);
        enc = (EncFn)fn;
        cudaFuncSetAttribute(k_chain, cudaFuncAttributeMaxDynamicSharedMemorySize, 232448);
        cudaFuncSetAttribute(k_side, cudaFuncAttributeMaxDynamicSharedMemorySize, SIDE_SMEM);
        attr_done = true;
    }
    CUtensorMap tmw[3];
    for (int i = 0; i < 3; i++) {
        const cuuint64_t dims[2] = {(cuuint64_t)HD, (cuuint64_t)DM};
        const cuuint64_t strides[1] = {(cuuint64_t)HD * 2};
        const cuuint32_t box[2] = {64, 64};
        const cuuint32_t es[2] = {1, 1};
        enc(&tmw[i], CU_TENSOR_MAP_DATA_TYPE_BFLOAT16, 2, (void*)(i == 0 ? Wq : (i == 1 ? Wk : Wv)), dims, strides, box, es, CU_TENSOR_MAP_INTERLEAVE_NONE,
            CU_TENSOR_MAP_SWIZZLE_128B, CU_TENSOR_MAP_L2_PROMOTION_L2_256B, CU_TENSOR_MAP_FLOAT_OOB_FILL_NONE);
    }
    CUtensorMap tmo;
    {
        const cuuint64_t dims[2] = {(cuuint64_t)DM, (cuuint64_t)HD};
        const cuuint64_t strides[1] = {(cuuint64_t)DM * 2};
        const cuuint32_t box[2] = {64, 128};
        const cuuint32_t es[2] = {1, 1};
        enc(&tmo, CU_TENSOR_MAP_DATA_TYPE_BFLOAT16, 2, (void*)Wo, dims, strides, box, es, CU_TENSOR_MAP_INTERLEAVE_NONE,
            CU_TENSOR_MAP_SWIZZLE_128B, CU_TENSOR_MAP_L2_PROMOTION_L2_128B, CU_TENSOR_MAP_FLOAT_OOB_FILL_NONE);
    }
    CUtensorMap tmx2;
    {
        const cuuint64_t dims[2] = {(cuuint64_t)DM, (cuuint64_t)S_LEN};
        const cuuint64_t strides[1] = {(cuuint64_t)DM * 2};
        const cuuint32_t box[2] = {64, 64};
        const cuuint32_t es[2] = {1, 1};
        enc(&tmx2, CU_TENSOR_MAP_DATA_TYPE_BFLOAT16, 2, (void*)x, dims, strides, box, es, CU_TENSOR_MAP_INTERLEAVE_NONE,
            CU_TENSOR_MAP_SWIZZLE_128B, CU_TENSOR_MAP_L2_PROMOTION_L2_128B, CU_TENSOR_MAP_FLOAT_OOB_FILL_NONE);
    }
    CUtensorMap tmm;
    {
        const cuuint64_t dims[2] = {(cuuint64_t)DM, (cuuint64_t)MEMT};
        const cuuint64_t strides[1] = {(cuuint64_t)DM * 2};
        const cuuint32_t box[2] = {64, (cuuint32_t)MEMT};
        const cuuint32_t es[2] = {1, 1};
        enc(&tmm, CU_TENSOR_MAP_DATA_TYPE_BFLOAT16, 2, (void*)mem0, dims, strides, box, es, CU_TENSOR_MAP_INTERLEAVE_NONE,
            CU_TENSOR_MAP_SWIZZLE_128B, CU_TENSOR_MAP_L2_PROMOTION_L2_128B, CU_TENSOR_MAP_FLOAT_OOB_FILL_NONE);
    }
    k_chain<<<NCTA, 384, 232448>>>(tmw[0], tmw[1], tmw[2], tmx2, tmo, tmm, x);
    {
        cudaLaunchConfig_t cfg = {};
        cfg.gridDim = dim3(SD_NCTA); cfg.blockDim = dim3(512); cfg.dynamicSmemBytes = SIDE_SMEM; cfg.stream = cudaStreamPerThread;
        cudaLaunchAttribute at[1];
        at[0].id = cudaLaunchAttributeProgrammaticStreamSerialization;
        at[0].val.programmaticStreamSerializationAllowed = 1;
        cfg.attrs = at; cfg.numAttrs = 1;
        cudaLaunchKernelEx(&cfg, k_side, tmo, x, logA, Aim, Cre, Cim, logdt, Wo, dskip, gw, out);
    }
}
```
